```python
import torch

def _softmax(x, axis=-1):
    return torch.softmax(x, dim=axis)
def _gelu(x):
    return torch.nn.functional.gelu(x, approximate="tanh")
def _silu(x):
    return torch.nn.functional.silu(x)
def _sigmoid(x):
    return torch.sigmoid(x)
def _layernorm(x, axis=-1, eps=1e-5):
    m = x.mean(dim=axis, keepdim=True)
    v = x.var(dim=axis, keepdim=True, unbiased=False)
    return (x - m) / torch.sqrt(v + eps)
def _scatter_add(tgt, idx, src, axis=0):
    return tgt.clone().index_add_(axis, idx, src)
def _segment_sum(src, seg, n):
    out = torch.zeros((n,) + src.shape[1:], dtype=src.dtype)
    return out.index_add_(0, seg, src)
def _pad(x, pw):
    flat = tuple(v for pair in reversed(pw) for v in pair)
    return torch.nn.functional.pad(x, flat)

kernel_name = 'sequential_preLN__ssm_conv_s4__moe_arch_mod__prompt'

def setup_inputs():

    _w = (lambda a: (lambda t: t.to(torch.bfloat16) if t.is_floating_point() else t)(torch.as_tensor(a)))
    def _A_setup():
        B, L, D, N = 1, 2048, 576, 128
        A_re = -(lambda _x: torch.exp(torch.as_tensor(_x)))((lambda *s: torch.randn(*s, dtype=torch.bfloat16) * 1.6)(D, N))
        A_im = torch.pi * (lambda *s: torch.randn(*s, dtype=torch.bfloat16) * 0.2)(D, N)
        B_re = (lambda *s: torch.randn(*s, dtype=torch.bfloat16) * 0.2)(D, N)
        B_im = (lambda *s: torch.randn(*s, dtype=torch.bfloat16) * 0.2)(D, N)
        C_re = (lambda *s: torch.randn(*s, dtype=torch.bfloat16) * 0.2)(D, N)
        C_im = (lambda *s: torch.randn(*s, dtype=torch.bfloat16) * 0.2)(D, N)
        log_dt = (lambda *s: torch.randn(*s, dtype=torch.bfloat16) * 0.2)(D) * 0.5 - 4.0
        Dskip = (lambda *s: torch.randn(*s, dtype=torch.bfloat16) * 0.2)(D)
        return {
            "u": _w((lambda *s: torch.randn(*s, dtype=torch.bfloat16) * 0.05)(B, L, D)),
            "A_re": _w(A_re),
            "A_im": _w(A_im),
            "B_re": _w(B_re),
            "B_im": _w(B_im),
            "C_re": _w(C_re),
            "C_im": _w(C_im),
            "log_dt": _w(log_dt),
            "Dskip": _w(Dskip),
        }
    _A_in = _A_setup()

    def _B_setup():
        B, S, D, F, C = 1, 2048, 576, 4608, 8
        return {
            "x": _w((lambda *s: torch.randn(*s, dtype=torch.bfloat16) * 0.05)(B, S, D)),
            "w_r": _w((lambda *s: torch.randn(*s, dtype=torch.bfloat16) * 0.2)(D)),
            "w_gate": _w((lambda *s: torch.randn(*s, dtype=torch.bfloat16) * 0.2)(D, F)),
            "w_up": _w((lambda *s: torch.randn(*s, dtype=torch.bfloat16) * 0.2)(D, F)),
            "w_down": _w((lambda *s: torch.randn(*s, dtype=torch.bfloat16) * 0.2)(F, D)),
        }
    _B_in = _B_setup()

    return {
        "A_u": _A_in["u"],
        "A_A_re": _A_in["A_re"],
        "A_A_im": _A_in["A_im"],
        "A_B_re": _A_in["B_re"],
        "A_B_im": _A_in["B_im"],
        "A_C_re": _A_in["C_re"],
        "A_C_im": _A_in["C_im"],
        "A_log_dt": _A_in["log_dt"],
        "A_Dskip": _A_in["Dskip"],
        "B_x": _B_in["x"],
        "B_w_r": _B_in["w_r"],
        "B_w_gate": _B_in["w_gate"],
        "B_w_up": _B_in["w_up"],
        "B_w_down": _B_in["w_down"],
    }

def reference(A_u, A_A_re, A_A_im, A_B_re, A_B_im, A_C_re, A_C_im, A_log_dt, A_Dskip, B_x, B_w_r, B_w_gate, B_w_up, B_w_down):
    def _A_ref(u, A_re, A_im, B_re, B_im, C_re, C_im, log_dt, Dskip):
        Bsz, L, D = u.shape
        dt = torch.exp(log_dt)[:, None]
        A = A_re + 1j * A_im
        Bc = B_re + 1j * B_im
        Cc = C_re + 1j * C_im
        logdA = dt * A
        dB = dt * Bc
        l = (lambda x, dt: x.to(dt))(torch.arange(L), A_re.dtype)
        P = torch.exp(logdA[:, :, None] * l[None, None, :])
        K = torch.einsum("dn,dnl,dn->dl", Cc, P, dB).real
        L2 = 2 * L
        Kp = _pad(K, ((0, 0), (0, L)))
        up = (lambda x, *d: x.permute(*d))(u, 0, 2, 1)
        up = _pad(up, ((0, 0), (0, 0), (0, L)))
        Kf = (lambda x, axes=(-2,-1): torch.fft.rfft2(x.float(), dim=axes))(Kp[:, None, :], axes=(-2, -1))
        Uf = (lambda x, axes=(-2,-1): torch.fft.rfft2(x.float(), dim=axes))(up[:, :, None, :], axes=(-2, -1))
        Yf = Uf * Kf[None, :, :, :]
        y = (lambda x, s, axes=(-2,-1): torch.fft.irfft2(x, s=s, dim=axes).to(torch.bfloat16))(Yf, (1, L2), axes=(-2, -1))[:, :, 0, :L]
        y = (lambda x, *d: x.permute(*d))(y, 0, 2, 1) + u * Dskip[None, None, :]
        return y

    def _B_ref(x, w_r, w_gate, w_up, w_down):
        B, S, D = x.shape
        C = 8
        r = x @ w_r
        idx = torch.argsort(-r, axis=-1)[:, :C]
        idx_e = (lambda x, n, axis: torch.repeat_interleave(x, n, dim=axis))(idx.reshape(B, C, 1), D, axis=2)
        x_sel = (lambda x, i, axis: torch.take_along_dim(x, i, dim=axis))(x, idx_e, axis=1)
        g = _silu(x_sel @ w_gate)
        u = x_sel @ w_up
        y = (g * u) @ w_down
        r_sel = _sigmoid((lambda x, i, axis: torch.take_along_dim(x, i, dim=axis))(r, idx, axis=1))
        y = y * r_sel.reshape(B, C, 1)
        b_off = (torch.arange(B) * S).reshape(B, 1)
        flat_idx = (idx + b_off).reshape(B * C)
        zero = (x * 0.0).reshape(B * S, D)
        upd = _scatter_add(zero, flat_idx, y.reshape(B * C, D), axis=0)
        return x + upd.reshape(B, S, D)

    x = A_u
    h = x + _A_ref(_layernorm(x, axis=-1), A_A_re, A_A_im, A_B_re, A_B_im, A_C_re, A_C_im, A_log_dt, A_Dskip)
    h2 = h + _B_ref(_layernorm(h, axis=-1), B_w_r, B_w_gate, B_w_up, B_w_down)
    return h2
```

```cpp
#include <cuda_runtime.h>
#include <cuda.h>
#include <cuda_bf16.h>
#include <cuda_fp16.h>
#include <stdint.h>

namespace {

constexpr int NCTA = 128;
constexpr int NT = 512;
constexpr int DM = 576;
constexpr int FF = 4608;
constexpr int SPIN_MAX = 1 << 20;

__device__ uint4 g_U2[NCTA * DM * 2];
__device__ uint4 g_Y2[NCTA * DM * 2];
__device__ uint32_t g_ROW[2048 * 288];
__device__ uint4 g_P[(NCTA + 1) * 1152];
__device__ uint4 g_R[256];
__device__ uint32_t g_FLAG[NCTA];

#define TS(i)

constexpr int GU_MAT = DM * 80;
constexpr int OFF_GU = 0;
constexpr int KT_WORDS = 1104;
constexpr int L3_ARR = 256;
constexpr int KT_BYTES = KT_WORDS * 4 + 4 * L3_ARR;
constexpr int OFF_KT = OFF_GU + 2 * GU_MAT;
constexpr int UP_PAD = 28;
constexpr int UP_PLANE = (128 + UP_PAD) * 16;
constexpr int OFF_UP = OFF_KT + 5 * KT_BYTES;
constexpr int SCR_WARP = 3200;
constexpr int SCR_WG = 4 * SCR_WARP + 1408;
constexpr int OFF_SCR = OFF_UP + 5 * 2 * UP_PLANE;
constexpr int YT_PITCH = 1184;
constexpr int OFF_YT = OFF_SCR + 4 * SCR_WG;
constexpr int OFF_MISC = OFF_YT + 16 * YT_PITCH + 64;
constexpr int SMEM_BYTES = OFF_MISC + 256;
static_assert(OFF_KT % 128 == 0 && OFF_UP % 16 == 0 && OFF_SCR % 16 == 0 && OFF_YT % 16 == 0 && OFF_MISC % 16 == 0, "align");
static_assert(SMEM_BYTES <= 232448, "smem");
constexpr int MISC_MBAR = 0;
constexpr int MISC_SCALE = 16;
constexpr int MISC_WMAX = 48;
constexpr int MISC_CNT = 80;
constexpr int MISC_EXP = 96;

__device__ __forceinline__ uint32_t smem_u32(const void* p) { return (uint32_t)__cvta_generic_to_shared(p); }
__device__ __forceinline__ uint32_t lds32(uint32_t a) { uint32_t v; asm volatile("ld.shared.b32 %0, [%1];" : "=r"(v) : "r"(a) : "memory"); return v; }
__device__ __forceinline__ uint32_t lds16(uint32_t a) { uint16_t v; asm volatile("ld.shared.u16 %0, [%1];" : "=h"(v) : "r"(a) : "memory"); return v; }
__device__ __forceinline__ uint2 lds64(uint32_t a) { uint2 v; asm volatile("ld.shared.v2.b32 {%0,%1}, [%2];" : "=r"(v.x), "=r"(v.y) : "r"(a) : "memory"); return v; }
__device__ __forceinline__ uint4 lds128(uint32_t a) { uint4 v; asm volatile("ld.shared.v4.b32 {%0,%1,%2,%3}, [%4];" : "=r"(v.x), "=r"(v.y), "=r"(v.z), "=r"(v.w) : "r"(a) : "memory"); return v; }
__device__ __forceinline__ void sts16(uint32_t a, uint32_t v) { asm volatile("st.shared.u16 [%0], %1;" :: "r"(a), "h"((uint16_t)v) : "memory"); }
__device__ __forceinline__ void sts32(uint32_t a, uint32_t v) { asm volatile("st.shared.b32 [%0], %1;" :: "r"(a), "r"(v) : "memory"); }
__device__ __forceinline__ void sts64(uint32_t a, uint32_t x, uint32_t y) { asm volatile("st.shared.v2.b32 [%0], {%1,%2};" :: "r"(a), "r"(x), "r"(y) : "memory"); }
__device__ __forceinline__ void sts128(uint32_t a, uint32_t x, uint32_t y, uint32_t z, uint32_t w) { asm volatile("st.shared.v4.b32 [%0], {%1,%2,%3,%4};" :: "r"(a), "r"(x), "r"(y), "r"(z), "r"(w) : "memory"); }
__device__ __forceinline__ void ldsm4(uint32_t a, uint32_t& r0, uint32_t& r1, uint32_t& r2, uint32_t& r3) {
  asm volatile("ldmatrix.sync.aligned.m8n8.x4.shared.b16 {%0,%1,%2,%3}, [%4];" : "=r"(r0), "=r"(r1), "=r"(r2), "=r"(r3) : "r"(a) : "memory");
}
__device__ __forceinline__ void ldsm2(uint32_t a, uint32_t& r0, uint32_t& r1) {
  asm volatile("ldmatrix.sync.aligned.m8n8.x2.shared.b16 {%0,%1}, [%2];" : "=r"(r0), "=r"(r1) : "r"(a) : "memory");
}
__device__ __forceinline__ void ldsm4t(uint32_t a, uint32_t& r0, uint32_t& r1, uint32_t& r2, uint32_t& r3) {
  asm volatile("ldmatrix.sync.aligned.m8n8.x4.trans.shared.b16 {%0,%1,%2,%3}, [%4];" : "=r"(r0), "=r"(r1), "=r"(r2), "=r"(r3) : "r"(a) : "memory");
}
__device__ __forceinline__ void stsm4t(uint32_t a, uint32_t r0, uint32_t r1, uint32_t r2, uint32_t r3) {
  asm volatile("stmatrix.sync.aligned.m8n8.x4.trans.shared.b16 [%0], {%1,%2,%3,%4};" :: "r"(a), "r"(r0), "r"(r1), "r"(r2), "r"(r3) : "memory");
}
__device__ __forceinline__ uint4 ldr128(const void* p) {
  unsigned long long lo, hi;
  asm volatile("{ .reg .b128 t; ld.relaxed.gpu.global.b128 t, [%2]; mov.b128 {%0, %1}, t; }" : "=l"(lo), "=l"(hi) : "l"(p) : "memory");
  return make_uint4((uint32_t)lo, (uint32_t)(lo >> 32), (uint32_t)hi, (uint32_t)(hi >> 32));
}
__device__ __forceinline__ void str128(void* p, uint32_t x, uint32_t y, uint32_t z, uint32_t w) {
  asm volatile("{ .reg .b128 t; .reg .b64 lo, hi; mov.b64 lo, {%1,%2}; mov.b64 hi, {%3,%4}; mov.b128 t, {lo, hi}; st.relaxed.gpu.global.b128 [%0], t; }"
               :: "l"(p), "r"(x), "r"(y), "r"(z), "r"(w) : "memory");
}
__device__ __forceinline__ void str64(void* p, uint32_t x, uint32_t y) {
  asm volatile("{ .reg .b64 t; mov.b64 t, {%1,%2}; st.relaxed.gpu.global.b64 [%0], t; }" :: "l"(p), "r"(x), "r"(y) : "memory");
}
__device__ __forceinline__ uint32_t ldr32(const void* p) { uint32_t v; asm volatile("ld.relaxed.gpu.global.b32 %0, [%1];" : "=r"(v) : "l"(p) : "memory"); return v; }
__device__ __forceinline__ void str32(void* p, uint32_t v) { asm volatile("st.relaxed.gpu.global.b32 [%0], %1;" :: "l"(p), "r"(v) : "memory"); }
__device__ __forceinline__ void str16(void* p, uint32_t v) { asm volatile("st.relaxed.gpu.global.u16 [%0], %1;" :: "l"(p), "h"((uint16_t)v) : "memory"); }
__device__ __forceinline__ void fence_gpu() { asm volatile("fence.acq_rel.gpu;" ::: "memory"); }
__device__ __forceinline__ void bar_sync(int id, int n) { asm volatile("bar.sync %0, %1;" :: "r"(id), "r"(n) : "memory"); }
__device__ __forceinline__ void bar_arrive(int id, int n) { asm volatile("bar.arrive %0, %1;" :: "r"(id), "r"(n) : "memory"); }

__device__ __forceinline__ float bf_lo(uint32_t w) { return __uint_as_float(w << 16); }
__device__ __forceinline__ float bf_hi(uint32_t w) { return __uint_as_float(w & 0xFFFF0000u); }
__device__ __forceinline__ uint32_t pack_bf(float lo, float hi) { uint32_t r; asm("cvt.rn.bf16x2.f32 %0, %1, %2;" : "=r"(r) : "f"(hi), "f"(lo)); return r; }
__device__ __forceinline__ uint32_t pack_h(float lo, float hi) { uint32_t r; asm("cvt.rn.f16x2.f32 %0, %1, %2;" : "=r"(r) : "f"(hi), "f"(lo)); return r; }
__device__ __forceinline__ float bfr(float x) { return bf_lo(pack_bf(x, 0.f)); }
__device__ __forceinline__ uint32_t bf_sub2(uint32_t a, uint32_t b) { __nv_bfloat162 r = __hsub2(*(__nv_bfloat162*)&a, *(__nv_bfloat162*)&b); return *(uint32_t*)&r; }
__device__ __forceinline__ uint32_t bf_add2(uint32_t a, uint32_t b) { __nv_bfloat162 r = __hadd2(*(__nv_bfloat162*)&a, *(__nv_bfloat162*)&b); return *(uint32_t*)&r; }
__device__ __forceinline__ uint32_t bf_mul2(uint32_t a, uint32_t b) { __nv_bfloat162 r = __hmul2(*(__nv_bfloat162*)&a, *(__nv_bfloat162*)&b); return *(uint32_t*)&r; }
__device__ __forceinline__ float2 h2f(uint32_t w) { return __half22float2(*(__half2*)&w); }
__device__ __forceinline__ float ex2(float x) { float r; asm("ex2.approx.ftz.f32 %0, %1;" : "=f"(r) : "f"(x)); return r; }
__device__ __forceinline__ float warp_sum(float v) {
#pragma unroll
  for (int o = 16; o > 0; o >>= 1) v += __shfl_xor_sync(0xffffffffu, v, o);
  return v;
}
__device__ __forceinline__ uint32_t cmul_xsel(uint32_t x, uint32_t w, uint32_t wp) {
  __half2 X = *(__half2*)&x;
  __half2 r = __hfma2(__high2half2(X), *(__half2*)&wp, __hmul2(__low2half2(X), *(__half2*)&w));
  return *(uint32_t*)&r;
}

__device__ __forceinline__ void mma_f16_f32(float* d, uint32_t a0, uint32_t a1, uint32_t a2, uint32_t a3, uint32_t b0, uint32_t b1) {
  asm volatile("mma.sync.aligned.m16n8k16.row.col.f32.f16.f16.f32 {%0,%1,%2,%3}, {%4,%5,%6,%7}, {%8,%9}, {%0,%1,%2,%3};"
               : "+f"(d[0]), "+f"(d[1]), "+f"(d[2]), "+f"(d[3]) : "r"(a0), "r"(a1), "r"(a2), "r"(a3), "r"(b0), "r"(b1));
}
__device__ __forceinline__ void mma_f16_f16(uint32_t& d0, uint32_t& d1, uint32_t a0, uint32_t a1, uint32_t a2, uint32_t a3, uint32_t b0, uint32_t b1) {
  asm volatile("mma.sync.aligned.m16n8k16.row.col.f16.f16.f16.f16 {%0,%1}, {%2,%3,%4,%5}, {%6,%7}, {%0,%1};"
               : "+r"(d0), "+r"(d1) : "r"(a0), "r"(a1), "r"(a2), "r"(a3), "r"(b0), "r"(b1));
}
__device__ __forceinline__ void mma_bf16(float* d, uint32_t a0, uint32_t a1, uint32_t a2, uint32_t a3, uint32_t b0, uint32_t b1) {
  asm volatile("mma.sync.aligned.m16n8k16.row.col.f32.bf16.bf16.f32 {%0,%1,%2,%3}, {%4,%5,%6,%7}, {%8,%9}, {%0,%1,%2,%3};"
               : "+f"(d[0]), "+f"(d[1]), "+f"(d[2]), "+f"(d[3]) : "r"(a0), "r"(a1), "r"(a2), "r"(a3), "r"(b0), "r"(b1));
}
__device__ __forceinline__ void mma_bf16_k8(float* d, uint32_t a0, uint32_t a1, uint32_t b0) {
  asm volatile("mma.sync.aligned.m16n8k8.row.col.f32.bf16.bf16.f32 {%0,%1,%2,%3}, {%4,%5}, {%6}, {%0,%1,%2,%3};"
               : "+f"(d[0]), "+f"(d[1]), "+f"(d[2]), "+f"(d[3]) : "r"(a0), "r"(a1), "r"(b0));
}

__device__ __forceinline__ void wg_fence() { asm volatile("wgmma.fence.sync.aligned;" ::: "memory"); }
__device__ __forceinline__ void wg_commit() { asm volatile("wgmma.commit_group.sync.aligned;" ::: "memory"); }
template <int N> __device__ __forceinline__ void wg_wait() { asm volatile("wgmma.wait_group.sync.aligned %0;" :: "n"(N) : "memory"); }
template <int TB> __device__ __forceinline__ void wgmma32(float* d, const uint32_t* a, uint32_t dlo, uint32_t dhi) {
  asm volatile("{ .reg .b64 dd; mov.b64 dd, {%20, %21}; wgmma.mma_async.sync.aligned.m64n32k16.f32.f16.f16 "
               "{%0,%1,%2,%3,%4,%5,%6,%7,%8,%9,%10,%11,%12,%13,%14,%15}, {%16,%17,%18,%19}, dd, 1, 1, 1, %22; }"
               : "+f"(d[0]), "+f"(d[1]), "+f"(d[2]), "+f"(d[3]), "+f"(d[4]), "+f"(d[5]), "+f"(d[6]), "+f"(d[7]),
                 "+f"(d[8]), "+f"(d[9]), "+f"(d[10]), "+f"(d[11]), "+f"(d[12]), "+f"(d[13]), "+f"(d[14]), "+f"(d[15])
               : "r"(a[0]), "r"(a[1]), "r"(a[2]), "r"(a[3]), "r"(dlo), "r"(dhi), "n"(TB));
}
__device__ __forceinline__ void wgmma32_init(float* d, const uint32_t* a, uint32_t dlo, uint32_t dhi) {
  asm volatile("{ .reg .b64 dd; mov.b64 dd, {%20, %21}; wgmma.mma_async.sync.aligned.m64n32k16.f32.f16.f16 "
               "{%0,%1,%2,%3,%4,%5,%6,%7,%8,%9,%10,%11,%12,%13,%14,%15}, {%16,%17,%18,%19}, dd, 0, 1, 1, 0; }"
               : "=f"(d[0]), "=f"(d[1]), "=f"(d[2]), "=f"(d[3]), "=f"(d[4]), "=f"(d[5]), "=f"(d[6]), "=f"(d[7]),
                 "=f"(d[8]), "=f"(d[9]), "=f"(d[10]), "=f"(d[11]), "=f"(d[12]), "=f"(d[13]), "=f"(d[14]), "=f"(d[15])
               : "r"(a[0]), "r"(a[1]), "r"(a[2]), "r"(a[3]), "r"(dlo), "r"(dhi));
}

struct Params {
  const uint32_t* x;
  const uint16_t* ssm[6];
  const uint16_t* log_dt;
  const uint32_t* dskip;
  const uint32_t* w_r;
  const unsigned char* w_down;
  uint32_t* out;
  uint32_t zero;
};

struct SsmRaw { uint32_t v[7]; };
__device__ __forceinline__ SsmRaw load_ssm(const Params& p, int ch, int n) {
  SsmRaw r;
#pragma unroll
  for (int i = 0; i < 6; i++) r.v[i] = __ldg(p.ssm[i] + ch * 128 + n);
  r.v[6] = __ldg(p.log_dt + ch);
  return r;
}

__device__ __forceinline__ void ln_stats(const uint32_t (&w)[9], uint32_t& m2, float& rden) {
  float s = 0.f;
#pragma unroll
  for (int i = 0; i < 9; i++) s += bf_lo(w[i]) + bf_hi(w[i]);
  const float mean = warp_sum(s) * (1.f / DM);
  float q = 0.f;
#pragma unroll
  for (int i = 0; i < 9; i++) { float a = bf_lo(w[i]) - mean, b = bf_hi(w[i]) - mean; q = fmaf(a, a, q); q = fmaf(b, b, q); }
  const float var = warp_sum(q) * (1.f / DM);
  m2 = pack_bf(mean, mean);
  const float den = bfr(sqrtf(bfr(bfr(var) + 1e-5f)));
  rden = 1.f / den;
}
__device__ __forceinline__ uint32_t ln_apply(uint32_t w, uint32_t m2, float rden) {
  const uint32_t d = bf_sub2(w, m2);
  return pack_bf(bf_lo(d) * rden, bf_hi(d) * rden);
}

__device__ __forceinline__ float2 cis_neg(float mag_log2, float rev) {
  const float m = ex2(mag_log2);
  const float ang = rev * 6.283185307179586f;
  return make_float2(m * __cosf(ang), -m * __sinf(ang));
}
__device__ __forceinline__ float2 csq(float2 a) { return make_float2(fmaf(a.x, a.x, -a.y * a.y), (a.x + a.x) * a.y); }
__device__ __forceinline__ float2 cmul(float2 a, float2 b) { return make_float2(fmaf(a.x, b.x, -a.y * b.y), fmaf(a.x, b.y, a.y * b.x)); }

__device__ __forceinline__ void kgen(const SsmRaw& raw, uint32_t sbase, int slot, int wg, int wt) {
  const int w = wt >> 5, lane = wt & 31, g = lane >> 2, t = lane & 3;
  const uint32_t scr = sbase + OFF_SCR + wg * SCR_WG;
  const uint32_t wscr = scr + w * SCR_WARP;
  const uint32_t misc = sbase + OFF_MISC;
  int ew;
  {
    const float dt = bfr(__expf(bf_lo(raw.v[6])));
    const float are = dt * bf_lo(raw.v[0]), th = dt * bf_lo(raw.v[1]);
    const float br = dt * bf_lo(raw.v[2]), bi = dt * bf_lo(raw.v[3]);
    const float Cr = bf_lo(raw.v[4]), Ci = bf_lo(raw.v[5]);
    float cr = fmaf(Cr, br, -Ci * bi), ci = fmaf(Cr, bi, Ci * br);
    const float a2 = are * 1.4426950408889634f;
    const float rh = th * 0.15915494309189535f;
    const float rl = fmaf(th, 0.15915494309189535f, -rh) + th * (float)(0.15915494309189535 - (double)0.15915494309189535f);
    const float rf = rh - rintf(rh);
    const float2 E1 = cis_neg(a2, rf + rl);
    const float p128 = rf * 128.f;
    const float2 E128 = cis_neg(a2 * 128.f, (p128 - rintf(p128)) + 128.f * rl);
    const float p240 = rf * 240.f;
    const float2 E240 = cis_neg(a2 * 240.f, (p240 - rintf(p240)) + (fmaf(rf, 240.f, -p240) + 240.f * rl));
    const float2 E256 = csq(E128), E512 = csq(E256), E1024 = csq(E512), E2048 = csq(E1024);
    const float2 E752 = cmul(E512, E240), E1264 = cmul(E1024, E240), E1504 = cmul(E1264, E240), E1744 = cmul(E1504, E240);
    const float k2048 = warp_sum(fmaf(cr, E2048.x, ci * E2048.y));
    uint32_t mx = __float_as_uint(fmaxf(fabsf(cr), fabsf(ci)));
    mx = __reduce_max_sync(0xffffffffu, mx);
    ew = max(min((int)(mx >> 23), 240), 16);
    const float sc = __uint_as_float((uint32_t)(127 + 4 + 127 - ew) << 23);
    cr *= sc; ci *= sc;
    const float c1r = fmaf(cr, E128.x, ci * E128.y), c1i = fmaf(ci, E128.x, -cr * E128.y);
    const uint32_t rec = wscr + lane * 80;
    sts128(rec, pack_h(E1.x, E1.y), pack_h(-E1.y, E1.x), pack_h(E256.x, E256.y), pack_h(-E256.y, E256.x));
    sts128(rec + 16, pack_h(cr, ci), pack_h(ci, -cr), pack_h(c1r, c1i), pack_h(c1i, -c1r));
    const uint32_t k2a = pack_h(E512.x, E512.y), k2b = pack_h(E752.x, E752.y);
    sts128(rec + 32, pack_h(E1024.x, E1024.y), k2a, pack_h(E1264.x, E1264.y), k2a);
    sts128(rec + 48, pack_h(E1504.x, E1504.y), k2b, pack_h(E1744.x, E1744.y), k2b);
    sts64(rec + 64, __float_as_uint(a2), __float_as_uint((rf + rl) * 6.283185307179586f));
    if (lane == 0) { sts32(misc + MISC_EXP + (wg * 4 + w) * 4, (uint32_t)ew); sts32(misc + MISC_EXP + 64 + (wg * 4 + w) * 4, __float_as_uint(k2048)); }
  }
  __syncwarp();
  float acc[5][4];
#pragma unroll
  for (int i = 0; i < 5; i++) { acc[i][0] = acc[i][1] = acc[i][2] = acc[i][3] = 0.f; }
  const float g2 = (float)(2 * g);
#pragma unroll 1
  for (int ks = 0; ks < 4; ks++) {
    uint32_t A[2][2], B[2][5];
#pragma unroll
    for (int s = 0; s < 2; s++) {
      const uint32_t rec = wscr + (ks * 8 + s * 4 + t) * 80;
      const uint2 ab = lds64(rec + 64);
      const uint4 wz = lds128(rec);
      const uint4 wc = lds128(rec + 16);
      const uint2 wk = lds64(rec + 32 + (g >> 1) * 8);
      const float m = ex2(__uint_as_float(ab.x) * g2);
      const float ang = __uint_as_float(ab.y) * g2;
      const float2 s1 = make_float2(m * __cosf(ang), -m * __sinf(ang));
      const float2 s2 = csq(s1), s4 = csq(s2), s8 = csq(s4);
      const uint32_t x1 = pack_h(s1.x, s1.y), x8 = pack_h(s8.x, s8.y);
      B[s][0] = x1;
      B[s][1] = cmul_xsel(x1, wz.x, wz.y);
      B[s][2] = cmul_xsel(x1, wz.z, wz.w);
      B[s][3] = cmul_xsel(wk.y, pack_h(s2.x, s2.y), pack_h(-s2.y, s2.x));
      B[s][4] = cmul_xsel(wk.x, pack_h(s4.x, s4.y), pack_h(-s4.y, s4.x));
      A[s][0] = cmul_xsel(x8, wc.x, wc.y);
      A[s][1] = cmul_xsel(x8, wc.z, wc.w);
    }
#pragma unroll
    for (int i = 0; i < 5; i++) mma_f16_f32(acc[i], A[0][0], A[0][1], A[1][0], A[1][1], B[0][i], B[1][i]);
  }
  __syncwarp();
#pragma unroll
  for (int h = 0; h < 2; h++) {
    sts128(wscr + (16 * g + 128 * h + 4 * t) * 4, __float_as_uint(acc[0][2 * h]), __float_as_uint(acc[1][2 * h]), __float_as_uint(acc[0][2 * h + 1]), __float_as_uint(acc[1][2 * h + 1]));
    sts64(wscr + (256 + 8 * g + 64 * h + 2 * t) * 4, __float_as_uint(acc[2][2 * h]), __float_as_uint(acc[2][2 * h + 1]));
    sts64(wscr + (384 + 4 * g + 32 * h + 2 * (t & 1) + 64 * (t >> 1)) * 4, __float_as_uint(acc[3][2 * h]), __float_as_uint(acc[3][2 * h + 1]));
    sts64(wscr + (512 + 2 * g + 16 * h + 32 * t) * 4, __float_as_uint(acc[4][2 * h]), __float_as_uint(acc[4][2 * h + 1]));
  }
  bar_sync(1 + wg, 128);
  const uint4 e4 = lds128(misc + MISC_EXP + wg * 16);
  const int em = max(max((int)e4.x, (int)e4.y), max((int)e4.z, (int)e4.w));
  float v0 = 0.f, v1 = 0.f, v2 = 0.f, v3 = 0.f, v4 = 0.f;
#pragma unroll
  for (int q = 0; q < 4; q++) {
    const int eq = (int)(q == 0 ? e4.x : q == 1 ? e4.y : q == 2 ? e4.z : e4.w);
    const float f = __uint_as_float((uint32_t)max(127 - 11 + eq - em, 0) << 23);
    const uint32_t ps = scr + q * SCR_WARP;
    const uint2 a = lds64(ps + wt * 8);
    v0 = fmaf(__uint_as_float(a.x), f, v0); v1 = fmaf(__uint_as_float(a.y), f, v1);
    v2 = fmaf(__uint_as_float(lds32(ps + (256 + wt) * 4)), f, v2);
    v3 = fmaf(__uint_as_float(lds32(ps + (384 + wt) * 4)), f, v3);
    v4 = fmaf(__uint_as_float(lds32(ps + (512 + wt) * 4)), f, v4);
  }
  const uint32_t kc = scr + 4 * SCR_WARP + 16;
  const uint32_t kt = sbase + OFF_KT + slot * KT_BYTES;
  const uint32_t l3 = kt + KT_WORDS * 4;
  const uint32_t h01 = pack_h(v0, v1), h23 = pack_h(v2, v3);
  uint32_t h4 = pack_h(v4, v4);
  sts32(kc + wt * 4, h01);
  sts16(kc + (256 + wt) * 2, h23);
  sts16(kc + (384 + wt) * 2, h23 >> 16);
  if (wt == 0) {
    sts16(kc + 512 * 2, h4);
    const uint32_t tw = kt + (16 + 1024) * 4;
    sts128(tw, h4, h4, h4, h4); sts64(tw + 16, h4, h4 & 0xFFFF0000u);
    const uint4 k4 = lds128(misc + MISC_EXP + 64 + wg * 16);
    const float inv = __uint_as_float((uint32_t)(127 + 127 - 7 - em) << 23);
    const float kl = ((__uint_as_float(k4.x) + __uint_as_float(k4.y)) + (__uint_as_float(k4.z) + __uint_as_float(k4.w))) * inv;
    h4 = pack_h(kl, kl);
    sts32(misc + MISC_SCALE + slot * 4, (uint32_t)(em + 7) << 23);
  }
  {
    const int m = wt == 0 ? 128 : wt;
    const uint32_t arr = l3 + (m & 1) * (2 * L3_ARR) + ((m - 1) >> 1) * 2;
    sts16(arr + 56 * 2, h4);
    sts16(arr + L3_ARR + 60 * 2, h4);
  }
  bar_sync(1 + wg, 128);
  {
    const uint32_t km1 = wt == 0 ? 0u : lds16(kc + wt * 4 - 2);
    const uint32_t p1 = lds16(kc + (256 + wt) * 2 - 2), n1 = lds16(kc + (256 + wt) * 2 + 2);
    const uint32_t n2 = lds16(kc + (384 + wt) * 2 + 2);
    const uint32_t wb = kt + 16 * 4;
    sts64(wb + wt * 8, (h01 & 0xFFFFu) | (km1 << 16), __byte_perm(h01, 0, 0x1032));
    const bool odd = wt & 1;
    const uint32_t c1 = h23 & 0xFFFFu, c2 = h23 >> 16;
    const uint32_t lo1 = (odd || wt == 0) ? p1 : c1, hi1 = odd ? n1 : c1;
    sts64(wb + (256 + 2 * wt) * 4, c1 | (lo1 << 16), hi1 | (c1 << 16));
    const uint32_t tie = odd ? n2 : c2, cc = c2 | (c2 << 16);
    sts128(wb + (512 + 4 * wt) * 4, cc, cc, tie | (c2 << 16), n2 | (tie << 16));
  }
}

__device__ __forceinline__ void load_u(uint32_t sbase, int slot, int ch, int wt, uint32_t epoch) {
  uint4 v[2];
#pragma unroll
  for (int r = 0; r < 2; r++) {
    const int a = (wt >> 1) + 64 * r;
#pragma unroll 1
    for (int it = 0; it < SPIN_MAX && ldr32(&g_FLAG[a]) != epoch; it++) {}
  }
#pragma unroll
  for (int r = 0; r < 2; r++) v[r] = ldr128(&g_U2[(((wt >> 1) + 64 * r) * DM + ch) * 2 + (wt & 1)]);
#pragma unroll
  for (int r = 0; r < 2; r++) {
    const int a = (wt >> 1) + 64 * r;
#pragma unroll 1
    for (int it = 0; it < SPIN_MAX && ((v[r].x ^ epoch) & 1u); it++) v[r] = ldr128(&g_U2[(a * DM + ch) * 2 + (wt & 1)]);
    sts128(sbase + OFF_UP + (slot * 2 + (wt & 1)) * UP_PLANE + (UP_PAD + a) * 16, v[r].x & ~1u, v[r].y, v[r].z, v[r].w);
  }
  asm volatile("fence.proxy.async.shared::cta;" ::: "memory");
}

__device__ __forceinline__ void load_a(uint32_t (&a)[4], uint32_t kp, int j, uint32_t zero) {
  a[0] = lds32(kp + 256 * j); a[1] = lds32(kp + 256 * j + 32); a[2] = lds32(kp + 256 * j - 32);
  asm volatile("xor.b32 %0, %1, %2;" : "=r"(a[3]) : "r"(a[0]), "r"(zero));
}
__device__ __forceinline__ uint32_t band(int d, int lo, int hi) {
  return ((d >= lo && d <= hi) ? 0x3C00u : 0u) | ((d - 1 >= lo && d - 1 <= hi) ? 0x3C000000u : 0u);
}

struct Epi { uint32_t st, ld; float scale; unsigned char* y; int w, wt, bar; };
template <int Q> __device__ __forceinline__ void epi_store(const float* acc, const Epi& e) {
#pragma unroll
  for (int h = 0; h < 2; h++)
    stsm4t(e.st + ((Q % 3) * 32 + 16 * h) * 32, pack_h(acc[8 * h], acc[8 * h + 1]), pack_h(acc[8 * h + 2], acc[8 * h + 3]),
           pack_h(acc[8 * h + 4], acc[8 * h + 5]), pack_h(acc[8 * h + 6], acc[8 * h + 7]));
}
template <int Q> __device__ __forceinline__ void epi_load(uint2 (&v)[4], const Epi& e) {
  const int cl = e.wt >> 2, qt = e.wt & 3;
#pragma unroll
  for (int ww = 0; ww < 4; ww++) {
    int s = (Q % 3) * 32 + cl - ww;
    if (Q == 3 && s < 0) s += 96;
    v[ww] = lds64(e.ld + ww * SCR_WARP + s * 32 + (((qt >> 1) ^ ((s >> 2) & 1)) << 4) + (qt & 1) * 8);
  }
}
template <int Q> __device__ __forceinline__ void epi_out(const uint2 (&v)[4], const Epi& e) {
  float s0 = 0.f, s1 = 0.f, s2 = 0.f, s3 = 0.f;
#pragma unroll
  for (int ww = 0; ww < 4; ww++) { const float2 a = h2f(v[ww].x), b = h2f(v[ww].y); s0 += a.x; s1 += a.y; s2 += b.x; s3 += b.y; }
  str64(e.y + (size_t)Q * (32 * DM * 32), pack_bf(s0 * e.scale, s1 * e.scale), pack_bf(s2 * e.scale, s3 * e.scale));
}

__global__ void __launch_bounds__(NT, 1)
fused_kernel(const Params p, const __grid_constant__ CUtensorMap tm_gate, const __grid_constant__ CUtensorMap tm_up) {
  extern __shared__ __align__(1024) unsigned char smem[];
  const uint32_t sb = smem_u32(smem);
  const int tid = threadIdx.x, lane = tid & 31, c = blockIdx.x;
  const int warp = __shfl_sync(0xffffffffu, tid >> 5, 0);
  const int wg = warp >> 2, w = warp & 3, wt = tid & 127, g = lane >> 2, t = lane & 3;
  const bool five = (c & 1) == 0;
  const int nu = five ? 4 : 5, u0 = (c >> 1) * 9 + (five ? 0 : 4);
  const int tok = c * 16 + warp;
  TS(0);

  uint32_t xw[9];
#pragma unroll
  for (int i = 0; i < 9; i++) xw[i] = __ldg(p.x + tok * 288 + lane + 32 * i);
  const uint32_t epoch = ldr32(&g_FLAG[c]) + 1u;
  SsmRaw raw = load_ssm(p, 4 * c + wg, wt);
  SsmRaw raw5 = load_ssm(p, (wg == 1 && five) ? 512 + (c >> 1) : 4 * c + wg, wt);
  if (warp == 15 && lane < 18) asm volatile("prefetch.global.L2 [%0];" :: "l"((lane < 9 ? p.dskip : p.w_r - 288) + lane * 32));
  if (tid == 0) {
    const uint32_t mb = sb + OFF_MISC + MISC_MBAR;
    asm volatile("mbarrier.init.shared::cta.b64 [%0], 1;" :: "r"(mb) : "memory");
    asm volatile("fence.proxy.async.shared::cta;" ::: "memory");
    asm volatile("mbarrier.arrive.expect_tx.shared::cta.b64 _, [%0], %1;" :: "r"(mb), "r"(2 * GU_MAT) : "memory");
#pragma unroll
    for (int r = 0; r < 3; r++) {
      asm volatile("cp.async.bulk.tensor.2d.shared::cluster.global.mbarrier::complete_tx::bytes [%0], [%1, {%3, %4}], [%2];"
                   :: "r"(sb + OFF_GU + r * 192 * 80), "l"(&tm_gate), "r"(mb), "r"(u0 * 8), "r"(r * 192) : "memory");
      asm volatile("cp.async.bulk.tensor.2d.shared::cluster.global.mbarrier::complete_tx::bytes [%0], [%1, {%3, %4}], [%2];"
                   :: "r"(sb + OFF_GU + GU_MAT + r * 192 * 80), "l"(&tm_up), "r"(mb), "r"(u0 * 8), "r"(r * 192) : "memory");
    }
    asm volatile("cp.async.bulk.prefetch.L2.global [%0], %1;" :: "l"(p.w_down + (size_t)u0 * 8 * DM * 2), "r"(nu * 8 * DM * 2) : "memory");
  }
  for (int i = tid; i < DM * 2; i += NT) str128(&g_Y2[c * DM * 2 + i], ~0u, ~0u, ~0u, ~0u);
  if (tid < 2) str128(&g_R[c * 2 + tid], ~0u, ~0u, ~0u, ~0u);
  if (c < 72 && tid >= 32 && tid < 48) str128(&g_P[NCTA * 1152 + c * 16 + tid - 32], ~0u, ~0u, ~0u, ~0u);
  if (tid < 10 * UP_PAD) sts128(sb + OFF_UP + (tid / UP_PAD) * UP_PLANE + (tid % UP_PAD) * 16, 0, 0, 0, 0);
  if (tid < 5 * 84) {
    const int s = tid / 84, i = tid % 84;
    sts128(sb + OFF_KT + s * KT_BYTES + (i < 4 ? i * 16 : (16 + 1024) * 4 + (i - 4) * 16), 0, 0, 0, 0);
  }
  if (tid == 0) sts32(sb + OFF_MISC + MISC_CNT, 0);
  TS(13);
  fence_gpu();
  TS(14);

  uint32_t m1; float rden1;
  ln_stats(xw, m1, rden1);
  {
    const uint32_t row = sb + OFF_YT + warp * YT_PITCH + (warp >> 3) * 64 + lane * 4;
#pragma unroll
    for (int i = 0; i < 9; i++) { const uint32_t u = ln_apply(xw[i], m1, rden1); sts32(row + i * 128, pack_h(bf_lo(u), bf_hi(u))); }
  }
  __syncthreads();
  const int tr_tok = 8 * ((lane >> 1) & 1) + 2 * (lane >> 3) + (lane & 1);
  const uint32_t tr_addr = sb + OFF_YT + tr_tok * YT_PITCH + (tr_tok >> 3) * 64 + ((lane >> 2) & 1) * 16;
  const int tr_chunk = (8 * (t >> 1) + g) * 2 + (t & 1);
  for (int op = warp; op < 36; op += 16) {
    uint32_t r0, r1, r2, r3;
    ldsm4t(tr_addr + op * 32, r0, r1, r2, r3);
    str128(&g_U2[c * DM * 2 + op * 32 + tr_chunk], (r0 & ~1u) | (epoch & 1u), r1, r2, r3);
  }
  __syncthreads();
  if (tid == 0) str32(&g_FLAG[c], epoch);
  TS(1);
  if (wg == 3) for (int i = wt; i < 1152; i += 128) str128(&g_P[c * 1152 + i], ~0u, ~0u, ~0u, ~0u);

  {
    const int nrep = (wg == 1 && five) ? 2 : 1;
#pragma unroll 1
    for (int rep = 0; rep < nrep; rep++) {
      kgen(raw, sb, rep ? 4 : wg, wg, wt);
      raw = raw5;
      if (rep + 1 < nrep) bar_sync(1 + wg, 128);
    }
    if (wg == 3) fence_gpu();
    TS(2);
#pragma unroll 1
    for (int rep = 0; rep < nrep; rep++) load_u(sb, rep ? 4 : wg, rep ? 512 + (c >> 1) : 4 * c + wg, wt, epoch);
    if (nrep == 2) bar_arrive(5, 256);
  }

  {
    const uint32_t zero = p.zero;
    int slot = wg, ch = 4 * c + wg;
    Epi e;
    e.w = w; e.wt = wt; e.bar = 1 + wg;
    e.ld = sb + OFF_SCR + wg * SCR_WG + 128;
    {
      const int mi = lane >> 3, rr = lane & 7, col = 8 * (mi >> 1) + rr;
      e.st = e.ld + w * SCR_WARP + col * 32 + (((mi & 1) ^ ((col >> 2) & 1)) << 4);
    }
    bar_sync(e.bar, 128);
    if (lane < 8) sts128(e.ld - 128 + w * SCR_WARP + lane * 16, 0, 0, 0, 0);
    TS(3);
    const int nitem = (wg == 0 && five) ? 2 : 1;
#pragma unroll 1
    for (int item = 0; item < nitem; item++) {
      if (item) { slot = 4; ch = 512 + (c >> 1); bar_sync(5, 256); }
      const uint32_t kt = sb + OFF_KT + slot * KT_BYTES;
      const uint32_t kp = kt + (16 + 16 * w + g - 2 * t) * 4;
      const uint32_t up = sb + OFF_UP + slot * 2 * UP_PLANE;
      const uint32_t dlo = ((up >> 4) & 0x3FFF) + UP_PAD + ((uint32_t)(UP_PLANE >> 4) << 16), dhi = 8;
      e.scale = __uint_as_float(lds32(sb + OFF_MISC + MISC_SCALE + slot * 4));
      e.y = (unsigned char*)g_Y2 + ((size_t)(wt >> 2) * DM + ch) * 32 + (wt & 3) * 8;
      float acc[4][16];
      uint32_t a0[4][4], a1[4][4];
#pragma unroll
      for (int j = 0; j < 4; j++) { load_a(a0[j], kp, 8 + j, zero); load_a(a1[j], kp, 12 + j, zero); }
      wg_fence();
#pragma unroll
      for (int j = 0; j < 4; j++)
#pragma unroll
        for (int q = 1; q < 4; q++) {
          if (j == 0) wgmma32_init(acc[q], a0[j], dlo + 32 * q - 4 * (8 + j), dhi);
          else wgmma32<0>(acc[q], a0[j], dlo + 32 * q - 4 * (8 + j), dhi);
        }
      wg_commit();
      uint32_t x9[4] = {0, 0, 0, 0}, x7[4] = {0, 0, 0, 0}, a16[4];
      {
        const int d0 = g - 2 * t;
        uint32_t b[2][5];
        const int rr = lane & 7, mi = lane >> 3;
#pragma unroll
        for (int tl = 0; tl < 2; tl++) {
          const int ci = 2 * (56 + 4 * tl - 8 * rr + w) - 3 + mi;
          ldsm4(up + (ci & 1) * UP_PLANE + (UP_PAD + (ci >> 1)) * 16, b[tl][0], b[tl][1], b[tl][2], b[tl][3]);
        }
        ldsm2(up + UP_PLANE + (UP_PAD + 56 + 4 * (mi & 1) - 8 * rr + w) * 16, b[0][4], b[1][4]);
        load_a(a16, kp, 16, zero);
        wg_fence();
#pragma unroll
        for (int j = 0; j < 4; j++)
#pragma unroll
          for (int q = 1; q < 4; q++) wgmma32<0>(acc[q], a1[j], dlo + 32 * q - 4 * (12 + j), dhi);
        wg_commit();
        const uint32_t n24 = band(d0 + 24, 12, 20), n16 = band(d0 + 16, 12, 20), n8 = band(d0 + 8, 12, 20);
        const uint32_t s16 = band(d0 + 16, 5, 11), s8 = band(d0 + 8, 5, 11), s0 = band(d0, 5, 11);
#pragma unroll
        for (int tl = 0; tl < 2; tl++) {
          mma_f16_f16(x9[2 * tl], x9[2 * tl + 1], n24, 0u, n16, n24, b[tl][0], b[tl][1]);
          mma_f16_f16(x7[2 * tl], x7[2 * tl + 1], s16, 0u, s8, s16, b[tl][1], b[tl][2]);
          mma_f16_f16(x9[2 * tl], x9[2 * tl + 1], n8, n16, 0u, n8, b[tl][2], b[tl][3]);
          mma_f16_f16(x7[2 * tl], x7[2 * tl + 1], s0, s8, 0u, s0, b[tl][3], b[tl][4]);
        }
      }
      wg_wait<1>();
#pragma unroll
      for (int j = 0; j < 4; j++) load_a(a0[j], kp, j, zero);
      {
        const uint32_t l3lo = (((kt + KT_WORDS * 4) >> 4) & 0x3FFF) + ((uint32_t)(L3_ARR >> 4) << 16), l3hi = 1;
        wg_fence();
#pragma unroll
        for (int q = 2; q < 4; q++) {
          wgmma32<0>(acc[q], a16, dlo + 32 * q - 64, dhi);
          wgmma32<1>(acc[q], x9, l3lo + 4 * (q - 2), l3hi);
          wgmma32<1>(acc[q], x7, l3lo + 4 * (q - 2) + (2 * L3_ARR >> 4), l3hi);
        }
        wg_commit();
      }
      wg_wait<1>();
#pragma unroll
      for (int j = 0; j < 4; j++) load_a(a1[j], kp, 4 + j, zero);
      wg_fence();
      wgmma32_init(acc[0], a0[0], dlo, dhi);
#pragma unroll
      for (int j = 1; j < 4; j++) wgmma32<0>(acc[0], a0[j], dlo - 4 * j, dhi);
#pragma unroll
      for (int j = 0; j < 4; j++) wgmma32<0>(acc[0], a1[j], dlo - 4 * (4 + j), dhi);
      wg_commit();
      uint2 ev[4];
#define CONV_GROUP(Q)                                                                          \
      wgmma32<0>(acc[Q], a0[0], dlo + 32 * Q, dhi); wgmma32<0>(acc[Q], a0[1], dlo + 32 * Q - 4, dhi);    \
      wg_commit(); wg_wait<1>();                                                               \
      epi_store<Q - 1>(acc[Q - 1], e); wg_fence();                                             \
      wgmma32<0>(acc[Q], a0[2], dlo + 32 * Q - 8, dhi); wgmma32<0>(acc[Q], a0[3], dlo + 32 * Q - 12, dhi); \
      bar_sync(e.bar, 128); epi_load<Q - 1>(ev, e);                                            \
      wgmma32<0>(acc[Q], a1[0], dlo + 32 * Q - 16, dhi); wgmma32<0>(acc[Q], a1[1], dlo + 32 * Q - 20, dhi); \
      epi_out<Q - 1>(ev, e);                                                                   \
      wgmma32<0>(acc[Q], a1[2], dlo + 32 * Q - 24, dhi); wgmma32<0>(acc[Q], a1[3], dlo + 32 * Q - 28, dhi); \
      wg_commit();
      CONV_GROUP(1) CONV_GROUP(2) CONV_GROUP(3)
#undef CONV_GROUP
      wg_wait<0>();
      epi_store<3>(acc[3], e);
      bar_sync(e.bar, 128);
      epi_load<3>(ev, e);
      epi_out<3>(ev, e);
    }
  }
  TS(4);

  uint32_t ds[9], wr[9];
#pragma unroll
  for (int i = 0; i < 9; i++) { xw[i] = __ldg(p.x + tok * 288 + lane + 32 * i); ds[i] = __ldg(p.dskip + lane + 32 * i); wr[i] = __ldg(p.w_r + lane + 32 * i); }
  uint4 wd[5][2];
  if (warp < 9) {
#pragma unroll
    for (int q = 0; q < 5; q++)
#pragma unroll
      for (int r = 0; r < 2; r++)
        wd[q][r] = q < nu ? __ldg((const uint4*)(p.w_down + ((size_t)(u0 + q) * 8 + 2 * t + r) * (DM * 2) + warp * 128 + g * 16)) : make_uint4(0, 0, 0, 0);
  }
  const int fu = warp / 3, fk = warp - fu * 3;
  uint32_t wa[12][4];
  {
    const uint32_t mb = sb + OFF_MISC + MISC_MBAR;
#pragma unroll 1
    for (int it = 0; it < SPIN_MAX; it++) {
      uint32_t ok;
      asm volatile("{ .reg .pred q; mbarrier.try_wait.parity.shared::cta.b64 q, [%1], 0; selp.u32 %0, 1, 0, q; }" : "=r"(ok) : "r"(mb) : "memory");
      if (ok) break;
    }
    if (warp < 15) {
      const uint32_t base = sb + OFF_GU + ((lane >> 3) & 1) * GU_MAT + (fk * 192 + (lane >> 4) * 8 + (lane & 7)) * 80 + fu * 16;
#pragma unroll
      for (int k = 0; k < 12; k++) ldsm4t(base + k * 16 * 80, wa[k][0], wa[k][1], wa[k][2], wa[k][3]);
    }
  }
  TS(5);
#pragma unroll
  for (int i = 0; i < 9; i++) ds[i] = bf_mul2(ln_apply(xw[i], m1, rden1), ds[i]);
  for (int op = warp; op < 36; op += 16) {
    const uint4* src = &g_Y2[c * DM * 2 + op * 32 + tr_chunk];
    uint4 v = ldr128(src);
#pragma unroll 1
    for (int it = 0; it < SPIN_MAX && (v.x == ~0u || v.z == ~0u); it++) v = ldr128(src);
    __syncwarp();
    stsm4t(tr_addr + op * 32, v.x, v.y, v.z, v.w);
  }
  __syncthreads();
  TS(6);
  uint32_t hw[9], lw[9];
  {
    const uint32_t row = sb + OFF_YT + warp * YT_PITCH + (warp >> 3) * 64 + lane * 4;
#pragma unroll
    for (int i = 0; i < 9; i++) hw[i] = bf_add2(xw[i], bf_add2(lds32(row + i * 128), ds[i]));
    uint32_t m2; float rden2;
    ln_stats(hw, m2, rden2);
    float r = 0.f;
#pragma unroll
    for (int i = 0; i < 9; i++) {
      lw[i] = ln_apply(hw[i], m2, rden2);
      r = fmaf(bf_lo(lw[i]), bf_lo(wr[i]), r); r = fmaf(bf_hi(lw[i]), bf_hi(wr[i]), r);
    }
    r = warp_sum(r);
    if (lane == 0) {
      const uint32_t b = pack_bf(r, 0.f) & 0xFFFFu;
      const uint32_t key = (b & 0x8000u) ? (~b & 0xFFFFu) : (b | 0x8000u);
      str16((uint16_t*)g_R + tok, min(key, 0xFFFEu));
    }
#pragma unroll
    for (int i = 0; i < 9; i++) str32(&g_ROW[tok * 288 + lane + 32 * i], (pack_h(bf_lo(lw[i]), bf_hi(lw[i])) & ~1u) | (epoch & 1u));
  }
  TS(7);

  const uint32_t cand = sb + OFF_SCR;
  uint32_t keys[8];
  if (tid < 256) {
    uint4 v = ldr128(&g_R[tid]);
#pragma unroll 1
    for (int it = 0; it < SPIN_MAX; it++) {
      const uint32_t bad = __vcmpeq2(v.x, ~0u) | __vcmpeq2(v.y, ~0u) | __vcmpeq2(v.z, ~0u) | __vcmpeq2(v.w, ~0u);
      if (!bad) break;
      v = ldr128(&g_R[tid]);
    }
    const uint32_t ib = 2047 - tid * 8;
    keys[0] = (v.x << 16) | ib;       keys[1] = (v.x & 0xFFFF0000u) | (ib - 1);
    keys[2] = (v.y << 16) | (ib - 2); keys[3] = (v.y & 0xFFFF0000u) | (ib - 3);
    keys[4] = (v.z << 16) | (ib - 4); keys[5] = (v.z & 0xFFFF0000u) | (ib - 5);
    keys[6] = (v.w << 16) | (ib - 6); keys[7] = (v.w & 0xFFFF0000u) | (ib - 7);
    uint32_t mx = max(max(max(keys[0], keys[1]), max(keys[2], keys[3])), max(max(keys[4], keys[5]), max(keys[6], keys[7])));
    __syncwarp();
    const uint32_t wm = __reduce_max_sync(0xffffffffu, mx);
    if (lane == 0) sts32(sb + OFF_MISC + MISC_WMAX + warp * 4, wm);
    bar_sync(6, 256);
    const uint4 q0 = lds128(sb + OFF_MISC + MISC_WMAX), q1 = lds128(sb + OFF_MISC + MISC_WMAX + 16);
    const uint32_t tau = min(min(min(q0.x, q0.y), min(q0.z, q0.w)), min(min(q1.x, q1.y), min(q1.z, q1.w)));
    if (mx >= tau) {
#pragma unroll
      for (int i = 0; i < 8; i++)
        if (keys[i] >= tau) {
          uint32_t pos;
          asm volatile("atom.shared.add.u32 %0, [%1], 1;" : "=r"(pos) : "r"(sb + OFF_MISC + MISC_CNT) : "memory");
          sts32(cand + pos * 4, keys[i]);
        }
    }
  }
  __syncthreads();
  TS(8);
  uint32_t selkey = 0;
  {
    const int n = (int)lds32(sb + OFF_MISC + MISC_CNT);
    for (int b = 0; b < n; b += 32) {
      const uint32_t mine = b + lane < n ? lds32(cand + (b + lane) * 4) : 0u;
      int rank = 0;
      for (int j = 0; j < n; j++) rank += lds32(cand + j * 4) > mine;
      uint32_t hit = __ballot_sync(0xffffffffu, rank < 8 && b + lane < n);
      while (hit) {
        const int src = __ffs(hit) - 1; hit &= hit - 1;
        const uint32_t kk = __shfl_sync(0xffffffffu, mine, src);
        const int rk = __shfl_sync(0xffffffffu, rank, src);
        if (lane == rk) selkey = kk;
      }
    }
  }
  const uint32_t xs = sb + OFF_SCR + 8192;
  {
    const int s = warp >> 1;
    const int tk = 2047 - (int)(__shfl_sync(0xffffffffu, selkey, s) & 0xFFFFu);
    const int c0 = (warp & 1) * 36 + lane;
    const uint4* src = (const uint4*)(g_ROW + tk * 288);
    uint4 v[2];
    v[0] = ldr128(src + c0);
    if (lane < 4) v[1] = ldr128(src + c0 + 32);
#pragma unroll
    for (int r = 0; r < 2; r++) {
      if (r == 0 || lane < 4) {
#pragma unroll 1
        for (int it = 0; it < SPIN_MAX && (((v[r].x ^ epoch) | (v[r].y ^ epoch) | (v[r].z ^ epoch) | (v[r].w ^ epoch)) & 1u); it++) v[r] = ldr128(src + c0 + 32 * r);
        const float2 f0 = h2f(v[r].x & ~1u), f1 = h2f(v[r].y & ~1u), f2 = h2f(v[r].z & ~1u), f3 = h2f(v[r].w & ~1u);
        sts128(xs + s * 1168 + (c0 + 32 * r) * 16, pack_bf(f0.x, f0.y), pack_bf(f1.x, f1.y), pack_bf(f2.x, f2.y), pack_bf(f3.x, f3.y));
      }
    }
  }
  {
    const uint32_t hit = __ballot_sync(0xffffffffu, lane < 8 && (int)(selkey & 0xFFFFu) == 2047 - tok);
    if (!hit) {
#pragma unroll
      for (int i = 0; i < 9; i++) p.out[tok * 288 + lane + 32 * i] = bf_add2(hw[i], lw[i]);
    } else {
      uint32_t* hs = (uint32_t*)(g_P + NCTA * 1152) + (__ffs(hit) - 1);
#pragma unroll
      for (int i = 0; i < 9; i++) {
        str32(hs + (lane + 32 * i) * 16, __byte_perm(hw[i], lw[i], 0x5410));
        str32(hs + (lane + 32 * i) * 16 + 8, __byte_perm(hw[i], lw[i], 0x7632));
      }
    }
  }
  __syncthreads();
  TS(9);

  const uint32_t red = sb + OFF_SCR + 8192 + 8 * 1168;
  if (warp < 15) {
    float d0[4] = {0.f, 0.f, 0.f, 0.f}, d1[4] = {0.f, 0.f, 0.f, 0.f};
    const uint32_t xb = xs + (lane & 7) * 1168 + (fk * 24 + (lane >> 3)) * 16;
#pragma unroll
    for (int k = 0; k < 12; k += 2) {
      uint32_t b0, b1, b2, b3;
      ldsm4(xb + k * 32, b0, b1, b2, b3);
      mma_bf16(d0, wa[k][0], wa[k][1], wa[k][2], wa[k][3], b0, b1);
      mma_bf16(d1, wa[k + 1][0], wa[k + 1][1], wa[k + 1][2], wa[k + 1][3], b2, b3);
    }
    sts128(red + warp * 512 + lane * 16, __float_as_uint(d0[0] + d1[0]), __float_as_uint(d0[1] + d1[1]), __float_as_uint(d0[2] + d1[2]), __float_as_uint(d0[3] + d1[3]));
  }
  __syncthreads();
  if (warp < 9) {
    float y[4][4];
#pragma unroll
    for (int j = 0; j < 4; j++) y[j][0] = y[j][1] = y[j][2] = y[j][3] = 0.f;
#pragma unroll
    for (int q = 0; q < 5; q++) {
      const uint4 pa = lds128(red + (q * 3) * 512 + lane * 16), pb = lds128(red + (q * 3 + 1) * 512 + lane * 16), pc = lds128(red + (q * 3 + 2) * 512 + lane * 16);
      const float ga = bfr(__uint_as_float(pa.x) + __uint_as_float(pb.x) + __uint_as_float(pc.x));
      const float gb = bfr(__uint_as_float(pa.y) + __uint_as_float(pb.y) + __uint_as_float(pc.y));
      const uint32_t uu = pack_bf(__uint_as_float(pa.z) + __uint_as_float(pb.z) + __uint_as_float(pc.z), __uint_as_float(pa.w) + __uint_as_float(pb.w) + __uint_as_float(pc.w));
      const uint32_t sg = pack_bf(__fdividef(ga, 1.f + __expf(-ga)), __fdividef(gb, 1.f + __expf(-gb)));
      uint32_t act = q < nu ? bf_mul2(sg, uu) : 0u;
      asm volatile("movmatrix.sync.aligned.m8n8.trans.b16 %0, %0;" : "+r"(act));
      const uint32_t* r0 = (const uint32_t*)&wd[q][0];
      const uint32_t* r1 = (const uint32_t*)&wd[q][1];
#pragma unroll
      for (int j = 0; j < 4; j++) mma_bf16_k8(y[j], __byte_perm(r0[j], r1[j], 0x5410), __byte_perm(r0[j], r1[j], 0x7632), act);
    }
    unsigned char* dst = (unsigned char*)(g_P + c * 1152) + (warp * 64 + g * 8) * 32 + t * 8;
#pragma unroll
    for (int j = 0; j < 4; j++) {
      str64(dst + (2 * j) * 32, __float_as_uint(y[j][0]), __float_as_uint(y[j][1]));
      str64(dst + (2 * j + 1) * 32, __float_as_uint(y[j][2]), __float_as_uint(y[j][3]));
    }
  }
  TS(10);

  {
    const uint32_t fr = sb + OFF_YT;
    const int sg = tid / 9, ck = tid - sg * 9;
    if (sg < 56) {
      uint4 v[3];
      float s0 = 0.f, s1 = 0.f, s2 = 0.f, s3 = 0.f;
#pragma unroll
      for (int r = 0; r < 3; r++) if (sg + 56 * r < NCTA) v[r] = ldr128(&g_P[(sg + 56 * r) * 1152 + c * 9 + ck]);
#pragma unroll
      for (int r = 0; r < 3; r++)
        if (sg + 56 * r < NCTA) {
#pragma unroll 1
          for (int it = 0; it < SPIN_MAX && (v[r].x == ~0u || v[r].z == ~0u); it++) v[r] = ldr128(&g_P[(sg + 56 * r) * 1152 + c * 9 + ck]);
          s0 += __uint_as_float(v[r].x); s1 += __uint_as_float(v[r].y); s2 += __uint_as_float(v[r].z); s3 += __uint_as_float(v[r].w);
        }
      sts128(fr + tid * 16, __float_as_uint(s0), __float_as_uint(s1), __float_as_uint(s2), __float_as_uint(s3));
    }
    const int o = tid >> 3, part = tid & 7;
    uint32_t hl = 0;
    const uint32_t* hsrc = (const uint32_t*)(g_P + NCTA * 1152) + c * 36 + o;
    if (o < 36 && part == 0) hl = ldr32(hsrc);
    __syncthreads();
    TS(11);
    const int og = c * 36 + o;
    const uint32_t key = __shfl_sync(0xffffffffu, selkey, og & 7);
    if (warp < 9) {
      float s = 0.f;
#pragma unroll
      for (int i = 0; i < 7; i++) s += __uint_as_float(lds32(fr + ((part * 7 + i) * 36 + o) * 4));
      s += __shfl_xor_sync(0xffffffffu, s, 1); s += __shfl_xor_sync(0xffffffffu, s, 2); s += __shfl_xor_sync(0xffffffffu, s, 4);
      if (part == 0) {
#pragma unroll 1
        for (int it = 0; it < SPIN_MAX && hl == ~0u; it++) hl = ldr32(hsrc);
        const uint32_t k16 = key >> 16;
        const float r = bf_lo((k16 & 0x8000u) ? (k16 & 0x7FFFu) : (~k16 & 0xFFFFu));
        const float rs = bfr(__fdividef(1.f, 1.f + __expf(-r)));
        const float upd = bfr(bfr(s) * rs);
        const float o1 = bfr(bf_hi(hl) + upd);
        ((uint16_t*)p.out)[(2047 - (int)(key & 0xFFFFu)) * DM + (og >> 3)] = (uint16_t)(pack_bf(bf_lo(hl) + o1, 0.f) & 0xFFFFu);
      }
    }
  }
  TS(12);
}

typedef CUresult (*EncodeFn)(CUtensorMap*, CUtensorMapDataType, cuuint32_t, void*, const cuuint64_t*, const cuuint64_t*, const cuuint32_t*,
                             const cuuint32_t*, CUtensorMapInterleave, CUtensorMapSwizzle, CUtensorMapL2promotion, CUtensorMapFloatOOBfill);

}

extern "C" void kernel_launch(void* const* d_in, const int* in_sizes, int n_in, void* d_out, int out_size) {
  (void)in_sizes; (void)n_in; (void)out_size;
  static EncodeFn enc = nullptr;
  if (!enc) {
    void* fn = nullptr;
    cudaDriverEntryPointQueryResult qr;
    cudaGetDriverEntryPoint("cuTensorMapEncodeTiled", &fn, cudaEnableDefault, &qr);
    enc = (EncodeFn)fn;
    cudaFuncSetAttribute(fused_kernel, cudaFuncAttributeMaxDynamicSharedMemorySize, SMEM_BYTES);
  }
  CUtensorMap tm[2];
  for (int i = 0; i < 2; i++) {
    cuuint64_t gd[2] = {FF, DM};
    cuuint64_t gs[1] = {FF * 2};
    cuuint32_t bx[2] = {40, 192};
    cuuint32_t es[2] = {1, 1};
    enc(&tm[i], CU_TENSOR_MAP_DATA_TYPE_BFLOAT16, 2, d_in[11 + i], gd, gs, bx, es, CU_TENSOR_MAP_INTERLEAVE_NONE, CU_TENSOR_MAP_SWIZZLE_NONE,
        CU_TENSOR_MAP_L2_PROMOTION_L2_128B, CU_TENSOR_MAP_FLOAT_OOB_FILL_NONE);
  }
  Params p;
  p.x = (const uint32_t*)d_in[0];
  for (int i = 0; i < 6; i++) p.ssm[i] = (const uint16_t*)d_in[1 + i];
  p.log_dt = (const uint16_t*)d_in[7];
  p.dskip = (const uint32_t*)d_in[8];
  p.w_r = (const uint32_t*)d_in[10];
  p.w_down = (const unsigned char*)d_in[13];
  p.out = (uint32_t*)d_out;
  p.zero = 0;
  fused_kernel<<<NCTA, NT, SMEM_BYTES, cudaStreamPerThread>>>(p, tm[0], tm[1]);
}
```

```cpp
#include <cuda_runtime.h>
#include <cuda.h>
#include <cuda_bf16.h>
#include <cuda_fp16.h>
#include <stdint.h>

namespace {

constexpr int NCTA = 128;
constexpr int NT = 512;
constexpr int DM = 576;
constexpr int FF = 4608;
constexpr int SPIN_MAX = 1 << 20;

__device__ uint4 g_U2[NCTA * DM * 2];
__device__ uint4 g_Y2[NCTA * DM * 2];
__device__ uint32_t g_ROW[2048 * 288];
__device__ uint4 g_P[NCTA * 576];
__device__ uint4 g_HS[576];
__device__ uint4 g_R[256];
__device__ uint32_t g_FLAG[NCTA];

#define TS(i)

constexpr int BOX = 192 * 80;
constexpr int OFF_G = 0;
constexpr int S_WG = 28672;
constexpr int OFF_S = 3 * BOX;
constexpr int S_UPBOX = 13312;
constexpr int EX_PLANE = 1600, EX_WARP = 3200;
constexpr int KT_WORDS = 1104;
constexpr int L3_ARR = 256;
constexpr int KT_BYTES = KT_WORDS * 4 + 4 * L3_ARR;
constexpr int OFF_KT = OFF_S + 4 * S_WG;
constexpr int UP_PAD = 28;
constexpr int UP_PLANE = (128 + UP_PAD) * 16;
constexpr int OFF_UP = OFF_KT + 5 * KT_BYTES;
constexpr int YT_PITCH = 1184;
constexpr int OFF_YT = OFF_UP + 5 * 2 * UP_PLANE;
constexpr int OFF_MISC = OFF_YT + 16 * YT_PITCH + 64;
constexpr int SMEM_BYTES = OFF_MISC + 512;
static_assert(OFF_S % 128 == 0 && OFF_KT % 16 == 0 && OFF_UP % 16 == 0 && OFF_YT % 16 == 0 && OFF_MISC % 16 == 0, "align");
static_assert(SMEM_BYTES <= 232448, "smem");
constexpr int MISC_MBAR = 0;
constexpr int MISC_SCALE = 16;
constexpr int MISC_WMAX = 48;
constexpr int MISC_CNT = 80;
constexpr int MISC_SEL = 96;
constexpr int MISC_EXP = 128;
constexpr int MISC_LN1 = 256;
constexpr int OFF_CAND = OFF_KT;
constexpr int OFF_XS = OFF_KT + 8192;
constexpr int OFF_RED = OFF_XS + 8 * 1168;
constexpr int OFF_ACT = OFF_RED + 7680;
constexpr int OFF_FIN = OFF_ACT + 768;
constexpr int OFF_ONES = OFF_KT + 4 * KT_BYTES + 64;

__device__ __forceinline__ uint32_t smem_u32(const void* p) { return (uint32_t)__cvta_generic_to_shared(p); }
__device__ __forceinline__ uint32_t lds32(uint32_t a) { uint32_t v; asm volatile("ld.shared.b32 %0, [%1];" : "=r"(v) : "r"(a) : "memory"); return v; }
__device__ __forceinline__ uint32_t lds16(uint32_t a) { uint16_t v; asm volatile("ld.shared.u16 %0, [%1];" : "=h"(v) : "r"(a) : "memory"); return v; }
__device__ __forceinline__ uint2 lds64(uint32_t a) { uint2 v; asm volatile("ld.shared.v2.b32 {%0,%1}, [%2];" : "=r"(v.x), "=r"(v.y) : "r"(a) : "memory"); return v; }
__device__ __forceinline__ uint4 lds128(uint32_t a) { uint4 v; asm volatile("ld.shared.v4.b32 {%0,%1,%2,%3}, [%4];" : "=r"(v.x), "=r"(v.y), "=r"(v.z), "=r"(v.w) : "r"(a) : "memory"); return v; }
__device__ __forceinline__ void sts16(uint32_t a, uint32_t v) { asm volatile("st.shared.u16 [%0], %1;" :: "r"(a), "h"((uint16_t)v) : "memory"); }
__device__ __forceinline__ void sts32(uint32_t a, uint32_t v) { asm volatile("st.shared.b32 [%0], %1;" :: "r"(a), "r"(v) : "memory"); }
__device__ __forceinline__ void sts64(uint32_t a, uint32_t x, uint32_t y) { asm volatile("st.shared.v2.b32 [%0], {%1,%2};" :: "r"(a), "r"(x), "r"(y) : "memory"); }
__device__ __forceinline__ void sts128(uint32_t a, uint32_t x, uint32_t y, uint32_t z, uint32_t w) { asm volatile("st.shared.v4.b32 [%0], {%1,%2,%3,%4};" :: "r"(a), "r"(x), "r"(y), "r"(z), "r"(w) : "memory"); }
__device__ __forceinline__ void ldsm4(uint32_t a, uint32_t& r0, uint32_t& r1, uint32_t& r2, uint32_t& r3) {
  asm volatile("ldmatrix.sync.aligned.m8n8.x4.shared.b16 {%0,%1,%2,%3}, [%4];" : "=r"(r0), "=r"(r1), "=r"(r2), "=r"(r3) : "r"(a) : "memory");
}
__device__ __forceinline__ void ldsm2(uint32_t a, uint32_t& r0, uint32_t& r1) {
  asm volatile("ldmatrix.sync.aligned.m8n8.x2.shared.b16 {%0,%1}, [%2];" : "=r"(r0), "=r"(r1) : "r"(a) : "memory");
}
__device__ __forceinline__ void ldsm4t(uint32_t a, uint32_t& r0, uint32_t& r1, uint32_t& r2, uint32_t& r3) {
  asm volatile("ldmatrix.sync.aligned.m8n8.x4.trans.shared.b16 {%0,%1,%2,%3}, [%4];" : "=r"(r0), "=r"(r1), "=r"(r2), "=r"(r3) : "r"(a) : "memory");
}
__device__ __forceinline__ void stsm4t(uint32_t a, uint32_t r0, uint32_t r1, uint32_t r2, uint32_t r3) {
  asm volatile("stmatrix.sync.aligned.m8n8.x4.trans.shared.b16 [%0], {%1,%2,%3,%4};" :: "r"(a), "r"(r0), "r"(r1), "r"(r2), "r"(r3) : "memory");
}
__device__ __forceinline__ uint4 ldr128(const void* p) {
  unsigned long long lo, hi;
  asm volatile("{ .reg .b128 t; ld.relaxed.gpu.global.b128 t, [%2]; mov.b128 {%0, %1}, t; }" : "=l"(lo), "=l"(hi) : "l"(p) : "memory");
  return make_uint4((uint32_t)lo, (uint32_t)(lo >> 32), (uint32_t)hi, (uint32_t)(hi >> 32));
}
__device__ __forceinline__ void str128(void* p, uint32_t x, uint32_t y, uint32_t z, uint32_t w) {
  asm volatile("{ .reg .b128 t; .reg .b64 lo, hi; mov.b64 lo, {%1,%2}; mov.b64 hi, {%3,%4}; mov.b128 t, {lo, hi}; st.relaxed.gpu.global.b128 [%0], t; }"
               :: "l"(p), "r"(x), "r"(y), "r"(z), "r"(w) : "memory");
}
__device__ __forceinline__ void str64(void* p, uint32_t x, uint32_t y) {
  asm volatile("{ .reg .b64 t; mov.b64 t, {%1,%2}; st.relaxed.gpu.global.b64 [%0], t; }" :: "l"(p), "r"(x), "r"(y) : "memory");
}
__device__ __forceinline__ uint32_t ldr32(const void* p) { uint32_t v; asm volatile("ld.relaxed.gpu.global.b32 %0, [%1];" : "=r"(v) : "l"(p) : "memory"); return v; }
__device__ __forceinline__ void str32(void* p, uint32_t v) { asm volatile("st.relaxed.gpu.global.b32 [%0], %1;" :: "l"(p), "r"(v) : "memory"); }
__device__ __forceinline__ void str16(void* p, uint32_t v) { asm volatile("st.relaxed.gpu.global.u16 [%0], %1;" :: "l"(p), "h"((uint16_t)v) : "memory"); }
__device__ __forceinline__ void fence_gpu() { asm volatile("fence.acq_rel.gpu;" ::: "memory"); }
__device__ __forceinline__ void bar_sync(int id, int n) { asm volatile("bar.sync %0, %1;" :: "r"(id), "r"(n) : "memory"); }
__device__ __forceinline__ void bar_arrive(int id, int n) { asm volatile("bar.arrive %0, %1;" :: "r"(id), "r"(n) : "memory"); }

__device__ __forceinline__ float bf_lo(uint32_t w) { return __uint_as_float(w << 16); }
__device__ __forceinline__ float bf_hi(uint32_t w) { return __uint_as_float(w & 0xFFFF0000u); }
__device__ __forceinline__ uint32_t pack_bf(float lo, float hi) { uint32_t r; asm("cvt.rn.bf16x2.f32 %0, %1, %2;" : "=r"(r) : "f"(hi), "f"(lo)); return r; }
__device__ __forceinline__ uint32_t pack_h(float lo, float hi) { uint32_t r; asm("cvt.rn.f16x2.f32 %0, %1, %2;" : "=r"(r) : "f"(hi), "f"(lo)); return r; }
__device__ __forceinline__ float bfr(float x) { return bf_lo(pack_bf(x, 0.f)); }
__device__ __forceinline__ uint32_t bf_sub2(uint32_t a, uint32_t b) { __nv_bfloat162 r = __hsub2(*(__nv_bfloat162*)&a, *(__nv_bfloat162*)&b); return *(uint32_t*)&r; }
__device__ __forceinline__ uint32_t bf_add2(uint32_t a, uint32_t b) { __nv_bfloat162 r = __hadd2(*(__nv_bfloat162*)&a, *(__nv_bfloat162*)&b); return *(uint32_t*)&r; }
__device__ __forceinline__ uint32_t bf_mul2(uint32_t a, uint32_t b) { __nv_bfloat162 r = __hmul2(*(__nv_bfloat162*)&a, *(__nv_bfloat162*)&b); return *(uint32_t*)&r; }
__device__ __forceinline__ float2 h2f(uint32_t w) { return __half22float2(*(__half2*)&w); }
__device__ __forceinline__ float ex2(float x) { float r; asm("ex2.approx.ftz.f32 %0, %1;" : "=f"(r) : "f"(x)); return r; }
__device__ __forceinline__ float warp_sum(float v) {
#pragma unroll
  for (int o = 16; o > 0; o >>= 1) v += __shfl_xor_sync(0xffffffffu, v, o);
  return v;
}
__device__ __forceinline__ void mma_f16_f32(float* d, uint32_t a0, uint32_t a1, uint32_t a2, uint32_t a3, uint32_t b0, uint32_t b1) {
  asm volatile("mma.sync.aligned.m16n8k16.row.col.f32.f16.f16.f32 {%0,%1,%2,%3}, {%4,%5,%6,%7}, {%8,%9}, {%0,%1,%2,%3};"
               : "+f"(d[0]), "+f"(d[1]), "+f"(d[2]), "+f"(d[3]) : "r"(a0), "r"(a1), "r"(a2), "r"(a3), "r"(b0), "r"(b1));
}
__device__ __forceinline__ void mma_f16_f16(uint32_t& d0, uint32_t& d1, uint32_t a0, uint32_t a1, uint32_t a2, uint32_t a3, uint32_t b0, uint32_t b1) {
  asm volatile("mma.sync.aligned.m16n8k16.row.col.f16.f16.f16.f16 {%0,%1}, {%2,%3,%4,%5}, {%6,%7}, {%0,%1};"
               : "+r"(d0), "+r"(d1) : "r"(a0), "r"(a1), "r"(a2), "r"(a3), "r"(b0), "r"(b1));
}
__device__ __forceinline__ void mma_bf16(float* d, uint32_t a0, uint32_t a1, uint32_t a2, uint32_t a3, uint32_t b0, uint32_t b1) {
  asm volatile("mma.sync.aligned.m16n8k16.row.col.f32.bf16.bf16.f32 {%0,%1,%2,%3}, {%4,%5,%6,%7}, {%8,%9}, {%0,%1,%2,%3};"
               : "+f"(d[0]), "+f"(d[1]), "+f"(d[2]), "+f"(d[3]) : "r"(a0), "r"(a1), "r"(a2), "r"(a3), "r"(b0), "r"(b1));
}
__device__ __forceinline__ void mma_bf16_k8(float* d, uint32_t a0, uint32_t a1, uint32_t b0) {
  asm volatile("mma.sync.aligned.m16n8k8.row.col.f32.bf16.bf16.f32 {%0,%1,%2,%3}, {%4,%5}, {%6}, {%0,%1,%2,%3};"
               : "+f"(d[0]), "+f"(d[1]), "+f"(d[2]), "+f"(d[3]) : "r"(a0), "r"(a1), "r"(b0));
}

__device__ __forceinline__ void wg_fence() { asm volatile("wgmma.fence.sync.aligned;" ::: "memory"); }
__device__ __forceinline__ void wg_commit() { asm volatile("wgmma.commit_group.sync.aligned;" ::: "memory"); }
template <int N> __device__ __forceinline__ void wg_wait() { asm volatile("wgmma.wait_group.sync.aligned %0;" :: "n"(N) : "memory"); }
template <int TB> __device__ __forceinline__ void wgmma32(float* d, const uint32_t* a, uint32_t dlo, uint32_t dhi) {
  asm volatile("{ .reg .b64 dd; mov.b64 dd, {%20, %21}; wgmma.mma_async.sync.aligned.m64n32k16.f32.f16.f16 "
               "{%0,%1,%2,%3,%4,%5,%6,%7,%8,%9,%10,%11,%12,%13,%14,%15}, {%16,%17,%18,%19}, dd, 1, 1, 1, %22; }"
               : "+f"(d[0]), "+f"(d[1]), "+f"(d[2]), "+f"(d[3]), "+f"(d[4]), "+f"(d[5]), "+f"(d[6]), "+f"(d[7]),
                 "+f"(d[8]), "+f"(d[9]), "+f"(d[10]), "+f"(d[11]), "+f"(d[12]), "+f"(d[13]), "+f"(d[14]), "+f"(d[15])
               : "r"(a[0]), "r"(a[1]), "r"(a[2]), "r"(a[3]), "r"(dlo), "r"(dhi), "n"(TB));
}
__device__ __forceinline__ void wgmma32_init(float* d, const uint32_t* a, uint32_t dlo, uint32_t dhi) {
  asm volatile("{ .reg .b64 dd; mov.b64 dd, {%20, %21}; wgmma.mma_async.sync.aligned.m64n32k16.f32.f16.f16 "
               "{%0,%1,%2,%3,%4,%5,%6,%7,%8,%9,%10,%11,%12,%13,%14,%15}, {%16,%17,%18,%19}, dd, 0, 1, 1, 0; }"
               : "=f"(d[0]), "=f"(d[1]), "=f"(d[2]), "=f"(d[3]), "=f"(d[4]), "=f"(d[5]), "=f"(d[6]), "=f"(d[7]),
                 "=f"(d[8]), "=f"(d[9]), "=f"(d[10]), "=f"(d[11]), "=f"(d[12]), "=f"(d[13]), "=f"(d[14]), "=f"(d[15])
               : "r"(a[0]), "r"(a[1]), "r"(a[2]), "r"(a[3]), "r"(dlo), "r"(dhi));
}

__device__ __forceinline__ void wgmma16_ss(float* d, uint32_t alo, uint32_t blo, uint32_t hi, int acc) {
  asm volatile("{ .reg .b64 da, db; .reg .pred q; setp.ne.b32 q, %11, 0; mov.b64 da, {%8, %10}; mov.b64 db, {%9, %10}; "
               "wgmma.mma_async.sync.aligned.m64n16k16.f32.f16.f16 {%0,%1,%2,%3,%4,%5,%6,%7}, da, db, q, 1, 1, 1, 1; }"
               : "+f"(d[0]), "+f"(d[1]), "+f"(d[2]), "+f"(d[3]), "+f"(d[4]), "+f"(d[5]), "+f"(d[6]), "+f"(d[7])
               : "r"(alo), "r"(blo), "r"(hi), "r"(acc));
}
__device__ __forceinline__ void tma_box(uint32_t dst, const CUtensorMap* tm, uint32_t mb, int x, int y) {
  asm volatile("cp.async.bulk.tensor.2d.shared::cluster.global.mbarrier::complete_tx::bytes [%0], [%1, {%3, %4}], [%2];"
               :: "r"(dst), "l"(tm), "r"(mb), "r"(x), "r"(y) : "memory");
}
__device__ __forceinline__ void l2_prefetch(const void* src, uint32_t bytes) {
  asm volatile("cp.async.bulk.prefetch.L2.global [%0], %1;" :: "l"(src), "r"(bytes) : "memory");
}
__device__ __forceinline__ uint32_t uni(uint32_t v) {
  uint32_t r; asm volatile("shfl.sync.idx.b32 %0, %1, 0, 0x1f, 0xffffffff;" : "=r"(r) : "r"(v)); return r;
}
__device__ __forceinline__ int fresh_tid() { int v; asm volatile("mov.u32 %0, %tid.x;" : "=r"(v)); return v; }

struct Params {
  const uint32_t* x;
  const uint16_t* ssm[6];
  const uint16_t* log_dt;
  const uint32_t* dskip;
  const uint32_t* w_r;
  const unsigned char* w_gate;
  const unsigned char* w_up;
  const unsigned char* w_down;
  uint32_t* out;
  uint32_t zero;
};

struct LnC { uint32_t m2, rh2, rl2; };
__device__ __forceinline__ float diag_sum(const float* d, int t) {
  float q = __shfl_sync(0xffffffffu, d[0], 9 * t) + __shfl_sync(0xffffffffu, d[1], 9 * t + 4);
  q += __shfl_xor_sync(0xffffffffu, q, 1);
  return q + __shfl_xor_sync(0xffffffffu, q, 2);
}
__device__ __forceinline__ LnC ln_stats(const uint32_t (&w)[9], int t) {
  const uint32_t ones = 0x3F803F80u;
  float d[4] = {0.f, 0.f, 0.f, 0.f};
  mma_bf16_k8(d, w[8], ones, w[8]);
#pragma unroll
  for (int i = 0; i < 8; i += 2) mma_bf16(d, w[i], ones, w[i + 1], ones, w[i], w[i + 1]);
  float s = d[2] + d[3];
  s += __shfl_xor_sync(0xffffffffu, s, 1);
  const float q = diag_sum(d, t);
  s += __shfl_xor_sync(0xffffffffu, s, 2);
  const float mean = s * (1.f / DM);
  const float var = fmaxf(fmaf(-mean, mean, q * (1.f / DM)), 0.f);
  float sd, r;
  asm("sqrt.approx.f32 %0, %1;" : "=f"(sd) : "f"(bfr(bfr(var) + 1e-5f)));
  asm("rcp.approx.f32 %0, %1;" : "=f"(r) : "f"(bfr(sd)));
  LnC c;
  c.m2 = pack_bf(mean, mean);
  c.rh2 = pack_bf(r, r);
  const float rl = r - bf_lo(c.rh2);
  c.rl2 = pack_bf(rl, rl);
  return c;
}
__device__ __forceinline__ uint32_t ln_apply(uint32_t w, const LnC& c) {
  const uint32_t d = bf_sub2(w, c.m2), lo = bf_mul2(d, c.rl2);
  __nv_bfloat162 r = __hfma2(*(const __nv_bfloat162*)&d, *(const __nv_bfloat162*)&c.rh2, *(const __nv_bfloat162*)&lo);
  return *(uint32_t*)&r;
}

__device__ __forceinline__ float2 cis(float mag_log2, float rev) {
  const float m = ex2(mag_log2), ang = rev * 6.283185307179586f;
  return make_float2(m * __cosf(ang), m * __sinf(ang));
}
__device__ __forceinline__ float2 csq(float2 a) { return make_float2(fmaf(a.x, a.x, -a.y * a.y), (a.x + a.x) * a.y); }
__device__ __forceinline__ float2 cmul(float2 a, float2 b) { return make_float2(fmaf(a.x, b.x, -a.y * b.y), fmaf(a.x, b.y, a.y * b.x)); }
__device__ __forceinline__ void pmul(uint32_t xr, uint32_t xi, uint32_t w, uint32_t& yr, uint32_t& yi) {
  const __half2 XR = *(__half2*)&xr, XI = *(__half2*)&xi, W = *(__half2*)&w;
  const __half2 a = __hfma2(__hneg2(XI), __high2half2(W), __hmul2(XR, __low2half2(W)));
  const __half2 b = __hfma2(XI, __low2half2(W), __hmul2(XR, __high2half2(W)));
  yr = *(const uint32_t*)&a; yi = *(const uint32_t*)&b;
}
__device__ __forceinline__ uint32_t pk(float2 a) { return pack_h(a.x, a.y); }
__device__ __forceinline__ uint32_t pkc(float2 a) { return pack_h(a.x, -a.y); }

__device__ __forceinline__ void kgen_issue(const uint32_t (&raw)[7], uint32_t sb, int wg, int wt, float (&acc)[8]) {
  const uint32_t scr = sb + OFF_S + wg * S_WG;
  const uint32_t misc = sb + OFF_MISC + MISC_EXP + wg * 16;
  const uint32_t dst = scr + (wt >> 3) * 256 + (wt & 7) * 16;
  const float dt = bfr(__expf(bf_lo(raw[6])));
  const float th = dt * bf_lo(raw[1]);
  const float br = dt * bf_lo(raw[2]), bi = dt * bf_lo(raw[3]);
  const float Cr = bf_lo(raw[4]), Ci = bf_lo(raw[5]);
  float2 c0 = make_float2(fmaf(Cr, br, -Ci * bi), fmaf(Cr, bi, Ci * br));
  {
    const uint32_t mx = __reduce_max_sync(0xffffffffu, __float_as_uint(fmaxf(fabsf(c0.x), fabsf(c0.y))));
    if ((wt & 31) == 0) sts32(misc + (wt >> 5) * 4, mx);
  }
  const float a2 = dt * bf_lo(raw[0]) * 1.4426950408889634f;
  const float rh = th * 0.15915494309189535f;
  const float rl = fmaf(th, (float)(0.15915494309189535 - (double)0.15915494309189535f), fmaf(th, 0.15915494309189535f, -rh));
  const float rf = rh - rintf(rh);
  const float2 z1 = cis(a2, rf + rl);
  const float p64 = rf * 64.f;
  const float2 z64 = cis(a2 * 64.f, fmaf(64.f, rl, p64 - rintf(p64)));
  const float2 z2 = csq(z1), z4 = csq(z2), z8 = csq(z4), z16 = csq(z8);
  const float2 z6 = cmul(z4, z2), z10 = cmul(z8, z2), z12 = cmul(z8, z4), z14 = cmul(z8, z6);
  uint32_t pr[4], pi[4], yr[4], yi[4];
  pr[0] = pack_h(1.f, z8.x);   pi[0] = pack_h(0.f, z8.y);
  pr[1] = pack_h(z4.x, z12.x); pi[1] = pack_h(z4.y, z12.y);
  pr[2] = pack_h(z2.x, z10.x); pi[2] = pack_h(z2.y, z10.y);
  pr[3] = pack_h(z6.x, z14.x); pi[3] = pack_h(z6.y, z14.y);
  sts128(dst, pr[0], pr[1], pr[2], pr[3]); sts128(dst + 128, pi[0], pi[1], pi[2], pi[3]);
  {
    const uint32_t w = pk(z1);
#pragma unroll
    for (int i = 0; i < 4; i++) pmul(pr[i], pi[i], w, yr[i], yi[i]);
    sts128(dst + 4096, yr[0], yr[1], yr[2], yr[3]); sts128(dst + 4096 + 128, yi[0], yi[1], yi[2], yi[3]);
  }
  const float2 z128 = csq(z64), z256 = csq(z128), z512 = csq(z256), z1024 = csq(z512), z2048 = csq(z1024);
  {
    const float k2048 = warp_sum(fmaf(c0.x, z2048.x, -c0.y * z2048.y));
    if ((wt & 31) == 0) sts32(misc + 64 + (wt >> 5) * 4, __float_as_uint(k2048));
  }
  {
    const uint32_t w = pk(z256);
#pragma unroll
    for (int i = 0; i < 4; i++) pmul(pr[i], pi[i], w, yr[i], yi[i]);
    sts128(dst + 8192, yr[0], yr[1], yr[2], yr[3]); sts128(dst + 8192 + 128, yi[0], yi[1], yi[2], yi[3]);
  }
  const float2 z768 = cmul(z512, z256);
  {
    const uint32_t wa = pk(z512), wb = pk(z768);
    pmul(pr[0], pi[0], wa, yr[0], yi[0]); pmul(pr[1], pi[1], wa, yr[1], yi[1]);
    pmul(pr[0], pi[0], wb, yr[2], yi[2]); pmul(pr[1], pi[1], wb, yr[3], yi[3]);
    sts128(dst + 12288, yr[0], yr[1], yr[2], yr[3]); sts128(dst + 12288 + 128, yi[0], yi[1], yi[2], yi[3]);
  }
  pmul(pr[0], pi[0], pk(z1024), yr[0], yi[0]);
  pmul(pr[0], pi[0], pk(cmul(z1024, z256)), yr[1], yi[1]);
  pmul(pr[0], pi[0], pk(cmul(z1024, z512)), yr[2], yi[2]);
  pmul(pr[0], pi[0], pk(cmul(z1024, z768)), yr[3], yi[3]);
  sts128(dst + 16384, yr[0], yr[1], yr[2], yr[3]); sts128(dst + 16384 + 128, yi[0], yi[1], yi[2], yi[3]);
  bar_sync(1 + wg, 128);
  {
    const uint4 e4 = lds128(misc);
    const int em = max(min((int)(max(max(e4.x, e4.y), max(e4.z, e4.w)) >> 23), 238), 16);
    const float sc = __uint_as_float((uint32_t)(127 + 4 + 127 - em) << 23);
    c0.x *= sc; c0.y *= sc;
  }
  const float2 c1 = cmul(c0, z16), c2 = cmul(c1, z16), c3 = cmul(c2, z16);
  pr[0] = pack_h(c0.x, c1.x); pi[0] = pack_h(-c0.y, -c1.y);
  pr[1] = pack_h(c2.x, c3.x); pi[1] = pack_h(-c2.y, -c3.y);
  {
    const uint32_t w = pkc(z64);
    pmul(pr[0], pi[0], w, pr[2], pi[2]); pmul(pr[1], pi[1], w, pr[3], pi[3]);
    sts128(dst + 20480, pr[0], pr[1], pr[2], pr[3]); sts128(dst + 20480 + 128, pi[0], pi[1], pi[2], pi[3]);
    const uint32_t wa = pkc(z128), wb = pkc(cmul(z128, z64));
    pmul(pr[0], pi[0], wa, yr[0], yi[0]); pmul(pr[1], pi[1], wa, yr[1], yi[1]);
    pmul(pr[0], pi[0], wb, yr[2], yi[2]); pmul(pr[1], pi[1], wb, yr[3], yi[3]);
    sts128(dst + 24576, yr[0], yr[1], yr[2], yr[3]); sts128(dst + 24576 + 128, yi[0], yi[1], yi[2], yi[3]);
  }
  asm volatile("fence.proxy.async.shared::cta;" ::: "memory");
  bar_sync(1 + wg, 128);
  const uint32_t alo = uni(((scr >> 4) & 0x3FFF) | (8u << 16));
  wg_fence();
#pragma unroll
  for (int ks = 0; ks < 16; ks++) wgmma16_ss(acc, alo + ks * 16, alo + (20480 >> 4) + ks * 16, 4096 >> 4, ks);
  wg_commit();
}

__device__ __forceinline__ void kgen_finish(float (&acc)[8], uint32_t sb, int slot, int wg, int wt) {
  const int w = wt >> 5, g = (wt >> 2) & 7, t = wt & 3;
  const uint32_t misc = sb + OFF_MISC + MISC_EXP + wg * 16;
  const uint32_t kc = sb + OFF_YT + wg * 1408 + 16;
  const uint32_t kt = sb + OFF_KT + slot * KT_BYTES;
  const int be = 8 * (g & 1) + 4 * ((g >> 1) & 1) + 2 * (g >> 2);
  const int a0 = w == 0 ? 2 * be : w == 1 ? 512 + be : 1024 + 2 * (g & 1) + 64 * (g >> 1);
  const int s0 = w == 0 ? 32 : w == 1 ? 16 : 4;
  const int a1 = w == 0 ? 2 * be + 2 : 768 + 4 * (g & 1) + (g & 2) + 128 * (g >> 2);
  const int s1 = w == 0 ? 32 : 8;
  wg_wait<0>();
  const float un = 1.f / 8192.f;
  if (w < 3) {
    const uint32_t p0 = kc + a0 + 2 * t * s0;
    const uint32_t h0 = pack_h(acc[0] * un, acc[1] * un), h1 = pack_h(acc[4] * un, acc[5] * un);
    sts16(p0, h0); sts16(p0 + s0, h0 >> 16); sts16(p0 + 8 * s0, h1); sts16(p0 + 9 * s0, h1 >> 16);
    if (w < 2) {
      const uint32_t p1 = kc + a1 + 2 * t * s1;
      const uint32_t h2 = pack_h(acc[2] * un, acc[3] * un), h3 = pack_h(acc[6] * un, acc[7] * un);
      sts16(p1, h2); sts16(p1 + s1, h2 >> 16); sts16(p1 + 8 * s1, h3); sts16(p1 + 9 * s1, h3 >> 16);
    }
  } else if (wt == 96) {
    const uint4 e4 = lds128(misc), k4 = lds128(misc + 64);
    const int em = max(min((int)(max(max(e4.x, e4.y), max(e4.z, e4.w)) >> 23), 238), 16);
    const float inv = __uint_as_float((uint32_t)(127 + 127 - 9 - em) << 23);
    const float kl = ((__uint_as_float(k4.x) + __uint_as_float(k4.y)) + (__uint_as_float(k4.z) + __uint_as_float(k4.w))) * inv;
    sts16(kc + 1280, pack_h(kl, kl));
    sts16(kc - 2, 0);
    sts32(sb + OFF_MISC + MISC_SCALE + slot * 4, (uint32_t)(em + 9) << 23);
  }
  bar_sync(1 + wg, 128);
  const uint32_t h01 = lds32(kc + wt * 4), km1 = lds16(kc + wt * 4 - 2);
  const uint32_t q1 = kc + 512 + wt * 2;
  const uint32_t p1 = lds16(q1 - 2), c1 = lds16(q1), n1 = lds16(q1 + 2), c2 = lds16(q1 + 256), n2 = lds16(q1 + 258), v3 = lds16(q1 + 514);
  const uint32_t wb = kt + 64;
  sts64(wb + wt * 8, __byte_perm(h01, km1, 0x5410), __byte_perm(h01, 0, 0x1032));
  const bool odd = wt & 1;
  const uint32_t lo1 = (odd || wt == 0) ? p1 : c1, hi1 = odd ? n1 : c1;
  sts64(wb + 1024 + wt * 8, __byte_perm(c1, lo1, 0x5410), __byte_perm(hi1, c1, 0x5410));
  const uint32_t tie = odd ? n2 : c2, cc = __byte_perm(c2, c2, 0x5410);
  sts128(wb + 2048 + wt * 16, cc, cc, __byte_perm(tie, c2, 0x5410), __byte_perm(n2, tie, 0x5410));
  const uint32_t arr = kt + KT_WORDS * 4 + (odd ? 0 : 2 * L3_ARR) + (wt >> 1) * 2;
  sts16(arr + 112, v3);
  sts16(arr + L3_ARR + 120, v3);
  if (wt == 127) {
    const uint32_t d = __byte_perm(n2, n2, 0x5410);
    sts128(wb + 4096, d, d, d, d); sts64(wb + 4096 + 16, d, d & 0xFFFF0000u);
  }
}

__device__ __forceinline__ void load_a(uint32_t (&a)[4], uint32_t kp, int j, uint32_t zero) {
  a[0] = lds32(kp + 256 * j); a[1] = lds32(kp + 256 * j + 32); a[2] = lds32(kp + 256 * j - 32);
  asm volatile("xor.b32 %0, %1, %2;" : "=r"(a[3]) : "r"(a[0]), "r"(zero));
}
__device__ __forceinline__ uint32_t band(int d, int lo, int hi) {
  return ((unsigned)(d - lo) <= (unsigned)(hi - lo) ? 0x3C00u : 0u) | ((unsigned)(d - 1 - lo) <= (unsigned)(hi - lo) ? 0x3C000000u : 0u);
}
__device__ __forceinline__ uint32_t hadd2u(uint32_t a, uint32_t b) { __half2 r = __hadd2(*(__half2*)&a, *(__half2*)&b); return *(uint32_t*)&r; }

template <int Q> __device__ __forceinline__ void epi_store(const float* acc, uint32_t st) {
#pragma unroll
  for (int h = 0; h < 2; h++)
    stsm4t(st + ((Q % 3) * 32 + 16 * h) * 16, pack_h(acc[8 * h], acc[8 * h + 1]), pack_h(acc[8 * h + 2], acc[8 * h + 3]),
           pack_h(acc[8 * h + 4], acc[8 * h + 5]), pack_h(acc[8 * h + 6], acc[8 * h + 7]));
}
template <int Q> __device__ __forceinline__ void epi_load(uint2 (&v)[4], uint32_t ld, int wt) {
#pragma unroll
  for (int ww = 0; ww < 4; ww++) {
    uint32_t a = ld + ww * (EX_WARP - 16) + (Q % 3) * 512;
    if (Q == 3 && ww > 0 && wt < 4 * ww) a += 96 * 16;
    v[ww] = lds64(a);
  }
}
template <int Q> __device__ __forceinline__ void epi_out(const uint2 (&v)[4], unsigned char* y, float scale) {
  const float2 a = h2f(hadd2u(hadd2u(v[0].x, v[1].x), hadd2u(v[2].x, v[3].x)));
  const float2 b = h2f(hadd2u(hadd2u(v[0].y, v[1].y), hadd2u(v[2].y, v[3].y)));
  str64(y + (size_t)Q * (32 * DM * 32), pack_bf(a.x * scale, a.y * scale), pack_bf(b.x * scale, b.y * scale));
}

__global__ void __launch_bounds__(NT, 1)
fused_kernel(const Params p, const __grid_constant__ CUtensorMap tm_gate, const __grid_constant__ CUtensorMap tm_up) {
  extern __shared__ __align__(1024) unsigned char smem[];
  const uint32_t sb = smem_u32(smem);
  const int c = blockIdx.x;
  const bool five = (c & 1) == 0;
  const int u0 = (c >> 1) * 9 + (five ? 0 : 4);
  uint32_t epoch;
  TS(0);
  {
    const int warp = (int)uni(threadIdx.x >> 5), wg = warp >> 2, tok = c * 16 + warp;
    const int tid = threadIdx.x, lane = tid & 31, wt = tid & 127, g = lane >> 2, t = lane & 3;
    uint32_t xw[9], raw[7];
#pragma unroll
    for (int i = 0; i < 9; i++) xw[i] = __ldg(p.x + tok * 288 + lane + 32 * i);
    const uint32_t flag0 = ldr32(&g_FLAG[c]);
#pragma unroll
    for (int i = 0; i < 6; i++) raw[i] = __ldg(p.ssm[i] + (4 * c + wg) * 128 + wt);
    raw[6] = __ldg(p.log_dt + 4 * c + wg);
    if (warp == 14) {
      if (lane < 18) asm volatile("prefetch.global.L2 [%0];" :: "l"((lane < 9 ? p.dskip : p.w_r - 288) + lane * 32));
      else if (lane < 20) {
        if (five) {
#pragma unroll
          for (int i = 0; i < 6; i++) asm volatile("prefetch.global.L2 [%0];" :: "l"(p.ssm[i] + (512 + (c >> 1)) * 128 + (lane & 1) * 64));
        }
      } else if (lane == 30) asm volatile("prefetch.global.L2 [%0];" :: "l"(p.log_dt + 512));
      else if (lane == 31) {
        const uint32_t mb = sb + OFF_MISC + MISC_MBAR;
        asm volatile("mbarrier.init.shared::cta.b64 [%0], 1;" :: "r"(mb) : "memory");
        asm volatile("mbarrier.arrive.expect_tx.shared::cta.b64 _, [%0], %1;" :: "r"(mb), "r"(6 * BOX) : "memory");
        sts32(sb + OFF_MISC + MISC_CNT, 0);
        asm volatile("fence.proxy.async.shared::cta;" ::: "memory");
        l2_prefetch(p.w_gate + (size_t)c * 41472, 41472);
      }
    }
    if (warp == 15) {
#pragma unroll
      for (int i = 0; i < 5; i++) if (lane + 32 * i < 144) sts128(sb + OFF_ONES + (lane + 32 * i) * 16, ~0u, ~0u, ~0u, ~0u);
      asm volatile("fence.proxy.async.shared::cta;" ::: "memory");
      __syncwarp();
      if (lane < 14 && (lane != 13 || c < 72)) {
        unsigned char* dst = lane < 8 ? (unsigned char*)g_Y2 + c * 18432 + lane * 2304 : lane < 12 ? (unsigned char*)g_P + c * 9216 + (lane - 8) * 2304
                           : lane == 12 ? (unsigned char*)g_R + c * 32 : (unsigned char*)g_HS + c * 128;
        const uint32_t bytes = lane < 12 ? 2304 : lane == 12 ? 32 : 128;
        asm volatile("cp.async.bulk.global.shared::cta.bulk_group [%0], [%1], %2;" :: "l"(dst), "r"(sb + OFF_ONES), "r"(bytes) : "memory");
        asm volatile("cp.async.bulk.commit_group;" ::: "memory");
      }
    }
    if (tid < 10 * UP_PAD) sts128(sb + OFF_UP + (tid / UP_PAD) * UP_PLANE + (tid % UP_PAD) * 16, 0, 0, 0, 0);
    if (tid < 5 * 84) {
      const int s = tid / 84, i = tid % 84;
      sts128(sb + OFF_KT + s * KT_BYTES + (i < 4 ? i * 16 : (16 + 1024) * 4 + (i - 4) * 16), 0, 0, 0, 0);
    }
    const uint32_t row = sb + OFF_YT + warp * YT_PITCH + (warp >> 3) * 64 + lane * 4;
    const int tr_tok = 8 * ((lane >> 1) & 1) + 2 * (lane >> 3) + (lane & 1);
    const uint32_t tr_addr = sb + OFF_YT + tr_tok * YT_PITCH + (tr_tok >> 3) * 64 + ((lane >> 2) & 1) * 16 + warp * 32;
    uint4* u2dst = &g_U2[c * DM * 2 + warp * 32 + (8 * (t >> 1) + g) * 2 + (t & 1)];
    TS(13);

    const LnC l1 = ln_stats(xw, t);
#pragma unroll
    for (int i = 0; i < 9; i++) { const uint32_t u = ln_apply(xw[i], l1); sts32(row + i * 128, pack_h(bf_lo(u), bf_hi(u))); }
    if (lane == 0) sts128(sb + OFF_MISC + MISC_LN1 + warp * 16, l1.m2, l1.rh2, l1.rl2, 0);
    epoch = __shfl_sync(0xffffffffu, flag0, 0) + 1u;
    __syncthreads();
#pragma unroll
    for (int r = 0; r < 3; r++) {
      if (r < 2 || warp < 4) {
        uint32_t r0, r1, r2, r3;
        ldsm4t(tr_addr + r * 512, r0, r1, r2, r3);
        str128(u2dst + r * 512, (r0 & ~1u) | (epoch & 1u), r1, r2, r3);
      }
    }
    if (warp == 15) asm volatile("cp.async.bulk.wait_group 0;" ::: "memory");
    __syncthreads();
    if (tid == 0) {
      str32(&g_FLAG[c], epoch);
      l2_prefetch(p.w_up + (size_t)c * 41472, 41472);
    }
    TS(1);

    const int nrep = (wg == 1 && five) ? 2 : 1;
#pragma unroll 1
    for (int rep = 0; rep < nrep; rep++) {
      float kacc[8];
      kgen_issue(raw, sb, wg, wt, kacc);
      TS(14);
      const int a = rep ? wt >> 1 : tid >> 3;
      const int pl = rep ? 8 + (wt & 1) : tid & 7;
      const uint4* src = &g_U2[a * (DM * 2) + (rep ? 1024 + (c & ~1) + (wt & 1) : 8 * c + pl)];
      if (rep == 0) {
        if (nrep == 2) {
#pragma unroll
          for (int i = 0; i < 6; i++) raw[i] = __ldg(p.ssm[i] + (512 + (c >> 1)) * 128 + wt);
          raw[6] = __ldg(p.log_dt + 512 + (c >> 1));
        }
#pragma unroll 1
        for (int it = 0; it < SPIN_MAX; it++) { const uint32_t f0 = ldr32(&g_FLAG[a]), f1 = ldr32(&g_FLAG[a + 64]); if (f0 == epoch && f1 == epoch) break; }
      }
      uint4 v0 = ldr128(src), v1 = ldr128(src + 64 * DM * 2);
      TS(15);
      kgen_finish(kacc, sb, rep ? 4 : wg, wg, wt);
      TS(2);
#pragma unroll 1
      for (int it = 0; it < SPIN_MAX && (((v0.x ^ epoch) | (v1.x ^ epoch)) & 1u); it++) { v0 = ldr128(src); v1 = ldr128(src + 64 * DM * 2); }
      const uint32_t ud = sb + OFF_UP + pl * UP_PLANE + (UP_PAD + a) * 16;
      sts128(ud, v0.x & ~1u, v0.y, v0.z, v0.w);
      sts128(ud + 1024, v1.x & ~1u, v1.y, v1.z, v1.w);
      asm volatile("fence.proxy.async.shared::cta;" ::: "memory");
      if (rep == 0) __syncthreads(); else bar_arrive(5, 256);
    }
  }
  TS(3);

  {
    const int tid = fresh_tid(), lane = tid & 31, wt = tid & 127;
    const int warp = (int)uni(tid >> 5), wg = warp >> 2, w = warp & 3;
    const uint32_t zero = p.zero;
    const uint32_t ex = sb + OFF_S + wg * S_WG;
    if (wt == 0 && wg != 1) {
      const int r = wg == 0 ? 0 : wg - 1;
      tma_box(sb + OFF_G + r * BOX, &tm_gate, sb + OFF_MISC + MISC_MBAR, u0 * 8, r * 192);
      tma_box(ex + S_UPBOX, &tm_up, sb + OFF_MISC + MISC_MBAR, u0 * 8, r * 192);
      if (wg == 3) l2_prefetch(p.w_down + (size_t)u0 * 8 * DM * 2, (five ? 4 : 5) * 8 * DM * 2);
    }
    if (lane < 8) sts128(ex + w * EX_WARP + (lane >> 2) * EX_PLANE + (lane & 3) * 16, 0, 0, 0, 0);
    const int nitem = (wg == 0 && five) ? 2 : 1;
#pragma unroll 1
    for (int item = 0; item < nitem; item++) {
      const int slot = item ? 4 : wg, ch = item ? 512 + (c >> 1) : 4 * c + wg;
      if (item) bar_sync(5, 256);
      const uint32_t kt = sb + OFF_KT + slot * KT_BYTES;
      const uint32_t kp = kt + (16 + 16 * w + (lane >> 2) - 2 * (lane & 3)) * 4;
      const uint32_t up = sb + OFF_UP + slot * 2 * UP_PLANE;
      uint32_t dlo = uni(((up >> 4) & 0x3FFF) + UP_PAD + ((uint32_t)(UP_PLANE >> 4) << 16));
      const uint32_t dhi = 8;
      float acc[4][16];
      uint32_t a0[4][4], a1[4][4];
#pragma unroll
      for (int j = 0; j < 4; j++) load_a(a0[j], kp, 8 + j, zero);
      wg_fence();
#pragma unroll
      for (int j = 0; j < 4; j++)
#pragma unroll
        for (int q = 1; q < 4; q++) {
          if (j == 0) wgmma32_init(acc[q], a0[j], dlo + 32 * q - 4 * (8 + j), dhi);
          else wgmma32<0>(acc[q], a0[j], dlo + 32 * q - 4 * (8 + j), dhi);
        }
      wg_commit();
#pragma unroll
      for (int j = 0; j < 4; j++) load_a(a1[j], kp, 12 + j, zero);
      uint32_t x9[4] = {0, 0, 0, 0}, x7[4] = {0, 0, 0, 0}, a16[4];
      {
        uint32_t b[2][5];
        const int ln = fresh_tid() & 31, mi = ln >> 3, d0 = (ln >> 2) - 2 * (ln & 3);
        const uint32_t rowb = up + (UP_PAD + 56 - 8 * (ln & 7) + w) * 16;
        const uint32_t ca = rowb + ((mi + 1) & 1) * UP_PLANE + ((mi - 3) >> 1) * 16;
        ldsm4(ca, b[0][0], b[0][1], b[0][2], b[0][3]);
        ldsm4(ca + 64, b[1][0], b[1][1], b[1][2], b[1][3]);
        ldsm2(rowb + UP_PLANE + (mi & 1) * 64, b[0][4], b[1][4]);
        wg_fence();
#pragma unroll
        for (int j = 0; j < 4; j++)
#pragma unroll
          for (int q = 1; q < 4; q++) wgmma32<0>(acc[q], a1[j], dlo + 32 * q - 4 * (12 + j), dhi);
        wg_commit();
        load_a(a16, kp, 16, zero);
        const uint32_t n24 = band(d0 + 24, 12, 20), n16 = band(d0 + 16, 12, 20), n8 = band(d0 + 8, 12, 20);
        const uint32_t s16 = band(d0 + 16, 5, 11), s8 = band(d0 + 8, 5, 11), s0 = band(d0, 5, 11);
#pragma unroll
        for (int tl = 0; tl < 2; tl++) {
          mma_f16_f16(x9[2 * tl], x9[2 * tl + 1], n24, 0u, n16, n24, b[tl][0], b[tl][1]);
          mma_f16_f16(x7[2 * tl], x7[2 * tl + 1], s16, 0u, s8, s16, b[tl][1], b[tl][2]);
        }
#pragma unroll
        for (int tl = 0; tl < 2; tl++) {
          mma_f16_f16(x9[2 * tl], x9[2 * tl + 1], n8, n16, 0u, n8, b[tl][2], b[tl][3]);
          mma_f16_f16(x7[2 * tl], x7[2 * tl + 1], s0, s8, 0u, s0, b[tl][3], b[tl][4]);
        }
      }
      wg_wait<1>();
#pragma unroll
      for (int j = 0; j < 4; j++) load_a(a0[j], kp, j, zero);
      {
        const uint32_t l3lo = uni((((kt + KT_WORDS * 4) >> 4) & 0x3FFF) + ((uint32_t)(L3_ARR >> 4) << 16)), l3hi = 1;
        dlo = uni(dlo);
        wg_fence();
#pragma unroll
        for (int q = 2; q < 4; q++) {
          wgmma32<0>(acc[q], a16, dlo + 32 * q - 64, dhi);
          wgmma32<1>(acc[q], x9, l3lo + 4 * (q - 2), l3hi);
          wgmma32<1>(acc[q], x7, l3lo + 4 * (q - 2) + (2 * L3_ARR >> 4), l3hi);
        }
        wg_commit();
      }
      wg_wait<1>();
#pragma unroll
      for (int j = 0; j < 4; j++) load_a(a1[j], kp, 4 + j, zero);
      dlo = uni(dlo);
      wg_fence();
#define WG2(Q, A, J) wgmma32<0>(acc[Q], A[(J) & 3], dlo + 32 * Q - 4 * (J), dhi); wgmma32<0>(acc[Q], A[((J) + 1) & 3], dlo + 32 * Q - 4 * (J) - 4, dhi);
      WG2(1, a0, 0) WG2(1, a0, 2) WG2(1, a1, 4) WG2(1, a1, 6)
      wg_commit();
      const float scale = __uint_as_float(lds32(sb + OFF_MISC + MISC_SCALE + slot * 4));
      const int et = fresh_tid() & 127;
      unsigned char* y = (unsigned char*)g_Y2 + ((et >> 2) * DM + ch) * 32 + (et & 3) * 8;
      const uint32_t est = ex + w * EX_WARP + ((et >> 3) & 1) * EX_PLANE + (4 + (et & 16) / 2 + (et & 7)) * 16;
      const uint32_t eld = ex + ((et >> 1) & 1) * EX_PLANE + (4 + (et >> 2)) * 16 + (et & 1) * 8;
      uint2 ev[4];
      wg_wait<1>(); wg_fence();
      wgmma32_init(acc[0], a0[0], dlo, dhi); wgmma32<0>(acc[0], a0[1], dlo - 4, dhi);
      wg_commit(); wg_wait<1>();
      epi_store<1>(acc[1], est); wg_fence();
      WG2(0, a0, 2) WG2(0, a1, 4) WG2(0, a1, 6)
      wg_commit();
      WG2(2, a0, 0)
      wg_commit(); wg_wait<1>();
      epi_store<0>(acc[0], est); wg_fence();
      WG2(2, a0, 2)
      bar_sync(1 + wg, 128); epi_load<0>(ev, eld, 0);
      WG2(2, a1, 4)
      epi_out<0>(ev, y, scale); epi_load<1>(ev, eld, 0);
      WG2(2, a1, 6)
      wg_commit();
      epi_out<1>(ev, y, scale);
      WG2(3, a0, 0)
      wg_commit(); wg_wait<1>();
      epi_store<2>(acc[2], est); wg_fence();
      WG2(3, a0, 2)
      bar_sync(1 + wg, 128); epi_load<2>(ev, eld, 0);
      WG2(3, a1, 4)
      epi_out<2>(ev, y, scale);
      WG2(3, a1, 6)
      wg_commit();
#undef WG2
      wg_wait<0>();
      epi_store<3>(acc[3], est);
      bar_sync(1 + wg, 128);
      epi_load<3>(ev, eld, fresh_tid() & 127);
      epi_out<3>(ev, y, scale);
    }
  }
  TS(4);

  const int tid = fresh_tid(), lane = tid & 31, g = lane >> 2, t = lane & 3;
  const int warp = (int)uni(tid >> 5), wg = warp >> 2, tok = c * 16 + warp;
  const uint32_t stash = sb + OFF_S + wg * S_WG + (warp & 3) * 2304 + lane * 8;
  {
    uint32_t hw[9], lw[9], ds[9], wr[9];
#pragma unroll
    for (int i = 0; i < 9; i++) { hw[i] = __ldg(p.x + tok * 288 + lane + 32 * i); ds[i] = __ldg(p.dskip + lane + 32 * i); wr[i] = __ldg(p.w_r + lane + 32 * i); }
    const uint4* ysrc = &g_Y2[c * DM * 2 + warp * 32 + (8 * (t >> 1) + g) * 2 + (t & 1)];
    uint4 v[3];
#pragma unroll
    for (int r = 0; r < 3; r++) if (r < 2 || warp < 4) v[r] = ldr128(ysrc + r * 512);
    {
      const uint4 q = lds128(sb + OFF_MISC + MISC_LN1 + warp * 16);
      LnC l1; l1.m2 = q.x; l1.rh2 = q.y; l1.rl2 = q.z;
#pragma unroll
      for (int i = 0; i < 9; i++) ds[i] = bf_mul2(ln_apply(hw[i], l1), ds[i]);
    }
    const int tr_tok = 8 * ((lane >> 1) & 1) + 2 * (lane >> 3) + (lane & 1);
    const uint32_t tr_addr = sb + OFF_YT + tr_tok * YT_PITCH + (tr_tok >> 3) * 64 + ((lane >> 2) & 1) * 16 + warp * 32;
    TS(5);
#pragma unroll
    for (int r = 0; r < 3; r++)
      if (r < 2 || warp < 4) {
#pragma unroll 1
        for (int it = 0; it < SPIN_MAX && (v[r].x == ~0u || v[r].z == ~0u); it++) v[r] = ldr128(ysrc + r * 512);
        __syncwarp();
        stsm4t(tr_addr + r * 512, v[r].x, v[r].y, v[r].z, v[r].w);
      }
    __syncthreads();
    TS(6);
    const uint32_t row = sb + OFF_YT + warp * YT_PITCH + (warp >> 3) * 64 + lane * 4;
#pragma unroll
    for (int i = 0; i < 9; i++) hw[i] = bf_add2(hw[i], bf_add2(lds32(row + i * 128), ds[i]));
    const LnC l2 = ln_stats(hw, t);
#pragma unroll
    for (int i = 0; i < 9; i++) lw[i] = ln_apply(hw[i], l2);
    float d[4] = {0.f, 0.f, 0.f, 0.f};
    mma_bf16_k8(d, lw[8], 0u, wr[8]);
#pragma unroll
    for (int i = 0; i < 8; i += 2) mma_bf16(d, lw[i], 0u, lw[i + 1], 0u, wr[i], wr[i + 1]);
    const float r = diag_sum(d, t);
    if (lane == 0) {
      const uint32_t b = pack_bf(r, 0.f) & 0xFFFFu;
      const uint32_t key = (b & 0x8000u) ? (~b & 0xFFFFu) : (b | 0x8000u);
      str16((uint16_t*)g_R + tok, min(key, 0xFFFEu));
    }
    uint32_t* rdst = &g_ROW[tok * 288 + lane];
#pragma unroll
    for (int i = 0; i < 9; i++) str32(rdst + 32 * i, (pack_h(bf_lo(lw[i]), bf_hi(lw[i])) & ~1u) | (epoch & 1u));
#pragma unroll
    for (int i = 0; i < 9; i++) sts64(stash + i * 256, bf_add2(hw[i], lw[i]), hw[i]);
  }
  TS(7);
  uint4 rv = make_uint4(~0u, 0, 0, 0);
  uint32_t wd[5][8];
  if (warp < 9) {
    const unsigned char* src = p.w_down + (size_t)(u0 * 8 + 2 * t) * (DM * 2) + warp * 128 + g * 16;
#pragma unroll
    for (int q = 0; q < 5; q++) {
      uint4 r0 = make_uint4(0, 0, 0, 0), r1 = r0;
      if (q < 4 || !five) { r0 = __ldg((const uint4*)(src + q * 8 * DM * 2)); r1 = __ldg((const uint4*)(src + (q * 8 + 1) * DM * 2)); }
      wd[q][0] = r0.x; wd[q][1] = r1.x; wd[q][2] = r0.y; wd[q][3] = r1.y; wd[q][4] = r0.z; wd[q][5] = r1.z; wd[q][6] = r0.w; wd[q][7] = r1.w;
    }
  }
  const int fu = warp / 3, fk = warp - fu * 3;
  uint32_t wa[12][4];
  {
    const uint32_t mb = sb + OFF_MISC + MISC_MBAR;
#pragma unroll 1
    for (int it = 0; it < SPIN_MAX; it++) {
      uint32_t ok;
      asm volatile("{ .reg .pred q; mbarrier.try_wait.parity.shared::cta.b64 q, [%1], 0; selp.u32 %0, 1, 0, q; }" : "=r"(ok) : "r"(mb) : "memory");
      if (ok) break;
    }
    if (tid >= 256) rv = ldr128(&g_R[tid - 256]);
    if (warp < 15) {
      const uint32_t base = sb + ((lane & 8) ? OFF_S + (fk ? fk + 1 : 0) * S_WG + S_UPBOX : OFF_G + fk * BOX) + ((lane >> 4) * 8 + (lane & 7)) * 80 + fu * 16;
#pragma unroll
      for (int k = 0; k < 12; k++) ldsm4t(base + k * 16 * 80, wa[k][0], wa[k][1], wa[k][2], wa[k][3]);
    }
  }
  TS(16);

  if (tid >= 256) {
    uint32_t mx;
#pragma unroll 1
    for (int it = 0; it < SPIN_MAX; it++) {
      mx = __vmaxu2(__vmaxu2(rv.x, rv.y), __vmaxu2(rv.z, rv.w));
      mx = max(mx & 0xFFFFu, mx >> 16);
      if (mx != 0xFFFFu) break;
      rv = ldr128(&g_R[tid - 256]);
    }
    __syncwarp();
    const uint32_t wm = __reduce_max_sync(0xffffffffu, mx);
    if (lane == 0) sts32(sb + OFF_MISC + MISC_WMAX + (warp - 8) * 4, wm);
    bar_sync(6, 256);
    const uint32_t tau = __reduce_min_sync(0xffffffffu, lds32(sb + OFF_MISC + MISC_WMAX + (lane & 7) * 4));
    if (mx >= tau) {
      const uint32_t ib = 2047 - (tid - 256) * 8, one = p.zero + 1;
      uint32_t key[8], pos[8];
      key[0] = rv.x << 16; key[1] = rv.x & 0xFFFF0000u; key[2] = rv.y << 16; key[3] = rv.y & 0xFFFF0000u;
      key[4] = rv.z << 16; key[5] = rv.z & 0xFFFF0000u; key[6] = rv.w << 16; key[7] = rv.w & 0xFFFF0000u;
#pragma unroll
      for (int i = 0; i < 8; i++)
        asm volatile("{ .reg .pred q; setp.ge.u32 q, %2, %3; @q atom.shared.add.u32 %0, [%1], %4; }"
                     : "=r"(pos[i]) : "r"(sb + OFF_MISC + MISC_CNT), "r"(key[i]), "r"(tau << 16), "r"(one) : "memory");
#pragma unroll
      for (int i = 0; i < 8; i++) if (key[i] >= (tau << 16)) sts32(sb + OFF_CAND + pos[i] * 4, key[i] | (ib - i));
    }
  } else if (warp < 8) {
#pragma unroll
    for (int q = 0; q < 5; q++)
#pragma unroll
      for (int j = 0; j < 4; j++) { const uint32_t a = wd[q][2 * j], b = wd[q][2 * j + 1]; wd[q][2 * j] = __byte_perm(a, b, 0x5410); wd[q][2 * j + 1] = __byte_perm(a, b, 0x7632); }
  }
  __syncthreads();
  TS(8);
  {
    const int n = (int)lds32(sb + OFF_MISC + MISC_CNT);
#pragma unroll 1
    for (int j = warp; j < n; j += 16) {
      const uint32_t mine = lds32(sb + OFF_CAND + j * 4);
      int rank = 0;
#pragma unroll 1
      for (int b = 0; b < n; b += 32) rank += __popc(__ballot_sync(0xffffffffu, b + lane < n && lds32(sb + OFF_CAND + (b + lane) * 4) > mine));
      if (rank < 8) {
        const uint4* src = (const uint4*)(g_ROW + (2047 - (int)(mine & 0xFFFFu)) * 288) + lane;
        uint4 v[3];
#pragma unroll
        for (int r = 0; r < 3; r++) if (r < 2 || lane < 8) v[r] = ldr128(src + 32 * r);
        if (lane == 0) sts32(sb + OFF_MISC + MISC_SEL + rank * 4, mine);
#pragma unroll
        for (int r = 0; r < 3; r++)
          if (r < 2 || lane < 8) {
#pragma unroll 1
            for (int it = 0; it < SPIN_MAX && (((v[r].x ^ epoch) | (v[r].y ^ epoch) | (v[r].z ^ epoch) | (v[r].w ^ epoch)) & 1u); it++) v[r] = ldr128(src + 32 * r);
            const float2 f0 = h2f(v[r].x & ~1u), f1 = h2f(v[r].y & ~1u), f2 = h2f(v[r].z & ~1u), f3 = h2f(v[r].w & ~1u);
            sts128(sb + OFF_XS + rank * 1168 + (lane + 32 * r) * 16, pack_bf(f0.x, f0.y), pack_bf(f1.x, f1.y), pack_bf(f2.x, f2.y), pack_bf(f3.x, f3.y));
          }
      }
    }
    if (warp == 8) {
#pragma unroll
      for (int q = 0; q < 5; q++)
#pragma unroll
        for (int j = 0; j < 4; j++) { const uint32_t a = wd[q][2 * j], b = wd[q][2 * j + 1]; wd[q][2 * j] = __byte_perm(a, b, 0x5410); wd[q][2 * j + 1] = __byte_perm(a, b, 0x7632); }
    }
  }
  __syncthreads();
  TS(9);

  if (warp < 15) {
    float d0[4] = {0.f, 0.f, 0.f, 0.f}, d1[4] = {0.f, 0.f, 0.f, 0.f};
    const uint32_t xb = sb + OFF_XS + (lane & 7) * 1168 + (fk * 24 + (lane >> 3)) * 16;
#pragma unroll
    for (int k = 0; k < 12; k += 2) {
      uint32_t b0, b1, b2, b3;
      ldsm4(xb + k * 32, b0, b1, b2, b3);
      mma_bf16(d0, wa[k][0], wa[k][1], wa[k][2], wa[k][3], b0, b1);
      mma_bf16(d1, wa[k + 1][0], wa[k + 1][1], wa[k + 1][2], wa[k + 1][3], b2, b3);
    }
    sts128(sb + OFF_RED + warp * 512 + lane * 16, __float_as_uint(d0[0] + d1[0]), __float_as_uint(d0[1] + d1[1]), __float_as_uint(d0[2] + d1[2]), __float_as_uint(d0[3] + d1[3]));
  }
  const uint32_t selkey = lds32(sb + OFF_MISC + MISC_SEL + (lane & 7) * 4);
  __syncthreads();
  if (warp >= 11) {
    const uint32_t rb = sb + OFF_RED + (warp - 11) * 1536 + lane * 16;
    const uint4 pa = lds128(rb), pb = lds128(rb + 512), pc = lds128(rb + 1024);
    const float ga = bfr(__uint_as_float(pa.x) + __uint_as_float(pb.x) + __uint_as_float(pc.x));
    const float gb = bfr(__uint_as_float(pa.y) + __uint_as_float(pb.y) + __uint_as_float(pc.y));
    const uint32_t uu = pack_bf(__uint_as_float(pa.z) + __uint_as_float(pb.z) + __uint_as_float(pc.z), __uint_as_float(pa.w) + __uint_as_float(pb.w) + __uint_as_float(pc.w));
    float ra, rb2;
    asm("rcp.approx.f32 %0, %1;" : "=f"(ra) : "f"(1.f + ex2(ga * -1.4426950408889634f)));
    asm("rcp.approx.f32 %0, %1;" : "=f"(rb2) : "f"(1.f + ex2(gb * -1.4426950408889634f)));
    const uint32_t act = bf_mul2(pack_bf(ga * ra, gb * rb2), uu);
    sts32(sb + OFF_ACT + (warp - 11) * 128 + lane * 4, (warp == 15 && five) ? 0u : act);
    bar_arrive(7, 14 * 32);
  } else if (warp < 9) {
    bar_sync(7, 14 * 32);
    uint32_t b0, b1, b2, b3, b4;
    ldsm4t(sb + OFF_ACT + lane * 16, b0, b1, b2, b3);
    asm volatile("ldmatrix.sync.aligned.m8n8.x1.trans.shared.b16 {%0}, [%1];" : "=r"(b4) : "r"(sb + OFF_ACT + 512 + (lane & 7) * 16) : "memory");
    float y[4][4];
#pragma unroll
    for (int j = 0; j < 4; j++) {
      y[j][0] = y[j][1] = y[j][2] = y[j][3] = 0.f;
      mma_bf16(y[j], wd[0][2 * j], wd[0][2 * j + 1], wd[1][2 * j], wd[1][2 * j + 1], b0, b1);
    }
#pragma unroll
    for (int j = 0; j < 4; j++) mma_bf16(y[j], wd[2][2 * j], wd[2][2 * j + 1], wd[3][2 * j], wd[3][2 * j + 1], b2, b3);
#pragma unroll
    for (int j = 0; j < 4; j++) mma_bf16_k8(y[j], wd[4][2 * j], wd[4][2 * j + 1], b4);
    uint4* dst = &g_P[c * 576 + (warp * 8 + g) * 8 + t];
    str128(dst, pack_bf(y[0][0], y[0][1]), pack_bf(y[0][2], y[0][3]), pack_bf(y[1][0], y[1][1]), pack_bf(y[1][2], y[1][3]));
    str128(dst + 4, pack_bf(y[2][0], y[2][1]), pack_bf(y[2][2], y[2][3]), pack_bf(y[3][0], y[3][1]), pack_bf(y[3][2], y[3][3]));
  }
  TS(10);
  {
    const uint32_t hit = __ballot_sync(0xffffffffu, (int)(selkey & 0xFFFFu) == 2047 - tok);
    uint32_t* o = (hit ? (uint32_t*)g_HS + (__ffs(hit) - 1) * 288 : p.out + tok * 288) + lane;
    const uint32_t sa = stash + (hit ? 4 : 0);
#pragma unroll
    for (int i = 0; i < 9; i++) str32(o + 32 * i, lds32(sa + i * 256));
  }

  if (c < 72) {
    const uint4* src = &g_P[(warp * 4 + t) * 576 + c * 8 + g];
    uint4 v0 = ldr128(src), v1 = ldr128(src + 64 * 576);
    const uint32_t* hsrc = (const uint32_t*)g_HS + g * 288 + c * 4 + t;
    uint32_t hv = 0;
    if (warp == 0) hv = ldr32(hsrc);
    const uint32_t sel = (g & 1) ? 0x3F800000u : 0x00003F80u;
#pragma unroll 1
    for (int it = 0; it < SPIN_MAX && (v0.x == ~0u || v1.x == ~0u); it++) { v0 = ldr128(src); v1 = ldr128(src + 64 * 576); }
    __syncwarp();
    float d[4] = {0.f, 0.f, 0.f, 0.f};
    {
      const uint32_t s0 = (g >> 1) == 0 ? sel : 0u, s1 = (g >> 1) == 1 ? sel : 0u, s2 = (g >> 1) == 2 ? sel : 0u, s3 = (g >> 1) == 3 ? sel : 0u;
      mma_bf16(d, s0, 0u, s0, 0u, v0.x, v1.x); mma_bf16(d, s1, 0u, s1, 0u, v0.y, v1.y);
      mma_bf16(d, s2, 0u, s2, 0u, v0.z, v1.z); mma_bf16(d, s3, 0u, s3, 0u, v0.w, v1.w);
    }
    {
      const uint32_t fb = sb + OFF_FIN + warp * 256 + ((4 * (t & 1) + (g & 1)) * 8 + 4 * (t >> 1) + (g >> 1)) * 4;
      sts32(fb, __float_as_uint(d[0])); sts32(fb + 64, __float_as_uint(d[1]));
    }
    __syncthreads();
    TS(11);
    if (warp == 0) {
      float s0 = 0.f, s1 = 0.f;
#pragma unroll
      for (int i = 0; i < 16; i++) { const uint2 q = lds64(sb + OFF_FIN + i * 256 + lane * 8); s0 += __uint_as_float(q.x); s1 += __uint_as_float(q.y); }
      const uint32_t key = __shfl_sync(0xffffffffu, selkey, g);
      const uint32_t k16 = key >> 16;
      const float r = bf_lo((k16 & 0x8000u) ? (k16 & 0x7FFFu) : (~k16 & 0xFFFFu));
      float rs;
      asm("rcp.approx.f32 %0, %1;" : "=f"(rs) : "f"(1.f + ex2(r * -1.4426950408889634f)));
      const uint32_t upd = bf_mul2(pack_bf(s0, s1), pack_bf(rs, rs));
      const uint32_t ln = lds32(sb + OFF_XS + g * 1168 + c * 16 + t * 4);
#pragma unroll 1
      for (int it = 0; it < SPIN_MAX && hv == ~0u; it++) hv = ldr32(hsrc);
      p.out[(2047 - (int)(key & 0xFFFFu)) * 288 + c * 4 + t] = bf_add2(hv, bf_add2(ln, upd));
    }
  }
  TS(12);
}

typedef CUresult (*EncodeFn)(CUtensorMap*, CUtensorMapDataType, cuuint32_t, void*, const cuuint64_t*, const cuuint64_t*, const cuuint32_t*,
                             const cuuint32_t*, CUtensorMapInterleave, CUtensorMapSwizzle, CUtensorMapL2promotion, CUtensorMapFloatOOBfill);

}

extern "C" void kernel_launch(void* const* d_in, const int* in_sizes, int n_in, void* d_out, int out_size) {
  (void)in_sizes; (void)n_in; (void)out_size;
  static EncodeFn enc = nullptr;
  if (!enc) {
    void* fn = nullptr;
    cudaDriverEntryPointQueryResult qr;
    cudaGetDriverEntryPoint("cuTensorMapEncodeTiled", &fn, cudaEnableDefault, &qr);
    enc = (EncodeFn)fn;
    cudaFuncSetAttribute(fused_kernel, cudaFuncAttributeMaxDynamicSharedMemorySize, SMEM_BYTES);
  }
  CUtensorMap tm[2];
  for (int i = 0; i < 2; i++) {
    cuuint64_t gd[2] = {FF, DM};
    cuuint64_t gs[1] = {FF * 2};
    cuuint32_t bx[2] = {40, 192};
    cuuint32_t es[2] = {1, 1};
    enc(&tm[i], CU_TENSOR_MAP_DATA_TYPE_BFLOAT16, 2, d_in[11 + i], gd, gs, bx, es, CU_TENSOR_MAP_INTERLEAVE_NONE, CU_TENSOR_MAP_SWIZZLE_NONE,
        CU_TENSOR_MAP_L2_PROMOTION_L2_128B, CU_TENSOR_MAP_FLOAT_OOB_FILL_NONE);
  }
  Params p;
  p.x = (const uint32_t*)d_in[0];
  for (int i = 0; i < 6; i++) p.ssm[i] = (const uint16_t*)d_in[1 + i];
  p.log_dt = (const uint16_t*)d_in[7];
  p.dskip = (const uint32_t*)d_in[8];
  p.w_r = (const uint32_t*)d_in[10];
  p.w_gate = (const unsigned char*)d_in[11];
  p.w_up = (const unsigned char*)d_in[12];
  p.w_down = (const unsigned char*)d_in[13];
  p.out = (uint32_t*)d_out;
  p.zero = 0;
  fused_kernel<<<NCTA, NT, SMEM_BYTES, cudaStreamPerThread>>>(p, tm[0], tm[1]);
}
```

```cpp
#include <cuda_runtime.h>
#include <cuda.h>
#include <cuda_bf16.h>
#include <cuda_fp16.h>
#include <stdint.h>
#include <stddef.h>

namespace {

constexpr int NCTA = 128;
constexpr int NT = 512;
constexpr int DM = 576;
constexpr int FF = 4608;
constexpr int SPIN_MAX = 1 << 20;

struct Scratch {
  uint4 U2[NCTA * DM * 2];
  uint4 Y2[NCTA * DM * 2];
  uint32_t ROW[2048 * 288];
  uint4 P[NCTA * 576];
  uint4 HS[576];
  uint4 R[256];
  uint32_t FLAG[NCTA];
};
__device__ Scratch g_S;

#define TS(i)

constexpr int SB = 1024;
constexpr int BOX = 192 * 80;
constexpr int OFF_G = SB;
constexpr int OFF_W = OFF_G + 3 * BOX;
constexpr int W_UPBOX = 13312;
constexpr int EX_PLANE = 1600, EX_WARP = 3200;
constexpr int KT_WORDS = 1104;
constexpr int L3_ARR = 256;
constexpr int W_KT = 28672;
constexpr int W_L3 = W_KT + KT_WORDS * 4;
constexpr int UP_PAD = 28;
constexpr int UP_PLANE = (128 + UP_PAD) * 16;
constexpr int W_UP = W_L3 + 4 * L3_ARR;
constexpr int W_KC = W_UP + 2 * UP_PLANE;
constexpr int W_MISC = W_KC + 1344;
constexpr int W_BYTES = 40576;
static_assert(W_MISC + 64 <= W_BYTES && W_BYTES % 128 == 0, "wg block");
constexpr int YT_PITCH = 1184;
constexpr int OFF_YT = OFF_W + 4 * W_BYTES;
constexpr int OFF_BAND = OFF_YT + 16 * YT_PITCH + 64;
constexpr int OFF_ATAB = OFF_BAND + 2048;
constexpr int OFF_MISC = OFF_ATAB + 2048;
constexpr int SMEM_BYTES = OFF_MISC + 512 - SB;
static_assert(OFF_W % 128 == 0 && OFF_YT % 16 == 0 && OFF_MISC % 16 == 0, "align");
static_assert(SMEM_BYTES <= 232448, "smem");
constexpr int MISC_MBAR = OFF_MISC;
constexpr int MISC_WMAX = OFF_MISC + 48;
constexpr int MISC_CNT = OFF_MISC + 80;
constexpr int MISC_SEL = OFF_MISC + 96;
constexpr int MISC_LN1 = OFF_MISC + 256;
constexpr int OFF_XS = OFF_W + W_UPBOX;
constexpr int OFF_RED = OFF_XS + 8 * 1168;
constexpr int OFF_ACT = OFF_RED + 7680;
constexpr int OFF_FIN = OFF_ACT + 768;
constexpr int OFF_CAND = OFF_W + W_BYTES + W_KT;
static_assert(OFF_FIN + 4096 <= OFF_W + W_BYTES && W_KT + 8192 <= W_BYTES, "alias");
constexpr int OFF_ONES = OFF_G;

__device__ __forceinline__ uint32_t smem_u32(const void* p) { return (uint32_t)__cvta_generic_to_shared(p); }
__device__ __forceinline__ uint32_t lds32(uint32_t a) { uint32_t v; asm volatile("ld.shared.b32 %0, [%1];" : "=r"(v) : "r"(a) : "memory"); return v; }
__device__ __forceinline__ uint32_t lds16(uint32_t a) { uint16_t v; asm volatile("ld.shared.u16 %0, [%1];" : "=h"(v) : "r"(a) : "memory"); return v; }
__device__ __forceinline__ uint2 lds64(uint32_t a) { uint2 v; asm volatile("ld.shared.v2.b32 {%0,%1}, [%2];" : "=r"(v.x), "=r"(v.y) : "r"(a) : "memory"); return v; }
__device__ __forceinline__ uint4 lds128(uint32_t a) { uint4 v; asm volatile("ld.shared.v4.b32 {%0,%1,%2,%3}, [%4];" : "=r"(v.x), "=r"(v.y), "=r"(v.z), "=r"(v.w) : "r"(a) : "memory"); return v; }
__device__ __forceinline__ void sts16(uint32_t a, uint32_t v) { asm volatile("st.shared.u16 [%0], %1;" :: "r"(a), "h"((uint16_t)v) : "memory"); }
__device__ __forceinline__ void sts32(uint32_t a, uint32_t v) { asm volatile("st.shared.b32 [%0], %1;" :: "r"(a), "r"(v) : "memory"); }
__device__ __forceinline__ void sts64(uint32_t a, uint32_t x, uint32_t y) { asm volatile("st.shared.v2.b32 [%0], {%1,%2};" :: "r"(a), "r"(x), "r"(y) : "memory"); }
__device__ __forceinline__ void sts128(uint32_t a, uint32_t x, uint32_t y, uint32_t z, uint32_t w) { asm volatile("st.shared.v4.b32 [%0], {%1,%2,%3,%4};" :: "r"(a), "r"(x), "r"(y), "r"(z), "r"(w) : "memory"); }
__device__ __forceinline__ void ldsm4(uint32_t a, uint32_t& r0, uint32_t& r1, uint32_t& r2, uint32_t& r3) {
  asm volatile("ldmatrix.sync.aligned.m8n8.x4.shared.b16 {%0,%1,%2,%3}, [%4];" : "=r"(r0), "=r"(r1), "=r"(r2), "=r"(r3) : "r"(a) : "memory");
}
__device__ __forceinline__ void ldsm2(uint32_t a, uint32_t& r0, uint32_t& r1) {
  asm volatile("ldmatrix.sync.aligned.m8n8.x2.shared.b16 {%0,%1}, [%2];" : "=r"(r0), "=r"(r1) : "r"(a) : "memory");
}
__device__ __forceinline__ void ldsm4t(uint32_t a, uint32_t& r0, uint32_t& r1, uint32_t& r2, uint32_t& r3) {
  asm volatile("ldmatrix.sync.aligned.m8n8.x4.trans.shared.b16 {%0,%1,%2,%3}, [%4];" : "=r"(r0), "=r"(r1), "=r"(r2), "=r"(r3) : "r"(a) : "memory");
}
__device__ __forceinline__ void stsm4t(uint32_t a, uint32_t r0, uint32_t r1, uint32_t r2, uint32_t r3) {
  asm volatile("stmatrix.sync.aligned.m8n8.x4.trans.shared.b16 [%0], {%1,%2,%3,%4};" :: "r"(a), "r"(r0), "r"(r1), "r"(r2), "r"(r3) : "memory");
}
__device__ __forceinline__ uint4 ldr128(const void* p) {
  unsigned long long lo, hi;
  asm volatile("{ .reg .b128 t; ld.relaxed.gpu.global.b128 t, [%2]; mov.b128 {%0, %1}, t; }" : "=l"(lo), "=l"(hi) : "l"(p) : "memory");
  return make_uint4((uint32_t)lo, (uint32_t)(lo >> 32), (uint32_t)hi, (uint32_t)(hi >> 32));
}
__device__ __forceinline__ void str128(void* p, uint32_t x, uint32_t y, uint32_t z, uint32_t w) {
  asm volatile("{ .reg .b128 t; .reg .b64 lo, hi; mov.b64 lo, {%1,%2}; mov.b64 hi, {%3,%4}; mov.b128 t, {lo, hi}; st.relaxed.gpu.global.b128 [%0], t; }"
               :: "l"(p), "r"(x), "r"(y), "r"(z), "r"(w) : "memory");
}
__device__ __forceinline__ void str64(void* p, uint32_t x, uint32_t y) {
  asm volatile("{ .reg .b64 t; mov.b64 t, {%1,%2}; st.relaxed.gpu.global.b64 [%0], t; }" :: "l"(p), "r"(x), "r"(y) : "memory");
}
__device__ __forceinline__ uint32_t ldr32(const void* p) { uint32_t v; asm volatile("ld.relaxed.gpu.global.b32 %0, [%1];" : "=r"(v) : "l"(p) : "memory"); return v; }
__device__ __forceinline__ void str32(void* p, uint32_t v) { asm volatile("st.relaxed.gpu.global.b32 [%0], %1;" :: "l"(p), "r"(v) : "memory"); }
__device__ __forceinline__ void str16(void* p, uint32_t v) { asm volatile("st.relaxed.gpu.global.u16 [%0], %1;" :: "l"(p), "h"((uint16_t)v) : "memory"); }
__device__ __forceinline__ void fence_gpu() { asm volatile("fence.acq_rel.gpu;" ::: "memory"); }
__device__ __forceinline__ void bar_sync(int id, int n) { asm volatile("bar.sync %0, %1;" :: "r"(id), "r"(n) : "memory"); }
__device__ __forceinline__ void bar_arrive(int id, int n) { asm volatile("bar.arrive %0, %1;" :: "r"(id), "r"(n) : "memory"); }

__device__ __forceinline__ float bf_lo(uint32_t w) { return __uint_as_float(w << 16); }
__device__ __forceinline__ float bf_hi(uint32_t w) { return __uint_as_float(w & 0xFFFF0000u); }
__device__ __forceinline__ uint32_t pack_bf(float lo, float hi) { uint32_t r; asm("cvt.rn.bf16x2.f32 %0, %1, %2;" : "=r"(r) : "f"(hi), "f"(lo)); return r; }
__device__ __forceinline__ uint32_t pack_h(float lo, float hi) { uint32_t r; asm("cvt.rn.f16x2.f32 %0, %1, %2;" : "=r"(r) : "f"(hi), "f"(lo)); return r; }
__device__ __forceinline__ float bfr(float x) { return bf_lo(pack_bf(x, 0.f)); }
__device__ __forceinline__ uint32_t bf_sub2(uint32_t a, uint32_t b) { __nv_bfloat162 r = __hsub2(*(__nv_bfloat162*)&a, *(__nv_bfloat162*)&b); return *(uint32_t*)&r; }
__device__ __forceinline__ uint32_t bf_add2(uint32_t a, uint32_t b) { __nv_bfloat162 r = __hadd2(*(__nv_bfloat162*)&a, *(__nv_bfloat162*)&b); return *(uint32_t*)&r; }
__device__ __forceinline__ uint32_t bf_mul2(uint32_t a, uint32_t b) { __nv_bfloat162 r = __hmul2(*(__nv_bfloat162*)&a, *(__nv_bfloat162*)&b); return *(uint32_t*)&r; }
__device__ __forceinline__ float2 h2f(uint32_t w) { return __half22float2(*(__half2*)&w); }
__device__ __forceinline__ float ex2(float x) { float r; asm("ex2.approx.ftz.f32 %0, %1;" : "=f"(r) : "f"(x)); return r; }
__device__ __forceinline__ float warp_sum(float v) {
#pragma unroll
  for (int o = 16; o > 0; o >>= 1) v += __shfl_xor_sync(0xffffffffu, v, o);
  return v;
}
__device__ __forceinline__ void mma_f16_f32(float* d, uint32_t a0, uint32_t a1, uint32_t a2, uint32_t a3, uint32_t b0, uint32_t b1) {
  asm volatile("mma.sync.aligned.m16n8k16.row.col.f32.f16.f16.f32 {%0,%1,%2,%3}, {%4,%5,%6,%7}, {%8,%9}, {%0,%1,%2,%3};"
               : "+f"(d[0]), "+f"(d[1]), "+f"(d[2]), "+f"(d[3]) : "r"(a0), "r"(a1), "r"(a2), "r"(a3), "r"(b0), "r"(b1));
}
__device__ __forceinline__ void mma_f16_f16(uint32_t& d0, uint32_t& d1, uint32_t a0, uint32_t a1, uint32_t a2, uint32_t a3, uint32_t b0, uint32_t b1) {
  asm volatile("mma.sync.aligned.m16n8k16.row.col.f16.f16.f16.f16 {%0,%1}, {%2,%3,%4,%5}, {%6,%7}, {%0,%1};"
               : "+r"(d0), "+r"(d1) : "r"(a0), "r"(a1), "r"(a2), "r"(a3), "r"(b0), "r"(b1));
}
__device__ __forceinline__ void mma_bf16(float* d, uint32_t a0, uint32_t a1, uint32_t a2, uint32_t a3, uint32_t b0, uint32_t b1) {
  asm volatile("mma.sync.aligned.m16n8k16.row.col.f32.bf16.bf16.f32 {%0,%1,%2,%3}, {%4,%5,%6,%7}, {%8,%9}, {%0,%1,%2,%3};"
               : "+f"(d[0]), "+f"(d[1]), "+f"(d[2]), "+f"(d[3]) : "r"(a0), "r"(a1), "r"(a2), "r"(a3), "r"(b0), "r"(b1));
}
__device__ __forceinline__ void mma_bf16_k8(float* d, uint32_t a0, uint32_t a1, uint32_t b0) {
  asm volatile("mma.sync.aligned.m16n8k8.row.col.f32.bf16.bf16.f32 {%0,%1,%2,%3}, {%4,%5}, {%6}, {%0,%1,%2,%3};"
               : "+f"(d[0]), "+f"(d[1]), "+f"(d[2]), "+f"(d[3]) : "r"(a0), "r"(a1), "r"(b0));
}

__device__ __forceinline__ void wg_fence() { asm volatile("wgmma.fence.sync.aligned;" ::: "memory"); }
__device__ __forceinline__ void wg_commit() { asm volatile("wgmma.commit_group.sync.aligned;" ::: "memory"); }
template <int N> __device__ __forceinline__ void wg_wait() { asm volatile("wgmma.wait_group.sync.aligned %0;" :: "n"(N) : "memory"); }
template <int TB> __device__ __forceinline__ void wgmma32(float* d, const uint32_t* a, uint32_t dlo, uint32_t dhi) {
  asm volatile("{ .reg .b64 dd; mov.b64 dd, {%20, %21}; wgmma.mma_async.sync.aligned.m64n32k16.f32.f16.f16 "
               "{%0,%1,%2,%3,%4,%5,%6,%7,%8,%9,%10,%11,%12,%13,%14,%15}, {%16,%17,%18,%19}, dd, 1, 1, 1, %22; }"
               : "+f"(d[0]), "+f"(d[1]), "+f"(d[2]), "+f"(d[3]), "+f"(d[4]), "+f"(d[5]), "+f"(d[6]), "+f"(d[7]),
                 "+f"(d[8]), "+f"(d[9]), "+f"(d[10]), "+f"(d[11]), "+f"(d[12]), "+f"(d[13]), "+f"(d[14]), "+f"(d[15])
               : "r"(a[0]), "r"(a[1]), "r"(a[2]), "r"(a[3]), "r"(dlo), "r"(dhi), "n"(TB));
}
__device__ __forceinline__ void wgmma32_init(float* d, const uint32_t* a, uint32_t dlo, uint32_t dhi) {
  asm volatile("{ .reg .b64 dd; mov.b64 dd, {%20, %21}; wgmma.mma_async.sync.aligned.m64n32k16.f32.f16.f16 "
               "{%0,%1,%2,%3,%4,%5,%6,%7,%8,%9,%10,%11,%12,%13,%14,%15}, {%16,%17,%18,%19}, dd, 0, 1, 1, 0; }"
               : "=f"(d[0]), "=f"(d[1]), "=f"(d[2]), "=f"(d[3]), "=f"(d[4]), "=f"(d[5]), "=f"(d[6]), "=f"(d[7]),
                 "=f"(d[8]), "=f"(d[9]), "=f"(d[10]), "=f"(d[11]), "=f"(d[12]), "=f"(d[13]), "=f"(d[14]), "=f"(d[15])
               : "r"(a[0]), "r"(a[1]), "r"(a[2]), "r"(a[3]), "r"(dlo), "r"(dhi));
}

__device__ __forceinline__ void wgmma16_ss(float* d, uint32_t alo, uint32_t blo, uint32_t hi, int acc) {
  asm volatile("{ .reg .b64 da, db; .reg .pred q; setp.ne.b32 q, %11, 0; mov.b64 da, {%8, %10}; mov.b64 db, {%9, %10}; "
               "wgmma.mma_async.sync.aligned.m64n16k16.f32.f16.f16 {%0,%1,%2,%3,%4,%5,%6,%7}, da, db, q, 1, 1, 1, 1; }"
               : "+f"(d[0]), "+f"(d[1]), "+f"(d[2]), "+f"(d[3]), "+f"(d[4]), "+f"(d[5]), "+f"(d[6]), "+f"(d[7])
               : "r"(alo), "r"(blo), "r"(hi), "r"(acc));
}
__device__ __forceinline__ void tma_box(uint32_t dst, const CUtensorMap* tm, uint32_t mb, int x, int y) {
  asm volatile("cp.async.bulk.tensor.2d.shared::cluster.global.mbarrier::complete_tx::bytes [%0], [%1, {%3, %4}], [%2];"
               :: "r"(dst), "l"(tm), "r"(mb), "r"(x), "r"(y) : "memory");
}
__device__ __forceinline__ void l2_prefetch(const void* src, uint32_t bytes) {
  asm volatile("cp.async.bulk.prefetch.L2.global [%0], %1;" :: "l"(src), "r"(bytes) : "memory");
}
__device__ __forceinline__ uint32_t uni(uint32_t v) {
  uint32_t r; asm volatile("shfl.sync.idx.b32 %0, %1, 0, 0x1f, 0xffffffff;" : "=r"(r) : "r"(v)); return r;
}
__device__ __forceinline__ int fresh_tid() { int v; asm volatile("mov.u32 %0, %tid.x;" : "=r"(v)); return v; }

struct Params {
  const uint32_t* x;
  Scratch* s;
  const unsigned char* ssm[6];
  const uint16_t* log_dt;
  const uint32_t* dskip;
  const uint32_t* w_r;
  const unsigned char* w_gate;
  const unsigned char* w_up;
  const unsigned char* w_down;
  uint32_t* out;
  uint32_t zero;
};
__device__ __forceinline__ uint32_t ldnc32(const void* p) { uint32_t v; asm volatile("ld.global.nc.b32 %0, [%1];" : "=r"(v) : "l"(p)); return v; }
__device__ __forceinline__ uint32_t ldnc16(const void* p) { uint16_t v; asm volatile("ld.global.nc.u16 %0, [%1];" : "=h"(v) : "l"(p)); return v; }
__device__ __forceinline__ uint4 ldnc128(const void* p) { uint4 v; asm volatile("ld.global.nc.v4.b32 {%0,%1,%2,%3}, [%4];" : "=r"(v.x), "=r"(v.y), "=r"(v.z), "=r"(v.w) : "l"(p)); return v; }
#define SPIN_WHILE(cond, body) _Pragma("unroll 1") for (int _it = 0; _it < SPIN_MAX && __any_sync(0xffffffffu, (cond)); _it++) { body; }

struct LnC { uint32_t m2, rh2, rl2; };
__device__ __forceinline__ float diag_sum(const float* d, int t) {
  float q = __shfl_sync(0xffffffffu, d[0], 9 * t) + __shfl_sync(0xffffffffu, d[1], 9 * t + 4);
  q += __shfl_xor_sync(0xffffffffu, q, 1);
  return q + __shfl_xor_sync(0xffffffffu, q, 2);
}
__device__ __forceinline__ LnC ln_stats(const uint32_t (&w)[9], int t) {
  const uint32_t ones = 0x3F803F80u;
  float d[4] = {0.f, 0.f, 0.f, 0.f};
  mma_bf16_k8(d, w[8], ones, w[8]);
#pragma unroll
  for (int i = 0; i < 8; i += 2) mma_bf16(d, w[i], ones, w[i + 1], ones, w[i], w[i + 1]);
  float s = d[2] + d[3];
  s += __shfl_xor_sync(0xffffffffu, s, 1);
  const float q = diag_sum(d, t);
  s += __shfl_xor_sync(0xffffffffu, s, 2);
  const float mean = s * (1.f / DM);
  const float var = fmaxf(fmaf(-mean, mean, q * (1.f / DM)), 0.f);
  float sd, r;
  asm("sqrt.approx.ftz.f32 %0, %1;" : "=f"(sd) : "f"(bfr(bfr(var) + 1e-5f)));
  asm("rcp.approx.ftz.f32 %0, %1;" : "=f"(r) : "f"(bfr(sd)));
  LnC c;
  c.m2 = pack_bf(mean, mean);
  c.rh2 = pack_bf(r, r);
  const float rl = r - bf_lo(c.rh2);
  c.rl2 = pack_bf(rl, rl);
  return c;
}
__device__ __forceinline__ uint32_t ln_apply(uint32_t w, const LnC& c) {
  const uint32_t d = bf_sub2(w, c.m2), lo = bf_mul2(d, c.rl2);
  __nv_bfloat162 r = __hfma2(*(const __nv_bfloat162*)&d, *(const __nv_bfloat162*)&c.rh2, *(const __nv_bfloat162*)&lo);
  return *(uint32_t*)&r;
}

__device__ __forceinline__ float2 cis(float mag_log2, float rev) {
  const float m = ex2(mag_log2), ang = rev * 6.283185307179586f;
  return make_float2(m * __cosf(ang), m * __sinf(ang));
}
__device__ __forceinline__ float2 csq(float2 a) { return make_float2(fmaf(a.x, a.x, -a.y * a.y), (a.x + a.x) * a.y); }
__device__ __forceinline__ float2 cmul(float2 a, float2 b) { return make_float2(fmaf(a.x, b.x, -a.y * b.y), fmaf(a.x, b.y, a.y * b.x)); }
__device__ __forceinline__ void pmul(uint32_t xr, uint32_t xi, uint32_t w, uint32_t& yr, uint32_t& yi) {
  const __half2 XR = *(__half2*)&xr, XI = *(__half2*)&xi, W = *(__half2*)&w;
  const __half2 a = __hfma2(__hneg2(XI), __high2half2(W), __hmul2(XR, __low2half2(W)));
  const __half2 b = __hfma2(XI, __low2half2(W), __hmul2(XR, __high2half2(W)));
  yr = *(const uint32_t*)&a; yi = *(const uint32_t*)&b;
}
__device__ __forceinline__ uint32_t pk(float2 a) { return pack_h(a.x, a.y); }
__device__ __forceinline__ uint32_t pkc(float2 a) { return pack_h(a.x, -a.y); }

__device__ __forceinline__ void kgen_issue(const uint32_t (&raw)[7], uint32_t scr, int wg, int wt, float (&acc)[8]) {
  const uint32_t misc = scr + W_MISC;
  const uint32_t dst = scr + (wt >> 3) * 256 + (wt & 7) * 16;
  const float dt = bfr(ex2(bf_lo(raw[6]) * 1.4426950408889634f));
  const float th = dt * bf_lo(raw[1]);
  const float br = dt * bf_lo(raw[2]), bi = dt * bf_lo(raw[3]);
  const float Cr = bf_lo(raw[4]), Ci = bf_lo(raw[5]);
  float2 c0 = make_float2(fmaf(Cr, br, -Ci * bi), fmaf(Cr, bi, Ci * br));
  {
    const uint32_t mx = __reduce_max_sync(0xffffffffu, __float_as_uint(fmaxf(fabsf(c0.x), fabsf(c0.y))));
    if ((wt & 31) == 0) sts32(misc + (wt >> 5) * 4, mx);
  }
  const float a2 = dt * bf_lo(raw[0]) * 1.4426950408889634f;
  const float rh = th * 0.15915494309189535f;
  const float rl = fmaf(th, (float)(0.15915494309189535 - (double)0.15915494309189535f), fmaf(th, 0.15915494309189535f, -rh));
  const float rf = rh - rintf(rh);
  const float2 z1 = cis(a2, rf + rl);
  const float p64 = rf * 64.f;
  const float2 z64 = cis(a2 * 64.f, fmaf(64.f, rl, p64 - rintf(p64)));
  const float2 z2 = csq(z1), z4 = csq(z2), z8 = csq(z4), z16 = csq(z8);
  const float2 z6 = cmul(z4, z2), z10 = cmul(z8, z2), z12 = cmul(z8, z4), z14 = cmul(z8, z6);
  uint32_t pr[4], pi[4], yr[4], yi[4];
  pr[0] = pack_h(1.f, z8.x);   pi[0] = pack_h(0.f, z8.y);
  pr[1] = pack_h(z4.x, z12.x); pi[1] = pack_h(z4.y, z12.y);
  pr[2] = pack_h(z2.x, z10.x); pi[2] = pack_h(z2.y, z10.y);
  pr[3] = pack_h(z6.x, z14.x); pi[3] = pack_h(z6.y, z14.y);
  sts128(dst, pr[0], pr[1], pr[2], pr[3]); sts128(dst + 128, pi[0], pi[1], pi[2], pi[3]);
  {
    const uint32_t w = pk(z1);
#pragma unroll
    for (int i = 0; i < 4; i++) pmul(pr[i], pi[i], w, yr[i], yi[i]);
    sts128(dst + 4096, yr[0], yr[1], yr[2], yr[3]); sts128(dst + 4096 + 128, yi[0], yi[1], yi[2], yi[3]);
  }
  const float2 z128 = csq(z64), z256 = csq(z128), z512 = csq(z256), z1024 = csq(z512), z2048 = csq(z1024);
  {
    const float k2048 = warp_sum(fmaf(c0.x, z2048.x, -c0.y * z2048.y));
    if ((wt & 31) == 0) sts32(misc + 16 + (wt >> 5) * 4, __float_as_uint(k2048));
  }
  {
    const uint32_t w = pk(z256);
#pragma unroll
    for (int i = 0; i < 4; i++) pmul(pr[i], pi[i], w, yr[i], yi[i]);
    sts128(dst + 8192, yr[0], yr[1], yr[2], yr[3]); sts128(dst + 8192 + 128, yi[0], yi[1], yi[2], yi[3]);
  }
  const float2 z768 = cmul(z512, z256);
  {
    const uint32_t wa = pk(z512), wb = pk(z768);
    pmul(pr[0], pi[0], wa, yr[0], yi[0]); pmul(pr[1], pi[1], wa, yr[1], yi[1]);
    pmul(pr[0], pi[0], wb, yr[2], yi[2]); pmul(pr[1], pi[1], wb, yr[3], yi[3]);
    sts128(dst + 12288, yr[0], yr[1], yr[2], yr[3]); sts128(dst + 12288 + 128, yi[0], yi[1], yi[2], yi[3]);
  }
  pmul(pr[0], pi[0], pk(z1024), yr[0], yi[0]);
  pmul(pr[0], pi[0], pk(cmul(z1024, z256)), yr[1], yi[1]);
  pmul(pr[0], pi[0], pk(cmul(z1024, z512)), yr[2], yi[2]);
  pmul(pr[0], pi[0], pk(cmul(z1024, z768)), yr[3], yi[3]);
  sts128(dst + 16384, yr[0], yr[1], yr[2], yr[3]); sts128(dst + 16384 + 128, yi[0], yi[1], yi[2], yi[3]);
  bar_sync(1 + wg, 128);
  {
    const uint4 e4 = lds128(misc);
    const int em = max(min((int)(max(max(e4.x, e4.y), max(e4.z, e4.w)) >> 23), 238), 16);
    const float sc = __uint_as_float((uint32_t)(127 + 4 + 127 - em) << 23);
    c0.x *= sc; c0.y *= sc;
  }
  const float2 c1 = cmul(c0, z16), c2 = cmul(c1, z16), c3 = cmul(c2, z16);
  pr[0] = pack_h(c0.x, c1.x); pi[0] = pack_h(-c0.y, -c1.y);
  pr[1] = pack_h(c2.x, c3.x); pi[1] = pack_h(-c2.y, -c3.y);
  {
    const uint32_t w = pkc(z64);
    pmul(pr[0], pi[0], w, pr[2], pi[2]); pmul(pr[1], pi[1], w, pr[3], pi[3]);
    sts128(dst + 20480, pr[0], pr[1], pr[2], pr[3]); sts128(dst + 20480 + 128, pi[0], pi[1], pi[2], pi[3]);
    const uint32_t wa = pkc(z128), wb = pkc(cmul(z128, z64));
    pmul(pr[0], pi[0], wa, yr[0], yi[0]); pmul(pr[1], pi[1], wa, yr[1], yi[1]);
    pmul(pr[0], pi[0], wb, yr[2], yi[2]); pmul(pr[1], pi[1], wb, yr[3], yi[3]);
    sts128(dst + 24576, yr[0], yr[1], yr[2], yr[3]); sts128(dst + 24576 + 128, yi[0], yi[1], yi[2], yi[3]);
  }
  asm volatile("fence.proxy.async.shared::cta;" ::: "memory");
  bar_sync(1 + wg, 128);
  const uint32_t alo = uni(lds32(misc + 48));
  wg_fence();
#pragma unroll
  for (int ks = 0; ks < 16; ks++) wgmma16_ss(acc, alo + ks * 16, alo + (20480 >> 4) + ks * 16, 4096 >> 4, ks);
  wg_commit();
}

__device__ __forceinline__ void kgen_finish(float (&acc)[8], uint32_t scr, int wg, int wt) {
  const int w = wt >> 5, g = (wt >> 2) & 7, t = wt & 3;
  const uint32_t misc = scr + W_MISC;
  const uint32_t kc = scr + W_KC + 16;
  const uint32_t kt = scr + W_KT;
  const int be = 8 * (g & 1) + 4 * ((g >> 1) & 1) + 2 * (g >> 2);
  const int a0 = w == 0 ? 2 * be : w == 1 ? 512 + be : 1024 + 2 * (g & 1) + 64 * (g >> 1);
  const int s0 = w == 0 ? 32 : w == 1 ? 16 : 4;
  const int a1 = w == 0 ? 2 * be + 2 : 768 + 4 * (g & 1) + (g & 2) + 128 * (g >> 2);
  const int s1 = w == 0 ? 32 : 8;
  wg_wait<0>();
  const float un = 1.f / 8192.f;
  if (w < 3) {
    const uint32_t p0 = kc + a0 + 2 * t * s0;
    const uint32_t h0 = pack_h(acc[0] * un, acc[1] * un), h1 = pack_h(acc[4] * un, acc[5] * un);
    sts16(p0, h0); sts16(p0 + s0, h0 >> 16); sts16(p0 + 8 * s0, h1); sts16(p0 + 9 * s0, h1 >> 16);
    if (w < 2) {
      const uint32_t p1 = kc + a1 + 2 * t * s1;
      const uint32_t h2 = pack_h(acc[2] * un, acc[3] * un), h3 = pack_h(acc[6] * un, acc[7] * un);
      sts16(p1, h2); sts16(p1 + s1, h2 >> 16); sts16(p1 + 8 * s1, h3); sts16(p1 + 9 * s1, h3 >> 16);
    }
  } else if (wt == 96) {
    const uint4 e4 = lds128(misc), k4 = lds128(misc + 16);
    const int em = max(min((int)(max(max(e4.x, e4.y), max(e4.z, e4.w)) >> 23), 238), 16);
    const float inv = __uint_as_float((uint32_t)(127 + 127 - 9 - em) << 23);
    const float kl = ((__uint_as_float(k4.x) + __uint_as_float(k4.y)) + (__uint_as_float(k4.z) + __uint_as_float(k4.w))) * inv;
    sts16(kc + 1280, pack_h(kl, kl));
    sts16(kc - 2, 0);
    sts32(misc + 32, (uint32_t)(em + 9) << 23);
  }
  bar_sync(1 + wg, 128);
  const uint32_t h01 = lds32(kc + wt * 4), km1 = lds16(kc + wt * 4 - 2);
  const uint32_t q1 = kc + 512 + wt * 2;
  const uint32_t p1 = lds16(q1 - 2), c1 = lds16(q1), n1 = lds16(q1 + 2), c2 = lds16(q1 + 256), n2 = lds16(q1 + 258), v3 = lds16(q1 + 514);
  const uint32_t wb = kt + 64;
  sts64(wb + wt * 8, __byte_perm(h01, km1, 0x5410), __byte_perm(h01, 0, 0x1032));
  const bool odd = wt & 1;
  const uint32_t lo1 = (odd || wt == 0) ? p1 : c1, hi1 = odd ? n1 : c1;
  sts64(wb + 1024 + wt * 8, __byte_perm(c1, lo1, 0x5410), __byte_perm(hi1, c1, 0x5410));
  const uint32_t tie = odd ? n2 : c2, cc = __byte_perm(c2, c2, 0x5410);
  sts128(wb + 2048 + wt * 16, cc, cc, __byte_perm(tie, c2, 0x5410), __byte_perm(n2, tie, 0x5410));
  const uint32_t arr = kt + KT_WORDS * 4 + (odd ? 0 : 2 * L3_ARR) + (wt >> 1) * 2;
  sts16(arr + 112, v3);
  sts16(arr + L3_ARR + 120, v3);
  if (wt == 127) {
    const uint32_t d = __byte_perm(n2, n2, 0x5410);
    sts128(wb + 4096, d, d, d, d); sts64(wb + 4096 + 16, d, d & 0xFFFF0000u);
  }
}

__device__ __forceinline__ void load_a(uint32_t (&a)[4], uint32_t kp, int j, uint32_t zero) {
  a[0] = lds32(kp + 256 * j); a[1] = lds32(kp + 256 * j + 32); a[2] = lds32(kp + 256 * j - 32);
  asm volatile("xor.b32 %0, %1, %2;" : "=r"(a[3]) : "r"(a[0]), "r"(zero));
}
__device__ __forceinline__ uint32_t band(int d, int lo, int hi) {
  return ((unsigned)(d - lo) <= (unsigned)(hi - lo) ? 0x3C00u : 0u) | ((unsigned)(d - 1 - lo) <= (unsigned)(hi - lo) ? 0x3C000000u : 0u);
}
__device__ __forceinline__ uint32_t hadd2u(uint32_t a, uint32_t b) { __half2 r = __hadd2(*(__half2*)&a, *(__half2*)&b); return *(uint32_t*)&r; }

template <int Q> __device__ __forceinline__ void epi_store(const float* acc, uint32_t st) {
#pragma unroll
  for (int h = 0; h < 2; h++)
    stsm4t(st + ((Q % 3) * 32 + 16 * h) * 16, pack_h(acc[8 * h], acc[8 * h + 1]), pack_h(acc[8 * h + 2], acc[8 * h + 3]),
           pack_h(acc[8 * h + 4], acc[8 * h + 5]), pack_h(acc[8 * h + 6], acc[8 * h + 7]));
}
template <int Q> __device__ __forceinline__ void epi_load(uint2 (&v)[4], uint32_t ld, int wt) {
#pragma unroll
  for (int ww = 0; ww < 4; ww++) {
    uint32_t a = ld + ww * (EX_WARP - 16) + (Q % 3) * 512;
    if (Q == 3 && ww > 0 && wt < 4 * ww) a += 96 * 16;
    v[ww] = lds64(a);
  }
}
template <int Q> __device__ __forceinline__ void epi_out(const uint2 (&v)[4], unsigned char* y, float scale) {
  const float2 a = h2f(hadd2u(hadd2u(v[0].x, v[1].x), hadd2u(v[2].x, v[3].x)));
  const float2 b = h2f(hadd2u(hadd2u(v[0].y, v[1].y), hadd2u(v[2].y, v[3].y)));
  str64(y + (size_t)Q * (32 * DM * 32), pack_bf(a.x * scale, a.y * scale), pack_bf(b.x * scale, b.y * scale));
}

__global__ void __launch_bounds__(NT, 1)
fused_kernel(const Params p, const __grid_constant__ CUtensorMap tm_gate, const __grid_constant__ CUtensorMap tm_up) {
  extern __shared__ __align__(1024) unsigned char smem[];
  const int c = blockIdx.x;
  const bool five = (c & 1) == 0;
  const int u0 = (c >> 1) * 9 + (five ? 0 : 4);
  uint32_t epoch;
  uint32_t raw[7];
  TS(0);
  {
    const int tid = threadIdx.x, lane = tid & 31, wt = tid & 127, g = lane >> 2, t = lane & 3;
    uint32_t xw[9];
    {
      const uint32_t* xp = p.x + (c * 16 + (tid >> 5)) * 288 + lane;
#pragma unroll
      for (int i = 0; i < 9; i++) xw[i] = ldnc32(xp + 32 * i);
    }
#pragma unroll
    for (int i = 0; i < 6; i++) raw[i] = ldnc16(p.ssm[i] + (uint32_t)(c * 1024 + tid * 2));
    raw[6] = ldnc16(p.log_dt + 4 * c + (tid >> 7));
    const uint32_t flag0 = ldr32(&p.s->FLAG[c]);
    const int warp = (int)uni(tid >> 5), wg = warp >> 2;
    const uint32_t wb = OFF_W + wg * W_BYTES;
    if (wt < 56) sts128(wb + W_UP + (wt >= UP_PAD ? UP_PLANE - UP_PAD * 16 : 0) + wt * 16, 0, 0, 0, 0);
    if (wt < 84) sts128(wb + W_KT + (wt < 4 ? 0 : 4096) + wt * 16, 0, 0, 0, 0);
    if (wt == 127) sts128(wb + W_MISC + 48, (wb >> 4) | (8u << 16), ((wb + W_UP) >> 4) + UP_PAD + ((uint32_t)(UP_PLANE >> 4) << 16),
                          ((wb + W_L3) >> 4) + ((uint32_t)(L3_ARR >> 4) << 16), 0);
    if (wg == 2) {
      const int w = warp & 3, mi = lane >> 3, d0 = g - 2 * t;
      const uint32_t rowb = W_UP + (UP_PAD + 56 - 8 * (lane & 7) + w) * 16;
      sts128(OFF_ATAB + wt * 16, W_KT + (16 + 16 * w + d0) * 4,
             (rowb + ((mi + 1) & 1) * UP_PLANE + ((mi - 3) >> 1) * 16) | ((rowb + UP_PLANE + (mi & 1) * 64) << 16),
             (w * EX_WARP + (mi & 1) * EX_PLANE + (4 + 8 * (mi >> 1) + (lane & 7)) * 16) | ((((wt >> 1) & 1) * EX_PLANE + (4 + (wt >> 2)) * 16 + (wt & 1) * 8) << 16),
             (wt >> 2) * (DM * 32) + (wt & 3) * 8);
      const int lo = (w & 1) ? 5 : 12, hi = (w & 1) ? 11 : 20, db = d0 + 24 - 8 * (w & 1) - 16 * (w >> 1);
      sts128(OFF_BAND + wt * 16, band(db, lo, hi), band(db + 8, lo, hi), band(db - 8, lo, hi), band(db, lo, hi));
    }
    if (warp == 14) {
      if (lane < 18) asm volatile("prefetch.global.L2 [%0];" :: "l"((lane < 9 ? p.dskip : p.w_r - 288) + lane * 32));
      else if (lane < 20) {
        if (five) {
#pragma unroll
          for (int i = 0; i < 6; i++) asm volatile("prefetch.global.L2 [%0];" :: "l"(p.ssm[i] + (512 + (c >> 1)) * 256 + (lane & 1) * 128));
        }
      } else if (lane == 30) asm volatile("prefetch.global.L2 [%0];" :: "l"(p.log_dt + 512));
      else if (lane == 31) {
        if (smem_u32(smem) != SB) __trap();
        asm volatile("mbarrier.init.shared::cta.b64 [%0], 1;" :: "r"(MISC_MBAR) : "memory");
        asm volatile("mbarrier.arrive.expect_tx.shared::cta.b64 _, [%0], %1;" :: "r"(MISC_MBAR), "r"(6 * BOX) : "memory");
        sts32(MISC_CNT, 0);
        asm volatile("fence.proxy.async.shared::cta;" ::: "memory");
        l2_prefetch(p.w_gate + (size_t)c * 41472, 41472);
      }
    }
    if (warp == 15) {
#pragma unroll
      for (int i = 0; i < 5; i++) if (lane + 32 * i < 144) sts128(OFF_ONES + (lane + 32 * i) * 16, ~0u, ~0u, ~0u, ~0u);
      asm volatile("fence.proxy.async.shared::cta;" ::: "memory");
      __syncwarp();
      if (lane < 14 && (lane != 13 || c < 72)) {
        const uint32_t off = lane < 8 ? offsetof(Scratch, Y2) + c * 18432 + lane * 2304 : lane < 12 ? offsetof(Scratch, P) + c * 9216 + (lane - 8) * 2304
                           : lane == 12 ? offsetof(Scratch, R) + c * 32 : offsetof(Scratch, HS) + c * 128;
        const uint32_t bytes = lane < 12 ? 2304 : lane == 12 ? 32 : 128;
        asm volatile("cp.async.bulk.global.shared::cta.bulk_group [%0], [%1], %2;" :: "l"((unsigned char*)p.s + off), "r"(OFF_ONES), "r"(bytes) : "memory");
        asm volatile("cp.async.bulk.commit_group;" ::: "memory");
      }
    }
    const uint32_t row = OFF_YT + warp * YT_PITCH + (warp >> 3) * 64 + lane * 4;
    const int tr_tok = 8 * ((lane >> 1) & 1) + 2 * (lane >> 3) + (lane & 1);
    const uint32_t tr_addr = OFF_YT + tr_tok * YT_PITCH + (tr_tok >> 3) * 64 + ((lane >> 2) & 1) * 16 + warp * 32;
    uint4* u2dst = &p.s->U2[c * DM * 2 + warp * 32 + (8 * (t >> 1) + g) * 2 + (t & 1)];
    TS(13);

    const LnC l1 = ln_stats(xw, t);
#pragma unroll
    for (int i = 0; i < 9; i++) { const uint32_t u = ln_apply(xw[i], l1); sts32(row + i * 128, pack_h(bf_lo(u), bf_hi(u))); }
    if (lane == 0) sts128(MISC_LN1 + warp * 16, l1.m2, l1.rh2, l1.rl2, 0);
    epoch = flag0 + 1u;
    __syncthreads();
#pragma unroll
    for (int r = 0; r < 3; r++) {
      if (r < 2 || warp < 4) {
        uint32_t r0, r1, r2, r3;
        ldsm4t(tr_addr + r * 512, r0, r1, r2, r3);
        str128(u2dst + r * 512, (r0 & ~1u) | (epoch & 1u), r1, r2, r3);
      }
    }
    if (wg < 2) bar_arrive(5, 288);
    else {
      if (warp == 15) {
        asm volatile("cp.async.bulk.wait_group 0;" ::: "memory");
        bar_sync(5, 288);
      }
      bar_sync(6, 256);
      if (tid == 511) {
        str32(&p.s->FLAG[c], epoch);
        l2_prefetch(p.w_up + (size_t)c * 41472, 41472);
      }
      TS(1);
      const int a = (tid - 256) >> 2;
      if (warp == 8) {
        uint4 f = ldr128(&p.s->FLAG[lane * 4]);
        SPIN_WHILE(f.x != epoch || f.y != epoch || f.z != epoch || f.w != epoch, f = ldr128(&p.s->FLAG[lane * 4]));
      }
      bar_sync(6, 256);
      const uint4* src = &p.s->U2[a * (DM * 2) + 8 * c + t];
      uint4 v0 = ldr128(src), v1 = ldr128(src + 64 * DM * 2), v2 = ldr128(src + 4), v3 = ldr128(src + 64 * DM * 2 + 4);
      TS(15);
      const uint32_t ud = OFF_W + (t >> 1) * W_BYTES + W_UP + (t & 1) * UP_PLANE + (UP_PAD + a) * 16;
      SPIN_WHILE(((v0.x ^ epoch) | (v1.x ^ epoch)) & 1u, v0 = ldr128(src); v1 = ldr128(src + 64 * DM * 2));
      sts128(ud, v0.x & ~1u, v0.y, v0.z, v0.w);
      sts128(ud + 1024, v1.x & ~1u, v1.y, v1.z, v1.w);
      asm volatile("fence.proxy.async.shared::cta;" ::: "memory");
      bar_arrive(7, 512);
      SPIN_WHILE(((v2.x ^ epoch) | (v3.x ^ epoch)) & 1u, v2 = ldr128(src + 4); v3 = ldr128(src + 64 * DM * 2 + 4));
      sts128(ud + 2 * W_BYTES, v2.x & ~1u, v2.y, v2.z, v2.w);
      sts128(ud + 2 * W_BYTES + 1024, v3.x & ~1u, v3.y, v3.z, v3.w);
      asm volatile("fence.proxy.async.shared::cta;" ::: "memory");
      bar_sync(6, 256);
    }
  }

  {
    const int wg = (int)uni(fresh_tid() >> 7);
    const uint32_t wb = OFF_W + wg * W_BYTES;
    const uint32_t zero = p.zero;
    const int nitem = (wg == 0 && five) ? 2 : 1;
#pragma unroll 1
    for (int item = 0; item < nitem; item++) {
      {
        const int wt = fresh_tid() & 127;
        uint4 v0, v1;
        const uint4* src = &p.s->U2[(wt >> 1) * (DM * 2) + 1024 + (c & ~1) + (wt & 1)];
        if (item) { v0 = ldr128(src); v1 = ldr128(src + 64 * DM * 2); }
        float kacc[8];
        kgen_issue(raw, wb, wg, wt, kacc);
        TS(14);
        if (item) {
          SPIN_WHILE(((v0.x ^ epoch) | (v1.x ^ epoch)) & 1u, v0 = ldr128(src); v1 = ldr128(src + 64 * DM * 2));
          const uint32_t ud = wb + W_UP + (wt & 1) * UP_PLANE + (UP_PAD + (wt >> 1)) * 16;
          sts128(ud, v0.x & ~1u, v0.y, v0.z, v0.w);
          sts128(ud + 1024, v1.x & ~1u, v1.y, v1.z, v1.w);
        }
        kgen_finish(kacc, wb, wg, wt);
        if ((wt & 31) < 8) sts128(wb + (wt >> 5) * EX_WARP + ((wt >> 2) & 1) * EX_PLANE + (wt & 3) * 16, 0, 0, 0, 0);
        asm volatile("fence.proxy.async.shared::cta;" ::: "memory");
        TS(2);
        if (wg < 2 && item == 0) bar_sync(7, 512); else bar_sync(1 + wg, 128);
        if (wt == 0 && wg > 0) {
          tma_box(OFF_G + (wg - 1) * BOX, &tm_gate, MISC_MBAR, u0 * 8, (wg - 1) * 192);
          tma_box(wb + W_UPBOX, &tm_up, MISC_MBAR, u0 * 8, (wg - 1) * 192);
          if (wg == 3) l2_prefetch(p.w_down + (size_t)u0 * 8 * DM * 2, (five ? 4 : 5) * 8 * DM * 2);
        }
        TS(3);
      }
      const uint32_t at = OFF_ATAB + (fresh_tid() & 127) * 16;
      const uint32_t kp = wb + lds32(at);
      uint32_t dlo = uni(lds32(wb + W_MISC + 52));
      const uint32_t dhi = 8;
      float acc[4][16];
      uint32_t a0[4][4], a1[4][4];
#pragma unroll
      for (int j = 0; j < 4; j++) load_a(a0[j], kp, 8 + j, zero);
      TS(20);
      wg_fence();
#pragma unroll
      for (int j = 0; j < 4; j++)
#pragma unroll
        for (int q = 1; q < 4; q++) {
          if (j == 0) wgmma32_init(acc[q], a0[j], dlo + 32 * q - 4 * (8 + j), dhi);
          else wgmma32<0>(acc[q], a0[j], dlo + 32 * q - 4 * (8 + j), dhi);
        }
      wg_commit();
      TS(21);
#pragma unroll
      for (int j = 0; j < 4; j++) load_a(a1[j], kp, 12 + j, zero);
      uint32_t x9[4] = {0, 0, 0, 0}, x7[4] = {0, 0, 0, 0}, a16[4];
      {
        uint32_t b[2][5];
        const uint32_t wa = lds32(at + 4);
        ldsm4(wb + (wa & 0xFFFFu), b[0][0], b[0][1], b[0][2], b[0][3]);
        ldsm4(wb + (wa & 0xFFFFu) + 64, b[1][0], b[1][1], b[1][2], b[1][3]);
        ldsm2(wb + (wa >> 16), b[0][4], b[1][4]);
        TS(22);
        wg_fence();
#pragma unroll
        for (int j = 0; j < 4; j++)
#pragma unroll
          for (int q = 1; q < 4; q++) wgmma32<0>(acc[q], a1[j], dlo + 32 * q - 4 * (12 + j), dhi);
        wg_commit();
        TS(23);
        load_a(a16, kp, 16, zero);
        const uint32_t bt = OFF_BAND + ((at - OFF_ATAB) & 0x1F0);
#pragma unroll
        for (int h = 0; h < 2; h++) {
          const uint4 n = lds128(bt + h * 1024);
          mma_f16_f16(x9[0], x9[1], n.x, n.y, n.z, n.w, b[0][2 * h], b[0][2 * h + 1]);
          mma_f16_f16(x9[2], x9[3], n.x, n.y, n.z, n.w, b[1][2 * h], b[1][2 * h + 1]);
          const uint4 s = lds128(bt + h * 1024 + 512);
          mma_f16_f16(x7[0], x7[1], s.x, s.y, s.z, s.w, b[0][2 * h + 1], b[0][2 * h + 2]);
          mma_f16_f16(x7[2], x7[3], s.x, s.y, s.z, s.w, b[1][2 * h + 1], b[1][2 * h + 2]);
        }
      }
      TS(17);
      dlo = uni(lds32(wb + W_MISC + 52));
      const uint32_t l3lo = uni(lds32(wb + W_MISC + 56));
      wg_wait<1>();
#pragma unroll
      for (int j = 0; j < 4; j++) load_a(a0[j], kp, j, zero);
      wg_fence();
#pragma unroll
      for (int q = 2; q < 4; q++) {
        wgmma32<0>(acc[q], a16, dlo + 32 * q - 64, dhi);
        wgmma32<1>(acc[q], x9, l3lo + 4 * (q - 2), 1);
        wgmma32<1>(acc[q], x7, l3lo + 4 * (q - 2) + (2 * L3_ARR >> 4), 1);
      }
      wg_commit();
      dlo = uni(lds32(wb + W_MISC + 52));
      wg_wait<1>();
#pragma unroll
      for (int j = 0; j < 4; j++) load_a(a1[j], kp, 4 + j, zero);
      wg_fence();
#define WG2(Q, A, J) wgmma32<0>(acc[Q], A[(J) & 3], dlo + 32 * Q - 4 * (J), dhi); wgmma32<0>(acc[Q], A[((J) + 1) & 3], dlo + 32 * Q - 4 * (J) - 4, dhi);
      WG2(1, a0, 0) WG2(1, a0, 2) WG2(1, a1, 4) WG2(1, a1, 6)
      wg_commit();
      TS(18);
      const float scale = __uint_as_float(lds32(wb + W_MISC + 32));
      const uint2 ea = lds64(at + 8);
      unsigned char* y = (unsigned char*)p.s->Y2 + (ea.y + (uint32_t)(item ? 512 + (c >> 1) : 4 * c + wg) * 32);
      const uint32_t est = wb + (ea.x & 0xFFFFu), eld = wb + (ea.x >> 16);
      uint2 ev[4];
      wg_wait<1>(); wg_fence();
      wgmma32_init(acc[0], a0[0], dlo, dhi); wgmma32<0>(acc[0], a0[1], dlo - 4, dhi);
      wg_commit(); wg_wait<1>();
      epi_store<1>(acc[1], est); wg_fence();
      WG2(0, a0, 2) WG2(0, a1, 4) WG2(0, a1, 6)
      wg_commit();
      WG2(2, a0, 0)
      wg_commit(); wg_wait<1>();
      epi_store<0>(acc[0], est); wg_fence();
      WG2(2, a0, 2)
      bar_sync(1 + wg, 128); epi_load<0>(ev, eld, 0);
      WG2(2, a1, 4)
      epi_out<0>(ev, y, scale); epi_load<1>(ev, eld, 0);
      WG2(2, a1, 6)
      wg_commit();
      epi_out<1>(ev, y, scale);
      TS(19);
      WG2(3, a0, 0)
      wg_commit(); wg_wait<1>();
      epi_store<2>(acc[2], est); wg_fence();
      WG2(3, a0, 2)
      bar_sync(1 + wg, 128); epi_load<2>(ev, eld, 0);
      WG2(3, a1, 4)
      epi_out<2>(ev, y, scale);
      WG2(3, a1, 6)
      wg_commit();
#undef WG2
      if (item + 1 < nitem) {
        const uint32_t off = (uint32_t)((512 + (c >> 1)) * 256) + ((at - OFF_ATAB) >> 3);
#pragma unroll
        for (int i = 0; i < 6; i++) raw[i] = ldnc16(p.ssm[i] + off);
        raw[6] = ldnc16(p.log_dt + 512 + (c >> 1));
      } else {
#pragma unroll
        for (int i = 0; i < 7; i++) raw[i] = 0;
      }
      wg_wait<0>();
      epi_store<3>(acc[3], est);
      bar_sync(1 + wg, 128);
      epi_load<3>(ev, eld, (at - OFF_ATAB) >> 4);
      epi_out<3>(ev, y, scale);
      if (item + 1 < nitem) bar_sync(1 + wg, 128);
    }
  }
  TS(4);

  const int tid = fresh_tid(), lane = tid & 31, g = lane >> 2, t = lane & 3;
  const int warp = (int)uni(tid >> 5), tok = c * 16 + warp;
  const uint32_t stash = OFF_W + (warp >> 2) * W_BYTES + (warp & 3) * 2304 + lane * 8;
  {
    uint32_t hw[9], lw[9], ds[9], wr[9];
    const uint4* ysrc = &p.s->Y2[c * DM * 2 + warp * 32 + (8 * (t >> 1) + g) * 2 + (t & 1)];
    uint4 v0 = ldr128(ysrc), v1 = ldr128(ysrc + 512), v2 = make_uint4(0, 0, 0, 0);
    if (warp < 4) v2 = ldr128(ysrc + 1024);
#pragma unroll
    for (int i = 0; i < 9; i++) { hw[i] = ldnc32(p.x + tok * 288 + lane + 32 * i); ds[i] = ldnc32(p.dskip + lane + 32 * i); }
#pragma unroll
    for (int i = 0; i < 9; i++) wr[i] = ldnc32(p.w_r + lane + 32 * i);
    {
      const uint4 q = lds128(MISC_LN1 + warp * 16);
      LnC l1; l1.m2 = q.x; l1.rh2 = q.y; l1.rl2 = q.z;
#pragma unroll
      for (int i = 0; i < 9; i++) ds[i] = bf_mul2(ln_apply(hw[i], l1), ds[i]);
    }
    const int tr_tok = 8 * ((lane >> 1) & 1) + 2 * (lane >> 3) + (lane & 1);
    const uint32_t tr_addr = OFF_YT + tr_tok * YT_PITCH + (tr_tok >> 3) * 64 + ((lane >> 2) & 1) * 16 + warp * 32;
    TS(5);
    SPIN_WHILE(v0.x == ~0u || v0.z == ~0u || v1.x == ~0u || v1.z == ~0u, v0 = ldr128(ysrc); v1 = ldr128(ysrc + 512));
    stsm4t(tr_addr, v0.x, v0.y, v0.z, v0.w);
    stsm4t(tr_addr + 512, v1.x, v1.y, v1.z, v1.w);
    if (warp < 4) {
      SPIN_WHILE(v2.x == ~0u || v2.z == ~0u, v2 = ldr128(ysrc + 1024));
      stsm4t(tr_addr + 1024, v2.x, v2.y, v2.z, v2.w);
    }
    __syncthreads();
    TS(6);
    const uint32_t row = OFF_YT + warp * YT_PITCH + (warp >> 3) * 64 + lane * 4;
#pragma unroll
    for (int i = 0; i < 9; i++) hw[i] = bf_add2(hw[i], bf_add2(lds32(row + i * 128), ds[i]));
    const LnC l2 = ln_stats(hw, t);
#pragma unroll
    for (int i = 0; i < 9; i++) lw[i] = ln_apply(hw[i], l2);
    float d[4] = {0.f, 0.f, 0.f, 0.f};
    mma_bf16_k8(d, lw[8], 0u, wr[8]);
#pragma unroll
    for (int i = 0; i < 8; i += 2) mma_bf16(d, lw[i], 0u, lw[i + 1], 0u, wr[i], wr[i + 1]);
    const uint32_t b = pack_bf(diag_sum(d, t), 0.f);
    uint32_t key = min((b & 0x8000u) ? (~b & 0xFFFFu) : (b | 0x8000u), 0xFFFEu);
    if (lane == 0) str16((uint16_t*)p.s->R + tok, key);
    key = (key >> 16) | (epoch & 1u);
    uint32_t* rdst = &p.s->ROW[tok * 288 + lane];
#pragma unroll
    for (int i = 0; i < 9; i++) {
      asm volatile("add.u32 %0, %0, %1;" : "+r"(lw[i]) : "r"(key >> 1));
      str32(rdst + 32 * i, (pack_h(bf_lo(lw[i]), bf_hi(lw[i])) & ~1u) | key);
    }
#pragma unroll
    for (int i = 0; i < 9; i++) sts64(stash + i * 256, bf_add2(hw[i], lw[i]), hw[i]);
  }
  TS(7);
  uint4 rv = make_uint4(~0u, 0, 0, 0);
  if (warp >= 8) rv = ldr128(&p.s->R[tid - 256]);
  uint32_t wd[5][8];
  if (warp < 9) {
    const unsigned char* src = p.w_down + (uint32_t)((u0 * 8 + 2 * t) * (DM * 2) + warp * 128 + g * 16);
#pragma unroll
    for (int q = 0; q < 5; q++) {
      uint4 r0 = make_uint4(0, 0, 0, 0), r1 = r0;
      if (q < 4 || !five) { r0 = ldnc128(src + q * 8 * DM * 2); r1 = ldnc128(src + (q * 8 + 1) * DM * 2); }
      wd[q][0] = r0.x; wd[q][1] = r1.x; wd[q][2] = r0.y; wd[q][3] = r1.y; wd[q][4] = r0.z; wd[q][5] = r1.z; wd[q][6] = r0.w; wd[q][7] = r1.w;
    }
  }
  const int fu = warp / 3, fk = warp - fu * 3;
  uint32_t wa[12][4];
  const uint32_t wabase = ((lane & 8) ? OFF_W + (fk + 1) * W_BYTES + W_UPBOX : OFF_G + fk * BOX) + ((lane >> 4) * 8 + (lane & 7)) * 80 + fu * 16;
#define LOAD_WA() do {                                                                                             \
    _Pragma("unroll 1") for (int it = 0; it < SPIN_MAX; it++) {                                                     \
      uint32_t ok;                                                                                                  \
      asm volatile("{ .reg .pred q; mbarrier.try_wait.parity.shared::cta.b64 q, [%1], 0; selp.u32 %0, 1, 0, q; }" : "=r"(ok) : "r"(MISC_MBAR) : "memory"); \
      if (ok) break;                                                                                                \
    }                                                                                                               \
    _Pragma("unroll") for (int k = 0; k < 12; k++) ldsm4t(wabase + k * 16 * 80, wa[k][0], wa[k][1], wa[k][2], wa[k][3]); \
  } while (0)
#define PERM_WD() do {                                                                                             \
    _Pragma("unroll") for (int q = 0; q < 5; q++)                                                                   \
    _Pragma("unroll") for (int j = 0; j < 4; j++) { const uint32_t a = wd[q][2 * j], b = wd[q][2 * j + 1]; wd[q][2 * j] = __byte_perm(a, b, 0x5410); wd[q][2 * j + 1] = __byte_perm(a, b, 0x7632); } \
  } while (0)

  if (warp >= 8) {
    uint32_t mx;
#pragma unroll 1
    for (int it = 0; it < SPIN_MAX; it++) {
      mx = __vmaxu2(__vmaxu2(rv.x, rv.y), __vmaxu2(rv.z, rv.w));
      mx = max(mx & 0xFFFFu, mx >> 16);
      const uint32_t wm = __reduce_max_sync(0xffffffffu, mx);
      if (wm != 0xFFFFu) { if (lane == 0) sts32(MISC_WMAX + (warp - 8) * 4, wm); break; }
      rv = ldr128(&p.s->R[tid - 256]);
    }
    TS(16);
    bar_sync(6, 256);
    const uint32_t tau = __reduce_min_sync(0xffffffffu, lds32(MISC_WMAX + (lane & 7) * 4)) << 16;
    if ((mx << 16) >= tau) {
      const uint32_t ib = 2047 - (tid - 256) * 8;
      uint32_t key[8];
      key[0] = rv.x << 16; key[1] = rv.x & 0xFFFF0000u; key[2] = rv.y << 16; key[3] = rv.y & 0xFFFF0000u;
      key[4] = rv.z << 16; key[5] = rv.z & 0xFFFF0000u; key[6] = rv.w << 16; key[7] = rv.w & 0xFFFF0000u;
      uint32_t cnt = 0, pos;
#pragma unroll
      for (int i = 0; i < 8; i++) cnt += key[i] >= tau ? 4 : 0;
      asm volatile("atom.shared.add.u32 %0, [%1], %2;" : "=r"(pos) : "r"(MISC_CNT), "r"(cnt) : "memory");
#pragma unroll
      for (int i = 0; i < 8; i++) if (key[i] >= tau) { sts32(OFF_CAND + pos, key[i] | (ib - i)); pos += 4; }
    }
  } else {
    LOAD_WA();
    PERM_WD();
  }
  __syncthreads();
  TS(8);
  {
    const int n4 = (int)lds32(MISC_CNT);
    const uint32_t first = lds32(OFF_CAND + lane * 4);
#pragma unroll 1
    for (int j = warp * 4; j < n4; j += 64) {
      const uint32_t mine = lds32(OFF_CAND + j);
      int rank = __popc(__ballot_sync(0xffffffffu, lane * 4 < n4 && first > mine));
#pragma unroll 1
      for (int b = 128; b < n4; b += 128) rank += __popc(__ballot_sync(0xffffffffu, b + lane * 4 < n4 && lds32(OFF_CAND + b + lane * 4) > mine));
      if (rank < 8) {
        const uint4* src = (const uint4*)(p.s->ROW + (2047 - (int)(mine & 0xFFFFu)) * 288) + lane;
        const uint4* src2 = src + (lane < 8 ? 64 : 0);
        uint4 v[3];
        v[0] = ldr128(src); v[1] = ldr128(src + 32); v[2] = ldr128(src2);
        if (lane == 0) sts32(MISC_SEL + rank * 4, mine);
        const uint32_t em = (epoch & 1u) ? ~0u : 0u;
#define BADV(q) ((q.x ^ em) | (q.y ^ em) | (q.z ^ em) | (q.w ^ em))
        SPIN_WHILE((BADV(v[0]) | BADV(v[1]) | BADV(v[2])) & 1u, v[0] = ldr128(src); v[1] = ldr128(src + 32); v[2] = ldr128(src2));
#undef BADV
#pragma unroll
        for (int r = 0; r < 3; r++) {
          const float2 f0 = h2f(v[r].x & ~1u), f1 = h2f(v[r].y & ~1u), f2 = h2f(v[r].z & ~1u), f3 = h2f(v[r].w & ~1u);
          if (r < 2 || lane < 8)
            sts128(OFF_XS + rank * 1168 + (lane + 32 * r) * 16, pack_bf(f0.x, f0.y), pack_bf(f1.x, f1.y), pack_bf(f2.x, f2.y), pack_bf(f3.x, f3.y));
        }
      }
    }
    if (warp >= 8) {
      if (warp < 15) LOAD_WA();
      if (warp == 8) PERM_WD();
    }
  }
  __syncthreads();
  TS(9);

  if (warp < 15) {
    float d0[4] = {0.f, 0.f, 0.f, 0.f}, d1[4] = {0.f, 0.f, 0.f, 0.f};
    const uint32_t xb = OFF_XS + (lane & 7) * 1168 + (fk * 24 + (lane >> 3)) * 16;
#pragma unroll
    for (int k = 0; k < 12; k += 2) {
      uint32_t b0, b1, b2, b3;
      ldsm4(xb + k * 32, b0, b1, b2, b3);
      mma_bf16(d0, wa[k][0], wa[k][1], wa[k][2], wa[k][3], b0, b1);
      mma_bf16(d1, wa[k + 1][0], wa[k + 1][1], wa[k + 1][2], wa[k + 1][3], b2, b3);
    }
    sts128(OFF_RED + warp * 512 + lane * 16, __float_as_uint(d0[0] + d1[0]), __float_as_uint(d0[1] + d1[1]), __float_as_uint(d0[2] + d1[2]), __float_as_uint(d0[3] + d1[3]));
  }
  const uint32_t selkey = lds32(MISC_SEL + (lane & 7) * 4);
  __syncthreads();
  if (warp >= 11) {
    const uint32_t rb = OFF_RED + (warp - 11) * 1536 + lane * 16;
    const uint4 pa = lds128(rb), pb = lds128(rb + 512), pc = lds128(rb + 1024);
    const float ga = bfr(__uint_as_float(pa.x) + __uint_as_float(pb.x) + __uint_as_float(pc.x));
    const float gb = bfr(__uint_as_float(pa.y) + __uint_as_float(pb.y) + __uint_as_float(pc.y));
    const uint32_t uu = pack_bf(__uint_as_float(pa.z) + __uint_as_float(pb.z) + __uint_as_float(pc.z), __uint_as_float(pa.w) + __uint_as_float(pb.w) + __uint_as_float(pc.w));
    float ra, rb2;
    asm("rcp.approx.ftz.f32 %0, %1;" : "=f"(ra) : "f"(1.f + ex2(ga * -1.4426950408889634f)));
    asm("rcp.approx.ftz.f32 %0, %1;" : "=f"(rb2) : "f"(1.f + ex2(gb * -1.4426950408889634f)));
    const uint32_t act = bf_mul2(pack_bf(ga * ra, gb * rb2), uu);
    sts32(OFF_ACT + (warp - 11) * 128 + lane * 4, (warp == 15 && five) ? 0u : act);
    bar_arrive(7, 14 * 32);
  } else if (warp < 9) {
    bar_sync(7, 14 * 32);
    uint32_t b0, b1, b2, b3, b4;
    ldsm4t(OFF_ACT + lane * 16, b0, b1, b2, b3);
    asm volatile("ldmatrix.sync.aligned.m8n8.x1.trans.shared.b16 {%0}, [%1];" : "=r"(b4) : "r"(OFF_ACT + 512 + (lane & 7) * 16) : "memory");
    float y[4][4];
#pragma unroll
    for (int j = 0; j < 4; j++) {
      y[j][0] = y[j][1] = y[j][2] = y[j][3] = 0.f;
      mma_bf16(y[j], wd[0][2 * j], wd[0][2 * j + 1], wd[1][2 * j], wd[1][2 * j + 1], b0, b1);
    }
#pragma unroll
    for (int j = 0; j < 4; j++) mma_bf16(y[j], wd[2][2 * j], wd[2][2 * j + 1], wd[3][2 * j], wd[3][2 * j + 1], b2, b3);
#pragma unroll
    for (int j = 0; j < 4; j++) mma_bf16_k8(y[j], wd[4][2 * j], wd[4][2 * j + 1], b4);
    uint4* dst = &p.s->P[c * 576 + (warp * 8 + g) * 8 + t];
    str128(dst, pack_bf(y[0][0], y[0][1]), pack_bf(y[0][2], y[0][3]), pack_bf(y[1][0], y[1][1]), pack_bf(y[1][2], y[1][3]));
    str128(dst + 4, pack_bf(y[2][0], y[2][1]), pack_bf(y[2][2], y[2][3]), pack_bf(y[3][0], y[3][1]), pack_bf(y[3][2], y[3][3]));
  }
  TS(10);
  {
    const uint32_t hit = __ballot_sync(0xffffffffu, (int)(selkey & 0xFFFFu) == 2047 - tok);
    uint32_t* o = (hit ? (uint32_t*)p.s->HS + (__ffs(hit) - 1) * 288 : p.out + tok * 288) + lane;
    const uint32_t sa = stash + (hit ? 4 : 0);
#pragma unroll
    for (int i = 0; i < 9; i++) str32(o + 32 * i, lds32(sa + i * 256));
  }

  if (c < 72) {
    const uint4* src = &p.s->P[(warp * 4 + t) * 576 + c * 8 + g];
    uint4 v0 = ldr128(src), v1 = ldr128(src + 64 * 576);
    const uint32_t* hsrc = (const uint32_t*)p.s->HS + g * 288 + c * 4 + t;
    uint32_t hv = 0;
    if (warp == 0) hv = ldr32(hsrc);
    const uint32_t sel = (g & 1) ? 0x3F800000u : 0x00003F80u;
    SPIN_WHILE(v0.x == ~0u || v1.x == ~0u, v0 = ldr128(src); v1 = ldr128(src + 64 * 576));
    float d[4] = {0.f, 0.f, 0.f, 0.f};
    {
      const uint32_t s0 = (g >> 1) == 0 ? sel : 0u, s1 = (g >> 1) == 1 ? sel : 0u, s2 = (g >> 1) == 2 ? sel : 0u, s3 = (g >> 1) == 3 ? sel : 0u;
      mma_bf16(d, s0, 0u, s0, 0u, v0.x, v1.x); mma_bf16(d, s1, 0u, s1, 0u, v0.y, v1.y);
      mma_bf16(d, s2, 0u, s2, 0u, v0.z, v1.z); mma_bf16(d, s3, 0u, s3, 0u, v0.w, v1.w);
    }
    {
      const uint32_t fb = OFF_FIN + warp * 256 + ((4 * (t & 1) + (g & 1)) * 8 + 4 * (t >> 1) + (g >> 1)) * 4;
      sts32(fb, __float_as_uint(d[0])); sts32(fb + 64, __float_as_uint(d[1]));
    }
    __syncthreads();
    TS(11);
    if (warp == 0) {
      float s0 = 0.f, s1 = 0.f;
#pragma unroll
      for (int i = 0; i < 16; i++) { const uint2 q = lds64(OFF_FIN + i * 256 + lane * 8); s0 += __uint_as_float(q.x); s1 += __uint_as_float(q.y); }
      const uint32_t key = __shfl_sync(0xffffffffu, selkey, g);
      const uint32_t k16 = key >> 16;
      const float r = bf_lo((k16 & 0x8000u) ? (k16 & 0x7FFFu) : (~k16 & 0xFFFFu));
      float rs;
      asm("rcp.approx.ftz.f32 %0, %1;" : "=f"(rs) : "f"(1.f + ex2(r * -1.4426950408889634f)));
      const uint32_t upd = bf_mul2(pack_bf(s0, s1), pack_bf(rs, rs));
      const uint32_t ln = lds32(OFF_XS + g * 1168 + c * 16 + t * 4);
      SPIN_WHILE(hv == ~0u, hv = ldr32(hsrc));
      p.out[(2047 - (int)(key & 0xFFFFu)) * 288 + c * 4 + t] = bf_add2(hv, bf_add2(ln, upd));
    }
  }
  TS(12);
}

typedef CUresult (*EncodeFn)(CUtensorMap*, CUtensorMapDataType, cuuint32_t, void*, const cuuint64_t*, const cuuint64_t*, const cuuint32_t*,
                             const cuuint32_t*, CUtensorMapInterleave, CUtensorMapSwizzle, CUtensorMapL2promotion, CUtensorMapFloatOOBfill);

}

extern "C" void kernel_launch(void* const* d_in, const int* in_sizes, int n_in, void* d_out, int out_size) {
  (void)in_sizes; (void)n_in; (void)out_size;
  static EncodeFn enc = nullptr;
  static Scratch* scratch = nullptr;
  if (!enc) {
    void* fn = nullptr;
    cudaDriverEntryPointQueryResult qr;
    cudaGetDriverEntryPoint("cuTensorMapEncodeTiled", &fn, cudaEnableDefault, &qr);
    enc = (EncodeFn)fn;
    cudaGetSymbolAddress((void**)&scratch, g_S);
    cudaFuncSetAttribute(fused_kernel, cudaFuncAttributeMaxDynamicSharedMemorySize, SMEM_BYTES);
  }
  CUtensorMap tm[2];
  for (int i = 0; i < 2; i++) {
    cuuint64_t gd[2] = {FF, DM};
    cuuint64_t gs[1] = {FF * 2};
    cuuint32_t bx[2] = {40, 192};
    cuuint32_t es[2] = {1, 1};
    enc(&tm[i], CU_TENSOR_MAP_DATA_TYPE_BFLOAT16, 2, d_in[11 + i], gd, gs, bx, es, CU_TENSOR_MAP_INTERLEAVE_NONE, CU_TENSOR_MAP_SWIZZLE_NONE,
        CU_TENSOR_MAP_L2_PROMOTION_L2_128B, CU_TENSOR_MAP_FLOAT_OOB_FILL_NONE);
  }
  Params p;
  p.x = (const uint32_t*)d_in[0];
  for (int i = 0; i < 6; i++) p.ssm[i] = (const unsigned char*)d_in[1 + i];
  p.log_dt = (const uint16_t*)d_in[7];
  p.dskip = (const uint32_t*)d_in[8];
  p.w_r = (const uint32_t*)d_in[10];
  p.w_gate = (const unsigned char*)d_in[11];
  p.w_up = (const unsigned char*)d_in[12];
  p.w_down = (const unsigned char*)d_in[13];
  p.out = (uint32_t*)d_out;
  p.zero = 0;
  p.s = scratch;
  fused_kernel<<<NCTA, NT, SMEM_BYTES, cudaStreamPerThread>>>(p, tm[0], tm[1]);
}
```

```cpp
#include <cuda_runtime.h>
#include <cuda.h>
#include <cuda_bf16.h>
#include <cuda_fp16.h>
#include <stdint.h>
#include <stddef.h>

namespace {

constexpr int NCTA = 128;
constexpr int NT = 512;
constexpr int DM = 576;
constexpr int FF = 4608;
constexpr int SPIN_MAX = 1 << 20;

struct Scratch {
  uint4 U2[NCTA * DM * 2];
  uint4 Y2[NCTA * DM * 2];
  uint4 P[NCTA * 576];
  uint4 HS[1152];
  uint4 R[256];
  uint32_t FLAG[NCTA * 8];
};
__device__ Scratch g_S;

#define TS(i)
#define TS_DUMP()

constexpr int SB = 1024;
constexpr int BOX = 192 * 80;
constexpr int OFF_G = SB;
constexpr int OFF_W = OFF_G + 3 * BOX;
constexpr int W_EX = BOX;
constexpr int EX_PLANE = 2112, EX_WARP = 4224;
constexpr int KT_WORDS = 1104;
constexpr int L3_ARR = 320;
constexpr int W_KT = 28672;
constexpr int W_L3 = W_KT + KT_WORDS * 4;
constexpr int UP_PAD = 32;
constexpr int UP_PLANE = (128 + UP_PAD) * 16;
constexpr int W_UP = W_L3 + 4 * L3_ARR;
constexpr int W_KC = W_UP + 2 * UP_PLANE;
constexpr int W_MISC = W_KC + 1344;
constexpr int W_BYTES = 40960;
constexpr int ALT = -W_KT;
constexpr int UPP_BYTES = 2304;
static_assert(W_MISC + 48 <= W_BYTES && W_BYTES % 128 == 0 && W_KC + ALT + UPP_BYTES <= W_EX && W_EX + 4 * EX_WARP <= W_L3, "wg block");
constexpr int YT_PITCH = 1184;
constexpr int OFF_YT = OFF_W + 4 * W_BYTES;
constexpr int OFF_ATAB = OFF_YT + 16 * YT_PITCH + 64;
constexpr int OFF_MISC = OFF_ATAB + 2048;
constexpr int SMEM_BYTES = OFF_MISC + 1024 - SB;
static_assert(OFF_W % 128 == 0 && OFF_YT % 16 == 0 && OFF_MISC % 16 == 0, "align");
static_assert(SMEM_BYTES <= 232448, "smem");
constexpr int OFF_PAR_END = OFF_G + 2 * BOX + 2560 + 20 * 416;
constexpr int MISC_MBAR = OFF_MISC;
constexpr int MISC_MBU = OFF_MISC + 8;
constexpr int MISC_MBWIN = OFF_MISC + 16;
constexpr int MISC_MBK = OFF_MISC + 24;
constexpr int MISC_WMAX = OFF_MISC + 48;
constexpr int MISC_CNT = OFF_MISC + 80;
constexpr int MISC_SEL = OFF_MISC + 96;
constexpr int MISC_RK = OFF_MISC + 128;
constexpr int MISC_LN1 = OFF_MISC + 256;
constexpr int MISC_MBW = OFF_PAR_END;
constexpr int OFF_XS = OFF_W;
constexpr int OFF_FIN = OFF_XS + 8 * 1168;
constexpr int OFF_ACT = OFF_FIN + 4096;
constexpr int OFF_RED = OFF_W + W_KT;
constexpr int OFF_CAND = OFF_W + W_BYTES + W_KT;
static_assert(OFF_ACT + 768 <= OFF_W + W_EX && W_KT + 8192 <= W_BYTES, "alias");
constexpr int OFF_ONES = OFF_G + 2 * BOX;
constexpr int OFF_PAR = OFF_ONES + 2560;

__device__ __forceinline__ uint32_t smem_u32(const void* p) { return (uint32_t)__cvta_generic_to_shared(p); }
__device__ __forceinline__ uint32_t lds32(uint32_t a) { uint32_t v; asm volatile("ld.shared.b32 %0, [%1];" : "=r"(v) : "r"(a) : "memory"); return v; }
__device__ __forceinline__ uint32_t lds16(uint32_t a) { uint16_t v; asm volatile("ld.shared.u16 %0, [%1];" : "=h"(v) : "r"(a) : "memory"); return v; }
__device__ __forceinline__ uint2 lds64(uint32_t a) { uint2 v; asm volatile("ld.shared.v2.b32 {%0,%1}, [%2];" : "=r"(v.x), "=r"(v.y) : "r"(a) : "memory"); return v; }
__device__ __forceinline__ uint4 lds128(uint32_t a) { uint4 v; asm volatile("ld.shared.v4.b32 {%0,%1,%2,%3}, [%4];" : "=r"(v.x), "=r"(v.y), "=r"(v.z), "=r"(v.w) : "r"(a) : "memory"); return v; }
__device__ __forceinline__ void sts16(uint32_t a, uint32_t v) { asm volatile("st.shared.u16 [%0], %1;" :: "r"(a), "h"((uint16_t)v) : "memory"); }
__device__ __forceinline__ void sts32(uint32_t a, uint32_t v) { asm volatile("st.shared.b32 [%0], %1;" :: "r"(a), "r"(v) : "memory"); }
__device__ __forceinline__ void sts64(uint32_t a, uint32_t x, uint32_t y) { asm volatile("st.shared.v2.b32 [%0], {%1,%2};" :: "r"(a), "r"(x), "r"(y) : "memory"); }
__device__ __forceinline__ void sts128(uint32_t a, uint32_t x, uint32_t y, uint32_t z, uint32_t w) { asm volatile("st.shared.v4.b32 [%0], {%1,%2,%3,%4};" :: "r"(a), "r"(x), "r"(y), "r"(z), "r"(w) : "memory"); }
__device__ __forceinline__ void ldsm4(uint32_t a, uint32_t& r0, uint32_t& r1, uint32_t& r2, uint32_t& r3) {
  asm volatile("ldmatrix.sync.aligned.m8n8.x4.shared.b16 {%0,%1,%2,%3}, [%4];" : "=r"(r0), "=r"(r1), "=r"(r2), "=r"(r3) : "r"(a) : "memory");
}
__device__ __forceinline__ void ldsm2(uint32_t a, uint32_t& r0, uint32_t& r1) {
  asm volatile("ldmatrix.sync.aligned.m8n8.x2.shared.b16 {%0,%1}, [%2];" : "=r"(r0), "=r"(r1) : "r"(a) : "memory");
}
__device__ __forceinline__ void ldsm4t(uint32_t a, uint32_t& r0, uint32_t& r1, uint32_t& r2, uint32_t& r3) {
  asm volatile("ldmatrix.sync.aligned.m8n8.x4.trans.shared.b16 {%0,%1,%2,%3}, [%4];" : "=r"(r0), "=r"(r1), "=r"(r2), "=r"(r3) : "r"(a) : "memory");
}
__device__ __forceinline__ void stsm4t(uint32_t a, uint32_t r0, uint32_t r1, uint32_t r2, uint32_t r3) {
  asm volatile("stmatrix.sync.aligned.m8n8.x4.trans.shared.b16 [%0], {%1,%2,%3,%4};" :: "r"(a), "r"(r0), "r"(r1), "r"(r2), "r"(r3) : "memory");
}
__device__ __forceinline__ uint4 ldr128(const void* p) {
  unsigned long long lo, hi;
  asm volatile("{ .reg .b128 t; ld.relaxed.gpu.global.b128 t, [%2]; mov.b128 {%0, %1}, t; }" : "=l"(lo), "=l"(hi) : "l"(p) : "memory");
  return make_uint4((uint32_t)lo, (uint32_t)(lo >> 32), (uint32_t)hi, (uint32_t)(hi >> 32));
}
__device__ __forceinline__ void str128(void* p, uint32_t x, uint32_t y, uint32_t z, uint32_t w) {
  asm volatile("{ .reg .b128 t; .reg .b64 lo, hi; mov.b64 lo, {%1,%2}; mov.b64 hi, {%3,%4}; mov.b128 t, {lo, hi}; st.relaxed.gpu.global.b128 [%0], t; }"
               :: "l"(p), "r"(x), "r"(y), "r"(z), "r"(w) : "memory");
}
__device__ __forceinline__ void str64(void* p, uint32_t x, uint32_t y) {
  asm volatile("{ .reg .b64 t; mov.b64 t, {%1,%2}; st.relaxed.gpu.global.b64 [%0], t; }" :: "l"(p), "r"(x), "r"(y) : "memory");
}
__device__ __forceinline__ uint32_t ldr32(const void* p) { uint32_t v; asm volatile("ld.relaxed.gpu.global.b32 %0, [%1];" : "=r"(v) : "l"(p) : "memory"); return v; }
__device__ __forceinline__ void str32(void* p, uint32_t v) { asm volatile("st.relaxed.gpu.global.b32 [%0], %1;" :: "l"(p), "r"(v) : "memory"); }
__device__ __forceinline__ void str16(void* p, uint32_t v) { asm volatile("st.relaxed.gpu.global.u16 [%0], %1;" :: "l"(p), "h"((uint16_t)v) : "memory"); }
__device__ __forceinline__ void fence_gpu() { asm volatile("fence.acq_rel.gpu;" ::: "memory"); }
__device__ __forceinline__ void bar_sync(int id, int n) { asm volatile("bar.sync %0, %1;" :: "r"(id), "r"(n) : "memory"); }
__device__ __forceinline__ void bar_arrive(int id, int n) { asm volatile("bar.arrive %0, %1;" :: "r"(id), "r"(n) : "memory"); }

__device__ __forceinline__ float bf_lo(uint32_t w) { return __uint_as_float(w << 16); }
__device__ __forceinline__ float bf_hi(uint32_t w) { return __uint_as_float(w & 0xFFFF0000u); }
__device__ __forceinline__ uint32_t pack_bf(float lo, float hi) { uint32_t r; asm("cvt.rn.bf16x2.f32 %0, %1, %2;" : "=r"(r) : "f"(hi), "f"(lo)); return r; }
__device__ __forceinline__ uint32_t pack_h(float lo, float hi) { uint32_t r; asm("cvt.rn.f16x2.f32 %0, %1, %2;" : "=r"(r) : "f"(hi), "f"(lo)); return r; }
__device__ __forceinline__ float bfr(float x) { return bf_lo(pack_bf(x, 0.f)); }
__device__ __forceinline__ uint32_t bf_sub2(uint32_t a, uint32_t b) { __nv_bfloat162 r = __hsub2(*(__nv_bfloat162*)&a, *(__nv_bfloat162*)&b); return *(uint32_t*)&r; }
__device__ __forceinline__ uint32_t bf_add2(uint32_t a, uint32_t b) { __nv_bfloat162 r = __hadd2(*(__nv_bfloat162*)&a, *(__nv_bfloat162*)&b); return *(uint32_t*)&r; }
__device__ __forceinline__ uint32_t bf_mul2(uint32_t a, uint32_t b) { __nv_bfloat162 r = __hmul2(*(__nv_bfloat162*)&a, *(__nv_bfloat162*)&b); return *(uint32_t*)&r; }
__device__ __forceinline__ float2 h2f(uint32_t w) { return __half22float2(*(__half2*)&w); }
__device__ __forceinline__ float ex2(float x) { float r; asm("ex2.approx.ftz.f32 %0, %1;" : "=f"(r) : "f"(x)); return r; }
__device__ __forceinline__ float warp_sum(float v) {
#pragma unroll
  for (int o = 16; o > 0; o >>= 1) v += __shfl_xor_sync(0xffffffffu, v, o);
  return v;
}
__device__ __forceinline__ void mma_f16_f32(float* d, uint32_t a0, uint32_t a1, uint32_t a2, uint32_t a3, uint32_t b0, uint32_t b1) {
  asm volatile("mma.sync.aligned.m16n8k16.row.col.f32.f16.f16.f32 {%0,%1,%2,%3}, {%4,%5,%6,%7}, {%8,%9}, {%0,%1,%2,%3};"
               : "+f"(d[0]), "+f"(d[1]), "+f"(d[2]), "+f"(d[3]) : "r"(a0), "r"(a1), "r"(a2), "r"(a3), "r"(b0), "r"(b1));
}
__device__ __forceinline__ void mma_f16_f16(uint32_t& d0, uint32_t& d1, uint32_t a0, uint32_t a1, uint32_t a2, uint32_t a3, uint32_t b0, uint32_t b1) {
  asm volatile("mma.sync.aligned.m16n8k16.row.col.f16.f16.f16.f16 {%0,%1}, {%2,%3,%4,%5}, {%6,%7}, {%0,%1};"
               : "+r"(d0), "+r"(d1) : "r"(a0), "r"(a1), "r"(a2), "r"(a3), "r"(b0), "r"(b1));
}
__device__ __forceinline__ void mma_bf16(float* d, uint32_t a0, uint32_t a1, uint32_t a2, uint32_t a3, uint32_t b0, uint32_t b1) {
  asm volatile("mma.sync.aligned.m16n8k16.row.col.f32.bf16.bf16.f32 {%0,%1,%2,%3}, {%4,%5,%6,%7}, {%8,%9}, {%0,%1,%2,%3};"
               : "+f"(d[0]), "+f"(d[1]), "+f"(d[2]), "+f"(d[3]) : "r"(a0), "r"(a1), "r"(a2), "r"(a3), "r"(b0), "r"(b1));
}
__device__ __forceinline__ void mma_bf16_k8(float* d, uint32_t a0, uint32_t a1, uint32_t b0) {
  asm volatile("mma.sync.aligned.m16n8k8.row.col.f32.bf16.bf16.f32 {%0,%1,%2,%3}, {%4,%5}, {%6}, {%0,%1,%2,%3};"
               : "+f"(d[0]), "+f"(d[1]), "+f"(d[2]), "+f"(d[3]) : "r"(a0), "r"(a1), "r"(b0));
}

__device__ __forceinline__ void wg_fence() { asm volatile("wgmma.fence.sync.aligned;" ::: "memory"); }
__device__ __forceinline__ void wg_commit() { asm volatile("wgmma.commit_group.sync.aligned;" ::: "memory"); }
template <int N> __device__ __forceinline__ void wg_wait() { asm volatile("wgmma.wait_group.sync.aligned %0;" :: "n"(N) : "memory"); }
template <int TB> __device__ __forceinline__ void wgmma32(float* d, const uint32_t* a, uint32_t dlo, uint32_t dhi) {
  asm volatile("{ .reg .b64 dd; mov.b64 dd, {%20, %21}; wgmma.mma_async.sync.aligned.m64n32k16.f32.f16.f16 "
               "{%0,%1,%2,%3,%4,%5,%6,%7,%8,%9,%10,%11,%12,%13,%14,%15}, {%16,%17,%18,%19}, dd, 1, 1, 1, %22; }"
               : "+f"(d[0]), "+f"(d[1]), "+f"(d[2]), "+f"(d[3]), "+f"(d[4]), "+f"(d[5]), "+f"(d[6]), "+f"(d[7]), "+f"(d[8]), "+f"(d[9]), "+f"(d[10]), "+f"(d[11]), "+f"(d[12]), "+f"(d[13]), "+f"(d[14]), "+f"(d[15])
               : "r"(a[0]), "r"(a[1]), "r"(a[2]), "r"(a[3]), "r"(dlo), "r"(dhi), "n"(TB));
}
template <int TB> __device__ __forceinline__ void wgmma96(float* d, const uint32_t* a, uint32_t dlo, uint32_t dhi) {
  asm volatile("{ .reg .b64 dd; mov.b64 dd, {%52, %53}; wgmma.mma_async.sync.aligned.m64n96k16.f32.f16.f16 "
               "{%0,%1,%2,%3,%4,%5,%6,%7,%8,%9,%10,%11,%12,%13,%14,%15,%16,%17,%18,%19,%20,%21,%22,%23,%24,%25,%26,%27,%28,%29,%30,%31,%32,%33,%34,%35,%36,%37,%38,%39,%40,%41,%42,%43,%44,%45,%46,%47}, {%48,%49,%50,%51}, dd, 1, 1, 1, %54; }"
               : "+f"(d[0]), "+f"(d[1]), "+f"(d[2]), "+f"(d[3]), "+f"(d[4]), "+f"(d[5]), "+f"(d[6]), "+f"(d[7]), "+f"(d[8]), "+f"(d[9]), "+f"(d[10]), "+f"(d[11]), "+f"(d[12]), "+f"(d[13]), "+f"(d[14]), "+f"(d[15]), "+f"(d[16]), "+f"(d[17]), "+f"(d[18]), "+f"(d[19]), "+f"(d[20]), "+f"(d[21]), "+f"(d[22]), "+f"(d[23]), "+f"(d[24]), "+f"(d[25]), "+f"(d[26]), "+f"(d[27]), "+f"(d[28]), "+f"(d[29]), "+f"(d[30]), "+f"(d[31]), "+f"(d[32]), "+f"(d[33]), "+f"(d[34]), "+f"(d[35]), "+f"(d[36]), "+f"(d[37]), "+f"(d[38]), "+f"(d[39]), "+f"(d[40]), "+f"(d[41]), "+f"(d[42]), "+f"(d[43]), "+f"(d[44]), "+f"(d[45]), "+f"(d[46]), "+f"(d[47])
               : "r"(a[0]), "r"(a[1]), "r"(a[2]), "r"(a[3]), "r"(dlo), "r"(dhi), "n"(TB));
}
template <int TB> __device__ __forceinline__ void wgmma96_init(float* d, const uint32_t* a, uint32_t dlo, uint32_t dhi) {
  asm volatile("{ .reg .b64 dd; mov.b64 dd, {%52, %53}; wgmma.mma_async.sync.aligned.m64n96k16.f32.f16.f16 "
               "{%0,%1,%2,%3,%4,%5,%6,%7,%8,%9,%10,%11,%12,%13,%14,%15,%16,%17,%18,%19,%20,%21,%22,%23,%24,%25,%26,%27,%28,%29,%30,%31,%32,%33,%34,%35,%36,%37,%38,%39,%40,%41,%42,%43,%44,%45,%46,%47}, {%48,%49,%50,%51}, dd, 0, 1, 1, %54; }"
               : "=f"(d[0]), "=f"(d[1]), "=f"(d[2]), "=f"(d[3]), "=f"(d[4]), "=f"(d[5]), "=f"(d[6]), "=f"(d[7]), "=f"(d[8]), "=f"(d[9]), "=f"(d[10]), "=f"(d[11]), "=f"(d[12]), "=f"(d[13]), "=f"(d[14]), "=f"(d[15]), "=f"(d[16]), "=f"(d[17]), "=f"(d[18]), "=f"(d[19]), "=f"(d[20]), "=f"(d[21]), "=f"(d[22]), "=f"(d[23]), "=f"(d[24]), "=f"(d[25]), "=f"(d[26]), "=f"(d[27]), "=f"(d[28]), "=f"(d[29]), "=f"(d[30]), "=f"(d[31]), "=f"(d[32]), "=f"(d[33]), "=f"(d[34]), "=f"(d[35]), "=f"(d[36]), "=f"(d[37]), "=f"(d[38]), "=f"(d[39]), "=f"(d[40]), "=f"(d[41]), "=f"(d[42]), "=f"(d[43]), "=f"(d[44]), "=f"(d[45]), "=f"(d[46]), "=f"(d[47])
               : "r"(a[0]), "r"(a[1]), "r"(a[2]), "r"(a[3]), "r"(dlo), "r"(dhi), "n"(TB));
}
template <int TB> __device__ __forceinline__ void wgmma32_init(float* d, const uint32_t* a, uint32_t dlo, uint32_t dhi) {
  asm volatile("{ .reg .b64 dd; mov.b64 dd, {%20, %21}; wgmma.mma_async.sync.aligned.m64n32k16.f32.f16.f16 "
               "{%0,%1,%2,%3,%4,%5,%6,%7,%8,%9,%10,%11,%12,%13,%14,%15}, {%16,%17,%18,%19}, dd, 0, 1, 1, %22; }"
               : "=f"(d[0]), "=f"(d[1]), "=f"(d[2]), "=f"(d[3]), "=f"(d[4]), "=f"(d[5]), "=f"(d[6]), "=f"(d[7]), "=f"(d[8]), "=f"(d[9]), "=f"(d[10]), "=f"(d[11]), "=f"(d[12]), "=f"(d[13]), "=f"(d[14]), "=f"(d[15])
               : "r"(a[0]), "r"(a[1]), "r"(a[2]), "r"(a[3]), "r"(dlo), "r"(dhi), "n"(TB));
}
__device__ __forceinline__ void wgmma16_ss(float* d, uint32_t alo, uint32_t blo, uint32_t hi) {
  asm volatile("{ .reg .b64 da, db; mov.b64 da, {%8, %10}; mov.b64 db, {%9, %10}; "
               "wgmma.mma_async.sync.aligned.m64n16k16.f32.f16.f16 {%0,%1,%2,%3,%4,%5,%6,%7}, da, db, 1, 1, 1, 1, 1; }"
               : "+f"(d[0]), "+f"(d[1]), "+f"(d[2]), "+f"(d[3]), "+f"(d[4]), "+f"(d[5]), "+f"(d[6]), "+f"(d[7])
               : "r"(alo), "r"(blo), "r"(hi));
}
__device__ __forceinline__ float vzero() { float v; asm volatile("mov.b32 %0, 0;" : "=f"(v)); return v; }
__device__ __forceinline__ void tma_box(uint32_t dst, const CUtensorMap* tm, uint32_t mb, int x, int y) {
  asm volatile("cp.async.bulk.tensor.2d.shared::cluster.global.mbarrier::complete_tx::bytes [%0], [%1, {%3, %4}], [%2];"
               :: "r"(dst), "l"(tm), "r"(mb), "r"(x), "r"(y) : "memory");
}
__device__ __forceinline__ void l2_prefetch(const void* src, uint32_t bytes) {
  asm volatile("cp.async.bulk.prefetch.L2.global [%0], %1;" :: "l"(src), "r"(bytes) : "memory");
}
__device__ __forceinline__ uint32_t uni(uint32_t v) {
  uint32_t r; asm volatile("shfl.sync.idx.b32 %0, %1, 0, 0x1f, 0xffffffff;" : "=r"(r) : "r"(v)); return r;
}
__device__ __forceinline__ int fresh_tid() { int v; asm volatile("mov.u32 %0, %tid.x;" : "=r"(v)); return v; }

struct Params {
  const uint32_t* x;
  Scratch* s;
  const unsigned char* ssm[6];
  const uint16_t* log_dt;
  const uint32_t* dskip;
  const uint32_t* w_r;
  const unsigned char* w_gate;
  const unsigned char* w_up;
  const unsigned char* w_down;
  uint32_t* out;
  long long* ts;
  uint32_t zero;
};
__device__ __forceinline__ uint32_t ldnc32(const void* p) { uint32_t v; asm volatile("ld.global.nc.b32 %0, [%1];" : "=r"(v) : "l"(p)); return v; }
__device__ __forceinline__ uint32_t ldnc16(const void* p) { uint16_t v; asm volatile("ld.global.nc.u16 %0, [%1];" : "=h"(v) : "l"(p)); return v; }
__device__ __forceinline__ uint4 ldnc128(const void* p) { uint4 v; asm volatile("ld.global.nc.v4.b32 {%0,%1,%2,%3}, [%4];" : "=r"(v.x), "=r"(v.y), "=r"(v.z), "=r"(v.w) : "l"(p)); return v; }
__device__ __forceinline__ void mbar_wait(uint32_t mb) {
#pragma unroll 1
  for (int it = 0; it < SPIN_MAX; it++) {
    uint32_t ok;
    asm volatile("{ .reg .pred q; mbarrier.try_wait.parity.shared::cta.b64 q, [%1], 0; selp.u32 %0, 1, 0, q; }" : "=r"(ok) : "r"(mb) : "memory");
    if (ok) break;
  }
}
__device__ __forceinline__ void mbar_wait_warp(uint32_t mb) {
#pragma unroll 1
  for (int it = 0; it < SPIN_MAX; it++) {
    uint32_t ok;
    asm volatile("{ .reg .pred q; mbarrier.try_wait.parity.shared::cta.b64 q, [%1], 0; selp.u32 %0, 1, 0, q; }" : "=r"(ok) : "r"(mb) : "memory");
    if (__all_sync(0xffffffffu, ok)) break;
  }
}
__device__ __forceinline__ void mbar_arrive(uint32_t mb) { asm volatile("mbarrier.arrive.shared::cta.b64 _, [%0];" :: "r"(mb) : "memory"); }
__device__ __forceinline__ void bulk_clear(void* dst, uint32_t bytes) {
  asm volatile("cp.async.bulk.global.shared::cta.bulk_group [%0], [%1], %2;" :: "l"(dst), "r"(OFF_ONES), "r"(bytes) : "memory");
  asm volatile("cp.async.bulk.commit_group;" ::: "memory");
}
#define SPIN_WHILE(cond, body) _Pragma("unroll 1") for (int _it = 0; _it < SPIN_MAX && __any_sync(0xffffffffu, (cond)); _it++) { body; }

struct LnC { uint32_t m2, rh2, rl2; };
__device__ __forceinline__ float diag_sum(float d0, float d1, int t) {
  float q = __shfl_sync(0xffffffffu, d0, 9 * t) + __shfl_sync(0xffffffffu, d1, 9 * t + 4);
  q += __shfl_xor_sync(0xffffffffu, q, 1);
  return q + __shfl_xor_sync(0xffffffffu, q, 2);
}
__device__ __forceinline__ LnC ln_consts(float s, float q, float& r) {
  const float mean = s * (1.f / DM);
  const float var = fmaxf(fmaf(-mean, mean, q * (1.f / DM)), 0.f);
  float sd;
  asm("sqrt.approx.ftz.f32 %0, %1;" : "=f"(sd) : "f"(bfr(bfr(var) + 1e-5f)));
  asm("rcp.approx.ftz.f32 %0, %1;" : "=f"(r) : "f"(bfr(sd)));
  LnC c;
  c.m2 = pack_bf(mean, mean);
  c.rh2 = pack_bf(r, r);
  const float rl = r - bf_lo(c.rh2);
  c.rl2 = pack_bf(rl, rl);
  return c;
}
__device__ __forceinline__ float quad_sum(float s) { s += __shfl_xor_sync(0xffffffffu, s, 1); return s + __shfl_xor_sync(0xffffffffu, s, 2); }
__device__ __forceinline__ uint32_t ln_apply(uint32_t w, const LnC& c) {
  const uint32_t d = bf_sub2(w, c.m2), lo = bf_mul2(d, c.rl2);
  __nv_bfloat162 r = __hfma2(*(const __nv_bfloat162*)&d, *(const __nv_bfloat162*)&c.rh2, *(const __nv_bfloat162*)&lo);
  return *(uint32_t*)&r;
}

__device__ __forceinline__ float2 cis(float mag_log2, float rev) {
  const float m = ex2(mag_log2), ang = rev * 6.283185307179586f;
  return make_float2(m * __cosf(ang), m * __sinf(ang));
}
__device__ __forceinline__ float2 csq(float2 a) { return make_float2(fmaf(a.x, a.x, -a.y * a.y), (a.x + a.x) * a.y); }
__device__ __forceinline__ float2 cmul(float2 a, float2 b) { return make_float2(fmaf(a.x, b.x, -a.y * b.y), fmaf(a.x, b.y, a.y * b.x)); }
__device__ __forceinline__ void pmul(uint32_t xr, uint32_t xi, uint32_t w, uint32_t& yr, uint32_t& yi) {
  const __half2 XR = *(__half2*)&xr, XI = *(__half2*)&xi, W = *(__half2*)&w;
  const __half2 a = __hfma2(__hneg2(XI), __high2half2(W), __hmul2(XR, __low2half2(W)));
  const __half2 b = __hfma2(XI, __low2half2(W), __hmul2(XR, __high2half2(W)));
  yr = *(const uint32_t*)&a; yi = *(const uint32_t*)&b;
}
__device__ __forceinline__ uint32_t pk(float2 a) { return pack_h(a.x, a.y); }
__device__ __forceinline__ uint32_t pkc(float2 a) { return pack_h(a.x, -a.y); }

struct KgState { float2 c0, z16, z64; uint32_t pr[4], pi[4]; };
__device__ __forceinline__ void kgen_tables_a(const uint32_t (&raw)[7], uint32_t scr, int wt, KgState& k) {
  const uint32_t dst = scr + (wt >> 3) * 256 + (wt & 7) * 16;
  const float dt = bfr(ex2(bf_lo(raw[6]) * 1.4426950408889634f));
  const float th = dt * bf_lo(raw[1]);
  const float br = dt * bf_lo(raw[2]), bi = dt * bf_lo(raw[3]);
  const float Cr = bf_lo(raw[4]), Ci = bf_lo(raw[5]);
  k.c0 = make_float2(fmaf(Cr, br, -Ci * bi), fmaf(Cr, bi, Ci * br));
  {
    const uint32_t mx = __reduce_max_sync(0xffffffffu, __float_as_uint(fmaxf(fabsf(k.c0.x), fabsf(k.c0.y))));
    if ((wt & 31) == 0) sts32(scr + W_MISC + (wt >> 5) * 4, mx);
  }
  const float a2 = dt * bf_lo(raw[0]) * 1.4426950408889634f;
  const float rh = th * 0.15915494309189535f;
  const float rl = fmaf(th, (float)(0.15915494309189535 - (double)0.15915494309189535f), fmaf(th, 0.15915494309189535f, -rh));
  const float rf = rh - rintf(rh);
  const float2 z1 = cis(a2, rf + rl);
  const float p64 = rf * 64.f;
  k.z64 = cis(a2 * 64.f, fmaf(64.f, rl, p64 - rintf(p64)));
  const float2 z2 = csq(z1), z4 = csq(z2), z8 = csq(z4);
  k.z16 = csq(z8);
  const float2 z6 = cmul(z4, z2), z10 = cmul(z8, z2), z12 = cmul(z8, z4), z14 = cmul(z8, z6);
  uint32_t yr[4], yi[4];
  k.pr[0] = pack_h(1.f, z8.x);   k.pi[0] = pack_h(0.f, z8.y);
  k.pr[1] = pack_h(z4.x, z12.x); k.pi[1] = pack_h(z4.y, z12.y);
  k.pr[2] = pack_h(z2.x, z10.x); k.pi[2] = pack_h(z2.y, z10.y);
  k.pr[3] = pack_h(z6.x, z14.x); k.pi[3] = pack_h(z6.y, z14.y);
  sts128(dst, k.pr[0], k.pr[1], k.pr[2], k.pr[3]); sts128(dst + 128, k.pi[0], k.pi[1], k.pi[2], k.pi[3]);
  const uint32_t w = pk(z1);
#pragma unroll
  for (int i = 0; i < 4; i++) pmul(k.pr[i], k.pi[i], w, yr[i], yi[i]);
  sts128(dst + 4096, yr[0], yr[1], yr[2], yr[3]); sts128(dst + 4096 + 128, yi[0], yi[1], yi[2], yi[3]);
}
__device__ __forceinline__ void kgen_tables_b(uint32_t scr, int wt, KgState& k) {
  const uint32_t misc = scr + W_MISC;
  const uint32_t dst = scr + (wt >> 3) * 256 + (wt & 7) * 16;
  uint32_t (&pr)[4] = k.pr; uint32_t (&pi)[4] = k.pi;
  uint32_t yr[4], yi[4];
  float2 c0 = k.c0;
  const float2 z16 = k.z16, z64 = k.z64;
  const uint4 e4 = lds128(misc);
  const float2 z128 = csq(z64), z256 = csq(z128), z512 = csq(z256), z1024 = csq(z512), z2048 = csq(z1024);
  {
    const float k2048 = warp_sum(fmaf(c0.x, z2048.x, -c0.y * z2048.y));
    if ((wt & 31) == 0) sts32(misc + 16 + (wt >> 5) * 4, __float_as_uint(k2048));
  }
  {
    const uint32_t w = pk(z256);
#pragma unroll
    for (int i = 0; i < 4; i++) pmul(pr[i], pi[i], w, yr[i], yi[i]);
    sts128(dst + 8192, yr[0], yr[1], yr[2], yr[3]); sts128(dst + 8192 + 128, yi[0], yi[1], yi[2], yi[3]);
  }
  const float2 z768 = cmul(z512, z256);
  {
    const uint32_t wa = pk(z512), wb = pk(z768);
    pmul(pr[0], pi[0], wa, yr[0], yi[0]); pmul(pr[1], pi[1], wa, yr[1], yi[1]);
    pmul(pr[0], pi[0], wb, yr[2], yi[2]); pmul(pr[1], pi[1], wb, yr[3], yi[3]);
    sts128(dst + 12288, yr[0], yr[1], yr[2], yr[3]); sts128(dst + 12288 + 128, yi[0], yi[1], yi[2], yi[3]);
  }
  pmul(pr[0], pi[0], pk(z1024), yr[0], yi[0]);
  pmul(pr[0], pi[0], pk(cmul(z1024, z256)), yr[1], yi[1]);
  pmul(pr[0], pi[0], pk(cmul(z1024, z512)), yr[2], yi[2]);
  pmul(pr[0], pi[0], pk(cmul(z1024, z768)), yr[3], yi[3]);
  sts128(dst + 16384, yr[0], yr[1], yr[2], yr[3]); sts128(dst + 16384 + 128, yi[0], yi[1], yi[2], yi[3]);
  {
    const int em = max(min((int)(max(max(e4.x, e4.y), max(e4.z, e4.w)) >> 23), 238), 16);
    const float sc = __uint_as_float((uint32_t)(127 + 4 + 127 - em) << 23);
    c0.x *= sc; c0.y *= sc;
  }
  const float2 c1 = cmul(c0, z16), c2 = cmul(c1, z16), c3 = cmul(c2, z16);
  pr[0] = pack_h(c0.x, c1.x); pi[0] = pack_h(-c0.y, -c1.y);
  pr[1] = pack_h(c2.x, c3.x); pi[1] = pack_h(-c2.y, -c3.y);
  {
    const uint32_t w = pkc(z64);
    pmul(pr[0], pi[0], w, pr[2], pi[2]); pmul(pr[1], pi[1], w, pr[3], pi[3]);
    sts128(dst + 20480, pr[0], pr[1], pr[2], pr[3]); sts128(dst + 20480 + 128, pi[0], pi[1], pi[2], pi[3]);
    const uint32_t wa = pkc(z128), wb = pkc(cmul(z128, z64));
    pmul(pr[0], pi[0], wa, yr[0], yi[0]); pmul(pr[1], pi[1], wa, yr[1], yi[1]);
    pmul(pr[0], pi[0], wb, yr[2], yi[2]); pmul(pr[1], pi[1], wb, yr[3], yi[3]);
    sts128(dst + 24576, yr[0], yr[1], yr[2], yr[3]); sts128(dst + 24576 + 128, yi[0], yi[1], yi[2], yi[3]);
  }
}
__device__ __forceinline__ void kgen_mma(uint32_t scr, float (&acc)[8]) {
#pragma unroll
  for (int i = 0; i < 8; i++) acc[i] = vzero();
  const uint32_t alo = (scr >> 4) | (8u << 16);
#pragma unroll 1
  for (int ks = 0; ks < 16; ks += 4) {
    wg_fence();
#pragma unroll
    for (int k = 0; k < 4; k++) wgmma16_ss(acc, alo + (ks + k) * 16, alo + (20480 >> 4) + (ks + k) * 16, 4096 >> 4);
    wg_commit();
  }
}

__device__ __forceinline__ void kgen_finish(float (&acc)[8], uint32_t scr, uint32_t kt, uint32_t scale_addr, int wg, int wt) {
  const int w = wt >> 5, g = (wt >> 2) & 7, t = wt & 3;
  const uint32_t misc = scr + W_MISC;
  const uint32_t kc = scr + W_KC + 16;
  const int be = 8 * (g & 1) + 4 * ((g >> 1) & 1) + 2 * (g >> 2);
  const int a0 = w == 0 ? 2 * be : w == 1 ? 512 + be : w == 2 ? 1024 + 2 * (g & 1) + 64 * (g >> 1) : 1296;
  const int s0 = w == 0 ? 32 : w == 1 ? 16 : w == 2 ? 4 : 0;
  const int a1 = w == 0 ? 2 * be + 2 : w == 1 ? 768 + 4 * (g & 1) + (g & 2) + 128 * (g >> 2) : 1296;
  const int s1 = w == 0 ? 32 : w == 1 ? 8 : 0;
  if (wt < 100) sts128(kt + (wt < 4 ? 0 : 4096) + wt * 16, 0, 0, 0, 0);
  if (wt == 96) {
    const uint4 e4 = lds128(misc), k4 = lds128(misc + 16);
    const int em = max(min((int)(max(max(e4.x, e4.y), max(e4.z, e4.w)) >> 23), 238), 16);
    const float inv = __uint_as_float((uint32_t)(127 + 127 - 9 - em) << 23);
    const float kl = ((__uint_as_float(k4.x) + __uint_as_float(k4.y)) + (__uint_as_float(k4.z) + __uint_as_float(k4.w))) * inv;
    sts16(kc + 1280, pack_h(kl, kl));
    sts16(kc - 2, 0);
    sts32(scale_addr, (uint32_t)(em + 9) << 23);
  }
  wg_wait<0>();
  const float un = 1.f / 8192.f;
  {
    const uint32_t p0 = kc + a0 + 2 * t * s0, p1 = kc + a1 + 2 * t * s1;
    const uint32_t h0 = pack_h(acc[0] * un, acc[1] * un), h1 = pack_h(acc[4] * un, acc[5] * un);
    const uint32_t h2 = pack_h(acc[2] * un, acc[3] * un), h3 = pack_h(acc[6] * un, acc[7] * un);
    sts16(p0, h0); sts16(p0 + s0, h0 >> 16); sts16(p0 + 8 * s0, h1); sts16(p0 + 9 * s0, h1 >> 16);
    sts16(p1, h2); sts16(p1 + s1, h2 >> 16); sts16(p1 + 8 * s1, h3); sts16(p1 + 9 * s1, h3 >> 16);
  }
}
__device__ __forceinline__ void kgen_build(uint32_t scr, uint32_t kt, int wg, int wt) {
  const uint32_t kc = scr + W_KC + 16;
  bar_sync(1 + wg, 128);
  const uint32_t h01 = lds32(kc + wt * 4), km1 = lds16(kc + wt * 4 - 2);
  const uint32_t q1 = kc + 512 + wt * 2;
  const uint32_t p1 = lds16(q1 - 2), c1 = lds16(q1), n1 = lds16(q1 + 2), c2 = lds16(q1 + 256), n2 = lds16(q1 + 258), v3 = lds16(q1 + 514);
  const uint32_t wb = kt + 64;
  sts64(wb + wt * 8, __byte_perm(h01, km1, 0x5410), __byte_perm(h01, 0, 0x1032));
  const bool odd = wt & 1;
  const uint32_t lo1 = (odd || wt == 0) ? p1 : c1, hi1 = odd ? n1 : c1;
  sts64(wb + 1024 + wt * 8, __byte_perm(c1, lo1, 0x5410), __byte_perm(hi1, c1, 0x5410));
  const uint32_t tie = odd ? n2 : c2, cc = __byte_perm(c2, c2, 0x5410);
  sts128(wb + 2048 + wt * 16, cc, cc, __byte_perm(tie, c2, 0x5410), __byte_perm(n2, tie, 0x5410));
  const uint32_t arr = kt + KT_WORDS * 4 + (odd ? 0 : 2 * L3_ARR) + (wt >> 1) * 2;
  sts16(arr + 176, v3);
  sts16(arr + L3_ARR + 184, v3);
  if (wt == 127) {
    const uint32_t d = __byte_perm(n2, n2, 0x5410);
    sts128(wb + 4096, d, d, d, d); sts64(wb + 4096 + 16, d, d & 0xFFFF0000u);
  }
}

__device__ __forceinline__ void load_a(uint32_t (&a)[4], uint32_t kp, int j, bool full) {
  a[0] = lds32(kp + 256 * j); a[1] = lds32(kp + 256 * j + 32); a[2] = lds32(kp + 256 * j - 32);
  if (full) asm volatile("ld.volatile.shared.b32 %0, [%1];" : "=r"(a[3]) : "r"(kp + 256 * j) : "memory");
}
__device__ __forceinline__ void dup_a(uint32_t (&a)[4], uint32_t zero) { asm volatile("xor.b32 %0, %1, %2;" : "=r"(a[3]) : "r"(a[0]), "r"(zero)); }
__device__ __forceinline__ uint32_t band(int d, int lo, int hi) {
  return ((unsigned)(d - lo) <= (unsigned)(hi - lo) ? 0x3C00u : 0u) | ((unsigned)(d - 1 - lo) <= (unsigned)(hi - lo) ? 0x3C000000u : 0u);
}
__device__ __forceinline__ uint32_t hadd2u(uint32_t a, uint32_t b) { __half2 r = __hadd2(*(__half2*)&a, *(__half2*)&b); return *(uint32_t*)&r; }

#define X_DELTA 1200
__global__ void __launch_bounds__(NT, 1)
fused_kernel(const __grid_constant__ Params p, const __grid_constant__ CUtensorMap tm_gate, const __grid_constant__ CUtensorMap tm_up) {
  extern __shared__ __align__(1024) unsigned char smem[];
  const int c = blockIdx.x;
  if (c >= NCTA) {
    if (smem_u32(smem) != SB) __trap();
    if ((threadIdx.x & 31) == 0) {
      __nanosleep(800);
#pragma unroll 1
      for (int i = (c - NCTA) * 16 + (threadIdx.x >> 5); i < FF * DM * 2 / 4608; i += 64) l2_prefetch(p.w_down + (size_t)i * 4608, 4608);
    }
    return;
  }
  const bool five = (c & 1) == 0;
  const int u0 = (c >> 1) * 9 + (five ? 0 : 4);
  const uint32_t ones = 0x3F803F80u;
  TS(0);
  {
    const int tid = threadIdx.x, lane = tid & 31, wt = tid & 127, g = lane >> 2, t = lane & 3;
    uint32_t raw[7];
    if (tid >= 480) {
#pragma unroll
      for (int i = 0; i < 5; i++) sts128(OFF_ONES + (lane + 32 * i) * 16, ~0u, ~0u, ~0u, ~0u);
      if (lane == 0) {
        asm volatile("mbarrier.init.shared::cta.b64 [%0], 1;" :: "r"(MISC_MBAR) : "memory");
        asm volatile("mbarrier.init.shared::cta.b64 [%0], 512;" :: "r"(MISC_MBU) : "memory");
        asm volatile("mbarrier.init.shared::cta.b64 [%0], 512;" :: "r"(MISC_MBWIN) : "memory");
        asm volatile("mbarrier.arrive.expect_tx.shared::cta.b64 _, [%0], %1;" :: "r"(MISC_MBAR), "r"(6 * BOX) : "memory");
        sts32(MISC_CNT, 0);
      }
      asm volatile("fence.proxy.async.shared::cta;" ::: "memory");
    }
    {
      const uint32_t o0 = ((tid >> 7) * 128 + c) * 256 + wt * 2;
#pragma unroll
      for (int i = 0; i < 6; i++) raw[i] = ldnc16(p.ssm[i] + o0);
      raw[6] = ldnc16(p.log_dt + (o0 >> 8));
    }
    __syncthreads();
    const int warp = (int)uni(tid >> 5), wg = warp >> 2;
    const uint32_t row = OFF_YT + warp * YT_PITCH + (warp >> 3) * 64;
    {
      const unsigned char* xp = (const unsigned char*)p.x + (uint32_t)((c * 16 + warp) * 1152 + lane * 16);
      asm volatile("cp.async.cg.shared.global [%0], [%1], 16;" :: "r"(row + lane * 16), "l"(xp) : "memory");
      asm volatile("cp.async.cg.shared.global [%0], [%1], 16;" :: "r"(row + lane * 16 + 512), "l"(xp + 512) : "memory");
      if (lane < 9) asm volatile("cp.async.cg.shared.global [%0], [%1], 16;" :: "r"(row + lane * 16 + 1024), "l"(lane < 8 ? xp + 1024 : (const unsigned char*)&p.s->FLAG[c * 8]) : "memory");
      asm volatile("cp.async.commit_group;" ::: "memory");
      if (lane == 0 && warp < 14)
        bulk_clear((unsigned char*)p.s + (warp < 8 ? offsetof(Scratch, Y2) + c * 18432 + warp * 2304 : warp < 12 ? offsetof(Scratch, P) + c * 9216 + (warp - 8) * 2304
                                          : warp == 12 ? offsetof(Scratch, R) + c * 32 : offsetof(Scratch, HS) + c * 144), warp < 12 ? 2304 : warp == 12 ? 32 : 144);
      const int w = warp & 3, mi = lane >> 3;
      const int c0 = 112 + 2 * w - 3 + mi, c1 = c0 + 8, c2 = 112 + 2 * w + 1 + 8 * (mi & 1), r16 = 16 - (lane & 7) * 16;
      sts128(OFF_ATAB + wt * 16, (W_KT + (16 + 16 * w + g - 2 * t) * 4) | (((c0 & 15) * 144 + (c0 >> 4) * 16 + r16) << 16),
             ((c1 & 15) * 144 + (c1 >> 4) * 16 + r16) | (((c2 & 15) * 144 + (c2 >> 4) * 16 + r16) << 16),
             (W_EX + w * EX_WARP + (mi & 1) * EX_PLANE + (4 + 8 * (mi >> 1) + (lane & 7)) * 16) | ((W_EX + ((wt >> 1) & 1) * EX_PLANE + (4 + (wt >> 2)) * 16 + (wt & 1) * 8) << 16),
             (wt >> 2) * (DM * 32) + (wt & 3) * 8);
    }
    TS(13);
    const uint32_t wb = OFF_W + wg * W_BYTES;
    const bool two = wg == 1 && five;
    uint32_t epoch = 0, tpub = 0;
    uint4 v0, v1;
#pragma unroll 1
    for (int item = 0;; item++) {
      KgState ks;
      kgen_tables_a(raw, wb, wt, ks);
      TS(20);
      if (item == 0) {
        asm volatile("cp.async.wait_all;" ::: "memory");
        asm volatile("cp.async.bulk.wait_group 0;" ::: "memory");
        __syncwarp();
        TS(21);
        uint32_t xw[9];
        float d[2][4] = {{0.f, 0.f, 0.f, 0.f}, {0.f, 0.f, 0.f, 0.f}}, r;
#pragma unroll
        for (int i = 0; i < 9; i++) { xw[i] = lds32(row + lane * 4 + i * 128); mma_bf16_k8(d[i & 1], xw[i], ones, xw[i]); }
        epoch = lds32(row + 1152) + 1u;
        const LnC lc = ln_consts(quad_sum((d[0][2] + d[1][2]) + (d[0][3] + d[1][3])), diag_sum(d[0][0] + d[1][0], d[0][1] + d[1][1], t), r);
#pragma unroll
        for (int i = 0; i < 9; i++) { const uint32_t u = ln_apply(xw[i], lc); sts32(row + lane * 4 + i * 128, pack_h(bf_lo(u), bf_hi(u))); }
        if (lane == 0) sts128(MISC_LN1 + warp * 16, lc.m2, lc.rh2, lc.rl2, 0);
        TS(22);
        const int tr_tok = 8 * ((lane >> 1) & 1) + 2 * (lane >> 3) + (lane & 1);
        const uint32_t tr_addr = OFF_YT + tr_tok * YT_PITCH + (tr_tok >> 3) * 64 + ((lane >> 2) & 1) * 16 + warp * 32;
        uint4* u2dst = &p.s->U2[c * DM * 2 + warp * 32 + (8 * (t >> 1) + g) * 2 + (t & 1)];
        __syncthreads();
        TS(23);
#pragma unroll
        for (int r = 0; r < 3; r++) {
          if (r < 2 || warp < 4) {
            uint32_t r0, r1, r2, r3;
            ldsm4t(tr_addr + r * 512, r0, r1, r2, r3);
            str128(u2dst + r * 512, (r0 & ~1u) | (epoch & 1u), r1, r2, r3);
          }
        }
        tpub = clock();
        mbar_arrive(MISC_MBU);
        if (tid == 480) {
          str32(&p.s->FLAG[c * 8], epoch);
          l2_prefetch(p.w_gate + (size_t)c * 41472, 20736);
        }
        if (two) {
          const uint32_t o1 = (512 + (c >> 1)) * 256 + wt * 2;
#pragma unroll
          for (int i = 0; i < 6; i++) raw[i] = ldnc16(p.ssm[i] + o1);
          raw[6] = ldnc16(p.log_dt + (o1 >> 8));
        }
        TS(1);
      } else bar_sync(6, 256);
      kgen_tables_b(wb, wt, ks);
      asm volatile("fence.proxy.async.shared::cta;" ::: "memory");
      bar_sync(1 + wg, 128);
      TS(14);
      float kacc[8];
      kgen_mma(wb, kacc);
      if (item || !two) {
        while (__any_sync(0xffffffffu, (int)(clock() - tpub) < X_DELTA)) {}
        const uint4* src = &p.s->U2[(wt >> 1) * (DM * 2) + (wg * 128 + c) * 2 + (wt & 1)];
        v0 = ldr128(src); v1 = ldr128(src + 64 * DM * 2);
      }
      const uint32_t tb = item ? OFF_W + ALT : wb;
      kgen_finish(kacc, wb, tb + W_KT, item ? OFF_W + W_MISC + 36 : wb + W_MISC + 32, wg, wt);
      TS(24);
      kgen_build(wb, tb + W_KT, wg, wt);
      if (wg == 0 && five) bar_arrive(6, 256);
      if (item || !two) break;
    }
    TS(15);
    mbar_wait(MISC_MBU);
#pragma unroll 1
    for (int item = 0;; item++) {
      const uint4* src = &p.s->U2[(wt >> 1) * (DM * 2) + (item ? 512 + (c >> 1) : wg * 128 + c) * 2 + (wt & 1)];
      const uint32_t ud = (item ? OFF_W + ALT : wb) + W_UP + (wt & 1) * UP_PLANE + (wt >> 1) * 16;
      const uint32_t pp = item ? OFF_W + W_KC + ALT : OFF_YT + wg * UPP_BYTES;
      if (wt < 64) sts128(ud, 0, 0, 0, 0);
      if (wt < 3) sts128(pp + (13 + wt) * 144, 0, 0, 0, 0);
      SPIN_WHILE(((v0.x ^ epoch) | (v1.x ^ epoch)) & 1u, v0 = ldr128(src); v1 = ldr128(src + 64 * DM * 2));
      sts128(ud + UP_PAD * 16, v0.x & ~1u, v0.y, v0.z, v0.w);
      sts128(ud + UP_PAD * 16 + 1024, v1.x & ~1u, v1.y, v1.z, v1.w);
      sts128(pp + (wt & 15) * 144 + ((wt >> 4) + 1) * 16, v0.x & ~1u, v0.y, v0.z, v0.w);
      if (item || !two) break;
      v0.x = ~epoch;
    }
    asm volatile("fence.proxy.async.shared::cta;" ::: "memory");
    if (two) bar_arrive(5, 256);
    bar_sync(1 + wg, 128);
    if (tid == 256) l2_prefetch(p.w_gate + (size_t)c * 41472 + 20736, 20736);
    if (wt == 96 && wg > 0) {
      tma_box(OFF_G + (wg - 1) * BOX, &tm_gate, MISC_MBAR, u0 * 8, (wg - 1) * 192);
      tma_box(wb, &tm_up, MISC_MBAR, u0 * 8, (wg - 1) * 192);
    }
    TS(2);
  }
  {
    const int wg = (int)uni(fresh_tid() >> 7);
    const uint32_t wb = OFF_W + wg * W_BYTES;
    const int nitem = (wg == 0 && five) ? 2 : 1;
#pragma unroll 1
    for (int item = 0; item < nitem; item++) {
      const uint32_t zero = p.zero;
      const uint32_t at = OFF_ATAB + (fresh_tid() & 127) * 16;
      const uint32_t tb = item ? OFF_W + ALT : wb;
      const uint2 aa = lds64(at);
      const uint32_t kp = tb + (aa.x & 0xFFFFu);
      const uint32_t dlo = ((tb + W_UP) >> 4) + UP_PAD + ((uint32_t)(UP_PLANE >> 4) << 16);
      float a32[16], a96[48];
      uint32_t X[4][4], Y[4][4];
      if (item) bar_sync(5, 256);
      load_a(Y[0], kp, 16, true);
#pragma unroll
      for (int j = 0; j < 4; j++) load_a(X[j], kp, j, j == 0);
      TS(3);
      wg_fence();
      wgmma96_init<0>(a96, Y[0], dlo - 32, 8);
      wg_commit();
#define STEP(A, J) { wgmma96<0>(a96, A[(J) & 3], dlo + 32 - 4 * (J), 8); if ((J) == 0) wgmma32_init<0>(a32, A[0], dlo, 8); else if ((J) < 8) wgmma32<0>(a32, A[(J) & 3], (dlo ^ zero) - 4 * (J), 8); }
#define BATCH(A, J, MID) { wg_fence(); STEP(A, J) wg_commit(); dup_a(A[1], zero); dup_a(A[2], zero); dup_a(A[3], zero); wg_wait<1>(); wg_fence(); STEP(A, J + 1) STEP(A, J + 2) STEP(A, J + 3) wg_commit(); MID }
#define LOADS(A, J) _Pragma("unroll") for (int j = 0; j < 4; j++) load_a(A[j], kp, J + j, j == 0);
      BATCH(X, 0, LOADS(Y, 4))
      BATCH(Y, 4, LOADS(X, 8))
      BATCH(X, 8, LOADS(Y, 12))
      TS(17);
      uint32_t b[2][5];
      const uint32_t pp = item ? OFF_W + W_KC + ALT : OFF_YT + wg * UPP_BYTES;
      BATCH(Y, 12, ldsm4(pp + (aa.x >> 16), b[0][0], b[0][1], b[0][2], b[0][3]); ldsm4(pp + (aa.y & 0xFFFFu), b[1][0], b[1][1], b[1][2], b[1][3]); ldsm2(pp + (aa.y >> 16), b[0][4], b[1][4]);)
#undef STEP
#undef BATCH
#undef LOADS
      const int wt2 = (at - OFF_ATAB) >> 4;
      {
        uint32_t x9[4] = {0, 0, 0, 0}, x7[4] = {0, 0, 0, 0};
        const int d0 = ((wt2 >> 2) & 7) - 2 * (wt2 & 3);
        const uint32_t n24 = band(d0 + 24, 12, 20), n16 = band(d0 + 16, 12, 20), n8 = band(d0 + 8, 12, 20);
        const uint32_t s16 = band(d0 + 16, 5, 11), s8 = band(d0 + 8, 5, 11), s0 = band(d0, 5, 11);
#pragma unroll
        for (int tl = 0; tl < 2; tl++) mma_f16_f16(x9[2 * tl], x9[2 * tl + 1], n24, 0u, n16, n24, b[tl][0], b[tl][1]);
#pragma unroll
        for (int tl = 0; tl < 2; tl++) mma_f16_f16(x7[2 * tl], x7[2 * tl + 1], s16, 0u, s8, s16, b[tl][1], b[tl][2]);
#pragma unroll
        for (int tl = 0; tl < 2; tl++) mma_f16_f16(x9[2 * tl], x9[2 * tl + 1], n8, n16, 0u, n8, b[tl][2], b[tl][3]);
#pragma unroll
        for (int tl = 0; tl < 2; tl++) mma_f16_f16(x7[2 * tl], x7[2 * tl + 1], s0, s8, 0u, s0, b[tl][3], b[tl][4]);
        const uint32_t l3lo = ((tb + W_L3) >> 4) + ((uint32_t)(L3_ARR >> 4) << 16);
        wg_fence();
        wgmma96<1>(a96, x9, l3lo, 1);
        wgmma96<1>(a96, x7, l3lo + (2 * L3_ARR >> 4), 1);
        wg_commit();
      }
      if (!item) mbar_arrive(MISC_MBWIN);
      TS(18);
      const float scale = __uint_as_float(lds32(wb + W_MISC + 32 + item * 4));
      const uint2 ea = lds64(at + 8);
      const uint32_t est = wb + (ea.x & 0xFFFFu);
      if ((wt2 & 31) < 8) sts128(wb + W_EX + (wt2 >> 5) * EX_WARP + ((wt2 >> 2) & 1) * EX_PLANE + (wt2 & 3) * 16, 0, 0, 0, 0);
#define EPI_ST(acc, i, col) stsm4t(est + (col) * 16, pack_h(acc[i], acc[i + 1]), pack_h(acc[i + 2], acc[i + 3]), pack_h(acc[i + 4], acc[i + 5]), pack_h(acc[i + 6], acc[i + 7]))
      EPI_ST(a32, 0, 0); EPI_ST(a32, 8, 16);
      wg_wait<0>();
#pragma unroll
      for (int h = 0; h < 6; h++) EPI_ST(a96, 8 * h, 32 + 16 * h);
#undef EPI_ST
      TS(25);
      bar_sync(1 + wg, 128);
      unsigned char* y = (unsigned char*)p.s->Y2 + (ea.y + (uint32_t)(item ? 512 + (c >> 1) : wg * 128 + c) * 32);
      uint32_t eld = wb + (ea.x >> 16);
#pragma unroll 2
      for (int q = 0; q < 4; q++) {
        uint2 v[4];
#pragma unroll
        for (int ww = 0; ww < 4; ww++) v[ww] = lds64(eld + ww * (EX_WARP - 16));
        const float2 fa = h2f(hadd2u(hadd2u(v[0].x, v[1].x), hadd2u(v[2].x, v[3].x)));
        const float2 fb = h2f(hadd2u(hadd2u(v[0].y, v[1].y), hadd2u(v[2].y, v[3].y)));
        str64(y, pack_bf(fa.x * scale, fa.y * scale), pack_bf(fb.x * scale, fb.y * scale));
        eld += 512; y += 32 * DM * 32;
      }
    }
    TS(4);

  }

  const int tid = fresh_tid(), lane = tid & 31, g = lane >> 2, t = lane & 3;
  const int warp = (int)uni(tid >> 5), tok = c * 16 + warp;
  const uint32_t stash = OFF_W + (warp >> 2) * W_BYTES + W_EX + (warp & 3) * 2304 + lane * 8;
  uint4 wd[5][2];
  {
    uint32_t hw[9], lw[9], wr[9];
    const uint4* ysrc = &p.s->Y2[c * DM * 2 + warp * 32 + (8 * (t >> 1) + g) * 2 + (t & 1)];
    const uint32_t* xp = p.x + tok * 288 + lane;
#pragma unroll
    for (int i = 0; i < 9; i++) { hw[i] = ldnc32(xp + 32 * i); lw[i] = ldnc32(p.dskip + lane + 32 * i); wr[i] = ldnc32(p.w_r + lane + 32 * i); }
    const uint4 q = lds128(MISC_LN1 + warp * 16);
    LnC l1; l1.m2 = q.x; l1.rh2 = q.y; l1.rl2 = q.z;
    float e[4] = {0.f, 0.f, 0.f, 0.f};
#pragma unroll
    for (int i = 0; i < 9; i++) { lw[i] = bf_mul2(ln_apply(hw[i], l1), lw[i]); mma_bf16_k8(e, ones, ones, wr[i]); }
    const float sw = quad_sum(e[0] + e[1]);
    const int tr_tok = 8 * ((lane >> 1) & 1) + 2 * (lane >> 3) + (lane & 1);
    const uint32_t tr_addr = OFF_YT + tr_tok * YT_PITCH + (tr_tok >> 3) * 64 + ((lane >> 2) & 1) * 16 + warp * 32;
    if (warp >= 7) {
      const unsigned char* src = p.w_down + (uint32_t)((u0 * 8 + 2 * t) * (DM * 2) + (warp - 7) * 128 + g * 16) + (lw[8] & p.zero);
#pragma unroll
      for (int q = 0; q < 5; q++) { wd[q][0] = ldnc128(src + q * 8 * DM * 2); wd[q][1] = ldnc128(src + (q * 8 + 1) * DM * 2); }
    }
    TS(5);
    mbar_wait(MISC_MBWIN);
    uint4 v0, v1, v2;
    const uint4* ysrc2 = ysrc + (warp < 4 ? 1024 : 0);
#pragma unroll 1
    for (int it = 0; it < SPIN_MAX; it++) {
      v0 = ldr128(ysrc); v1 = ldr128(ysrc + 512); v2 = ldr128(ysrc2);
      if (!__any_sync(0xffffffffu, max(max(max(v0.x, v0.z), max(v1.x, v1.z)), max(v2.x, v2.z)) == ~0u)) break;
    }
    stsm4t(tr_addr, v0.x, v0.y, v0.z, v0.w);
    stsm4t(tr_addr + 512, v1.x, v1.y, v1.z, v1.w);
    if (warp < 4) stsm4t(tr_addr + 1024, v2.x, v2.y, v2.z, v2.w);
    __syncthreads();
    TS(6);
    const uint32_t row = OFF_YT + warp * YT_PITCH + (warp >> 3) * 64 + lane * 4;
    float d[4] = {0.f, 0.f, 0.f, 0.f}, rd;
    e[0] = e[1] = e[2] = e[3] = 0.f;
#pragma unroll
    for (int i = 0; i < 9; i++) {
      hw[i] = bf_add2(hw[i], bf_add2(lds32(row + i * 128), lw[i]));
      mma_bf16_k8(d, hw[i], wr[i], hw[i]);
      mma_bf16_k8(e, ones, ones, hw[i]);
    }
    const float hwsum = diag_sum(d[2], d[3], t);
    const LnC l2 = ln_consts(quad_sum(e[0] + e[1]), diag_sum(d[0], d[1], t), rd);
    const uint32_t b = pack_bf(fmaf(-bf_lo(l2.m2), sw, hwsum) * rd, 0.f);
    if (lane == 0) sts16(MISC_RK + warp * 2, min((b & 0x8000u) ? (~b & 0xFFFFu) : (b | 0x8000u), 0xFFFEu));
    if (warp == 15) {
      bar_sync(5, 512);
      if (lane < 2) { const uint4 k = lds128(MISC_RK + lane * 16); str128(&p.s->R[c * 2 + lane], k.x, k.y, k.z, k.w); }
    } else bar_arrive(5, 512);
    TS(7);
    uint32_t* o = p.out + tok * 288 + lane;
#pragma unroll
    for (int i = 0; i < 9; i++) {
      lw[i] = ln_apply(hw[i], l2);
      sts64(stash + i * 256, lw[i], hw[i]);
      str32(o + 32 * i, bf_add2(hw[i], lw[i]));
    }
  }
  const int fu = warp < 15 ? warp / 3 : 0, fk = warp - (warp / 3) * 3;
  uint32_t wa[12][4];
  {
    const uint32_t wabase = ((lane & 8) ? OFF_W + (fk + 1) * W_BYTES : OFF_G + fk * BOX) + ((lane >> 4) * 8 + (lane & 7)) * 80 + fu * 16;
    mbar_wait(MISC_MBAR);
#pragma unroll
    for (int k = 0; k < 12; k++) ldsm4t(wabase + k * 16 * 80, wa[k][0], wa[k][1], wa[k][2], wa[k][3]);
  }
  TS(19);

  if (warp < 8) {
    uint32_t key[8], mx, wm;
#pragma unroll 1
    for (int it = 0; it < SPIN_MAX; it++) {
      const uint4 rv = ldr128(&p.s->R[tid]);
      const uint32_t ib = 2047 - tid * 8;
      key[0] = (rv.x << 16) | ib;       key[1] = (rv.x & 0xFFFF0000u) | (ib - 1);
      key[2] = (rv.y << 16) | (ib - 2); key[3] = (rv.y & 0xFFFF0000u) | (ib - 3);
      key[4] = (rv.z << 16) | (ib - 4); key[5] = (rv.z & 0xFFFF0000u) | (ib - 5);
      key[6] = (rv.w << 16) | (ib - 6); key[7] = (rv.w & 0xFFFF0000u) | (ib - 7);
      mx = max(max(max(key[0], key[1]), max(key[2], key[3])), max(max(key[4], key[5]), max(key[6], key[7])));
      wm = __reduce_max_sync(0xffffffffu, mx);
      if (wm < 0xFFFF0000u) break;
    }
    if (lane == 0) sts32(MISC_WMAX + warp * 4, wm);
    TS(16);
    bar_sync(6, 256);
    const uint32_t tau = __reduce_min_sync(0xffffffffu, lds32(MISC_WMAX + (lane & 7) * 4));
#pragma unroll 1
    for (;;) {
      const uint32_t m = __ballot_sync(0xffffffffu, mx >= tau);
      if (!m) break;
      uint32_t pos = 0;
      if (lane == 0) asm volatile("atom.shared.add.u32 %0, [%1], %2;" : "=r"(pos) : "r"(MISC_CNT), "r"(__popc(m)) : "memory");
      const uint32_t cur = mx;
      mx = 0;
#pragma unroll
      for (int i = 0; i < 8; i++) mx = max(mx, key[i] < cur ? key[i] : 0u);
      pos = __shfl_sync(0xffffffffu, pos, 0) + __popc(m & ((1u << lane) - 1u));
      if (cur >= tau) sts32(OFF_CAND + pos * 4, cur);
    }
  }
  __syncthreads();
  TS(8);
  {
    const int n = (int)lds32(MISC_CNT);
#pragma unroll 1
    for (int j = warp; j < n; j += 16) {
      const uint32_t mine = lds32(OFF_CAND + j * 4);
      int rank = 0;
#pragma unroll 1
      for (int b = lane; b - lane < n; b += 32) rank += __popc(__ballot_sync(0xffffffffu, b < n && lds32(OFF_CAND + b * 4) > mine));
      if (rank < 8) {
        if (lane == 0) sts32(MISC_SEL + rank * 4, mine);
        const int lt = 2047 - (int)(mine & 0xFFFFu) - c * 16;
        if ((unsigned)lt < 16u) {
          const uint32_t sa = OFF_W + (lt >> 2) * W_BYTES + W_EX + (lt & 3) * 2304 + lane * 8;
          uint32_t* hs = (uint32_t*)p.s->HS + rank * 288 + lane;
#pragma unroll
          for (int r = 0; r < 9; r++) str32(hs + 32 * r, lds32(sa + r * 256));
        }
      }
    }
    const uint4* src = &p.s->HS[tid];
    const uint4* src2 = src + (tid < 64 ? 512 : 0);
    uint4 v0, v1;
#pragma unroll 1
    for (int it = 0; it < SPIN_MAX; it++) {
      v0 = ldr128(src); v1 = v0;
      if (warp < 2) v1 = ldr128(src2);
      if (!__any_sync(0xffffffffu, max(max(max(v0.x, v0.y), max(v0.z, v0.w)), max(max(v1.x, v1.y), max(v1.z, v1.w))) == ~0u)) break;
    }
    sts128(OFF_XS + tid * 16 + (tid / 72) * 16, v0.x, v0.y, v0.z, v0.w);
    if (warp < 2) sts128(OFF_XS + (tid + 512 + 7) * 16, v1.x, v1.y, v1.z, v1.w);
  }
  __syncthreads();
  TS(9);

  const uint32_t selkey = lds32(MISC_SEL + (lane & 7) * 4);
  const uint32_t hit = __ballot_sync(0xffffffffu, (int)(selkey & 0xFFFFu) == 2047 - tok);
  uint32_t rb0 = 0;
  if (hit) {
#pragma unroll
    for (int r = 0; r < 9; r++) rb0 |= ldr32(p.out + tok * 288 + lane + 32 * r);
  }
  {
    float d0[4] = {0.f, 0.f, 0.f, 0.f}, d1[4] = {0.f, 0.f, 0.f, 0.f};
    const uint32_t xb = OFF_XS + (lane & 7) * 1168 + (fk * 24 + (lane >> 3)) * 16;
#pragma unroll
    for (int k = 0; k < 12; k += 2) {
      uint32_t b0, b1, b2, b3;
      ldsm4(xb + k * 32, b0, b1, b2, b3);
      mma_bf16(d0, wa[k][0], wa[k][1], wa[k][2], wa[k][3], b0, b1);
      mma_bf16(d1, wa[k + 1][0], wa[k + 1][1], wa[k + 1][2], wa[k + 1][3], b2, b3);
    }
    sts128(OFF_RED + warp * 512 + lane * 16, __float_as_uint(d0[0] + d1[0]), __float_as_uint(d0[1] + d1[1]), __float_as_uint(d0[2] + d1[2]), __float_as_uint(d0[3] + d1[3]));
  }
  __syncthreads();
  TS(26);
  if (hit) {
    uint32_t* hs = (uint32_t*)p.s->HS + 2304 + (__ffs(hit) - 1) * 288 + lane + (rb0 & p.zero);
#pragma unroll
    for (int r = 0; r < 9; r++) str32(hs + 32 * r, lds32(stash + 4 + r * 256));
  }
  if (warp < 5) {
    const uint32_t rb = OFF_RED + warp * 1536 + lane * 16;
    const uint4 pa = lds128(rb), pb = lds128(rb + 512), pc = lds128(rb + 1024);
    const float ga = bfr(__uint_as_float(pa.x) + __uint_as_float(pb.x) + __uint_as_float(pc.x));
    const float gb = bfr(__uint_as_float(pa.y) + __uint_as_float(pb.y) + __uint_as_float(pc.y));
    const uint32_t uu = pack_bf(__uint_as_float(pa.z) + __uint_as_float(pb.z) + __uint_as_float(pc.z), __uint_as_float(pa.w) + __uint_as_float(pb.w) + __uint_as_float(pc.w));
    float ra, rb2;
    asm("rcp.approx.ftz.f32 %0, %1;" : "=f"(ra) : "f"(1.f + ex2(ga * -1.4426950408889634f)));
    asm("rcp.approx.ftz.f32 %0, %1;" : "=f"(rb2) : "f"(1.f + ex2(gb * -1.4426950408889634f)));
    const uint32_t act = bf_mul2(pack_bf(ga * ra, gb * rb2), uu);
    sts32(OFF_ACT + warp * 128 + lane * 4, act);
    bar_arrive(7, 14 * 32);
  } else if (warp >= 7) {
    uint32_t f[5][8];
#pragma unroll
    for (int q = 0; q < 5; q++) {
      const uint32_t* r0 = (const uint32_t*)&wd[q][0];
      const uint32_t* r1 = (const uint32_t*)&wd[q][1];
#pragma unroll
      for (int j = 0; j < 4; j++) { f[q][2 * j] = __byte_perm(r0[j], r1[j], 0x5410); f[q][2 * j + 1] = __byte_perm(r0[j], r1[j], 0x7632); }
    }
    bar_sync(7, 14 * 32);
    uint32_t b0, b1, b2, b3, b4;
    ldsm4t(OFF_ACT + lane * 16, b0, b1, b2, b3);
    asm volatile("ldmatrix.sync.aligned.m8n8.x1.trans.shared.b16 {%0}, [%1];" : "=r"(b4) : "r"(OFF_ACT + 512 + (lane & 7) * 16) : "memory");
    float y[4][4];
#pragma unroll
    for (int j = 0; j < 4; j++) {
      y[j][0] = y[j][1] = y[j][2] = y[j][3] = 0.f;
      mma_bf16(y[j], f[0][2 * j], f[0][2 * j + 1], f[1][2 * j], f[1][2 * j + 1], b0, b1);
    }
#pragma unroll
    for (int j = 0; j < 4; j++) mma_bf16(y[j], f[2][2 * j], f[2][2 * j + 1], f[3][2 * j], f[3][2 * j + 1], b2, b3);
    if (!five) {
#pragma unroll
      for (int j = 0; j < 4; j++) mma_bf16_k8(y[j], f[4][2 * j], f[4][2 * j + 1], b4);
    }
    uint4* dst = &p.s->P[c * 576 + ((warp - 7) * 8 + g) * 8 + t];
    str128(dst, pack_bf(y[0][0], y[0][1]), pack_bf(y[0][2], y[0][3]), pack_bf(y[1][0], y[1][1]), pack_bf(y[1][2], y[1][3]));
    str128(dst + 4, pack_bf(y[2][0], y[2][1]), pack_bf(y[2][2], y[2][3]), pack_bf(y[3][0], y[3][1]), pack_bf(y[3][2], y[3][3]));
  }
  TS(10);

  if (c < 72) {
    const uint4* src = &p.s->P[(warp * 4 + t) * 576 + c * 8 + g];
    const uint32_t* hsrc = (const uint32_t*)p.s->HS + 2304 + g * 288 + c * 4 + t;
    uint4 v0, v1; uint32_t hv = 0;
#pragma unroll 1
    for (int it = 0; it < SPIN_MAX; it++) {
      v0 = ldr128(src); v1 = ldr128(src + 64 * 576);
      if (warp == 0) hv = ldr32(hsrc);
      if (!__any_sync(0xffffffffu, max(max(v0.x, v1.x), hv) == ~0u)) break;
    }
    float d[4] = {0.f, 0.f, 0.f, 0.f};
    {
      const uint32_t sel = (g & 1) ? 0x3F800000u : 0x00003F80u;
      const uint32_t s0 = (g >> 1) == 0 ? sel : 0u, s1 = (g >> 1) == 1 ? sel : 0u, s2 = (g >> 1) == 2 ? sel : 0u, s3 = (g >> 1) == 3 ? sel : 0u;
      mma_bf16(d, s0, 0u, s1, 0u, v0.x, v0.y); mma_bf16(d, s2, 0u, s3, 0u, v0.z, v0.w);
      mma_bf16(d, s0, 0u, s1, 0u, v1.x, v1.y); mma_bf16(d, s2, 0u, s3, 0u, v1.z, v1.w);
    }
    {
      const uint32_t fb = OFF_FIN + warp * 256 + ((4 * (t & 1) + (g & 1)) * 8 + 4 * (t >> 1) + (g >> 1)) * 4;
      sts32(fb, __float_as_uint(d[0])); sts32(fb + 64, __float_as_uint(d[1]));
    }
    __syncthreads();
    TS(11);
    if (warp == 0) {
      float s0 = 0.f, s1 = 0.f;
#pragma unroll
      for (int i = 0; i < 16; i++) { const uint2 q = lds64(OFF_FIN + i * 256 + lane * 8); s0 += __uint_as_float(q.x); s1 += __uint_as_float(q.y); }
      const uint32_t key = __shfl_sync(0xffffffffu, selkey, g);
      const uint32_t k16 = key >> 16;
      const float r = bf_lo((k16 & 0x8000u) ? (k16 & 0x7FFFu) : (~k16 & 0xFFFFu));
      float rs;
      asm("rcp.approx.ftz.f32 %0, %1;" : "=f"(rs) : "f"(1.f + ex2(r * -1.4426950408889634f)));
      const uint32_t upd = bf_mul2(pack_bf(s0, s1), pack_bf(rs, rs));
      const uint32_t ln = lds32(OFF_XS + g * 1168 + c * 16 + t * 4);
      p.out[(2047 - (int)(key & 0xFFFFu)) * 288 + c * 4 + t] = bf_add2(hv, bf_add2(ln, upd));
    }
  }
  TS(12);
  TS_DUMP();
}

typedef CUresult (*EncodeFn)(CUtensorMap*, CUtensorMapDataType, cuuint32_t, void*, const cuuint64_t*, const cuuint64_t*, const cuuint32_t*,
                             const cuuint32_t*, CUtensorMapInterleave, CUtensorMapSwizzle, CUtensorMapL2promotion, CUtensorMapFloatOOBfill);

}

extern "C" void kernel_launch(void* const* d_in, const int* in_sizes, int n_in, void* d_out, int out_size) {
  (void)in_sizes; (void)n_in; (void)out_size;
  static EncodeFn enc = nullptr;
  static Scratch* scratch = nullptr;
  if (!enc) {
    void* fn = nullptr;
    cudaDriverEntryPointQueryResult qr;
    cudaGetDriverEntryPoint("cuTensorMapEncodeTiled", &fn, cudaEnableDefault, &qr);
    enc = (EncodeFn)fn;
    cudaGetSymbolAddress((void**)&scratch, g_S);
    cudaFuncSetAttribute(fused_kernel, cudaFuncAttributeMaxDynamicSharedMemorySize, SMEM_BYTES);
  }
  CUtensorMap tm[2];
  for (int i = 0; i < 2; i++) {
    cuuint64_t gd[2] = {FF, DM};
    cuuint64_t gs[1] = {FF * 2};
    cuuint32_t bx[2] = {40, 192};
    cuuint32_t es[2] = {1, 1};
    enc(&tm[i], CU_TENSOR_MAP_DATA_TYPE_BFLOAT16, 2, d_in[11 + i], gd, gs, bx, es, CU_TENSOR_MAP_INTERLEAVE_NONE, CU_TENSOR_MAP_SWIZZLE_NONE,
        CU_TENSOR_MAP_L2_PROMOTION_L2_128B, CU_TENSOR_MAP_FLOAT_OOB_FILL_NONE);
  }
  Params p;
  p.x = (const uint32_t*)d_in[0];
  for (int i = 0; i < 6; i++) p.ssm[i] = (const unsigned char*)d_in[1 + i];
  p.log_dt = (const uint16_t*)d_in[7];
  p.dskip = (const uint32_t*)d_in[8];
  p.w_r = (const uint32_t*)d_in[10];
  p.w_gate = (const unsigned char*)d_in[11];
  p.w_up = (const unsigned char*)d_in[12];
  p.w_down = (const unsigned char*)d_in[13];
  p.out = (uint32_t*)d_out;
  p.zero = 0;
  p.ts = nullptr;
  p.s = scratch;
  fused_kernel<<<NCTA + 4, NT, SMEM_BYTES, cudaStreamPerThread>>>(p, tm[0], tm[1]);
}
```

```cpp
#include <cuda_runtime.h>
#include <cuda.h>
#include <cuda_bf16.h>
#include <cuda_fp16.h>
#include <stdint.h>
#include <stddef.h>

namespace {

constexpr int NCTA = 128;
constexpr int NT = 640;
constexpr int DM = 576;
constexpr int FF = 4608;
constexpr int SPIN_MAX = 1 << 20;

struct Scratch {
  uint4 X[NCTA * DM * 2];
  uint4 KX[64 * 128];
  uint4 HS[1152 + 8];
  uint4 R[256];
  uint16_t SC[640];
  uint32_t FLAG[NCTA * 8];
};
__device__ Scratch g_S;

#define TS(i)
#define TS_DUMP()

constexpr int SB = 1024;
constexpr int BOX = 15360;
constexpr int OFF_G = SB;
constexpr int OFF_W = OFF_G + 3 * BOX;
constexpr int W_UP = 26624;
constexpr int W_KT = W_UP + 5120;
constexpr int W_L3 = W_KT + 4416;
constexpr int W_CW = W_L3 + 4096;
constexpr int W_MISC = W_CW + 640;
constexpr int W_BYTES = 40960;
constexpr int ALT = -W_UP;
static_assert(W_MISC + 32 <= W_BYTES && OFF_W % 1024 == 0 && W_UP % 256 == 0 && W_BYTES + ALT + 3 * 4096 <= W_UP, "wg block");
constexpr int OFF_K5 = OFF_G + 40960;
constexpr int YT_PITCH = 1184;
constexpr int OFF_YT = OFF_W + 4 * W_BYTES;
constexpr int OFF_WR = OFF_YT + 16 * YT_PITCH + 64;
constexpr int OFF_MISC = OFF_WR + 2304;
constexpr int SMEM_BYTES = OFF_MISC + 1024 - SB;
static_assert(OFF_YT % 16 == 0 && OFF_MISC % 16 == 0, "align");
static_assert(SMEM_BYTES <= 232448, "smem");
constexpr int MB_GU = OFF_MISC;
constexpr int MB_D = OFF_MISC + 8;
constexpr int MB_KF = OFF_MISC + 16;
constexpr int MB_GF = OFF_MISC + 48;
constexpr int MB_SC = OFF_MISC + 56;
constexpr int MB_UL = OFF_MISC + 64;
constexpr int MB_UV = OFF_MISC + 104;
constexpr int MISC_EPOCH = OFF_MISC + 144;
constexpr int MISC_SW = OFF_MISC + 148;
constexpr int MISC_RK = OFF_MISC + 160;
constexpr int MISC_LN1 = OFF_MISC + 192;
constexpr int OFF_XS = OFF_W + W_BYTES + W_UP;
constexpr int OFF_RED = OFF_W + 2 * W_BYTES + W_UP;
constexpr int OFF_FIN = OFF_W + 3 * W_BYTES + W_UP;
constexpr int OFF_ACT = OFF_FIN + 4096;
constexpr int MISC_CNT = OFF_ACT + 1024;

__device__ __forceinline__ uint32_t smem_u32(const void* p) { return (uint32_t)__cvta_generic_to_shared(p); }
__device__ __forceinline__ uint32_t lds32(uint32_t a) { uint32_t v; asm volatile("ld.shared.b32 %0, [%1];" : "=r"(v) : "r"(a) : "memory"); return v; }
__device__ __forceinline__ uint32_t lds16(uint32_t a) { uint16_t v; asm volatile("ld.shared.u16 %0, [%1];" : "=h"(v) : "r"(a) : "memory"); return v; }
__device__ __forceinline__ uint2 lds64(uint32_t a) { uint2 v; asm volatile("ld.shared.v2.b32 {%0,%1}, [%2];" : "=r"(v.x), "=r"(v.y) : "r"(a) : "memory"); return v; }
__device__ __forceinline__ uint4 lds128(uint32_t a) { uint4 v; asm volatile("ld.shared.v4.b32 {%0,%1,%2,%3}, [%4];" : "=r"(v.x), "=r"(v.y), "=r"(v.z), "=r"(v.w) : "r"(a) : "memory"); return v; }
__device__ __forceinline__ void sts16(uint32_t a, uint32_t v) { asm volatile("st.shared.u16 [%0], %1;" :: "r"(a), "h"((uint16_t)v) : "memory"); }
__device__ __forceinline__ void sts32(uint32_t a, uint32_t v) { asm volatile("st.shared.b32 [%0], %1;" :: "r"(a), "r"(v) : "memory"); }
__device__ __forceinline__ void sts64(uint32_t a, uint32_t x, uint32_t y) { asm volatile("st.shared.v2.b32 [%0], {%1,%2};" :: "r"(a), "r"(x), "r"(y) : "memory"); }
__device__ __forceinline__ void sts128(uint32_t a, uint32_t x, uint32_t y, uint32_t z, uint32_t w) { asm volatile("st.shared.v4.b32 [%0], {%1,%2,%3,%4};" :: "r"(a), "r"(x), "r"(y), "r"(z), "r"(w) : "memory"); }
__device__ __forceinline__ void ldsm4(uint32_t a, uint32_t& r0, uint32_t& r1, uint32_t& r2, uint32_t& r3) {
  asm volatile("ldmatrix.sync.aligned.m8n8.x4.shared.b16 {%0,%1,%2,%3}, [%4];" : "=r"(r0), "=r"(r1), "=r"(r2), "=r"(r3) : "r"(a) : "memory");
}
__device__ __forceinline__ void ldsm2(uint32_t a, uint32_t& r0, uint32_t& r1) {
  asm volatile("ldmatrix.sync.aligned.m8n8.x2.shared.b16 {%0,%1}, [%2];" : "=r"(r0), "=r"(r1) : "r"(a) : "memory");
}
__device__ __forceinline__ void ldsm4t(uint32_t a, uint32_t& r0, uint32_t& r1, uint32_t& r2, uint32_t& r3) {
  asm volatile("ldmatrix.sync.aligned.m8n8.x4.trans.shared.b16 {%0,%1,%2,%3}, [%4];" : "=r"(r0), "=r"(r1), "=r"(r2), "=r"(r3) : "r"(a) : "memory");
}
__device__ __forceinline__ void stsm4t(uint32_t a, uint32_t r0, uint32_t r1, uint32_t r2, uint32_t r3) {
  asm volatile("stmatrix.sync.aligned.m8n8.x4.trans.shared.b16 [%0], {%1,%2,%3,%4};" :: "r"(a), "r"(r0), "r"(r1), "r"(r2), "r"(r3) : "memory");
}
__device__ __forceinline__ uint4 ldr128(const void* p) {
  unsigned long long lo, hi;
  asm volatile("{ .reg .b128 t; ld.relaxed.gpu.global.b128 t, [%2]; mov.b128 {%0, %1}, t; }" : "=l"(lo), "=l"(hi) : "l"(p) : "memory");
  return make_uint4((uint32_t)lo, (uint32_t)(lo >> 32), (uint32_t)hi, (uint32_t)(hi >> 32));
}
__device__ __forceinline__ void str128(void* p, uint32_t x, uint32_t y, uint32_t z, uint32_t w) {
  asm volatile("{ .reg .b128 t; .reg .b64 lo, hi; mov.b64 lo, {%1,%2}; mov.b64 hi, {%3,%4}; mov.b128 t, {lo, hi}; st.relaxed.gpu.global.b128 [%0], t; }"
               :: "l"(p), "r"(x), "r"(y), "r"(z), "r"(w) : "memory");
}
__device__ __forceinline__ void str64(void* p, uint32_t x, uint32_t y) {
  asm volatile("{ .reg .b64 t; mov.b64 t, {%1,%2}; st.relaxed.gpu.global.b64 [%0], t; }" :: "l"(p), "r"(x), "r"(y) : "memory");
}
__device__ __forceinline__ uint32_t ldr32(const void* p) { uint32_t v; asm volatile("ld.relaxed.gpu.global.b32 %0, [%1];" : "=r"(v) : "l"(p) : "memory"); return v; }
__device__ __forceinline__ void str32(void* p, uint32_t v) { asm volatile("st.relaxed.gpu.global.b32 [%0], %1;" :: "l"(p), "r"(v) : "memory"); }
__device__ __forceinline__ void str16(void* p, uint32_t v) { asm volatile("st.relaxed.gpu.global.u16 [%0], %1;" :: "l"(p), "h"((uint16_t)v) : "memory"); }
__device__ __forceinline__ void fence_gpu() { asm volatile("fence.acq_rel.gpu;" ::: "memory"); }
__device__ __forceinline__ void bar_sync(int id, int n) { asm volatile("bar.sync %0, %1;" :: "r"(id), "r"(n) : "memory"); }
__device__ __forceinline__ void bar_arrive(int id, int n) { asm volatile("bar.arrive %0, %1;" :: "r"(id), "r"(n) : "memory"); }

__device__ __forceinline__ float bf_lo(uint32_t w) { return __uint_as_float(w << 16); }
__device__ __forceinline__ float bf_hi(uint32_t w) { return __uint_as_float(w & 0xFFFF0000u); }
__device__ __forceinline__ uint32_t pack_bf(float lo, float hi) { uint32_t r; asm("cvt.rn.bf16x2.f32 %0, %1, %2;" : "=r"(r) : "f"(hi), "f"(lo)); return r; }
__device__ __forceinline__ uint32_t pack_h(float lo, float hi) { uint32_t r; asm("cvt.rn.f16x2.f32 %0, %1, %2;" : "=r"(r) : "f"(hi), "f"(lo)); return r; }
__device__ __forceinline__ uint32_t pack_hv(float lo, float hi) { uint32_t r; asm volatile("cvt.rn.f16x2.f32 %0, %1, %2;" : "=r"(r) : "f"(hi), "f"(lo) : "memory"); return r; }
__device__ __forceinline__ float bfr(float x) { return bf_lo(pack_bf(x, 0.f)); }
__device__ __forceinline__ uint32_t bf_sub2(uint32_t a, uint32_t b) { __nv_bfloat162 r = __hsub2(*(__nv_bfloat162*)&a, *(__nv_bfloat162*)&b); return *(uint32_t*)&r; }
__device__ __forceinline__ uint32_t bf_add2(uint32_t a, uint32_t b) { __nv_bfloat162 r = __hadd2(*(__nv_bfloat162*)&a, *(__nv_bfloat162*)&b); return *(uint32_t*)&r; }
__device__ __forceinline__ uint32_t bf_mul2(uint32_t a, uint32_t b) { __nv_bfloat162 r = __hmul2(*(__nv_bfloat162*)&a, *(__nv_bfloat162*)&b); return *(uint32_t*)&r; }
__device__ __forceinline__ float2 h2f(uint32_t w) { return __half22float2(*(__half2*)&w); }
__device__ __forceinline__ float ex2(float x) { float r; asm("ex2.approx.ftz.f32 %0, %1;" : "=f"(r) : "f"(x)); return r; }
__device__ __forceinline__ float warp_sum(float v) {
#pragma unroll
  for (int o = 16; o > 0; o >>= 1) v += __shfl_xor_sync(0xffffffffu, v, o);
  return v;
}
__device__ __forceinline__ void mma_f16_f32(float* d, uint32_t a0, uint32_t a1, uint32_t a2, uint32_t a3, uint32_t b0, uint32_t b1) {
  asm volatile("mma.sync.aligned.m16n8k16.row.col.f32.f16.f16.f32 {%0,%1,%2,%3}, {%4,%5,%6,%7}, {%8,%9}, {%0,%1,%2,%3};"
               : "+f"(d[0]), "+f"(d[1]), "+f"(d[2]), "+f"(d[3]) : "r"(a0), "r"(a1), "r"(a2), "r"(a3), "r"(b0), "r"(b1));
}
__device__ __forceinline__ void mma_f16_f16(uint32_t& d0, uint32_t& d1, uint32_t a0, uint32_t a1, uint32_t a2, uint32_t a3, uint32_t b0, uint32_t b1) {
  asm volatile("mma.sync.aligned.m16n8k16.row.col.f16.f16.f16.f16 {%0,%1}, {%2,%3,%4,%5}, {%6,%7}, {%0,%1};"
               : "+r"(d0), "+r"(d1) : "r"(a0), "r"(a1), "r"(a2), "r"(a3), "r"(b0), "r"(b1));
}
__device__ __forceinline__ void mma_bf16(float* d, uint32_t a0, uint32_t a1, uint32_t a2, uint32_t a3, uint32_t b0, uint32_t b1) {
  asm volatile("mma.sync.aligned.m16n8k16.row.col.f32.bf16.bf16.f32 {%0,%1,%2,%3}, {%4,%5,%6,%7}, {%8,%9}, {%0,%1,%2,%3};"
               : "+f"(d[0]), "+f"(d[1]), "+f"(d[2]), "+f"(d[3]) : "r"(a0), "r"(a1), "r"(a2), "r"(a3), "r"(b0), "r"(b1));
}
__device__ __forceinline__ void mma_bf16_k8(float* d, uint32_t a0, uint32_t a1, uint32_t b0) {
  asm volatile("mma.sync.aligned.m16n8k8.row.col.f32.bf16.bf16.f32 {%0,%1,%2,%3}, {%4,%5}, {%6}, {%0,%1,%2,%3};"
               : "+f"(d[0]), "+f"(d[1]), "+f"(d[2]), "+f"(d[3]) : "r"(a0), "r"(a1), "r"(b0));
}

__device__ __forceinline__ void wg_fence() { asm volatile("wgmma.fence.sync.aligned;" ::: "memory"); }
__device__ __forceinline__ void wg_commit() { asm volatile("wgmma.commit_group.sync.aligned;" ::: "memory"); }
template <int N> __device__ __forceinline__ void wg_wait() { asm volatile("wgmma.wait_group.sync.aligned %0;" :: "n"(N) : "memory"); }
template <int TB> __device__ __forceinline__ void wgmma32(float* d, const uint32_t* a, uint32_t dlo, uint32_t dhi) {
  asm volatile("{ .reg .b64 dd; mov.b64 dd, {%20, %21}; wgmma.mma_async.sync.aligned.m64n32k16.f32.f16.f16 "
               "{%0,%1,%2,%3,%4,%5,%6,%7,%8,%9,%10,%11,%12,%13,%14,%15}, {%16,%17,%18,%19}, dd, 1, 1, 1, %22; }"
               : "+f"(d[0]), "+f"(d[1]), "+f"(d[2]), "+f"(d[3]), "+f"(d[4]), "+f"(d[5]), "+f"(d[6]), "+f"(d[7]), "+f"(d[8]), "+f"(d[9]), "+f"(d[10]), "+f"(d[11]), "+f"(d[12]), "+f"(d[13]), "+f"(d[14]), "+f"(d[15])
               : "r"(a[0]), "r"(a[1]), "r"(a[2]), "r"(a[3]), "r"(dlo), "r"(dhi), "n"(TB));
}
template <int TB> __device__ __forceinline__ void wgmma96(float* d, const uint32_t* a, uint32_t dlo, uint32_t dhi) {
  asm volatile("{ .reg .b64 dd; mov.b64 dd, {%52, %53}; wgmma.mma_async.sync.aligned.m64n96k16.f32.f16.f16 "
               "{%0,%1,%2,%3,%4,%5,%6,%7,%8,%9,%10,%11,%12,%13,%14,%15,%16,%17,%18,%19,%20,%21,%22,%23,%24,%25,%26,%27,%28,%29,%30,%31,%32,%33,%34,%35,%36,%37,%38,%39,%40,%41,%42,%43,%44,%45,%46,%47}, {%48,%49,%50,%51}, dd, 1, 1, 1, %54; }"
               : "+f"(d[0]), "+f"(d[1]), "+f"(d[2]), "+f"(d[3]), "+f"(d[4]), "+f"(d[5]), "+f"(d[6]), "+f"(d[7]), "+f"(d[8]), "+f"(d[9]), "+f"(d[10]), "+f"(d[11]), "+f"(d[12]), "+f"(d[13]), "+f"(d[14]), "+f"(d[15]), "+f"(d[16]), "+f"(d[17]), "+f"(d[18]), "+f"(d[19]), "+f"(d[20]), "+f"(d[21]), "+f"(d[22]), "+f"(d[23]), "+f"(d[24]), "+f"(d[25]), "+f"(d[26]), "+f"(d[27]), "+f"(d[28]), "+f"(d[29]), "+f"(d[30]), "+f"(d[31]), "+f"(d[32]), "+f"(d[33]), "+f"(d[34]), "+f"(d[35]), "+f"(d[36]), "+f"(d[37]), "+f"(d[38]), "+f"(d[39]), "+f"(d[40]), "+f"(d[41]), "+f"(d[42]), "+f"(d[43]), "+f"(d[44]), "+f"(d[45]), "+f"(d[46]), "+f"(d[47])
               : "r"(a[0]), "r"(a[1]), "r"(a[2]), "r"(a[3]), "r"(dlo), "r"(dhi), "n"(TB));
}
template <int TB> __device__ __forceinline__ void wgmma96_init(float* d, const uint32_t* a, uint32_t dlo, uint32_t dhi) {
  asm volatile("{ .reg .b64 dd; mov.b64 dd, {%52, %53}; wgmma.mma_async.sync.aligned.m64n96k16.f32.f16.f16 "
               "{%0,%1,%2,%3,%4,%5,%6,%7,%8,%9,%10,%11,%12,%13,%14,%15,%16,%17,%18,%19,%20,%21,%22,%23,%24,%25,%26,%27,%28,%29,%30,%31,%32,%33,%34,%35,%36,%37,%38,%39,%40,%41,%42,%43,%44,%45,%46,%47}, {%48,%49,%50,%51}, dd, 0, 1, 1, %54; }"
               : "=f"(d[0]), "=f"(d[1]), "=f"(d[2]), "=f"(d[3]), "=f"(d[4]), "=f"(d[5]), "=f"(d[6]), "=f"(d[7]), "=f"(d[8]), "=f"(d[9]), "=f"(d[10]), "=f"(d[11]), "=f"(d[12]), "=f"(d[13]), "=f"(d[14]), "=f"(d[15]), "=f"(d[16]), "=f"(d[17]), "=f"(d[18]), "=f"(d[19]), "=f"(d[20]), "=f"(d[21]), "=f"(d[22]), "=f"(d[23]), "=f"(d[24]), "=f"(d[25]), "=f"(d[26]), "=f"(d[27]), "=f"(d[28]), "=f"(d[29]), "=f"(d[30]), "=f"(d[31]), "=f"(d[32]), "=f"(d[33]), "=f"(d[34]), "=f"(d[35]), "=f"(d[36]), "=f"(d[37]), "=f"(d[38]), "=f"(d[39]), "=f"(d[40]), "=f"(d[41]), "=f"(d[42]), "=f"(d[43]), "=f"(d[44]), "=f"(d[45]), "=f"(d[46]), "=f"(d[47])
               : "r"(a[0]), "r"(a[1]), "r"(a[2]), "r"(a[3]), "r"(dlo), "r"(dhi), "n"(TB));
}
template <int TB> __device__ __forceinline__ void wgmma32_init(float* d, const uint32_t* a, uint32_t dlo, uint32_t dhi) {
  asm volatile("{ .reg .b64 dd; mov.b64 dd, {%20, %21}; wgmma.mma_async.sync.aligned.m64n32k16.f32.f16.f16 "
               "{%0,%1,%2,%3,%4,%5,%6,%7,%8,%9,%10,%11,%12,%13,%14,%15}, {%16,%17,%18,%19}, dd, 0, 1, 1, %22; }"
               : "=f"(d[0]), "=f"(d[1]), "=f"(d[2]), "=f"(d[3]), "=f"(d[4]), "=f"(d[5]), "=f"(d[6]), "=f"(d[7]), "=f"(d[8]), "=f"(d[9]), "=f"(d[10]), "=f"(d[11]), "=f"(d[12]), "=f"(d[13]), "=f"(d[14]), "=f"(d[15])
               : "r"(a[0]), "r"(a[1]), "r"(a[2]), "r"(a[3]), "r"(dlo), "r"(dhi), "n"(TB));
}
__device__ __forceinline__ void wgmma64h(uint32_t* d, uint32_t a0, uint32_t a1, uint32_t a2, uint32_t a3, uint32_t dlo, uint32_t dhi) {
  asm volatile("{ .reg .b64 dd; mov.b64 dd, {%20, %21}; wgmma.mma_async.sync.aligned.m64n64k16.f16.f16.f16 "
               "{%0,%1,%2,%3,%4,%5,%6,%7,%8,%9,%10,%11,%12,%13,%14,%15}, {%16,%17,%18,%19}, dd, 1, 1, 1, 0; }"
               : "+r"(d[0]), "+r"(d[1]), "+r"(d[2]), "+r"(d[3]), "+r"(d[4]), "+r"(d[5]), "+r"(d[6]), "+r"(d[7]), "+r"(d[8]), "+r"(d[9]), "+r"(d[10]), "+r"(d[11]), "+r"(d[12]), "+r"(d[13]), "+r"(d[14]), "+r"(d[15])
               : "r"(a0), "r"(a1), "r"(a2), "r"(a3), "r"(dlo), "r"(dhi));
}
__device__ __forceinline__ void wgmma64h_init(uint32_t* d, uint32_t a0, uint32_t a1, uint32_t a2, uint32_t a3, uint32_t dlo, uint32_t dhi) {
  asm volatile("{ .reg .b64 dd; mov.b64 dd, {%20, %21}; wgmma.mma_async.sync.aligned.m64n64k16.f16.f16.f16 "
               "{%0,%1,%2,%3,%4,%5,%6,%7,%8,%9,%10,%11,%12,%13,%14,%15}, {%16,%17,%18,%19}, dd, 0, 1, 1, 0; }"
               : "=r"(d[0]), "=r"(d[1]), "=r"(d[2]), "=r"(d[3]), "=r"(d[4]), "=r"(d[5]), "=r"(d[6]), "=r"(d[7]), "=r"(d[8]), "=r"(d[9]), "=r"(d[10]), "=r"(d[11]), "=r"(d[12]), "=r"(d[13]), "=r"(d[14]), "=r"(d[15])
               : "r"(a0), "r"(a1), "r"(a2), "r"(a3), "r"(dlo), "r"(dhi));
}
__device__ __forceinline__ void wgmma40_ss(float* d, uint32_t alo, uint32_t blo, uint32_t hi) {
  asm volatile("{ .reg .b64 da, db; mov.b64 da, {%20, %22}; mov.b64 db, {%21, %22}; "
               "wgmma.mma_async.sync.aligned.m64n40k16.f32.f16.f16 {%0,%1,%2,%3,%4,%5,%6,%7,%8,%9,%10,%11,%12,%13,%14,%15,%16,%17,%18,%19}, da, db, 1, 1, 1, 1, 1; }"
               : "+f"(d[0]), "+f"(d[1]), "+f"(d[2]), "+f"(d[3]), "+f"(d[4]), "+f"(d[5]), "+f"(d[6]), "+f"(d[7]), "+f"(d[8]), "+f"(d[9]), "+f"(d[10]), "+f"(d[11]), "+f"(d[12]), "+f"(d[13]), "+f"(d[14]), "+f"(d[15]), "+f"(d[16]), "+f"(d[17]), "+f"(d[18]), "+f"(d[19])
               : "r"(alo), "r"(blo), "r"(hi));
}
__device__ __forceinline__ void wgmma40_ss_init(float* d, uint32_t alo, uint32_t blo, uint32_t hi) {
  asm volatile("{ .reg .b64 da, db; mov.b64 da, {%20, %22}; mov.b64 db, {%21, %22}; "
               "wgmma.mma_async.sync.aligned.m64n40k16.f32.f16.f16 {%0,%1,%2,%3,%4,%5,%6,%7,%8,%9,%10,%11,%12,%13,%14,%15,%16,%17,%18,%19}, da, db, 0, 1, 1, 1, 1; }"
               : "=f"(d[0]), "=f"(d[1]), "=f"(d[2]), "=f"(d[3]), "=f"(d[4]), "=f"(d[5]), "=f"(d[6]), "=f"(d[7]), "=f"(d[8]), "=f"(d[9]), "=f"(d[10]), "=f"(d[11]), "=f"(d[12]), "=f"(d[13]), "=f"(d[14]), "=f"(d[15]), "=f"(d[16]), "=f"(d[17]), "=f"(d[18]), "=f"(d[19])
               : "r"(alo), "r"(blo), "r"(hi));
}
__device__ __forceinline__ float vzero() { float v; asm volatile("mov.b32 %0, 0;" : "=f"(v)); return v; }
__device__ __forceinline__ void tma_box(uint32_t dst, const CUtensorMap* tm, uint32_t mb, int x, int y) {
  asm volatile("cp.async.bulk.tensor.2d.shared::cluster.global.mbarrier::complete_tx::bytes [%0], [%1, {%3, %4}], [%2];"
               :: "r"(dst), "l"(tm), "r"(mb), "r"(x), "r"(y) : "memory");
}
__device__ __forceinline__ void l2_prefetch(const void* src, uint32_t bytes) {
  asm volatile("cp.async.bulk.prefetch.L2.global [%0], %1;" :: "l"(src), "r"(bytes) : "memory");
}
__device__ __forceinline__ uint32_t uni(uint32_t v) {
  uint32_t r; asm volatile("shfl.sync.idx.b32 %0, %1, 0, 0x1f, 0xffffffff;" : "=r"(r) : "r"(v)); return r;
}
__device__ __forceinline__ int fresh_tid() { int v; asm volatile("mov.u32 %0, %tid.x;" : "=r"(v)); return v; }

struct Params {
  const unsigned char* x;
  Scratch* s;
  int off[7];
  uint32_t zero;
  uint32_t* out;
  const uint32_t* dskip;
  const uint32_t* w_r;
  const unsigned char* w_gate;
  const unsigned char* w_up;
  const unsigned char* w_down;
  long long* ts;
  const unsigned char* far[7];
};
__device__ __forceinline__ uint32_t ldnc32(const void* p) { uint32_t v; asm volatile("ld.global.nc.b32 %0, [%1];" : "=r"(v) : "l"(p)); return v; }
__device__ __forceinline__ uint32_t ldnc16(const void* p) { uint16_t v; asm volatile("ld.global.nc.u16 %0, [%1];" : "=h"(v) : "l"(p)); return v; }
__device__ __forceinline__ uint4 ldnc128(const void* p) { uint4 v; asm volatile("ld.global.nc.v4.b32 {%0,%1,%2,%3}, [%4];" : "=r"(v.x), "=r"(v.y), "=r"(v.z), "=r"(v.w) : "l"(p)); return v; }
__device__ __forceinline__ void mbar_wait(uint32_t mb, uint32_t ph = 0) {
#pragma unroll 1
  for (int it = 0; it < SPIN_MAX; it++) {
    uint32_t ok;
    asm volatile("{ .reg .pred q; mbarrier.try_wait.parity.shared::cta.b64 q, [%1], %2; selp.u32 %0, 1, 0, q; }" : "=r"(ok) : "r"(mb), "r"(ph) : "memory");
    if (ok) break;
  }
}
__device__ __forceinline__ uint32_t mbar_test(uint32_t mb) {
  uint32_t ok;
  asm volatile("{ .reg .pred q; mbarrier.test_wait.parity.shared::cta.b64 q, [%1], 0; selp.u32 %0, 1, 0, q; }" : "=r"(ok) : "r"(mb) : "memory");
  return ok;
}
__device__ __forceinline__ void mbar_arrive(uint32_t mb) { asm volatile("mbarrier.arrive.shared::cta.b64 _, [%0];" :: "r"(mb) : "memory"); }
__device__ __forceinline__ uint32_t ldg16(const void* p) { uint16_t v; asm volatile("ld.global.u16 %0, [%1];" : "=h"(v) : "l"(p) : "memory"); return v; }
__device__ __forceinline__ uint32_t ldr16(const void* p) { uint16_t v; asm volatile("ld.relaxed.gpu.global.u16 %0, [%1];" : "=h"(v) : "l"(p) : "memory"); return v; }
__device__ __forceinline__ void fence_async() { asm volatile("fence.proxy.async.shared::cta;" ::: "memory"); }
#define SPIN_WHILE(cond, body) _Pragma("unroll 1") for (int _it = 0; _it < SPIN_MAX && __any_sync(0xffffffffu, (cond)); _it++) { body; }

struct LnC { uint32_t m2, rh2, rl2; };
__device__ __forceinline__ float diag_sum(float d0, float d1, int t) {
  float q = __shfl_sync(0xffffffffu, d0, 9 * t) + __shfl_sync(0xffffffffu, d1, 9 * t + 4);
  q += __shfl_xor_sync(0xffffffffu, q, 1);
  return q + __shfl_xor_sync(0xffffffffu, q, 2);
}
__device__ __forceinline__ LnC ln_consts(float s, float q, float& r) {
  const float mean = s * (1.f / DM);
  const float var = fmaxf(fmaf(-mean, mean, q * (1.f / DM)), 0.f);
  float sd;
  asm("sqrt.approx.ftz.f32 %0, %1;" : "=f"(sd) : "f"(bfr(bfr(var) + 1e-5f)));
  asm("rcp.approx.ftz.f32 %0, %1;" : "=f"(r) : "f"(bfr(sd)));
  LnC c;
  c.m2 = pack_bf(mean, mean);
  c.rh2 = pack_bf(r, r);
  const float rl = r - bf_lo(c.rh2);
  c.rl2 = pack_bf(rl, rl);
  return c;
}
__device__ __forceinline__ float quad_sum(float s) { s += __shfl_xor_sync(0xffffffffu, s, 1); return s + __shfl_xor_sync(0xffffffffu, s, 2); }
__device__ __forceinline__ uint32_t bf_fma2(uint32_t a, uint32_t b, uint32_t c) {
  __nv_bfloat162 r = __hfma2(*(const __nv_bfloat162*)&a, *(const __nv_bfloat162*)&b, *(const __nv_bfloat162*)&c);
  return *(uint32_t*)&r;
}
__device__ __forceinline__ uint32_t ln_apply(uint32_t w, uint32_t m2, uint32_t rh2, uint32_t rl2) {
  const uint32_t d = bf_sub2(w, m2);
  return bf_fma2(d, rh2, bf_mul2(d, rl2));
}

__device__ __forceinline__ float2 cis(float mag_log2, float rev) {
  const float m = ex2(mag_log2), ang = rev * 6.283185307179586f;
  return make_float2(m * __cosf(ang), m * __sinf(ang));
}
__device__ __forceinline__ float2 csq(float2 a) { return make_float2(fmaf(a.x, a.x, -a.y * a.y), (a.x + a.x) * a.y); }
__device__ __forceinline__ float2 cmul(float2 a, float2 b) { return make_float2(fmaf(a.x, b.x, -a.y * b.y), fmaf(a.x, b.y, a.y * b.x)); }
__device__ __forceinline__ void pmul(uint32_t xr, uint32_t xi, uint32_t w, uint32_t& yr, uint32_t& yi) {
  const __half2 XR = *(__half2*)&xr, XI = *(__half2*)&xi, W = *(__half2*)&w;
  const __half2 a = __hfma2(__hneg2(XI), __high2half2(W), __hmul2(XR, __low2half2(W)));
  const __half2 b = __hfma2(XI, __low2half2(W), __hmul2(XR, __high2half2(W)));
  yr = *(const uint32_t*)&a; yi = *(const uint32_t*)&b;
}
__device__ __forceinline__ uint32_t pk(float2 a) { return pack_h(a.x, a.y); }

struct KgState { float2 c0, z8; uint32_t w64, w128, w192; };
__device__ __forceinline__ void kgen_tables_n(const uint32_t (&raw)[7], uint32_t scr, int wt, KgState& k) {
  const uint32_t dst = scr + 16384 + wt * 16;
  const float dt = bfr(ex2(bf_lo(raw[6]) * 1.4426950408889634f));
  const float th = dt * bf_lo(raw[1]);
  const float br = dt * bf_lo(raw[2]), bi = dt * bf_lo(raw[3]);
  const float Cr = bf_lo(raw[4]), Ci = bf_lo(raw[5]);
  k.c0 = make_float2(fmaf(Cr, br, -Ci * bi), fmaf(Cr, bi, Ci * br));
  const uint32_t mx = __reduce_max_sync(0xffffffffu, __float_as_uint(fmaxf(fabsf(k.c0.x), fabsf(k.c0.y))));
  const float a2 = dt * bf_lo(raw[0]) * 1.4426950408889634f;
  const float rh = th * 0.15915494309189535f;
  const float rl = fmaf(th, (float)(0.15915494309189535 - (double)0.15915494309189535f), fmaf(th, 0.15915494309189535f, -rh));
  const float rf = rh - rintf(rh);
  const float2 z1 = cis(a2, rf + rl);
  const float p64 = rf * 64.f;
  const float2 z64 = cis(a2 * 64.f, fmaf(64.f, rl, p64 - rintf(p64)));
  const float2 z2 = csq(z1), z128 = csq(z64), z3 = cmul(z2, z1), z4 = csq(z2), z256 = csq(z128), z6 = csq(z3), z512 = csq(z256);
  k.z8 = csq(z4);
  k.w64 = pk(z64); k.w128 = pk(z128); k.w192 = pk(cmul(z128, z64));
  sts128(dst, 0x00003C00u, pk(z2), pk(z4), pk(z6));
  const float2 z1024 = csq(z512), z768 = cmul(z512, z256);
  sts128(dst + 2048, pk(z1), pk(z3), pk(cmul(z4, z1)), pk(cmul(z4, z3)));
  const float2 z2048 = csq(z1024);
  const float k2048 = warp_sum(fmaf(k.c0.x, z2048.x, -k.c0.y * z2048.y));
  sts128(dst + 4096, pk(z256), pk(cmul(z256, z2)), pk(cmul(z256, z4)), pk(cmul(z256, z6)));
  sts128(dst + 6144, pk(z512), pk(cmul(z512, z4)), pk(z768), pk(cmul(z768, z4)));
  sts128(dst + 8192, pk(z1024), pk(cmul(z1024, z256)), pk(cmul(z1024, z512)), pk(cmul(z1024, z768)));
  if ((wt & 31) == 0) { sts32(scr + W_MISC + (wt >> 5) * 4, mx); sts32(scr + W_MISC + 16 + (wt >> 5) * 4, __float_as_uint(k2048)); }
}
__device__ __forceinline__ int kgen_tables_m(uint32_t scr, int wt, const KgState& k, float& k2048) {
  const uint32_t dst = scr + wt * 16;
  const uint4 e4 = lds128(scr + W_MISC), k4 = lds128(scr + W_MISC + 16);
  const float2 z16 = csq(k.z8), z32 = csq(z16);
  const int em = max(min((int)(max(max(e4.x, e4.y), max(e4.z, e4.w)) >> 23), 238), 16);
  const float sc = __uint_as_float((uint32_t)(127 + 4 + 127 - em) << 23);
  k2048 = ((__uint_as_float(k4.x) + __uint_as_float(k4.y)) + (__uint_as_float(k4.z) + __uint_as_float(k4.w))) * sc;
  const float2 c0 = make_float2(k.c0.x * sc, k.c0.y * sc);
  const float2 c1 = cmul(c0, k.z8), c2 = cmul(c0, z16), c4 = cmul(c0, z32), c3 = cmul(c1, z16), c5 = cmul(c1, z32), c6 = cmul(c2, z32), c7 = cmul(c3, z32);
  uint32_t pr[4], pi[4], yr[4], yi[4];
  pr[0] = pack_h(c0.x, c1.x); pi[0] = pack_h(c0.y, c1.y);
  pr[1] = pack_h(c2.x, c3.x); pi[1] = pack_h(c2.y, c3.y);
  pr[2] = pack_h(c4.x, c5.x); pi[2] = pack_h(c4.y, c5.y);
  pr[3] = pack_h(c6.x, c7.x); pi[3] = pack_h(c6.y, c7.y);
  sts128(dst, pr[0], pr[1], pr[2], pr[3]); sts128(dst + 2048, pi[0], pi[1], pi[2], pi[3]);
#pragma unroll
  for (int q = 1; q < 4; q++) {
    const uint32_t w = q == 1 ? k.w64 : q == 2 ? k.w128 : k.w192;
#pragma unroll
    for (int i = 0; i < 4; i++) pmul(pr[i], pi[i], w, yr[i], yi[i]);
    sts128(dst + q * 4096, yr[0], yr[1], yr[2], yr[3]); sts128(dst + q * 4096 + 2048, yi[0], yi[1], yi[2], yi[3]);
  }
  return em;
}
__device__ __forceinline__ void kgen_build(uint32_t wb, int wg, int wt, uint32_t k0, uint32_t k1, uint32_t k2) {
  const uint32_t kt = wb + W_KT;
  const bool ev = !(wt & 1), mid = ev && wt;
  const uint32_t a0 = kt + 64 + wt * 8;
  const uint32_t a2 = kt + 64 + 2048 + (wt >> 2) * 32 + (wt & 1) * 16 + (wt & 2) * 512;
  const int ix = ((wt >> 2) + (wt & 3) * 32 - 1) & 127;
  const uint32_t a3 = wb + W_CW + 32 + ((ix & 1) ? 0 : 320) + (ix >> 1) * 4;
  const uint32_t v3 = wt ? k2 : k2 >> 16;
  sts16(a3, v3); sts16(a3 + 6, v3);
  if ((unsigned)(wt - 32) < 18u) sts128(kt + (wt < 36 ? -512 : 64 + 4128 - 576) + wt * 16, 0, 0, 0, 0);
  const uint32_t sw = __byte_perm(k0, 0, 0x1032), d2 = __byte_perm(k1, 0, 0x1010), d3 = __byte_perm(k1, 0, 0x3232);
  sts16(a0, k0); sts32(a0 + 4, sw); sts16(a0 + 10, sw);
  sts16(a0 + 1024 - (mid ? 4 : 0), d2); sts16(a0 + 1024 + (ev ? 10 : 6), d2);
  sts16(a2 - (mid ? 8 : 4), d3); sts64(a2, d3, d3); sts16(a2 + (ev ? 14 : 10), d3);
  if (mid) { sts64(a0 + 1024, d2, d2); sts32(a2 - 4, d3); }
  if (ev) sts32(a2 + 8, d3);
  if (wt == 0) {
    const uint32_t d = __byte_perm(k2, 0, 0x1010);
    sts16(kt + 66, 0); sts32(kt + 64 + 1028, d2);
    sts16(kt + 64 + 4088, d); sts32(kt + 64 + 4092, d); sts128(kt + 64 + 4096, d, d, d, d); sts128(kt + 64 + 4112, d, d << 16, 0, 0);
  }
  bar_sync(1 + wg, 128);
  const uint32_t cw = wb + W_CW + 32 + (wt >> 6) * 64 + wt * 4;
  sts128(wb + W_L3 + 1024 + (wt >> 6) * 1024 + wt * 16, lds32(cw), lds32(cw - 8), lds32(cw - 16), lds32(cw - 24));
}

__device__ __forceinline__ void load_a(uint32_t (&a)[4], uint32_t kp, int j) {
  a[0] = lds32(kp + 64 * j); a[1] = lds32(kp + 64 * j + 512); a[2] = lds32(kp + 64 * j - 32); a[3] = lds32(kp + 64 * j + 480);
}
__device__ __forceinline__ uint32_t band(int d, int lo, int hi) {
  return ((unsigned)(d - lo) <= (unsigned)(hi - lo) ? 1u : 0u) | ((unsigned)(d - 1 - lo) <= (unsigned)(hi - lo) ? 0x10000u : 0u);
}
__device__ __forceinline__ uint32_t hadd2u(uint32_t a, uint32_t b) { __half2 r = __hadd2(*(__half2*)&a, *(__half2*)&b); return *(uint32_t*)&r; }

__device__ __forceinline__ void zero_pads(uint32_t tb, int wt) {
  sts128(tb + W_L3 + (wt >> 6) * 1024 + wt * 16, 0, 0, 0, 0);
  if ((wt & 63) < 3) sts128(tb + W_CW + (wt >> 6) * 320 + (wt & 63) * 16, 0, 0, 0, 0);
}
__device__ __forceinline__ uint32_t tr_base(int lane) {
  return OFF_YT + (2 * (lane >> 3) + (lane & 1)) * YT_PITCH + ((lane >> 1) & 1) * (8 * YT_PITCH + 64) + ((lane >> 2) & 1) * 16;
}

__device__ __forceinline__ uint32_t sc_addr(int tp) { return OFF_YT + (tp < 16 ? tp * YT_PITCH + (tp >> 3) * 64 + 1152 : 8 * YT_PITCH - 512 + tp * 32); }
#define X_SCT 9000
#define X_DELTA 1400
#define X_DSTEP 100
#define X_PF0 3200
#define X_PFD 560
#define X_T0 7500
#define X_TD 480
#define X_YD 600
struct TMaps { CUtensorMap m[8]; };
__device__ __forceinline__ uint32_t h2bf(uint32_t w) { const float2 f = h2f(w); return pack_bf(f.x, f.y); }
__device__ __forceinline__ uint32_t keep(uint32_t v) { asm volatile("" : "+r"(v)); return v; }
__device__ __forceinline__ uint2 ldr64(const void* p) { uint2 v; asm volatile("{ .reg .b64 t; ld.relaxed.gpu.global.b64 t, [%2]; mov.b64 {%0, %1}, t; }" : "=r"(v.x), "=r"(v.y) : "l"(p) : "memory"); return v; }
__device__ __forceinline__ uint32_t down_box(int s, bool five) {
  return s < 3 ? OFF_W + (five ? W_BYTES + ALT + s * 4096 : s * 5120) : OFF_W + ((s - 1) >> 1) * W_BYTES + BOX + ((s - 1) & 1) * 5120;
}
__device__ __forceinline__ void load_tile(const CUtensorMap* tmx, int i, int c) {
  asm volatile("mbarrier.arrive.expect_tx.shared::cta.b64 _, [%0], 5120;" :: "r"(MB_UL + i * 8) : "memory");
  tma_box(OFF_W + (i < 4 ? i * W_BYTES : ALT) + W_UP, tmx, MB_UL + i * 8, (i < 4 ? i * 128 + c : 512 + (c >> 1)) * 16, -32);
}
template <bool FAR> __device__ __forceinline__ void load_params(const Params& p, uint32_t ch, int wt, uint32_t dst) {
  if (wt < 97) {
    const unsigned char* b = FAR ? p.far[wt >> 4] : p.x + (long long)p.off[wt >> 4] * 16;
    asm volatile("cp.async.cg.shared.global [%0], [%1], 16;" :: "r"(dst + wt * 16), "l"(b + (wt < 96 ? ch * 256 + (wt & 15) * 16 : (ch >> 3) * 16)) : "memory");
  }
  asm volatile("cp.async.commit_group;" ::: "memory");
}

struct ConvC { uint32_t ca, cb, bands; };
__device__ __forceinline__ ConvC conv_consts(int w, int lane) {
  const int h = w & 1, P = w >> 1, d0 = 8 * h + (lane >> 2) - 2 * (lane & 3);
  ConvC k;
  k.ca = keep((W_KT + (16 + 256 * P + d0) * 4) | ((W_UP + (32 + 64 * P + lane) * 32 + ((h ^ (lane >> 2)) & 1) * 16) << 16));
  k.cb = keep(lane < 8 ? 0xFFFEFFFEu : ~0u);
  k.bands = keep(band(d0, 12, 20) + 2 * band(d0 + 8, 12, 20) + 4 * band(d0 + 16, 12, 20) + 8 * band(d0 + 24, 12, 20)
                 + 16 * band(d0 - 8, 5, 11) + 32 * band(d0, 5, 11) + 64 * band(d0 + 8, 5, 11) + 128 * band(d0 + 16, 5, 11));
  return k;
}
__device__ __forceinline__ void conv_item(uint32_t tb, const ConvC& cv, uint32_t zero, const CUtensorMap* tmx, int ch, int warp, int lane) {
  const uint32_t kp = tb + (cv.ca & 0xFFFFu);
  const uint32_t dlo = ((tb + W_UP) >> 4) + 64 + (1u << 16), dhi = 16u | (3u << 30);
  const bool P = warp & 2;
  float a32[16], a96[48];
  uint32_t A[40][4];
#define STEP(J) { wgmma96<0>(a96, A[J], dlo + 64 - 2 * (J), dhi); if ((J) == 0) wgmma32_init<0>(a32, A[J], dlo, dhi); else if ((J) < 8) wgmma32<0>(a32, A[J], (dlo ^ zero) - 2 * (J), dhi); }
#define LD(J) load_a(A[J], kp, J);
#define FIRST(J) wg_fence(); STEP(J) wg_commit(); wg_wait<1>(); wg_fence();
  {
    uint32_t win[16], x9[4], x7[4], e[4], f[4];
    const uint32_t bz = keep(cv.bands);
#define BAND(i) keep((bz & (0x10001u << (i))) * (0x3C00u >> (i)))
    e[0] = lds32(kp + (P ? 3232 : 4096)); e[2] = lds32(kp + (P ? 3200 : 4064)); e[1] = keep(bz & 0x100u); e[3] = keep(bz & 0x200u);
    f[3] = lds32(kp + (P ? 3200 : 4128)); f[0] = keep(bz & 0x4000u); f[1] = keep(bz & 0x8000u); f[2] = keep(bz & 0x300u);
    const uint32_t q[12] = {BAND(0), BAND(5), keep(bz & 0x400u), BAND(4), BAND(2), BAND(7), BAND(1), BAND(6), keep(bz & 0x800u), keep(bz & 0x1000u), BAND(3), keep(bz & 0x2000u)};
#undef BAND
    TS(3);
    wg_fence();
    wgmma64h_init(win, q[0], q[1], q[2], q[3], dlo, dhi);
    wgmma64h(win, q[4], q[5], q[6], q[7], dlo - 2, dhi);
    wgmma64h(win, q[8], q[9], q[10], q[11], dlo - 4, dhi);
    wg_commit();
    wgmma96_init<0>(a96, e, dlo - 64, dhi);
    wgmma96<0>(a96, f, dlo - 50, dhi);
    wg_commit();
    wg_wait<1>();
#pragma unroll
    for (int i = 0; i < 4; i++) {
      const int tl = 2 * ((i & 1) + ((i & 2) ? 0 : 4));
      x9[i] = P ? win[tl + 4] : win[tl]; x7[i] = P ? win[tl + 5] : win[tl + 1];
    }
    const uint32_t l3lo = ((tb + W_L3) >> 4) + (32u << 16);
    wg_fence();
    wgmma96<0>(a96, x9, l3lo, 8);
    wgmma96<0>(a96, x7, l3lo + 128, 8);
    wg_commit();
  }
  LD(32) LD(33) LD(34) LD(35)
  FIRST(32) STEP(33) STEP(34) STEP(35) wg_commit();
  LD(36) LD(37) LD(38)
  FIRST(36) STEP(37) STEP(38) wg_commit();
  LD(39) LD(0)
  TS(17);
  FIRST(39) STEP(0) wg_commit();
  LD(1) LD(2) LD(3)
  FIRST(1) STEP(2) STEP(3) wg_commit();
  LD(4) LD(5)
  FIRST(4) STEP(5) wg_commit();
  LD(6) LD(7)
  wg_fence(); STEP(6) STEP(7) wg_commit();
#undef STEP
#undef LD
#undef FIRST
  TS(18);
  const uint32_t xc = tb + W_KT + (warp & 3) * 1024 + lane * 16;
  wg_wait<0>();
  uint32_t E[16], o[8];
#define ACC(i) ((i) < 16 ? a32[i] : a96[(i) - 16])
  E[0] = pack_h(a32[0], a32[1]);
#pragma unroll
  for (int i = 1; i < 16; i++) E[i] = pack_h(ACC(4 * i) + ACC(4 * i - 2), ACC(4 * i + 1) + ACC(4 * i - 1));
#undef ACC
#pragma unroll
  for (int j = 0; j < 8; j++) o[j] = P ? (j < 2 ? 0u : E[j - 2]) : E[8 + j];
  sts128(xc, o[0], o[1], o[2], o[3]); sts128(xc + 512, o[4], o[5], o[6], o[7]);
#pragma unroll
  for (int j = 0; j < 8; j++) o[j] = P ? E[6 + j] : E[j];
  TS(25);
  bar_sync(1 + (warp >> 2), 128);
#pragma unroll
  for (int q = 0; q < 2; q++) {
    const uint4 v = lds128(xc + (P ? -2048 : 2048) + q * 512);
    stsm4t(tb + (cv.ca >> 16) + q * 1024, hadd2u(o[4 * q], v.x) & cv.cb, hadd2u(o[4 * q + 1], v.y) & cv.cb, hadd2u(o[4 * q + 2], v.z) & cv.cb, hadd2u(o[4 * q + 3], v.w) & cv.cb);
  }
  fence_async();
  bar_sync(1 + (warp >> 2), 128);
  if ((warp & 3) == 3 && lane == 0) {
    asm volatile("cp.async.bulk.tensor.2d.global.shared::cta.bulk_group [%0, {%2, %3}], [%1];" :: "l"(tmx), "r"(tb + W_UP + 1024), "r"(ch * 16), "r"(0) : "memory");
    asm volatile("cp.async.bulk.commit_group;" ::: "memory");
  }
}

template <bool FAR> __global__ void __launch_bounds__(NT, 1)
fused_kernel(const __grid_constant__ Params p, const __grid_constant__ TMaps tm) {
  extern __shared__ __align__(1024) unsigned char smem[];
  const int c = blockIdx.x;
  const bool five = (c & 1) == 0;
  const uint32_t pitch = five ? 64 : 80;
  const uint32_t ones = 0x3F803F80u;
  const int tid = threadIdx.x, lane = tid & 31;
  const int warp = (int)uni(tid >> 5), wg = warp >> 2;
  TS(0);
  if (__builtin_expect(wg == 4, 0)) {
    asm volatile("setmaxnreg.dec.sync.aligned.u32 32;");
    const int role = warp;
    const int u0 = (c >> 1) * 9 + (five ? ((c & 2) ? 5 : 0) : ((c & 2) ? 0 : 4));
    const uint32_t t0 = clock() + c * 4;
    if (role == 16) {
      if (lane < 18) asm volatile("mbarrier.init.shared::cta.b64 [%0], 1;" :: "r"(OFF_MISC + lane * 8) : "memory");
      if (lane < 2) asm volatile("mbarrier.arrive.expect_tx.shared::cta.b64 _, [%0], %1;" :: "r"(OFF_MISC + lane * 8), "r"(pitch * (lane ? 576 : 1152)) : "memory");
      fence_async();
      bar_arrive(0, 576);
      const CUtensorMap* tmb = &tm.m[five ? 3 : 0];
      int tn = X_T0;
#pragma unroll 1
      for (int it = 0; it < 21; it++) {
        const int dn = it >= 12, s = dn ? it - 12 : it < 6 ? it : it - 6;
        const uint32_t dst = it < 6 ? OFF_G + s * 96 * pitch : dn ? down_box(s, five) : OFF_W + W_BYTES + (s >> 1) * W_BYTES + (s & 1) * 96 * pitch;
        while ((int)(clock() - t0) < tn) __nanosleep(40);
        mbar_wait(it < 6 ? MB_GF : MB_KF + (dn ? 0 : 8 + (s >> 1) * 8));
        if (lane == 0) tma_box(dst, tmb + (dn ? 2 : it >= 6), dn ? MB_D : MB_GU, dn ? s * 64 : u0 * 8, dn ? u0 * 8 : s * 96);
        tn = max(tn, (int)(clock() - t0) - X_TD) + (dn ? X_TD * 2 / 3 : X_TD);
        if (it == 5) TS(2);
        if (it == 11) TS(3);
      }
      TS(4);
      TS_DUMP();
    } else if (role == 17) {
      if (smem_u32(smem) != SB) __trap();
#pragma unroll 1
      for (int ip = 0; ip < 18; ip++) {
        const unsigned char* src = ip < 12 ? (ip < 6 ? p.w_gate : p.w_up - 6 * 884736) + (uint32_t)(ip * 884736 + c * 6912) : p.w_down + (uint32_t)(u0 * 9216 + (ip - 12) * pitch * 96);
        while ((int)(clock() - t0) < X_PF0 + ip * X_PFD) __nanosleep(40);
        if (lane == 0) l2_prefetch(src, ip < 12 ? 6912 : pitch * 96);
      }
    } else if (role == 18) {
      sts32(MISC_EPOCH, 0);
      bar_arrive(0, 576);
      uint4* q = lane < 2 ? &p.s->R[c * 2 + lane] : lane < 11 ? &p.s->HS[c * 9 + lane - 2] : lane == 11 ? &p.s->HS[1152 + (c & 7)] : (uint4*)&p.s->FLAG[c * 8];
      if (lane < (c < 8 ? 12 : 11)) str128(q, ~0u, ~0u, ~0u, ~0u);
      const uint32_t ep = __shfl_sync(0xffffffffu, ldr32(q), 31) + 1u;
      if (lane == 31) { sts32(MISC_EPOCH, ep | 0x80000000u); str32(q, ep); }
      bar_sync(10, 576);
      if (lane == 0) {
        asm volatile("cp.async.bulk.global.shared::cta.bulk_group [%0], [%1], %2;" :: "l"(&p.s->X[c * DM * 2]), "r"(OFF_G), "n"(DM * 32) : "memory");
        asm volatile("cp.async.bulk.commit_group;" ::: "memory");
        const uint32_t tp = clock();
        asm volatile("cp.async.bulk.wait_group 0;" ::: "memory");
        mbar_arrive(MB_GF);
#pragma unroll 1
        for (int i = 0; i < 4 + five; i++) {
          while ((int)(clock() - tp) < X_DELTA + i * X_DSTEP) {}
          if (i == 4) mbar_wait(MB_KF);
          load_tile(&tm.m[6], i, c);
        }
      }
      __syncwarp();
      while ((int)(clock() - t0) < X_SCT) __nanosleep(100);
#pragma unroll 1
      for (int i = lane; i < 96; i += 32) {
        const uint4* sp = (const uint4*)p.s->SC + min(i, 71);
        const uint32_t e2 = (ep & 127u) * 0x10001u;
        uint4 v = ldr128(sp);
        SPIN_WHILE(((v.x ^ e2) | (v.y ^ e2) | (v.z ^ e2) | (v.w ^ e2)) & 0x7F007Fu, __nanosleep(100); v = ldr128(sp));
        if (i < 72) sts64(sc_addr(i >> 2) + (i & 3) * 8, __byte_perm(v.x << 1, v.y << 1, 0x7531), __byte_perm(v.z << 1, v.w << 1, 0x7531));
      }
      bar_sync(11, 64);
      if (lane == 0) mbar_arrive(MB_SC);
    } else {
      uint32_t w[9], d[9];
      float s = 0.f;
#pragma unroll
      for (int i = 0; i < 9; i++) { w[i] = ldnc32(p.w_r + lane + 32 * i); d[i] = ldnc32(p.dskip + lane + 32 * i); }
#pragma unroll
      for (int i = 0; i < 9; i++) { sts32(OFF_WR + lane * 4 + i * 128, w[i]); sts32(OFF_WR + 1152 + lane * 4 + i * 128, d[i]); s += bf_lo(w[i]) + bf_hi(w[i]); }
      sts32(MISC_SW, __float_as_uint(warp_sum(s)));
      bar_arrive(11, 64);
      bar_sync(10, 576);
#pragma unroll 1
      for (int i = 0; i < 4 + five; i++) {
        const uint32_t ta = OFF_W + (i < 4 ? i * W_BYTES : ALT) + W_UP + 1024 + lane * 32 + (lane & 4) * 4;
#pragma unroll 1
        for (int it = 0; it < SPIN_MAX; it++) {
          mbar_wait(MB_UL + i * 8, it & 1);
          uint32_t m = 1;
#pragma unroll
          for (int q = 0; q < 4; q++) { uint32_t r0, r1, r2, r3; ldsm4(ta + q * 1024, r0, r1, r2, r3); m &= r0 & r1 & r2 & r3; }
          if (__all_sync(0xffffffffu, m || (lane & 3))) break;
          if (lane == 0) load_tile(&tm.m[6], i, c);
        }
        if (lane == 0) mbar_arrive(MB_UV + i * 8);
      }
    }
    return;
  }
  const int wt = tid & 127, g = lane >> 2, t = lane & 3;
  const uint32_t wb = OFF_W + wg * W_BYTES;
  {
    const int lw = warp - (five ? 8 : 4);
    if ((unsigned)lw < 8u) {
      const unsigned char* xp = p.x + (uint32_t)((c * 8 + lw) * 2304 + lane * 16);
      const uint32_t row = OFF_YT + lw * (2 * YT_PITCH) + (lw >> 2) * 64 + lane * 16;
#pragma unroll
      for (int k = 0; k < 5; k++)
        if (k < 4 || lane < 16)
          asm volatile("cp.async.cg.shared.global [%0], [%1], 16;" :: "r"(row + k * 512 + ((k > 2 || (k == 2 && lane >= 8)) ? 32 : 0)), "l"(xp + k * 512) : "memory");
      asm volatile("cp.async.commit_group;" ::: "memory");
    } else load_params<FAR>(p, wg == 3 ? 512 + (c >> 1) : wg * 128 + c, wt, wb + W_KT + (wg == 3) * 2048);
  }
  TS(29);
  const ConvC cv = conv_consts(warp & 3, lane);
  zero_pads(wb, wt);
  if (wg > (five ? 1 : 0)) load_params<FAR>(p, wg * 128 + c, wt, wb + W_KT);
  asm volatile("setmaxnreg.inc.sync.aligned.u32 112;");
  bar_sync(0, 576);
  TS(13);
  {
    uint4 kw;
    uint4* kx = &p.s->KX[(c >> 1) * 128 + wt];
    const int lw = warp - (five ? 8 : 4);
    bool two = wg == 3;
    uint32_t ep;
    int phase = (unsigned)lw < 8u ? 2 : 1;
#pragma unroll 1
    for (;;) {
      KgState ks;
      const bool first = two && !five;
      if (first || phase == 2) asm volatile("cp.async.wait_group 1;" ::: "memory"); else asm volatile("cp.async.wait_group 0;" ::: "memory");
      if (phase == 2) {
        __syncwarp();
        TS(21);
        float d[4][4];
#pragma unroll
        for (int r = 0; r < 2; r++) {
          const uint32_t row = OFF_YT + (2 * lw + r) * YT_PITCH + (lw >> 2) * 64;
          const uint4 a = lds128(row + lane * 16), b = lds128(row + 512 + lane * 16);
          const uint32_t e = lds32(row + 1024 + lane * 4);
#pragma unroll
          for (int i = 0; i < 4; i++) d[r][i] = d[r + 2][i] = 0.f;
          mma_bf16(d[r], a.x, ones, a.y, ones, a.x, a.y); mma_bf16(d[r + 2], a.z, ones, a.w, ones, a.z, a.w);
          mma_bf16(d[r], b.x, ones, b.y, ones, b.x, b.y); mma_bf16(d[r + 2], b.z, ones, b.w, ones, b.z, b.w);
          mma_bf16_k8(d[r], e, ones, e);
#pragma unroll
          for (int i = 0; i < 4; i++) d[r][i] += d[r + 2][i];
        }
        const float q0 = __shfl_sync(0xffffffffu, d[0][0], 9 * t) + __shfl_sync(0xffffffffu, d[0][1], 9 * t + 4);
        const float q1 = __shfl_sync(0xffffffffu, d[1][0], 9 * t) + __shfl_sync(0xffffffffu, d[1][1], 9 * t + 4);
        float r;
        const LnC lc = ln_consts(quad_sum(lane & 16 ? d[1][2] + d[1][3] : d[0][2] + d[0][3]), quad_sum(lane & 16 ? q1 : q0), r);
        if ((lane & 15) < 3) sts16(MISC_LN1 + (lane & 15) * 32 + lw * 4 + (lane >> 4) * 2, t == 0 ? lc.m2 : t == 1 ? lc.rh2 : lc.rl2);
        ks.c0 = ks.z8 = make_float2(0.f, 0.f); ks.w64 = ks.w128 = ks.w192 = 0;
      } else {
        uint32_t raw[7];
        bar_sync(1 + wg, 128);
        TS(22);
#pragma unroll
        for (int i = 0; i < 7; i++) raw[i] = lds16(wb + W_KT + first * 2048 + i * 256 + (i < 6 ? wt : (c >> first) & 7) * 2);
        kgen_tables_n(raw, wb, wt, ks);
        TS(20);
      }
      if (phase) {
        const uint32_t tr_addr = tr_base(lane) + warp * 32;
        const uint32_t dst = OFF_G + warp * 512 + (8 * (t >> 1) + g) * 32 + (t & 1) * 16;
        TS(23);
        bar_sync(5, 512);
        const uint4 m = lds128(MISC_LN1 + (t & 1) * 16), rh = lds128(MISC_LN1 + 32 + (t & 1) * 16), rl = lds128(MISC_LN1 + 64 + (t & 1) * 16);
        uint32_t x[3][4];
#pragma unroll
        for (int q = 0; q < 3; q++) ldsm4t(tr_addr + q * 512 - (q == 2 ? 256 : 0), x[q][0], x[q][1], x[q][2], x[q][3]);
#pragma unroll
        for (int q = 0; q < 3; q++) {
          if (q < 2 || wg == 2) {
            const uint32_t r0 = ln_apply(x[q][0], m.x, rh.x, rl.x), r1 = ln_apply(x[q][1], m.y, rh.y, rl.y), r2 = ln_apply(x[q][2], m.z, rh.z, rl.z), r3 = ln_apply(x[q][3], m.w, rh.w, rl.w);
            sts128(dst + q * 8192 - (q == 2 ? 4096 : 0), (pack_h(bf_lo(r0), bf_hi(r0)) & 0xFFFEFFFEu) | 1u, pack_h(bf_lo(r1), bf_hi(r1)), pack_h(bf_lo(r2), bf_hi(r2)), pack_h(bf_lo(r3), bf_hi(r3)));
          }
          if (q == 0) TS(30);
        }
        fence_async();
        bar_arrive(10, 576);
        TS(1);
        phase >>= 1;
        if (phase) { phase = 0; continue; }
      } else bar_sync(1 + wg, 128);
      float k2048;
      const int em = kgen_tables_m(wb, wt, ks, k2048);
      if (two && five) { mbar_wait(MB_KF); zero_pads(OFF_W + ALT, wt); }
      ep = lds32(MISC_EPOCH);
      fence_async();
      bar_sync(1 + wg, 128);
      TS(14);
      float acc[20];
      {
        const uint32_t alo = (wb >> 4) | (8u << 16);
        wg_fence();
        wgmma40_ss_init(acc, alo, alo + 1024, 2048 >> 4);
#pragma unroll
        for (int k = 1; k < 8; k++) wgmma40_ss(acc, alo + k * 16, alo + 1024 + k * 16, 2048 >> 4);
        wg_commit();
      }
      if (two && five) {
        asm volatile("cp.async.cg.shared.global [%0], [%1], 16;" :: "r"(OFF_K5 + wt * 16), "l"(kx) : "memory");
        asm volatile("cp.async.commit_group;" ::: "memory");
      }
      SPIN_WHILE(ep == 0, ep = lds32(MISC_EPOCH));
      if (wt == 0) str16(&p.s->SC[two && !five ? 512 + (c >> 1) : wg * 128 + c], ((uint32_t)(em + 9) << 7) | (ep & 127u));
      wg_wait<0>();
      const float un = 1.f / 8192.f;
      kw.x = pack_h((acc[0] - acc[3]) * un, (acc[4] - acc[7]) * un);
      kw.y = pack_h((acc[8] - acc[11]) * un, (acc[12] - acc[15]) * un);
      kw.z = pack_h((acc[16] - acc[19]) * un, k2048 * un);
      TS(24);
      if (five || !two) break;
      str128(kx, kw.x, kw.y, kw.z, ep);
      two = false;
    }
    uint32_t tb = wb;
#pragma unroll 1
    for (;;) {
      kgen_build(tb, wg, wt, kw.x, kw.y, kw.z);
      if (wt == 0 && tb == wb) mbar_arrive(MB_KF + wg * 8);
      TS(15);
      if (!two) break;
      two = false;
      asm volatile("cp.async.wait_group 0;" ::: "memory");
      kw = lds128(OFF_K5 + wt * 16);
      SPIN_WHILE(kw.w != ep, kw = ldr128(kx));
      tb = OFF_W + ALT;
    }
    fence_async();
    if (tb != wb) bar_arrive(7, 256);
    bar_sync(1 + wg, 128);
    TS(31);
  }
  uint32_t tpub;
#pragma unroll 1
  for (int item = 0;; item++) {
    mbar_wait(MB_UV + (item ? 32 : wg * 8));
    TS(2);
    conv_item(item ? OFF_W + ALT : wb, cv, p.zero, &tm.m[7], item ? 512 + (c >> 1) : wg * 128 + c, warp, lane);
    tpub = clock() - item * X_YD;
    if (wg || !five || item) break;
    TS(27);
    bar_sync(7, 256);
  }
  TS(4);

  const int tok = c * 16 + warp;
  const uint32_t row = OFF_YT + warp * YT_PITCH + (warp >> 3) * 64;
  const int fu = warp / 3, fk = warp - fu * 3;
  uint32_t wa[12][4];
  {
    uint32_t hw[9], wr[9];
    {
      const uint4 m = lds128(MISC_LN1 + (t & 1) * 16), rh = lds128(MISC_LN1 + 32 + (t & 1) * 16), rl = lds128(MISC_LN1 + 64 + (t & 1) * 16);
      mbar_wait(MB_SC);
#pragma unroll 1
      for (int tp = warp;; tp += 12) {
        const int ch = tp * 32 + 8 * (t >> 1) + g;
        const uint32_t tr_addr = tr_base(lane) + tp * 64;
        const uint4* ysrc = &p.s->X[c * DM * 2 + ch * 2 + (t & 1)];
        uint32_t x[2][4], ud[2][4], s[2];
#pragma unroll
        for (int q = 0; q < 2; q++) {
          asm volatile("ld.shared.u8 %0, [%1];" : "=r"(s[q]) : "r"(sc_addr(tp) + (ch & 31) + q * 16) : "memory");
          s[q] *= 0x800080u;
          const uint32_t dk = lds16(OFF_WR + 1152 + ch * 2 + q * 32) * 0x10001u;
          ldsm4t(tr_addr + q * 32, x[q][0], x[q][1], x[q][2], x[q][3]);
          ud[q][0] = bf_mul2(ln_apply(x[q][0], m.x, rh.x, rl.x), dk); ud[q][1] = bf_mul2(ln_apply(x[q][1], m.y, rh.y, rl.y), dk);
          ud[q][2] = bf_mul2(ln_apply(x[q][2], m.z, rh.z, rl.z), dk); ud[q][3] = bf_mul2(ln_apply(x[q][3], m.w, rh.w, rl.w), dk);
        }
        while ((int)(clock() - tpub) < X_YD) {}
        TS(5);
        uint4 v[2];
        v[0] = ldr128(ysrc); v[1] = ldr128(ysrc + 32);
        SPIN_WHILE((v[0].x | v[1].x) & 1u, if (v[0].x & 1u) v[0] = ldr128(ysrc); if (v[1].x & 1u) v[1] = ldr128(ysrc + 32));
#pragma unroll
        for (int q = 0; q < 2; q++) {
          const uint32_t s2 = s[q];
          stsm4t(tr_addr + q * 32, bf_add2(x[q][0], bf_fma2(h2bf(v[q].x), s2, ud[q][0])), bf_add2(x[q][1], bf_fma2(h2bf(v[q].y), s2, ud[q][1])),
                 bf_add2(x[q][2], bf_fma2(h2bf(v[q].z), s2, ud[q][2])), bf_add2(x[q][3], bf_fma2(h2bf(v[q].w), s2, ud[q][3])));
        }
        if ((tp & ~1) != 4) break;
      }
    }
#pragma unroll
    for (int i = 0; i < 9; i++) wr[i] = lds32(OFF_WR + lane * 4 + i * 128);
    const float sw = __uint_as_float(lds32(MISC_SW));
    asm volatile("cp.async.bulk.wait_group.read 0;" ::: "memory");
    TS(28);
    bar_sync(0, 512);
    TS(6);
    float d[4] = {0.f, 0.f, 0.f, 0.f}, e[4] = {0.f, 0.f, 0.f, 0.f}, rd;
#pragma unroll
    for (int i = 0; i < 9; i++) hw[i] = lds32(row + lane * 4 + i * 128);
#pragma unroll
    for (int i = 0; i < 8; i += 2) {
      mma_bf16(d, hw[i], wr[i], hw[i + 1], wr[i + 1], hw[i], hw[i + 1]);
      mma_bf16(e, ones, ones, ones, ones, hw[i], hw[i + 1]);
    }
    mma_bf16_k8(d, hw[8], wr[8], hw[8]);
    mma_bf16_k8(e, ones, ones, hw[8]);
    const float hwsum = diag_sum(d[2], d[3], t);
    LnC l2 = ln_consts(quad_sum(e[0] + e[1]), diag_sum(d[0], d[1], t), rd);
    const uint32_t b = pack_bf(fmaf(-bf_lo(l2.m2), sw, hwsum) * rd, 0.f);
    uint32_t key = max(min((b & 0x8000u) ? (~b & 0xFFFFu) : (b | 0x8000u), 0xFFFEu), 1u);
    if (lane == 0) sts16(MISC_RK + warp * 2, key);
    bar_sync(5, 512);
    if (tid >= 510) { const uint4 k = lds128(MISC_RK + (tid & 1) * 16); str128(&p.s->R[c * 2 + (tid & 1)], k.x, k.y, k.z, k.w); }
    asm volatile("" : "+r"(l2.m2) :: "memory");
    TS(7);
    key = (key << 16) | (2047 - tok);
    uint32_t loc = lane < 16 ? (lds16(MISC_RK + lane * 2) << 16) | (2047 - c * 16 - lane) : 0u;
    int rank = __popc(__ballot_sync(0xffffffffu, loc > key));
#pragma unroll
    for (int i = 0; i < 9; i++) {
      wr[i] = ln_apply(hw[i], l2.m2, l2.rh2, l2.rl2);
      sts32(row + lane * 4 + i * 128, bf_add2(hw[i], wr[i]));
    }
    const uint32_t wabase = ((lane & 8) ? OFF_W + (fk + 1) * W_BYTES : OFF_G + fk * 192 * pitch) + ((lane >> 4) * 8 + (lane & 7)) * pitch
                            + (five ? ((fu ^ (lane >> 1)) & 3) : min(fu, 4)) * 16;
    const bool early = uni(mbar_test(MB_GU));
    if (early) {
#pragma unroll
      for (int k = 0; k < 12; k++) ldsm4t(wabase + k * 16 * pitch, wa[k][0], wa[k][1], wa[k][2], wa[k][3]);
    }
    fence_async();
    uint2 rv = make_uint2(~0u, 0u);
#pragma unroll 1
    for (int base = 0; base < 8; base += 4) {
      uint32_t T[4];
#pragma unroll
      for (int j = 0; j < 4; j++) {
        const uint32_t mx = __reduce_max_sync(0xffffffffu, loc);
        if (loc == mx) loc = 0;
        T[j] = (tid >> 2) == c ? ~0u : (tid >> 2) < c ? (mx & 0xFFFF0000u) - 1u : mx | 0xFFFFu;
      }
      SPIN_WHILE(rv.x == ~0u, if (rv.x == ~0u) rv = ldr64((const uint2*)p.s->R + tid));
      TS(16);
      uint32_t cnt = 0;
#pragma unroll
      for (int j = 0; j < 4; j++) cnt += ((rv.x > T[j]) + ((rv.x << 16) > T[j]) + (rv.y > T[j]) + ((rv.y << 16) > T[j])) << (8 * j);
      cnt = __reduce_add_sync(0xffffffffu, cnt);
      if (lane == 0) sts32(MISC_CNT + base * 16 + warp * 4, cnt);
      bar_sync(0, 512);
      cnt = lds32(MISC_CNT + base * 16 + (lane & 15) * 4);
      cnt = __reduce_add_sync(0xffffffffu, lane < 16 ? (cnt >> (8 * (rank & 3))) & 255u : (cnt >> 24) << 16);
      if ((rank & ~3) == base && rank + (int)(cnt & 0xFFFFu) < 8) {
        rank += cnt & 0xFFFFu;
        uint32_t* hs = (uint32_t*)p.s->HS + rank * 288 + lane;
#pragma unroll
        for (int r = 0; r < 9; r++) str32(hs + 32 * r, wr[r]);
#pragma unroll
        for (int r = 0; r < 9; r++) str32(hs + 2304 + 32 * r, hw[r]);
        if (lane == 0) { str32(&p.s->HS[1152 + rank], key); sts16(MISC_RK + warp * 2, 0); }
        rank = 16;
      }
      if (cnt >= (4u << 16)) break;
    }
    TS(8);
    if (!early) {
      mbar_wait(MB_GU);
#pragma unroll
      for (int k = 0; k < 12; k++) ldsm4t(wabase + k * 16 * pitch, wa[k][0], wa[k][1], wa[k][2], wa[k][3]);
    }
  }
  uint32_t wd[10][4];
  if (warp >= 7) {
    const uint32_t db = down_box(warp - 7, five) + (lane & 7) * 128;
    mbar_wait(MB_D);
#pragma unroll
    for (int j = 0; j < 4; j++) {
      const uint32_t a = db + (lane >> 4) * 1024 + (((2 * j + ((lane >> 3) & 1)) ^ (lane & 7)) << 4);
      ldsm4t(a, wd[j][0], wd[j][1], wd[j][2], wd[j][3]);
      ldsm4t(a + 2048, wd[4 + j][0], wd[4 + j][1], wd[4 + j][2], wd[4 + j][3]);
    }
#pragma unroll
    for (int j = 0; j < 2; j++) ldsm4t(db + 4096 + (((4 * j + (lane >> 3)) ^ (lane & 7)) << 4), wd[8 + j][0], wd[8 + j][1], wd[8 + j][2], wd[8 + j][3]);
  } else if (warp < 6) {
    const uint4* src = &p.s->HS[tid];
    uint4 a[3];
    TS(19);
#pragma unroll 1
    for (int it = 0; it < SPIN_MAX; it++) {
      uint32_t m = 0;
#pragma unroll
      for (int q = 0; q < 3; q++) a[q] = ldr128(src + q * 192);
#pragma unroll
      for (int q = 0; q < 3; q++) m = max(max(m, max(a[q].x, a[q].y)), max(a[q].z, a[q].w));
      if (!__any_sync(0xffffffffu, m == ~0u)) break;
    }
#pragma unroll
    for (int q = 0; q < 3; q++) sts128(OFF_XS + (tid + q * 192 + (tid + q * 192) / 72) * 16, a[q].x, a[q].y, a[q].z, a[q].w);
  }
  bar_sync(0, 512);
  TS(9);

  {
    float d0[4] = {0.f, 0.f, 0.f, 0.f}, d1[4] = {0.f, 0.f, 0.f, 0.f};
    const uint32_t xb = OFF_XS + (lane & 7) * 1168 + (fk * 24 + (lane >> 3)) * 16;
#pragma unroll
    for (int k = 0; k < 12; k += 2) {
      uint32_t b0, b1, b2, b3;
      ldsm4(xb + k * 32, b0, b1, b2, b3);
      mma_bf16(d0, wa[k][0], wa[k][1], wa[k][2], wa[k][3], b0, b1);
      mma_bf16(d1, wa[k + 1][0], wa[k + 1][1], wa[k + 1][2], wa[k + 1][3], b2, b3);
    }
    sts128(OFF_RED + tid * 16, __float_as_uint(d0[0] + d1[0]), __float_as_uint(d0[1] + d1[1]), __float_as_uint(d0[2] + d1[2]), __float_as_uint(d0[3] + d1[3]));
  }
  TS(26);
  if (warp < 5) {
    bar_sync(9, 512);
    const uint32_t rb = OFF_RED + warp * 1536 + lane * 16;
    const uint4 pa = lds128(rb), pb = lds128(rb + 512), pc = lds128(rb + 1024);
    const float ga = bfr(__uint_as_float(pa.x) + __uint_as_float(pb.x) + __uint_as_float(pc.x));
    const float gb = bfr(__uint_as_float(pa.y) + __uint_as_float(pb.y) + __uint_as_float(pc.y));
    const uint32_t uu = pack_bf(__uint_as_float(pa.z) + __uint_as_float(pb.z) + __uint_as_float(pc.z), __uint_as_float(pa.w) + __uint_as_float(pb.w) + __uint_as_float(pc.w));
    float ra, rb2;
    asm("rcp.approx.ftz.f32 %0, %1;" : "=f"(ra) : "f"(1.f + ex2(ga * -1.4426950408889634f)));
    asm("rcp.approx.ftz.f32 %0, %1;" : "=f"(rb2) : "f"(1.f + ex2(gb * -1.4426950408889634f)));
    const uint32_t act = bf_mul2(pack_bf(ga * ra, gb * rb2), uu);
    sts32(OFF_ACT + tid * 4, act);
    bar_arrive(8, 14 * 32);
  } else {
    bar_arrive(9, 512);
    if (warp >= 7) {
      uint4* dst = &p.s->X[c * DM * 2 + (warp - 7) * 64 + t * 8 + g];
      bar_sync(8, 14 * 32);
      uint32_t b0, b1, b2, b3, b4;
      ldsm4t(OFF_ACT + lane * 16, b0, b1, b2, b3);
      asm volatile("ldmatrix.sync.aligned.m8n8.x1.trans.shared.b16 {%0}, [%1];" : "=r"(b4) : "r"(OFF_ACT + 512 + lane * 16) : "memory");
      float y[4][4];
#pragma unroll
      for (int j = 0; j < 4; j++) {
        y[j][0] = y[j][1] = y[j][2] = y[j][3] = 0.f;
        mma_bf16(y[j], wd[j][0], wd[j][1], wd[j][2], wd[j][3], b0, b1);
      }
#pragma unroll
      for (int j = 0; j < 4; j++) mma_bf16(y[j], wd[4 + j][0], wd[4 + j][1], wd[4 + j][2], wd[4 + j][3], b2, b3);
      if (!five) {
#pragma unroll
        for (int j = 0; j < 4; j++) mma_bf16_k8(y[j], wd[8 + (j >> 1)][2 * (j & 1)], wd[8 + (j >> 1)][2 * (j & 1) + 1], b4);
      }
      str128(dst, (pack_bf(y[0][0], y[0][1]) & ~1u) | 0x10000u, pack_bf(y[0][2], y[0][3]), pack_bf(y[1][0], y[1][1]), pack_bf(y[1][2], y[1][3]));
      str128(dst + 32, (pack_bf(y[2][0], y[2][1]) & ~1u) | 0x10000u, pack_bf(y[2][2], y[2][3]), pack_bf(y[3][0], y[3][1]), pack_bf(y[3][2], y[3][3]));
    } else if (lane < 8) {
      const int r = (warp - 5) * 8 + lane;
      if (lds16(MISC_RK + r * 2))
        asm volatile("cp.async.bulk.global.shared::cta.bulk_group [%0], [%1], 1152;" :: "l"(p.out + (c * 16 + r) * 288), "r"(OFF_YT + r * YT_PITCH + (r >> 3) * 64) : "memory");
      asm volatile("cp.async.bulk.commit_group;" ::: "memory");
    }
  }
  TS(10);

  if (c < 72) {
    const uint4* src = &p.s->X[(warp * 4 + t) * (DM * 2) + c * 8 + g];
    const int slot = (c & 3) * 2 + (lane >> 4), dw = (c >> 2) * 16 + (lane & 15);
    uint32_t hv = 0, kv = 0, res = 0;
    float rs = 0.f;
    if (warp == 0) {
      hv = ~0u;
      SPIN_WHILE(max(hv, kv) == ~0u, hv = ldr32((const uint32_t*)p.s->HS + 2304 + slot * 288 + dw); kv = ldr32(&p.s->HS[1152 + slot]));
      const uint32_t k16 = kv >> 16;
      const float r = bf_lo((k16 & 0x8000u) ? (k16 & 0x7FFFu) : (~k16 & 0xFFFFu));
      asm("rcp.approx.ftz.f32 %0, %1;" : "=f"(rs) : "f"(1.f + ex2(r * -1.4426950408889634f)));
      res = lds32(OFF_XS + slot * 1168 + dw * 4);
    }
    const uint32_t sel = (g & 1) ? 0x3F800000u : 0x00003F80u;
    const uint32_t q0 = keep((g >> 1) == 0 ? sel : 0u), q1 = keep((g >> 1) == 1 ? sel : 0u), q2 = keep((g >> 1) == 2 ? sel : 0u), q3 = keep((g >> 1) == 3 ? sel : 0u);
    uint4 a0 = make_uint4(0, 0, 0, 0), a1 = a0;
    SPIN_WHILE(!(a0.x & a1.x & 0x10000u), if (!(a0.x & 0x10000u)) a0 = ldr128(src); if (!(a1.x & 0x10000u)) a1 = ldr128(src + 64 * DM * 2));
    float d[4] = {0.f, 0.f, 0.f, 0.f}, e[4] = {0.f, 0.f, 0.f, 0.f};
    mma_bf16(d, q0, 0u, q1, 0u, a0.x, a0.y); mma_bf16(e, q2, 0u, q3, 0u, a0.z, a0.w);
    mma_bf16(d, q0, 0u, q1, 0u, a1.x, a1.y); mma_bf16(e, q2, 0u, q3, 0u, a1.z, a1.w);
    sts64(OFF_FIN + warp * 256 + (g & 1) * 128 + (g >> 1) * 32 + t * 8, __float_as_uint(d[0] + e[0]), __float_as_uint(d[1] + e[1]));
    TS(11);
    if (warp == 0) {
      bar_sync(0, 512);
      float2 s[16];
#pragma unroll
      for (int i = 0; i < 16; i++) { const uint2 q = lds64(OFF_FIN + i * 256 + lane * 8); s[i] = make_float2(__uint_as_float(q.x), __uint_as_float(q.y)); }
#pragma unroll
      for (int o = 1; o < 16; o *= 2)
#pragma unroll
        for (int i = 0; i < 16; i += 2 * o) { s[i].x += s[i + o].x; s[i].y += s[i + o].y; }
      const uint32_t upd = keep(bf_mul2(pack_bf(s[0].x, s[0].y), pack_bf(rs, rs)));
      p.out[(2047 - (int)(kv & 2047u)) * 288 + dw] = bf_add2(hv, bf_add2(res, upd));
    } else bar_arrive(0, 512);
  }
  asm volatile("cp.async.bulk.wait_group.read 0;" ::: "memory");
  TS(12);
  TS_DUMP();
}

typedef CUresult (*EncodeFn)(CUtensorMap*, CUtensorMapDataType, cuuint32_t, void*, const cuuint64_t*, const cuuint64_t*, const cuuint32_t*,
                             const cuuint32_t*, CUtensorMapInterleave, CUtensorMapSwizzle, CUtensorMapL2promotion, CUtensorMapFloatOOBfill);

}

extern "C" void kernel_launch(void* const* d_in, const int* in_sizes, int n_in, void* d_out, int out_size) {
  (void)in_sizes; (void)n_in; (void)out_size;
  static EncodeFn enc = nullptr;
  static Scratch* scratch = nullptr;
  if (!enc) {
    void* fn = nullptr;
    cudaDriverEntryPointQueryResult qr;
    cudaGetDriverEntryPoint("cuTensorMapEncodeTiled", &fn, cudaEnableDefault, &qr);
    enc = (EncodeFn)fn;
    cudaGetSymbolAddress((void**)&scratch, g_S);
    cudaFuncSetAttribute(fused_kernel<false>, cudaFuncAttributeMaxDynamicSharedMemorySize, SMEM_BYTES);
    cudaFuncSetAttribute(fused_kernel<true>, cudaFuncAttributeMaxDynamicSharedMemorySize, SMEM_BYTES);
  }
  TMaps tm;
  for (int i = 0; i < 6; i++) {
    const bool dn = i % 3 == 2;
    const cuuint32_t w = i < 3 ? 40 : 32;
    cuuint64_t gd[2] = {(cuuint64_t)(dn ? DM : FF), (cuuint64_t)(dn ? FF : DM)};
    cuuint64_t gs[1] = {(cuuint64_t)(dn ? DM * 2 : FF * 2)};
    cuuint32_t bx[2] = {dn ? 64 : w, dn ? w : 96};
    cuuint32_t es[2] = {1, 1};
    enc(&tm.m[i], CU_TENSOR_MAP_DATA_TYPE_BFLOAT16, 2, d_in[11 + i % 3], gd, gs, bx, es, CU_TENSOR_MAP_INTERLEAVE_NONE,
        dn ? CU_TENSOR_MAP_SWIZZLE_128B : i < 3 ? CU_TENSOR_MAP_SWIZZLE_NONE : CU_TENSOR_MAP_SWIZZLE_64B,
        CU_TENSOR_MAP_L2_PROMOTION_NONE, CU_TENSOR_MAP_FLOAT_OOB_FILL_NONE);
  }
  for (int i = 6; i < 8; i++) {
    cuuint64_t gd[2] = {DM * 16, NCTA};
    cuuint64_t gs[1] = {DM * 32};
    cuuint32_t bx[2] = {16, i == 6 ? 160u : 128u};
    cuuint32_t es[2] = {1, 1};
    enc(&tm.m[i], CU_TENSOR_MAP_DATA_TYPE_FLOAT16, 2, scratch->X, gd, gs, bx, es, CU_TENSOR_MAP_INTERLEAVE_NONE, CU_TENSOR_MAP_SWIZZLE_32B,
        CU_TENSOR_MAP_L2_PROMOTION_NONE, CU_TENSOR_MAP_FLOAT_OOB_FILL_NONE);
  }
  Params p;
  p.x = (const unsigned char*)d_in[0];
  bool far = false;
  for (int i = 0; i < 7; i++) {
    p.far[i] = (const unsigned char*)d_in[1 + i];
    const long long d = (long long)((intptr_t)d_in[1 + i] - (intptr_t)d_in[0]);
    p.off[i] = (int)(d / 16);
    if ((long long)p.off[i] * 16 != d) far = true;
  }
  p.dskip = (const uint32_t*)d_in[8];
  p.w_r = (const uint32_t*)d_in[10];
  p.w_gate = (const unsigned char*)d_in[11];
  p.w_up = (const unsigned char*)d_in[12];
  p.w_down = (const unsigned char*)d_in[13];
  p.out = (uint32_t*)d_out;
  p.zero = 0;
  p.ts = nullptr;
  p.s = scratch;
  if (far) { fused_kernel<true><<<NCTA, NT, SMEM_BYTES, cudaStreamPerThread>>>(p, tm); return; }
  fused_kernel<false><<<NCTA, NT, SMEM_BYTES, cudaStreamPerThread>>>(p, tm);
}
```

```cpp
#include <cuda_runtime.h>
#include <cuda.h>
#include <cuda_bf16.h>
#include <cuda_fp16.h>
#include <stdint.h>
#include <stddef.h>

namespace {

constexpr int NCTA = 128;
constexpr int NT = 640;
constexpr int DM = 576;
constexpr int FF = 4608;
constexpr int SPIN_MAX = 1 << 20;

struct Scratch {
  uint4 X[NCTA * DM * 2];
  uint4 KX[64 * 128];
  uint4 HS[1152 + 8];
  uint4 R[256];
  uint4 SC[256];
  uint32_t FLAG[NCTA * 8];
};
__device__ Scratch g_S;

#define TS(i)
#define TS_DUMP()

constexpr int SB = 1024;
constexpr int BOX = 15360;
constexpr int OFF_G = SB;
constexpr int OFF_W = OFF_G + 3 * BOX;
constexpr int W_UP = 26624;
constexpr int W_KT = W_UP + 5120;
constexpr int W_L3 = W_KT + 4416;
constexpr int W_CW = W_L3 + 4096;
constexpr int W_MISC = W_CW + 640;
constexpr int W_BYTES = 40960;
constexpr int ALT = -W_UP;
static_assert(W_MISC + 32 <= W_BYTES && OFF_W % 1024 == 0 && W_UP % 256 == 0 && W_BYTES + ALT + 3 * 4096 <= W_UP, "wg block");
constexpr int OFF_K5 = OFF_G + 40960;
constexpr int YT_PITCH = 1184;
constexpr int OFF_YT = OFF_W + 4 * W_BYTES;
constexpr int OFF_WR = OFF_YT + 16 * YT_PITCH + 64;
constexpr int OFF_MISC = OFF_WR + 2304;
constexpr int SMEM_BYTES = OFF_MISC + 1024 - SB;
static_assert(OFF_YT % 16 == 0 && OFF_MISC % 16 == 0, "align");
static_assert(SMEM_BYTES <= 232448, "smem");
constexpr int MB_GU = OFF_MISC;
constexpr int MB_D = OFF_MISC + 8;
constexpr int MB_KF = OFF_MISC + 16;
constexpr int MB_GF = OFF_MISC + 48;
constexpr int MB_SC = OFF_MISC + 56;
constexpr int MB_UL = OFF_MISC + 64;
constexpr int MB_UV = OFF_MISC + 104;
constexpr int MB_H = MB_KF + 128;
constexpr int MISC_EPOCH = OFF_MISC + 152;
constexpr int MISC_SW = OFF_MISC + 156;
constexpr int MISC_RK = OFF_MISC + 160;
constexpr int MISC_LN1 = OFF_MISC + 192;
constexpr int OFF_XS = OFF_W + W_BYTES + W_UP;
constexpr int OFF_RED = OFF_W + 2 * W_BYTES + W_UP;
constexpr int OFF_FIN = OFF_W + 3 * W_BYTES + W_UP;
constexpr int OFF_ACT = OFF_FIN + 4096;
constexpr int MISC_CNT = OFF_ACT + 1024;

__device__ __forceinline__ uint32_t smem_u32(const void* p) { return (uint32_t)__cvta_generic_to_shared(p); }
__device__ __forceinline__ uint32_t lds32(uint32_t a) { uint32_t v; asm volatile("ld.shared.b32 %0, [%1];" : "=r"(v) : "r"(a) : "memory"); return v; }
__device__ __forceinline__ uint32_t lds16(uint32_t a) { uint16_t v; asm volatile("ld.shared.u16 %0, [%1];" : "=h"(v) : "r"(a) : "memory"); return v; }
__device__ __forceinline__ uint2 lds64(uint32_t a) { uint2 v; asm volatile("ld.shared.v2.b32 {%0,%1}, [%2];" : "=r"(v.x), "=r"(v.y) : "r"(a) : "memory"); return v; }
__device__ __forceinline__ uint4 lds128(uint32_t a) { uint4 v; asm volatile("ld.shared.v4.b32 {%0,%1,%2,%3}, [%4];" : "=r"(v.x), "=r"(v.y), "=r"(v.z), "=r"(v.w) : "r"(a) : "memory"); return v; }
__device__ __forceinline__ void sts16(uint32_t a, uint32_t v) { asm volatile("st.shared.u16 [%0], %1;" :: "r"(a), "h"((uint16_t)v) : "memory"); }
__device__ __forceinline__ void sts32(uint32_t a, uint32_t v) { asm volatile("st.shared.b32 [%0], %1;" :: "r"(a), "r"(v) : "memory"); }
__device__ __forceinline__ void sts64(uint32_t a, uint32_t x, uint32_t y) { asm volatile("st.shared.v2.b32 [%0], {%1,%2};" :: "r"(a), "r"(x), "r"(y) : "memory"); }
__device__ __forceinline__ void sts128(uint32_t a, uint32_t x, uint32_t y, uint32_t z, uint32_t w) { asm volatile("st.shared.v4.b32 [%0], {%1,%2,%3,%4};" :: "r"(a), "r"(x), "r"(y), "r"(z), "r"(w) : "memory"); }
__device__ __forceinline__ void ldsm4(uint32_t a, uint32_t& r0, uint32_t& r1, uint32_t& r2, uint32_t& r3) {
  asm volatile("ldmatrix.sync.aligned.m8n8.x4.shared.b16 {%0,%1,%2,%3}, [%4];" : "=r"(r0), "=r"(r1), "=r"(r2), "=r"(r3) : "r"(a) : "memory");
}
__device__ __forceinline__ void ldsm2(uint32_t a, uint32_t& r0, uint32_t& r1) {
  asm volatile("ldmatrix.sync.aligned.m8n8.x2.shared.b16 {%0,%1}, [%2];" : "=r"(r0), "=r"(r1) : "r"(a) : "memory");
}
__device__ __forceinline__ void ldsm4t(uint32_t a, uint32_t& r0, uint32_t& r1, uint32_t& r2, uint32_t& r3) {
  asm volatile("ldmatrix.sync.aligned.m8n8.x4.trans.shared.b16 {%0,%1,%2,%3}, [%4];" : "=r"(r0), "=r"(r1), "=r"(r2), "=r"(r3) : "r"(a) : "memory");
}
__device__ __forceinline__ void stsm4t(uint32_t a, uint32_t r0, uint32_t r1, uint32_t r2, uint32_t r3) {
  asm volatile("stmatrix.sync.aligned.m8n8.x4.trans.shared.b16 [%0], {%1,%2,%3,%4};" :: "r"(a), "r"(r0), "r"(r1), "r"(r2), "r"(r3) : "memory");
}
__device__ __forceinline__ uint4 ldr128(const void* p) {
  unsigned long long lo, hi;
  asm volatile("{ .reg .b128 t; ld.relaxed.gpu.global.b128 t, [%2]; mov.b128 {%0, %1}, t; }" : "=l"(lo), "=l"(hi) : "l"(p) : "memory");
  return make_uint4((uint32_t)lo, (uint32_t)(lo >> 32), (uint32_t)hi, (uint32_t)(hi >> 32));
}
__device__ __forceinline__ void str128(void* p, uint32_t x, uint32_t y, uint32_t z, uint32_t w) {
  asm volatile("{ .reg .b128 t; .reg .b64 lo, hi; mov.b64 lo, {%1,%2}; mov.b64 hi, {%3,%4}; mov.b128 t, {lo, hi}; st.relaxed.gpu.global.b128 [%0], t; }"
               :: "l"(p), "r"(x), "r"(y), "r"(z), "r"(w) : "memory");
}
__device__ __forceinline__ void str64(void* p, uint32_t x, uint32_t y) {
  asm volatile("{ .reg .b64 t; mov.b64 t, {%1,%2}; st.relaxed.gpu.global.b64 [%0], t; }" :: "l"(p), "r"(x), "r"(y) : "memory");
}
__device__ __forceinline__ uint32_t ldr32(const void* p) { uint32_t v; asm volatile("ld.relaxed.gpu.global.b32 %0, [%1];" : "=r"(v) : "l"(p) : "memory"); return v; }
__device__ __forceinline__ void str32(void* p, uint32_t v) { asm volatile("st.relaxed.gpu.global.b32 [%0], %1;" :: "l"(p), "r"(v) : "memory"); }
__device__ __forceinline__ void str16(void* p, uint32_t v) { asm volatile("st.relaxed.gpu.global.u16 [%0], %1;" :: "l"(p), "h"((uint16_t)v) : "memory"); }
__device__ __forceinline__ void fence_gpu() { asm volatile("fence.acq_rel.gpu;" ::: "memory"); }
__device__ __forceinline__ void bar_sync(int id, int n) { asm volatile("bar.sync %0, %1;" :: "r"(id), "r"(n) : "memory"); }
__device__ __forceinline__ void bar_arrive(int id, int n) { asm volatile("bar.arrive %0, %1;" :: "r"(id), "r"(n) : "memory"); }

__device__ __forceinline__ float bf_lo(uint32_t w) { return __uint_as_float(w << 16); }
__device__ __forceinline__ float bf_hi(uint32_t w) { return __uint_as_float(w & 0xFFFF0000u); }
__device__ __forceinline__ uint32_t pack_bf(float lo, float hi) { uint32_t r; asm("cvt.rn.bf16x2.f32 %0, %1, %2;" : "=r"(r) : "f"(hi), "f"(lo)); return r; }
__device__ __forceinline__ uint32_t pack_h(float lo, float hi) { uint32_t r; asm("cvt.rn.f16x2.f32 %0, %1, %2;" : "=r"(r) : "f"(hi), "f"(lo)); return r; }
__device__ __forceinline__ uint32_t pack_hv(float lo, float hi) { uint32_t r; asm volatile("cvt.rn.f16x2.f32 %0, %1, %2;" : "=r"(r) : "f"(hi), "f"(lo) : "memory"); return r; }
__device__ __forceinline__ float bfr(float x) { return bf_lo(pack_bf(x, 0.f)); }
__device__ __forceinline__ uint32_t bf_sub2(uint32_t a, uint32_t b) { __nv_bfloat162 r = __hsub2(*(__nv_bfloat162*)&a, *(__nv_bfloat162*)&b); return *(uint32_t*)&r; }
__device__ __forceinline__ uint32_t bf_add2(uint32_t a, uint32_t b) { __nv_bfloat162 r = __hadd2(*(__nv_bfloat162*)&a, *(__nv_bfloat162*)&b); return *(uint32_t*)&r; }
__device__ __forceinline__ uint32_t bf_mul2(uint32_t a, uint32_t b) { __nv_bfloat162 r = __hmul2(*(__nv_bfloat162*)&a, *(__nv_bfloat162*)&b); return *(uint32_t*)&r; }
__device__ __forceinline__ float2 h2f(uint32_t w) { return __half22float2(*(__half2*)&w); }
__device__ __forceinline__ float ex2(float x) { float r; asm("ex2.approx.ftz.f32 %0, %1;" : "=f"(r) : "f"(x)); return r; }
__device__ __forceinline__ float warp_sum(float v) {
#pragma unroll
  for (int o = 16; o > 0; o >>= 1) v += __shfl_xor_sync(0xffffffffu, v, o);
  return v;
}
__device__ __forceinline__ void mma_f16_f32(float* d, uint32_t a0, uint32_t a1, uint32_t a2, uint32_t a3, uint32_t b0, uint32_t b1) {
  asm volatile("mma.sync.aligned.m16n8k16.row.col.f32.f16.f16.f32 {%0,%1,%2,%3}, {%4,%5,%6,%7}, {%8,%9}, {%0,%1,%2,%3};"
               : "+f"(d[0]), "+f"(d[1]), "+f"(d[2]), "+f"(d[3]) : "r"(a0), "r"(a1), "r"(a2), "r"(a3), "r"(b0), "r"(b1));
}
__device__ __forceinline__ void mma_f16_f16(uint32_t& d0, uint32_t& d1, uint32_t a0, uint32_t a1, uint32_t a2, uint32_t a3, uint32_t b0, uint32_t b1) {
  asm volatile("mma.sync.aligned.m16n8k16.row.col.f16.f16.f16.f16 {%0,%1}, {%2,%3,%4,%5}, {%6,%7}, {%0,%1};"
               : "+r"(d0), "+r"(d1) : "r"(a0), "r"(a1), "r"(a2), "r"(a3), "r"(b0), "r"(b1));
}
__device__ __forceinline__ void mma_bf16(float* d, uint32_t a0, uint32_t a1, uint32_t a2, uint32_t a3, uint32_t b0, uint32_t b1) {
  asm volatile("mma.sync.aligned.m16n8k16.row.col.f32.bf16.bf16.f32 {%0,%1,%2,%3}, {%4,%5,%6,%7}, {%8,%9}, {%0,%1,%2,%3};"
               : "+f"(d[0]), "+f"(d[1]), "+f"(d[2]), "+f"(d[3]) : "r"(a0), "r"(a1), "r"(a2), "r"(a3), "r"(b0), "r"(b1));
}
__device__ __forceinline__ void mma_bf16_k8(float* d, uint32_t a0, uint32_t a1, uint32_t b0) {
  asm volatile("mma.sync.aligned.m16n8k8.row.col.f32.bf16.bf16.f32 {%0,%1,%2,%3}, {%4,%5}, {%6}, {%0,%1,%2,%3};"
               : "+f"(d[0]), "+f"(d[1]), "+f"(d[2]), "+f"(d[3]) : "r"(a0), "r"(a1), "r"(b0));
}

__device__ __forceinline__ void wg_fence() { asm volatile("wgmma.fence.sync.aligned;" ::: "memory"); }
__device__ __forceinline__ void wg_commit() { asm volatile("wgmma.commit_group.sync.aligned;" ::: "memory"); }
template <int N> __device__ __forceinline__ void wg_wait() { asm volatile("wgmma.wait_group.sync.aligned %0;" :: "n"(N) : "memory"); }
template <int TB> __device__ __forceinline__ void wgmma32(float* d, const uint32_t* a, uint32_t dlo, uint32_t dhi) {
  asm volatile("{ .reg .b64 dd; mov.b64 dd, {%20, %21}; wgmma.mma_async.sync.aligned.m64n32k16.f32.f16.f16 "
               "{%0,%1,%2,%3,%4,%5,%6,%7,%8,%9,%10,%11,%12,%13,%14,%15}, {%16,%17,%18,%19}, dd, 1, 1, 1, %22; }"
               : "+f"(d[0]), "+f"(d[1]), "+f"(d[2]), "+f"(d[3]), "+f"(d[4]), "+f"(d[5]), "+f"(d[6]), "+f"(d[7]), "+f"(d[8]), "+f"(d[9]), "+f"(d[10]), "+f"(d[11]), "+f"(d[12]), "+f"(d[13]), "+f"(d[14]), "+f"(d[15])
               : "r"(a[0]), "r"(a[1]), "r"(a[2]), "r"(a[3]), "r"(dlo), "r"(dhi), "n"(TB));
}
template <int TB> __device__ __forceinline__ void wgmma96(float* d, const uint32_t* a, uint32_t dlo, uint32_t dhi) {
  asm volatile("{ .reg .b64 dd; mov.b64 dd, {%52, %53}; wgmma.mma_async.sync.aligned.m64n96k16.f32.f16.f16 "
               "{%0,%1,%2,%3,%4,%5,%6,%7,%8,%9,%10,%11,%12,%13,%14,%15,%16,%17,%18,%19,%20,%21,%22,%23,%24,%25,%26,%27,%28,%29,%30,%31,%32,%33,%34,%35,%36,%37,%38,%39,%40,%41,%42,%43,%44,%45,%46,%47}, {%48,%49,%50,%51}, dd, 1, 1, 1, %54; }"
               : "+f"(d[0]), "+f"(d[1]), "+f"(d[2]), "+f"(d[3]), "+f"(d[4]), "+f"(d[5]), "+f"(d[6]), "+f"(d[7]), "+f"(d[8]), "+f"(d[9]), "+f"(d[10]), "+f"(d[11]), "+f"(d[12]), "+f"(d[13]), "+f"(d[14]), "+f"(d[15]), "+f"(d[16]), "+f"(d[17]), "+f"(d[18]), "+f"(d[19]), "+f"(d[20]), "+f"(d[21]), "+f"(d[22]), "+f"(d[23]), "+f"(d[24]), "+f"(d[25]), "+f"(d[26]), "+f"(d[27]), "+f"(d[28]), "+f"(d[29]), "+f"(d[30]), "+f"(d[31]), "+f"(d[32]), "+f"(d[33]), "+f"(d[34]), "+f"(d[35]), "+f"(d[36]), "+f"(d[37]), "+f"(d[38]), "+f"(d[39]), "+f"(d[40]), "+f"(d[41]), "+f"(d[42]), "+f"(d[43]), "+f"(d[44]), "+f"(d[45]), "+f"(d[46]), "+f"(d[47])
               : "r"(a[0]), "r"(a[1]), "r"(a[2]), "r"(a[3]), "r"(dlo), "r"(dhi), "n"(TB));
}
template <int TB> __device__ __forceinline__ void wgmma96_init(float* d, const uint32_t* a, uint32_t dlo, uint32_t dhi) {
  asm volatile("{ .reg .b64 dd; mov.b64 dd, {%52, %53}; wgmma.mma_async.sync.aligned.m64n96k16.f32.f16.f16 "
               "{%0,%1,%2,%3,%4,%5,%6,%7,%8,%9,%10,%11,%12,%13,%14,%15,%16,%17,%18,%19,%20,%21,%22,%23,%24,%25,%26,%27,%28,%29,%30,%31,%32,%33,%34,%35,%36,%37,%38,%39,%40,%41,%42,%43,%44,%45,%46,%47}, {%48,%49,%50,%51}, dd, 0, 1, 1, %54; }"
               : "=f"(d[0]), "=f"(d[1]), "=f"(d[2]), "=f"(d[3]), "=f"(d[4]), "=f"(d[5]), "=f"(d[6]), "=f"(d[7]), "=f"(d[8]), "=f"(d[9]), "=f"(d[10]), "=f"(d[11]), "=f"(d[12]), "=f"(d[13]), "=f"(d[14]), "=f"(d[15]), "=f"(d[16]), "=f"(d[17]), "=f"(d[18]), "=f"(d[19]), "=f"(d[20]), "=f"(d[21]), "=f"(d[22]), "=f"(d[23]), "=f"(d[24]), "=f"(d[25]), "=f"(d[26]), "=f"(d[27]), "=f"(d[28]), "=f"(d[29]), "=f"(d[30]), "=f"(d[31]), "=f"(d[32]), "=f"(d[33]), "=f"(d[34]), "=f"(d[35]), "=f"(d[36]), "=f"(d[37]), "=f"(d[38]), "=f"(d[39]), "=f"(d[40]), "=f"(d[41]), "=f"(d[42]), "=f"(d[43]), "=f"(d[44]), "=f"(d[45]), "=f"(d[46]), "=f"(d[47])
               : "r"(a[0]), "r"(a[1]), "r"(a[2]), "r"(a[3]), "r"(dlo), "r"(dhi), "n"(TB));
}
template <int TB> __device__ __forceinline__ void wgmma32_init(float* d, const uint32_t* a, uint32_t dlo, uint32_t dhi) {
  asm volatile("{ .reg .b64 dd; mov.b64 dd, {%20, %21}; wgmma.mma_async.sync.aligned.m64n32k16.f32.f16.f16 "
               "{%0,%1,%2,%3,%4,%5,%6,%7,%8,%9,%10,%11,%12,%13,%14,%15}, {%16,%17,%18,%19}, dd, 0, 1, 1, %22; }"
               : "=f"(d[0]), "=f"(d[1]), "=f"(d[2]), "=f"(d[3]), "=f"(d[4]), "=f"(d[5]), "=f"(d[6]), "=f"(d[7]), "=f"(d[8]), "=f"(d[9]), "=f"(d[10]), "=f"(d[11]), "=f"(d[12]), "=f"(d[13]), "=f"(d[14]), "=f"(d[15])
               : "r"(a[0]), "r"(a[1]), "r"(a[2]), "r"(a[3]), "r"(dlo), "r"(dhi), "n"(TB));
}
__device__ __forceinline__ void wgmma64h(uint32_t* d, uint32_t a0, uint32_t a1, uint32_t a2, uint32_t a3, uint32_t dlo, uint32_t dhi) {
  asm volatile("{ .reg .b64 dd; mov.b64 dd, {%20, %21}; wgmma.mma_async.sync.aligned.m64n64k16.f16.f16.f16 "
               "{%0,%1,%2,%3,%4,%5,%6,%7,%8,%9,%10,%11,%12,%13,%14,%15}, {%16,%17,%18,%19}, dd, 1, 1, 1, 0; }"
               : "+r"(d[0]), "+r"(d[1]), "+r"(d[2]), "+r"(d[3]), "+r"(d[4]), "+r"(d[5]), "+r"(d[6]), "+r"(d[7]), "+r"(d[8]), "+r"(d[9]), "+r"(d[10]), "+r"(d[11]), "+r"(d[12]), "+r"(d[13]), "+r"(d[14]), "+r"(d[15])
               : "r"(a0), "r"(a1), "r"(a2), "r"(a3), "r"(dlo), "r"(dhi));
}
__device__ __forceinline__ void wgmma64h_init(uint32_t* d, uint32_t a0, uint32_t a1, uint32_t a2, uint32_t a3, uint32_t dlo, uint32_t dhi) {
  asm volatile("{ .reg .b64 dd; mov.b64 dd, {%20, %21}; wgmma.mma_async.sync.aligned.m64n64k16.f16.f16.f16 "
               "{%0,%1,%2,%3,%4,%5,%6,%7,%8,%9,%10,%11,%12,%13,%14,%15}, {%16,%17,%18,%19}, dd, 0, 1, 1, 0; }"
               : "=r"(d[0]), "=r"(d[1]), "=r"(d[2]), "=r"(d[3]), "=r"(d[4]), "=r"(d[5]), "=r"(d[6]), "=r"(d[7]), "=r"(d[8]), "=r"(d[9]), "=r"(d[10]), "=r"(d[11]), "=r"(d[12]), "=r"(d[13]), "=r"(d[14]), "=r"(d[15])
               : "r"(a0), "r"(a1), "r"(a2), "r"(a3), "r"(dlo), "r"(dhi));
}
__device__ __forceinline__ void wgmma40_ss(float* d, uint32_t alo, uint32_t blo, uint32_t hi) {
  asm volatile("{ .reg .b64 da, db; mov.b64 da, {%20, %22}; mov.b64 db, {%21, %22}; "
               "wgmma.mma_async.sync.aligned.m64n40k16.f32.f16.f16 {%0,%1,%2,%3,%4,%5,%6,%7,%8,%9,%10,%11,%12,%13,%14,%15,%16,%17,%18,%19}, da, db, 1, 1, 1, 1, 1; }"
               : "+f"(d[0]), "+f"(d[1]), "+f"(d[2]), "+f"(d[3]), "+f"(d[4]), "+f"(d[5]), "+f"(d[6]), "+f"(d[7]), "+f"(d[8]), "+f"(d[9]), "+f"(d[10]), "+f"(d[11]), "+f"(d[12]), "+f"(d[13]), "+f"(d[14]), "+f"(d[15]), "+f"(d[16]), "+f"(d[17]), "+f"(d[18]), "+f"(d[19])
               : "r"(alo), "r"(blo), "r"(hi));
}
__device__ __forceinline__ void wgmma40_ss_init(float* d, uint32_t alo, uint32_t blo, uint32_t hi) {
  asm volatile("{ .reg .b64 da, db; mov.b64 da, {%20, %22}; mov.b64 db, {%21, %22}; "
               "wgmma.mma_async.sync.aligned.m64n40k16.f32.f16.f16 {%0,%1,%2,%3,%4,%5,%6,%7,%8,%9,%10,%11,%12,%13,%14,%15,%16,%17,%18,%19}, da, db, 0, 1, 1, 1, 1; }"
               : "=f"(d[0]), "=f"(d[1]), "=f"(d[2]), "=f"(d[3]), "=f"(d[4]), "=f"(d[5]), "=f"(d[6]), "=f"(d[7]), "=f"(d[8]), "=f"(d[9]), "=f"(d[10]), "=f"(d[11]), "=f"(d[12]), "=f"(d[13]), "=f"(d[14]), "=f"(d[15]), "=f"(d[16]), "=f"(d[17]), "=f"(d[18]), "=f"(d[19])
               : "r"(alo), "r"(blo), "r"(hi));
}
__device__ __forceinline__ float vzero() { float v; asm volatile("mov.b32 %0, 0;" : "=f"(v)); return v; }
__device__ __forceinline__ void tma_box(uint32_t dst, const CUtensorMap* tm, uint32_t mb, int x, int y) {
  asm volatile("cp.async.bulk.tensor.2d.shared::cluster.global.mbarrier::complete_tx::bytes [%0], [%1, {%3, %4}], [%2];"
               :: "r"(dst), "l"(tm), "r"(mb), "r"(x), "r"(y) : "memory");
}
__device__ __forceinline__ void l2_prefetch(const void* src, uint32_t bytes) {
  asm volatile("cp.async.bulk.prefetch.L2.global [%0], %1;" :: "l"(src), "r"(bytes) : "memory");
}
__device__ __forceinline__ uint32_t uni(uint32_t v) {
  uint32_t r; asm volatile("shfl.sync.idx.b32 %0, %1, 0, 0x1f, 0xffffffff;" : "=r"(r) : "r"(v)); return r;
}
__device__ __forceinline__ int fresh_tid() { int v; asm volatile("mov.u32 %0, %tid.x;" : "=r"(v)); return v; }

struct Params {
  const unsigned char* x;
  Scratch* s;
  int off[7];
  uint32_t zero;
  uint32_t* out;
  const uint32_t* dskip;
  const uint32_t* w_r;
  const unsigned char* w_gate;
  const unsigned char* w_up;
  long long* ts;
  const unsigned char* far[7];
  uint32_t sched[2][17];
};
__device__ __forceinline__ uint32_t ldnc32(const void* p) { uint32_t v; asm volatile("ld.global.nc.b32 %0, [%1];" : "=r"(v) : "l"(p)); return v; }
__device__ __forceinline__ uint32_t ldnc16(const void* p) { uint16_t v; asm volatile("ld.global.nc.u16 %0, [%1];" : "=h"(v) : "l"(p)); return v; }
__device__ __forceinline__ uint4 ldnc128(const void* p) { uint4 v; asm volatile("ld.global.nc.v4.b32 {%0,%1,%2,%3}, [%4];" : "=r"(v.x), "=r"(v.y), "=r"(v.z), "=r"(v.w) : "l"(p)); return v; }
__device__ __forceinline__ void mbar_wait(uint32_t mb, uint32_t ph = 0) {
#pragma unroll 1
  for (int it = 0; it < SPIN_MAX; it++) {
    uint32_t ok;
    asm volatile("{ .reg .pred q; mbarrier.try_wait.parity.shared::cta.b64 q, [%1], %2; selp.u32 %0, 1, 0, q; }" : "=r"(ok) : "r"(mb), "r"(ph) : "memory");
    if (ok) break;
  }
}
__device__ __forceinline__ uint32_t mbar_test(uint32_t mb) {
  uint32_t ok;
  asm volatile("{ .reg .pred q; mbarrier.test_wait.parity.shared::cta.b64 q, [%1], 0; selp.u32 %0, 1, 0, q; }" : "=r"(ok) : "r"(mb) : "memory");
  return ok;
}
__device__ __forceinline__ void mbar_arrive(uint32_t mb) { asm volatile("mbarrier.arrive.shared::cta.b64 _, [%0];" :: "r"(mb) : "memory"); }
__device__ __forceinline__ uint32_t ldg16(const void* p) { uint16_t v; asm volatile("ld.global.u16 %0, [%1];" : "=h"(v) : "l"(p) : "memory"); return v; }
__device__ __forceinline__ uint32_t ldr16(const void* p) { uint16_t v; asm volatile("ld.relaxed.gpu.global.u16 %0, [%1];" : "=h"(v) : "l"(p) : "memory"); return v; }
__device__ __forceinline__ void fence_async() { asm volatile("fence.proxy.async.shared::cta;" ::: "memory"); }
#define SPIN_WHILE(cond, body) _Pragma("unroll 1") for (int _it = 0; _it < SPIN_MAX && __any_sync(0xffffffffu, (cond)); _it++) { body; }

struct LnC { uint32_t m2, rh2, rl2; };
__device__ __forceinline__ float diag_sum(float d0, float d1, int t) {
  float q = __shfl_sync(0xffffffffu, d0, 9 * t) + __shfl_sync(0xffffffffu, d1, 9 * t + 4);
  q += __shfl_xor_sync(0xffffffffu, q, 1);
  return q + __shfl_xor_sync(0xffffffffu, q, 2);
}
__device__ __forceinline__ LnC ln_consts(float s, float q, float& r) {
  const float mean = s * (1.f / DM);
  const float var = fmaxf(fmaf(-mean, mean, q * (1.f / DM)), 0.f);
  float sd;
  asm("sqrt.approx.ftz.f32 %0, %1;" : "=f"(sd) : "f"(bfr(bfr(var) + 1e-5f)));
  asm("rcp.approx.ftz.f32 %0, %1;" : "=f"(r) : "f"(bfr(sd)));
  LnC c;
  c.m2 = pack_bf(mean, mean);
  c.rh2 = pack_bf(r, r);
  const float rl = r - bf_lo(c.rh2);
  c.rl2 = pack_bf(rl, rl);
  return c;
}
__device__ __forceinline__ float quad_sum(float s) { s += __shfl_xor_sync(0xffffffffu, s, 1); return s + __shfl_xor_sync(0xffffffffu, s, 2); }
__device__ __forceinline__ uint32_t bf_fma2(uint32_t a, uint32_t b, uint32_t c) {
  __nv_bfloat162 r = __hfma2(*(const __nv_bfloat162*)&a, *(const __nv_bfloat162*)&b, *(const __nv_bfloat162*)&c);
  return *(uint32_t*)&r;
}
__device__ __forceinline__ uint32_t ln_apply(uint32_t w, uint32_t m2, uint32_t rh2, uint32_t rl2) {
  const uint32_t d = bf_sub2(w, m2);
  return bf_fma2(d, rh2, bf_mul2(d, rl2));
}

__device__ __forceinline__ float2 cis(float mag_log2, float rev) {
  const float m = ex2(mag_log2), ang = rev * 6.283185307179586f;
  return make_float2(m * __cosf(ang), m * __sinf(ang));
}
__device__ __forceinline__ float2 csq(float2 a) { return make_float2(fmaf(a.x, a.x, -a.y * a.y), (a.x + a.x) * a.y); }
__device__ __forceinline__ float2 cmul(float2 a, float2 b) { return make_float2(fmaf(a.x, b.x, -a.y * b.y), fmaf(a.x, b.y, a.y * b.x)); }
__device__ __forceinline__ void pmul(uint32_t xr, uint32_t xi, uint32_t w, uint32_t& yr, uint32_t& yi) {
  const __half2 XR = *(__half2*)&xr, XI = *(__half2*)&xi, W = *(__half2*)&w;
  const __half2 a = __hfma2(__hneg2(XI), __high2half2(W), __hmul2(XR, __low2half2(W)));
  const __half2 b = __hfma2(XI, __low2half2(W), __hmul2(XR, __high2half2(W)));
  yr = *(const uint32_t*)&a; yi = *(const uint32_t*)&b;
}
__device__ __forceinline__ uint32_t pk(float2 a) { return pack_h(a.x, a.y); }

struct KgState { float2 c0, z8; uint32_t w64, w128, w192; };
__device__ __forceinline__ void kgen_tables_n(const uint32_t (&raw)[7], uint32_t scr, int wt, KgState& k) {
  const uint32_t dst = scr + 16384 + wt * 16;
  const float dt = bfr(ex2(bf_lo(raw[6]) * 1.4426950408889634f));
  const float th = dt * bf_lo(raw[1]);
  const float br = dt * bf_lo(raw[2]), bi = dt * bf_lo(raw[3]);
  const float Cr = bf_lo(raw[4]), Ci = bf_lo(raw[5]);
  k.c0 = make_float2(fmaf(Cr, br, -Ci * bi), fmaf(Cr, bi, Ci * br));
  const uint32_t mx = __reduce_max_sync(0xffffffffu, __float_as_uint(fmaxf(fabsf(k.c0.x), fabsf(k.c0.y))));
  const float a2 = dt * bf_lo(raw[0]) * 1.4426950408889634f;
  const float rh = th * 0.15915494309189535f;
  const float rl = fmaf(th, (float)(0.15915494309189535 - (double)0.15915494309189535f), fmaf(th, 0.15915494309189535f, -rh));
  const float rf = rh - rintf(rh);
  const float2 z1 = cis(a2, rf + rl);
  const float p64 = rf * 64.f;
  const float2 z64 = cis(a2 * 64.f, fmaf(64.f, rl, p64 - rintf(p64)));
  const float2 z2 = csq(z1), z128 = csq(z64), z3 = cmul(z2, z1), z4 = csq(z2), z256 = csq(z128), z6 = csq(z3), z512 = csq(z256);
  k.z8 = csq(z4);
  k.w64 = pk(z64); k.w128 = pk(z128); k.w192 = pk(cmul(z128, z64));
  sts128(dst, 0x00003C00u, pk(z2), pk(z4), pk(z6));
  const float2 z1024 = csq(z512), z768 = cmul(z512, z256);
  sts128(dst + 2048, pk(z1), pk(z3), pk(cmul(z4, z1)), pk(cmul(z4, z3)));
  const float2 z2048 = csq(z1024);
  const float k2048 = warp_sum(fmaf(k.c0.x, z2048.x, -k.c0.y * z2048.y));
  sts128(dst + 4096, pk(z256), pk(cmul(z256, z2)), pk(cmul(z256, z4)), pk(cmul(z256, z6)));
  sts128(dst + 6144, pk(z512), pk(cmul(z512, z4)), pk(z768), pk(cmul(z768, z4)));
  sts128(dst + 8192, pk(z1024), pk(cmul(z1024, z256)), pk(cmul(z1024, z512)), pk(cmul(z1024, z768)));
  if ((wt & 31) == 0) { sts32(scr + W_MISC + (wt >> 5) * 4, mx); sts32(scr + W_MISC + 16 + (wt >> 5) * 4, __float_as_uint(k2048)); }
}
__device__ __forceinline__ int kgen_tables_m(uint32_t scr, int wt, const KgState& k, float& k2048) {
  const uint32_t dst = scr + wt * 16;
  const uint4 e4 = lds128(scr + W_MISC), k4 = lds128(scr + W_MISC + 16);
  const float2 z16 = csq(k.z8), z32 = csq(z16);
  const int em = max(min((int)(max(max(e4.x, e4.y), max(e4.z, e4.w)) >> 23), 238), 16);
  const float sc = __uint_as_float((uint32_t)(127 + 4 + 127 - em) << 23);
  k2048 = ((__uint_as_float(k4.x) + __uint_as_float(k4.y)) + (__uint_as_float(k4.z) + __uint_as_float(k4.w))) * sc;
  const float2 c0 = make_float2(k.c0.x * sc, k.c0.y * sc);
  const float2 c1 = cmul(c0, k.z8), c2 = cmul(c0, z16), c4 = cmul(c0, z32), c3 = cmul(c1, z16), c5 = cmul(c1, z32), c6 = cmul(c2, z32), c7 = cmul(c3, z32);
  uint32_t pr[4], pi[4], yr[4], yi[4];
  pr[0] = pack_h(c0.x, c1.x); pi[0] = pack_h(c0.y, c1.y);
  pr[1] = pack_h(c2.x, c3.x); pi[1] = pack_h(c2.y, c3.y);
  pr[2] = pack_h(c4.x, c5.x); pi[2] = pack_h(c4.y, c5.y);
  pr[3] = pack_h(c6.x, c7.x); pi[3] = pack_h(c6.y, c7.y);
  sts128(dst, pr[0], pr[1], pr[2], pr[3]); sts128(dst + 2048, pi[0], pi[1], pi[2], pi[3]);
#pragma unroll
  for (int q = 1; q < 4; q++) {
    const uint32_t w = q == 1 ? k.w64 : q == 2 ? k.w128 : k.w192;
#pragma unroll
    for (int i = 0; i < 4; i++) pmul(pr[i], pi[i], w, yr[i], yi[i]);
    sts128(dst + q * 4096, yr[0], yr[1], yr[2], yr[3]); sts128(dst + q * 4096 + 2048, yi[0], yi[1], yi[2], yi[3]);
  }
  return em;
}
__device__ __forceinline__ void kgen_build(uint32_t wb, int wg, int wt, uint32_t k0, uint32_t k1, uint32_t k2) {
  const uint32_t kt = wb + W_KT;
  const bool ev = !(wt & 1), mid = ev && wt;
  const uint32_t a0 = kt + 64 + wt * 8;
  const uint32_t a2 = kt + 64 + 2048 + (wt >> 2) * 32 + (wt & 1) * 16 + (wt & 2) * 512;
  const int ix = ((wt >> 2) + (wt & 3) * 32 - 1) & 127;
  const uint32_t a3 = wb + W_CW + 32 + ((ix & 1) ? 0 : 320) + (ix >> 1) * 4;
  const uint32_t v3 = wt ? k2 : k2 >> 16;
  sts16(a3, v3); sts16(a3 + 6, v3);
  if ((unsigned)(wt - 32) < 18u) sts128(kt + (wt < 36 ? -512 : 64 + 4128 - 576) + wt * 16, 0, 0, 0, 0);
  const uint32_t sw = __byte_perm(k0, 0, 0x1032), d2 = __byte_perm(k1, 0, 0x1010), d3 = __byte_perm(k1, 0, 0x3232);
  sts16(a0, k0); sts32(a0 + 4, sw); sts16(a0 + 10, sw);
  sts16(a0 + 1024 - (mid ? 4 : 0), d2); sts16(a0 + 1024 + (ev ? 10 : 6), d2);
  sts16(a2 - (mid ? 8 : 4), d3); sts64(a2, d3, d3); sts16(a2 + (ev ? 14 : 10), d3);
  if (mid) { sts64(a0 + 1024, d2, d2); sts32(a2 - 4, d3); }
  if (ev) sts32(a2 + 8, d3);
  if (wt == 0) {
    const uint32_t d = __byte_perm(k2, 0, 0x1010);
    sts16(kt + 66, 0); sts32(kt + 64 + 1028, d2);
    sts16(kt + 64 + 4088, d); sts32(kt + 64 + 4092, d); sts128(kt + 64 + 4096, d, d, d, d); sts128(kt + 64 + 4112, d, d << 16, 0, 0);
  }
  bar_sync(1 + wg, 128);
  const uint32_t cw = wb + W_CW + 32 + (wt >> 6) * 64 + wt * 4;
  sts128(wb + W_L3 + 1024 + (wt >> 6) * 1024 + wt * 16, lds32(cw), lds32(cw - 8), lds32(cw - 16), lds32(cw - 24));
}

__device__ __forceinline__ void load_a(uint32_t (&a)[4], uint32_t kp, int j) {
  a[0] = lds32(kp + 64 * j); a[1] = lds32(kp + 64 * j + 512); a[2] = lds32(kp + 64 * j - 32); a[3] = lds32(kp + 64 * j + 480);
}
__device__ __forceinline__ uint32_t band(int d, int lo, int hi) {
  return ((unsigned)(d - lo) <= (unsigned)(hi - lo) ? 1u : 0u) | ((unsigned)(d - 1 - lo) <= (unsigned)(hi - lo) ? 0x10000u : 0u);
}
__device__ __forceinline__ uint32_t hadd2u(uint32_t a, uint32_t b) { __half2 r = __hadd2(*(__half2*)&a, *(__half2*)&b); return *(uint32_t*)&r; }

__device__ __forceinline__ void zero_pads(uint32_t tb, int wt) {
  sts128(tb + W_L3 + (wt >> 6) * 1024 + wt * 16, 0, 0, 0, 0);
  if ((wt & 63) < 3) sts128(tb + W_CW + (wt >> 6) * 320 + (wt & 63) * 16, 0, 0, 0, 0);
}
__device__ __forceinline__ uint32_t tr_base(int lane) {
  return OFF_YT + (2 * (lane >> 3) + (lane & 1)) * YT_PITCH + ((lane >> 1) & 1) * (8 * YT_PITCH + 64) + ((lane >> 2) & 1) * 16;
}

__device__ __forceinline__ uint32_t sc_addr(int tp) { return OFF_YT + (tp < 16 ? tp * YT_PITCH + (tp >> 3) * 64 + 1152 : 8 * YT_PITCH - 512 + tp * 32); }
#define X_NE 3
#define X_NS 1
#define X_SCT 10500
#define X_DELTA 1300
#define X_DSTEP 200
#define X_PF0 2800
#define X_PFD 560
#define X_TD 700
#define X_ORD 1
#define X_WS 6
#define X_OR 8
#define X_LAG 1600
#define X_YD 600
struct TMaps { CUtensorMap m[8]; };
__device__ __forceinline__ uint32_t h2bf(uint32_t w) { const float2 f = h2f(w); return pack_bf(f.x, f.y); }
__device__ __forceinline__ uint32_t keep(uint32_t v) { asm volatile("" : "+r"(v)); return v; }
__device__ __forceinline__ uint2 ldr64(const void* p) { uint2 v; asm volatile("{ .reg .b64 t; ld.relaxed.gpu.global.b64 t, [%2]; mov.b64 {%0, %1}, t; }" : "=r"(v.x), "=r"(v.y) : "l"(p) : "memory"); return v; }
__host__ __device__ __forceinline__ uint32_t down_box(int s, bool five) {
  return five ? OFF_W + W_BYTES + 12288 + (s / 3) * (W_BYTES - 12288) + s * 4096 : s < 6 ? OFF_W + W_BYTES + BOX + (s >> 1) * (W_BYTES - 10240) + s * 5120 : OFF_W + (s - 6) * 5120;
}
__device__ __forceinline__ void load_tile(const CUtensorMap* tmx, int i, int c) {
  asm volatile("mbarrier.arrive.expect_tx.shared::cta.b64 _, [%0], 5120;" :: "r"(MB_UL + i * 8) : "memory");
  tma_box(OFF_W + (i < 4 ? i * W_BYTES : ALT) + W_UP, tmx, MB_UL + i * 8, (i < 4 ? i * 128 + c : 512 + (c >> 1)) * 16, -32);
}
template <bool FAR> __device__ __forceinline__ void load_params(const Params& p, uint32_t ch, int wt, uint32_t dst) {
  if (wt < 97) {
    const unsigned char* b = FAR ? p.far[wt >> 4] : p.x + (long long)p.off[wt >> 4] * 16;
    asm volatile("cp.async.cg.shared.global [%0], [%1], 16;" :: "r"(dst + wt * 16), "l"(b + (wt < 96 ? ch * 256 + (wt & 15) * 16 : (ch >> 3) * 16)) : "memory");
  }
  asm volatile("cp.async.commit_group;" ::: "memory");
}

struct ConvC { uint32_t ca, cb, bands; };
__device__ __forceinline__ ConvC conv_consts(int w, int lane) {
  const int h = w & 1, P = w >> 1, d0 = 8 * h + (lane >> 2) - 2 * (lane & 3);
  ConvC k;
  k.ca = keep((W_KT + (16 + 256 * P + d0) * 4) | ((W_UP + (32 + 64 * P + lane) * 32 + ((h ^ (lane >> 2)) & 1) * 16) << 16));
  k.cb = keep(lane < 8 ? 0xFFFEFFFEu : ~0u);
  k.bands = keep(band(d0, 12, 20) + 2 * band(d0 + 8, 12, 20) + 4 * band(d0 + 16, 12, 20) + 8 * band(d0 + 24, 12, 20)
                 + 16 * band(d0 - 8, 5, 11) + 32 * band(d0, 5, 11) + 64 * band(d0 + 8, 5, 11) + 128 * band(d0 + 16, 5, 11));
  return k;
}
__device__ __forceinline__ void conv_item(uint32_t tb, const ConvC& cv, uint32_t zero, const CUtensorMap* tmx, int ch, int warp, int lane) {
  const uint32_t kp = tb + (cv.ca & 0xFFFFu);
  const uint32_t dlo = ((tb + W_UP) >> 4) + 64 + (1u << 16), dhi = 16u | (3u << 30);
  const bool P = warp & 2;
  float a32[16], a96[48];
  uint32_t A[40][4];
#define STEP(J) { wgmma96<0>(a96, A[J], dlo + 64 - 2 * (J), dhi); if ((J) == 0) wgmma32_init<0>(a32, A[J], dlo, dhi); else if ((J) < 8) wgmma32<0>(a32, A[J], (dlo ^ zero) - 2 * (J), dhi); }
#define LD(J) load_a(A[J], kp, J);
#define FIRST(J) wg_fence(); STEP(J) wg_commit(); wg_wait<1>(); wg_fence();
  {
    uint32_t win[16], x9[4], x7[4], e[4], f[4];
    const uint32_t bz = keep(cv.bands);
#define BAND(i) keep((bz & (0x10001u << (i))) * (0x3C00u >> (i)))
    e[0] = lds32(kp + (P ? 3232 : 4096)); e[2] = lds32(kp + (P ? 3200 : 4064)); e[1] = keep(bz & 0x100u); e[3] = keep(bz & 0x200u);
    f[3] = lds32(kp + (P ? 3200 : 4128)); f[0] = keep(bz & 0x4000u); f[1] = keep(bz & 0x8000u); f[2] = keep(bz & 0x300u);
    const uint32_t q[12] = {BAND(0), BAND(5), keep(bz & 0x400u), BAND(4), BAND(2), BAND(7), BAND(1), BAND(6), keep(bz & 0x800u), keep(bz & 0x1000u), BAND(3), keep(bz & 0x2000u)};
#undef BAND
    TS(3);
    wg_fence();
    wgmma64h_init(win, q[0], q[1], q[2], q[3], dlo, dhi);
    wgmma64h(win, q[4], q[5], q[6], q[7], dlo - 2, dhi);
    wgmma64h(win, q[8], q[9], q[10], q[11], dlo - 4, dhi);
    wg_commit();
    wgmma96_init<0>(a96, e, dlo - 64, dhi);
    wgmma96<0>(a96, f, dlo - 50, dhi);
    wg_commit();
    wg_wait<1>();
#pragma unroll
    for (int i = 0; i < 4; i++) {
      const int tl = 2 * ((i & 1) + ((i & 2) ? 0 : 4));
      x9[i] = P ? win[tl + 4] : win[tl]; x7[i] = P ? win[tl + 5] : win[tl + 1];
    }
    const uint32_t l3lo = ((tb + W_L3) >> 4) + (32u << 16);
    wg_fence();
    wgmma96<0>(a96, x9, l3lo, 8);
    wgmma96<0>(a96, x7, l3lo + 128, 8);
    wg_commit();
  }
  LD(32) LD(33) LD(34) LD(35)
  FIRST(32) STEP(33) STEP(34) STEP(35) wg_commit();
  LD(36) LD(37) LD(38)
  FIRST(36) STEP(37) STEP(38) wg_commit();
  LD(39) LD(0)
  TS(17);
  FIRST(39) STEP(0) wg_commit();
  LD(1) LD(2) LD(3)
  FIRST(1) STEP(2) STEP(3) wg_commit();
  LD(4) LD(5)
  FIRST(4) STEP(5) wg_commit();
  LD(6) LD(7)
  wg_fence(); STEP(6) STEP(7) wg_commit();
#undef STEP
#undef LD
#undef FIRST
  TS(18);
  const uint32_t xc = tb + W_KT + (warp & 3) * 1024 + lane * 16;
  wg_wait<0>();
  uint32_t E[16], o[8];
#define ACC(i) ((i) < 16 ? a32[i] : a96[(i) - 16])
  E[0] = pack_h(a32[0], a32[1]);
#pragma unroll
  for (int i = 1; i < 16; i++) E[i] = pack_h(ACC(4 * i) + ACC(4 * i - 2), ACC(4 * i + 1) + ACC(4 * i - 1));
#undef ACC
#pragma unroll
  for (int j = 0; j < 8; j++) o[j] = P ? (j < 2 ? 0u : E[j - 2]) : E[8 + j];
  sts128(xc, o[0], o[1], o[2], o[3]); sts128(xc + 512, o[4], o[5], o[6], o[7]);
#pragma unroll
  for (int j = 0; j < 8; j++) o[j] = P ? E[6 + j] : E[j];
  TS(25);
  bar_sync(1 + (warp >> 2), 128);
#pragma unroll
  for (int q = 0; q < 2; q++) {
    const uint4 v = lds128(xc + (P ? -2048 : 2048) + q * 512);
    stsm4t(tb + (cv.ca >> 16) + q * 1024, hadd2u(o[4 * q], v.x) & cv.cb, hadd2u(o[4 * q + 1], v.y) & cv.cb, hadd2u(o[4 * q + 2], v.z) & cv.cb, hadd2u(o[4 * q + 3], v.w) & cv.cb);
  }
  fence_async();
  bar_sync(1 + (warp >> 2), 128);
  if ((warp & 3) == 3 && lane == 0) {
    asm volatile("cp.async.bulk.tensor.2d.global.shared::cta.bulk_group [%0, {%2, %3}], [%1];" :: "l"(tmx), "r"(tb + W_UP + 1024), "r"(ch * 16), "r"(0) : "memory");
    asm volatile("cp.async.bulk.commit_group;" ::: "memory");
  }
}

template <bool FAR> __global__ void __launch_bounds__(NT, 1)
fused_kernel(const __grid_constant__ Params p, const __grid_constant__ TMaps tm) {
  extern __shared__ __align__(1024) unsigned char smem[];
  const int c = blockIdx.x;
  const bool five = (c & 1) == 0;
  const uint32_t pitch = five ? 64 : 80;
  const uint32_t ones = 0x3F803F80u;
  const int tid = threadIdx.x, lane = tid & 31;
  const int warp = (int)uni(tid >> 5), wg = warp >> 2;
  TS(0);
  if (__builtin_expect(wg == 4, 0)) {
    asm volatile("setmaxnreg.dec.sync.aligned.u32 32;");
    const int role = warp;
    const int u0 = (c >> 1) * 9 + (five ? ((c & 2) ? 5 : 0) : ((c & 2) ? 0 : 4));
    const uint32_t t0 = clock() + c * 4;
    if (role < 18) {
      const bool pf = role == 17;
      if (!pf) {
        if (lane < 19) asm volatile("mbarrier.init.shared::cta.b64 [%0], %1;" :: "r"(OFF_MISC + lane * 8), "r"(1) : "memory");
        if (lane < 2) asm volatile("mbarrier.arrive.expect_tx.shared::cta.b64 _, [%0], %1;" :: "r"(OFF_MISC + lane * 8), "r"(lane ? (five ? 36864 : 51200) : pitch * 1152) : "memory");
        fence_async();
        bar_arrive(0, 576);
      } else if (smem_u32(smem) != SB) __trap();
      const CUtensorMap* tmb = &tm.m[five ? 3 : 0];
#pragma unroll 1
      for (int u = pf ? X_NE : 0; u < 17; u++) {
        const uint32_t e = p.sched[five][u], kind = e & 3, s = (e >> 2) & 15, dst = e >> 14;
        if (kind == 3) continue;
        while ((int)(clock() - t0) < X_PF0 + (pf || u < X_NE ? u * X_PFD : X_LAG + u * X_TD)) __nanosleep(20);
        if (!pf && (e & 0x3FC0)) mbar_wait(OFF_MISC + ((e >> 6) & 255));
        if (lane == 0) {
          if (pf) {
            if (kind == 2) asm volatile("cp.async.bulk.prefetch.tensor.3d.L2.global [%0, {%1, %2, %3}];" :: "l"(tmb + 2), "r"(0), "r"(u0 * 8), "r"(s) : "memory");
            else l2_prefetch((kind ? p.w_up : p.w_gate) + (uint32_t)(s * 884736 + c * 6912), 6912);
          } else if (kind == 2) asm volatile("cp.async.bulk.tensor.3d.shared::cluster.global.mbarrier::complete_tx::bytes [%0], [%1, {%3, %4, %5}], [%2];"
                                             :: "r"(dst), "l"(tmb + 2), "r"(MB_D), "r"(0), "r"(u0 * 8), "r"(s) : "memory");
          else tma_box(dst, tmb + kind, MB_GU, u0 * 8, s * 96);
        }
        if (u == 5) TS(2);
        if (u == 10) TS(3);
      }
      TS(4);
      TS_DUMP();
    } else if (role == 18) {
      sts32(MISC_EPOCH, 0);
      bar_arrive(0, 576);
      uint4* q = lane < 4 ? &p.s->R[c * 2 + (lane & 1) + (lane >> 1) * 256] : lane < 13 ? &p.s->HS[c * 9 + lane - 4] : lane == 13 ? &p.s->HS[1152 + (c & 7)] : (uint4*)&p.s->FLAG[c * 8];
      if (lane < (c < 8 ? 14 : 13)) str128(q, ~0u, ~0u, ~0u, ~0u);
      const uint32_t ep = __shfl_sync(0xffffffffu, ldr32(q), 31) + 1u;
      if (lane == 31) { sts32(MISC_EPOCH, ep | 0x80000000u); str32(q, ep); }
      bar_sync(10, 576);
      if (lane == 0) {
        asm volatile("cp.async.bulk.global.shared::cta.bulk_group [%0], [%1], %2;" :: "l"(&p.s->X[c * DM * 2]), "r"(OFF_G), "n"(DM * 32) : "memory");
        asm volatile("cp.async.bulk.commit_group;" ::: "memory");
        const uint32_t tp = clock();
        asm volatile("cp.async.bulk.wait_group 0;" ::: "memory");
#pragma unroll 1
        for (int i = 0; i < 4 + five; i++) {
          while ((int)(clock() - tp) < X_DELTA + i * X_DSTEP) {}
          if (i == 4) mbar_wait(MB_KF);
          load_tile(&tm.m[6], i, c);
          if (i == X_NS) mbar_arrive(MB_GF);
        }
      }
      __syncwarp();
      while ((int)(clock() - t0) < X_SCT) __nanosleep(100);
      {
        uint2 v[4];
#pragma unroll 1
        for (int it = 0; it < SPIN_MAX; it++) {
          uint32_t bad = 0;
#pragma unroll
          for (int q = 0; q < 4; q++) v[q] = ldr64(&p.s->SC[lane * 2 + q * 64]);
#pragma unroll
          for (int q = 0; q < 4; q++) bad |= __vcmpeq4(v[q].x, ~0u) | ((lane & 1) && v[q].y == ~0u);
          if (!__any_sync(0xffffffffu, bad)) break;
        }
#pragma unroll
        for (int q = 0; q < 4; q++) {
#pragma unroll
          for (int k = 0; k < 4; k++) asm volatile("st.shared.u8 [%0], %1;" :: "r"(sc_addr(4 * k + q) + lane), "r"(v[q].x >> (8 * k)) : "memory");
          if (lane & 1) asm volatile("st.shared.u8 [%0], %1;" :: "r"(sc_addr(16) + q * 16 + (lane >> 1)), "r"(v[q].y) : "memory");
        }
      }
      bar_sync(11, 64);
      if (lane == 0) mbar_arrive(MB_SC);
    } else {
      uint32_t w[9], d[9];
      float s = 0.f;
#pragma unroll
      for (int i = 0; i < 9; i++) { w[i] = ldnc32(p.w_r + lane + 32 * i); d[i] = ldnc32(p.dskip + lane + 32 * i); }
#pragma unroll
      for (int i = 0; i < 9; i++) { sts32(OFF_WR + lane * 4 + i * 128, w[i]); sts32(OFF_WR + 1152 + lane * 4 + i * 128, d[i]); s += bf_lo(w[i]) + bf_hi(w[i]); }
      sts32(MISC_SW, __float_as_uint(warp_sum(s)));
      bar_arrive(11, 64);
      bar_sync(10, 576);
#pragma unroll 1
      for (int i = 0; i < 4 + five; i++) {
        const uint32_t ta = OFF_W + (i < 4 ? i * W_BYTES : ALT) + W_UP + 1024 + lane * 32 + (lane & 4) * 4;
#pragma unroll 1
        for (int it = 0; it < SPIN_MAX; it++) {
          mbar_wait(MB_UL + i * 8, it & 1);
          uint32_t m = 1;
#pragma unroll
          for (int q = 0; q < 4; q++) { uint32_t r0, r1, r2, r3; ldsm4(ta + q * 1024, r0, r1, r2, r3); m &= r0 & r1 & r2 & r3; }
          if (__all_sync(0xffffffffu, m || (lane & 3))) break;
          if (lane == 0) load_tile(&tm.m[6], i, c);
        }
        if (lane == 0) mbar_arrive(MB_UV + i * 8);
      }
    }
    return;
  }
  const int wt = tid & 127, g = lane >> 2, t = lane & 3;
  const uint32_t wb = OFF_W + wg * W_BYTES;
  {
    const int lw = warp - (five ? 8 : 4);
    if ((unsigned)lw < 8u) {
      const unsigned char* xp = p.x + (uint32_t)((c * 8 + lw) * 2304 + lane * 16);
      const uint32_t row = OFF_YT + lw * (2 * YT_PITCH) + (lw >> 2) * 64 + lane * 16;
#pragma unroll
      for (int k = 0; k < 5; k++)
        if (k < 4 || lane < 16)
          asm volatile("cp.async.cg.shared.global [%0], [%1], 16;" :: "r"(row + k * 512 + ((k > 2 || (k == 2 && lane >= 8)) ? 32 : 0)), "l"(xp + k * 512) : "memory");
      asm volatile("cp.async.commit_group;" ::: "memory");
    } else load_params<FAR>(p, wg == 3 ? 512 + (c >> 1) : wg * 128 + c, wt, wb + W_KT + (wg == 3) * 2048);
  }
  TS(29);
  const ConvC cv = conv_consts(warp & 3, lane);
  zero_pads(wb, wt);
  if (wg > (five ? 1 : 0)) load_params<FAR>(p, wg * 128 + c, wt, wb + W_KT);
  asm volatile("setmaxnreg.inc.sync.aligned.u32 112;");
  bar_sync(0, 576);
  TS(13);
  {
    uint4 kw;
    uint4* kx = &p.s->KX[(c >> 1) * 128 + wt];
    const int lw = warp - (five ? 8 : 4);
    bool two = wg == 3;
    uint32_t ep;
    int phase = (unsigned)lw < 8u ? 2 : 1;
#pragma unroll 1
    for (;;) {
      KgState ks;
      const bool first = two && !five;
      if (first || phase == 2) asm volatile("cp.async.wait_group 1;" ::: "memory"); else asm volatile("cp.async.wait_group 0;" ::: "memory");
      if (phase == 2) {
        __syncwarp();
        TS(21);
        float d[4][4];
#pragma unroll
        for (int r = 0; r < 2; r++) {
          const uint32_t row = OFF_YT + (2 * lw + r) * YT_PITCH + (lw >> 2) * 64;
          const uint4 a = lds128(row + lane * 16), b = lds128(row + 512 + lane * 16);
          const uint32_t e = lds32(row + 1024 + lane * 4);
#pragma unroll
          for (int i = 0; i < 4; i++) d[r][i] = d[r + 2][i] = 0.f;
          mma_bf16(d[r], a.x, ones, a.y, ones, a.x, a.y); mma_bf16(d[r + 2], a.z, ones, a.w, ones, a.z, a.w);
          mma_bf16(d[r], b.x, ones, b.y, ones, b.x, b.y); mma_bf16(d[r + 2], b.z, ones, b.w, ones, b.z, b.w);
          mma_bf16_k8(d[r], e, ones, e);
#pragma unroll
          for (int i = 0; i < 4; i++) d[r][i] += d[r + 2][i];
        }
        const float q0 = __shfl_sync(0xffffffffu, d[0][0], 9 * t) + __shfl_sync(0xffffffffu, d[0][1], 9 * t + 4);
        const float q1 = __shfl_sync(0xffffffffu, d[1][0], 9 * t) + __shfl_sync(0xffffffffu, d[1][1], 9 * t + 4);
        float r;
        const LnC lc = ln_consts(quad_sum(lane & 16 ? d[1][2] + d[1][3] : d[0][2] + d[0][3]), quad_sum(lane & 16 ? q1 : q0), r);
        if ((lane & 15) < 3) sts16(MISC_LN1 + (lane & 15) * 32 + lw * 4 + (lane >> 4) * 2, t == 0 ? lc.m2 : t == 1 ? lc.rh2 : lc.rl2);
        ks.c0 = ks.z8 = make_float2(0.f, 0.f); ks.w64 = ks.w128 = ks.w192 = 0;
      } else {
        uint32_t raw[7];
        bar_sync(1 + wg, 128);
        TS(22);
#pragma unroll
        for (int i = 0; i < 7; i++) raw[i] = lds16(wb + W_KT + first * 2048 + i * 256 + (i < 6 ? wt : (c >> first) & 7) * 2);
        kgen_tables_n(raw, wb, wt, ks);
        TS(20);
      }
      if (phase) {
        const uint32_t tr_addr = tr_base(lane) + warp * 32;
        const uint32_t dst = OFF_G + warp * 512 + (8 * (t >> 1) + g) * 32 + (t & 1) * 16;
        TS(23);
        bar_sync(5, 512);
        const uint4 m = lds128(MISC_LN1 + (t & 1) * 16), rh = lds128(MISC_LN1 + 32 + (t & 1) * 16), rl = lds128(MISC_LN1 + 64 + (t & 1) * 16);
        uint32_t x[3][4];
#pragma unroll
        for (int q = 0; q < 3; q++) ldsm4t(tr_addr + q * 512 - (q == 2 ? 256 : 0), x[q][0], x[q][1], x[q][2], x[q][3]);
#pragma unroll
        for (int q = 0; q < 3; q++) {
          if (q < 2 || wg == 2) {
            const uint32_t r0 = ln_apply(x[q][0], m.x, rh.x, rl.x), r1 = ln_apply(x[q][1], m.y, rh.y, rl.y), r2 = ln_apply(x[q][2], m.z, rh.z, rl.z), r3 = ln_apply(x[q][3], m.w, rh.w, rl.w);
            sts128(dst + q * 8192 - (q == 2 ? 4096 : 0), (pack_h(bf_lo(r0), bf_hi(r0)) & 0xFFFEFFFEu) | 1u, pack_h(bf_lo(r1), bf_hi(r1)), pack_h(bf_lo(r2), bf_hi(r2)), pack_h(bf_lo(r3), bf_hi(r3)));
          }
          if (q == 0) TS(30);
        }
        fence_async();
        bar_arrive(10, 576);
        TS(1);
        phase >>= 1;
        if (phase) { phase = 0; continue; }
      } else bar_sync(1 + wg, 128);
      float k2048;
      const int em = kgen_tables_m(wb, wt, ks, k2048);
      if (two && five) { mbar_wait(MB_KF); zero_pads(OFF_W + ALT, wt); }
      ep = lds32(MISC_EPOCH);
      fence_async();
      bar_sync(1 + wg, 128);
      TS(14);
      float acc[20];
      {
        const uint32_t alo = (wb >> 4) | (8u << 16);
        wg_fence();
        wgmma40_ss_init(acc, alo, alo + 1024, 2048 >> 4);
#pragma unroll
        for (int k = 1; k < 8; k++) wgmma40_ss(acc, alo + k * 16, alo + 1024 + k * 16, 2048 >> 4);
        wg_commit();
      }
      if (two && five) {
        asm volatile("cp.async.cg.shared.global [%0], [%1], 16;" :: "r"(OFF_K5 + wt * 16), "l"(kx) : "memory");
        asm volatile("cp.async.commit_group;" ::: "memory");
      }
      SPIN_WHILE(ep == 0, ep = lds32(MISC_EPOCH));
      if (wt == 0) asm volatile("st.relaxed.gpu.global.u8 [%0], %1;" :: "l"((unsigned char*)&p.s->SC[c * 2] + wg + first), "r"(em + 9) : "memory");
      wg_wait<0>();
      const float un = 1.f / 8192.f;
      kw.x = pack_h((acc[0] - acc[3]) * un, (acc[4] - acc[7]) * un);
      kw.y = pack_h((acc[8] - acc[11]) * un, (acc[12] - acc[15]) * un);
      kw.z = pack_h((acc[16] - acc[19]) * un, k2048 * un);
      TS(24);
      if (five || !two) break;
      str128(kx, kw.x, kw.y, kw.z, ep);
      two = false;
    }
    uint32_t tb = wb;
#pragma unroll 1
    for (;;) {
      kgen_build(tb, wg, wt, kw.x, kw.y, kw.z);
      if (wt == 0 && tb == wb) mbar_arrive(MB_KF + wg * 8);
      TS(15);
      if (!two) break;
      two = false;
      asm volatile("cp.async.wait_group 0;" ::: "memory");
      kw = lds128(OFF_K5 + wt * 16);
      SPIN_WHILE(kw.w != ep, kw = ldr128(kx));
      tb = OFF_W + ALT;
    }
    fence_async();
    if (tb != wb) bar_arrive(7, 256);
    bar_sync(1 + wg, 128);
    TS(31);
  }
  uint32_t tpub;
#pragma unroll 1
  for (int item = 0;; item++) {
    mbar_wait(MB_UV + (item ? 32 : wg * 8));
    TS(2);
    conv_item(item ? OFF_W + ALT : wb, cv, p.zero, &tm.m[7], item ? 512 + (c >> 1) : wg * 128 + c, warp, lane);
    tpub = clock() - item * X_YD;
    if (wg || !five || item) break;
    TS(27);
    bar_sync(7, 256);
  }
  TS(4);

  const int tok = c * 16 + warp;
  const uint32_t row = OFF_YT + warp * YT_PITCH + (warp >> 3) * 64;
  const int fu = warp / 3, fk = warp - fu * 3;
  uint32_t wa[12][4];
  {
    uint32_t hw[9], wr[9];
    {
      const uint4 m = lds128(MISC_LN1 + (t & 1) * 16), rh = lds128(MISC_LN1 + 32 + (t & 1) * 16), rl = lds128(MISC_LN1 + 64 + (t & 1) * 16);
      mbar_wait(MB_SC);
#pragma unroll 1
      for (int tp = warp;; tp += 12) {
        const int ch = tp * 32 + 8 * (t >> 1) + g;
        const uint32_t tr_addr = tr_base(lane) + tp * 64;
        const uint4* ysrc = &p.s->X[c * DM * 2 + ch * 2 + (t & 1)];
        uint32_t x[2][4], ud[2][4], s[2];
#pragma unroll
        for (int q = 0; q < 2; q++) {
          asm volatile("ld.shared.u8 %0, [%1];" : "=r"(s[q]) : "r"(sc_addr(tp) + (ch & 31) + q * 16) : "memory");
          s[q] *= 0x800080u;
          const uint32_t dk = lds16(OFF_WR + 1152 + ch * 2 + q * 32) * 0x10001u;
          ldsm4t(tr_addr + q * 32, x[q][0], x[q][1], x[q][2], x[q][3]);
          ud[q][0] = bf_mul2(ln_apply(x[q][0], m.x, rh.x, rl.x), dk); ud[q][1] = bf_mul2(ln_apply(x[q][1], m.y, rh.y, rl.y), dk);
          ud[q][2] = bf_mul2(ln_apply(x[q][2], m.z, rh.z, rl.z), dk); ud[q][3] = bf_mul2(ln_apply(x[q][3], m.w, rh.w, rl.w), dk);
        }
        while ((int)(clock() - tpub) < X_YD) {}
        TS(5);
        uint4 v[2];
        v[0] = ldr128(ysrc); v[1] = ldr128(ysrc + 32);
        SPIN_WHILE((v[0].x | v[1].x) & 1u, if (v[0].x & 1u) v[0] = ldr128(ysrc); if (v[1].x & 1u) v[1] = ldr128(ysrc + 32));
#pragma unroll
        for (int q = 0; q < 2; q++) {
          const uint32_t s2 = s[q];
          stsm4t(tr_addr + q * 32, bf_add2(x[q][0], bf_fma2(h2bf(v[q].x), s2, ud[q][0])), bf_add2(x[q][1], bf_fma2(h2bf(v[q].y), s2, ud[q][1])),
                 bf_add2(x[q][2], bf_fma2(h2bf(v[q].z), s2, ud[q][2])), bf_add2(x[q][3], bf_fma2(h2bf(v[q].w), s2, ud[q][3])));
        }
        if ((tp & ~1) != 4) break;
      }
    }
#pragma unroll
    for (int i = 0; i < 9; i++) wr[i] = lds32(OFF_WR + lane * 4 + i * 128);
    const float sw = __uint_as_float(lds32(MISC_SW));
    asm volatile("cp.async.bulk.wait_group.read 0;" ::: "memory");
    TS(28);
    bar_sync(0, 512);
    if (tid == 0) mbar_arrive(MB_H);
    TS(6);
    float d[4] = {0.f, 0.f, 0.f, 0.f}, e[4] = {0.f, 0.f, 0.f, 0.f}, rd;
#pragma unroll
    for (int i = 0; i < 9; i++) hw[i] = lds32(row + lane * 4 + i * 128);
#pragma unroll
    for (int i = 0; i < 8; i += 2) {
      mma_bf16(d, hw[i], wr[i], hw[i + 1], wr[i + 1], hw[i], hw[i + 1]);
      mma_bf16(e, ones, ones, ones, ones, hw[i], hw[i + 1]);
    }
    mma_bf16_k8(d, hw[8], wr[8], hw[8]);
    mma_bf16_k8(e, ones, ones, hw[8]);
    const float hwsum = diag_sum(d[2], d[3], t);
    LnC l2 = ln_consts(quad_sum(e[0] + e[1]), diag_sum(d[0], d[1], t), rd);
    const uint32_t b = pack_bf(fmaf(-bf_lo(l2.m2), sw, hwsum) * rd, 0.f);
    uint32_t key = max(min((b & 0x8000u) ? (~b & 0xFFFFu) : (b | 0x8000u), 0xFFFEu), 1u);
    if (lane == 0) sts16(MISC_RK + warp * 2, key);
    bar_sync(5, 512);
    if (tid >= 510) { const uint4 k = lds128(MISC_RK + (tid & 1) * 16); str128(&p.s->R[c * 2 + (tid & 1)], k.x, k.y, k.z, k.w); }
    asm volatile("" : "+r"(l2.m2) :: "memory");
    TS(7);
    key = (key << 16) | (2047 - tok);
    uint32_t loc = lane < 16 ? (lds16(MISC_RK + lane * 2) << 16) | (2047 - c * 16 - lane) : 0u;
    int rank = __popc(__ballot_sync(0xffffffffu, loc > key));
    const uint32_t wabase = ((lane & 8) ? OFF_W + (fk + 1) * W_BYTES : OFF_G + fk * 192 * pitch) + ((lane >> 4) * 8 + (lane & 7)) * pitch
                            + (five ? ((fu ^ (lane >> 1)) & 3) : min(fu, 4)) * 16;
    mbar_wait(MB_GU);
    if (warp < (five ? 12 : 15)) {
#pragma unroll
      for (int k = 0; k < X_WS; k++) ldsm4t(wabase + k * 16 * pitch, wa[k][0], wa[k][1], wa[k][2], wa[k][3]);
    }
#pragma unroll
    for (int i = 0; i < 9; i++) {
      wr[i] = keep(ln_apply(hw[i], l2.m2, l2.rh2, l2.rl2));
    }
#define OUT_ROW { _Pragma("unroll") for (int i = 0; i < 9; i++) sts32(row + lane * 4 + i * 128, bf_add2(hw[i], wr[i])); fence_async(); __syncwarp(); if (lane == 0) { \
      asm volatile("cp.async.bulk.global.shared::cta.bulk_group [%0], [%1], 1152;" :: "l"(p.out + tok * 288), "r"(row) : "memory"); \
      asm volatile("cp.async.bulk.commit_group;" ::: "memory"); } }
#undef OUT_ROW
#define OUT_ROW { _Pragma("unroll") for (int i = 0; i < 9; i++) p.out[tok * 288 + lane + 32 * i] = bf_add2(hw[i], wr[i]); }
    if (rank >= X_OR) OUT_ROW
    uint2 rv = make_uint2(~0u, 0u);
#pragma unroll 1
    for (int base = 0; base < 8; base += 4) {
      uint32_t T[4];
#pragma unroll
      for (int j = 0; j < 4; j++) {
        const uint32_t mx = __reduce_max_sync(0xffffffffu, loc);
        if (loc == mx) loc = 0;
        T[j] = (tid >> 2) == c ? ~0u : (tid >> 2) < c ? (mx & 0xFFFF0000u) - 1u : mx | 0xFFFFu;
      }
      SPIN_WHILE(rv.x == ~0u, if (rv.x == ~0u) rv = ldr64((const uint2*)p.s->R + tid));
      TS(16);
      uint32_t cnt = 0;
#pragma unroll
      for (int j = 0; j < 4; j++) cnt += ((rv.x > T[j]) + ((rv.x << 16) > T[j]) + (rv.y > T[j]) + ((rv.y << 16) > T[j])) << (8 * j);
      cnt = __reduce_add_sync(0xffffffffu, cnt);
      if (lane == 0) sts32(MISC_CNT + base * 16 + warp * 4, cnt);
      bar_sync(0, 512);
      cnt = lds32(MISC_CNT + base * 16 + (lane & 15) * 4);
      cnt = __reduce_add_sync(0xffffffffu, lane < 16 ? (cnt >> (8 * (rank & 3))) & 255u : (cnt >> 24) << 16);
      if ((rank & ~3) == base && rank + (int)(cnt & 0xFFFFu) < 8) {
        rank += cnt & 0xFFFFu;
        uint32_t* hs = (uint32_t*)p.s->HS + rank * 288 + lane;
#pragma unroll
        for (int r = 0; r < 9; r++) str32(hs + 32 * r, wr[r]);
#pragma unroll
        for (int r = 0; r < 9; r++) str32(hs + 2304 + 32 * r, hw[r]);
        if (lane == 0) str32(&p.s->HS[1152 + rank], key);
        rank = 16;
      }
      if (cnt >= (4u << 16)) break;
    }
    TS(8);
    if (rank < X_OR) OUT_ROW
    if (warp < (five ? 12 : 15)) {
#pragma unroll
      for (int k = X_WS; k < 12; k++) ldsm4t(wabase + k * 16 * pitch, wa[k][0], wa[k][1], wa[k][2], wa[k][3]);
    }
  }
  uint32_t wd[10][4];
  if (warp >= 7) {
    const uint32_t db = down_box(warp - 7, five) + (lane & 7) * 128;
    mbar_wait(MB_D);
#pragma unroll
    for (int j = 0; j < 4; j++) {
      const uint32_t a = db + (lane >> 4) * 1024 + (((2 * j + ((lane >> 3) & 1)) ^ (lane & 7)) << 4);
      ldsm4t(a, wd[j][0], wd[j][1], wd[j][2], wd[j][3]);
      ldsm4t(a + 2048, wd[4 + j][0], wd[4 + j][1], wd[4 + j][2], wd[4 + j][3]);
    }
#pragma unroll
    for (int j = 0; j < 2; j++) ldsm4t(db + 4096 + (((4 * j + (lane >> 3)) ^ (lane & 7)) << 4), wd[8 + j][0], wd[8 + j][1], wd[8 + j][2], wd[8 + j][3]);
  } else if (warp < 6) {
    const uint4* src = &p.s->HS[tid];
    uint4 a[3];
    TS(19);
#pragma unroll 1
    for (int it = 0; it < SPIN_MAX; it++) {
      uint32_t m = 0;
#pragma unroll
      for (int q = 0; q < 3; q++) a[q] = ldr128(src + q * 192);
#pragma unroll
      for (int q = 0; q < 3; q++) m = max(max(m, max(a[q].x, a[q].y)), max(a[q].z, a[q].w));
      if (!__any_sync(0xffffffffu, m == ~0u)) break;
    }
#pragma unroll
    for (int q = 0; q < 3; q++) sts128(OFF_XS + (tid + q * 192 + (tid + q * 192) / 72) * 16, a[q].x, a[q].y, a[q].z, a[q].w);
  }
  bar_sync(0, 512);
  TS(9);

  if (warp < (five ? 12 : 15)) {
    float d0[4] = {0.f, 0.f, 0.f, 0.f}, d1[4] = {0.f, 0.f, 0.f, 0.f};
    const uint32_t xb = OFF_XS + (lane & 7) * 1168 + (fk * 24 + (lane >> 3)) * 16;
#pragma unroll
    for (int k = 0; k < 12; k += 2) {
      uint32_t b0, b1, b2, b3;
      ldsm4(xb + k * 32, b0, b1, b2, b3);
      mma_bf16(d0, wa[k][0], wa[k][1], wa[k][2], wa[k][3], b0, b1);
      mma_bf16(d1, wa[k + 1][0], wa[k + 1][1], wa[k + 1][2], wa[k + 1][3], b2, b3);
    }
    sts128(OFF_RED + tid * 16, __float_as_uint(d0[0] + d1[0]), __float_as_uint(d0[1] + d1[1]), __float_as_uint(d0[2] + d1[2]), __float_as_uint(d0[3] + d1[3]));
  }
  TS(26);
  if (warp < 5) {
    bar_sync(9, 512);
    const uint32_t rb = OFF_RED + warp * 1536 + lane * 16;
    const uint4 pa = lds128(rb), pb = lds128(rb + 512), pc = lds128(rb + 1024);
    const float ga = bfr(__uint_as_float(pa.x) + __uint_as_float(pb.x) + __uint_as_float(pc.x));
    const float gb = bfr(__uint_as_float(pa.y) + __uint_as_float(pb.y) + __uint_as_float(pc.y));
    const uint32_t uu = pack_bf(__uint_as_float(pa.z) + __uint_as_float(pb.z) + __uint_as_float(pc.z), __uint_as_float(pa.w) + __uint_as_float(pb.w) + __uint_as_float(pc.w));
    float ra, rb2;
    asm("rcp.approx.ftz.f32 %0, %1;" : "=f"(ra) : "f"(1.f + ex2(ga * -1.4426950408889634f)));
    asm("rcp.approx.ftz.f32 %0, %1;" : "=f"(rb2) : "f"(1.f + ex2(gb * -1.4426950408889634f)));
    const uint32_t act = bf_mul2(pack_bf(ga * ra, gb * rb2), uu);
    sts32(OFF_ACT + tid * 4, act);
    bar_arrive(8, 14 * 32);
  } else {
    bar_arrive(9, 512);
    if (warp >= 7) {
      uint4* dst = &p.s->X[c * DM * 2 + (warp - 7) * 64 + t * 8 + g];
      bar_sync(8, 14 * 32);
      uint32_t b0, b1, b2, b3, b4;
      ldsm4t(OFF_ACT + lane * 16, b0, b1, b2, b3);
      asm volatile("ldmatrix.sync.aligned.m8n8.x1.trans.shared.b16 {%0}, [%1];" : "=r"(b4) : "r"(OFF_ACT + 512 + lane * 16) : "memory");
      float y[4][4];
#pragma unroll
      for (int j = 0; j < 4; j++) {
        y[j][0] = y[j][1] = y[j][2] = y[j][3] = 0.f;
        mma_bf16(y[j], wd[j][0], wd[j][1], wd[j][2], wd[j][3], b0, b1);
      }
#pragma unroll
      for (int j = 0; j < 4; j++) mma_bf16(y[j], wd[4 + j][0], wd[4 + j][1], wd[4 + j][2], wd[4 + j][3], b2, b3);
      if (!five) {
#pragma unroll
        for (int j = 0; j < 4; j++) mma_bf16_k8(y[j], wd[8 + (j >> 1)][2 * (j & 1)], wd[8 + (j >> 1)][2 * (j & 1) + 1], b4);
      }
      str128(dst, (pack_bf(y[0][0], y[0][1]) & ~1u) | 0x10000u, pack_bf(y[0][2], y[0][3]), pack_bf(y[1][0], y[1][1]), pack_bf(y[1][2], y[1][3]));
      str128(dst + 32, (pack_bf(y[2][0], y[2][1]) & ~1u) | 0x10000u, pack_bf(y[2][2], y[2][3]), pack_bf(y[3][0], y[3][1]), pack_bf(y[3][2], y[3][3]));
    }
  }
  TS(10);

  if (c < 72) {
    const uint4* src = &p.s->X[(warp * 4 + t) * (DM * 2) + c * 8 + g];
    const int slot = (c & 3) * 2 + (lane >> 4), dw = (c >> 2) * 16 + (lane & 15);
    uint32_t hv = 0, kv = 0, res = 0;
    float rs = 0.f;
    if (warp == 0) {
      hv = ~0u;
      SPIN_WHILE(max(hv, kv) == ~0u, hv = ldr32((const uint32_t*)p.s->HS + 2304 + slot * 288 + dw); kv = ldr32(&p.s->HS[1152 + slot]));
      const uint32_t k16 = kv >> 16;
      const float r = bf_lo((k16 & 0x8000u) ? (k16 & 0x7FFFu) : (~k16 & 0xFFFFu));
      asm("rcp.approx.ftz.f32 %0, %1;" : "=f"(rs) : "f"(1.f + ex2(r * -1.4426950408889634f)));
      res = lds32(OFF_XS + slot * 1168 + dw * 4);
    }
    const uint32_t sel = (g & 1) ? 0x3F800000u : 0x00003F80u;
    const uint32_t q0 = keep((g >> 1) == 0 ? sel : 0u), q1 = keep((g >> 1) == 1 ? sel : 0u), q2 = keep((g >> 1) == 2 ? sel : 0u), q3 = keep((g >> 1) == 3 ? sel : 0u);
    uint4 a0 = make_uint4(0, 0, 0, 0), a1 = a0;
    SPIN_WHILE(!(a0.x & a1.x & 0x10000u), if (!(a0.x & 0x10000u)) a0 = ldr128(src); if (!(a1.x & 0x10000u)) a1 = ldr128(src + 64 * DM * 2));
    float d[4] = {0.f, 0.f, 0.f, 0.f}, e[4] = {0.f, 0.f, 0.f, 0.f};
    mma_bf16(d, q0, 0u, q1, 0u, a0.x, a0.y); mma_bf16(e, q2, 0u, q3, 0u, a0.z, a0.w);
    mma_bf16(d, q0, 0u, q1, 0u, a1.x, a1.y); mma_bf16(e, q2, 0u, q3, 0u, a1.z, a1.w);
    sts64(OFF_FIN + warp * 256 + (g & 1) * 128 + (g >> 1) * 32 + t * 8, __float_as_uint(d[0] + e[0]), __float_as_uint(d[1] + e[1]));
    TS(11);
    if (warp == 0) {
      bar_sync(0, 512);
      float2 s[16];
#pragma unroll
      for (int i = 0; i < 16; i++) { const uint2 q = lds64(OFF_FIN + i * 256 + lane * 8); s[i] = make_float2(__uint_as_float(q.x), __uint_as_float(q.y)); }
#pragma unroll
      for (int o = 1; o < 16; o *= 2)
#pragma unroll
        for (int i = 0; i < 16; i += 2 * o) { s[i].x += s[i + o].x; s[i].y += s[i + o].y; }
      const uint32_t upd = keep(bf_mul2(pack_bf(s[0].x, s[0].y), pack_bf(rs, rs)));
      p.out[(2047 - (int)(kv & 2047u)) * 288 + dw] = bf_add2(hv, bf_add2(res, upd));
    } else bar_arrive(0, 512);
  }
  asm volatile("cp.async.bulk.wait_group.read 0;" ::: "memory");
  TS(12);
  TS_DUMP();
}

typedef CUresult (*EncodeFn)(CUtensorMap*, CUtensorMapDataType, cuuint32_t, void*, const cuuint64_t*, const cuuint64_t*, const cuuint32_t*,
                             const cuuint32_t*, CUtensorMapInterleave, CUtensorMapSwizzle, CUtensorMapL2promotion, CUtensorMapFloatOOBfill);

}

extern "C" void kernel_launch(void* const* d_in, const int* in_sizes, int n_in, void* d_out, int out_size) {
  (void)in_sizes; (void)n_in; (void)out_size;
  static EncodeFn enc = nullptr;
  static Scratch* scratch = nullptr;
  if (!enc) {
    void* fn = nullptr;
    cudaDriverEntryPointQueryResult qr;
    cudaGetDriverEntryPoint("cuTensorMapEncodeTiled", &fn, cudaEnableDefault, &qr);
    enc = (EncodeFn)fn;
    cudaGetSymbolAddress((void**)&scratch, g_S);
    cudaFuncSetAttribute(fused_kernel<false>, cudaFuncAttributeMaxDynamicSharedMemorySize, SMEM_BYTES);
    cudaFuncSetAttribute(fused_kernel<true>, cudaFuncAttributeMaxDynamicSharedMemorySize, SMEM_BYTES);
  }
  TMaps tm;
  for (int i = 0; i < 6; i++) {
    const bool dn = i % 3 == 2;
    const cuuint32_t w = i < 3 ? 40 : 32;
    cuuint64_t gd[3] = {(cuuint64_t)(dn ? 64 : FF), (cuuint64_t)(dn ? FF : DM), 9};
    cuuint64_t gs[2] = {(cuuint64_t)(dn ? DM * 2 : FF * 2), 128};
    cuuint32_t bx[3] = {dn ? 64 : w, dn ? w : 96, i < 3 ? 2u : 3u};
    cuuint32_t es[3] = {1, 1, 1};
    enc(&tm.m[i], CU_TENSOR_MAP_DATA_TYPE_BFLOAT16, dn ? 3 : 2, d_in[11 + i % 3], gd, gs, bx, es, CU_TENSOR_MAP_INTERLEAVE_NONE,
        dn ? CU_TENSOR_MAP_SWIZZLE_128B : i < 3 ? CU_TENSOR_MAP_SWIZZLE_NONE : CU_TENSOR_MAP_SWIZZLE_64B,
        CU_TENSOR_MAP_L2_PROMOTION_NONE, CU_TENSOR_MAP_FLOAT_OOB_FILL_NONE);
  }
  for (int i = 6; i < 8; i++) {
    cuuint64_t gd[2] = {DM * 16, NCTA};
    cuuint64_t gs[1] = {DM * 32};
    cuuint32_t bx[2] = {16, i == 6 ? 160u : 128u};
    cuuint32_t es[2] = {1, 1};
    enc(&tm.m[i], CU_TENSOR_MAP_DATA_TYPE_FLOAT16, 2, scratch->X, gd, gs, bx, es, CU_TENSOR_MAP_INTERLEAVE_NONE, CU_TENSOR_MAP_SWIZZLE_32B,
        CU_TENSOR_MAP_L2_PROMOTION_NONE, CU_TENSOR_MAP_FLOAT_OOB_FILL_NONE);
  }
  Params p;
  p.x = (const unsigned char*)d_in[0];
  bool far = false;
  for (int i = 0; i < 7; i++) {
    p.far[i] = (const unsigned char*)d_in[1 + i];
    const long long d = (long long)((intptr_t)d_in[1 + i] - (intptr_t)d_in[0]);
    p.off[i] = (int)(d / 16);
    if ((long long)p.off[i] * 16 != d) far = true;
  }
  p.dskip = (const uint32_t*)d_in[8];
  p.w_r = (const uint32_t*)d_in[10];
  p.w_gate = (const unsigned char*)d_in[11];
  p.w_up = (const unsigned char*)d_in[12];
  for (int f = 0; f < 2; f++) {
    static const int kind[17] = {0, 0, 0, 0, 0, 0, 1, 1, 1, 1, 1, 1, 2, 2, 2, 2, 2};
    static const int idx[2][17] = {{3, 4, 5, 0, 1, 2, 0, 1, 2, 3, 4, 5, 6, 8, 0, 2, 4}, {3, 4, 5, 0, 1, 2, 0, 1, 2, 3, 4, 5, 0, -1, 3, -1, 6}};
    static const int blk[2][17] = {{-1, -1, -1, -1, -1, -1, 1, -1, 2, -1, 3, -1, 16, -1, -1, -1, -1}, {-1, -1, -1, -1, -1, -1, 1, -1, 2, -1, 3, -1, 16, -1, -1, -1, -1}};
    const int pitch = f ? 64 : 80;
    for (int u = 0; u < 17; u++) {
      const int s = idx[f][u];
      const uint32_t dst = kind[u] == 0 ? OFF_G + s * 96 * pitch : kind[u] == 2 ? down_box(s, f) : OFF_W + W_BYTES + (s >> 1) * W_BYTES + (s & 1) * 96 * pitch;
      const uint32_t mb = u == X_NE ? MB_GF - OFF_MISC : blk[f][u] >= 0 ? MB_KF - OFF_MISC + blk[f][u] * 8 : 0;
      p.sched[f][u] = s < 0 ? 3u : kind[u] | s << 2 | mb << 6 | dst << 14;
    }
  }
  p.out = (uint32_t*)d_out;
  p.zero = 0;
  p.ts = nullptr;
  p.s = scratch;
  if (far) { fused_kernel<true><<<NCTA, NT, SMEM_BYTES, cudaStreamPerThread>>>(p, tm); return; }
  fused_kernel<false><<<NCTA, NT, SMEM_BYTES, cudaStreamPerThread>>>(p, tm);
}
```

```cpp
#include <cuda_runtime.h>
#include <cuda.h>
#include <cuda_bf16.h>
#include <cuda_fp16.h>
#include <stdint.h>
#include <stddef.h>

namespace {

constexpr int NCTA = 128;
constexpr int NT = 640;
constexpr int DM = 576;
constexpr int FF = 4608;
constexpr int SPIN_MAX = 1 << 20;

struct Scratch {
  uint4 X[NCTA * DM * 2];
  uint4 KX[64 * 128];
  uint4 HS[1152 + 8];
  uint4 R[256];
  uint4 SC[256];
  uint32_t FLAG[NCTA * 8];
};
__device__ Scratch g_S;

#define TS(i)
#define TSX(i)
#define TS_DUMP()

constexpr int SB = 1024;
constexpr int BOX = 15360;
constexpr int OFF_G = SB;
constexpr int OFF_W = OFF_G + 3 * BOX;
constexpr int W_UP = 26624;
constexpr int W_KT = W_UP + 5120;
constexpr int W_L3 = W_KT + 4416;
constexpr int W_CW = W_L3 + 4096;
constexpr int W_MISC = W_CW + 640;
constexpr int W_BYTES = 40960;
constexpr int ALT = -W_UP;
static_assert(W_MISC + 32 <= W_BYTES && OFF_W % 1024 == 0 && W_UP % 256 == 0 && W_BYTES + ALT + 3 * 4096 <= W_UP, "wg block");
constexpr int OFF_K5 = OFF_G + 40960;
constexpr int YT_PITCH = 1184;
constexpr int OFF_YT = OFF_W + 4 * W_BYTES;
constexpr int OFF_WR = OFF_YT + 16 * YT_PITCH + 64;
constexpr int OFF_MISC = OFF_WR + 2304;
constexpr int SMEM_BYTES = OFF_MISC + 1024 - SB;
static_assert(OFF_YT % 16 == 0 && OFF_MISC % 16 == 0, "align");
static_assert(SMEM_BYTES <= 232448, "smem");
constexpr int MB_GU = OFF_MISC;
constexpr int MB_D = OFF_MISC + 8;
constexpr int MB_KF = OFF_MISC + 16;
constexpr int MB_GF = OFF_MISC + 48;
constexpr int MB_SC = OFF_MISC + 56;
constexpr int MB_UL = OFF_MISC + 64;
constexpr int MB_H = MB_KF + 128;
constexpr int MISC_EPOCH = OFF_MISC + 152;
constexpr int MISC_SW = OFF_MISC + 156;
constexpr int MISC_EM = OFF_MISC + 288;
constexpr int MISC_RK = OFF_MISC + 160;
constexpr int MISC_LN1 = OFF_MISC + 192;
constexpr int OFF_XS = OFF_W + W_BYTES + W_UP;
constexpr int OFF_RED = OFF_W + 2 * W_BYTES + W_UP;
constexpr int OFF_FIN = OFF_W + 3 * W_BYTES + W_UP;
constexpr int OFF_ACT = OFF_FIN + 4096;
constexpr int MISC_CNT = OFF_ACT + 1024;

__device__ __forceinline__ uint32_t smem_u32(const void* p) { return (uint32_t)__cvta_generic_to_shared(p); }
__device__ __forceinline__ uint32_t lds32(uint32_t a) { uint32_t v; asm volatile("ld.shared.b32 %0, [%1];" : "=r"(v) : "r"(a) : "memory"); return v; }
__device__ __forceinline__ uint32_t lds16(uint32_t a) { uint16_t v; asm volatile("ld.shared.u16 %0, [%1];" : "=h"(v) : "r"(a) : "memory"); return v; }
__device__ __forceinline__ uint2 lds64(uint32_t a) { uint2 v; asm volatile("ld.shared.v2.b32 {%0,%1}, [%2];" : "=r"(v.x), "=r"(v.y) : "r"(a) : "memory"); return v; }
__device__ __forceinline__ uint4 lds128(uint32_t a) { uint4 v; asm volatile("ld.shared.v4.b32 {%0,%1,%2,%3}, [%4];" : "=r"(v.x), "=r"(v.y), "=r"(v.z), "=r"(v.w) : "r"(a) : "memory"); return v; }
__device__ __forceinline__ void sts16(uint32_t a, uint32_t v) { asm volatile("st.shared.u16 [%0], %1;" :: "r"(a), "h"((uint16_t)v) : "memory"); }
__device__ __forceinline__ void sts32(uint32_t a, uint32_t v) { asm volatile("st.shared.b32 [%0], %1;" :: "r"(a), "r"(v) : "memory"); }
__device__ __forceinline__ void sts64(uint32_t a, uint32_t x, uint32_t y) { asm volatile("st.shared.v2.b32 [%0], {%1,%2};" :: "r"(a), "r"(x), "r"(y) : "memory"); }
__device__ __forceinline__ void sts128(uint32_t a, uint32_t x, uint32_t y, uint32_t z, uint32_t w) { asm volatile("st.shared.v4.b32 [%0], {%1,%2,%3,%4};" :: "r"(a), "r"(x), "r"(y), "r"(z), "r"(w) : "memory"); }
__device__ __forceinline__ void ldsm4(uint32_t a, uint32_t& r0, uint32_t& r1, uint32_t& r2, uint32_t& r3) {
  asm volatile("ldmatrix.sync.aligned.m8n8.x4.shared.b16 {%0,%1,%2,%3}, [%4];" : "=r"(r0), "=r"(r1), "=r"(r2), "=r"(r3) : "r"(a) : "memory");
}
__device__ __forceinline__ void ldsm2(uint32_t a, uint32_t& r0, uint32_t& r1) {
  asm volatile("ldmatrix.sync.aligned.m8n8.x2.shared.b16 {%0,%1}, [%2];" : "=r"(r0), "=r"(r1) : "r"(a) : "memory");
}
__device__ __forceinline__ void ldsm4t(uint32_t a, uint32_t& r0, uint32_t& r1, uint32_t& r2, uint32_t& r3) {
  asm volatile("ldmatrix.sync.aligned.m8n8.x4.trans.shared.b16 {%0,%1,%2,%3}, [%4];" : "=r"(r0), "=r"(r1), "=r"(r2), "=r"(r3) : "r"(a) : "memory");
}
__device__ __forceinline__ void stsm4t(uint32_t a, uint32_t r0, uint32_t r1, uint32_t r2, uint32_t r3) {
  asm volatile("stmatrix.sync.aligned.m8n8.x4.trans.shared.b16 [%0], {%1,%2,%3,%4};" :: "r"(a), "r"(r0), "r"(r1), "r"(r2), "r"(r3) : "memory");
}
__device__ __forceinline__ uint4 ldr128(const void* p) {
  unsigned long long lo, hi;
  asm volatile("{ .reg .b128 t; ld.relaxed.gpu.global.b128 t, [%2]; mov.b128 {%0, %1}, t; }" : "=l"(lo), "=l"(hi) : "l"(p) : "memory");
  return make_uint4((uint32_t)lo, (uint32_t)(lo >> 32), (uint32_t)hi, (uint32_t)(hi >> 32));
}
__device__ __forceinline__ void str128(void* p, uint32_t x, uint32_t y, uint32_t z, uint32_t w) {
  asm volatile("{ .reg .b128 t; .reg .b64 lo, hi; mov.b64 lo, {%1,%2}; mov.b64 hi, {%3,%4}; mov.b128 t, {lo, hi}; st.relaxed.gpu.global.b128 [%0], t; }"
               :: "l"(p), "r"(x), "r"(y), "r"(z), "r"(w) : "memory");
}
__device__ __forceinline__ void str64(void* p, uint32_t x, uint32_t y) {
  asm volatile("{ .reg .b64 t; mov.b64 t, {%1,%2}; st.relaxed.gpu.global.b64 [%0], t; }" :: "l"(p), "r"(x), "r"(y) : "memory");
}
__device__ __forceinline__ uint32_t ldr32(const void* p) { uint32_t v; asm volatile("ld.relaxed.gpu.global.b32 %0, [%1];" : "=r"(v) : "l"(p) : "memory"); return v; }
__device__ __forceinline__ void str32(void* p, uint32_t v) { asm volatile("st.relaxed.gpu.global.b32 [%0], %1;" :: "l"(p), "r"(v) : "memory"); }
__device__ __forceinline__ void str16(void* p, uint32_t v) { asm volatile("st.relaxed.gpu.global.u16 [%0], %1;" :: "l"(p), "h"((uint16_t)v) : "memory"); }
__device__ __forceinline__ void fence_gpu() { asm volatile("fence.acq_rel.gpu;" ::: "memory"); }
__device__ __forceinline__ void bar_sync(int id, int n) { asm volatile("bar.sync %0, %1;" :: "r"(id), "r"(n) : "memory"); }
__device__ __forceinline__ void bar_arrive(int id, int n) { asm volatile("bar.arrive %0, %1;" :: "r"(id), "r"(n) : "memory"); }

__device__ __forceinline__ float bf_lo(uint32_t w) { return __uint_as_float(w << 16); }
__device__ __forceinline__ float bf_hi(uint32_t w) { return __uint_as_float(w & 0xFFFF0000u); }
__device__ __forceinline__ uint32_t pack_bf(float lo, float hi) { uint32_t r; asm("cvt.rn.bf16x2.f32 %0, %1, %2;" : "=r"(r) : "f"(hi), "f"(lo)); return r; }
__device__ __forceinline__ uint32_t pack_h(float lo, float hi) { uint32_t r; asm("cvt.rn.f16x2.f32 %0, %1, %2;" : "=r"(r) : "f"(hi), "f"(lo)); return r; }
__device__ __forceinline__ uint32_t pack_hv(float lo, float hi) { uint32_t r; asm volatile("cvt.rn.f16x2.f32 %0, %1, %2;" : "=r"(r) : "f"(hi), "f"(lo) : "memory"); return r; }
__device__ __forceinline__ float bfr(float x) { return bf_lo(pack_bf(x, 0.f)); }
__device__ __forceinline__ uint32_t bf_sub2(uint32_t a, uint32_t b) { __nv_bfloat162 r = __hsub2(*(__nv_bfloat162*)&a, *(__nv_bfloat162*)&b); return *(uint32_t*)&r; }
__device__ __forceinline__ uint32_t bf_add2(uint32_t a, uint32_t b) { __nv_bfloat162 r = __hadd2(*(__nv_bfloat162*)&a, *(__nv_bfloat162*)&b); return *(uint32_t*)&r; }
__device__ __forceinline__ uint32_t bf_mul2(uint32_t a, uint32_t b) { __nv_bfloat162 r = __hmul2(*(__nv_bfloat162*)&a, *(__nv_bfloat162*)&b); return *(uint32_t*)&r; }
__device__ __forceinline__ float2 h2f(uint32_t w) { return __half22float2(*(__half2*)&w); }
__device__ __forceinline__ float ex2(float x) { float r; asm("ex2.approx.ftz.f32 %0, %1;" : "=f"(r) : "f"(x)); return r; }
__device__ __forceinline__ float warp_sum(float v) {
#pragma unroll
  for (int o = 16; o > 0; o >>= 1) v += __shfl_xor_sync(0xffffffffu, v, o);
  return v;
}
__device__ __forceinline__ void mma_f16_f32(float* d, uint32_t a0, uint32_t a1, uint32_t a2, uint32_t a3, uint32_t b0, uint32_t b1) {
  asm volatile("mma.sync.aligned.m16n8k16.row.col.f32.f16.f16.f32 {%0,%1,%2,%3}, {%4,%5,%6,%7}, {%8,%9}, {%0,%1,%2,%3};"
               : "+f"(d[0]), "+f"(d[1]), "+f"(d[2]), "+f"(d[3]) : "r"(a0), "r"(a1), "r"(a2), "r"(a3), "r"(b0), "r"(b1));
}
__device__ __forceinline__ void mma_f16_f16(uint32_t& d0, uint32_t& d1, uint32_t a0, uint32_t a1, uint32_t a2, uint32_t a3, uint32_t b0, uint32_t b1) {
  asm volatile("mma.sync.aligned.m16n8k16.row.col.f16.f16.f16.f16 {%0,%1}, {%2,%3,%4,%5}, {%6,%7}, {%0,%1};"
               : "+r"(d0), "+r"(d1) : "r"(a0), "r"(a1), "r"(a2), "r"(a3), "r"(b0), "r"(b1));
}
__device__ __forceinline__ void mma_bf16(float* d, uint32_t a0, uint32_t a1, uint32_t a2, uint32_t a3, uint32_t b0, uint32_t b1) {
  asm volatile("mma.sync.aligned.m16n8k16.row.col.f32.bf16.bf16.f32 {%0,%1,%2,%3}, {%4,%5,%6,%7}, {%8,%9}, {%0,%1,%2,%3};"
               : "+f"(d[0]), "+f"(d[1]), "+f"(d[2]), "+f"(d[3]) : "r"(a0), "r"(a1), "r"(a2), "r"(a3), "r"(b0), "r"(b1));
}
__device__ __forceinline__ void mma_bf16_k8(float* d, uint32_t a0, uint32_t a1, uint32_t b0) {
  asm volatile("mma.sync.aligned.m16n8k8.row.col.f32.bf16.bf16.f32 {%0,%1,%2,%3}, {%4,%5}, {%6}, {%0,%1,%2,%3};"
               : "+f"(d[0]), "+f"(d[1]), "+f"(d[2]), "+f"(d[3]) : "r"(a0), "r"(a1), "r"(b0));
}

__device__ __forceinline__ void wg_fence() { asm volatile("wgmma.fence.sync.aligned;" ::: "memory"); }
__device__ __forceinline__ void wg_commit() { asm volatile("wgmma.commit_group.sync.aligned;" ::: "memory"); }
template <int N> __device__ __forceinline__ void wg_wait() { asm volatile("wgmma.wait_group.sync.aligned %0;" :: "n"(N) : "memory"); }
template <int TB> __device__ __forceinline__ void wgmma32(float* d, const uint32_t* a, uint32_t dlo, uint32_t dhi) {
  asm volatile("{ .reg .b64 dd; mov.b64 dd, {%20, %21}; wgmma.mma_async.sync.aligned.m64n32k16.f32.f16.f16 "
               "{%0,%1,%2,%3,%4,%5,%6,%7,%8,%9,%10,%11,%12,%13,%14,%15}, {%16,%17,%18,%19}, dd, 1, 1, 1, %22; }"
               : "+f"(d[0]), "+f"(d[1]), "+f"(d[2]), "+f"(d[3]), "+f"(d[4]), "+f"(d[5]), "+f"(d[6]), "+f"(d[7]), "+f"(d[8]), "+f"(d[9]), "+f"(d[10]), "+f"(d[11]), "+f"(d[12]), "+f"(d[13]), "+f"(d[14]), "+f"(d[15])
               : "r"(a[0]), "r"(a[1]), "r"(a[2]), "r"(a[3]), "r"(dlo), "r"(dhi), "n"(TB));
}
template <int TB> __device__ __forceinline__ void wgmma96(float* d, const uint32_t* a, uint32_t dlo, uint32_t dhi) {
  asm volatile("{ .reg .b64 dd; mov.b64 dd, {%52, %53}; wgmma.mma_async.sync.aligned.m64n96k16.f32.f16.f16 "
               "{%0,%1,%2,%3,%4,%5,%6,%7,%8,%9,%10,%11,%12,%13,%14,%15,%16,%17,%18,%19,%20,%21,%22,%23,%24,%25,%26,%27,%28,%29,%30,%31,%32,%33,%34,%35,%36,%37,%38,%39,%40,%41,%42,%43,%44,%45,%46,%47}, {%48,%49,%50,%51}, dd, 1, 1, 1, %54; }"
               : "+f"(d[0]), "+f"(d[1]), "+f"(d[2]), "+f"(d[3]), "+f"(d[4]), "+f"(d[5]), "+f"(d[6]), "+f"(d[7]), "+f"(d[8]), "+f"(d[9]), "+f"(d[10]), "+f"(d[11]), "+f"(d[12]), "+f"(d[13]), "+f"(d[14]), "+f"(d[15]), "+f"(d[16]), "+f"(d[17]), "+f"(d[18]), "+f"(d[19]), "+f"(d[20]), "+f"(d[21]), "+f"(d[22]), "+f"(d[23]), "+f"(d[24]), "+f"(d[25]), "+f"(d[26]), "+f"(d[27]), "+f"(d[28]), "+f"(d[29]), "+f"(d[30]), "+f"(d[31]), "+f"(d[32]), "+f"(d[33]), "+f"(d[34]), "+f"(d[35]), "+f"(d[36]), "+f"(d[37]), "+f"(d[38]), "+f"(d[39]), "+f"(d[40]), "+f"(d[41]), "+f"(d[42]), "+f"(d[43]), "+f"(d[44]), "+f"(d[45]), "+f"(d[46]), "+f"(d[47])
               : "r"(a[0]), "r"(a[1]), "r"(a[2]), "r"(a[3]), "r"(dlo), "r"(dhi), "n"(TB));
}
template <int TB> __device__ __forceinline__ void wgmma96_init(float* d, const uint32_t* a, uint32_t dlo, uint32_t dhi) {
  asm volatile("{ .reg .b64 dd; mov.b64 dd, {%52, %53}; wgmma.mma_async.sync.aligned.m64n96k16.f32.f16.f16 "
               "{%0,%1,%2,%3,%4,%5,%6,%7,%8,%9,%10,%11,%12,%13,%14,%15,%16,%17,%18,%19,%20,%21,%22,%23,%24,%25,%26,%27,%28,%29,%30,%31,%32,%33,%34,%35,%36,%37,%38,%39,%40,%41,%42,%43,%44,%45,%46,%47}, {%48,%49,%50,%51}, dd, 0, 1, 1, %54; }"
               : "=f"(d[0]), "=f"(d[1]), "=f"(d[2]), "=f"(d[3]), "=f"(d[4]), "=f"(d[5]), "=f"(d[6]), "=f"(d[7]), "=f"(d[8]), "=f"(d[9]), "=f"(d[10]), "=f"(d[11]), "=f"(d[12]), "=f"(d[13]), "=f"(d[14]), "=f"(d[15]), "=f"(d[16]), "=f"(d[17]), "=f"(d[18]), "=f"(d[19]), "=f"(d[20]), "=f"(d[21]), "=f"(d[22]), "=f"(d[23]), "=f"(d[24]), "=f"(d[25]), "=f"(d[26]), "=f"(d[27]), "=f"(d[28]), "=f"(d[29]), "=f"(d[30]), "=f"(d[31]), "=f"(d[32]), "=f"(d[33]), "=f"(d[34]), "=f"(d[35]), "=f"(d[36]), "=f"(d[37]), "=f"(d[38]), "=f"(d[39]), "=f"(d[40]), "=f"(d[41]), "=f"(d[42]), "=f"(d[43]), "=f"(d[44]), "=f"(d[45]), "=f"(d[46]), "=f"(d[47])
               : "r"(a[0]), "r"(a[1]), "r"(a[2]), "r"(a[3]), "r"(dlo), "r"(dhi), "n"(TB));
}
template <int TB> __device__ __forceinline__ void wgmma32_init(float* d, const uint32_t* a, uint32_t dlo, uint32_t dhi) {
  asm volatile("{ .reg .b64 dd; mov.b64 dd, {%20, %21}; wgmma.mma_async.sync.aligned.m64n32k16.f32.f16.f16 "
               "{%0,%1,%2,%3,%4,%5,%6,%7,%8,%9,%10,%11,%12,%13,%14,%15}, {%16,%17,%18,%19}, dd, 0, 1, 1, %22; }"
               : "=f"(d[0]), "=f"(d[1]), "=f"(d[2]), "=f"(d[3]), "=f"(d[4]), "=f"(d[5]), "=f"(d[6]), "=f"(d[7]), "=f"(d[8]), "=f"(d[9]), "=f"(d[10]), "=f"(d[11]), "=f"(d[12]), "=f"(d[13]), "=f"(d[14]), "=f"(d[15])
               : "r"(a[0]), "r"(a[1]), "r"(a[2]), "r"(a[3]), "r"(dlo), "r"(dhi), "n"(TB));
}
__device__ __forceinline__ void wgmma64h(uint32_t* d, uint32_t a0, uint32_t a1, uint32_t a2, uint32_t a3, uint32_t dlo, uint32_t dhi) {
  asm volatile("{ .reg .b64 dd; mov.b64 dd, {%20, %21}; wgmma.mma_async.sync.aligned.m64n64k16.f16.f16.f16 "
               "{%0,%1,%2,%3,%4,%5,%6,%7,%8,%9,%10,%11,%12,%13,%14,%15}, {%16,%17,%18,%19}, dd, 1, 1, 1, 0; }"
               : "+r"(d[0]), "+r"(d[1]), "+r"(d[2]), "+r"(d[3]), "+r"(d[4]), "+r"(d[5]), "+r"(d[6]), "+r"(d[7]), "+r"(d[8]), "+r"(d[9]), "+r"(d[10]), "+r"(d[11]), "+r"(d[12]), "+r"(d[13]), "+r"(d[14]), "+r"(d[15])
               : "r"(a0), "r"(a1), "r"(a2), "r"(a3), "r"(dlo), "r"(dhi));
}
__device__ __forceinline__ void wgmma64h_init(uint32_t* d, uint32_t a0, uint32_t a1, uint32_t a2, uint32_t a3, uint32_t dlo, uint32_t dhi) {
  asm volatile("{ .reg .b64 dd; mov.b64 dd, {%20, %21}; wgmma.mma_async.sync.aligned.m64n64k16.f16.f16.f16 "
               "{%0,%1,%2,%3,%4,%5,%6,%7,%8,%9,%10,%11,%12,%13,%14,%15}, {%16,%17,%18,%19}, dd, 0, 1, 1, 0; }"
               : "=r"(d[0]), "=r"(d[1]), "=r"(d[2]), "=r"(d[3]), "=r"(d[4]), "=r"(d[5]), "=r"(d[6]), "=r"(d[7]), "=r"(d[8]), "=r"(d[9]), "=r"(d[10]), "=r"(d[11]), "=r"(d[12]), "=r"(d[13]), "=r"(d[14]), "=r"(d[15])
               : "r"(a0), "r"(a1), "r"(a2), "r"(a3), "r"(dlo), "r"(dhi));
}
__device__ __forceinline__ void wgmma40_ss(float* d, uint32_t alo, uint32_t blo, uint32_t hi) {
  asm volatile("{ .reg .b64 da, db; mov.b64 da, {%20, %22}; mov.b64 db, {%21, %22}; "
               "wgmma.mma_async.sync.aligned.m64n40k16.f32.f16.f16 {%0,%1,%2,%3,%4,%5,%6,%7,%8,%9,%10,%11,%12,%13,%14,%15,%16,%17,%18,%19}, da, db, 1, 1, 1, 1, 1; }"
               : "+f"(d[0]), "+f"(d[1]), "+f"(d[2]), "+f"(d[3]), "+f"(d[4]), "+f"(d[5]), "+f"(d[6]), "+f"(d[7]), "+f"(d[8]), "+f"(d[9]), "+f"(d[10]), "+f"(d[11]), "+f"(d[12]), "+f"(d[13]), "+f"(d[14]), "+f"(d[15]), "+f"(d[16]), "+f"(d[17]), "+f"(d[18]), "+f"(d[19])
               : "r"(alo), "r"(blo), "r"(hi));
}
__device__ __forceinline__ void wgmma40_ss_init(float* d, uint32_t alo, uint32_t blo, uint32_t hi) {
  asm volatile("{ .reg .b64 da, db; mov.b64 da, {%20, %22}; mov.b64 db, {%21, %22}; "
               "wgmma.mma_async.sync.aligned.m64n40k16.f32.f16.f16 {%0,%1,%2,%3,%4,%5,%6,%7,%8,%9,%10,%11,%12,%13,%14,%15,%16,%17,%18,%19}, da, db, 0, 1, 1, 1, 1; }"
               : "=f"(d[0]), "=f"(d[1]), "=f"(d[2]), "=f"(d[3]), "=f"(d[4]), "=f"(d[5]), "=f"(d[6]), "=f"(d[7]), "=f"(d[8]), "=f"(d[9]), "=f"(d[10]), "=f"(d[11]), "=f"(d[12]), "=f"(d[13]), "=f"(d[14]), "=f"(d[15]), "=f"(d[16]), "=f"(d[17]), "=f"(d[18]), "=f"(d[19])
               : "r"(alo), "r"(blo), "r"(hi));
}
__device__ __forceinline__ float vzero() { float v; asm volatile("mov.b32 %0, 0;" : "=f"(v)); return v; }
__device__ __forceinline__ void tma_box(uint32_t dst, const CUtensorMap* tm, uint32_t mb, int x, int y) {
  asm volatile("cp.async.bulk.tensor.2d.shared::cluster.global.mbarrier::complete_tx::bytes [%0], [%1, {%3, %4}], [%2];"
               :: "r"(dst), "l"(tm), "r"(mb), "r"(x), "r"(y) : "memory");
}
__device__ __forceinline__ void l2_prefetch(const void* src, uint32_t bytes) {
  asm volatile("cp.async.bulk.prefetch.L2.global [%0], %1;" :: "l"(src), "r"(bytes) : "memory");
}
__device__ __forceinline__ uint32_t uni(uint32_t v) {
  uint32_t r; asm volatile("shfl.sync.idx.b32 %0, %1, 0, 0x1f, 0xffffffff;" : "=r"(r) : "r"(v)); return r;
}
__device__ __forceinline__ int fresh_tid() { int v; asm volatile("mov.u32 %0, %tid.x;" : "=r"(v)); return v; }

struct Params {
  const unsigned char* x;
  Scratch* s;
  int off[7];
  uint32_t zero;
  uint32_t* out;
  const uint32_t* dskip;
  const uint32_t* w_r;
  const unsigned char* w_gate;
  const unsigned char* w_up;
  long long* ts;
  const unsigned char* far[7];
  uint32_t sched[2][17];
};
__device__ __forceinline__ uint32_t ldnc32(const void* p) { uint32_t v; asm volatile("ld.global.nc.b32 %0, [%1];" : "=r"(v) : "l"(p)); return v; }
__device__ __forceinline__ uint32_t ldnc16(const void* p) { uint16_t v; asm volatile("ld.global.nc.u16 %0, [%1];" : "=h"(v) : "l"(p)); return v; }
__device__ __forceinline__ uint4 ldnc128(const void* p) { uint4 v; asm volatile("ld.global.nc.v4.b32 {%0,%1,%2,%3}, [%4];" : "=r"(v.x), "=r"(v.y), "=r"(v.z), "=r"(v.w) : "l"(p)); return v; }
__device__ __forceinline__ void mbar_wait(uint32_t mb, uint32_t ph = 0) {
#pragma unroll 1
  for (int it = 0; it < SPIN_MAX; it++) {
    uint32_t ok;
    asm volatile("{ .reg .pred q; mbarrier.try_wait.parity.shared::cta.b64 q, [%1], %2; selp.u32 %0, 1, 0, q; }" : "=r"(ok) : "r"(mb), "r"(ph) : "memory");
    if (ok) break;
  }
}
__device__ __forceinline__ uint32_t mbar_test(uint32_t mb) {
  uint32_t ok;
  asm volatile("{ .reg .pred q; mbarrier.test_wait.parity.shared::cta.b64 q, [%1], 0; selp.u32 %0, 1, 0, q; }" : "=r"(ok) : "r"(mb) : "memory");
  return ok;
}
__device__ __forceinline__ void mbar_arrive(uint32_t mb) { asm volatile("mbarrier.arrive.shared::cta.b64 _, [%0];" :: "r"(mb) : "memory"); }
__device__ __forceinline__ uint32_t ldg16(const void* p) { uint16_t v; asm volatile("ld.global.u16 %0, [%1];" : "=h"(v) : "l"(p) : "memory"); return v; }
__device__ __forceinline__ uint32_t ldr16(const void* p) { uint16_t v; asm volatile("ld.relaxed.gpu.global.u16 %0, [%1];" : "=h"(v) : "l"(p) : "memory"); return v; }
__device__ __forceinline__ void fence_async() { asm volatile("fence.proxy.async.shared::cta;" ::: "memory"); }
#define SPIN_WHILE(cond, body) _Pragma("unroll 1") for (int _it = 0; _it < SPIN_MAX && __any_sync(0xffffffffu, (cond)); _it++) { body; }

struct LnC { uint32_t m2, rh2, rl2; };
__device__ __forceinline__ float diag_sum(float d0, float d1, int t) {
  float q = __shfl_sync(0xffffffffu, d0, 9 * t) + __shfl_sync(0xffffffffu, d1, 9 * t + 4);
  q += __shfl_xor_sync(0xffffffffu, q, 1);
  return q + __shfl_xor_sync(0xffffffffu, q, 2);
}
__device__ __forceinline__ LnC ln_consts(float s, float q, float& r) {
  const float mean = s * (1.f / DM);
  const float var = fmaxf(fmaf(-mean, mean, q * (1.f / DM)), 0.f);
  float sd;
  asm("sqrt.approx.ftz.f32 %0, %1;" : "=f"(sd) : "f"(bfr(bfr(var) + 1e-5f)));
  asm("rcp.approx.ftz.f32 %0, %1;" : "=f"(r) : "f"(bfr(sd)));
  LnC c;
  c.m2 = pack_bf(mean, mean);
  c.rh2 = pack_bf(r, r);
  const float rl = r - bf_lo(c.rh2);
  c.rl2 = pack_bf(rl, rl);
  return c;
}
__device__ __forceinline__ float quad_sum(float s) { s += __shfl_xor_sync(0xffffffffu, s, 1); return s + __shfl_xor_sync(0xffffffffu, s, 2); }
__device__ __forceinline__ uint32_t bf_fma2(uint32_t a, uint32_t b, uint32_t c) {
  __nv_bfloat162 r = __hfma2(*(const __nv_bfloat162*)&a, *(const __nv_bfloat162*)&b, *(const __nv_bfloat162*)&c);
  return *(uint32_t*)&r;
}
__device__ __forceinline__ uint32_t ln_apply(uint32_t w, uint32_t m2, uint32_t rh2, uint32_t rl2) {
  const uint32_t d = bf_sub2(w, m2);
  return bf_fma2(d, rh2, bf_mul2(d, rl2));
}

__device__ __forceinline__ float2 cis(float mag_log2, float rev) {
  const float m = ex2(mag_log2), ang = rev * 6.283185307179586f;
  return make_float2(m * __cosf(ang), m * __sinf(ang));
}
__device__ __forceinline__ float2 csq(float2 a) { return make_float2(fmaf(a.x, a.x, -a.y * a.y), (a.x + a.x) * a.y); }
__device__ __forceinline__ float2 cmul(float2 a, float2 b) { return make_float2(fmaf(a.x, b.x, -a.y * b.y), fmaf(a.x, b.y, a.y * b.x)); }
__device__ __forceinline__ void pmul(uint32_t xr, uint32_t xi, uint32_t w, uint32_t& yr, uint32_t& yi) {
  const __half2 XR = *(__half2*)&xr, XI = *(__half2*)&xi, W = *(__half2*)&w;
  const __half2 a = __hfma2(__hneg2(XI), __high2half2(W), __hmul2(XR, __low2half2(W)));
  const __half2 b = __hfma2(XI, __low2half2(W), __hmul2(XR, __high2half2(W)));
  yr = *(const uint32_t*)&a; yi = *(const uint32_t*)&b;
}
__device__ __forceinline__ uint32_t pk(float2 a) { return pack_h(a.x, a.y); }

struct KgState { float2 c0, z8; float kl; uint32_t w64, w128, w192; };
__device__ __forceinline__ void kgen_tables_n(const uint32_t (&raw)[7], uint32_t scr, int wt, KgState& k) {
  const uint32_t dst = scr + 16384 + wt * 16;
  const float dt = bfr(ex2(bf_lo(raw[6]) * 1.4426950408889634f));
  const float th = dt * bf_lo(raw[1]);
  const float br = dt * bf_lo(raw[2]), bi = dt * bf_lo(raw[3]);
  const float Cr = bf_lo(raw[4]), Ci = bf_lo(raw[5]);
  k.c0 = make_float2(fmaf(Cr, br, -Ci * bi), fmaf(Cr, bi, Ci * br));
  const uint32_t mx = __reduce_max_sync(0xffffffffu, __float_as_uint(fmaxf(fabsf(k.c0.x), fabsf(k.c0.y))));
  const float a2 = dt * bf_lo(raw[0]) * 1.4426950408889634f;
  const float rh = th * 0.15915494309189535f;
  const float rl = fmaf(th, (float)(0.15915494309189535 - (double)0.15915494309189535f), fmaf(th, 0.15915494309189535f, -rh));
  const float rf = rh - rintf(rh);
  const float2 z1 = cis(a2, rf + rl);
  const float p64 = rf * 64.f;
  const float2 z64 = cis(a2 * 64.f, fmaf(64.f, rl, p64 - rintf(p64)));
  const float2 z2 = csq(z1), z128 = csq(z64), z3 = cmul(z2, z1), z4 = csq(z2), z256 = csq(z128), z6 = csq(z3), z512 = csq(z256);
  k.z8 = csq(z4);
  k.w64 = pk(z64); k.w128 = pk(z128); k.w192 = pk(cmul(z128, z64));
  sts128(dst, 0x00003C00u, pk(z2), pk(z4), pk(z6));
  const float2 z1024 = csq(z512), z768 = cmul(z512, z256);
  sts128(dst + 2048, pk(z1), pk(z3), pk(cmul(z4, z1)), pk(cmul(z4, z3)));
  const float2 z2048 = csq(z1024);
  k.kl = fmaf(k.c0.x, z2048.x, -k.c0.y * z2048.y);
  sts128(dst + 4096, pk(z256), pk(cmul(z256, z2)), pk(cmul(z256, z4)), pk(cmul(z256, z6)));
  sts128(dst + 6144, pk(z512), pk(cmul(z512, z4)), pk(z768), pk(cmul(z768, z4)));
  sts128(dst + 8192, pk(z1024), pk(cmul(z1024, z256)), pk(cmul(z1024, z512)), pk(cmul(z1024, z768)));
  sts32(scr + W_MISC + (wt >> 5) * 4, mx);
}
__device__ __forceinline__ int kgen_tables_m(uint32_t scr, int wt, const KgState& k) {
  const uint32_t dst = scr + wt * 16;
  const uint4 e4 = lds128(scr + W_MISC);
  const float2 z16 = csq(k.z8), z32 = csq(z16);
  const int em = max(min((int)(max(max(e4.x, e4.y), max(e4.z, e4.w)) >> 23), 238), 16);
  const float sc = __uint_as_float((uint32_t)(127 + 4 + 127 - em) << 23);
  sts32(scr + W_MISC + 16 + (wt >> 5) * 4, __reduce_add_sync(0xffffffffu, __float2int_rn(k.kl * sc * 262144.f)));
  const float2 c0 = make_float2(k.c0.x * sc, k.c0.y * sc);
  const float2 c1 = cmul(c0, k.z8), c2 = cmul(c0, z16), c4 = cmul(c0, z32), c3 = cmul(c1, z16), c5 = cmul(c1, z32), c6 = cmul(c2, z32), c7 = cmul(c3, z32);
  uint32_t pr[4], pi[4], yr[4], yi[4];
  pr[0] = pack_h(c0.x, c1.x); pi[0] = pack_h(c0.y, c1.y);
  pr[1] = pack_h(c2.x, c3.x); pi[1] = pack_h(c2.y, c3.y);
  pr[2] = pack_h(c4.x, c5.x); pi[2] = pack_h(c4.y, c5.y);
  pr[3] = pack_h(c6.x, c7.x); pi[3] = pack_h(c6.y, c7.y);
  sts128(dst, pr[0], pr[1], pr[2], pr[3]); sts128(dst + 2048, pi[0], pi[1], pi[2], pi[3]);
#pragma unroll
  for (int q = 1; q < 4; q++) {
    const uint32_t w = q == 1 ? k.w64 : q == 2 ? k.w128 : k.w192;
#pragma unroll
    for (int i = 0; i < 4; i++) pmul(pr[i], pi[i], w, yr[i], yi[i]);
    sts128(dst + q * 4096, yr[0], yr[1], yr[2], yr[3]); sts128(dst + q * 4096 + 2048, yi[0], yi[1], yi[2], yi[3]);
  }
  return em;
}
__device__ __forceinline__ void kgen_build(uint32_t wb, int wg, int wt, uint32_t k0, uint32_t k1, uint32_t k2) {
  const uint32_t kt = wb + W_KT;
  const bool ev = !(wt & 1), mid = ev && wt;
  const uint32_t a0 = kt + 64 + wt * 8;
  const uint32_t a2 = kt + 64 + 2048 + (wt >> 2) * 32 + (wt & 1) * 16 + (wt & 2) * 512;
  const int ix = ((wt >> 2) + (wt & 3) * 32 - 1) & 127;
  const uint32_t a3 = wb + W_CW + 32 + ((ix & 1) ? 0 : 320) + (ix >> 1) * 4;
  const uint32_t v3 = wt ? k2 : k2 >> 16;
  sts16(a3, v3); sts16(a3 + 6, v3);
  if ((unsigned)(wt - 32) < 18u) sts128(kt + (wt < 36 ? -512 : 64 + 4128 - 576) + wt * 16, 0, 0, 0, 0);
  const uint32_t sw = __byte_perm(k0, 0, 0x1032), d2 = __byte_perm(k1, 0, 0x1010), d3 = __byte_perm(k1, 0, 0x3232);
  sts16(a0, k0); sts32(a0 + 4, sw); sts16(a0 + 10, sw);
  sts16(a0 + 1024 - (mid ? 4 : 0), d2); sts16(a0 + 1024 + (ev ? 10 : 6), d2);
  sts16(a2 - (mid ? 8 : 4), d3); sts64(a2, d3, d3); sts16(a2 + (ev ? 14 : 10), d3);
  if (mid) { sts64(a0 + 1024, d2, d2); sts32(a2 - 4, d3); }
  if (ev) sts32(a2 + 8, d3);
  if (wt == 0) {
    const uint32_t d = __byte_perm(k2, 0, 0x1010);
    sts16(kt + 66, 0); sts32(kt + 64 + 1028, d2);
    sts16(kt + 64 + 4088, d); sts32(kt + 64 + 4092, d); sts128(kt + 64 + 4096, d, d, d, d); sts128(kt + 64 + 4112, d, d << 16, 0, 0);
  }
  bar_sync(1 + wg, 128);
  const uint32_t cw = wb + W_CW + 32 + (wt >> 6) * 64 + wt * 4;
  sts128(wb + W_L3 + 1024 + (wt >> 6) * 1024 + wt * 16, lds32(cw), lds32(cw - 8), lds32(cw - 16), lds32(cw - 24));
}

__device__ __forceinline__ void load_a(uint32_t (&a)[4], uint32_t kp, int j) {
  a[0] = lds32(kp + 64 * j); a[1] = lds32(kp + 64 * j + 512); a[2] = lds32(kp + 64 * j - 32); a[3] = lds32(kp + 64 * j + 480);
}
__device__ __forceinline__ uint32_t band(int d, int lo, int hi) {
  return ((unsigned)(d - lo) <= (unsigned)(hi - lo) ? 1u : 0u) | ((unsigned)(d - 1 - lo) <= (unsigned)(hi - lo) ? 0x10000u : 0u);
}
__device__ __forceinline__ uint32_t hadd2u(uint32_t a, uint32_t b) { __half2 r = __hadd2(*(__half2*)&a, *(__half2*)&b); return *(uint32_t*)&r; }

__device__ __forceinline__ void zero_pads(uint32_t tb, int wt) {
  sts128(tb + W_L3 + (wt >> 6) * 1024 + wt * 16, 0, 0, 0, 0);
  if ((wt & 63) < 3) sts128(tb + W_CW + (wt >> 6) * 320 + (wt & 63) * 16, 0, 0, 0, 0);
}
__device__ __forceinline__ uint32_t tr_base(int lane) {
  return OFF_YT + (2 * (lane >> 3) + (lane & 1)) * YT_PITCH + ((lane >> 1) & 1) * (8 * YT_PITCH + 64) + ((lane >> 2) & 1) * 16;
}

__device__ __forceinline__ uint32_t sc_addr(int tp) { return OFF_YT + (tp < 16 ? tp * YT_PITCH + (tp >> 3) * 64 + 1152 : 8 * YT_PITCH - 512 + tp * 32); }
#define X_NE 3
#define X_NS 3
#define X_SCT 10500
#define X_DELTA 600
#define X_DSTEP 500
#define X_PF0 3000
#define X_PFD 560
#define X_TD 700
#define X_ORD 1
#define X_WS 6
#define X_OR 8
#define X_ABS 5000
#define X_XD 200
#define X_REL 0
#define X_RW 1
#define X_LAG 1600
#define X_YD 600
struct TMaps { CUtensorMap m[8]; };
__device__ __forceinline__ uint32_t h2bf(uint32_t w) { const float2 f = h2f(w); return pack_bf(f.x, f.y); }
__device__ __forceinline__ uint32_t keep(uint32_t v) { asm volatile("" : "+r"(v)); return v; }
__device__ __forceinline__ uint2 ldr64(const void* p) { uint2 v; asm volatile("{ .reg .b64 t; ld.relaxed.gpu.global.b64 t, [%2]; mov.b64 {%0, %1}, t; }" : "=r"(v.x), "=r"(v.y) : "l"(p) : "memory"); return v; }
__host__ __device__ __forceinline__ uint32_t down_box(int s, bool five) {
  return five ? OFF_W + W_BYTES + 12288 + (s / 3) * (W_BYTES - 12288) + s * 4096 : s < 6 ? OFF_W + W_BYTES + BOX + (s >> 1) * (W_BYTES - 10240) + s * 5120 : OFF_W + (s - 6) * 5120;
}
__device__ __forceinline__ void load_tile(const CUtensorMap* tmx, int i, int c) {
  asm volatile("mbarrier.arrive.expect_tx.shared::cta.b64 _, [%0], 5120;" :: "r"(MB_UL + i * 8) : "memory");
  tma_box(OFF_W + (i < 4 ? i * W_BYTES : ALT) + W_UP, tmx, MB_UL + i * 8, (i < 4 ? i * 128 + c : 512 + (c >> 1)) * 16, -32);
}
__device__ __forceinline__ void check_tile(uint32_t tb, const CUtensorMap* tmx, int i, int c, int wg, int wt) {
#pragma unroll 1
  for (int it = 0; it < SPIN_MAX; it++) {
    uint32_t r0, r1, r2, r3, ok;
    mbar_wait(MB_UL + i * 8, it & 1);
    if (it == 0) TS(29);
    if (it == 1) TS(13);
    ldsm4(tb + W_UP + 1024 + wt * 32 + (wt & 4) * 4, r0, r1, r2, r3);
    asm volatile("{ .reg .pred q; setp.ne.u32 q, %1, 0; barrier.red.and.pred q, %2, 128, q; selp.u32 %0, 1, 0, q; }" : "=r"(ok) : "r"((r0 & r1 & r2 & r3 & 1u) | (wt & 3)), "r"(1 + wg) : "memory");
    if (ok) break;
    if (wt == 0) load_tile(tmx, i, c);
  }
}
template <bool FAR> __device__ __forceinline__ void load_params(const Params& p, uint32_t ch, int wt, uint32_t dst) {
  if (wt < 97) {
    const unsigned char* b = FAR ? p.far[wt >> 4] : p.x + (long long)p.off[wt >> 4] * 16;
    asm volatile("cp.async.cg.shared.global [%0], [%1], 16;" :: "r"(dst + wt * 16), "l"(b + (wt < 96 ? ch * 256 + (wt & 15) * 16 : (ch >> 3) * 16)) : "memory");
  }
  asm volatile("cp.async.commit_group;" ::: "memory");
}

struct ConvC { uint32_t ca, cb, bands; };
__device__ __forceinline__ ConvC conv_consts(int w, int lane) {
  const int h = w & 1, P = w >> 1, d0 = 8 * h + (lane >> 2) - 2 * (lane & 3);
  ConvC k;
  k.ca = keep((W_KT + (16 + 256 * P + d0) * 4) | ((W_UP + (32 + 64 * P + lane) * 32 + ((h ^ (lane >> 2)) & 1) * 16) << 16));
  k.cb = keep(lane < 8 ? 0xFFFEFFFEu : ~0u);
  k.bands = keep(band(d0, 12, 20) + 2 * band(d0 + 8, 12, 20) + 4 * band(d0 + 16, 12, 20) + 8 * band(d0 + 24, 12, 20)
                 + 16 * band(d0 - 8, 5, 11) + 32 * band(d0, 5, 11) + 64 * band(d0 + 8, 5, 11) + 128 * band(d0 + 16, 5, 11));
  return k;
}
__device__ __forceinline__ void conv_item(uint32_t tb, const ConvC& cv, uint32_t zero, const CUtensorMap* tmx, int ch, int warp, int lane, bool rel) {
  const uint32_t kp = tb + (cv.ca & 0xFFFFu);
  const uint32_t dlo = ((tb + W_UP) >> 4) + 64 + (1u << 16), dhi = 16u | (3u << 30);
  const bool P = warp & 2;
  float a32[16], a96[48];
  uint32_t A[40][4];
#define STEP(J) { wgmma96<0>(a96, A[J], dlo + 64 - 2 * (J), dhi); if ((J) == 0) wgmma32_init<0>(a32, A[J], dlo, dhi); else if ((J) < 8) wgmma32<0>(a32, A[J], (dlo ^ zero) - 2 * (J), dhi); }
#define LD(J) load_a(A[J], kp, J);
#define FIRST(J) wg_fence(); STEP(J) wg_commit(); wg_wait<1>(); wg_fence();
  {
    uint32_t win[16], x9[4], x7[4], e[4], f[4];
    const uint32_t bz = keep(cv.bands);
#define BAND(i) keep((bz & (0x10001u << (i))) * (0x3C00u >> (i)))
    e[0] = lds32(kp + (P ? 3232 : 4096)); e[2] = lds32(kp + (P ? 3200 : 4064)); e[1] = keep(bz & 0x100u); e[3] = keep(bz & 0x200u);
    f[3] = lds32(kp + (P ? 3200 : 4128)); f[0] = keep(bz & 0x4000u); f[1] = keep(bz & 0x8000u); f[2] = keep(bz & 0x300u);
    const uint32_t q[12] = {BAND(0), BAND(5), keep(bz & 0x400u), BAND(4), BAND(2), BAND(7), BAND(1), BAND(6), keep(bz & 0x800u), keep(bz & 0x1000u), BAND(3), keep(bz & 0x2000u)};
#undef BAND
    if (ch < 512) check_tile(tb, tmx - 1, warp >> 2, ch & 127, warp >> 2, (warp & 3) * 32 + lane);
    TS(3);
    wg_fence();
    wgmma64h_init(win, q[0], q[1], q[2], q[3], dlo, dhi);
    wgmma64h(win, q[4], q[5], q[6], q[7], dlo - 2, dhi);
    wgmma64h(win, q[8], q[9], q[10], q[11], dlo - 4, dhi);
    wg_commit();
    wgmma96_init<0>(a96, e, dlo - 64, dhi);
    wgmma96<0>(a96, f, dlo - 50, dhi);
    wg_commit();
    wg_wait<1>();
#pragma unroll
    for (int i = 0; i < 4; i++) {
      const int tl = 2 * ((i & 1) + ((i & 2) ? 0 : 4));
      x9[i] = P ? win[tl + 4] : win[tl]; x7[i] = P ? win[tl + 5] : win[tl + 1];
    }
    const uint32_t l3lo = ((tb + W_L3) >> 4) + (32u << 16);
    wg_fence();
    wgmma96<0>(a96, x9, l3lo, 8);
    wgmma96<0>(a96, x7, l3lo + 128, 8);
    wg_commit();
  }
  LD(32) LD(33) LD(34) LD(35)
  FIRST(32) STEP(33) STEP(34) STEP(35) wg_commit();
  LD(36) LD(37) LD(38)
  FIRST(36) STEP(37) STEP(38) wg_commit();
  LD(39) LD(0)
  TS(17);
  if (X_REL == 1 && rel) bar_arrive(6, 640 - 128 * X_RW);
  FIRST(39) STEP(0) wg_commit();
  LD(1) LD(2) LD(3)
  FIRST(1) STEP(2) STEP(3) wg_commit();
  LD(4) LD(5)
  if (X_REL == 2 && rel) bar_arrive(6, 640 - 128 * X_RW);
  FIRST(4) STEP(5) wg_commit();
  LD(6) LD(7)
  wg_fence(); STEP(6) STEP(7) wg_commit();
#undef STEP
#undef LD
#undef FIRST
  TS(18);
  if (X_REL == 3 && rel) bar_arrive(6, 640 - 128 * X_RW);
  const uint32_t xc = tb + W_KT + (warp & 3) * 1024 + lane * 16;
  wg_wait<0>();
  uint32_t E[16], o[8];
#define ACC(i) ((i) < 16 ? a32[i] : a96[(i) - 16])
  E[0] = pack_h(a32[0], a32[1]);
#pragma unroll
  for (int i = 1; i < 16; i++) E[i] = pack_h(ACC(4 * i) + ACC(4 * i - 2), ACC(4 * i + 1) + ACC(4 * i - 1));
#undef ACC
#pragma unroll
  for (int j = 0; j < 8; j++) o[j] = P ? (j < 2 ? 0u : E[j - 2]) : E[8 + j];
  sts128(xc, o[0], o[1], o[2], o[3]); sts128(xc + 512, o[4], o[5], o[6], o[7]);
#pragma unroll
  for (int j = 0; j < 8; j++) o[j] = P ? E[6 + j] : E[j];
  TS(25);
  bar_sync(1 + (warp >> 2), 128);
#pragma unroll
  for (int q = 0; q < 2; q++) {
    const uint4 v = lds128(xc + (P ? -2048 : 2048) + q * 512);
    stsm4t(tb + (cv.ca >> 16) + q * 1024, hadd2u(o[4 * q], v.x) & cv.cb, hadd2u(o[4 * q + 1], v.y) & cv.cb, hadd2u(o[4 * q + 2], v.z) & cv.cb, hadd2u(o[4 * q + 3], v.w) & cv.cb);
  }
  fence_async();
  bar_sync(1 + (warp >> 2), 128);
  if ((warp & 3) == 3 && lane == 0) {
    asm volatile("cp.async.bulk.tensor.2d.global.shared::cta.bulk_group [%0, {%2, %3}], [%1];" :: "l"(tmx), "r"(tb + W_UP + 1024), "r"(ch * 16), "r"(0) : "memory");
    asm volatile("cp.async.bulk.commit_group;" ::: "memory");
  }
}

template <bool FAR> __global__ void __launch_bounds__(NT, 1)
fused_kernel(const __grid_constant__ Params p, const __grid_constant__ TMaps tm) {
  extern __shared__ __align__(1024) unsigned char smem[];
  const int c = blockIdx.x;
  const bool five = (c & 1) == 0;
  const uint32_t pitch = five ? 64 : 80;
  const uint32_t ones = 0x3F803F80u;
  const int tid = threadIdx.x, lane = tid & 31;
  const int warp = (int)uni(tid >> 5), wg = warp >> 2;
  TS(0);
  if (__builtin_expect(wg == 4, 0)) {
    asm volatile("setmaxnreg.dec.sync.aligned.u32 32;");
    const int role = warp;
    const int u0 = (c >> 1) * 9 + (five ? ((c & 2) ? 5 : 0) : ((c & 2) ? 0 : 4));
    const uint32_t t0 = clock() + c * 4;
    if (role < 18) {
      const bool pf = role == 17;
      if (!pf) {
        if (lane < 19) asm volatile("mbarrier.init.shared::cta.b64 [%0], %1;" :: "r"(OFF_MISC + lane * 8), "r"((unsigned)(lane - 2) < 4u ? 4 : 1) : "memory");
        if (lane < 2) asm volatile("mbarrier.arrive.expect_tx.shared::cta.b64 _, [%0], %1;" :: "r"(OFF_MISC + lane * 8), "r"(lane ? (five ? 36864 : 51200) : pitch * 1152) : "memory");
        fence_async();
        bar_arrive(5, 576);
      } else if (smem_u32(smem) != SB) __trap();
      const CUtensorMap* tmb = &tm.m[five ? 3 : 0];
#pragma unroll 1
      for (int u = pf ? X_NE : 0; u < 17; u++) {
        const uint32_t e = p.sched[five][u], kind = e & 3, s = (e >> 2) & 15, dst = e >> 14;
        if (kind == 3) continue;
        while ((int)(clock() - t0) < X_PF0 + (pf || u < X_NE ? u * X_PFD : X_LAG + u * X_TD)) __nanosleep(20);
        if (!pf && (e & 0x3FC0)) mbar_wait(OFF_MISC + ((e >> 6) & 255));
        if (lane == 0) {
          if (pf) {
            if (kind == 2) asm volatile("cp.async.bulk.prefetch.tensor.3d.L2.global [%0, {%1, %2, %3}];" :: "l"(tmb + 2), "r"(0), "r"(u0 * 8), "r"(s) : "memory");
            else l2_prefetch((kind ? p.w_up : p.w_gate) + (uint32_t)(s * 884736 + c * 6912), 6912);
          } else if (kind == 2) asm volatile("cp.async.bulk.tensor.3d.shared::cluster.global.mbarrier::complete_tx::bytes [%0], [%1, {%3, %4, %5}], [%2];"
                                             :: "r"(dst), "l"(tmb + 2), "r"(MB_D), "r"(0), "r"(u0 * 8), "r"(s) : "memory");
          else tma_box(dst, tmb + kind, MB_GU, u0 * 8, s * 96);
        }
        if (u == 5) TS(2);
        if (u == 10) TS(3);
      }
      TS(4);
      TS_DUMP();
    } else if (role == 18) {
      sts32(MISC_EPOCH, 0);
      bar_arrive(5, 576);
      uint4* q = lane < 2 ? &p.s->R[c * 2 + lane] : lane < 11 ? &p.s->HS[c * 9 + lane - 2] : lane == 11 ? &p.s->HS[1152 + (c & 7)] : (uint4*)&p.s->FLAG[c * 8];
      if (lane < (c < 8 ? 12 : 11)) str128(q, ~0u, ~0u, ~0u, ~0u);
      const uint32_t ep = __shfl_sync(0xffffffffu, ldr32(q), 31) + 1u;
      sts32(MISC_EPOCH, ep | 0x80000000u);
      TSX(21);
      if (lane == 31) str32(q, ep);
      bar_sync(11, 64);
      if (lane == 0) { load_tile(&tm.m[6], 1, c); load_tile(&tm.m[6], 3, c); }
      TSX(14);
      mbar_wait(MB_KF + (lane & 3) * 8);
      __syncwarp();
      { const uint2 e = lds64(MISC_EM); if (lane < 2) str128(&p.s->SC[c * 2 + lane], e.x, __byte_perm(e.y, ep, 0x6540), 0, 0); }
      while ((int)(clock() - t0) < X_SCT) __nanosleep(100);
      {
        uint2 v[4];
#pragma unroll 1
        for (int it = 0; it < SPIN_MAX; it++) {
          uint32_t bad = 0;
#pragma unroll
          for (int q = 0; q < 4; q++) v[q] = ldr64(&p.s->SC[lane * 2 + q * 64]);
#pragma unroll
          for (int q = 0; q < 4; q++) bad |= (v[q].y >> 8) ^ (ep & 0xFFFFFFu);
          if (!__any_sync(0xffffffffu, bad)) break;
        }
#pragma unroll
        for (int q = 0; q < 4; q++) {
#pragma unroll
          for (int k = 0; k < 4; k++) asm volatile("st.shared.u8 [%0], %1;" :: "r"(sc_addr(4 * k + q) + lane), "r"(v[q].x >> (8 * k)) : "memory");
          if (lane & 1) asm volatile("st.shared.u8 [%0], %1;" :: "r"(sc_addr(16) + q * 16 + (lane >> 1)), "r"(v[q].y) : "memory");
        }
      }
      __syncwarp();
      if (lane == 0) mbar_arrive(MB_SC);
    } else {
      uint32_t w[9], d[9];
      float s = 0.f;
#pragma unroll
      for (int i = 0; i < 9; i++) { w[i] = ldnc32(p.w_r + lane + 32 * i); d[i] = ldnc32(p.dskip + lane + 32 * i); }
#pragma unroll
      for (int i = 0; i < 9; i++) { sts32(OFF_WR + lane * 4 + i * 128, w[i]); sts32(OFF_WR + 1152 + lane * 4 + i * 128, d[i]); s += bf_lo(w[i]) + bf_hi(w[i]); }
      sts32(MISC_SW, __float_as_uint(warp_sum(s)));
      TSX(23);
      bar_sync(10, 544);
      if (lane == 0) {
        const uint32_t tp = clock();
        TSX(1);
        while ((int)(clock() - tp) < X_DELTA || (int)(clock() - t0) < X_ABS - c * 4) {}
        TSX(24);
        load_tile(&tm.m[6], 0, c);
        TSX(15);
        while ((int)(clock() - t0) < X_ABS + X_DSTEP - c * 4) {}
      }
      bar_sync(11, 64);
      if (lane == 0) {
        load_tile(&tm.m[6], 2, c);
        mbar_arrive(MB_GF);
        if (five) { mbar_wait(MB_KF); load_tile(&tm.m[6], 4, c); }
      }
    }
    return;
  }
  const int wt = tid & 127, g = lane >> 2, t = lane & 3;
  const uint32_t wb = OFF_W + wg * W_BYTES;
  const int lw = warp - (five ? 8 : 4);
  if ((unsigned)lw < 8u) {
    const unsigned char* xp = p.x + (uint32_t)((c * 8 + lw) * 2304 + lane * 16);
    const uint32_t row = OFF_YT + lw * (2 * YT_PITCH) + (lw >> 2) * 64 + lane * 16;
    { const uint32_t tq = clock(); while ((int)(clock() - tq) < X_XD) {} }
#pragma unroll
    for (int k = 0; k < 5; k++)
      if (k < 4 || lane < 16)
        asm volatile("cp.async.cg.shared.global [%0], [%1], 16;" :: "r"(row + k * 512 + ((k > 2 || (k == 2 && lane >= 8)) ? 32 : 0)), "l"(xp + k * 512) : "memory");
    asm volatile("cp.async.commit_group;" ::: "memory");
  } else load_params<FAR>(p, lw >= 8 ? 512 + (c >> 1) : wg * 128 + c, wt, wb + W_KT + (lw >= 8) * 2048);
  const ConvC cv = conv_consts(warp & 3, lane);
  zero_pads(wb, wt);
  if (lw >= 0) load_params<FAR>(p, wg * 128 + c, wt, wb + W_KT);
  asm volatile("setmaxnreg.inc.sync.aligned.u32 112;");
  {
    uint4 kw;
    uint4* kx = &p.s->KX[(c >> 1) * 128 + wt];
    bool two = wg == 3;
    uint32_t ep;
    int phase = (unsigned)lw < 8u ? 3 : 2;
#pragma unroll 1
    for (;;) {
      const bool first = two && !five;
      if (first || phase == 3) asm volatile("cp.async.wait_group 1;" ::: "memory"); else asm volatile("cp.async.wait_group 0;" ::: "memory");
      if (phase == 3) {
        __syncwarp();
        TS(21);
        float d[4][4];
#pragma unroll
        for (int r = 0; r < 2; r++) {
          const uint32_t row = OFF_YT + (2 * lw + r) * YT_PITCH + (lw >> 2) * 64;
          const uint4 a = lds128(row + lane * 16), b = lds128(row + 512 + lane * 16);
          const uint32_t e = lds32(row + 1024 + lane * 4);
#pragma unroll
          for (int i = 0; i < 4; i++) d[r][i] = d[r + 2][i] = 0.f;
          mma_bf16(d[r], a.x, ones, a.y, ones, a.x, a.y); mma_bf16(d[r + 2], a.z, ones, a.w, ones, a.z, a.w);
          mma_bf16(d[r], b.x, ones, b.y, ones, b.x, b.y); mma_bf16(d[r + 2], b.z, ones, b.w, ones, b.z, b.w);
          mma_bf16_k8(d[r], e, ones, e);
#pragma unroll
          for (int i = 0; i < 4; i++) d[r][i] += d[r + 2][i];
        }
        const float q0 = __shfl_sync(0xffffffffu, d[0][0], 9 * t) + __shfl_sync(0xffffffffu, d[0][1], 9 * t + 4);
        const float q1 = __shfl_sync(0xffffffffu, d[1][0], 9 * t) + __shfl_sync(0xffffffffu, d[1][1], 9 * t + 4);
        float r;
        const LnC lc = ln_consts(quad_sum(lane & 16 ? d[1][2] + d[1][3] : d[0][2] + d[0][3]), quad_sum(lane & 16 ? q1 : q0), r);
        if ((lane & 15) < 3) sts16(MISC_LN1 + (lane & 15) * 32 + lw * 4 + (lane >> 4) * 2, t == 0 ? lc.m2 : t == 1 ? lc.rh2 : lc.rl2);
      } else {
        KgState ks;
        uint32_t raw[7];
        bar_sync(1 + wg, 128);
        TS(22);
#pragma unroll
        for (int i = 0; i < 7; i++) raw[i] = lds16(wb + W_KT + first * 2048 + i * 256 + (i < 6 ? wt : (c >> first) & 7) * 2);
        kgen_tables_n(raw, wb, wt, ks);
        TS(20);
        bar_sync(1 + wg, 128);
        const int em = kgen_tables_m(wb, wt, ks);
        asm volatile("st.shared.u8 [%0], %1;" :: "r"(MISC_EM + wg + first), "r"(em + 9) : "memory");
        fence_async();
      }
      if (phase & 2) {
        const uint32_t tr_addr = tr_base(lane) + warp * 32;
        uint4* dst = &p.s->X[c * DM * 2 + warp * 32 + (8 * (t >> 1) + g) * 2 + (t & 1)];
        TS(23);
        bar_sync(5, 576);
        uint32_t x[3][4];
        ldsm4t(tr_addr, x[0][0], x[0][1], x[0][2], x[0][3]);
        const uint4 m = lds128(MISC_LN1 + (t & 1) * 16), rl = lds128(MISC_LN1 + 64 + (t & 1) * 16), rh = lds128(MISC_LN1 + 32 + (t & 1) * 16);
        ldsm4t(tr_addr + 512, x[1][0], x[1][1], x[1][2], x[1][3]);
        if (wg == 2) ldsm4t(tr_addr + 768, x[2][0], x[2][1], x[2][2], x[2][3]);
#pragma unroll
        for (int q = 0; q < 3; q++) {
          if (q < 2 || wg == 2) {
            const uint32_t r0 = ln_apply(x[q][0], m.x, rh.x, rl.x), r1 = ln_apply(x[q][1], m.y, rh.y, rl.y), r2 = ln_apply(x[q][2], m.z, rh.z, rl.z), r3 = ln_apply(x[q][3], m.w, rh.w, rl.w);
            str128(dst + q * 512 - (q == 2 ? 256 : 0), (pack_h(bf_lo(r0), bf_hi(r0)) & 0xFFFEFFFEu) | 1u, pack_h(bf_lo(r1), bf_hi(r1)), pack_h(bf_lo(r2), bf_hi(r2)), pack_h(bf_lo(r3), bf_hi(r3)));
          }
          if (q == 0) TS(30);
        }
        bar_arrive(10, 544);
        TS(1);
      } else bar_sync(1 + wg, 128);
      phase &= 1;
      if (phase) { phase = 0; continue; }
      TS(14);
      float acc[20];
      const uint32_t alo = (wb >> 4) | (8u << 16);
      wg_fence();
      wgmma40_ss_init(acc, alo, alo + 1024, 2048 >> 4);
#pragma unroll
      for (int k = 1; k < 8; k++) wgmma40_ss(acc, alo + k * 16, alo + 1024 + k * 16, 2048 >> 4);
      wg_commit();
      if (two && five) {
        asm volatile("cp.async.cg.shared.global [%0], [%1], 16;" :: "r"(OFF_K5 + wt * 16), "l"(kx) : "memory");
        asm volatile("cp.async.commit_group;" ::: "memory");
      }
      const uint4 k4 = lds128(wb + W_MISC + 16);
      const float k2048 = (float)(int)(k4.x + k4.y + k4.z + k4.w) * (1.f / 262144.f);
      wg_wait<0>();
      const float un = 1.f / 8192.f;
      kw.x = pack_h((acc[0] - acc[3]) * un, (acc[4] - acc[7]) * un);
      kw.y = pack_h((acc[8] - acc[11]) * un, (acc[12] - acc[15]) * un);
      kw.z = pack_h((acc[16] - acc[19]) * un, k2048 * un);
      TS(24);
      ep = 0;
      if (two) SPIN_WHILE(ep == 0, ep = lds32(MISC_EPOCH));
      if (five || !two) break;
      str128(kx, kw.x, kw.y, kw.z, ep);
      two = false;
    }
    if (lane == 0) mbar_arrive(MB_KF + wg * 8);
    if (two) { mbar_wait(MB_KF); zero_pads(OFF_W + ALT, wt); }
    uint32_t tb = wb;
#pragma unroll 1
    for (;;) {
      kgen_build(tb, wg, wt, kw.x, kw.y, kw.z);
      TS(15);
      if (!two) break;
      two = false;
      asm volatile("cp.async.wait_group 0;" ::: "memory");
      kw = lds128(OFF_K5 + wt * 16);
      SPIN_WHILE(kw.w != ep, kw = ldr128(kx));
      tb = OFF_W + ALT;
    }
    fence_async();
    TS(31);
    if (tb != wb) { check_tile(tb, &tm.m[6], 4, c, wg, wt); bar_arrive(7, 256); } else bar_sync(1 + wg, 128);
  }
  uint32_t tpub;
#pragma unroll 1
  for (int item = 0;; item++) {
    if (X_REL && five && wg >= X_RW) bar_sync(6, 640 - 128 * X_RW);
    TS(2);
    conv_item(item ? OFF_W + ALT : wb, cv, p.zero, &tm.m[7], item ? 512 + (c >> 1) : wg * 128 + c, warp, lane, five && !wg && !item);
    tpub = clock() - item * X_YD;
    if (wg || !five || item) break;
    TS(27);
    bar_sync(7, 256);
  }
  TS(4);

  const int tok = c * 16 + warp;
  const uint32_t row = OFF_YT + warp * YT_PITCH + (warp >> 3) * 64;
  const int fu = warp / 3, fk = warp - fu * 3;
  uint32_t wa[12][4];
  {
    uint32_t hw[9], wr[9];
    {
      const uint4 m = lds128(MISC_LN1 + (t & 1) * 16), rh = lds128(MISC_LN1 + 32 + (t & 1) * 16), rl = lds128(MISC_LN1 + 64 + (t & 1) * 16);
      mbar_wait(MB_SC);
#pragma unroll 1
      for (int tp = warp;; tp += 12) {
        const int ch = tp * 32 + 8 * (t >> 1) + g;
        const uint32_t tr_addr = tr_base(lane) + tp * 64;
        const uint4* ysrc = &p.s->X[c * DM * 2 + ch * 2 + (t & 1)];
        uint32_t x[2][4], ud[2][4], s[2];
#pragma unroll
        for (int q = 0; q < 2; q++) {
          asm volatile("ld.shared.u8 %0, [%1];" : "=r"(s[q]) : "r"(sc_addr(tp) + (ch & 31) + q * 16) : "memory");
          s[q] *= 0x800080u;
          const uint32_t dk = lds16(OFF_WR + 1152 + ch * 2 + q * 32) * 0x10001u;
          ldsm4t(tr_addr + q * 32, x[q][0], x[q][1], x[q][2], x[q][3]);
          ud[q][0] = bf_mul2(ln_apply(x[q][0], m.x, rh.x, rl.x), dk); ud[q][1] = bf_mul2(ln_apply(x[q][1], m.y, rh.y, rl.y), dk);
          ud[q][2] = bf_mul2(ln_apply(x[q][2], m.z, rh.z, rl.z), dk); ud[q][3] = bf_mul2(ln_apply(x[q][3], m.w, rh.w, rl.w), dk);
        }
        while ((int)(clock() - tpub) < X_YD) {}
        TS(5);
        uint4 v[2];
        v[0] = ldr128(ysrc); v[1] = ldr128(ysrc + 32);
        SPIN_WHILE((v[0].x | v[1].x) & 1u, if (v[0].x & 1u) v[0] = ldr128(ysrc); if (v[1].x & 1u) v[1] = ldr128(ysrc + 32));
#pragma unroll
        for (int q = 0; q < 2; q++) {
          const uint32_t s2 = s[q];
          stsm4t(tr_addr + q * 32, bf_add2(x[q][0], bf_fma2(h2bf(v[q].x), s2, ud[q][0])), bf_add2(x[q][1], bf_fma2(h2bf(v[q].y), s2, ud[q][1])),
                 bf_add2(x[q][2], bf_fma2(h2bf(v[q].z), s2, ud[q][2])), bf_add2(x[q][3], bf_fma2(h2bf(v[q].w), s2, ud[q][3])));
        }
        if ((tp & ~1) != 4) break;
      }
    }
#pragma unroll
    for (int i = 0; i < 9; i++) wr[i] = lds32(OFF_WR + lane * 4 + i * 128);
    const float sw = __uint_as_float(lds32(MISC_SW));
    asm volatile("cp.async.bulk.wait_group.read 0;" ::: "memory");
    TS(28);
    bar_sync(0, 512);
    if (tid == 0) mbar_arrive(MB_H);
    TS(6);
    float d[4] = {0.f, 0.f, 0.f, 0.f}, e[4] = {0.f, 0.f, 0.f, 0.f}, rd;
#pragma unroll
    for (int i = 0; i < 9; i++) hw[i] = lds32(row + lane * 4 + i * 128);
#pragma unroll
    for (int i = 0; i < 8; i += 2) {
      mma_bf16(d, hw[i], wr[i], hw[i + 1], wr[i + 1], hw[i], hw[i + 1]);
      mma_bf16(e, ones, ones, ones, ones, hw[i], hw[i + 1]);
    }
    mma_bf16_k8(d, hw[8], wr[8], hw[8]);
    mma_bf16_k8(e, ones, ones, hw[8]);
    const float hwsum = diag_sum(d[2], d[3], t);
    LnC l2 = ln_consts(quad_sum(e[0] + e[1]), diag_sum(d[0], d[1], t), rd);
    const uint32_t b = pack_bf(fmaf(-bf_lo(l2.m2), sw, hwsum) * rd, 0.f);
    uint32_t key = max(min((b & 0x8000u) ? (~b & 0xFFFFu) : (b | 0x8000u), 0xFFFEu), 1u);
    if (lane == 0) sts16(MISC_RK + warp * 2, key);
    bar_sync(5, 512);
    if (tid >= 510) { const uint4 k = lds128(MISC_RK + (tid & 1) * 16); str128(&p.s->R[c * 2 + (tid & 1)], k.x, k.y, k.z, k.w); }
    asm volatile("" : "+r"(l2.m2) :: "memory");
    TS(7);
    key = (key << 16) | (2047 - tok);
    uint32_t loc = lane < 16 ? (lds16(MISC_RK + lane * 2) << 16) | (2047 - c * 16 - lane) : 0u;
    int rank = __popc(__ballot_sync(0xffffffffu, loc > key));
    const uint32_t wabase = ((lane & 8) ? OFF_W + (fk + 1) * W_BYTES : OFF_G + fk * 192 * pitch) + ((lane >> 4) * 8 + (lane & 7)) * pitch
                            + (five ? ((fu ^ (lane >> 1)) & 3) : min(fu, 4)) * 16;
    mbar_wait(MB_GU);
    if (warp < (five ? 12 : 15)) {
#pragma unroll
      for (int k = 0; k < X_WS; k++) ldsm4t(wabase + k * 16 * pitch, wa[k][0], wa[k][1], wa[k][2], wa[k][3]);
    }
#pragma unroll
    for (int i = 0; i < 9; i++) {
      wr[i] = keep(ln_apply(hw[i], l2.m2, l2.rh2, l2.rl2));
    }
#define OUT_ROW { _Pragma("unroll") for (int i = 0; i < 9; i++) sts32(row + lane * 4 + i * 128, bf_add2(hw[i], wr[i])); fence_async(); __syncwarp(); if (lane == 0) { \
      asm volatile("cp.async.bulk.global.shared::cta.bulk_group [%0], [%1], 1152;" :: "l"(p.out + tok * 288), "r"(row) : "memory"); \
      asm volatile("cp.async.bulk.commit_group;" ::: "memory"); } }
#undef OUT_ROW
#define OUT_ROW { _Pragma("unroll") for (int i = 0; i < 9; i++) p.out[tok * 288 + lane + 32 * i] = bf_add2(hw[i], wr[i]); }
    if (rank >= X_OR) OUT_ROW
    uint2 rv = make_uint2(~0u, 0u);
#pragma unroll 1
    for (int base = 0; base < 8; base += 4) {
      uint32_t T[4];
#pragma unroll
      for (int j = 0; j < 4; j++) {
        const uint32_t mx = __reduce_max_sync(0xffffffffu, loc);
        if (loc == mx) loc = 0;
        T[j] = (tid >> 2) == c ? ~0u : (tid >> 2) < c ? (mx & 0xFFFF0000u) - 1u : mx | 0xFFFFu;
      }
      SPIN_WHILE(rv.x == ~0u, if (rv.x == ~0u) rv = ldr64((const uint2*)p.s->R + tid));
      TS(16);
      uint32_t cnt = 0;
#pragma unroll
      for (int j = 0; j < 4; j++) cnt += ((rv.x > T[j]) + ((rv.x << 16) > T[j]) + (rv.y > T[j]) + ((rv.y << 16) > T[j])) << (8 * j);
      cnt = __reduce_add_sync(0xffffffffu, cnt);
      if (lane == 0) sts32(MISC_CNT + base * 16 + warp * 4, cnt);
      bar_sync(0, 512);
      cnt = lds32(MISC_CNT + base * 16 + (lane & 15) * 4);
      cnt = __reduce_add_sync(0xffffffffu, lane < 16 ? (cnt >> (8 * (rank & 3))) & 255u : (cnt >> 24) << 16);
      if ((rank & ~3) == base && rank + (int)(cnt & 0xFFFFu) < 8) {
        rank += cnt & 0xFFFFu;
        uint32_t* hs = (uint32_t*)p.s->HS + rank * 288 + lane;
#pragma unroll
        for (int r = 0; r < 9; r++) str32(hs + 32 * r, wr[r]);
#pragma unroll
        for (int r = 0; r < 9; r++) str32(hs + 2304 + 32 * r, hw[r]);
        if (lane == 0) str32(&p.s->HS[1152 + rank], key);
        rank = 16;
      }
      if (cnt >= (4u << 16)) break;
    }
    TS(8);
    if (rank < X_OR) OUT_ROW
    if (warp < (five ? 12 : 15)) {
#pragma unroll
      for (int k = X_WS; k < 12; k++) ldsm4t(wabase + k * 16 * pitch, wa[k][0], wa[k][1], wa[k][2], wa[k][3]);
    }
  }
  uint32_t wd[10][4];
  if (warp >= 7) {
    const uint32_t db = down_box(warp - 7, five) + (lane & 7) * 128;
    mbar_wait(MB_D);
#pragma unroll
    for (int j = 0; j < 4; j++) {
      const uint32_t a = db + (lane >> 4) * 1024 + (((2 * j + ((lane >> 3) & 1)) ^ (lane & 7)) << 4);
      ldsm4t(a, wd[j][0], wd[j][1], wd[j][2], wd[j][3]);
      ldsm4t(a + 2048, wd[4 + j][0], wd[4 + j][1], wd[4 + j][2], wd[4 + j][3]);
    }
#pragma unroll
    for (int j = 0; j < 2; j++) ldsm4t(db + 4096 + (((4 * j + (lane >> 3)) ^ (lane & 7)) << 4), wd[8 + j][0], wd[8 + j][1], wd[8 + j][2], wd[8 + j][3]);
  } else if (warp < 6) {
    const uint4* src = &p.s->HS[tid];
    uint4 a[3];
    TS(19);
#pragma unroll 1
    for (int it = 0; it < SPIN_MAX; it++) {
      uint32_t m = 0;
#pragma unroll
      for (int q = 0; q < 3; q++) a[q] = ldr128(src + q * 192);
#pragma unroll
      for (int q = 0; q < 3; q++) m = max(max(m, max(a[q].x, a[q].y)), max(a[q].z, a[q].w));
      if (!__any_sync(0xffffffffu, m == ~0u)) break;
    }
#pragma unroll
    for (int q = 0; q < 3; q++) sts128(OFF_XS + (tid + q * 192 + (tid + q * 192) / 72) * 16, a[q].x, a[q].y, a[q].z, a[q].w);
  }
  bar_sync(0, 512);
  TS(9);

  if (warp < (five ? 12 : 15)) {
    float d0[4] = {0.f, 0.f, 0.f, 0.f}, d1[4] = {0.f, 0.f, 0.f, 0.f};
    const uint32_t xb = OFF_XS + (lane & 7) * 1168 + (fk * 24 + (lane >> 3)) * 16;
#pragma unroll
    for (int k = 0; k < 12; k += 2) {
      uint32_t b0, b1, b2, b3;
      ldsm4(xb + k * 32, b0, b1, b2, b3);
      mma_bf16(d0, wa[k][0], wa[k][1], wa[k][2], wa[k][3], b0, b1);
      mma_bf16(d1, wa[k + 1][0], wa[k + 1][1], wa[k + 1][2], wa[k + 1][3], b2, b3);
    }
    sts128(OFF_RED + tid * 16, __float_as_uint(d0[0] + d1[0]), __float_as_uint(d0[1] + d1[1]), __float_as_uint(d0[2] + d1[2]), __float_as_uint(d0[3] + d1[3]));
  }
  TS(26);
  if (warp < 5) {
    bar_sync(9, 512);
    const uint32_t rb = OFF_RED + warp * 1536 + lane * 16;
    const uint4 pa = lds128(rb), pb = lds128(rb + 512), pc = lds128(rb + 1024);
    const float ga = bfr(__uint_as_float(pa.x) + __uint_as_float(pb.x) + __uint_as_float(pc.x));
    const float gb = bfr(__uint_as_float(pa.y) + __uint_as_float(pb.y) + __uint_as_float(pc.y));
    const uint32_t uu = pack_bf(__uint_as_float(pa.z) + __uint_as_float(pb.z) + __uint_as_float(pc.z), __uint_as_float(pa.w) + __uint_as_float(pb.w) + __uint_as_float(pc.w));
    float ra, rb2;
    asm("rcp.approx.ftz.f32 %0, %1;" : "=f"(ra) : "f"(1.f + ex2(ga * -1.4426950408889634f)));
    asm("rcp.approx.ftz.f32 %0, %1;" : "=f"(rb2) : "f"(1.f + ex2(gb * -1.4426950408889634f)));
    const uint32_t act = bf_mul2(pack_bf(ga * ra, gb * rb2), uu);
    sts32(OFF_ACT + tid * 4, act);
    bar_arrive(8, 14 * 32);
  } else {
    bar_arrive(9, 512);
    if (warp >= 7) {
      uint4* dst = &p.s->X[c * DM * 2 + (warp - 7) * 64 + t * 8 + g];
      bar_sync(8, 14 * 32);
      uint32_t b0, b1, b2, b3, b4;
      ldsm4t(OFF_ACT + lane * 16, b0, b1, b2, b3);
      asm volatile("ldmatrix.sync.aligned.m8n8.x1.trans.shared.b16 {%0}, [%1];" : "=r"(b4) : "r"(OFF_ACT + 512 + lane * 16) : "memory");
      float y[4][4];
#pragma unroll
      for (int j = 0; j < 4; j++) {
        y[j][0] = y[j][1] = y[j][2] = y[j][3] = 0.f;
        mma_bf16(y[j], wd[j][0], wd[j][1], wd[j][2], wd[j][3], b0, b1);
      }
#pragma unroll
      for (int j = 0; j < 4; j++) mma_bf16(y[j], wd[4 + j][0], wd[4 + j][1], wd[4 + j][2], wd[4 + j][3], b2, b3);
      if (!five) {
#pragma unroll
        for (int j = 0; j < 4; j++) mma_bf16_k8(y[j], wd[8 + (j >> 1)][2 * (j & 1)], wd[8 + (j >> 1)][2 * (j & 1) + 1], b4);
      }
      str128(dst, (pack_bf(y[0][0], y[0][1]) & ~1u) | 0x10000u, pack_bf(y[0][2], y[0][3]), pack_bf(y[1][0], y[1][1]), pack_bf(y[1][2], y[1][3]));
      str128(dst + 32, (pack_bf(y[2][0], y[2][1]) & ~1u) | 0x10000u, pack_bf(y[2][2], y[2][3]), pack_bf(y[3][0], y[3][1]), pack_bf(y[3][2], y[3][3]));
    }
  }
  TS(10);

  if (c < 72) {
    const uint4* src = &p.s->X[(warp * 4 + t) * (DM * 2) + c * 8 + g];
    const int slot = (c & 3) * 2 + (lane >> 4), dw = (c >> 2) * 16 + (lane & 15);
    uint32_t hv = 0, kv = 0, res = 0;
    float rs = 0.f;
    if (warp == 0) {
      hv = ~0u;
      SPIN_WHILE(max(hv, kv) == ~0u, hv = ldr32((const uint32_t*)p.s->HS + 2304 + slot * 288 + dw); kv = ldr32(&p.s->HS[1152 + slot]));
      const uint32_t k16 = kv >> 16;
      const float r = bf_lo((k16 & 0x8000u) ? (k16 & 0x7FFFu) : (~k16 & 0xFFFFu));
      asm("rcp.approx.ftz.f32 %0, %1;" : "=f"(rs) : "f"(1.f + ex2(r * -1.4426950408889634f)));
      res = lds32(OFF_XS + slot * 1168 + dw * 4);
    }
    const uint32_t sel = (g & 1) ? 0x3F800000u : 0x00003F80u;
    const uint32_t q0 = keep((g >> 1) == 0 ? sel : 0u), q1 = keep((g >> 1) == 1 ? sel : 0u), q2 = keep((g >> 1) == 2 ? sel : 0u), q3 = keep((g >> 1) == 3 ? sel : 0u);
    uint4 a0 = make_uint4(0, 0, 0, 0), a1 = a0;
    SPIN_WHILE(!(a0.x & a1.x & 0x10000u), if (!(a0.x & 0x10000u)) a0 = ldr128(src); if (!(a1.x & 0x10000u)) a1 = ldr128(src + 64 * DM * 2));
    float d[4] = {0.f, 0.f, 0.f, 0.f}, e[4] = {0.f, 0.f, 0.f, 0.f};
    mma_bf16(d, q0, 0u, q1, 0u, a0.x, a0.y); mma_bf16(e, q2, 0u, q3, 0u, a0.z, a0.w);
    mma_bf16(d, q0, 0u, q1, 0u, a1.x, a1.y); mma_bf16(e, q2, 0u, q3, 0u, a1.z, a1.w);
    sts64(OFF_FIN + warp * 256 + (g & 1) * 128 + (g >> 1) * 32 + t * 8, __float_as_uint(d[0] + e[0]), __float_as_uint(d[1] + e[1]));
    TS(11);
    if (warp == 0) {
      bar_sync(0, 512);
      float2 s[16];
#pragma unroll
      for (int i = 0; i < 16; i++) { const uint2 q = lds64(OFF_FIN + i * 256 + lane * 8); s[i] = make_float2(__uint_as_float(q.x), __uint_as_float(q.y)); }
#pragma unroll
      for (int o = 1; o < 16; o *= 2)
#pragma unroll
        for (int i = 0; i < 16; i += 2 * o) { s[i].x += s[i + o].x; s[i].y += s[i + o].y; }
      const uint32_t upd = keep(bf_mul2(pack_bf(s[0].x, s[0].y), pack_bf(rs, rs)));
      p.out[(2047 - (int)(kv & 2047u)) * 288 + dw] = bf_add2(hv, bf_add2(res, upd));
    } else bar_arrive(0, 512);
  }
  asm volatile("cp.async.bulk.wait_group.read 0;" ::: "memory");
  TS(12);
  TS_DUMP();
}

typedef CUresult (*EncodeFn)(CUtensorMap*, CUtensorMapDataType, cuuint32_t, void*, const cuuint64_t*, const cuuint64_t*, const cuuint32_t*,
                             const cuuint32_t*, CUtensorMapInterleave, CUtensorMapSwizzle, CUtensorMapL2promotion, CUtensorMapFloatOOBfill);

}

extern "C" void kernel_launch(void* const* d_in, const int* in_sizes, int n_in, void* d_out, int out_size) {
  (void)in_sizes; (void)n_in; (void)out_size;
  static EncodeFn enc = nullptr;
  static Scratch* scratch = nullptr;
  if (!enc) {
    void* fn = nullptr;
    cudaDriverEntryPointQueryResult qr;
    cudaGetDriverEntryPoint("cuTensorMapEncodeTiled", &fn, cudaEnableDefault, &qr);
    enc = (EncodeFn)fn;
    cudaGetSymbolAddress((void**)&scratch, g_S);
    cudaFuncSetAttribute(fused_kernel<false>, cudaFuncAttributeMaxDynamicSharedMemorySize, SMEM_BYTES);
    cudaFuncSetAttribute(fused_kernel<true>, cudaFuncAttributeMaxDynamicSharedMemorySize, SMEM_BYTES);
  }
  TMaps tm;
  for (int i = 0; i < 6; i++) {
    const bool dn = i % 3 == 2;
    const cuuint32_t w = i < 3 ? 40 : 32;
    cuuint64_t gd[3] = {(cuuint64_t)(dn ? 64 : FF), (cuuint64_t)(dn ? FF : DM), 9};
    cuuint64_t gs[2] = {(cuuint64_t)(dn ? DM * 2 : FF * 2), 128};
    cuuint32_t bx[3] = {dn ? 64 : w, dn ? w : 96, i < 3 ? 2u : 3u};
    cuuint32_t es[3] = {1, 1, 1};
    enc(&tm.m[i], CU_TENSOR_MAP_DATA_TYPE_BFLOAT16, dn ? 3 : 2, d_in[11 + i % 3], gd, gs, bx, es, CU_TENSOR_MAP_INTERLEAVE_NONE,
        dn ? CU_TENSOR_MAP_SWIZZLE_128B : i < 3 ? CU_TENSOR_MAP_SWIZZLE_NONE : CU_TENSOR_MAP_SWIZZLE_64B,
        CU_TENSOR_MAP_L2_PROMOTION_NONE, CU_TENSOR_MAP_FLOAT_OOB_FILL_NONE);
  }
  for (int i = 6; i < 8; i++) {
    cuuint64_t gd[2] = {DM * 16, NCTA};
    cuuint64_t gs[1] = {DM * 32};
    cuuint32_t bx[2] = {16, i == 6 ? 160u : 128u};
    cuuint32_t es[2] = {1, 1};
    enc(&tm.m[i], CU_TENSOR_MAP_DATA_TYPE_FLOAT16, 2, scratch->X, gd, gs, bx, es, CU_TENSOR_MAP_INTERLEAVE_NONE, CU_TENSOR_MAP_SWIZZLE_32B,
        CU_TENSOR_MAP_L2_PROMOTION_NONE, CU_TENSOR_MAP_FLOAT_OOB_FILL_NONE);
  }
  Params p;
  p.x = (const unsigned char*)d_in[0];
  bool far = false;
  for (int i = 0; i < 7; i++) {
    p.far[i] = (const unsigned char*)d_in[1 + i];
    const long long d = (long long)((intptr_t)d_in[1 + i] - (intptr_t)d_in[0]);
    p.off[i] = (int)(d / 16);
    if ((long long)p.off[i] * 16 != d) far = true;
  }
  p.dskip = (const uint32_t*)d_in[8];
  p.w_r = (const uint32_t*)d_in[10];
  p.w_gate = (const unsigned char*)d_in[11];
  p.w_up = (const unsigned char*)d_in[12];
  for (int f = 0; f < 2; f++) {
    static const int kind[17] = {0, 0, 0, 0, 0, 0, 1, 1, 1, 1, 1, 1, 2, 2, 2, 2, 2};
    static const int idx[2][17] = {{3, 4, 5, 0, 1, 2, 0, 1, 2, 3, 4, 5, 6, 8, 0, 2, 4}, {3, 4, 5, 0, 1, 2, 0, 1, 2, 3, 4, 5, 0, -1, 3, -1, 6}};
    static const int blk[2][17] = {{-1, -1, -1, -1, -1, -1, 1, -1, 2, -1, 3, -1, 16, -1, -1, -1, -1}, {-1, -1, -1, -1, -1, -1, 1, -1, 2, -1, 3, -1, 16, -1, -1, -1, -1}};
    const int pitch = f ? 64 : 80;
    for (int u = 0; u < 17; u++) {
      const int s = idx[f][u];
      const uint32_t dst = kind[u] == 0 ? OFF_G + s * 96 * pitch : kind[u] == 2 ? down_box(s, f) : OFF_W + W_BYTES + (s >> 1) * W_BYTES + (s & 1) * 96 * pitch;
      const uint32_t mb = u == X_NE ? MB_GF - OFF_MISC : blk[f][u] >= 0 ? MB_KF - OFF_MISC + blk[f][u] * 8 : 0;
      p.sched[f][u] = s < 0 ? 3u : kind[u] | s << 2 | mb << 6 | dst << 14;
    }
  }
  p.out = (uint32_t*)d_out;
  p.zero = 0;
  p.ts = nullptr;
  p.s = scratch;
  if (far) { fused_kernel<true><<<NCTA, NT, SMEM_BYTES, cudaStreamPerThread>>>(p, tm); return; }
  fused_kernel<false><<<NCTA, NT, SMEM_BYTES, cudaStreamPerThread>>>(p, tm);
}
```

```cpp
#include <cuda_runtime.h>
#include <cuda.h>
#include <cuda_bf16.h>
#include <cuda_fp16.h>
#include <stdint.h>
#include <stddef.h>

namespace {

constexpr int NCTA = 128;
constexpr int NT = 640;
constexpr int DM = 576;
constexpr int FF = 4608;
constexpr int SPIN_MAX = 1 << 20;

struct Scratch {
  uint4 X[NCTA * DM * 2];
  uint4 KX[64 * 128];
  uint4 HS[1152 + 8];
  uint4 R[256];
  uint4 SC[256];
  uint32_t FLAG[NCTA * 8];
};
__device__ Scratch g_S;

#define TS(i)
#define TSX(i)
#define TS_DUMP()

constexpr int SB = 1024;
constexpr int BOX = 15360;
constexpr int OFF_G = SB;
constexpr int OFF_W = OFF_G + 3 * BOX;
constexpr int W_UP = 26624;
constexpr int W_KT = W_UP + 5120;
constexpr int W_L3 = W_KT + 4416;
constexpr int W_CW = W_L3 + 4096;
constexpr int W_MISC = W_CW + 640;
constexpr int W_BYTES = 40960;
constexpr int ALT = -W_UP;
static_assert(W_MISC + 32 <= W_BYTES && OFF_W % 1024 == 0 && W_UP % 256 == 0 && W_BYTES + ALT + 3 * 4096 <= W_UP, "wg block");
constexpr int OFF_K5 = OFF_G + 40960;
constexpr int YT_PITCH = 1184;
constexpr int OFF_YT = OFF_W + 4 * W_BYTES;
constexpr int OFF_WR = OFF_YT + 16 * YT_PITCH + 64;
constexpr int OFF_MISC = OFF_WR + 2304;
constexpr int SMEM_BYTES = OFF_MISC + 1024 - SB;
static_assert(OFF_YT % 16 == 0 && OFF_MISC % 16 == 0, "align");
static_assert(SMEM_BYTES <= 232448, "smem");
constexpr int MB_GU = OFF_MISC;
constexpr int MB_D = OFF_MISC + 8;
constexpr int MB_KF = OFF_MISC + 16;
constexpr int MB_GF = OFF_MISC + 48;
constexpr int MB_SC = OFF_MISC + 56;
constexpr int MB_UL = OFF_MISC + 64;
constexpr int MB_H = MB_KF + 128;
constexpr int MISC_EPOCH = OFF_MISC + 152;
constexpr int MISC_SW = OFF_MISC + 156;
constexpr int MISC_EM = OFF_MISC + 288;
constexpr int MISC_RK = OFF_MISC + 160;
constexpr int MISC_LN1 = OFF_MISC + 192;
constexpr int OFF_XS = OFF_W + W_BYTES + W_UP;
constexpr int OFF_RED = OFF_W + 2 * W_BYTES + W_UP;
constexpr int OFF_FIN = OFF_W + 3 * W_BYTES + W_UP;
constexpr int OFF_ACT = OFF_FIN + 4096;
constexpr int MISC_CNT = OFF_ACT + 1024;

__device__ __forceinline__ uint32_t smem_u32(const void* p) { return (uint32_t)__cvta_generic_to_shared(p); }
__device__ __forceinline__ uint32_t lds32(uint32_t a) { uint32_t v; asm volatile("ld.shared.b32 %0, [%1];" : "=r"(v) : "r"(a) : "memory"); return v; }
__device__ __forceinline__ uint32_t lds16(uint32_t a) { uint16_t v; asm volatile("ld.shared.u16 %0, [%1];" : "=h"(v) : "r"(a) : "memory"); return v; }
__device__ __forceinline__ uint2 lds64(uint32_t a) { uint2 v; asm volatile("ld.shared.v2.b32 {%0,%1}, [%2];" : "=r"(v.x), "=r"(v.y) : "r"(a) : "memory"); return v; }
__device__ __forceinline__ uint4 lds128(uint32_t a) { uint4 v; asm volatile("ld.shared.v4.b32 {%0,%1,%2,%3}, [%4];" : "=r"(v.x), "=r"(v.y), "=r"(v.z), "=r"(v.w) : "r"(a) : "memory"); return v; }
__device__ __forceinline__ void sts16(uint32_t a, uint32_t v) { asm volatile("st.shared.u16 [%0], %1;" :: "r"(a), "h"((uint16_t)v) : "memory"); }
__device__ __forceinline__ void sts32(uint32_t a, uint32_t v) { asm volatile("st.shared.b32 [%0], %1;" :: "r"(a), "r"(v) : "memory"); }
__device__ __forceinline__ void sts64(uint32_t a, uint32_t x, uint32_t y) { asm volatile("st.shared.v2.b32 [%0], {%1,%2};" :: "r"(a), "r"(x), "r"(y) : "memory"); }
__device__ __forceinline__ void sts128(uint32_t a, uint32_t x, uint32_t y, uint32_t z, uint32_t w) { asm volatile("st.shared.v4.b32 [%0], {%1,%2,%3,%4};" :: "r"(a), "r"(x), "r"(y), "r"(z), "r"(w) : "memory"); }
__device__ __forceinline__ void ldsm4(uint32_t a, uint32_t& r0, uint32_t& r1, uint32_t& r2, uint32_t& r3) {
  asm volatile("ldmatrix.sync.aligned.m8n8.x4.shared.b16 {%0,%1,%2,%3}, [%4];" : "=r"(r0), "=r"(r1), "=r"(r2), "=r"(r3) : "r"(a) : "memory");
}
__device__ __forceinline__ void ldsm2(uint32_t a, uint32_t& r0, uint32_t& r1) {
  asm volatile("ldmatrix.sync.aligned.m8n8.x2.shared.b16 {%0,%1}, [%2];" : "=r"(r0), "=r"(r1) : "r"(a) : "memory");
}
__device__ __forceinline__ void ldsm4t(uint32_t a, uint32_t& r0, uint32_t& r1, uint32_t& r2, uint32_t& r3) {
  asm volatile("ldmatrix.sync.aligned.m8n8.x4.trans.shared.b16 {%0,%1,%2,%3}, [%4];" : "=r"(r0), "=r"(r1), "=r"(r2), "=r"(r3) : "r"(a) : "memory");
}
__device__ __forceinline__ void stsm4t(uint32_t a, uint32_t r0, uint32_t r1, uint32_t r2, uint32_t r3) {
  asm volatile("stmatrix.sync.aligned.m8n8.x4.trans.shared.b16 [%0], {%1,%2,%3,%4};" :: "r"(a), "r"(r0), "r"(r1), "r"(r2), "r"(r3) : "memory");
}
__device__ __forceinline__ uint4 ldr128(const void* p) {
  unsigned long long lo, hi;
  asm volatile("{ .reg .b128 t; ld.relaxed.gpu.global.b128 t, [%2]; mov.b128 {%0, %1}, t; }" : "=l"(lo), "=l"(hi) : "l"(p) : "memory");
  return make_uint4((uint32_t)lo, (uint32_t)(lo >> 32), (uint32_t)hi, (uint32_t)(hi >> 32));
}
__device__ __forceinline__ void str128(void* p, uint32_t x, uint32_t y, uint32_t z, uint32_t w) {
  asm volatile("{ .reg .b128 t; .reg .b64 lo, hi; mov.b64 lo, {%1,%2}; mov.b64 hi, {%3,%4}; mov.b128 t, {lo, hi}; st.relaxed.gpu.global.b128 [%0], t; }"
               :: "l"(p), "r"(x), "r"(y), "r"(z), "r"(w) : "memory");
}
__device__ __forceinline__ void str64(void* p, uint32_t x, uint32_t y) {
  asm volatile("{ .reg .b64 t; mov.b64 t, {%1,%2}; st.relaxed.gpu.global.b64 [%0], t; }" :: "l"(p), "r"(x), "r"(y) : "memory");
}
__device__ __forceinline__ uint32_t ldr32(const void* p) { uint32_t v; asm volatile("ld.relaxed.gpu.global.b32 %0, [%1];" : "=r"(v) : "l"(p) : "memory"); return v; }
__device__ __forceinline__ void str32(void* p, uint32_t v) { asm volatile("st.relaxed.gpu.global.b32 [%0], %1;" :: "l"(p), "r"(v) : "memory"); }
__device__ __forceinline__ void str16(void* p, uint32_t v) { asm volatile("st.relaxed.gpu.global.u16 [%0], %1;" :: "l"(p), "h"((uint16_t)v) : "memory"); }
__device__ __forceinline__ void fence_gpu() { asm volatile("fence.acq_rel.gpu;" ::: "memory"); }
__device__ __forceinline__ void bar_sync(int id, int n) { asm volatile("bar.sync %0, %1;" :: "r"(id), "r"(n) : "memory"); }
__device__ __forceinline__ void bar_arrive(int id, int n) { asm volatile("bar.arrive %0, %1;" :: "r"(id), "r"(n) : "memory"); }

__device__ __forceinline__ float bf_lo(uint32_t w) { return __uint_as_float(w << 16); }
__device__ __forceinline__ float bf_hi(uint32_t w) { return __uint_as_float(w & 0xFFFF0000u); }
__device__ __forceinline__ uint32_t pack_bf(float lo, float hi) { uint32_t r; asm("cvt.rn.bf16x2.f32 %0, %1, %2;" : "=r"(r) : "f"(hi), "f"(lo)); return r; }
__device__ __forceinline__ uint32_t pack_h(float lo, float hi) { uint32_t r; asm("cvt.rn.f16x2.f32 %0, %1, %2;" : "=r"(r) : "f"(hi), "f"(lo)); return r; }
__device__ __forceinline__ uint32_t pack_hv(float lo, float hi) { uint32_t r; asm volatile("cvt.rn.f16x2.f32 %0, %1, %2;" : "=r"(r) : "f"(hi), "f"(lo) : "memory"); return r; }
__device__ __forceinline__ float bfr(float x) { return bf_lo(pack_bf(x, 0.f)); }
__device__ __forceinline__ uint32_t bf_sub2(uint32_t a, uint32_t b) { __nv_bfloat162 r = __hsub2(*(__nv_bfloat162*)&a, *(__nv_bfloat162*)&b); return *(uint32_t*)&r; }
__device__ __forceinline__ uint32_t bf_add2(uint32_t a, uint32_t b) { __nv_bfloat162 r = __hadd2(*(__nv_bfloat162*)&a, *(__nv_bfloat162*)&b); return *(uint32_t*)&r; }
__device__ __forceinline__ uint32_t bf_mul2(uint32_t a, uint32_t b) { __nv_bfloat162 r = __hmul2(*(__nv_bfloat162*)&a, *(__nv_bfloat162*)&b); return *(uint32_t*)&r; }
__device__ __forceinline__ float2 h2f(uint32_t w) { return __half22float2(*(__half2*)&w); }
__device__ __forceinline__ float ex2(float x) { float r; asm("ex2.approx.ftz.f32 %0, %1;" : "=f"(r) : "f"(x)); return r; }
__device__ __forceinline__ float warp_sum(float v) {
#pragma unroll
  for (int o = 16; o > 0; o >>= 1) v += __shfl_xor_sync(0xffffffffu, v, o);
  return v;
}
__device__ __forceinline__ void mma_f16_f32(float* d, uint32_t a0, uint32_t a1, uint32_t a2, uint32_t a3, uint32_t b0, uint32_t b1) {
  asm volatile("mma.sync.aligned.m16n8k16.row.col.f32.f16.f16.f32 {%0,%1,%2,%3}, {%4,%5,%6,%7}, {%8,%9}, {%0,%1,%2,%3};"
               : "+f"(d[0]), "+f"(d[1]), "+f"(d[2]), "+f"(d[3]) : "r"(a0), "r"(a1), "r"(a2), "r"(a3), "r"(b0), "r"(b1));
}
__device__ __forceinline__ void mma_f16_f16(uint32_t& d0, uint32_t& d1, uint32_t a0, uint32_t a1, uint32_t a2, uint32_t a3, uint32_t b0, uint32_t b1) {
  asm volatile("mma.sync.aligned.m16n8k16.row.col.f16.f16.f16.f16 {%0,%1}, {%2,%3,%4,%5}, {%6,%7}, {%0,%1};"
               : "+r"(d0), "+r"(d1) : "r"(a0), "r"(a1), "r"(a2), "r"(a3), "r"(b0), "r"(b1));
}
__device__ __forceinline__ void mma_bf16(float* d, uint32_t a0, uint32_t a1, uint32_t a2, uint32_t a3, uint32_t b0, uint32_t b1) {
  asm volatile("mma.sync.aligned.m16n8k16.row.col.f32.bf16.bf16.f32 {%0,%1,%2,%3}, {%4,%5,%6,%7}, {%8,%9}, {%0,%1,%2,%3};"
               : "+f"(d[0]), "+f"(d[1]), "+f"(d[2]), "+f"(d[3]) : "r"(a0), "r"(a1), "r"(a2), "r"(a3), "r"(b0), "r"(b1));
}
__device__ __forceinline__ void mma_bf16_k8(float* d, uint32_t a0, uint32_t a1, uint32_t b0) {
  asm volatile("mma.sync.aligned.m16n8k8.row.col.f32.bf16.bf16.f32 {%0,%1,%2,%3}, {%4,%5}, {%6}, {%0,%1,%2,%3};"
               : "+f"(d[0]), "+f"(d[1]), "+f"(d[2]), "+f"(d[3]) : "r"(a0), "r"(a1), "r"(b0));
}

__device__ __forceinline__ void wg_fence() { asm volatile("wgmma.fence.sync.aligned;" ::: "memory"); }
__device__ __forceinline__ void wg_commit() { asm volatile("wgmma.commit_group.sync.aligned;" ::: "memory"); }
template <int N> __device__ __forceinline__ void wg_wait() { asm volatile("wgmma.wait_group.sync.aligned %0;" :: "n"(N) : "memory"); }
template <int TB> __device__ __forceinline__ void wgmma32(float* d, const uint32_t* a, uint32_t dlo, uint32_t dhi) {
  asm volatile("{ .reg .b64 dd; mov.b64 dd, {%20, %21}; wgmma.mma_async.sync.aligned.m64n32k16.f32.f16.f16 "
               "{%0,%1,%2,%3,%4,%5,%6,%7,%8,%9,%10,%11,%12,%13,%14,%15}, {%16,%17,%18,%19}, dd, 1, 1, 1, %22; }"
               : "+f"(d[0]), "+f"(d[1]), "+f"(d[2]), "+f"(d[3]), "+f"(d[4]), "+f"(d[5]), "+f"(d[6]), "+f"(d[7]), "+f"(d[8]), "+f"(d[9]), "+f"(d[10]), "+f"(d[11]), "+f"(d[12]), "+f"(d[13]), "+f"(d[14]), "+f"(d[15])
               : "r"(a[0]), "r"(a[1]), "r"(a[2]), "r"(a[3]), "r"(dlo), "r"(dhi), "n"(TB));
}
template <int TB> __device__ __forceinline__ void wgmma96(float* d, const uint32_t* a, uint32_t dlo, uint32_t dhi) {
  asm volatile("{ .reg .b64 dd; mov.b64 dd, {%52, %53}; wgmma.mma_async.sync.aligned.m64n96k16.f32.f16.f16 "
               "{%0,%1,%2,%3,%4,%5,%6,%7,%8,%9,%10,%11,%12,%13,%14,%15,%16,%17,%18,%19,%20,%21,%22,%23,%24,%25,%26,%27,%28,%29,%30,%31,%32,%33,%34,%35,%36,%37,%38,%39,%40,%41,%42,%43,%44,%45,%46,%47}, {%48,%49,%50,%51}, dd, 1, 1, 1, %54; }"
               : "+f"(d[0]), "+f"(d[1]), "+f"(d[2]), "+f"(d[3]), "+f"(d[4]), "+f"(d[5]), "+f"(d[6]), "+f"(d[7]), "+f"(d[8]), "+f"(d[9]), "+f"(d[10]), "+f"(d[11]), "+f"(d[12]), "+f"(d[13]), "+f"(d[14]), "+f"(d[15]), "+f"(d[16]), "+f"(d[17]), "+f"(d[18]), "+f"(d[19]), "+f"(d[20]), "+f"(d[21]), "+f"(d[22]), "+f"(d[23]), "+f"(d[24]), "+f"(d[25]), "+f"(d[26]), "+f"(d[27]), "+f"(d[28]), "+f"(d[29]), "+f"(d[30]), "+f"(d[31]), "+f"(d[32]), "+f"(d[33]), "+f"(d[34]), "+f"(d[35]), "+f"(d[36]), "+f"(d[37]), "+f"(d[38]), "+f"(d[39]), "+f"(d[40]), "+f"(d[41]), "+f"(d[42]), "+f"(d[43]), "+f"(d[44]), "+f"(d[45]), "+f"(d[46]), "+f"(d[47])
               : "r"(a[0]), "r"(a[1]), "r"(a[2]), "r"(a[3]), "r"(dlo), "r"(dhi), "n"(TB));
}
template <int TB> __device__ __forceinline__ void wgmma96_init(float* d, const uint32_t* a, uint32_t dlo, uint32_t dhi) {
  asm volatile("{ .reg .b64 dd; mov.b64 dd, {%52, %53}; wgmma.mma_async.sync.aligned.m64n96k16.f32.f16.f16 "
               "{%0,%1,%2,%3,%4,%5,%6,%7,%8,%9,%10,%11,%12,%13,%14,%15,%16,%17,%18,%19,%20,%21,%22,%23,%24,%25,%26,%27,%28,%29,%30,%31,%32,%33,%34,%35,%36,%37,%38,%39,%40,%41,%42,%43,%44,%45,%46,%47}, {%48,%49,%50,%51}, dd, 0, 1, 1, %54; }"
               : "=f"(d[0]), "=f"(d[1]), "=f"(d[2]), "=f"(d[3]), "=f"(d[4]), "=f"(d[5]), "=f"(d[6]), "=f"(d[7]), "=f"(d[8]), "=f"(d[9]), "=f"(d[10]), "=f"(d[11]), "=f"(d[12]), "=f"(d[13]), "=f"(d[14]), "=f"(d[15]), "=f"(d[16]), "=f"(d[17]), "=f"(d[18]), "=f"(d[19]), "=f"(d[20]), "=f"(d[21]), "=f"(d[22]), "=f"(d[23]), "=f"(d[24]), "=f"(d[25]), "=f"(d[26]), "=f"(d[27]), "=f"(d[28]), "=f"(d[29]), "=f"(d[30]), "=f"(d[31]), "=f"(d[32]), "=f"(d[33]), "=f"(d[34]), "=f"(d[35]), "=f"(d[36]), "=f"(d[37]), "=f"(d[38]), "=f"(d[39]), "=f"(d[40]), "=f"(d[41]), "=f"(d[42]), "=f"(d[43]), "=f"(d[44]), "=f"(d[45]), "=f"(d[46]), "=f"(d[47])
               : "r"(a[0]), "r"(a[1]), "r"(a[2]), "r"(a[3]), "r"(dlo), "r"(dhi), "n"(TB));
}
template <int TB> __device__ __forceinline__ void wgmma32_init(float* d, const uint32_t* a, uint32_t dlo, uint32_t dhi) {
  asm volatile("{ .reg .b64 dd; mov.b64 dd, {%20, %21}; wgmma.mma_async.sync.aligned.m64n32k16.f32.f16.f16 "
               "{%0,%1,%2,%3,%4,%5,%6,%7,%8,%9,%10,%11,%12,%13,%14,%15}, {%16,%17,%18,%19}, dd, 0, 1, 1, %22; }"
               : "=f"(d[0]), "=f"(d[1]), "=f"(d[2]), "=f"(d[3]), "=f"(d[4]), "=f"(d[5]), "=f"(d[6]), "=f"(d[7]), "=f"(d[8]), "=f"(d[9]), "=f"(d[10]), "=f"(d[11]), "=f"(d[12]), "=f"(d[13]), "=f"(d[14]), "=f"(d[15])
               : "r"(a[0]), "r"(a[1]), "r"(a[2]), "r"(a[3]), "r"(dlo), "r"(dhi), "n"(TB));
}
__device__ __forceinline__ void wgmma64h(uint32_t* d, uint32_t a0, uint32_t a1, uint32_t a2, uint32_t a3, uint32_t dlo, uint32_t dhi) {
  asm volatile("{ .reg .b64 dd; mov.b64 dd, {%20, %21}; wgmma.mma_async.sync.aligned.m64n64k16.f16.f16.f16 "
               "{%0,%1,%2,%3,%4,%5,%6,%7,%8,%9,%10,%11,%12,%13,%14,%15}, {%16,%17,%18,%19}, dd, 1, 1, 1, 0; }"
               : "+r"(d[0]), "+r"(d[1]), "+r"(d[2]), "+r"(d[3]), "+r"(d[4]), "+r"(d[5]), "+r"(d[6]), "+r"(d[7]), "+r"(d[8]), "+r"(d[9]), "+r"(d[10]), "+r"(d[11]), "+r"(d[12]), "+r"(d[13]), "+r"(d[14]), "+r"(d[15])
               : "r"(a0), "r"(a1), "r"(a2), "r"(a3), "r"(dlo), "r"(dhi));
}
__device__ __forceinline__ void wgmma64h_init(uint32_t* d, uint32_t a0, uint32_t a1, uint32_t a2, uint32_t a3, uint32_t dlo, uint32_t dhi) {
  asm volatile("{ .reg .b64 dd; mov.b64 dd, {%20, %21}; wgmma.mma_async.sync.aligned.m64n64k16.f16.f16.f16 "
               "{%0,%1,%2,%3,%4,%5,%6,%7,%8,%9,%10,%11,%12,%13,%14,%15}, {%16,%17,%18,%19}, dd, 0, 1, 1, 0; }"
               : "=r"(d[0]), "=r"(d[1]), "=r"(d[2]), "=r"(d[3]), "=r"(d[4]), "=r"(d[5]), "=r"(d[6]), "=r"(d[7]), "=r"(d[8]), "=r"(d[9]), "=r"(d[10]), "=r"(d[11]), "=r"(d[12]), "=r"(d[13]), "=r"(d[14]), "=r"(d[15])
               : "r"(a0), "r"(a1), "r"(a2), "r"(a3), "r"(dlo), "r"(dhi));
}
__device__ __forceinline__ void wgmma40_ss(float* d, uint32_t alo, uint32_t blo, uint32_t hi) {
  asm volatile("{ .reg .b64 da, db; mov.b64 da, {%20, %22}; mov.b64 db, {%21, %22}; "
               "wgmma.mma_async.sync.aligned.m64n40k16.f32.f16.f16 {%0,%1,%2,%3,%4,%5,%6,%7,%8,%9,%10,%11,%12,%13,%14,%15,%16,%17,%18,%19}, da, db, 1, 1, 1, 1, 1; }"
               : "+f"(d[0]), "+f"(d[1]), "+f"(d[2]), "+f"(d[3]), "+f"(d[4]), "+f"(d[5]), "+f"(d[6]), "+f"(d[7]), "+f"(d[8]), "+f"(d[9]), "+f"(d[10]), "+f"(d[11]), "+f"(d[12]), "+f"(d[13]), "+f"(d[14]), "+f"(d[15]), "+f"(d[16]), "+f"(d[17]), "+f"(d[18]), "+f"(d[19])
               : "r"(alo), "r"(blo), "r"(hi));
}
__device__ __forceinline__ void wgmma40_ss_init(float* d, uint32_t alo, uint32_t blo, uint32_t hi) {
  asm volatile("{ .reg .b64 da, db; mov.b64 da, {%20, %22}; mov.b64 db, {%21, %22}; "
               "wgmma.mma_async.sync.aligned.m64n40k16.f32.f16.f16 {%0,%1,%2,%3,%4,%5,%6,%7,%8,%9,%10,%11,%12,%13,%14,%15,%16,%17,%18,%19}, da, db, 0, 1, 1, 1, 1; }"
               : "=f"(d[0]), "=f"(d[1]), "=f"(d[2]), "=f"(d[3]), "=f"(d[4]), "=f"(d[5]), "=f"(d[6]), "=f"(d[7]), "=f"(d[8]), "=f"(d[9]), "=f"(d[10]), "=f"(d[11]), "=f"(d[12]), "=f"(d[13]), "=f"(d[14]), "=f"(d[15]), "=f"(d[16]), "=f"(d[17]), "=f"(d[18]), "=f"(d[19])
               : "r"(alo), "r"(blo), "r"(hi));
}
__device__ __forceinline__ float vzero() { float v; asm volatile("mov.b32 %0, 0;" : "=f"(v)); return v; }
__device__ __forceinline__ void tma_box(uint32_t dst, const CUtensorMap* tm, uint32_t mb, int x, int y) {
  asm volatile("cp.async.bulk.tensor.2d.shared::cluster.global.mbarrier::complete_tx::bytes [%0], [%1, {%3, %4}], [%2];"
               :: "r"(dst), "l"(tm), "r"(mb), "r"(x), "r"(y) : "memory");
}
__device__ __forceinline__ void l2_prefetch(const void* src, uint32_t bytes) {
  asm volatile("cp.async.bulk.prefetch.L2.global [%0], %1;" :: "l"(src), "r"(bytes) : "memory");
}
__device__ __forceinline__ uint32_t uni(uint32_t v) {
  uint32_t r; asm volatile("shfl.sync.idx.b32 %0, %1, 0, 0x1f, 0xffffffff;" : "=r"(r) : "r"(v)); return r;
}
__device__ __forceinline__ int fresh_tid() { int v; asm volatile("mov.u32 %0, %tid.x;" : "=r"(v)); return v; }

struct Params {
  const unsigned char* x;
  Scratch* s;
  int off[7];
  uint32_t zero;
  uint32_t* out;
  const uint32_t* dskip;
  const uint32_t* w_r;
  const unsigned char* w_gate;
  const unsigned char* w_up;
  long long* ts;
  const unsigned char* far[7];
  uint32_t sched[2][17];
};
__device__ __forceinline__ uint32_t ldnc32(const void* p) { uint32_t v; asm volatile("ld.global.nc.b32 %0, [%1];" : "=r"(v) : "l"(p)); return v; }
__device__ __forceinline__ uint32_t ldnc16(const void* p) { uint16_t v; asm volatile("ld.global.nc.u16 %0, [%1];" : "=h"(v) : "l"(p)); return v; }
__device__ __forceinline__ uint4 ldnc128(const void* p) { uint4 v; asm volatile("ld.global.nc.v4.b32 {%0,%1,%2,%3}, [%4];" : "=r"(v.x), "=r"(v.y), "=r"(v.z), "=r"(v.w) : "l"(p)); return v; }
__device__ __forceinline__ void mbar_wait(uint32_t mb, uint32_t ph = 0) {
#pragma unroll 1
  for (int it = 0; it < SPIN_MAX; it++) {
    uint32_t ok;
    asm volatile("{ .reg .pred q; mbarrier.try_wait.parity.shared::cta.b64 q, [%1], %2; selp.u32 %0, 1, 0, q; }" : "=r"(ok) : "r"(mb), "r"(ph) : "memory");
    if (ok) break;
  }
}
__device__ __forceinline__ uint32_t mbar_test(uint32_t mb) {
  uint32_t ok;
  asm volatile("{ .reg .pred q; mbarrier.test_wait.parity.shared::cta.b64 q, [%1], 0; selp.u32 %0, 1, 0, q; }" : "=r"(ok) : "r"(mb) : "memory");
  return ok;
}
__device__ __forceinline__ void mbar_arrive(uint32_t mb) { asm volatile("mbarrier.arrive.shared::cta.b64 _, [%0];" :: "r"(mb) : "memory"); }
__device__ __forceinline__ uint32_t ldg16(const void* p) { uint16_t v; asm volatile("ld.global.u16 %0, [%1];" : "=h"(v) : "l"(p) : "memory"); return v; }
__device__ __forceinline__ uint32_t ldr16(const void* p) { uint16_t v; asm volatile("ld.relaxed.gpu.global.u16 %0, [%1];" : "=h"(v) : "l"(p) : "memory"); return v; }
__device__ __forceinline__ void fence_async() { asm volatile("fence.proxy.async.shared::cta;" ::: "memory"); }
#define SPIN_WHILE(cond, body) _Pragma("unroll 1") for (int _it = 0; _it < SPIN_MAX && __any_sync(0xffffffffu, (cond)); _it++) { body; }

struct LnC { uint32_t m2, rh2, rl2; };
__device__ __forceinline__ float diag_sum(float d0, float d1, int t) {
  float q = __shfl_sync(0xffffffffu, d0, 9 * t) + __shfl_sync(0xffffffffu, d1, 9 * t + 4);
  q += __shfl_xor_sync(0xffffffffu, q, 1);
  return q + __shfl_xor_sync(0xffffffffu, q, 2);
}
__device__ __forceinline__ LnC ln_consts(float s, float q, float& r) {
  const float mean = s * (1.f / DM);
  const float var = fmaxf(fmaf(-mean, mean, q * (1.f / DM)), 0.f);
  float sd;
  asm("sqrt.approx.ftz.f32 %0, %1;" : "=f"(sd) : "f"(bfr(bfr(var) + 1e-5f)));
  asm("rcp.approx.ftz.f32 %0, %1;" : "=f"(r) : "f"(bfr(sd)));
  LnC c;
  c.m2 = pack_bf(mean, mean);
  c.rh2 = pack_bf(r, r);
  const float rl = r - bf_lo(c.rh2);
  c.rl2 = pack_bf(rl, rl);
  return c;
}
__device__ __forceinline__ float quad_sum(float s) { s += __shfl_xor_sync(0xffffffffu, s, 1); return s + __shfl_xor_sync(0xffffffffu, s, 2); }
__device__ __forceinline__ uint32_t bf_fma2(uint32_t a, uint32_t b, uint32_t c) {
  __nv_bfloat162 r = __hfma2(*(const __nv_bfloat162*)&a, *(const __nv_bfloat162*)&b, *(const __nv_bfloat162*)&c);
  return *(uint32_t*)&r;
}
__device__ __forceinline__ uint32_t ln_apply(uint32_t w, uint32_t m2, uint32_t rh2, uint32_t rl2) {
  const uint32_t d = bf_sub2(w, m2);
  return bf_fma2(d, rh2, bf_mul2(d, rl2));
}

__device__ __forceinline__ float2 cis(float mag_log2, float rev) {
  const float m = ex2(mag_log2), ang = rev * 6.283185307179586f;
  return make_float2(m * __cosf(ang), m * __sinf(ang));
}
__device__ __forceinline__ float2 csq(float2 a) { return make_float2(fmaf(a.x, a.x, -a.y * a.y), (a.x + a.x) * a.y); }
__device__ __forceinline__ float2 cmul(float2 a, float2 b) { return make_float2(fmaf(a.x, b.x, -a.y * b.y), fmaf(a.x, b.y, a.y * b.x)); }
__device__ __forceinline__ void pmul(uint32_t xr, uint32_t xi, uint32_t w, uint32_t& yr, uint32_t& yi) {
  const __half2 XR = *(__half2*)&xr, XI = *(__half2*)&xi, W = *(__half2*)&w;
  const __half2 a = __hfma2(__hneg2(XI), __high2half2(W), __hmul2(XR, __low2half2(W)));
  const __half2 b = __hfma2(XI, __low2half2(W), __hmul2(XR, __high2half2(W)));
  yr = *(const uint32_t*)&a; yi = *(const uint32_t*)&b;
}
__device__ __forceinline__ uint32_t pk(float2 a) { return pack_h(a.x, a.y); }

struct KgState { float2 c0, z8; float kl; uint32_t w64, w128, w192; };
__device__ __forceinline__ void kgen_tables_n(const uint32_t (&raw)[7], uint32_t scr, int wt, KgState& k) {
  const uint32_t dst = scr + 16384 + wt * 16;
  const float dt = bfr(ex2(bf_lo(raw[6]) * 1.4426950408889634f));
  const float th = dt * bf_lo(raw[1]);
  const float br = dt * bf_lo(raw[2]), bi = dt * bf_lo(raw[3]);
  const float Cr = bf_lo(raw[4]), Ci = bf_lo(raw[5]);
  k.c0 = make_float2(fmaf(Cr, br, -Ci * bi), fmaf(Cr, bi, Ci * br));
  const uint32_t mx = __reduce_max_sync(0xffffffffu, __float_as_uint(fmaxf(fabsf(k.c0.x), fabsf(k.c0.y))));
  const float a2 = dt * bf_lo(raw[0]) * 1.4426950408889634f;
  const float rh = th * 0.15915494309189535f;
  const float rl = fmaf(th, (float)(0.15915494309189535 - (double)0.15915494309189535f), fmaf(th, 0.15915494309189535f, -rh));
  const float rf = rh - rintf(rh);
  const float2 z1 = cis(a2, rf + rl);
  const float p64 = rf * 64.f;
  const float2 z64 = cis(a2 * 64.f, fmaf(64.f, rl, p64 - rintf(p64)));
  const float2 z2 = csq(z1), z128 = csq(z64), z3 = cmul(z2, z1), z4 = csq(z2), z256 = csq(z128), z6 = csq(z3), z512 = csq(z256);
  k.z8 = csq(z4);
  k.w64 = pk(z64); k.w128 = pk(z128); k.w192 = pk(cmul(z128, z64));
  sts128(dst, 0x00003C00u, pk(z2), pk(z4), pk(z6));
  const float2 z1024 = csq(z512), z768 = cmul(z512, z256);
  sts128(dst + 2048, pk(z1), pk(z3), pk(cmul(z4, z1)), pk(cmul(z4, z3)));
  const float2 z2048 = csq(z1024);
  k.kl = fmaf(k.c0.x, z2048.x, -k.c0.y * z2048.y);
  sts128(dst + 4096, pk(z256), pk(cmul(z256, z2)), pk(cmul(z256, z4)), pk(cmul(z256, z6)));
  sts128(dst + 6144, pk(z512), pk(cmul(z512, z4)), pk(z768), pk(cmul(z768, z4)));
  sts128(dst + 8192, pk(z1024), pk(cmul(z1024, z256)), pk(cmul(z1024, z512)), pk(cmul(z1024, z768)));
  sts32(scr + W_MISC + (wt >> 5) * 4, mx);
}
__device__ __forceinline__ int kgen_tables_m(uint32_t scr, int wt, const KgState& k) {
  const uint32_t dst = scr + wt * 16;
  const uint4 e4 = lds128(scr + W_MISC);
  const float2 z16 = csq(k.z8), z32 = csq(z16);
  const int em = max(min((int)(max(max(e4.x, e4.y), max(e4.z, e4.w)) >> 23), 238), 16);
  const float sc = __uint_as_float((uint32_t)(127 + 4 + 127 - em) << 23);
  sts32(scr + W_MISC + 16 + (wt >> 5) * 4, __reduce_add_sync(0xffffffffu, __float2int_rn(k.kl * sc * 262144.f)));
  const float2 c0 = make_float2(k.c0.x * sc, k.c0.y * sc);
  const float2 c1 = cmul(c0, k.z8), c2 = cmul(c0, z16), c4 = cmul(c0, z32), c3 = cmul(c1, z16), c5 = cmul(c1, z32), c6 = cmul(c2, z32), c7 = cmul(c3, z32);
  uint32_t pr[4], pi[4], yr[4], yi[4];
  pr[0] = pack_h(c0.x, c1.x); pi[0] = pack_h(c0.y, c1.y);
  pr[1] = pack_h(c2.x, c3.x); pi[1] = pack_h(c2.y, c3.y);
  pr[2] = pack_h(c4.x, c5.x); pi[2] = pack_h(c4.y, c5.y);
  pr[3] = pack_h(c6.x, c7.x); pi[3] = pack_h(c6.y, c7.y);
  sts128(dst, pr[0], pr[1], pr[2], pr[3]); sts128(dst + 2048, pi[0], pi[1], pi[2], pi[3]);
#pragma unroll
  for (int q = 1; q < 4; q++) {
    const uint32_t w = q == 1 ? k.w64 : q == 2 ? k.w128 : k.w192;
#pragma unroll
    for (int i = 0; i < 4; i++) pmul(pr[i], pi[i], w, yr[i], yi[i]);
    sts128(dst + q * 4096, yr[0], yr[1], yr[2], yr[3]); sts128(dst + q * 4096 + 2048, yi[0], yi[1], yi[2], yi[3]);
  }
  return em;
}
__device__ __forceinline__ void kgen_build(uint32_t wb, int wg, int wt, uint32_t k0, uint32_t k1, uint32_t k2) {
  const uint32_t kt = wb + W_KT;
  const bool ev = !(wt & 1), mid = ev && wt;
  const uint32_t a0 = kt + 64 + wt * 8;
  const uint32_t a2 = kt + 64 + 2048 + (wt >> 2) * 32 + (wt & 1) * 16 + (wt & 2) * 512;
  const int ix = ((wt >> 2) + (wt & 3) * 32 - 1) & 127;
  const uint32_t a3 = wb + W_CW + 32 + ((ix & 1) ? 0 : 304) + (ix >> 1) * 4;
  const uint32_t v3 = wt ? k2 : k2 >> 16;
  sts16(a3, v3); sts16(a3 + 6, v3);
  if ((unsigned)(wt - 32) < 18u) sts128(kt + (wt < 36 ? -512 : 64 + 4128 - 576) + wt * 16, 0, 0, 0, 0);
  const uint32_t sw = __byte_perm(k0, 0, 0x1032), d2 = __byte_perm(k1, 0, 0x1010), d3 = __byte_perm(k1, 0, 0x3232);
  sts16(a0, k0); sts32(a0 + 4, sw); sts16(a0 + 10, sw);
  sts16(a0 + 1024 - (mid ? 4 : 0), d2); sts16(a0 + 1024 + (ev ? 10 : 6), d2);
  sts16(a2 - (mid ? 8 : 4), d3); sts64(a2, d3, d3); sts16(a2 + (ev ? 14 : 10), d3);
  if (mid) { sts64(a0 + 1024, d2, d2); sts32(a2 - 4, d3); }
  if (ev) sts32(a2 + 8, d3);
  if (wt == 0) {
    const uint32_t d = __byte_perm(k2, 0, 0x1010);
    sts16(kt + 66, 0); sts32(kt + 64 + 1028, d2);
    sts16(kt + 64 + 4088, d); sts32(kt + 64 + 4092, d); sts128(kt + 64 + 4096, d, d, d, d); sts128(kt + 64 + 4112, d, d << 16, 0, 0);
  }
  bar_sync(1 + wg, 128);
  const uint32_t cw = wb + W_CW + 32 + (wt >> 6) * 48 + wt * 4;
  sts128(wb + W_L3 + 1024 + (wt >> 6) * 1024 + wt * 16, lds32(cw), lds32(cw - 8), lds32(cw - 16), lds32(cw - 24));
}

__device__ __forceinline__ void load_a(uint32_t (&a)[4], uint32_t kp, int j) {
  a[0] = lds32(kp + 64 * j); a[1] = lds32(kp + 64 * j + 512); a[2] = lds32(kp + 64 * j - 32); a[3] = lds32(kp + 64 * j + 480);
}
__device__ __forceinline__ uint32_t band(int d, int lo, int hi) {
  return ((unsigned)(d - lo) <= (unsigned)(hi - lo) ? 1u : 0u) | ((unsigned)(d - 1 - lo) <= (unsigned)(hi - lo) ? 0x10000u : 0u);
}
__device__ __forceinline__ uint32_t hadd2u(uint32_t a, uint32_t b) { __half2 r = __hadd2(*(__half2*)&a, *(__half2*)&b); return *(uint32_t*)&r; }

__device__ __forceinline__ void zero_pads(uint32_t tb, int wt) {
  sts128(tb + W_L3 + (wt >> 6) * 1024 + wt * 16, 0, 0, 0, 0);
  if ((wt & 63) < 3) sts128(tb + W_CW + (wt >> 6) * 304 + (wt & 63) * 16, 0, 0, 0, 0);
}
__device__ __forceinline__ uint32_t tr_base(int lane) {
  return OFF_YT + (2 * (lane >> 3) + (lane & 1)) * YT_PITCH + ((lane >> 1) & 1) * (8 * YT_PITCH + 64) + ((lane >> 2) & 1) * 16;
}

__device__ __forceinline__ uint32_t sc_addr(int tp) { return OFF_YT + (tp < 16 ? tp * YT_PITCH + (tp >> 3) * 64 + 1152 : 8 * YT_PITCH - 512 + tp * 32); }
#define X_NE 3
#define X_NS 3
#define X_SCT 10500
#define X_DELTA 600
#define X_DSTEP 500
#define X_PF0 3000
#define X_PFD 560
#define X_TD 700
#define X_ORD 1
#define X_WS 6
#define X_OR 8
#define X_ABS 5000
#define X_XD 200
#define X_REL 0
#define X_RW 1
#define X_RD 500
#define X_HD 500
#define X_PD 900
#define X_HU 14
#define X_LAG 1600
#define X_YD 600
struct TMaps { CUtensorMap m[8]; };
__device__ __forceinline__ uint32_t h2bf(uint32_t w) { const float2 f = h2f(w); return pack_bf(f.x, f.y); }
__device__ __forceinline__ uint32_t keep(uint32_t v) { asm volatile("" : "+r"(v)); return v; }
__device__ __forceinline__ uint2 ldr64(const void* p) { uint2 v; asm volatile("{ .reg .b64 t; ld.relaxed.gpu.global.b64 t, [%2]; mov.b64 {%0, %1}, t; }" : "=r"(v.x), "=r"(v.y) : "l"(p) : "memory"); return v; }
__host__ __device__ __forceinline__ uint32_t down_box(int s, bool five) {
  return five ? OFF_W + W_BYTES + 12288 + (s / 3) * (W_BYTES - 12288) + s * 4096 : s < 6 ? OFF_W + W_BYTES + BOX + (s >> 1) * (W_BYTES - 10240) + s * 5120 : OFF_W + (s - 6) * 5120;
}
__device__ __forceinline__ void load_tile(const CUtensorMap* tmx, int i, int c) {
  asm volatile("mbarrier.arrive.expect_tx.shared::cta.b64 _, [%0], 5120;" :: "r"(MB_UL + i * 8) : "memory");
  tma_box(OFF_W + (i < 4 ? i * W_BYTES : ALT) + W_UP, tmx, MB_UL + i * 8, (i < 4 ? i * 128 + c : 512 + (c >> 1)) * 16, -32);
}
__device__ __forceinline__ void check_tile(uint32_t tb, const CUtensorMap* tmx, int i, int c, int wg, int wt) {
#pragma unroll 1
  for (int it = 0; it < SPIN_MAX; it++) {
    uint32_t r0, r1, r2, r3, ok;
    mbar_wait(MB_UL + i * 8, it & 1);
    if (it == 0) TS(29);
    if (it == 1) TS(13);
    ldsm4(tb + W_UP + 1024 + wt * 32 + (wt & 4) * 4, r0, r1, r2, r3);
    asm volatile("{ .reg .pred q; setp.ne.u32 q, %1, 0; barrier.red.and.pred q, %2, 128, q; selp.u32 %0, 1, 0, q; }" : "=r"(ok) : "r"((r0 & r1 & r2 & r3 & 1u) | (wt & 3)), "r"(1 + wg) : "memory");
    if (ok) break;
    if (wt == 0) load_tile(tmx, i, c);
  }
}
template <bool FAR> __device__ __forceinline__ void load_params(const Params& p, uint32_t ch, int wt, uint32_t dst) {
  if (wt < 97) {
    const unsigned char* b = FAR ? p.far[wt >> 4] : p.x + (long long)p.off[wt >> 4] * 16;
    asm volatile("cp.async.cg.shared.global [%0], [%1], 16;" :: "r"(dst + wt * 16), "l"(b + (wt < 96 ? ch * 256 + (wt & 15) * 16 : (ch >> 3) * 16)) : "memory");
  }
  asm volatile("cp.async.commit_group;" ::: "memory");
}

struct ConvC { uint32_t ca, cb, bands; };
__device__ __forceinline__ ConvC conv_consts(int w, int lane) {
  const int h = w & 1, P = w >> 1, d0 = 8 * h + (lane >> 2) - 2 * (lane & 3);
  ConvC k;
  k.ca = keep((W_KT + (16 + 256 * P + d0) * 4) | ((W_UP + (32 + 64 * P + lane) * 32 + ((h ^ (lane >> 2)) & 1) * 16) << 16));
  k.cb = keep(lane < 8 ? 0xFFFEFFFEu : ~0u);
  k.bands = keep(band(d0, 12, 20) + 2 * band(d0 + 8, 12, 20) + 4 * band(d0 + 16, 12, 20) + 8 * band(d0 + 24, 12, 20)
                 + 16 * band(d0 - 8, 5, 11) + 32 * band(d0, 5, 11) + 64 * band(d0 + 8, 5, 11) + 128 * band(d0 + 16, 5, 11));
  return k;
}
__device__ __forceinline__ void conv_item(uint32_t tb, const ConvC& cv, uint32_t zero, const CUtensorMap* tmx, int ch, int warp, int lane, bool rel) {
  const uint32_t kp = tb + (cv.ca & 0xFFFFu);
  const uint32_t dlo = ((tb + W_UP) >> 4) + 64 + (1u << 16), dhi = 16u | (3u << 30);
  const bool P = warp & 2;
  float a32[16], a96[48];
  uint32_t A[40][4];
#define STEP(J) { wgmma96<0>(a96, A[J], dlo + 64 - 2 * (J), dhi); if ((J) == 0) wgmma32_init<0>(a32, A[J], dlo, dhi); else if ((J) < 8) wgmma32<0>(a32, A[J], (dlo ^ zero) - 2 * (J), dhi); }
#define LD(J) load_a(A[J], kp, J);
#define FIRST(J) wg_fence(); STEP(J) wg_commit(); wg_wait<1>(); wg_fence();
  {
    uint32_t win[16], x9[4], x7[4], e[4], f[4];
    const uint32_t bz = keep(cv.bands);
#define BAND(i) keep((bz & (0x10001u << (i))) * (0x3C00u >> (i)))
    e[0] = lds32(kp + (P ? 3232 : 4096)); e[2] = lds32(kp + (P ? 3200 : 4064)); e[1] = keep(bz & 0x100u); e[3] = keep(bz & 0x200u);
    f[3] = lds32(kp + (P ? 3200 : 4128)); f[0] = keep(bz & 0x4000u); f[1] = keep(bz & 0x8000u); f[2] = keep(bz & 0x300u);
    const uint32_t q[12] = {BAND(0), BAND(5), keep(bz & 0x400u), BAND(4), BAND(2), BAND(7), BAND(1), BAND(6), keep(bz & 0x800u), keep(bz & 0x1000u), BAND(3), keep(bz & 0x2000u)};
#undef BAND
    if (ch < 512) check_tile(tb, tmx - 1, warp >> 2, ch & 127, warp >> 2, (warp & 3) * 32 + lane);
    TS(3);
    wg_fence();
    wgmma64h_init(win, q[0], q[1], q[2], q[3], dlo, dhi);
    wgmma64h(win, q[4], q[5], q[6], q[7], dlo - 2, dhi);
    wgmma64h(win, q[8], q[9], q[10], q[11], dlo - 4, dhi);
    wg_commit();
    wgmma96_init<0>(a96, e, dlo - 64, dhi);
    wgmma96<0>(a96, f, dlo - 50, dhi);
    wg_commit();
    wg_wait<1>();
#pragma unroll
    for (int i = 0; i < 4; i++) {
      const int tl = 2 * ((i & 1) + ((i & 2) ? 0 : 4));
      x9[i] = P ? win[tl + 4] : win[tl]; x7[i] = P ? win[tl + 5] : win[tl + 1];
    }
    const uint32_t l3lo = ((tb + W_L3) >> 4) + (32u << 16);
    wg_fence();
    wgmma96<0>(a96, x9, l3lo, 8);
    wgmma96<0>(a96, x7, l3lo + 128, 8);
    wg_commit();
  }
  LD(32) LD(33) LD(34) LD(35)
  FIRST(32) STEP(33) STEP(34) STEP(35) wg_commit();
  LD(36) LD(37) LD(38)
  FIRST(36) STEP(37) STEP(38) wg_commit();
  LD(39) LD(0)
  TS(17);
  if (X_REL == 1 && rel) bar_arrive(6, 640 - 128 * X_RW);
  FIRST(39) STEP(0) wg_commit();
  LD(1) LD(2) LD(3)
  FIRST(1) STEP(2) STEP(3) wg_commit();
  LD(4) LD(5)
  if (X_REL == 2 && rel) bar_arrive(6, 640 - 128 * X_RW);
  FIRST(4) STEP(5) wg_commit();
  LD(6) LD(7)
  wg_fence(); STEP(6) STEP(7) wg_commit();
#undef STEP
#undef LD
#undef FIRST
  TS(18);
  if (X_REL == 3 && rel) bar_arrive(6, 640 - 128 * X_RW);
  const uint32_t xc = tb + W_KT + (warp & 3) * 1024 + lane * 16;
  wg_wait<0>();
  uint32_t E[16], o[8];
#define ACC(i) ((i) < 16 ? a32[i] : a96[(i) - 16])
  E[0] = pack_h(a32[0], a32[1]);
#pragma unroll
  for (int i = 1; i < 16; i++) E[i] = pack_h(ACC(4 * i) + ACC(4 * i - 2), ACC(4 * i + 1) + ACC(4 * i - 1));
#undef ACC
#pragma unroll
  for (int j = 0; j < 8; j++) o[j] = P ? (j < 2 ? 0u : E[j - 2]) : E[8 + j];
  sts128(xc, o[0], o[1], o[2], o[3]); sts128(xc + 512, o[4], o[5], o[6], o[7]);
#pragma unroll
  for (int j = 0; j < 8; j++) o[j] = P ? E[6 + j] : E[j];
  TS(25);
  bar_sync(1 + (warp >> 2), 128);
  const uint4 vv[2] = {lds128(xc + (P ? -2048 : 2048)), lds128(xc + (P ? -1536 : 2560))};
#pragma unroll
  for (int q = 0; q < 2; q++) {
    const uint4 v = vv[q];
    stsm4t(tb + (cv.ca >> 16) + q * 1024, hadd2u(o[4 * q], v.x) & cv.cb, hadd2u(o[4 * q + 1], v.y) & cv.cb, hadd2u(o[4 * q + 2], v.z) & cv.cb, hadd2u(o[4 * q + 3], v.w) & cv.cb);
  }
  fence_async();
  bar_sync(1 + (warp >> 2), 128);
  if ((warp & 3) == 3 && lane == 0) {
    asm volatile("cp.async.bulk.tensor.2d.global.shared::cta.bulk_group [%0, {%2, %3}], [%1];" :: "l"(tmx), "r"(tb + W_UP + 1024), "r"(ch * 16), "r"(0) : "memory");
    asm volatile("cp.async.bulk.commit_group;" ::: "memory");
  }
}

template <bool FAR> __global__ void __launch_bounds__(NT, 1)
fused_kernel(const __grid_constant__ Params p, const __grid_constant__ TMaps tm) {
  extern __shared__ __align__(1024) unsigned char smem[];
  const int c = blockIdx.x;
  const bool five = (c & 1) == 0;
  const uint32_t pitch = five ? 64 : 80;
  const uint32_t ones = 0x3F803F80u;
  const int tid = threadIdx.x, lane = tid & 31;
  const int warp = (int)uni(tid >> 5), wg = warp >> 2;
  TS(0);
  if (__builtin_expect(wg == 4, 0)) {
    asm volatile("setmaxnreg.dec.sync.aligned.u32 32;");
    const int role = warp;
    const int u0 = (c >> 1) * 9 + (five ? ((c & 2) ? 5 : 0) : ((c & 2) ? 0 : 4));
    const uint32_t t0 = clock() + c * 4;
    if (role < 18) {
      const bool pf = role == 17;
      if (!pf) {
        if (lane < 19) asm volatile("mbarrier.init.shared::cta.b64 [%0], %1;" :: "r"(OFF_MISC + lane * 8), "r"((unsigned)(lane - 2) < 4u ? 4 : 1) : "memory");
        if (lane < 2) asm volatile("mbarrier.arrive.expect_tx.shared::cta.b64 _, [%0], %1;" :: "r"(OFF_MISC + lane * 8), "r"(lane ? (five ? 36864 : 51200) : pitch * 1152) : "memory");
        fence_async();
        bar_arrive(5, 576);
      } else if (smem_u32(smem) != SB) __trap();
      const CUtensorMap* tmb = &tm.m[five ? 3 : 0];
#pragma unroll 1
      for (int u = pf ? X_NE : 0; u < 17; u++) {
        const uint32_t e = p.sched[five][u], kind = e & 3, s = (e >> 2) & 15, dst = e >> 14;
        if (kind == 3) continue;
        while ((int)(clock() - t0) < X_PF0 + (pf || u < X_NE ? u * X_PFD : X_LAG + u * X_TD)) __nanosleep(20);
        if (!pf && (e & 0x3FC0)) mbar_wait(OFF_MISC + ((e >> 6) & 255));
        if (lane == 0) {
          if (pf) {
            if (kind == 2) asm volatile("cp.async.bulk.prefetch.tensor.3d.L2.global [%0, {%1, %2, %3}];" :: "l"(tmb + 2), "r"(0), "r"(u0 * 8), "r"(s) : "memory");
            else l2_prefetch((kind ? p.w_up : p.w_gate) + (uint32_t)(s * 884736 + c * 6912), 6912);
          } else if (kind == 2) asm volatile("cp.async.bulk.tensor.3d.shared::cluster.global.mbarrier::complete_tx::bytes [%0], [%1, {%3, %4, %5}], [%2];"
                                             :: "r"(dst), "l"(tmb + 2), "r"(MB_D), "r"(0), "r"(u0 * 8), "r"(s) : "memory");
          else tma_box(dst, tmb + kind, MB_GU, u0 * 8, s * 96);
        }
        if (u == 5) TS(2);
        if (u == 10) TS(3);
      }
      TS(4);
      TS_DUMP();
    } else if (role == 18) {
      sts32(MISC_EPOCH, 0);
      bar_arrive(5, 576);
      uint4* q = lane < 2 ? &p.s->R[c * 2 + lane] : lane < 11 ? &p.s->HS[c * 9 + lane - 2] : lane == 11 ? &p.s->HS[1152 + (c & 7)] : (uint4*)&p.s->FLAG[c * 8];
      if (lane < (c < 8 ? 12 : 11)) str128(q, ~0u, ~0u, ~0u, ~0u);
      const uint32_t ep = __shfl_sync(0xffffffffu, ldr32(q), 31) + 1u;
      sts32(MISC_EPOCH, ep | 0x80000000u);
      TSX(21);
      if (lane == 31) str32(q, ep);
      bar_sync(11, 64);
      if (lane == 0) { load_tile(&tm.m[6], 1, c); load_tile(&tm.m[6], 3, c); }
      TSX(14);
      mbar_wait(MB_KF + (lane & 3) * 8);
      __syncwarp();
      { const uint2 e = lds64(MISC_EM); if (lane < 2) str128(&p.s->SC[c * 2 + lane], e.x, __byte_perm(e.y, ep, 0x6540), 0, 0); }
      while ((int)(clock() - t0) < X_SCT) __nanosleep(100);
      {
        uint2 v[4];
#pragma unroll 1
        for (int it = 0; it < SPIN_MAX; it++) {
          uint32_t bad = 0;
#pragma unroll
          for (int q = 0; q < 4; q++) v[q] = ldr64(&p.s->SC[lane * 2 + q * 64]);
#pragma unroll
          for (int q = 0; q < 4; q++) bad |= (v[q].y >> 8) ^ (ep & 0xFFFFFFu);
          if (!__any_sync(0xffffffffu, bad)) break;
        }
#pragma unroll
        for (int q = 0; q < 4; q++) {
#pragma unroll
          for (int k = 0; k < 4; k++) asm volatile("st.shared.u8 [%0], %1;" :: "r"(sc_addr(4 * k + q) + lane), "r"(v[q].x >> (8 * k)) : "memory");
          if (lane & 1) asm volatile("st.shared.u8 [%0], %1;" :: "r"(sc_addr(16) + q * 16 + (lane >> 1)), "r"(v[q].y) : "memory");
        }
      }
      __syncwarp();
      if (lane == 0) mbar_arrive(MB_SC);
    } else {
      uint32_t w[9], d[9];
      float s = 0.f;
#pragma unroll
      for (int i = 0; i < 9; i++) { w[i] = ldnc32(p.w_r + (i < 8 ? lane * 4 + (i & 3) + (i >> 2) * 128 : 256 + lane)); d[i] = ldnc32(p.dskip + lane + 32 * i); }
#pragma unroll
      for (int i = 0; i < 9; i++) { sts32(OFF_WR + lane * 4 + i * 128, w[i]); sts32(OFF_WR + 1152 + lane * 4 + i * 128, d[i]); s += bf_lo(w[i]) + bf_hi(w[i]); }
      sts32(MISC_SW, __float_as_uint(warp_sum(s)));
      TSX(23);
      bar_sync(10, 544);
      if (lane == 0) {
        const uint32_t tp = clock();
        TSX(1);
        while ((int)(clock() - tp) < X_DELTA || (int)(clock() - t0) < X_ABS - c * 4) {}
        TSX(24);
        load_tile(&tm.m[6], 0, c);
        TSX(15);
        while ((int)(clock() - t0) < X_ABS + X_DSTEP - c * 4) {}
      }
      bar_sync(11, 64);
      if (lane == 0) {
        load_tile(&tm.m[6], 2, c);
        mbar_arrive(MB_GF);
        if (five) { mbar_wait(MB_KF); load_tile(&tm.m[6], 4, c); }
      }
      uint4* rp = &p.s->R[c * 2 + (lane & 1)];
      asm volatile("" : "+l"(rp));
      bar_sync(0, 544);
      if (lane == 0) mbar_arrive(MB_H);
      bar_sync(5, 544);
      const uint4 k = lds128(MISC_RK + (lane & 1) * 16);
      if (lane < 2) str128(rp, k.x, k.y, k.z, k.w);
    }
    return;
  }
  const int wt = tid & 127, g = lane >> 2, t = lane & 3;
  const uint32_t wb = OFF_W + wg * W_BYTES;
  const int lw = warp - (five ? 8 : 4);
  if ((unsigned)lw < 8u) {
    const unsigned char* xp = p.x + (uint32_t)((c * 8 + lw) * 2304 + lane * 16);
    const uint32_t row = OFF_YT + lw * (2 * YT_PITCH) + (lw >> 2) * 64 + lane * 16;
    { const uint32_t tq = clock(); while ((int)(clock() - tq) < X_XD) {} }
#pragma unroll
    for (int k = 0; k < 5; k++)
      if (k < 4 || lane < 16)
        asm volatile("cp.async.cg.shared.global [%0], [%1], 16;" :: "r"(row + k * 512 + ((k > 2 || (k == 2 && lane >= 8)) ? 32 : 0)), "l"(xp + k * 512) : "memory");
    asm volatile("cp.async.commit_group;" ::: "memory");
  } else load_params<FAR>(p, lw >= 8 ? 512 + (c >> 1) : wg * 128 + c, wt, wb + W_KT + (lw >= 8) * 2048);
  const ConvC cv = conv_consts(warp & 3, lane);
  zero_pads(wb, wt);
  if (lw >= 0) load_params<FAR>(p, wg * 128 + c, wt, wb + W_KT);
  asm volatile("setmaxnreg.inc.sync.aligned.u32 112;");
  {
    uint4 kw;
    uint4* kx = &p.s->KX[(c >> 1) * 128 + wt];
    bool two = wg == 3;
    uint32_t ep;
    int phase = (unsigned)lw < 8u ? 3 : 2;
#pragma unroll 1
    for (;;) {
      const bool first = two && !five;
      if (first || phase == 3) asm volatile("cp.async.wait_group 1;" ::: "memory"); else asm volatile("cp.async.wait_group 0;" ::: "memory");
      if (phase == 3) {
        __syncwarp();
        TS(21);
        float d[4][4];
#pragma unroll
        for (int r = 0; r < 2; r++) {
          const uint32_t row = OFF_YT + (2 * lw + r) * YT_PITCH + (lw >> 2) * 64;
          const uint4 a = lds128(row + lane * 16), b = lds128(row + 512 + lane * 16);
          const uint32_t e = lds32(row + 1024 + lane * 4);
#pragma unroll
          for (int i = 0; i < 4; i++) d[r][i] = d[r + 2][i] = 0.f;
          mma_bf16(d[r], a.x, ones, a.y, ones, a.x, a.y); mma_bf16(d[r + 2], a.z, ones, a.w, ones, a.z, a.w);
          mma_bf16(d[r], b.x, ones, b.y, ones, b.x, b.y); mma_bf16(d[r + 2], b.z, ones, b.w, ones, b.z, b.w);
          mma_bf16_k8(d[r], e, ones, e);
#pragma unroll
          for (int i = 0; i < 4; i++) d[r][i] += d[r + 2][i];
        }
        const float q0 = __shfl_sync(0xffffffffu, d[0][0], 9 * t) + __shfl_sync(0xffffffffu, d[0][1], 9 * t + 4);
        const float q1 = __shfl_sync(0xffffffffu, d[1][0], 9 * t) + __shfl_sync(0xffffffffu, d[1][1], 9 * t + 4);
        float r;
        const LnC lc = ln_consts(quad_sum(lane & 16 ? d[1][2] + d[1][3] : d[0][2] + d[0][3]), quad_sum(lane & 16 ? q1 : q0), r);
        if ((lane & 15) < 3) sts16(MISC_LN1 + (lane & 15) * 32 + lw * 4 + (lane >> 4) * 2, t == 0 ? lc.m2 : t == 1 ? lc.rh2 : lc.rl2);
      } else {
        KgState ks;
        uint32_t raw[7];
        bar_sync(1 + wg, 128);
        TS(22);
#pragma unroll
        for (int i = 0; i < 7; i++) raw[i] = lds16(wb + W_KT + first * 2048 + i * 256 + (i < 6 ? wt : (c >> first) & 7) * 2);
        kgen_tables_n(raw, wb, wt, ks);
        TS(20);
        bar_sync(1 + wg, 128);
        const int em = kgen_tables_m(wb, wt, ks);
        asm volatile("st.shared.u8 [%0], %1;" :: "r"(MISC_EM + wg + first), "r"(em + 9) : "memory");
        fence_async();
      }
      if (phase & 2) {
        const uint32_t tr_addr = tr_base(lane) + warp * 32;
        uint4* dst = &p.s->X[c * DM * 2 + warp * 32 + (8 * (t >> 1) + g) * 2 + (t & 1)];
        TS(23);
        bar_sync(5, 576);
        uint32_t x[3][4];
        ldsm4t(tr_addr, x[0][0], x[0][1], x[0][2], x[0][3]);
        const uint4 m = lds128(MISC_LN1 + (t & 1) * 16), rl = lds128(MISC_LN1 + 64 + (t & 1) * 16), rh = lds128(MISC_LN1 + 32 + (t & 1) * 16);
        ldsm4t(tr_addr + 512, x[1][0], x[1][1], x[1][2], x[1][3]);
        if (wg == 2) ldsm4t(tr_addr + 768, x[2][0], x[2][1], x[2][2], x[2][3]);
#pragma unroll
        for (int q = 0; q < 3; q++) {
          if (q < 2 || wg == 2) {
            const uint32_t r0 = ln_apply(x[q][0], m.x, rh.x, rl.x), r1 = ln_apply(x[q][1], m.y, rh.y, rl.y), r2 = ln_apply(x[q][2], m.z, rh.z, rl.z), r3 = ln_apply(x[q][3], m.w, rh.w, rl.w);
            str128(dst + q * 512 - (q == 2 ? 256 : 0), (pack_h(bf_lo(r0), bf_hi(r0)) & 0xFFFEFFFEu) | 1u, pack_h(bf_lo(r1), bf_hi(r1)), pack_h(bf_lo(r2), bf_hi(r2)), pack_h(bf_lo(r3), bf_hi(r3)));
          }
          if (q == 0) TS(30);
        }
        bar_arrive(10, 544);
        TS(1);
      } else bar_sync(1 + wg, 128);
      phase &= 1;
      if (phase) { phase = 0; continue; }
      TS(14);
      float acc[20];
      const uint32_t alo = (wb >> 4) | (8u << 16);
      wg_fence();
      wgmma40_ss_init(acc, alo, alo + 1024, 2048 >> 4);
#pragma unroll
      for (int k = 1; k < 8; k++) wgmma40_ss(acc, alo + k * 16, alo + 1024 + k * 16, 2048 >> 4);
      wg_commit();
      if (two && five) {
        asm volatile("cp.async.cg.shared.global [%0], [%1], 16;" :: "r"(OFF_K5 + wt * 16), "l"(kx) : "memory");
        asm volatile("cp.async.commit_group;" ::: "memory");
      }
      const uint4 k4 = lds128(wb + W_MISC + 16);
      const float k2048 = (float)(int)(k4.x + k4.y + k4.z + k4.w) * (1.f / 262144.f);
      wg_wait<0>();
      const float un = 1.f / 8192.f;
      kw.x = pack_h((acc[0] - acc[3]) * un, (acc[4] - acc[7]) * un);
      kw.y = pack_h((acc[8] - acc[11]) * un, (acc[12] - acc[15]) * un);
      kw.z = pack_h((acc[16] - acc[19]) * un, k2048 * un);
      TS(24);
      ep = 0;
      if (two) SPIN_WHILE(ep == 0, ep = lds32(MISC_EPOCH));
      if (five || !two) break;
      str128(kx, kw.x, kw.y, kw.z, ep);
      two = false;
    }
    if (lane == 0) mbar_arrive(MB_KF + wg * 8);
    if (two) { mbar_wait(MB_KF); zero_pads(OFF_W + ALT, wt); }
    uint32_t tb = wb;
#pragma unroll 1
    for (;;) {
      kgen_build(tb, wg, wt, kw.x, kw.y, kw.z);
      TS(15);
      if (!two) break;
      two = false;
      asm volatile("cp.async.wait_group 0;" ::: "memory");
      kw = lds128(OFF_K5 + wt * 16);
      SPIN_WHILE(kw.w != ep, kw = ldr128(kx));
      tb = OFF_W + ALT;
    }
    fence_async();
    TS(31);
    if (tb != wb) { check_tile(tb, &tm.m[6], 4, c, wg, wt); bar_arrive(7, 256); } else bar_sync(1 + wg, 128);
  }
  uint32_t tpub;
#pragma unroll 1
  for (int item = 0;; item++) {
    if (X_REL && five && wg >= X_RW) bar_sync(6, 640 - 128 * X_RW);
    TS(2);
    conv_item(item ? OFF_W + ALT : wb, cv, p.zero, &tm.m[7], item ? 512 + (c >> 1) : wg * 128 + c, warp, lane, five && !wg && !item);
    tpub = clock() - item * X_YD;
    if (wg || !five || item) break;
    TS(27);
    bar_sync(7, 256);
  }
  TS(4);

  const int ln = lane ^ p.zero, td = warp * 32 + ln, gg = ln >> 2, tt = ln & 3;
  const int tok = c * 16 + warp;
  const int fu = warp / 3, fk = warp - fu * 3;
  uint32_t wa[12][4];
  {
    uint32_t hw[9], wr[9];
    const uint32_t row = keep(OFF_YT + warp * YT_PITCH + (warp >> 3) * 64 + ln * 16);
    const uint32_t wabase = keep(((ln & 8) ? OFF_W + (fk + 1) * W_BYTES : OFF_G + fk * 192 * pitch) + ((ln >> 4) * 8 + (ln & 7)) * pitch
                                 + (five ? ((fu ^ (ln >> 1)) & 3) : min(fu, 4)) * 16);
    float sw;
    {
      const uint4 m = lds128(MISC_LN1 + (tt & 1) * 16), rh = lds128(MISC_LN1 + 32 + (tt & 1) * 16), rl = lds128(MISC_LN1 + 64 + (tt & 1) * 16);
      mbar_wait(MB_SC);
#pragma unroll
      for (int i = 0; i < 9; i++) wr[i] = lds32(OFF_WR + ln * 4 + i * 128);
      sw = __uint_as_float(lds32(MISC_SW));
#pragma unroll 1
      for (int tp = warp;; tp += 12) {
        const int ch = tp * 32 + 8 * (tt >> 1) + gg;
        const uint32_t tr_addr = tr_base(ln) + tp * 64;
        const uint4* ysrc = &p.s->X[c * DM * 2 + ch * 2 + (tt & 1)];
        uint32_t x[2][4], ud[2][4], s[2];
#pragma unroll
        for (int q = 0; q < 2; q++) {
          asm volatile("ld.shared.u8 %0, [%1];" : "=r"(s[q]) : "r"(sc_addr(tp) + (ch & 31) + q * 16) : "memory");
          s[q] *= 0x800080u;
          const uint32_t dk = lds16(OFF_WR + 1152 + ch * 2 + q * 32) * 0x10001u;
          ldsm4t(tr_addr + q * 32, x[q][0], x[q][1], x[q][2], x[q][3]);
          ud[q][0] = bf_mul2(ln_apply(x[q][0], m.x, rh.x, rl.x), dk); ud[q][1] = bf_mul2(ln_apply(x[q][1], m.y, rh.y, rl.y), dk);
          ud[q][2] = bf_mul2(ln_apply(x[q][2], m.z, rh.z, rl.z), dk); ud[q][3] = bf_mul2(ln_apply(x[q][3], m.w, rh.w, rl.w), dk);
        }
        asm volatile("cp.async.bulk.wait_group.read 0;" ::: "memory");
        while ((int)(clock() - tpub) < X_YD) {}
        TS(5);
        uint4 v[2];
        v[0] = ldr128(ysrc); v[1] = ldr128(ysrc + 32);
        SPIN_WHILE((v[0].x | v[1].x) & 1u, if (v[0].x & 1u) v[0] = ldr128(ysrc); if (v[1].x & 1u) v[1] = ldr128(ysrc + 32));
#pragma unroll
        for (int q = 0; q < 2; q++) {
          const uint32_t s2 = s[q];
          stsm4t(tr_addr + q * 32, bf_add2(x[q][0], bf_fma2(h2bf(v[q].x), s2, ud[q][0])), bf_add2(x[q][1], bf_fma2(h2bf(v[q].y), s2, ud[q][1])),
                 bf_add2(x[q][2], bf_fma2(h2bf(v[q].z), s2, ud[q][2])), bf_add2(x[q][3], bf_fma2(h2bf(v[q].w), s2, ud[q][3])));
        }
        if ((tp & ~1) != 4) break;
      }
    }
    TS(28);
    bar_sync(0, 544);
    TS(6);
    float d[4] = {0.f, 0.f, 0.f, 0.f}, e[4] = {0.f, 0.f, 0.f, 0.f}, rd;
    {
      const uint4 a = lds128(row), b = lds128(row + 512);
      hw[8] = lds32(row + 1024 - ln * 12);
      hw[0] = a.x; hw[1] = a.y; hw[2] = a.z; hw[3] = a.w; hw[4] = b.x; hw[5] = b.y; hw[6] = b.z; hw[7] = b.w;
    }
    mma_bf16(e, hw[0], hw[1], hw[2], hw[3], ones, ones);
#pragma unroll
    for (int i = 0; i < 8; i += 2) mma_bf16(d, hw[i], wr[i], hw[i + 1], wr[i + 1], hw[i], hw[i + 1]);
    mma_bf16(e, hw[4], hw[5], hw[6], hw[7], ones, ones);
    e[0] += e[2];
    mma_bf16_k8(e, hw[8], wr[8], ones);
    mma_bf16_k8(d, hw[8], wr[8], hw[8]);
    const float hwsum = diag_sum(d[2], d[3], tt);
    LnC l2 = ln_consts(diag_sum(e[0], e[0], tt), diag_sum(d[0], d[1], tt), rd);
    const uint32_t b = pack_bf(0.f, fmaf(-bf_lo(l2.m2), sw, hwsum) * rd);
    uint32_t key = max(min((b ^ (((int)b >> 31) | 0x80000000u)) >> 16, 0xFFFEu), 1u);
    sts16(MISC_RK + warp * 2, key);
    bar_sync(5, 544);
    asm volatile("" : "+r"(l2.m2) :: "memory");
    TS(7);
    const uint32_t tr0 = clock();
    key = (key << 16) | (2047 - tok);
    uint32_t loc = ln < 16 ? (lds16(MISC_RK + ln * 2) << 16) | (2047 - c * 16 - ln) : 0u;
    int rank = __popc(__ballot_sync(0xffffffffu, loc > key));
#pragma unroll
    for (int i = 0; i < 9; i++) wr[i] = keep(ln_apply(hw[i], l2.m2, l2.rh2, l2.rl2));
    const uint2* rsrc = (const uint2*)p.s->R + td;
    while ((int)(clock() - tr0) < X_RD) {}
    uint2 rv = ldr64(rsrc);
    mbar_wait(MB_GU);
    if (warp < (five ? 12 : 15)) {
#pragma unroll
      for (int k = 0; k < X_WS; k++) ldsm4t(wabase + k * 16 * pitch, wa[k][0], wa[k][1], wa[k][2], wa[k][3]);
    }
#define OUT_ROW { uint32_t* o = p.out + tok * 288 + ln * 4; \
      *(uint4*)o = make_uint4(bf_add2(hw[0], wr[0]), bf_add2(hw[1], wr[1]), bf_add2(hw[2], wr[2]), bf_add2(hw[3], wr[3])); \
      *(uint4*)(o + 128) = make_uint4(bf_add2(hw[4], wr[4]), bf_add2(hw[5], wr[5]), bf_add2(hw[6], wr[6]), bf_add2(hw[7], wr[7])); \
      o[256 - ln * 3] = bf_add2(hw[8], wr[8]); }
    if (rank >= X_OR) OUT_ROW
#pragma unroll 1
    for (int base = 0; base < 8; base += 4) {
      uint32_t T[4];
#pragma unroll
      for (int j = 0; j < 4; j++) {
        const uint32_t mx = __reduce_max_sync(0xffffffffu, loc);
        if (loc == mx) loc = 0;
        T[j] = (td >> 2) == c ? ~0u : (td >> 2) < c ? (mx & 0xFFFF0000u) - 1u : mx | 0xFFFFu;
      }
      const uint32_t sh = keep(ln < 16 ? 0x4440u + (rank & 3) : 0x4344u), ca = keep(MISC_CNT + base * 16 + (ln & 15) * 4);
      SPIN_WHILE(rv.x == ~0u, if (rv.x == ~0u) rv = ldr64(rsrc));
      TS(16);
      uint32_t cnt = 0, cn2 = 0;
#pragma unroll
      for (int j = 0; j < 4; j++)
        asm("{ .reg .pred a, b, c, d; setp.gt.u32 a, %2, %6; setp.gt.u32 b, %3, %6; setp.gt.u32 c, %4, %6; setp.gt.u32 d, %5, %6; "
            "@a add.u32 %0, %0, %7; @b add.u32 %1, %1, %7; @c add.u32 %0, %0, %7; @d add.u32 %1, %1, %7; }"
            : "+r"(cnt), "+r"(cn2) : "r"(rv.x), "r"(rv.x << 16), "r"(rv.y), "r"(rv.y << 16), "r"(T[j]), "r"(1u << (8 * j)));
      sts32(MISC_CNT + base * 16 + warp * 4, __reduce_add_sync(0xffffffffu, cnt + cn2));
      bar_sync(0, 512);
      cnt = __reduce_add_sync(0xffffffffu, __byte_perm(lds32(ca), 0, sh));
      if ((rank & ~3) == base && rank + (int)(cnt & 0xFFFFu) < 8) {
        rank += cnt & 0xFFFFu;
        uint4* hs = p.s->HS + rank * 72 + ln;
        str128(hs, wr[0], wr[1], wr[2], wr[3]); str128(hs + 32, wr[4], wr[5], wr[6], wr[7]); str32((uint32_t*)(hs + 64) - ln * 3, wr[8]);
        str128(hs + 576, hw[0], hw[1], hw[2], hw[3]); str128(hs + 608, hw[4], hw[5], hw[6], hw[7]); str32((uint32_t*)(hs + 640) - ln * 3, hw[8]);
        if (ln == 0) str32(&p.s->HS[1152 + rank], key);
        rank = 16;
      }
      if (cnt >= (4u << 16)) break;
    }
    TS(8);
    tpub = clock();
    if (rank < X_OR) OUT_ROW
    if (warp < (five ? 12 : 15)) {
#pragma unroll
      for (int k = X_WS; k < 12; k++) ldsm4t(wabase + k * 16 * pitch, wa[k][0], wa[k][1], wa[k][2], wa[k][3]);
    }
  }
  uint32_t wd[10][4];
  const uint32_t xb = keep(OFF_XS + (ln & 7) * 1168 + (fk * 24 + (ln >> 3)) * 16);
  if (warp >= 7) {
    const uint32_t db = down_box(warp - 7, five) + (ln & 7) * 128;
    mbar_wait(MB_D);
#pragma unroll
    for (int j = 0; j < 4; j++) {
      const uint32_t a = db + (ln >> 4) * 1024 + (((2 * j + ((ln >> 3) & 1)) ^ (ln & 7)) << 4);
      ldsm4t(a, wd[j][0], wd[j][1], wd[j][2], wd[j][3]);
      ldsm4t(a + 2048, wd[4 + j][0], wd[4 + j][1], wd[4 + j][2], wd[4 + j][3]);
    }
#pragma unroll
    for (int j = 0; j < 2; j++) ldsm4t(db + 4096 + (((4 * j + (ln >> 3)) ^ (ln & 7)) << 4), wd[8 + j][0], wd[8 + j][1], wd[8 + j][2], wd[8 + j][3]);
  } else if (warp < 6) {
    const int r = td / 24;
    const uint4* src = &p.s->HS[td + r * 48];
    const uint32_t xs = keep(OFF_XS + (td + r * 49) * 16);
    uint4 a[3];
    uint32_t m = ~0u;
    while ((int)(clock() - tpub) < X_HD) {}
    TS(19);
    SPIN_WHILE(m == ~0u, if (m == ~0u) { a[0] = ldr128(src); a[1] = ldr128(src + 24); a[2] = ldr128(src + 48); } m = max(max(max(a[0].x, a[1].x), max(a[2].x, a[2].y)), max(a[2].z, a[2].w)));
#pragma unroll
    for (int q = 0; q < 3; q++) sts128(xs + q * 384, a[q].x, a[q].y, a[q].z, a[q].w);
  }
  bar_sync(0, 512);
  TS(9);

  if (warp < (five ? 12 : 15)) {
    float d0[4] = {0.f, 0.f, 0.f, 0.f}, d1[4] = {0.f, 0.f, 0.f, 0.f};
#pragma unroll
    for (int k = 0; k < 12; k += 2) {
      uint32_t b0, b1, b2, b3;
      ldsm4(xb + k * 32, b0, b1, b2, b3);
      mma_bf16(d0, wa[k][0], wa[k][1], wa[k][2], wa[k][3], b0, b1);
      mma_bf16(d1, wa[k + 1][0], wa[k + 1][1], wa[k + 1][2], wa[k + 1][3], b2, b3);
    }
    sts128(OFF_RED + td * 16, __float_as_uint(d0[0] + d1[0]), __float_as_uint(d0[1] + d1[1]), __float_as_uint(d0[2] + d1[2]), __float_as_uint(d0[3] + d1[3]));
  }
  TS(26);
  if (warp < 5) {
    const uint32_t rb = OFF_RED + warp * 1536 + ln * 16;
    bar_sync(9, 512);
    const uint4 pa = lds128(rb), pb = lds128(rb + 512), pc = lds128(rb + 1024);
    const float ga = bfr(__uint_as_float(pa.x) + __uint_as_float(pb.x) + __uint_as_float(pc.x));
    const float gb = bfr(__uint_as_float(pa.y) + __uint_as_float(pb.y) + __uint_as_float(pc.y));
    const uint32_t uu = pack_bf(__uint_as_float(pa.z) + __uint_as_float(pb.z) + __uint_as_float(pc.z), __uint_as_float(pa.w) + __uint_as_float(pb.w) + __uint_as_float(pc.w));
    float ra, rb2;
    asm("rcp.approx.ftz.f32 %0, %1;" : "=f"(ra) : "f"(1.f + ex2(ga * -1.4426950408889634f)));
    asm("rcp.approx.ftz.f32 %0, %1;" : "=f"(rb2) : "f"(1.f + ex2(gb * -1.4426950408889634f)));
    const uint32_t act = bf_mul2(pack_bf(ga * ra, gb * rb2), uu);
    sts32(OFF_ACT + td * 4, act);
  } else bar_arrive(9, 512);
  uint4* dst = &p.s->X[c * DM * 2 + (warp - 7) * 64 + tt * 8 + gg];
  asm volatile("" : "+l"(dst));
  bar_sync(8, 512);
  tpub = clock();
  if (warp >= 7) {
    uint32_t b0, b1, b2, b3, b4;
    ldsm4t(OFF_ACT + ln * 16, b0, b1, b2, b3);
    asm volatile("ldmatrix.sync.aligned.m8n8.x1.trans.shared.b16 {%0}, [%1];" : "=r"(b4) : "r"(OFF_ACT + 512 + ln * 16) : "memory");
    float y[4][4];
#pragma unroll
    for (int j = 0; j < 4; j++) {
      y[j][0] = y[j][1] = y[j][2] = y[j][3] = 0.f;
      mma_bf16(y[j], wd[j][0], wd[j][1], wd[j][2], wd[j][3], b0, b1);
    }
#pragma unroll
    for (int j = 0; j < 4; j++) mma_bf16(y[j], wd[4 + j][0], wd[4 + j][1], wd[4 + j][2], wd[4 + j][3], b2, b3);
    if (!five) {
#pragma unroll
      for (int j = 0; j < 4; j++) mma_bf16_k8(y[j], wd[8 + (j >> 1)][2 * (j & 1)], wd[8 + (j >> 1)][2 * (j & 1) + 1], b4);
    }
    str128(dst, (pack_bf(y[0][0], y[0][1]) & ~1u) | 0x10000u, pack_bf(y[0][2], y[0][3]), pack_bf(y[1][0], y[1][1]), pack_bf(y[1][2], y[1][3]));
    str128(dst + 32, (pack_bf(y[2][0], y[2][1]) & ~1u) | 0x10000u, pack_bf(y[2][2], y[2][3]), pack_bf(y[3][0], y[3][1]), pack_bf(y[3][2], y[3][3]));
  }
  TS(10);

  if (c < 72) {
    const uint4* src = &p.s->X[(warp * 4 + tt) * (DM * 2) + c * 8 + gg];
    const int slot = (c & 3) * 2 + (ln >> 4), dw = (c >> 2) * 16 + (ln & 15);
    uint32_t hv = 0, kv = 0, res = 0, rs2 = 0;
    uint32_t* o = p.out;
    if (warp == 0) {
      hv = ~0u;
      SPIN_WHILE(max(hv, kv) == ~0u, hv = ldr32((const uint32_t*)p.s->HS + 2304 + slot * 288 + dw); kv = ldr32(&p.s->HS[1152 + slot]));
      const float r = bf_hi(kv ^ (((int)~kv >> 31) | 0x80000000u));
      float rs;
      asm("rcp.approx.ftz.f32 %0, %1;" : "=f"(rs) : "f"(1.f + ex2(r * -1.4426950408889634f)));
      rs2 = keep(pack_bf(rs, rs));
      res = lds32(OFF_XS + slot * 1168 + dw * 4);
      o += (2047 - (int)(kv & 2047u)) * 288 + dw;
      asm volatile("" : "+l"(o));
    }
    const uint32_t sel = (gg & 1) ? 0x3F800000u : 0x00003F80u;
    const uint32_t q0 = keep((gg >> 1) == 0 ? sel : 0u), q1 = keep((gg >> 1) == 1 ? sel : 0u), q2 = keep((gg >> 1) == 2 ? sel : 0u), q3 = keep((gg >> 1) == 3 ? sel : 0u);
    const uint32_t fa = keep(OFF_FIN + warp * 256 + (gg & 1) * 128 + (gg >> 1) * 32 + tt * 8), fb = keep(OFF_FIN + ln * 8);
    uint4 a0 = make_uint4(0, 0, 0, 0), a1 = a0;
    while ((int)(clock() - tpub) < X_PD) {}
    SPIN_WHILE(!(a0.x & a1.x & 0x10000u), if (!(a0.x & 0x10000u)) a0 = ldr128(src); if (!(a1.x & 0x10000u)) a1 = ldr128(src + 64 * DM * 2));
    float d[4] = {0.f, 0.f, 0.f, 0.f}, e[4] = {0.f, 0.f, 0.f, 0.f};
    mma_bf16(d, q0, q2, q1, q3, a0.x, a0.y); mma_bf16(e, q0, q2, q1, q3, a0.z, a0.w);
    mma_bf16(d, q0, q2, q1, q3, a1.x, a1.y); mma_bf16(e, q0, q2, q1, q3, a1.z, a1.w);
    sts64(fa, __float_as_uint(d[0] + e[2]), __float_as_uint(d[1] + e[3]));
    TS(11);
    if (warp == 0) {
      bar_sync(0, 512);
      float2 s[16];
#pragma unroll
      for (int i = 0; i < 16; i++) { const uint2 q = lds64(fb + i * 256); s[i] = make_float2(__uint_as_float(q.x), __uint_as_float(q.y)); }
#pragma unroll
      for (int k = 1; k < 16; k *= 2)
#pragma unroll
        for (int i = 0; i < 16; i += 2 * k) { s[i].x += s[i + k].x; s[i].y += s[i + k].y; }
      *o = bf_add2(hv, bf_add2(res, bf_mul2(pack_bf(s[0].x, s[0].y), rs2)));
    } else bar_arrive(0, 512);
  }
  TS(12);
  TS_DUMP();
}

typedef CUresult (*EncodeFn)(CUtensorMap*, CUtensorMapDataType, cuuint32_t, void*, const cuuint64_t*, const cuuint64_t*, const cuuint32_t*,
                             const cuuint32_t*, CUtensorMapInterleave, CUtensorMapSwizzle, CUtensorMapL2promotion, CUtensorMapFloatOOBfill);

}

extern "C" void kernel_launch(void* const* d_in, const int* in_sizes, int n_in, void* d_out, int out_size) {
  (void)in_sizes; (void)n_in; (void)out_size;
  static EncodeFn enc = nullptr;
  static Scratch* scratch = nullptr;
  if (!enc) {
    void* fn = nullptr;
    cudaDriverEntryPointQueryResult qr;
    cudaGetDriverEntryPoint("cuTensorMapEncodeTiled", &fn, cudaEnableDefault, &qr);
    enc = (EncodeFn)fn;
    cudaGetSymbolAddress((void**)&scratch, g_S);
    cudaFuncSetAttribute(fused_kernel<false>, cudaFuncAttributeMaxDynamicSharedMemorySize, SMEM_BYTES);
    cudaFuncSetAttribute(fused_kernel<true>, cudaFuncAttributeMaxDynamicSharedMemorySize, SMEM_BYTES);
  }
  TMaps tm;
  for (int i = 0; i < 6; i++) {
    const bool dn = i % 3 == 2;
    const cuuint32_t w = i < 3 ? 40 : 32;
    cuuint64_t gd[3] = {(cuuint64_t)(dn ? 64 : FF), (cuuint64_t)(dn ? FF : DM), 9};
    cuuint64_t gs[2] = {(cuuint64_t)(dn ? DM * 2 : FF * 2), 128};
    cuuint32_t bx[3] = {dn ? 64 : w, dn ? w : 96, i < 3 ? 2u : 3u};
    cuuint32_t es[3] = {1, 1, 1};
    enc(&tm.m[i], CU_TENSOR_MAP_DATA_TYPE_BFLOAT16, dn ? 3 : 2, d_in[11 + i % 3], gd, gs, bx, es, CU_TENSOR_MAP_INTERLEAVE_NONE,
        dn ? CU_TENSOR_MAP_SWIZZLE_128B : i < 3 ? CU_TENSOR_MAP_SWIZZLE_NONE : CU_TENSOR_MAP_SWIZZLE_64B,
        CU_TENSOR_MAP_L2_PROMOTION_NONE, CU_TENSOR_MAP_FLOAT_OOB_FILL_NONE);
  }
  for (int i = 6; i < 8; i++) {
    cuuint64_t gd[2] = {DM * 16, NCTA};
    cuuint64_t gs[1] = {DM * 32};
    cuuint32_t bx[2] = {16, i == 6 ? 160u : 128u};
    cuuint32_t es[2] = {1, 1};
    enc(&tm.m[i], CU_TENSOR_MAP_DATA_TYPE_FLOAT16, 2, scratch->X, gd, gs, bx, es, CU_TENSOR_MAP_INTERLEAVE_NONE, CU_TENSOR_MAP_SWIZZLE_32B,
        CU_TENSOR_MAP_L2_PROMOTION_NONE, CU_TENSOR_MAP_FLOAT_OOB_FILL_NONE);
  }
  Params p;
  p.x = (const unsigned char*)d_in[0];
  bool far = false;
  for (int i = 0; i < 7; i++) {
    p.far[i] = (const unsigned char*)d_in[1 + i];
    const long long d = (long long)((intptr_t)d_in[1 + i] - (intptr_t)d_in[0]);
    p.off[i] = (int)(d / 16);
    if ((long long)p.off[i] * 16 != d) far = true;
  }
  p.dskip = (const uint32_t*)d_in[8];
  p.w_r = (const uint32_t*)d_in[10];
  p.w_gate = (const unsigned char*)d_in[11];
  p.w_up = (const unsigned char*)d_in[12];
  for (int f = 0; f < 2; f++) {
    static const int kind[17] = {0, 0, 0, 0, 0, 0, 1, 1, 1, 1, 1, 1, 2, 2, 2, 2, 2};
    static const int idx[2][17] = {{3, 4, 5, 0, 1, 2, 0, 1, 2, 3, 4, 5, 6, 8, 0, 2, 4}, {3, 4, 5, 0, 1, 2, 0, 1, 2, 3, 4, 5, 0, -1, 3, -1, 6}};
    static const int blk[2][17] = {{-1, -1, -1, -1, -1, -1, 1, -1, 2, -1, 3, -1, 16, -1, -1, -1, -1}, {-1, -1, -1, -1, -1, -1, 1, -1, 2, -1, 3, -1, 16, -1, -1, -1, -1}};
    const int pitch = f ? 64 : 80;
    for (int u = 0; u < 17; u++) {
      const int s = idx[f][u];
      const uint32_t dst = kind[u] == 0 ? OFF_G + s * 96 * pitch : kind[u] == 2 ? down_box(s, f) : OFF_W + W_BYTES + (s >> 1) * W_BYTES + (s & 1) * 96 * pitch;
      const uint32_t mb = u == X_NE ? MB_GF - OFF_MISC : blk[f][u] >= 0 ? MB_KF - OFF_MISC + blk[f][u] * 8 : 0;
      p.sched[f][u] = s < 0 ? 3u : kind[u] | s << 2 | mb << 6 | dst << 14;
    }
  }
  p.out = (uint32_t*)d_out;
  p.zero = 0;
  p.ts = nullptr;
  p.s = scratch;
  if (far) { fused_kernel<true><<<NCTA, NT, SMEM_BYTES, cudaStreamPerThread>>>(p, tm); return; }
  fused_kernel<false><<<NCTA, NT, SMEM_BYTES, cudaStreamPerThread>>>(p, tm);
}
```

```cpp
#include <cuda_runtime.h>
#include <cuda.h>
#include <cuda_bf16.h>
#include <cuda_fp16.h>
#include <stdint.h>
#include <stddef.h>

namespace {

constexpr int NCTA = 128;
constexpr int NT = 640;
constexpr int DM = 576;
constexpr int FF = 4608;
constexpr int SPIN_MAX = 1 << 20;

struct Scratch {
  uint4 X[NCTA * DM * 2];
  uint4 KX[64 * 128];
  uint4 HS[1152 + 8];
  uint4 R[256];
  uint4 SC[256];
  uint32_t FLAG[NCTA * 8];
};
__device__ Scratch g_S;

#define TS(i)
#define TSX(i)
#define TS_DUMP()

constexpr int SB = 1024;
constexpr int BOX = 15360;
constexpr int OFF_G = SB;
constexpr int OFF_W = OFF_G + 3 * BOX;
constexpr int W_UP = 26624;
constexpr int W_KT = W_UP + 5120;
constexpr int W_L3 = W_KT + 4416;
constexpr int W_CW = W_L3 + 4096;
constexpr int W_MISC = W_CW + 640;
constexpr int W_BYTES = 40960;
constexpr int ALT = -W_UP;
static_assert(W_MISC + 32 <= W_BYTES && OFF_W % 1024 == 0 && W_UP % 256 == 0 && W_BYTES + ALT + 3 * 4096 <= W_UP, "wg block");
constexpr int YT_PITCH = 1184;
constexpr int OFF_YT = OFF_W + 4 * W_BYTES;
constexpr int OFF_WR = OFF_YT + 16 * YT_PITCH + 64;
constexpr int OFF_MISC = OFF_WR + 2304;
constexpr int SMEM_BYTES = OFF_MISC + 1024 - SB;
static_assert(OFF_YT % 16 == 0 && OFF_MISC % 16 == 0, "align");
static_assert(SMEM_BYTES <= 232448, "smem");
constexpr int MB_GU = OFF_MISC;
constexpr int MB_D = OFF_MISC + 8;
constexpr int MB_KF = OFF_MISC + 16;
constexpr int MB_GF = OFF_MISC + 48;
constexpr int MB_SC = OFF_MISC + 56;
constexpr int MB_UL = OFF_MISC + 64;
constexpr int MB_REL = OFF_MISC + 104;
constexpr int MB_H = MB_KF + 128;
constexpr int MISC_EPOCH = OFF_MISC + 152;
constexpr int MISC_SW = OFF_MISC + 156;
constexpr int MISC_EM = OFF_MISC + 288;
constexpr int MISC_RK = OFF_MISC + 160;
constexpr int MISC_LN1 = OFF_MISC + 192;
constexpr int OFF_XS = OFF_W + W_BYTES + W_UP;
constexpr int OFF_RED = OFF_W + 2 * W_BYTES + W_UP;
constexpr int OFF_FIN = OFF_W + 3 * W_BYTES + W_UP;
constexpr int OFF_ACT = OFF_FIN + 4096;
constexpr int MISC_CNT = OFF_ACT + 1024;

__device__ __forceinline__ uint32_t smem_u32(const void* p) { return (uint32_t)__cvta_generic_to_shared(p); }
__device__ __forceinline__ uint32_t lds32(uint32_t a) { uint32_t v; asm volatile("ld.shared.b32 %0, [%1];" : "=r"(v) : "r"(a) : "memory"); return v; }
__device__ __forceinline__ uint32_t lds16(uint32_t a) { uint16_t v; asm volatile("ld.shared.u16 %0, [%1];" : "=h"(v) : "r"(a) : "memory"); return v; }
__device__ __forceinline__ uint2 lds64(uint32_t a) { uint2 v; asm volatile("ld.shared.v2.b32 {%0,%1}, [%2];" : "=r"(v.x), "=r"(v.y) : "r"(a) : "memory"); return v; }
__device__ __forceinline__ uint4 lds128(uint32_t a) { uint4 v; asm volatile("ld.shared.v4.b32 {%0,%1,%2,%3}, [%4];" : "=r"(v.x), "=r"(v.y), "=r"(v.z), "=r"(v.w) : "r"(a) : "memory"); return v; }
__device__ __forceinline__ void sts16(uint32_t a, uint32_t v) { asm volatile("st.shared.u16 [%0], %1;" :: "r"(a), "h"((uint16_t)v) : "memory"); }
__device__ __forceinline__ void sts32(uint32_t a, uint32_t v) { asm volatile("st.shared.b32 [%0], %1;" :: "r"(a), "r"(v) : "memory"); }
__device__ __forceinline__ void sts64(uint32_t a, uint32_t x, uint32_t y) { asm volatile("st.shared.v2.b32 [%0], {%1,%2};" :: "r"(a), "r"(x), "r"(y) : "memory"); }
__device__ __forceinline__ void sts128(uint32_t a, uint32_t x, uint32_t y, uint32_t z, uint32_t w) { asm volatile("st.shared.v4.b32 [%0], {%1,%2,%3,%4};" :: "r"(a), "r"(x), "r"(y), "r"(z), "r"(w) : "memory"); }
__device__ __forceinline__ void ldsm4(uint32_t a, uint32_t& r0, uint32_t& r1, uint32_t& r2, uint32_t& r3) {
  asm volatile("ldmatrix.sync.aligned.m8n8.x4.shared.b16 {%0,%1,%2,%3}, [%4];" : "=r"(r0), "=r"(r1), "=r"(r2), "=r"(r3) : "r"(a) : "memory");
}
__device__ __forceinline__ void ldsm2(uint32_t a, uint32_t& r0, uint32_t& r1) {
  asm volatile("ldmatrix.sync.aligned.m8n8.x2.shared.b16 {%0,%1}, [%2];" : "=r"(r0), "=r"(r1) : "r"(a) : "memory");
}
__device__ __forceinline__ void ldsm4t(uint32_t a, uint32_t& r0, uint32_t& r1, uint32_t& r2, uint32_t& r3) {
  asm volatile("ldmatrix.sync.aligned.m8n8.x4.trans.shared.b16 {%0,%1,%2,%3}, [%4];" : "=r"(r0), "=r"(r1), "=r"(r2), "=r"(r3) : "r"(a) : "memory");
}
__device__ __forceinline__ void stsm4t(uint32_t a, uint32_t r0, uint32_t r1, uint32_t r2, uint32_t r3) {
  asm volatile("stmatrix.sync.aligned.m8n8.x4.trans.shared.b16 [%0], {%1,%2,%3,%4};" :: "r"(a), "r"(r0), "r"(r1), "r"(r2), "r"(r3) : "memory");
}
__device__ __forceinline__ uint4 ldr128(const void* p) {
  unsigned long long lo, hi;
  asm volatile("{ .reg .b128 t; ld.relaxed.gpu.global.b128 t, [%2]; mov.b128 {%0, %1}, t; }" : "=l"(lo), "=l"(hi) : "l"(p) : "memory");
  return make_uint4((uint32_t)lo, (uint32_t)(lo >> 32), (uint32_t)hi, (uint32_t)(hi >> 32));
}
__device__ __forceinline__ void str128(void* p, uint32_t x, uint32_t y, uint32_t z, uint32_t w) {
  asm volatile("{ .reg .b128 t; .reg .b64 lo, hi; mov.b64 lo, {%1,%2}; mov.b64 hi, {%3,%4}; mov.b128 t, {lo, hi}; st.relaxed.gpu.global.b128 [%0], t; }"
               :: "l"(p), "r"(x), "r"(y), "r"(z), "r"(w) : "memory");
}
__device__ __forceinline__ void str64(void* p, uint32_t x, uint32_t y) {
  asm volatile("{ .reg .b64 t; mov.b64 t, {%1,%2}; st.relaxed.gpu.global.b64 [%0], t; }" :: "l"(p), "r"(x), "r"(y) : "memory");
}
__device__ __forceinline__ uint32_t ldr32(const void* p) { uint32_t v; asm volatile("ld.relaxed.gpu.global.b32 %0, [%1];" : "=r"(v) : "l"(p) : "memory"); return v; }
__device__ __forceinline__ void str32(void* p, uint32_t v) { asm volatile("st.relaxed.gpu.global.b32 [%0], %1;" :: "l"(p), "r"(v) : "memory"); }
__device__ __forceinline__ void str16(void* p, uint32_t v) { asm volatile("st.relaxed.gpu.global.u16 [%0], %1;" :: "l"(p), "h"((uint16_t)v) : "memory"); }
__device__ __forceinline__ void fence_gpu() { asm volatile("fence.acq_rel.gpu;" ::: "memory"); }
__device__ __forceinline__ void bar_sync(int id, int n) { asm volatile("bar.sync %0, %1;" :: "r"(id), "r"(n) : "memory"); }
__device__ __forceinline__ void bar_arrive(int id, int n) { asm volatile("bar.arrive %0, %1;" :: "r"(id), "r"(n) : "memory"); }

__device__ __forceinline__ float bf_lo(uint32_t w) { return __uint_as_float(w << 16); }
__device__ __forceinline__ float bf_hi(uint32_t w) { return __uint_as_float(w & 0xFFFF0000u); }
__device__ __forceinline__ uint32_t pack_bf(float lo, float hi) { uint32_t r; asm("cvt.rn.bf16x2.f32 %0, %1, %2;" : "=r"(r) : "f"(hi), "f"(lo)); return r; }
__device__ __forceinline__ uint32_t pack_h(float lo, float hi) { uint32_t r; asm("cvt.rn.f16x2.f32 %0, %1, %2;" : "=r"(r) : "f"(hi), "f"(lo)); return r; }
__device__ __forceinline__ uint32_t pack_hv(float lo, float hi) { uint32_t r; asm volatile("cvt.rn.f16x2.f32 %0, %1, %2;" : "=r"(r) : "f"(hi), "f"(lo) : "memory"); return r; }
__device__ __forceinline__ float bfr(float x) { return bf_lo(pack_bf(x, 0.f)); }
__device__ __forceinline__ uint32_t bf_sub2(uint32_t a, uint32_t b) { __nv_bfloat162 r = __hsub2(*(__nv_bfloat162*)&a, *(__nv_bfloat162*)&b); return *(uint32_t*)&r; }
__device__ __forceinline__ uint32_t bf_add2(uint32_t a, uint32_t b) { __nv_bfloat162 r = __hadd2(*(__nv_bfloat162*)&a, *(__nv_bfloat162*)&b); return *(uint32_t*)&r; }
__device__ __forceinline__ uint32_t bf_mul2(uint32_t a, uint32_t b) { __nv_bfloat162 r = __hmul2(*(__nv_bfloat162*)&a, *(__nv_bfloat162*)&b); return *(uint32_t*)&r; }
__device__ __forceinline__ float2 h2f(uint32_t w) { return __half22float2(*(__half2*)&w); }
__device__ __forceinline__ float ex2(float x) { float r; asm("ex2.approx.ftz.f32 %0, %1;" : "=f"(r) : "f"(x)); return r; }
__device__ __forceinline__ float warp_sum(float v) {
#pragma unroll
  for (int o = 16; o > 0; o >>= 1) v += __shfl_xor_sync(0xffffffffu, v, o);
  return v;
}
__device__ __forceinline__ void mma_f16_f32(float* d, uint32_t a0, uint32_t a1, uint32_t a2, uint32_t a3, uint32_t b0, uint32_t b1) {
  asm volatile("mma.sync.aligned.m16n8k16.row.col.f32.f16.f16.f32 {%0,%1,%2,%3}, {%4,%5,%6,%7}, {%8,%9}, {%0,%1,%2,%3};"
               : "+f"(d[0]), "+f"(d[1]), "+f"(d[2]), "+f"(d[3]) : "r"(a0), "r"(a1), "r"(a2), "r"(a3), "r"(b0), "r"(b1));
}
__device__ __forceinline__ void mma_f16_f16(uint32_t& d0, uint32_t& d1, uint32_t a0, uint32_t a1, uint32_t a2, uint32_t a3, uint32_t b0, uint32_t b1) {
  asm volatile("mma.sync.aligned.m16n8k16.row.col.f16.f16.f16.f16 {%0,%1}, {%2,%3,%4,%5}, {%6,%7}, {%0,%1};"
               : "+r"(d0), "+r"(d1) : "r"(a0), "r"(a1), "r"(a2), "r"(a3), "r"(b0), "r"(b1));
}
__device__ __forceinline__ void mma_bf16(float* d, uint32_t a0, uint32_t a1, uint32_t a2, uint32_t a3, uint32_t b0, uint32_t b1) {
  asm volatile("mma.sync.aligned.m16n8k16.row.col.f32.bf16.bf16.f32 {%0,%1,%2,%3}, {%4,%5,%6,%7}, {%8,%9}, {%0,%1,%2,%3};"
               : "+f"(d[0]), "+f"(d[1]), "+f"(d[2]), "+f"(d[3]) : "r"(a0), "r"(a1), "r"(a2), "r"(a3), "r"(b0), "r"(b1));
}
__device__ __forceinline__ void mma_bf16_k8(float* d, uint32_t a0, uint32_t a1, uint32_t b0) {
  asm volatile("mma.sync.aligned.m16n8k8.row.col.f32.bf16.bf16.f32 {%0,%1,%2,%3}, {%4,%5}, {%6}, {%0,%1,%2,%3};"
               : "+f"(d[0]), "+f"(d[1]), "+f"(d[2]), "+f"(d[3]) : "r"(a0), "r"(a1), "r"(b0));
}

__device__ __forceinline__ void wg_fence() { asm volatile("wgmma.fence.sync.aligned;" ::: "memory"); }
__device__ __forceinline__ void wg_commit() { asm volatile("wgmma.commit_group.sync.aligned;" ::: "memory"); }
template <int N> __device__ __forceinline__ void wg_wait() { asm volatile("wgmma.wait_group.sync.aligned %0;" :: "n"(N) : "memory"); }
template <int TB> __device__ __forceinline__ void wgmma32(float* d, const uint32_t* a, uint32_t dlo, uint32_t dhi) {
  asm volatile("{ .reg .b64 dd; mov.b64 dd, {%20, %21}; wgmma.mma_async.sync.aligned.m64n32k16.f32.f16.f16 "
               "{%0,%1,%2,%3,%4,%5,%6,%7,%8,%9,%10,%11,%12,%13,%14,%15}, {%16,%17,%18,%19}, dd, 1, 1, 1, %22; }"
               : "+f"(d[0]), "+f"(d[1]), "+f"(d[2]), "+f"(d[3]), "+f"(d[4]), "+f"(d[5]), "+f"(d[6]), "+f"(d[7]), "+f"(d[8]), "+f"(d[9]), "+f"(d[10]), "+f"(d[11]), "+f"(d[12]), "+f"(d[13]), "+f"(d[14]), "+f"(d[15])
               : "r"(a[0]), "r"(a[1]), "r"(a[2]), "r"(a[3]), "r"(dlo), "r"(dhi), "n"(TB));
}
template <int TB> __device__ __forceinline__ void wgmma96(float* d, const uint32_t* a, uint32_t dlo, uint32_t dhi) {
  asm volatile("{ .reg .b64 dd; mov.b64 dd, {%52, %53}; wgmma.mma_async.sync.aligned.m64n96k16.f32.f16.f16 "
               "{%0,%1,%2,%3,%4,%5,%6,%7,%8,%9,%10,%11,%12,%13,%14,%15,%16,%17,%18,%19,%20,%21,%22,%23,%24,%25,%26,%27,%28,%29,%30,%31,%32,%33,%34,%35,%36,%37,%38,%39,%40,%41,%42,%43,%44,%45,%46,%47}, {%48,%49,%50,%51}, dd, 1, 1, 1, %54; }"
               : "+f"(d[0]), "+f"(d[1]), "+f"(d[2]), "+f"(d[3]), "+f"(d[4]), "+f"(d[5]), "+f"(d[6]), "+f"(d[7]), "+f"(d[8]), "+f"(d[9]), "+f"(d[10]), "+f"(d[11]), "+f"(d[12]), "+f"(d[13]), "+f"(d[14]), "+f"(d[15]), "+f"(d[16]), "+f"(d[17]), "+f"(d[18]), "+f"(d[19]), "+f"(d[20]), "+f"(d[21]), "+f"(d[22]), "+f"(d[23]), "+f"(d[24]), "+f"(d[25]), "+f"(d[26]), "+f"(d[27]), "+f"(d[28]), "+f"(d[29]), "+f"(d[30]), "+f"(d[31]), "+f"(d[32]), "+f"(d[33]), "+f"(d[34]), "+f"(d[35]), "+f"(d[36]), "+f"(d[37]), "+f"(d[38]), "+f"(d[39]), "+f"(d[40]), "+f"(d[41]), "+f"(d[42]), "+f"(d[43]), "+f"(d[44]), "+f"(d[45]), "+f"(d[46]), "+f"(d[47])
               : "r"(a[0]), "r"(a[1]), "r"(a[2]), "r"(a[3]), "r"(dlo), "r"(dhi), "n"(TB));
}
template <int TB> __device__ __forceinline__ void wgmma96_init(float* d, const uint32_t* a, uint32_t dlo, uint32_t dhi) {
  asm volatile("{ .reg .b64 dd; mov.b64 dd, {%52, %53}; wgmma.mma_async.sync.aligned.m64n96k16.f32.f16.f16 "
               "{%0,%1,%2,%3,%4,%5,%6,%7,%8,%9,%10,%11,%12,%13,%14,%15,%16,%17,%18,%19,%20,%21,%22,%23,%24,%25,%26,%27,%28,%29,%30,%31,%32,%33,%34,%35,%36,%37,%38,%39,%40,%41,%42,%43,%44,%45,%46,%47}, {%48,%49,%50,%51}, dd, 0, 1, 1, %54; }"
               : "=f"(d[0]), "=f"(d[1]), "=f"(d[2]), "=f"(d[3]), "=f"(d[4]), "=f"(d[5]), "=f"(d[6]), "=f"(d[7]), "=f"(d[8]), "=f"(d[9]), "=f"(d[10]), "=f"(d[11]), "=f"(d[12]), "=f"(d[13]), "=f"(d[14]), "=f"(d[15]), "=f"(d[16]), "=f"(d[17]), "=f"(d[18]), "=f"(d[19]), "=f"(d[20]), "=f"(d[21]), "=f"(d[22]), "=f"(d[23]), "=f"(d[24]), "=f"(d[25]), "=f"(d[26]), "=f"(d[27]), "=f"(d[28]), "=f"(d[29]), "=f"(d[30]), "=f"(d[31]), "=f"(d[32]), "=f"(d[33]), "=f"(d[34]), "=f"(d[35]), "=f"(d[36]), "=f"(d[37]), "=f"(d[38]), "=f"(d[39]), "=f"(d[40]), "=f"(d[41]), "=f"(d[42]), "=f"(d[43]), "=f"(d[44]), "=f"(d[45]), "=f"(d[46]), "=f"(d[47])
               : "r"(a[0]), "r"(a[1]), "r"(a[2]), "r"(a[3]), "r"(dlo), "r"(dhi), "n"(TB));
}
template <int TB> __device__ __forceinline__ void wgmma32_init(float* d, const uint32_t* a, uint32_t dlo, uint32_t dhi) {
  asm volatile("{ .reg .b64 dd; mov.b64 dd, {%20, %21}; wgmma.mma_async.sync.aligned.m64n32k16.f32.f16.f16 "
               "{%0,%1,%2,%3,%4,%5,%6,%7,%8,%9,%10,%11,%12,%13,%14,%15}, {%16,%17,%18,%19}, dd, 0, 1, 1, %22; }"
               : "=f"(d[0]), "=f"(d[1]), "=f"(d[2]), "=f"(d[3]), "=f"(d[4]), "=f"(d[5]), "=f"(d[6]), "=f"(d[7]), "=f"(d[8]), "=f"(d[9]), "=f"(d[10]), "=f"(d[11]), "=f"(d[12]), "=f"(d[13]), "=f"(d[14]), "=f"(d[15])
               : "r"(a[0]), "r"(a[1]), "r"(a[2]), "r"(a[3]), "r"(dlo), "r"(dhi), "n"(TB));
}
__device__ __forceinline__ void wgmma64h(uint32_t* d, uint32_t a0, uint32_t a1, uint32_t a2, uint32_t a3, uint32_t dlo, uint32_t dhi) {
  asm volatile("{ .reg .b64 dd; mov.b64 dd, {%20, %21}; wgmma.mma_async.sync.aligned.m64n64k16.f16.f16.f16 "
               "{%0,%1,%2,%3,%4,%5,%6,%7,%8,%9,%10,%11,%12,%13,%14,%15}, {%16,%17,%18,%19}, dd, 1, 1, 1, 0; }"
               : "+r"(d[0]), "+r"(d[1]), "+r"(d[2]), "+r"(d[3]), "+r"(d[4]), "+r"(d[5]), "+r"(d[6]), "+r"(d[7]), "+r"(d[8]), "+r"(d[9]), "+r"(d[10]), "+r"(d[11]), "+r"(d[12]), "+r"(d[13]), "+r"(d[14]), "+r"(d[15])
               : "r"(a0), "r"(a1), "r"(a2), "r"(a3), "r"(dlo), "r"(dhi));
}
__device__ __forceinline__ void wgmma64h_init(uint32_t* d, uint32_t a0, uint32_t a1, uint32_t a2, uint32_t a3, uint32_t dlo, uint32_t dhi) {
  asm volatile("{ .reg .b64 dd; mov.b64 dd, {%20, %21}; wgmma.mma_async.sync.aligned.m64n64k16.f16.f16.f16 "
               "{%0,%1,%2,%3,%4,%5,%6,%7,%8,%9,%10,%11,%12,%13,%14,%15}, {%16,%17,%18,%19}, dd, 0, 1, 1, 0; }"
               : "=r"(d[0]), "=r"(d[1]), "=r"(d[2]), "=r"(d[3]), "=r"(d[4]), "=r"(d[5]), "=r"(d[6]), "=r"(d[7]), "=r"(d[8]), "=r"(d[9]), "=r"(d[10]), "=r"(d[11]), "=r"(d[12]), "=r"(d[13]), "=r"(d[14]), "=r"(d[15])
               : "r"(a0), "r"(a1), "r"(a2), "r"(a3), "r"(dlo), "r"(dhi));
}
__device__ __forceinline__ void wgmma40_ss(float* d, uint32_t alo, uint32_t blo, uint32_t hi) {
  asm volatile("{ .reg .b64 da, db; mov.b64 da, {%20, %22}; mov.b64 db, {%21, %22}; "
               "wgmma.mma_async.sync.aligned.m64n40k16.f32.f16.f16 {%0,%1,%2,%3,%4,%5,%6,%7,%8,%9,%10,%11,%12,%13,%14,%15,%16,%17,%18,%19}, da, db, 1, 1, 1, 1, 1; }"
               : "+f"(d[0]), "+f"(d[1]), "+f"(d[2]), "+f"(d[3]), "+f"(d[4]), "+f"(d[5]), "+f"(d[6]), "+f"(d[7]), "+f"(d[8]), "+f"(d[9]), "+f"(d[10]), "+f"(d[11]), "+f"(d[12]), "+f"(d[13]), "+f"(d[14]), "+f"(d[15]), "+f"(d[16]), "+f"(d[17]), "+f"(d[18]), "+f"(d[19])
               : "r"(alo), "r"(blo), "r"(hi));
}
__device__ __forceinline__ void wgmma40_ss_init(float* d, uint32_t alo, uint32_t blo, uint32_t hi) {
  asm volatile("{ .reg .b64 da, db; mov.b64 da, {%20, %22}; mov.b64 db, {%21, %22}; "
               "wgmma.mma_async.sync.aligned.m64n40k16.f32.f16.f16 {%0,%1,%2,%3,%4,%5,%6,%7,%8,%9,%10,%11,%12,%13,%14,%15,%16,%17,%18,%19}, da, db, 0, 1, 1, 1, 1; }"
               : "=f"(d[0]), "=f"(d[1]), "=f"(d[2]), "=f"(d[3]), "=f"(d[4]), "=f"(d[5]), "=f"(d[6]), "=f"(d[7]), "=f"(d[8]), "=f"(d[9]), "=f"(d[10]), "=f"(d[11]), "=f"(d[12]), "=f"(d[13]), "=f"(d[14]), "=f"(d[15]), "=f"(d[16]), "=f"(d[17]), "=f"(d[18]), "=f"(d[19])
               : "r"(alo), "r"(blo), "r"(hi));
}
__device__ __forceinline__ float vzero() { float v; asm volatile("mov.b32 %0, 0;" : "=f"(v)); return v; }
__device__ __forceinline__ void tma_box(uint32_t dst, const CUtensorMap* tm, uint32_t mb, int x, int y) {
  asm volatile("cp.async.bulk.tensor.2d.shared::cluster.global.mbarrier::complete_tx::bytes [%0], [%1, {%3, %4}], [%2];"
               :: "r"(dst), "l"(tm), "r"(mb), "r"(x), "r"(y) : "memory");
}
__device__ __forceinline__ void l2_prefetch(const void* src, uint32_t bytes) {
  asm volatile("cp.async.bulk.prefetch.L2.global [%0], %1;" :: "l"(src), "r"(bytes) : "memory");
}
__device__ __forceinline__ uint32_t uni(uint32_t v) {
  uint32_t r; asm volatile("shfl.sync.idx.b32 %0, %1, 0, 0x1f, 0xffffffff;" : "=r"(r) : "r"(v)); return r;
}
__device__ __forceinline__ int fresh_tid() { int v; asm volatile("mov.u32 %0, %tid.x;" : "=r"(v)); return v; }

struct Params {
  const unsigned char* x;
  Scratch* s;
  int off[7];
  uint32_t zero;
  uint32_t* out;
  const uint32_t* dskip;
  const uint32_t* w_r;
  const unsigned char* w_gate;
  const unsigned char* w_up;
  long long* ts;
  const unsigned char* far[7];
  uint32_t sched[2][17];
};
__device__ __forceinline__ uint32_t ldnc32(const void* p) { uint32_t v; asm volatile("ld.global.nc.b32 %0, [%1];" : "=r"(v) : "l"(p)); return v; }
__device__ __forceinline__ uint32_t ldnc16(const void* p) { uint16_t v; asm volatile("ld.global.nc.u16 %0, [%1];" : "=h"(v) : "l"(p)); return v; }
__device__ __forceinline__ uint4 ldnc128(const void* p) { uint4 v; asm volatile("ld.global.nc.v4.b32 {%0,%1,%2,%3}, [%4];" : "=r"(v.x), "=r"(v.y), "=r"(v.z), "=r"(v.w) : "l"(p)); return v; }
__device__ __forceinline__ void mbar_wait(uint32_t mb, uint32_t ph = 0) {
#pragma unroll 1
  for (int it = 0; it < SPIN_MAX; it++) {
    uint32_t ok;
    asm volatile("{ .reg .pred q; mbarrier.try_wait.parity.shared::cta.b64 q, [%1], %2; selp.u32 %0, 1, 0, q; }" : "=r"(ok) : "r"(mb), "r"(ph) : "memory");
    if (ok) break;
  }
}
__device__ __forceinline__ uint32_t mbar_test(uint32_t mb) {
  uint32_t ok;
  asm volatile("{ .reg .pred q; mbarrier.test_wait.parity.shared::cta.b64 q, [%1], 0; selp.u32 %0, 1, 0, q; }" : "=r"(ok) : "r"(mb) : "memory");
  return ok;
}
__device__ __forceinline__ void mbar_arrive(uint32_t mb) { asm volatile("mbarrier.arrive.shared::cta.b64 _, [%0];" :: "r"(mb) : "memory"); }
__device__ __forceinline__ uint32_t ldg16(const void* p) { uint16_t v; asm volatile("ld.global.u16 %0, [%1];" : "=h"(v) : "l"(p) : "memory"); return v; }
__device__ __forceinline__ uint32_t ldr16(const void* p) { uint16_t v; asm volatile("ld.relaxed.gpu.global.u16 %0, [%1];" : "=h"(v) : "l"(p) : "memory"); return v; }
__device__ __forceinline__ void fence_async() { asm volatile("fence.proxy.async.shared::cta;" ::: "memory"); }
#define SPIN_WHILE(cond, body) _Pragma("unroll 1") for (int _it = 0; _it < SPIN_MAX && __any_sync(0xffffffffu, (cond)); _it++) { body; }

struct LnC { uint32_t m2, rh2, rl2; };
__device__ __forceinline__ float diag_sum(float d0, float d1, int t) {
  float q = __shfl_sync(0xffffffffu, d0, 9 * t) + __shfl_sync(0xffffffffu, d1, 9 * t + 4);
  q += __shfl_xor_sync(0xffffffffu, q, 1);
  return q + __shfl_xor_sync(0xffffffffu, q, 2);
}
__device__ __forceinline__ LnC ln_consts(float s, float q, float& r) {
  const float mean = s * (1.f / DM);
  const float var = fmaxf(fmaf(-mean, mean, q * (1.f / DM)), 0.f);
  float sd;
  asm("sqrt.approx.ftz.f32 %0, %1;" : "=f"(sd) : "f"(bfr(bfr(var) + 1e-5f)));
  asm("rcp.approx.ftz.f32 %0, %1;" : "=f"(r) : "f"(bfr(sd)));
  LnC c;
  c.m2 = pack_bf(mean, mean);
  c.rh2 = pack_bf(r, r);
  const float rl = r - bf_lo(c.rh2);
  c.rl2 = pack_bf(rl, rl);
  return c;
}
__device__ __forceinline__ float quad_sum(float s) { s += __shfl_xor_sync(0xffffffffu, s, 1); return s + __shfl_xor_sync(0xffffffffu, s, 2); }
__device__ __forceinline__ uint32_t bf_fma2(uint32_t a, uint32_t b, uint32_t c) {
  __nv_bfloat162 r = __hfma2(*(const __nv_bfloat162*)&a, *(const __nv_bfloat162*)&b, *(const __nv_bfloat162*)&c);
  return *(uint32_t*)&r;
}
__device__ __forceinline__ uint32_t ln_apply(uint32_t w, uint32_t m2, uint32_t rh2, uint32_t rl2) {
  const uint32_t d = bf_sub2(w, m2);
  return bf_fma2(d, rh2, bf_mul2(d, rl2));
}

__device__ __forceinline__ float2 cis(float mag_log2, float rev) {
  const float m = ex2(mag_log2), ang = rev * 6.283185307179586f;
  return make_float2(m * __cosf(ang), m * __sinf(ang));
}
__device__ __forceinline__ float2 csq(float2 a) { return make_float2(fmaf(a.x, a.x, -a.y * a.y), (a.x + a.x) * a.y); }
__device__ __forceinline__ float2 cmul(float2 a, float2 b) { return make_float2(fmaf(a.x, b.x, -a.y * b.y), fmaf(a.x, b.y, a.y * b.x)); }
__device__ __forceinline__ void pmul(uint32_t xr, uint32_t xi, uint32_t w, uint32_t& yr, uint32_t& yi) {
  const __half2 XR = *(__half2*)&xr, XI = *(__half2*)&xi, W = *(__half2*)&w;
  const __half2 a = __hfma2(__hneg2(XI), __high2half2(W), __hmul2(XR, __low2half2(W)));
  const __half2 b = __hfma2(XI, __low2half2(W), __hmul2(XR, __high2half2(W)));
  yr = *(const uint32_t*)&a; yi = *(const uint32_t*)&b;
}
__device__ __forceinline__ uint32_t pk(float2 a) { return pack_h(a.x, a.y); }

struct KgState { float2 c0, z8; float kl; uint32_t w64, w128, w192; };
__device__ __forceinline__ void kgen_tables_n(const uint32_t (&raw)[7], uint32_t scr, int wt, KgState& k) {
  const uint32_t dst = scr + 16384 + wt * 16;
  const float dt = bfr(ex2(bf_lo(raw[6]) * 1.4426950408889634f));
  const float th = dt * bf_lo(raw[1]);
  const float br = dt * bf_lo(raw[2]), bi = dt * bf_lo(raw[3]);
  const float Cr = bf_lo(raw[4]), Ci = bf_lo(raw[5]);
  k.c0 = make_float2(fmaf(Cr, br, -Ci * bi), fmaf(Cr, bi, Ci * br));
  const uint32_t mx = __reduce_max_sync(0xffffffffu, __float_as_uint(fmaxf(fabsf(k.c0.x), fabsf(k.c0.y))));
  const float a2 = dt * bf_lo(raw[0]) * 1.4426950408889634f;
  const float rh = th * 0.15915494309189535f;
  const float rl = fmaf(th, (float)(0.15915494309189535 - (double)0.15915494309189535f), fmaf(th, 0.15915494309189535f, -rh));
  const float rf = rh - rintf(rh);
  const float2 z1 = cis(a2, rf + rl);
  const float p64 = rf * 64.f;
  const float2 z64 = cis(a2 * 64.f, fmaf(64.f, rl, p64 - rintf(p64)));
  const float2 z2 = csq(z1), z128 = csq(z64), z3 = cmul(z2, z1), z4 = csq(z2), z256 = csq(z128), z6 = csq(z3), z512 = csq(z256);
  k.z8 = csq(z4);
  k.w64 = pk(z64); k.w128 = pk(z128); k.w192 = pk(cmul(z128, z64));
  sts128(dst, 0x00003C00u, pk(z2), pk(z4), pk(z6));
  const float2 z1024 = csq(z512), z768 = cmul(z512, z256);
  sts128(dst + 2048, pk(z1), pk(z3), pk(cmul(z4, z1)), pk(cmul(z4, z3)));
  const float2 z2048 = csq(z1024);
  k.kl = fmaf(k.c0.x, z2048.x, -k.c0.y * z2048.y);
  sts128(dst + 4096, pk(z256), pk(cmul(z256, z2)), pk(cmul(z256, z4)), pk(cmul(z256, z6)));
  sts128(dst + 6144, pk(z512), pk(cmul(z512, z4)), pk(z768), pk(cmul(z768, z4)));
  sts128(dst + 8192, pk(z1024), pk(cmul(z1024, z256)), pk(cmul(z1024, z512)), pk(cmul(z1024, z768)));
  sts32(scr + W_MISC + (wt >> 5) * 4, mx);
}
__device__ __forceinline__ int kgen_tables_m(uint32_t scr, int wt, const KgState& k) {
  const uint32_t dst = scr + wt * 16;
  const uint4 e4 = lds128(scr + W_MISC);
  const float2 z16 = csq(k.z8), z32 = csq(z16);
  const int em = max(min((int)(max(max(e4.x, e4.y), max(e4.z, e4.w)) >> 23), 238), 16);
  const float sc = __uint_as_float((uint32_t)(127 + 4 + 127 - em) << 23);
  sts32(scr + W_MISC + 16 + (wt >> 5) * 4, __reduce_add_sync(0xffffffffu, __float2int_rn(k.kl * sc * 262144.f)));
  const float2 c0 = make_float2(k.c0.x * sc, k.c0.y * sc);
  const float2 c1 = cmul(c0, k.z8), c2 = cmul(c0, z16), c4 = cmul(c0, z32), c3 = cmul(c1, z16), c5 = cmul(c1, z32), c6 = cmul(c2, z32), c7 = cmul(c3, z32);
  uint32_t pr[4], pi[4], yr[4], yi[4];
  pr[0] = pack_h(c0.x, c1.x); pi[0] = pack_h(c0.y, c1.y);
  pr[1] = pack_h(c2.x, c3.x); pi[1] = pack_h(c2.y, c3.y);
  pr[2] = pack_h(c4.x, c5.x); pi[2] = pack_h(c4.y, c5.y);
  pr[3] = pack_h(c6.x, c7.x); pi[3] = pack_h(c6.y, c7.y);
  sts128(dst, pr[0], pr[1], pr[2], pr[3]); sts128(dst + 2048, pi[0], pi[1], pi[2], pi[3]);
#pragma unroll
  for (int q = 1; q < 4; q++) {
    const uint32_t w = q == 1 ? k.w64 : q == 2 ? k.w128 : k.w192;
#pragma unroll
    for (int i = 0; i < 4; i++) pmul(pr[i], pi[i], w, yr[i], yi[i]);
    sts128(dst + q * 4096, yr[0], yr[1], yr[2], yr[3]); sts128(dst + q * 4096 + 2048, yi[0], yi[1], yi[2], yi[3]);
  }
  return em;
}
__device__ __forceinline__ void kgen_build(uint32_t tb, uint32_t sc, int wg, int wt, uint32_t k0, uint32_t k1, uint32_t k2) {
  const uint32_t kt = tb + W_KT;
  const int ix = ((wt >> 2) + (wt & 3) * 32 - 1) & 127;
  const uint32_t a3 = tb + W_CW + 32 + ((ix & 1) ? 0 : 304) + (ix >> 1) * 4;
  const uint32_t v3 = wt ? k2 : k2 >> 16;
  sts32(sc + 4 + wt * 4, __byte_perm(k0, k1, 0x5432));
  sts16(sc + 544 + (wt & ~3) + (wt & 1) * 2 + (wt & 2) * 64, k1 >> 16);
  sts16(a3, v3); sts16(a3 + 6, v3);
  if ((unsigned)(wt - 32) < 18u) sts128(kt + (wt < 36 ? -512 : 64 + 4128 - 576) + wt * 16, 0, 0, 0, 0);
  if (wt == 127) sts32(sc, k0 & 0xFFFF0000u);
  if (wt == 0) { sts32(sc + 516, k1); sts16(sc + 800, k2); }
  bar_sync(1 + wg, 128);
  const uint32_t cw = tb + W_CW + 32 + (wt >> 6) * 48 + wt * 4;
  const uint32_t pv = lds32(sc + wt * 4), nx = lds32(sc + 8 + wt * 4), c2 = lds16(sc + 544 + wt * 2), n2 = lds16(sc + 546 + wt * 2);
  sts128(tb + W_L3 + 1024 + (wt >> 6) * 1024 + wt * 16, lds32(cw), lds32(cw - 8), lds32(cw - 16), lds32(cw - 24));
  const bool odd = wt & 1;
  sts64(kt + 64 + wt * 8, __byte_perm(k0, pv, 0x5410), __byte_perm(k0, 0, 0x1032));
  sts64(kt + 64 + 1024 + wt * 8, __byte_perm(k1, pv, (odd || wt == 0) ? 0x7610 : 0x1010), __byte_perm(k1, nx, odd ? 0x1076 : 0x1010));
  const uint32_t cc = c2 * 0x10001u, nc = __byte_perm(n2, c2, 0x5410), nn = n2 * 0x10001u;
  sts128(kt + 64 + 2048 + wt * 16, cc, cc, odd ? nc : cc, odd ? nn : nc);
  if (wt == 127) { sts128(kt + 64 + 4096, nn, nn, nn, nn); sts128(kt + 64 + 4112, nn, nn << 16, 0, 0); }
}

__device__ __forceinline__ void load_a(uint32_t (&a)[4], uint32_t kp, int j) {
  a[0] = lds32(kp + 64 * j); a[1] = lds32(kp + 64 * j + 512); a[2] = lds32(kp + 64 * j - 32); a[3] = lds32(kp + 64 * j + 480);
}
__device__ __forceinline__ uint32_t band(int d, int lo, int hi) {
  return ((unsigned)(d - lo) <= (unsigned)(hi - lo) ? 1u : 0u) | ((unsigned)(d - 1 - lo) <= (unsigned)(hi - lo) ? 0x10000u : 0u);
}
__device__ __forceinline__ uint32_t hadd2u(uint32_t a, uint32_t b) { __half2 r = __hadd2(*(__half2*)&a, *(__half2*)&b); return *(uint32_t*)&r; }

__device__ __forceinline__ void zero_pads(uint32_t tb, int wt) {
  sts128(tb + W_L3 + (wt >> 6) * 1024 + wt * 16, 0, 0, 0, 0);
  if ((wt & 63) < 3) sts128(tb + W_CW + (wt >> 6) * 304 + (wt & 63) * 16, 0, 0, 0, 0);
}
__device__ __forceinline__ uint32_t tr_base(int lane) {
  return OFF_YT + (2 * (lane >> 3) + (lane & 1)) * YT_PITCH + ((lane >> 1) & 1) * (8 * YT_PITCH + 64) + ((lane >> 2) & 1) * 16;
}

__device__ __forceinline__ uint32_t sc_addr(int tp) { return OFF_YT + (tp < 16 ? tp * YT_PITCH + (tp >> 3) * 64 + 1152 : 8 * YT_PITCH - 512 + tp * 32); }
#define X_NE 3
#define X_NS 3
#define X_SCT 10500
#define X_DELTA 600
#define X_DSTEP 750
#define X_PF0 2500
#define X_PFD 530
#define X_TD 620
#define X_ORD 1
#define X_WS 6
#define X_OR 8
#define X_ABS 5200
#define X_XD 0
#define X_REL 0
#define X_RW 1
#define X_RD 850
#define X_HD 500
#define X_PD 1050
#define X_HU 14
#define X_LAG 1000
#define X_YD 800
struct TMaps { CUtensorMap m[8]; };
__device__ __forceinline__ uint32_t h2bf(uint32_t w) { const float2 f = h2f(w); return pack_bf(f.x, f.y); }
__device__ __forceinline__ uint32_t keep(uint32_t v) { asm volatile("" : "+r"(v)); return v; }
__device__ __forceinline__ uint2 ldr64(const void* p) { uint2 v; asm volatile("{ .reg .b64 t; ld.relaxed.gpu.global.b64 t, [%2]; mov.b64 {%0, %1}, t; }" : "=r"(v.x), "=r"(v.y) : "l"(p) : "memory"); return v; }
__host__ __device__ __forceinline__ uint32_t down_box(int s, bool five) {
  return five ? OFF_W + W_BYTES + 12288 + (s / 3) * (W_BYTES - 12288) + s * 4096 : s < 6 ? OFF_W + W_BYTES + BOX + (s >> 1) * (W_BYTES - 10240) + s * 5120 : OFF_W + (s - 6) * 5120;
}
__device__ __forceinline__ void load_tile(const CUtensorMap* tmx, int i, int c) {
  asm volatile("mbarrier.arrive.expect_tx.shared::cta.b64 _, [%0], 5120;" :: "r"(MB_UL + i * 8) : "memory");
  tma_box(OFF_W + (i < 4 ? i * W_BYTES : ALT) + W_UP, tmx, MB_UL + i * 8, (i < 4 ? i * 128 + c : 512 + (c >> 1)) * 16, -32);
}
__device__ __forceinline__ void check_tile(uint32_t tb, const CUtensorMap* tmx, int i, int c, int wg, int wt) {
#pragma unroll 1
  for (int it = 0; it < SPIN_MAX; it++) {
    uint32_t r0, r1, r2, r3, ok;
    mbar_wait(MB_UL + i * 8, it & 1);
    if (it == 0) TS(29);
    if (it == 1) TS(13);
    ldsm4(tb + W_UP + 1024 + wt * 32 + (wt & 4) * 4, r0, r1, r2, r3);
    asm volatile("{ .reg .pred q; setp.ne.u32 q, %1, 0; barrier.red.and.pred q, %2, 128, q; selp.u32 %0, 1, 0, q; }" : "=r"(ok) : "r"((r0 & r1 & r2 & r3 & 1u) | (wt & 3)), "r"(1 + wg) : "memory");
    if (ok) break;
    if (wt == 0) load_tile(tmx, i, c);
  }
}
template <bool FAR> __device__ __forceinline__ void load_params(const Params& p, uint32_t ch, int wt, uint32_t dst, bool on) {
  const int o01 = (wt & 16) ? p.off[1] : p.off[0], o23 = (wt & 16) ? p.off[3] : p.off[2], o45 = (wt & 16) ? p.off[5] : p.off[4];
  const int o = (wt & 64) ? ((wt & 32) ? p.off[6] : o45) : ((wt & 32) ? o23 : o01);
  const unsigned char* b = FAR ? p.far[min(wt >> 4, 6)] : p.x + (long long)o * 16;
  asm volatile("{ .reg .pred q; setp.ne.u32 q, %2, 0; @q cp.async.cg.shared.global [%0], [%1], 16; }"
               :: "r"(dst + wt * 16), "l"(b + (wt < 96 ? ch * 256 + (wt & 15) * 16 : (ch >> 3) * 16)), "r"((uint32_t)(on && wt < 97)) : "memory");
}

struct ConvC { uint32_t ca, cb, bands; };
__device__ __forceinline__ ConvC conv_consts(int w, int lane) {
  const int h = w & 1, P = w >> 1, d0 = 8 * h + (lane >> 2) - 2 * (lane & 3);
  ConvC k;
  k.ca = keep((W_KT + (16 + 256 * P + d0) * 4) | ((W_UP + (32 + 64 * P + lane) * 32 + ((h ^ (lane >> 2)) & 1) * 16) << 16));
  k.cb = keep(lane < 8 ? 0xFFFEFFFEu : ~0u);
  k.bands = keep(band(d0, 12, 20) + 2 * band(d0 + 8, 12, 20) + 4 * band(d0 + 16, 12, 20) + 8 * band(d0 + 24, 12, 20)
                 + 16 * band(d0 - 8, 5, 11) + 32 * band(d0, 5, 11) + 64 * band(d0 + 8, 5, 11) + 128 * band(d0 + 16, 5, 11));
  return k;
}
__device__ __forceinline__ void conv_item(uint32_t tb, const ConvC& cv, uint32_t zero, const CUtensorMap* tmx, int ch, int warp, int lane, bool rel, bool hold, bool more) {
  const uint32_t kp = tb + (cv.ca & 0xFFFFu);
  const uint32_t dlo = ((tb + W_UP) >> 4) + 64 + (1u << 16), dhi = 16u | (3u << 30);
  const bool P = warp & 2;
  float a32[16], a96[48];
  uint32_t A[40][4];
#define STEP(J) { wgmma96<0>(a96, A[J], dlo + 64 - 2 * (J), dhi); if ((J) == 0) wgmma32_init<0>(a32, A[J], dlo, dhi); else if ((J) < 8) wgmma32<0>(a32, A[J], (dlo ^ zero) - 2 * (J), dhi); }
#define LD(J) load_a(A[J], kp, J);
#define FIRST(J) wg_fence(); STEP(J) wg_commit(); wg_wait<1>(); wg_fence();
  {
    uint32_t win[16], x9[4], x7[4], e[4], f[4];
    const uint32_t bz = keep(cv.bands);
#define BAND(i) keep((bz & (0x10001u << (i))) * (0x3C00u >> (i)))
    e[0] = lds32(kp + (P ? 3232 : 4096)); e[2] = lds32(kp + (P ? 3200 : 4064)); e[1] = keep(bz & 0x100u); e[3] = keep(bz & 0x200u);
    f[3] = lds32(kp + (P ? 3200 : 4128)); f[0] = keep(bz & 0x4000u); f[1] = keep(bz & 0x8000u); f[2] = keep(bz & 0x300u);
    const uint32_t q[12] = {BAND(0), BAND(5), keep(bz & 0x400u), BAND(4), BAND(2), BAND(7), BAND(1), BAND(6), keep(bz & 0x800u), keep(bz & 0x1000u), BAND(3), keep(bz & 0x2000u)};
#undef BAND
    if (ch < 512) check_tile(tb, tmx - 1, warp >> 2, ch & 127, warp >> 2, (warp & 3) * 32 + lane);
    if (X_REL && hold) mbar_wait(MB_REL);
    TS(3);
    wg_fence();
    wgmma64h_init(win, q[0], q[1], q[2], q[3], dlo, dhi);
    wgmma64h(win, q[4], q[5], q[6], q[7], dlo - 2, dhi);
    wgmma64h(win, q[8], q[9], q[10], q[11], dlo - 4, dhi);
    wg_commit();
    wgmma96_init<0>(a96, e, dlo - 64, dhi);
    wgmma96<0>(a96, f, dlo - 50, dhi);
    wg_commit();
    wg_wait<1>();
#pragma unroll
    for (int i = 0; i < 4; i++) {
      const int tl = 2 * ((i & 1) + ((i & 2) ? 0 : 4));
      x9[i] = P ? win[tl + 4] : win[tl]; x7[i] = P ? win[tl + 5] : win[tl + 1];
    }
    const uint32_t l3lo = ((tb + W_L3) >> 4) + (32u << 16);
    wg_fence();
    wgmma96<0>(a96, x9, l3lo, 8);
    wgmma96<0>(a96, x7, l3lo + 128, 8);
    wg_commit();
  }
  LD(32) LD(33) LD(34) LD(35)
  FIRST(32) STEP(33) STEP(34) STEP(35) wg_commit();
  LD(36) LD(37) LD(38)
  FIRST(36) STEP(37) STEP(38) wg_commit();
  LD(39) LD(0)
  TS(17);
  if (X_REL == 1 && rel) mbar_arrive(MB_REL);
  FIRST(39) STEP(0) wg_commit();
  LD(1) LD(2) LD(3)
  FIRST(1) STEP(2) STEP(3) wg_commit();
  LD(4) LD(5)
  if (X_REL == 2 && rel) mbar_arrive(MB_REL);
  FIRST(4) STEP(5) wg_commit();
  LD(6) LD(7)
  wg_fence(); STEP(6) STEP(7) wg_commit();
#undef STEP
#undef LD
#undef FIRST
  TS(18);
  if (X_REL == 3 && rel) mbar_arrive(MB_REL);
  const uint32_t xc = tb + W_KT + (warp & 3) * 1024 + lane * 16;
  wg_wait<0>();
  uint32_t E[16], o[8];
#define ACC(i) ((i) < 16 ? a32[i] : a96[(i) - 16])
  E[0] = pack_h(a32[0], a32[1]);
#pragma unroll
  for (int i = 1; i < 16; i++) E[i] = pack_h(ACC(4 * i) + ACC(4 * i - 2), ACC(4 * i + 1) + ACC(4 * i - 1));
#undef ACC
#pragma unroll
  for (int j = 0; j < 8; j++) o[j] = P ? (j < 2 ? 0u : E[j - 2]) : E[8 + j];
  sts128(xc, o[0], o[1], o[2], o[3]); sts128(xc + 512, o[4], o[5], o[6], o[7]);
#pragma unroll
  for (int j = 0; j < 8; j++) o[j] = P ? E[6 + j] : E[j];
  TS(25);
  if (more) {
    sts128(xc + 4096, o[0], o[1], o[2], o[3]); sts128(xc + 4608, o[4], o[5], o[6], o[7]);
    bar_arrive(12, 160);
    return;
  }
  bar_sync(1 + (warp >> 2), 128);
  const uint4 vv[2] = {lds128(xc + (P ? -2048 : 2048)), lds128(xc + (P ? -1536 : 2560))};
#pragma unroll
  for (int q = 0; q < 2; q++) {
    const uint4 v = vv[q];
    stsm4t(tb + (cv.ca >> 16) + q * 1024, hadd2u(o[4 * q], v.x) & cv.cb, hadd2u(o[4 * q + 1], v.y) & cv.cb, hadd2u(o[4 * q + 2], v.z) & cv.cb, hadd2u(o[4 * q + 3], v.w) & cv.cb);
  }
  fence_async();
  bar_sync(1 + (warp >> 2), 128);
  if ((warp & 3) == 3 && lane == 0) {
    asm volatile("cp.async.bulk.tensor.2d.global.shared::cta.bulk_group [%0, {%2, %3}], [%1];" :: "l"(tmx), "r"(tb + W_UP + 1024), "r"(ch * 16), "r"(0) : "memory");
    asm volatile("cp.async.bulk.commit_group;" ::: "memory");
  }
}

template <bool FAR> __global__ void __launch_bounds__(NT, 1)
fused_kernel(const __grid_constant__ Params p, const __grid_constant__ TMaps tm) {
  extern __shared__ __align__(1024) unsigned char smem[];
  const int c = blockIdx.x;
  const bool five = (c & 1) == 0;
  const uint32_t pitch = five ? 64 : 80;
  const uint32_t ones = 0x3F803F80u;
  const int tid = threadIdx.x, lane = tid & 31;
  {
    const int w4 = tid >> 7, k5 = !five && w4 == 3;
    load_params<FAR>(p, k5 ? 512 + (c >> 1) : w4 * 128 + c, tid & 127, OFF_W + w4 * W_BYTES + W_KT + k5 * 2048, w4 == 0 || w4 == (five ? 1 : 3));
  }
  const int warp = (int)uni(tid >> 5), wg = warp >> 2;
  TS(0);
  if (__builtin_expect(wg == 4, 0)) {
    asm volatile("setmaxnreg.dec.sync.aligned.u32 32;");
    const int role = warp;
    const int u0 = (c >> 1) * 9 + (five ? ((c & 2) ? 5 : 0) : ((c & 2) ? 0 : 4));
    const uint32_t t0 = clock() + c * 4;
    if (role < 18) {
      const bool pf = role == 17;
      if (!pf) {
        if (lane < 19) asm volatile("mbarrier.init.shared::cta.b64 [%0], %1;" :: "r"(OFF_MISC + lane * 8), "r"((unsigned)(lane - 2) < 4u ? 4 : 1) : "memory");
        if (lane < 2) asm volatile("mbarrier.arrive.expect_tx.shared::cta.b64 _, [%0], %1;" :: "r"(OFF_MISC + lane * 8), "r"(lane ? (five ? 36864 : 51200) : pitch * 1152) : "memory");
        fence_async();
        bar_arrive(5, 576);
      } else if (smem_u32(smem) != SB) __trap();
      const CUtensorMap* tmb = &tm.m[five ? 3 : 0];
#pragma unroll 1
      for (int u = pf ? X_NE : 0; u < 17; u++) {
        const uint32_t e = p.sched[five][u], kind = e & 3, s = (e >> 2) & 15, dst = e >> 14;
        if (kind == 3) continue;
        while ((int)(clock() - t0) < X_PF0 + (pf || u < X_NE ? u * X_PFD : X_LAG + u * X_TD)) __nanosleep(20);
        if (!pf && (e & 0x3FC0)) mbar_wait(OFF_MISC + ((e >> 6) & 255));
        if (lane == 0) {
          if (pf) {
            if (kind == 2) asm volatile("cp.async.bulk.prefetch.tensor.3d.L2.global [%0, {%1, %2, %3}];" :: "l"(tmb + 2), "r"(0), "r"(u0 * 8), "r"(s) : "memory");
            else l2_prefetch((kind ? p.w_up : p.w_gate) + (uint32_t)(s * 884736 + c * 6912), 6912);
          } else if (kind == 2) asm volatile("cp.async.bulk.tensor.3d.shared::cluster.global.mbarrier::complete_tx::bytes [%0], [%1, {%3, %4, %5}], [%2];"
                                             :: "r"(dst), "l"(tmb + 2), "r"(MB_D), "r"(0), "r"(u0 * 8), "r"(s) : "memory");
          else tma_box(dst, tmb + kind, MB_GU, u0 * 8, s * 96);
        }
        if (u == 5) TS(2);
        if (u == 10) TS(3);
      }
      TS(4);
      TS_DUMP();
    } else if (role == 18) {
      sts32(MISC_EPOCH, 0);
      bar_arrive(5, 576);
      uint4* q = lane < 2 ? &p.s->R[c * 2 + lane] : lane < 11 ? &p.s->HS[c * 9 + lane - 2] : lane == 11 ? &p.s->HS[1152 + (c & 7)] : (uint4*)&p.s->FLAG[c * 8];
      if (lane < (c < 8 ? 12 : 11)) str128(q, ~0u, ~0u, ~0u, ~0u);
      const uint32_t ep = __shfl_sync(0xffffffffu, ldr32(q), 31) + 1u;
      sts32(MISC_EPOCH, ep | 0x80000000u);
      TSX(21);
      if (lane == 31) str32(q, ep);
      bar_sync(11, 64);
      if (lane == 0) { load_tile(&tm.m[6], 1, c); load_tile(&tm.m[6], 3, c); }
      TSX(14);
      mbar_wait(MB_KF + (lane & 3) * 8);
      __syncwarp();
      { const uint2 e = lds64(MISC_EM); if (lane < 2) str128(&p.s->SC[c * 2 + lane], e.x, __byte_perm(e.y, ep, 0x6540), 0, 0); }
      while ((int)(clock() - t0) < X_SCT) __nanosleep(100);
      {
        uint2 v[4];
#pragma unroll 1
        for (int it = 0; it < SPIN_MAX; it++) {
          uint32_t bad = 0;
#pragma unroll
          for (int q = 0; q < 4; q++) v[q] = ldr64(&p.s->SC[lane * 2 + q * 64]);
#pragma unroll
          for (int q = 0; q < 4; q++) bad |= (v[q].y >> 8) ^ (ep & 0xFFFFFFu);
          if (!__any_sync(0xffffffffu, bad)) break;
        }
#pragma unroll
        for (int q = 0; q < 4; q++) {
#pragma unroll
          for (int k = 0; k < 4; k++) asm volatile("st.shared.u8 [%0], %1;" :: "r"(sc_addr(4 * k + q) + lane), "r"(v[q].x >> (8 * k)) : "memory");
          if (lane & 1) asm volatile("st.shared.u8 [%0], %1;" :: "r"(sc_addr(16) + q * 16 + (lane >> 1)), "r"(v[q].y) : "memory");
        }
      }
      __syncwarp();
      if (lane == 0) mbar_arrive(MB_SC);
    } else {
      uint32_t w[9], d[9];
      float s = 0.f;
#pragma unroll
      for (int i = 0; i < 9; i++) { w[i] = ldnc32(p.w_r + (i < 8 ? lane * 4 + (i & 3) + (i >> 2) * 128 : 256 + lane)); d[i] = ldnc32(p.dskip + lane + 32 * i); }
#pragma unroll
      for (int i = 0; i < 9; i++) { sts32(OFF_WR + lane * 4 + i * 128, w[i]); sts32(OFF_WR + 1152 + lane * 4 + i * 128, d[i]); s += bf_lo(w[i]) + bf_hi(w[i]); }
      sts32(MISC_SW, __float_as_uint(warp_sum(s)));
      TSX(23);
      bar_sync(10, 544);
      if (lane == 0) {
        const uint32_t tp = clock();
        TSX(1);
        while ((int)(clock() - tp) < X_DELTA || (int)(clock() - t0) < X_ABS - c * 4) {}
        TSX(24);
        load_tile(&tm.m[6], 0, c);
        TSX(15);
        while ((int)(clock() - t0) < X_ABS + X_DSTEP - c * 4) {}
      }
      bar_sync(11, 64);
      if (lane == 0) {
        load_tile(&tm.m[6], 2, c);
        mbar_arrive(MB_GF);
      }
      if (five) {
        mbar_wait(MB_KF);
#pragma unroll 1
        for (int it = 0; it < SPIN_MAX; it++) {
          if (lane == 0) load_tile(&tm.m[6], 4, c);
          mbar_wait(MB_UL + 32, it & 1);
          uint32_t m = 1;
#pragma unroll
          for (int q = 0; q < 4; q++) { uint32_t r0, r1, r2, r3; ldsm4(OFF_W + ALT + W_UP + 1024 + lane * 32 + (lane & 4) * 4 + q * 1024, r0, r1, r2, r3); m &= r0 & r1 & r2 & r3; }
          if (__all_sync(0xffffffffu, m || (lane & 3))) break;
        }
        bar_arrive(7, 288);
        bar_sync(12, 160);
#pragma unroll 1
        for (int w = 0; w < 4; w++) {
          const uint32_t xa = OFF_W + W_KT + lane * 16, mk = lane < 8 ? 0xFFFEFFFEu : ~0u, ya = OFF_W + W_UP + (32 + lane) * 32 + ((w ^ (lane >> 2)) & 1) * 16 + (w & 2) * 1024;
          const uint4 a = lds128(xa + 4096 + w * 1024), b = lds128(xa + (w ^ 2) * 1024), d = lds128(xa + 4608 + w * 1024), e = lds128(xa + 512 + (w ^ 2) * 1024);
          stsm4t(ya, hadd2u(a.x, b.x) & mk, hadd2u(a.y, b.y) & mk, hadd2u(a.z, b.z) & mk, hadd2u(a.w, b.w) & mk);
          stsm4t(ya + 1024, hadd2u(d.x, e.x) & mk, hadd2u(d.y, e.y) & mk, hadd2u(d.z, e.z) & mk, hadd2u(d.w, e.w) & mk);
        }
        fence_async();
        __syncwarp();
        if (lane == 0) {
          asm volatile("cp.async.bulk.tensor.2d.global.shared::cta.bulk_group [%0, {%2, %3}], [%1];" :: "l"(&tm.m[7]), "r"(OFF_W + W_UP + 1024), "r"(c * 16), "r"(0) : "memory");
          asm volatile("cp.async.bulk.commit_group;" ::: "memory");
          asm volatile("cp.async.bulk.wait_group.read 0;" ::: "memory");
        }
      }
      uint4* rp = &p.s->R[c * 2 + (lane & 1)];
      asm volatile("" : "+l"(rp));
      bar_sync(0, 544);
      if (lane == 0) mbar_arrive(MB_H);
      bar_sync(5, 544);
      const uint4 k = lds128(MISC_RK + (lane & 1) * 16);
      if (lane < 2) str128(rp, k.x, k.y, k.z, k.w);
    }
    return;
  }
  const int wt = tid & 127, g = lane >> 2, t = lane & 3;
  const uint32_t wb = OFF_W + wg * W_BYTES;
  const int lw = warp - (five ? 8 : 4);
  if ((unsigned)lw < 8u) {
    const unsigned char* xp = p.x + (uint32_t)((c * 8 + lw) * 2304 + lane * 16);
    const uint32_t row = OFF_YT + lw * (2 * YT_PITCH) + (lw >> 2) * 64 + lane * 16;
    { const uint32_t tq = clock(); while ((int)(clock() - tq) < X_XD) {} }
#pragma unroll
    for (int k = 0; k < 5; k++)
      if (k < 4 || lane < 16)
        asm volatile("cp.async.cg.shared.global [%0], [%1], 16;" :: "r"(row + k * 512 + ((k > 2 || (k == 2 && lane >= 8)) ? 32 : 0)), "l"(xp + k * 512) : "memory");
  }
  asm volatile("cp.async.commit_group;" ::: "memory");
  const ConvC cv = conv_consts(warp & 3, lane);
  zero_pads(wb, wt);
  load_params<FAR>(p, wg * 128 + c, wt, wb + W_KT, lw >= 0);
  asm volatile("cp.async.commit_group;" ::: "memory");
  asm volatile("setmaxnreg.inc.sync.aligned.u32 112;");
  {
    uint4 kw;
    uint4* kx = &p.s->KX[(c >> 1) * 128 + wt];
    bool two = wg == (five ? 1 : 3);
    uint32_t ep;
    int phase = (unsigned)lw < 8u ? 3 : 2;
#pragma unroll 1
    for (;;) {
      const bool first = two && !five;
      if (phase) asm volatile("cp.async.wait_group 1;" ::: "memory"); else asm volatile("cp.async.wait_group 0;" ::: "memory");
      if (phase == 3) {
        __syncwarp();
        TS(21);
        float d[4][4];
#pragma unroll
        for (int r = 0; r < 2; r++) {
          const uint32_t row = OFF_YT + (2 * lw + r) * YT_PITCH + (lw >> 2) * 64;
          const uint4 a = lds128(row + lane * 16), b = lds128(row + 512 + lane * 16);
          const uint32_t e = lds32(row + 1024 + lane * 4);
#pragma unroll
          for (int i = 0; i < 4; i++) d[r][i] = d[r + 2][i] = 0.f;
          mma_bf16(d[r], a.x, ones, a.y, ones, a.x, a.y); mma_bf16(d[r + 2], a.z, ones, a.w, ones, a.z, a.w);
          mma_bf16(d[r], b.x, ones, b.y, ones, b.x, b.y); mma_bf16(d[r + 2], b.z, ones, b.w, ones, b.z, b.w);
          mma_bf16_k8(d[r], e, ones, e);
#pragma unroll
          for (int i = 0; i < 4; i++) d[r][i] += d[r + 2][i];
        }
        const float q0 = __shfl_sync(0xffffffffu, d[0][0], 9 * t) + __shfl_sync(0xffffffffu, d[0][1], 9 * t + 4);
        const float q1 = __shfl_sync(0xffffffffu, d[1][0], 9 * t) + __shfl_sync(0xffffffffu, d[1][1], 9 * t + 4);
        float r;
        const LnC lc = ln_consts(quad_sum(lane & 16 ? d[1][2] + d[1][3] : d[0][2] + d[0][3]), quad_sum(lane & 16 ? q1 : q0), r);
        if ((lane & 15) < 3) sts16(MISC_LN1 + (lane & 15) * 32 + lw * 4 + (lane >> 4) * 2, t == 0 ? lc.m2 : t == 1 ? lc.rh2 : lc.rl2);
      } else {
        KgState ks;
        uint32_t raw[7];
        bar_sync(1 + wg, 128);
        TS(22);
#pragma unroll
        for (int i = 0; i < 7; i++) raw[i] = lds16(wb + W_KT + first * 2048 + i * 256 + (i < 6 ? wt : (c >> first) & 7) * 2);
        kgen_tables_n(raw, wb, wt, ks);
        TS(20);
        bar_sync(1 + wg, 128);
        const int em = kgen_tables_m(wb, wt, ks);
        asm volatile("st.shared.u8 [%0], %1;" :: "r"(MISC_EM + wg + first), "r"(em + 9) : "memory");
        fence_async();
      }
      if (phase & 2) {
        const uint32_t tr_addr = tr_base(lane) + warp * 32;
        uint4* dst = &p.s->X[c * DM * 2 + warp * 32 + (8 * (t >> 1) + g) * 2 + (t & 1)];
        TS(23);
        bar_sync(5, 576);
        uint32_t x[3][4];
        ldsm4t(tr_addr, x[0][0], x[0][1], x[0][2], x[0][3]);
        const uint4 m = lds128(MISC_LN1 + (t & 1) * 16), rl = lds128(MISC_LN1 + 64 + (t & 1) * 16), rh = lds128(MISC_LN1 + 32 + (t & 1) * 16);
        ldsm4t(tr_addr + 512, x[1][0], x[1][1], x[1][2], x[1][3]);
        if (wg == 2) ldsm4t(tr_addr + 768, x[2][0], x[2][1], x[2][2], x[2][3]);
#pragma unroll
        for (int q = 0; q < 3; q++) {
          if (q < 2 || wg == 2) {
            const uint32_t r0 = ln_apply(x[q][0], m.x, rh.x, rl.x), r1 = ln_apply(x[q][1], m.y, rh.y, rl.y), r2 = ln_apply(x[q][2], m.z, rh.z, rl.z), r3 = ln_apply(x[q][3], m.w, rh.w, rl.w);
            str128(dst + q * 512 - (q == 2 ? 256 : 0), (pack_h(bf_lo(r0), bf_hi(r0)) & 0xFFFEFFFEu) | 1u, pack_h(bf_lo(r1), bf_hi(r1)), pack_h(bf_lo(r2), bf_hi(r2)), pack_h(bf_lo(r3), bf_hi(r3)));
          }
          if (q == 0) TS(30);
        }
        bar_arrive(10, 544);
        TS(1);
      } else bar_sync(1 + wg, 128);
      phase &= 1;
      if (phase) { phase = 0; continue; }
      TS(14);
      float acc[20];
      const uint32_t alo = (wb >> 4) | (8u << 16);
      wg_fence();
      wgmma40_ss_init(acc, alo, alo + 1024, 2048 >> 4);
#pragma unroll
      for (int k = 1; k < 8; k++) wgmma40_ss(acc, alo + k * 16, alo + 1024 + k * 16, 2048 >> 4);
      wg_commit();
      const uint4 k4 = lds128(wb + W_MISC + 16);
      const float k2048 = (float)(int)(k4.x + k4.y + k4.z + k4.w) * (1.f / 262144.f);
      wg_wait<0>();
      const float un = 1.f / 8192.f;
      kw.x = pack_h((acc[0] - acc[3]) * un, (acc[4] - acc[7]) * un);
      kw.y = pack_h((acc[8] - acc[11]) * un, (acc[12] - acc[15]) * un);
      kw.z = pack_h((acc[16] - acc[19]) * un, k2048 * un);
      TS(24);
      ep = 0;
      if (two) SPIN_WHILE(ep == 0, ep = lds32(MISC_EPOCH));
      if (five || !two) break;
      str128(kx, kw.x, kw.y, kw.z, ep);
      two = false;
    }
    if (lane == 0) mbar_arrive(MB_KF + wg * 8);
    mbar_wait(MB_KF + wg * 8);
    if (two) { mbar_wait(MB_KF); zero_pads(OFF_W + ALT, wt); }
    uint32_t tb = wb;
#pragma unroll 1
    for (;;) {
      kgen_build(tb, (tb == wb ? wb : OFF_W + 16384 - 25600) + 25600, wg, wt, kw.x, kw.y, kw.z);
      TS(15);
      if (!two) break;
      two = false;
      kw.w = 0;
      SPIN_WHILE(kw.w != ep, kw = ldr128(kx));
      tb = OFF_W + ALT;
    }
    fence_async();
    TS(31);
    if (tb != wb) bar_arrive(7, 288);
    bar_sync(1 + wg, 128);
  }
  uint32_t tpub;
#pragma unroll 1
  for (int item = 0;; item++) {
    TS(2);
    conv_item(item ? OFF_W + ALT : wb, cv, p.zero, &tm.m[7], item ? 512 + (c >> 1) : wg * 128 + c, warp, lane, tid == 0 && !item, five && wg >= X_RW, five && !wg && !item);
    tpub = clock() - item * X_YD;
    if (wg || !five || item) break;
    TS(27);
    bar_sync(7, 288);
  }
  TS(4);

  const int ln = lane ^ p.zero, td = warp * 32 + ln, gg = ln >> 2, tt = ln & 3;
  const int tok = c * 16 + warp;
  const int fu = warp / 3, fk = warp - fu * 3;
  uint32_t wa[12][4];
  {
    uint32_t hw[9], wr[9];
    const uint32_t row = keep(OFF_YT + warp * YT_PITCH + (warp >> 3) * 64 + ln * 16);
    const uint32_t wabase = keep(((ln & 8) ? OFF_W + (fk + 1) * W_BYTES : OFF_G + fk * 192 * pitch) + ((ln >> 4) * 8 + (ln & 7)) * pitch
                                 + (five ? ((fu ^ (ln >> 1)) & 3) : min(fu, 4)) * 16);
    float sw;
    {
      const uint4 m = lds128(MISC_LN1 + (tt & 1) * 16), rh = lds128(MISC_LN1 + 32 + (tt & 1) * 16), rl = lds128(MISC_LN1 + 64 + (tt & 1) * 16);
      mbar_wait(MB_SC);
#pragma unroll
      for (int i = 0; i < 9; i++) wr[i] = lds32(OFF_WR + ln * 4 + i * 128);
      sw = __uint_as_float(lds32(MISC_SW));
#pragma unroll 1
      for (int tp = warp;; tp += 12) {
        const int ch = tp * 32 + 8 * (tt >> 1) + gg;
        const uint32_t tr_addr = tr_base(ln) + tp * 64;
        const uint4* ysrc = &p.s->X[c * DM * 2 + ch * 2 + (tt & 1)];
        uint32_t x[2][4], ud[2][4], s[2];
#pragma unroll
        for (int q = 0; q < 2; q++) {
          asm volatile("ld.shared.u8 %0, [%1];" : "=r"(s[q]) : "r"(sc_addr(tp) + (ch & 31) + q * 16) : "memory");
          s[q] *= 0x800080u;
          const uint32_t dk = lds16(OFF_WR + 1152 + ch * 2 + q * 32) * 0x10001u;
          ldsm4t(tr_addr + q * 32, x[q][0], x[q][1], x[q][2], x[q][3]);
          ud[q][0] = bf_mul2(ln_apply(x[q][0], m.x, rh.x, rl.x), dk); ud[q][1] = bf_mul2(ln_apply(x[q][1], m.y, rh.y, rl.y), dk);
          ud[q][2] = bf_mul2(ln_apply(x[q][2], m.z, rh.z, rl.z), dk); ud[q][3] = bf_mul2(ln_apply(x[q][3], m.w, rh.w, rl.w), dk);
        }
        asm volatile("cp.async.bulk.wait_group.read 0;" ::: "memory");
        while ((int)(clock() - tpub) < X_YD) {}
        TS(5);
        uint4 v[2];
        v[0] = ldr128(ysrc); v[1] = ldr128(ysrc + 32);
        SPIN_WHILE((v[0].x | v[1].x) & 1u, if (v[0].x & 1u) v[0] = ldr128(ysrc); if (v[1].x & 1u) v[1] = ldr128(ysrc + 32));
#pragma unroll
        for (int q = 0; q < 2; q++) {
          const uint32_t s2 = s[q];
          stsm4t(tr_addr + q * 32, bf_add2(x[q][0], bf_fma2(h2bf(v[q].x), s2, ud[q][0])), bf_add2(x[q][1], bf_fma2(h2bf(v[q].y), s2, ud[q][1])),
                 bf_add2(x[q][2], bf_fma2(h2bf(v[q].z), s2, ud[q][2])), bf_add2(x[q][3], bf_fma2(h2bf(v[q].w), s2, ud[q][3])));
        }
        if ((tp & ~1) != 4) break;
      }
    }
    TS(28);
    bar_sync(0, 544);
    TS(6);
    float d[4] = {0.f, 0.f, 0.f, 0.f}, e[4] = {0.f, 0.f, 0.f, 0.f}, rd;
    {
      const uint4 a = lds128(row), b = lds128(row + 512);
      hw[8] = lds32(row + 1024 - ln * 12);
      hw[0] = a.x; hw[1] = a.y; hw[2] = a.z; hw[3] = a.w; hw[4] = b.x; hw[5] = b.y; hw[6] = b.z; hw[7] = b.w;
    }
    mma_bf16(e, hw[0], hw[1], hw[2], hw[3], ones, ones);
#pragma unroll
    for (int i = 0; i < 8; i += 2) mma_bf16(d, hw[i], wr[i], hw[i + 1], wr[i + 1], hw[i], hw[i + 1]);
    mma_bf16(e, hw[4], hw[5], hw[6], hw[7], ones, ones);
    e[0] += e[2];
    mma_bf16_k8(e, hw[8], wr[8], ones);
    mma_bf16_k8(d, hw[8], wr[8], hw[8]);
    const float hwsum = diag_sum(d[2], d[3], tt);
    LnC l2 = ln_consts(diag_sum(e[0], e[0], tt), diag_sum(d[0], d[1], tt), rd);
    const uint32_t b = pack_bf(0.f, fmaf(-bf_lo(l2.m2), sw, hwsum) * rd);
    uint32_t key = max(min((b ^ (((int)b >> 31) | 0x80000000u)) >> 16, 0xFFFEu), 1u);
    sts16(MISC_RK + warp * 2, key);
    bar_sync(5, 544);
    asm volatile("" : "+r"(l2.m2) :: "memory");
    TS(7);
    const uint32_t tr0 = clock();
    key = (key << 16) | (2047 - tok);
    uint32_t loc = ln < 16 ? (lds16(MISC_RK + ln * 2) << 16) | (2047 - c * 16 - ln) : 0u;
    int rank = __popc(__ballot_sync(0xffffffffu, loc > key));
#pragma unroll
    for (int i = 0; i < 9; i++) wr[i] = keep(ln_apply(hw[i], l2.m2, l2.rh2, l2.rl2));
    const uint2* rsrc = (const uint2*)p.s->R + td;
    while ((int)(clock() - tr0) < X_RD) {}
    uint2 rv = ldr64(rsrc);
    mbar_wait(MB_GU);
    if (warp < (five ? 12 : 15)) {
#pragma unroll
      for (int k = 0; k < X_WS; k++) ldsm4t(wabase + k * 16 * pitch, wa[k][0], wa[k][1], wa[k][2], wa[k][3]);
    }
#define OUT_ROW { uint32_t* o = p.out + tok * 288 + ln * 4; \
      *(uint4*)o = make_uint4(bf_add2(hw[0], wr[0]), bf_add2(hw[1], wr[1]), bf_add2(hw[2], wr[2]), bf_add2(hw[3], wr[3])); \
      *(uint4*)(o + 128) = make_uint4(bf_add2(hw[4], wr[4]), bf_add2(hw[5], wr[5]), bf_add2(hw[6], wr[6]), bf_add2(hw[7], wr[7])); \
      o[256 - ln * 3] = bf_add2(hw[8], wr[8]); }
    if (rank >= X_OR) OUT_ROW
#pragma unroll 1
    for (int base = 0; base < 8; base += 4) {
      uint32_t T[4];
#pragma unroll
      for (int j = 0; j < 4; j++) {
        const uint32_t mx = __reduce_max_sync(0xffffffffu, loc);
        if (loc == mx) loc = 0;
        T[j] = (td >> 2) == c ? ~0u : (td >> 2) < c ? (mx & 0xFFFF0000u) - 1u : mx | 0xFFFFu;
      }
      const uint32_t sh = keep(ln < 16 ? 0x4440u + (rank & 3) : 0x4344u), ca = keep(MISC_CNT + base * 16 + (ln & 15) * 4);
      SPIN_WHILE(rv.x == ~0u, if (rv.x == ~0u) rv = ldr64(rsrc));
      TS(16);
      uint32_t cnt = 0, cn2 = 0;
#pragma unroll
      for (int j = 0; j < 4; j++)
        asm("{ .reg .pred a, b, c, d; setp.gt.u32 a, %2, %6; setp.gt.u32 b, %3, %6; setp.gt.u32 c, %4, %6; setp.gt.u32 d, %5, %6; "
            "@a add.u32 %0, %0, %7; @b add.u32 %1, %1, %7; @c add.u32 %0, %0, %7; @d add.u32 %1, %1, %7; }"
            : "+r"(cnt), "+r"(cn2) : "r"(rv.x), "r"(rv.x << 16), "r"(rv.y), "r"(rv.y << 16), "r"(T[j]), "r"(1u << (8 * j)));
      sts32(MISC_CNT + base * 16 + warp * 4, __reduce_add_sync(0xffffffffu, cnt + cn2));
      bar_sync(0, 512);
      cnt = __reduce_add_sync(0xffffffffu, __byte_perm(lds32(ca), 0, sh));
      if ((rank & ~3) == base && rank + (int)(cnt & 0xFFFFu) < 8) {
        rank += cnt & 0xFFFFu;
        uint4* hs = p.s->HS + rank * 72 + ln;
        str128(hs, wr[0], wr[1], wr[2], wr[3]); str128(hs + 32, wr[4], wr[5], wr[6], wr[7]); str32((uint32_t*)(hs + 64) - ln * 3, wr[8]);
        str128(hs + 576, hw[0], hw[1], hw[2], hw[3]); str128(hs + 608, hw[4], hw[5], hw[6], hw[7]); str32((uint32_t*)(hs + 640) - ln * 3, hw[8]);
        if (ln == 0) str32(&p.s->HS[1152 + rank], key);
        rank = 16;
      }
      if (cnt >= (4u << 16)) break;
    }
    TS(8);
    tpub = clock();
    if (rank < X_OR) OUT_ROW
    if (warp < (five ? 12 : 15)) {
#pragma unroll
      for (int k = X_WS; k < 12; k++) ldsm4t(wabase + k * 16 * pitch, wa[k][0], wa[k][1], wa[k][2], wa[k][3]);
    }
  }
  uint32_t wd[10][4];
  const uint32_t xb = keep(OFF_XS + (ln & 7) * 1168 + (fk * 24 + (ln >> 3)) * 16);
  if (warp >= 7) {
    const uint32_t db = down_box(warp - 7, five) + (ln & 7) * 128;
    mbar_wait(MB_D);
#pragma unroll
    for (int j = 0; j < 4; j++) {
      const uint32_t a = db + (ln >> 4) * 1024 + (((2 * j + ((ln >> 3) & 1)) ^ (ln & 7)) << 4);
      ldsm4t(a, wd[j][0], wd[j][1], wd[j][2], wd[j][3]);
      ldsm4t(a + 2048, wd[4 + j][0], wd[4 + j][1], wd[4 + j][2], wd[4 + j][3]);
    }
#pragma unroll
    for (int j = 0; j < 2; j++) ldsm4t(db + 4096 + (((4 * j + (ln >> 3)) ^ (ln & 7)) << 4), wd[8 + j][0], wd[8 + j][1], wd[8 + j][2], wd[8 + j][3]);
  } else if (warp < 6) {
    const int r = td / 24;
    const uint4* src = &p.s->HS[td + r * 48];
    const uint32_t xs = keep(OFF_XS + (td + r * 49) * 16);
    uint4 a[3];
    uint32_t m = ~0u;
    while ((int)(clock() - tpub) < X_HD) {}
    TS(19);
    SPIN_WHILE(m == ~0u, if (m == ~0u) { a[0] = ldr128(src); a[1] = ldr128(src + 24); a[2] = ldr128(src + 48); } m = max(max(max(a[0].x, a[1].x), max(a[2].x, a[2].y)), max(a[2].z, a[2].w)));
#pragma unroll
    for (int q = 0; q < 3; q++) sts128(xs + q * 384, a[q].x, a[q].y, a[q].z, a[q].w);
  }
  bar_sync(0, 512);
  TS(9);

  if (warp < (five ? 12 : 15)) {
    float d0[4] = {0.f, 0.f, 0.f, 0.f}, d1[4] = {0.f, 0.f, 0.f, 0.f};
#pragma unroll
    for (int k = 0; k < 12; k += 2) {
      uint32_t b0, b1, b2, b3;
      ldsm4(xb + k * 32, b0, b1, b2, b3);
      mma_bf16(d0, wa[k][0], wa[k][1], wa[k][2], wa[k][3], b0, b1);
      mma_bf16(d1, wa[k + 1][0], wa[k + 1][1], wa[k + 1][2], wa[k + 1][3], b2, b3);
    }
    sts128(OFF_RED + td * 16, __float_as_uint(d0[0] + d1[0]), __float_as_uint(d0[1] + d1[1]), __float_as_uint(d0[2] + d1[2]), __float_as_uint(d0[3] + d1[3]));
  }
  TS(26);
  if (warp < 5) {
    const uint32_t rb = OFF_RED + warp * 1536 + ln * 16;
    bar_sync(9, 512);
    const uint4 pa = lds128(rb), pb = lds128(rb + 512), pc = lds128(rb + 1024);
    const float ga = bfr(__uint_as_float(pa.x) + __uint_as_float(pb.x) + __uint_as_float(pc.x));
    const float gb = bfr(__uint_as_float(pa.y) + __uint_as_float(pb.y) + __uint_as_float(pc.y));
    const uint32_t uu = pack_bf(__uint_as_float(pa.z) + __uint_as_float(pb.z) + __uint_as_float(pc.z), __uint_as_float(pa.w) + __uint_as_float(pb.w) + __uint_as_float(pc.w));
    float ra, rb2;
    asm("rcp.approx.ftz.f32 %0, %1;" : "=f"(ra) : "f"(1.f + ex2(ga * -1.4426950408889634f)));
    asm("rcp.approx.ftz.f32 %0, %1;" : "=f"(rb2) : "f"(1.f + ex2(gb * -1.4426950408889634f)));
    const uint32_t act = bf_mul2(pack_bf(ga * ra, gb * rb2), uu);
    sts32(OFF_ACT + td * 4, act);
  } else bar_arrive(9, 512);
  uint4* dst = &p.s->X[c * DM * 2 + (warp - 7) * 64 + tt * 8 + gg];
  asm volatile("" : "+l"(dst));
  bar_sync(8, 512);
  tpub = clock();
  if (warp >= 7) {
    uint32_t b0, b1, b2, b3, b4;
    ldsm4t(OFF_ACT + ln * 16, b0, b1, b2, b3);
    asm volatile("ldmatrix.sync.aligned.m8n8.x1.trans.shared.b16 {%0}, [%1];" : "=r"(b4) : "r"(OFF_ACT + 512 + ln * 16) : "memory");
    float y[4][4];
#pragma unroll
    for (int j = 0; j < 4; j++) {
      y[j][0] = y[j][1] = y[j][2] = y[j][3] = 0.f;
      mma_bf16(y[j], wd[j][0], wd[j][1], wd[j][2], wd[j][3], b0, b1);
    }
#pragma unroll
    for (int j = 0; j < 4; j++) mma_bf16(y[j], wd[4 + j][0], wd[4 + j][1], wd[4 + j][2], wd[4 + j][3], b2, b3);
    if (!five) {
#pragma unroll
      for (int j = 0; j < 4; j++) mma_bf16_k8(y[j], wd[8 + (j >> 1)][2 * (j & 1)], wd[8 + (j >> 1)][2 * (j & 1) + 1], b4);
    }
    str128(dst, (pack_bf(y[0][0], y[0][1]) & ~1u) | 0x10000u, pack_bf(y[0][2], y[0][3]), pack_bf(y[1][0], y[1][1]), pack_bf(y[1][2], y[1][3]));
    str128(dst + 32, (pack_bf(y[2][0], y[2][1]) & ~1u) | 0x10000u, pack_bf(y[2][2], y[2][3]), pack_bf(y[3][0], y[3][1]), pack_bf(y[3][2], y[3][3]));
  }
  TS(10);

  if (c < 72) {
    const uint4* src = &p.s->X[(warp * 4 + tt) * (DM * 2) + c * 8 + gg];
    const int slot = (c & 3) * 2 + (ln >> 4), dw = (c >> 2) * 16 + (ln & 15);
    uint32_t hv = 0, kv = 0, res = 0, rs2 = 0;
    uint32_t* o = p.out;
    if (warp == 0) {
      hv = ~0u;
      SPIN_WHILE(max(hv, kv) == ~0u, hv = ldr32((const uint32_t*)p.s->HS + 2304 + slot * 288 + dw); kv = ldr32(&p.s->HS[1152 + slot]));
      const float r = bf_hi(kv ^ (((int)~kv >> 31) | 0x80000000u));
      float rs;
      asm("rcp.approx.ftz.f32 %0, %1;" : "=f"(rs) : "f"(1.f + ex2(r * -1.4426950408889634f)));
      rs2 = keep(pack_bf(rs, rs));
      res = lds32(OFF_XS + slot * 1168 + dw * 4);
      o += (2047 - (int)(kv & 2047u)) * 288 + dw;
      asm volatile("" : "+l"(o));
    }
    const uint32_t sel = (gg & 1) ? 0x3F800000u : 0x00003F80u;
    const uint32_t q0 = keep((gg >> 1) == 0 ? sel : 0u), q1 = keep((gg >> 1) == 1 ? sel : 0u), q2 = keep((gg >> 1) == 2 ? sel : 0u), q3 = keep((gg >> 1) == 3 ? sel : 0u);
    const uint32_t fa = keep(OFF_FIN + warp * 256 + (gg & 1) * 128 + (gg >> 1) * 32 + tt * 8), fb = keep(OFF_FIN + ln * 8);
    uint4 a0 = make_uint4(0, 0, 0, 0), a1 = a0;
    while ((int)(clock() - tpub) < X_PD) {}
    SPIN_WHILE(!(a0.x & a1.x & 0x10000u), if (!(a0.x & 0x10000u)) a0 = ldr128(src); if (!(a1.x & 0x10000u)) a1 = ldr128(src + 64 * DM * 2));
    float d[4] = {0.f, 0.f, 0.f, 0.f}, e[4] = {0.f, 0.f, 0.f, 0.f};
    mma_bf16(d, q0, q2, q1, q3, a0.x, a0.y); mma_bf16(e, q0, q2, q1, q3, a0.z, a0.w);
    mma_bf16(d, q0, q2, q1, q3, a1.x, a1.y); mma_bf16(e, q0, q2, q1, q3, a1.z, a1.w);
    sts64(fa, __float_as_uint(d[0] + e[2]), __float_as_uint(d[1] + e[3]));
    TS(11);
    if (warp == 0) {
      bar_sync(0, 512);
      float2 s[16];
#pragma unroll
      for (int i = 0; i < 16; i++) { const uint2 q = lds64(fb + i * 256); s[i] = make_float2(__uint_as_float(q.x), __uint_as_float(q.y)); }
#pragma unroll
      for (int k = 1; k < 16; k *= 2)
#pragma unroll
        for (int i = 0; i < 16; i += 2 * k) { s[i].x += s[i + k].x; s[i].y += s[i + k].y; }
      *o = bf_add2(hv, bf_add2(res, bf_mul2(pack_bf(s[0].x, s[0].y), rs2)));
    } else bar_arrive(0, 512);
  }
  TS(12);
  TS_DUMP();
}

typedef CUresult (*EncodeFn)(CUtensorMap*, CUtensorMapDataType, cuuint32_t, void*, const cuuint64_t*, const cuuint64_t*, const cuuint32_t*,
                             const cuuint32_t*, CUtensorMapInterleave, CUtensorMapSwizzle, CUtensorMapL2promotion, CUtensorMapFloatOOBfill);

}

extern "C" void kernel_launch(void* const* d_in, const int* in_sizes, int n_in, void* d_out, int out_size) {
  (void)in_sizes; (void)n_in; (void)out_size;
  static EncodeFn enc = nullptr;
  static Scratch* scratch = nullptr;
  if (!enc) {
    void* fn = nullptr;
    cudaDriverEntryPointQueryResult qr;
    cudaGetDriverEntryPoint("cuTensorMapEncodeTiled", &fn, cudaEnableDefault, &qr);
    enc = (EncodeFn)fn;
    cudaGetSymbolAddress((void**)&scratch, g_S);
    cudaFuncSetAttribute(fused_kernel<false>, cudaFuncAttributeMaxDynamicSharedMemorySize, SMEM_BYTES);
    cudaFuncSetAttribute(fused_kernel<true>, cudaFuncAttributeMaxDynamicSharedMemorySize, SMEM_BYTES);
  }
  TMaps tm;
  for (int i = 0; i < 6; i++) {
    const bool dn = i % 3 == 2;
    const cuuint32_t w = i < 3 ? 40 : 32;
    cuuint64_t gd[3] = {(cuuint64_t)(dn ? 64 : FF), (cuuint64_t)(dn ? FF : DM), 9};
    cuuint64_t gs[2] = {(cuuint64_t)(dn ? DM * 2 : FF * 2), 128};
    cuuint32_t bx[3] = {dn ? 64 : w, dn ? w : 96, i < 3 ? 2u : 3u};
    cuuint32_t es[3] = {1, 1, 1};
    enc(&tm.m[i], CU_TENSOR_MAP_DATA_TYPE_BFLOAT16, dn ? 3 : 2, d_in[11 + i % 3], gd, gs, bx, es, CU_TENSOR_MAP_INTERLEAVE_NONE,
        dn ? CU_TENSOR_MAP_SWIZZLE_128B : i < 3 ? CU_TENSOR_MAP_SWIZZLE_NONE : CU_TENSOR_MAP_SWIZZLE_64B,
        CU_TENSOR_MAP_L2_PROMOTION_NONE, CU_TENSOR_MAP_FLOAT_OOB_FILL_NONE);
  }
  for (int i = 6; i < 8; i++) {
    cuuint64_t gd[2] = {DM * 16, NCTA};
    cuuint64_t gs[1] = {DM * 32};
    cuuint32_t bx[2] = {16, i == 6 ? 160u : 128u};
    cuuint32_t es[2] = {1, 1};
    enc(&tm.m[i], CU_TENSOR_MAP_DATA_TYPE_FLOAT16, 2, scratch->X, gd, gs, bx, es, CU_TENSOR_MAP_INTERLEAVE_NONE, CU_TENSOR_MAP_SWIZZLE_32B,
        CU_TENSOR_MAP_L2_PROMOTION_NONE, CU_TENSOR_MAP_FLOAT_OOB_FILL_NONE);
  }
  Params p;
  p.x = (const unsigned char*)d_in[0];
  bool far = false;
  for (int i = 0; i < 7; i++) {
    p.far[i] = (const unsigned char*)d_in[1 + i];
    const long long d = (long long)((intptr_t)d_in[1 + i] - (intptr_t)d_in[0]);
    p.off[i] = (int)(d / 16);
    if ((long long)p.off[i] * 16 != d) far = true;
  }
  p.dskip = (const uint32_t*)d_in[8];
  p.w_r = (const uint32_t*)d_in[10];
  p.w_gate = (const unsigned char*)d_in[11];
  p.w_up = (const unsigned char*)d_in[12];
  for (int f = 0; f < 2; f++) {
    static const int kind[17] = {0, 0, 0, 0, 0, 0, 1, 1, 1, 1, 1, 1, 2, 2, 2, 2, 2};
    static const int idx[2][17] = {{3, 4, 5, 0, 1, 2, 0, 1, 2, 3, 4, 5, 6, 8, 0, 2, 4}, {3, 4, 5, 0, 1, 2, 0, 1, 2, 3, 4, 5, 0, -1, 3, -1, 6}};
    static const int blk[2][17] = {{-1, -1, -1, -1, -1, -1, 1, -1, 2, -1, 3, -1, 16, -1, -1, -1, -1}, {-1, -1, -1, -1, -1, -1, 1, -1, 2, -1, 3, -1, 16, -1, -1, -1, -1}};
    const int pitch = f ? 64 : 80;
    for (int u = 0; u < 17; u++) {
      const int s = idx[f][u];
      const uint32_t dst = kind[u] == 0 ? OFF_G + s * 96 * pitch : kind[u] == 2 ? down_box(s, f) : OFF_W + W_BYTES + (s >> 1) * W_BYTES + (s & 1) * 96 * pitch;
      const uint32_t mb = u == X_NE ? MB_GF - OFF_MISC : blk[f][u] >= 0 ? MB_KF - OFF_MISC + blk[f][u] * 8 : 0;
      p.sched[f][u] = s < 0 ? 3u : kind[u] | s << 2 | mb << 6 | dst << 14;
    }
  }
  p.out = (uint32_t*)d_out;
  p.zero = 0;
  p.ts = nullptr;
  p.s = scratch;
  if (far) { fused_kernel<true><<<NCTA, NT, SMEM_BYTES, cudaStreamPerThread>>>(p, tm); return; }
  fused_kernel<false><<<NCTA, NT, SMEM_BYTES, cudaStreamPerThread>>>(p, tm);
}
```

```cpp
#include <cuda_runtime.h>
#include <cuda.h>
#include <cuda_bf16.h>
#include <cuda_fp16.h>
#include <stdint.h>
#include <stddef.h>

namespace {

constexpr int NCTA = 128;
constexpr int NT = 640;
constexpr int DM = 576;
constexpr int FF = 4608;
constexpr int SPIN_MAX = 1 << 20;

struct Scratch {
  uint4 X[NCTA * DM * 2];
  uint4 KX[64 * 128];
  uint4 HS[1152 + 8];
  uint4 R[256];
  uint4 SC[256];
  uint32_t FLAG[NCTA * 8];
};
__device__ Scratch g_S;

#define CLKS(i)
#define TS(i)
#define TSX(i)
#define TS_DUMP()

constexpr int SB = 1024;
constexpr int BOX = 15360;
constexpr int OFF_G = SB;
constexpr int OFF_W = OFF_G + 3 * BOX;
constexpr int W_UP = 26624;
constexpr int W_KT = W_UP + 5120;
constexpr int W_L3 = W_KT + 4416;
constexpr int W_CW = W_L3 + 4096;
constexpr int W_MISC = W_CW + 640;
constexpr int W_BYTES = 40960;
constexpr int ALT = -W_UP;
static_assert(W_MISC + 32 <= W_BYTES && OFF_W % 1024 == 0 && W_UP % 256 == 0 && W_BYTES + ALT + 3 * 4096 <= W_UP, "wg block");
constexpr int YT_PITCH = 1184;
constexpr int OFF_YT = OFF_W + 4 * W_BYTES;
constexpr int OFF_WR = OFF_YT + 16 * YT_PITCH + 64;
constexpr int OFF_MISC = OFF_WR + 2304;
constexpr int SMEM_BYTES = OFF_MISC + 1024 - SB;
static_assert(OFF_YT % 16 == 0 && OFF_MISC % 16 == 0, "align");
static_assert(SMEM_BYTES <= 232448, "smem");
constexpr int MB_GU = OFF_MISC;
constexpr int MB_D = OFF_MISC + 8;
constexpr int MB_KF = OFF_MISC + 16;
constexpr int MB_GF = OFF_MISC + 48;
constexpr int MB_SC = OFF_MISC + 56;
constexpr int MB_UL = OFF_MISC + 64;
constexpr int MB_REL = OFF_MISC + 104;
constexpr int MB_GO = OFF_MISC + 112;
constexpr int MB_H = MB_KF + 128;
constexpr int MISC_EPOCH = OFF_MISC + 152;
constexpr int MISC_SW = OFF_MISC + 156;
constexpr int MISC_EM = OFF_MISC + 288;
constexpr int MISC_RK = OFF_MISC + 160;
constexpr int MISC_LN1 = OFF_MISC + 192;
constexpr int OFF_XS = OFF_W + W_BYTES + W_UP;
constexpr int OFF_RED = OFF_W + 2 * W_BYTES + W_UP;
constexpr int OFF_FIN = OFF_W + 3 * W_BYTES + W_UP;
constexpr int OFF_ACT = OFF_FIN + 4096;
constexpr int MISC_CNT = OFF_ACT + 1024;

__device__ __forceinline__ uint32_t smem_u32(const void* p) { return (uint32_t)__cvta_generic_to_shared(p); }
__device__ __forceinline__ uint32_t lds32(uint32_t a) { uint32_t v; asm volatile("ld.shared.b32 %0, [%1];" : "=r"(v) : "r"(a) : "memory"); return v; }
__device__ __forceinline__ uint32_t lds16(uint32_t a) { uint16_t v; asm volatile("ld.shared.u16 %0, [%1];" : "=h"(v) : "r"(a) : "memory"); return v; }
__device__ __forceinline__ uint2 lds64(uint32_t a) { uint2 v; asm volatile("ld.shared.v2.b32 {%0,%1}, [%2];" : "=r"(v.x), "=r"(v.y) : "r"(a) : "memory"); return v; }
__device__ __forceinline__ uint4 lds128(uint32_t a) { uint4 v; asm volatile("ld.shared.v4.b32 {%0,%1,%2,%3}, [%4];" : "=r"(v.x), "=r"(v.y), "=r"(v.z), "=r"(v.w) : "r"(a) : "memory"); return v; }
__device__ __forceinline__ void sts16(uint32_t a, uint32_t v) { asm volatile("st.shared.u16 [%0], %1;" :: "r"(a), "h"((uint16_t)v) : "memory"); }
__device__ __forceinline__ void sts32(uint32_t a, uint32_t v) { asm volatile("st.shared.b32 [%0], %1;" :: "r"(a), "r"(v) : "memory"); }
__device__ __forceinline__ void sts64(uint32_t a, uint32_t x, uint32_t y) { asm volatile("st.shared.v2.b32 [%0], {%1,%2};" :: "r"(a), "r"(x), "r"(y) : "memory"); }
__device__ __forceinline__ void sts128(uint32_t a, uint32_t x, uint32_t y, uint32_t z, uint32_t w) { asm volatile("st.shared.v4.b32 [%0], {%1,%2,%3,%4};" :: "r"(a), "r"(x), "r"(y), "r"(z), "r"(w) : "memory"); }
__device__ __forceinline__ void ldsm4(uint32_t a, uint32_t& r0, uint32_t& r1, uint32_t& r2, uint32_t& r3) {
  asm volatile("ldmatrix.sync.aligned.m8n8.x4.shared.b16 {%0,%1,%2,%3}, [%4];" : "=r"(r0), "=r"(r1), "=r"(r2), "=r"(r3) : "r"(a) : "memory");
}
__device__ __forceinline__ void ldsm2(uint32_t a, uint32_t& r0, uint32_t& r1) {
  asm volatile("ldmatrix.sync.aligned.m8n8.x2.shared.b16 {%0,%1}, [%2];" : "=r"(r0), "=r"(r1) : "r"(a) : "memory");
}
__device__ __forceinline__ void ldsm4t(uint32_t a, uint32_t& r0, uint32_t& r1, uint32_t& r2, uint32_t& r3) {
  asm volatile("ldmatrix.sync.aligned.m8n8.x4.trans.shared.b16 {%0,%1,%2,%3}, [%4];" : "=r"(r0), "=r"(r1), "=r"(r2), "=r"(r3) : "r"(a) : "memory");
}
__device__ __forceinline__ void stsm4t(uint32_t a, uint32_t r0, uint32_t r1, uint32_t r2, uint32_t r3) {
  asm volatile("stmatrix.sync.aligned.m8n8.x4.trans.shared.b16 [%0], {%1,%2,%3,%4};" :: "r"(a), "r"(r0), "r"(r1), "r"(r2), "r"(r3) : "memory");
}
__device__ __forceinline__ uint4 ldr128(const void* p) {
  unsigned long long lo, hi;
  asm volatile("{ .reg .b128 t; ld.relaxed.gpu.global.b128 t, [%2]; mov.b128 {%0, %1}, t; }" : "=l"(lo), "=l"(hi) : "l"(p) : "memory");
  return make_uint4((uint32_t)lo, (uint32_t)(lo >> 32), (uint32_t)hi, (uint32_t)(hi >> 32));
}
__device__ __forceinline__ void str128(void* p, uint32_t x, uint32_t y, uint32_t z, uint32_t w) {
  asm volatile("{ .reg .b128 t; .reg .b64 lo, hi; mov.b64 lo, {%1,%2}; mov.b64 hi, {%3,%4}; mov.b128 t, {lo, hi}; st.relaxed.gpu.global.b128 [%0], t; }"
               :: "l"(p), "r"(x), "r"(y), "r"(z), "r"(w) : "memory");
}
__device__ __forceinline__ void str64(void* p, uint32_t x, uint32_t y) {
  asm volatile("{ .reg .b64 t; mov.b64 t, {%1,%2}; st.relaxed.gpu.global.b64 [%0], t; }" :: "l"(p), "r"(x), "r"(y) : "memory");
}
__device__ __forceinline__ uint32_t ldr32(const void* p) { uint32_t v; asm volatile("ld.relaxed.gpu.global.b32 %0, [%1];" : "=r"(v) : "l"(p) : "memory"); return v; }
__device__ __forceinline__ void str32(void* p, uint32_t v) { asm volatile("st.relaxed.gpu.global.b32 [%0], %1;" :: "l"(p), "r"(v) : "memory"); }
__device__ __forceinline__ void str16(void* p, uint32_t v) { asm volatile("st.relaxed.gpu.global.u16 [%0], %1;" :: "l"(p), "h"((uint16_t)v) : "memory"); }
__device__ __forceinline__ void fence_gpu() { asm volatile("fence.acq_rel.gpu;" ::: "memory"); }
__device__ __forceinline__ void bar_sync(int id, int n) { asm volatile("bar.sync %0, %1;" :: "r"(id), "r"(n) : "memory"); }
__device__ __forceinline__ void bar_arrive(int id, int n) { asm volatile("bar.arrive %0, %1;" :: "r"(id), "r"(n) : "memory"); }

__device__ __forceinline__ float bf_lo(uint32_t w) { return __uint_as_float(w << 16); }
__device__ __forceinline__ float bf_hi(uint32_t w) { return __uint_as_float(w & 0xFFFF0000u); }
__device__ __forceinline__ uint32_t pack_bf(float lo, float hi) { uint32_t r; asm("cvt.rn.bf16x2.f32 %0, %1, %2;" : "=r"(r) : "f"(hi), "f"(lo)); return r; }
__device__ __forceinline__ uint32_t pack_h(float lo, float hi) { uint32_t r; asm("cvt.rn.f16x2.f32 %0, %1, %2;" : "=r"(r) : "f"(hi), "f"(lo)); return r; }
__device__ __forceinline__ uint32_t pack_hv(float lo, float hi) { uint32_t r; asm volatile("cvt.rn.f16x2.f32 %0, %1, %2;" : "=r"(r) : "f"(hi), "f"(lo) : "memory"); return r; }
__device__ __forceinline__ float bfr(float x) { return bf_lo(pack_bf(x, 0.f)); }
__device__ __forceinline__ uint32_t bf_sub2(uint32_t a, uint32_t b) { __nv_bfloat162 r = __hsub2(*(__nv_bfloat162*)&a, *(__nv_bfloat162*)&b); return *(uint32_t*)&r; }
__device__ __forceinline__ uint32_t bf_add2(uint32_t a, uint32_t b) { __nv_bfloat162 r = __hadd2(*(__nv_bfloat162*)&a, *(__nv_bfloat162*)&b); return *(uint32_t*)&r; }
__device__ __forceinline__ uint32_t bf_mul2(uint32_t a, uint32_t b) { __nv_bfloat162 r = __hmul2(*(__nv_bfloat162*)&a, *(__nv_bfloat162*)&b); return *(uint32_t*)&r; }
__device__ __forceinline__ float2 h2f(uint32_t w) { return __half22float2(*(__half2*)&w); }
__device__ __forceinline__ float ex2(float x) { float r; asm("ex2.approx.ftz.f32 %0, %1;" : "=f"(r) : "f"(x)); return r; }
__device__ __forceinline__ float warp_sum(float v) {
#pragma unroll
  for (int o = 16; o > 0; o >>= 1) v += __shfl_xor_sync(0xffffffffu, v, o);
  return v;
}
__device__ __forceinline__ void mma_f16_f32(float* d, uint32_t a0, uint32_t a1, uint32_t a2, uint32_t a3, uint32_t b0, uint32_t b1) {
  asm volatile("mma.sync.aligned.m16n8k16.row.col.f32.f16.f16.f32 {%0,%1,%2,%3}, {%4,%5,%6,%7}, {%8,%9}, {%0,%1,%2,%3};"
               : "+f"(d[0]), "+f"(d[1]), "+f"(d[2]), "+f"(d[3]) : "r"(a0), "r"(a1), "r"(a2), "r"(a3), "r"(b0), "r"(b1));
}
__device__ __forceinline__ void mma_f16_f16(uint32_t& d0, uint32_t& d1, uint32_t a0, uint32_t a1, uint32_t a2, uint32_t a3, uint32_t b0, uint32_t b1) {
  asm volatile("mma.sync.aligned.m16n8k16.row.col.f16.f16.f16.f16 {%0,%1}, {%2,%3,%4,%5}, {%6,%7}, {%0,%1};"
               : "+r"(d0), "+r"(d1) : "r"(a0), "r"(a1), "r"(a2), "r"(a3), "r"(b0), "r"(b1));
}
__device__ __forceinline__ void mma_bf16(float* d, uint32_t a0, uint32_t a1, uint32_t a2, uint32_t a3, uint32_t b0, uint32_t b1) {
  asm volatile("mma.sync.aligned.m16n8k16.row.col.f32.bf16.bf16.f32 {%0,%1,%2,%3}, {%4,%5,%6,%7}, {%8,%9}, {%0,%1,%2,%3};"
               : "+f"(d[0]), "+f"(d[1]), "+f"(d[2]), "+f"(d[3]) : "r"(a0), "r"(a1), "r"(a2), "r"(a3), "r"(b0), "r"(b1));
}
__device__ __forceinline__ void mma_bf16_k8(float* d, uint32_t a0, uint32_t a1, uint32_t b0) {
  asm volatile("mma.sync.aligned.m16n8k8.row.col.f32.bf16.bf16.f32 {%0,%1,%2,%3}, {%4,%5}, {%6}, {%0,%1,%2,%3};"
               : "+f"(d[0]), "+f"(d[1]), "+f"(d[2]), "+f"(d[3]) : "r"(a0), "r"(a1), "r"(b0));
}

__device__ __forceinline__ void wg_fence() { asm volatile("wgmma.fence.sync.aligned;" ::: "memory"); }
__device__ __forceinline__ void wg_commit() { asm volatile("wgmma.commit_group.sync.aligned;" ::: "memory"); }
template <int N> __device__ __forceinline__ void wg_wait() { asm volatile("wgmma.wait_group.sync.aligned %0;" :: "n"(N) : "memory"); }
template <int TB> __device__ __forceinline__ void wgmma32(float* d, const uint32_t* a, uint32_t dlo, uint32_t dhi) {
  asm volatile("{ .reg .b64 dd; mov.b64 dd, {%20, %21}; wgmma.mma_async.sync.aligned.m64n32k16.f32.f16.f16 "
               "{%0,%1,%2,%3,%4,%5,%6,%7,%8,%9,%10,%11,%12,%13,%14,%15}, {%16,%17,%18,%19}, dd, 1, 1, 1, %22; }"
               : "+f"(d[0]), "+f"(d[1]), "+f"(d[2]), "+f"(d[3]), "+f"(d[4]), "+f"(d[5]), "+f"(d[6]), "+f"(d[7]), "+f"(d[8]), "+f"(d[9]), "+f"(d[10]), "+f"(d[11]), "+f"(d[12]), "+f"(d[13]), "+f"(d[14]), "+f"(d[15])
               : "r"(a[0]), "r"(a[1]), "r"(a[2]), "r"(a[3]), "r"(dlo), "r"(dhi), "n"(TB));
}
template <int TB> __device__ __forceinline__ void wgmma96(float* d, const uint32_t* a, uint32_t dlo, uint32_t dhi) {
  asm volatile("{ .reg .b64 dd; mov.b64 dd, {%52, %53}; wgmma.mma_async.sync.aligned.m64n96k16.f32.f16.f16 "
               "{%0,%1,%2,%3,%4,%5,%6,%7,%8,%9,%10,%11,%12,%13,%14,%15,%16,%17,%18,%19,%20,%21,%22,%23,%24,%25,%26,%27,%28,%29,%30,%31,%32,%33,%34,%35,%36,%37,%38,%39,%40,%41,%42,%43,%44,%45,%46,%47}, {%48,%49,%50,%51}, dd, 1, 1, 1, %54; }"
               : "+f"(d[0]), "+f"(d[1]), "+f"(d[2]), "+f"(d[3]), "+f"(d[4]), "+f"(d[5]), "+f"(d[6]), "+f"(d[7]), "+f"(d[8]), "+f"(d[9]), "+f"(d[10]), "+f"(d[11]), "+f"(d[12]), "+f"(d[13]), "+f"(d[14]), "+f"(d[15]), "+f"(d[16]), "+f"(d[17]), "+f"(d[18]), "+f"(d[19]), "+f"(d[20]), "+f"(d[21]), "+f"(d[22]), "+f"(d[23]), "+f"(d[24]), "+f"(d[25]), "+f"(d[26]), "+f"(d[27]), "+f"(d[28]), "+f"(d[29]), "+f"(d[30]), "+f"(d[31]), "+f"(d[32]), "+f"(d[33]), "+f"(d[34]), "+f"(d[35]), "+f"(d[36]), "+f"(d[37]), "+f"(d[38]), "+f"(d[39]), "+f"(d[40]), "+f"(d[41]), "+f"(d[42]), "+f"(d[43]), "+f"(d[44]), "+f"(d[45]), "+f"(d[46]), "+f"(d[47])
               : "r"(a[0]), "r"(a[1]), "r"(a[2]), "r"(a[3]), "r"(dlo), "r"(dhi), "n"(TB));
}
template <int TB> __device__ __forceinline__ void wgmma96_init(float* d, const uint32_t* a, uint32_t dlo, uint32_t dhi) {
  asm volatile("{ .reg .b64 dd; mov.b64 dd, {%52, %53}; wgmma.mma_async.sync.aligned.m64n96k16.f32.f16.f16 "
               "{%0,%1,%2,%3,%4,%5,%6,%7,%8,%9,%10,%11,%12,%13,%14,%15,%16,%17,%18,%19,%20,%21,%22,%23,%24,%25,%26,%27,%28,%29,%30,%31,%32,%33,%34,%35,%36,%37,%38,%39,%40,%41,%42,%43,%44,%45,%46,%47}, {%48,%49,%50,%51}, dd, 0, 1, 1, %54; }"
               : "=f"(d[0]), "=f"(d[1]), "=f"(d[2]), "=f"(d[3]), "=f"(d[4]), "=f"(d[5]), "=f"(d[6]), "=f"(d[7]), "=f"(d[8]), "=f"(d[9]), "=f"(d[10]), "=f"(d[11]), "=f"(d[12]), "=f"(d[13]), "=f"(d[14]), "=f"(d[15]), "=f"(d[16]), "=f"(d[17]), "=f"(d[18]), "=f"(d[19]), "=f"(d[20]), "=f"(d[21]), "=f"(d[22]), "=f"(d[23]), "=f"(d[24]), "=f"(d[25]), "=f"(d[26]), "=f"(d[27]), "=f"(d[28]), "=f"(d[29]), "=f"(d[30]), "=f"(d[31]), "=f"(d[32]), "=f"(d[33]), "=f"(d[34]), "=f"(d[35]), "=f"(d[36]), "=f"(d[37]), "=f"(d[38]), "=f"(d[39]), "=f"(d[40]), "=f"(d[41]), "=f"(d[42]), "=f"(d[43]), "=f"(d[44]), "=f"(d[45]), "=f"(d[46]), "=f"(d[47])
               : "r"(a[0]), "r"(a[1]), "r"(a[2]), "r"(a[3]), "r"(dlo), "r"(dhi), "n"(TB));
}
template <int TB> __device__ __forceinline__ void wgmma32_init(float* d, const uint32_t* a, uint32_t dlo, uint32_t dhi) {
  asm volatile("{ .reg .b64 dd; mov.b64 dd, {%20, %21}; wgmma.mma_async.sync.aligned.m64n32k16.f32.f16.f16 "
               "{%0,%1,%2,%3,%4,%5,%6,%7,%8,%9,%10,%11,%12,%13,%14,%15}, {%16,%17,%18,%19}, dd, 0, 1, 1, %22; }"
               : "=f"(d[0]), "=f"(d[1]), "=f"(d[2]), "=f"(d[3]), "=f"(d[4]), "=f"(d[5]), "=f"(d[6]), "=f"(d[7]), "=f"(d[8]), "=f"(d[9]), "=f"(d[10]), "=f"(d[11]), "=f"(d[12]), "=f"(d[13]), "=f"(d[14]), "=f"(d[15])
               : "r"(a[0]), "r"(a[1]), "r"(a[2]), "r"(a[3]), "r"(dlo), "r"(dhi), "n"(TB));
}
__device__ __forceinline__ void wgmma64h(uint32_t* d, uint32_t a0, uint32_t a1, uint32_t a2, uint32_t a3, uint32_t dlo, uint32_t dhi) {
  asm volatile("{ .reg .b64 dd; mov.b64 dd, {%20, %21}; wgmma.mma_async.sync.aligned.m64n64k16.f16.f16.f16 "
               "{%0,%1,%2,%3,%4,%5,%6,%7,%8,%9,%10,%11,%12,%13,%14,%15}, {%16,%17,%18,%19}, dd, 1, 1, 1, 0; }"
               : "+r"(d[0]), "+r"(d[1]), "+r"(d[2]), "+r"(d[3]), "+r"(d[4]), "+r"(d[5]), "+r"(d[6]), "+r"(d[7]), "+r"(d[8]), "+r"(d[9]), "+r"(d[10]), "+r"(d[11]), "+r"(d[12]), "+r"(d[13]), "+r"(d[14]), "+r"(d[15])
               : "r"(a0), "r"(a1), "r"(a2), "r"(a3), "r"(dlo), "r"(dhi));
}
__device__ __forceinline__ void wgmma64h_init(uint32_t* d, uint32_t a0, uint32_t a1, uint32_t a2, uint32_t a3, uint32_t dlo, uint32_t dhi) {
  asm volatile("{ .reg .b64 dd; mov.b64 dd, {%20, %21}; wgmma.mma_async.sync.aligned.m64n64k16.f16.f16.f16 "
               "{%0,%1,%2,%3,%4,%5,%6,%7,%8,%9,%10,%11,%12,%13,%14,%15}, {%16,%17,%18,%19}, dd, 0, 1, 1, 0; }"
               : "=r"(d[0]), "=r"(d[1]), "=r"(d[2]), "=r"(d[3]), "=r"(d[4]), "=r"(d[5]), "=r"(d[6]), "=r"(d[7]), "=r"(d[8]), "=r"(d[9]), "=r"(d[10]), "=r"(d[11]), "=r"(d[12]), "=r"(d[13]), "=r"(d[14]), "=r"(d[15])
               : "r"(a0), "r"(a1), "r"(a2), "r"(a3), "r"(dlo), "r"(dhi));
}
__device__ __forceinline__ void wgmma40_ss(float* d, uint32_t alo, uint32_t blo, uint32_t hi) {
  asm volatile("{ .reg .b64 da, db; mov.b64 da, {%20, %22}; mov.b64 db, {%21, %22}; "
               "wgmma.mma_async.sync.aligned.m64n40k16.f32.f16.f16 {%0,%1,%2,%3,%4,%5,%6,%7,%8,%9,%10,%11,%12,%13,%14,%15,%16,%17,%18,%19}, da, db, 1, 1, 1, 1, 1; }"
               : "+f"(d[0]), "+f"(d[1]), "+f"(d[2]), "+f"(d[3]), "+f"(d[4]), "+f"(d[5]), "+f"(d[6]), "+f"(d[7]), "+f"(d[8]), "+f"(d[9]), "+f"(d[10]), "+f"(d[11]), "+f"(d[12]), "+f"(d[13]), "+f"(d[14]), "+f"(d[15]), "+f"(d[16]), "+f"(d[17]), "+f"(d[18]), "+f"(d[19])
               : "r"(alo), "r"(blo), "r"(hi));
}
__device__ __forceinline__ void wgmma40_ss_init(float* d, uint32_t alo, uint32_t blo, uint32_t hi) {
  asm volatile("{ .reg .b64 da, db; mov.b64 da, {%20, %22}; mov.b64 db, {%21, %22}; "
               "wgmma.mma_async.sync.aligned.m64n40k16.f32.f16.f16 {%0,%1,%2,%3,%4,%5,%6,%7,%8,%9,%10,%11,%12,%13,%14,%15,%16,%17,%18,%19}, da, db, 0, 1, 1, 1, 1; }"
               : "=f"(d[0]), "=f"(d[1]), "=f"(d[2]), "=f"(d[3]), "=f"(d[4]), "=f"(d[5]), "=f"(d[6]), "=f"(d[7]), "=f"(d[8]), "=f"(d[9]), "=f"(d[10]), "=f"(d[11]), "=f"(d[12]), "=f"(d[13]), "=f"(d[14]), "=f"(d[15]), "=f"(d[16]), "=f"(d[17]), "=f"(d[18]), "=f"(d[19])
               : "r"(alo), "r"(blo), "r"(hi));
}
__device__ __forceinline__ float vzero() { float v; asm volatile("mov.b32 %0, 0;" : "=f"(v)); return v; }
__device__ __forceinline__ void tma_box(uint32_t dst, const CUtensorMap* tm, uint32_t mb, int x, int y) {
  asm volatile("cp.async.bulk.tensor.2d.shared::cluster.global.mbarrier::complete_tx::bytes [%0], [%1, {%3, %4}], [%2];"
               :: "r"(dst), "l"(tm), "r"(mb), "r"(x), "r"(y) : "memory");
}
__device__ __forceinline__ void l2_prefetch(const void* src, uint32_t bytes) {
  asm volatile("cp.async.bulk.prefetch.L2.global [%0], %1;" :: "l"(src), "r"(bytes) : "memory");
}
__device__ __forceinline__ uint32_t uni(uint32_t v) {
  uint32_t r; asm volatile("shfl.sync.idx.b32 %0, %1, 0, 0x1f, 0xffffffff;" : "=r"(r) : "r"(v)); return r;
}
__device__ __forceinline__ int fresh_tid() { int v; asm volatile("mov.u32 %0, %tid.x;" : "=r"(v)); return v; }

struct Params {
  const unsigned char* x;
  Scratch* s;
  int off[7];
  uint32_t zero;
  uint32_t* out;
  const uint32_t* dskip;
  const uint32_t* w_r;
  long long* ts;
  const unsigned char* far[7];
  uint32_t sched[2][17];
};
__device__ __forceinline__ uint32_t ldnc32(const void* p) { uint32_t v; asm volatile("ld.global.nc.b32 %0, [%1];" : "=r"(v) : "l"(p)); return v; }
__device__ __forceinline__ uint32_t ldnc16(const void* p) { uint16_t v; asm volatile("ld.global.nc.u16 %0, [%1];" : "=h"(v) : "l"(p)); return v; }
__device__ __forceinline__ uint4 ldnc128(const void* p) { uint4 v; asm volatile("ld.global.nc.v4.b32 {%0,%1,%2,%3}, [%4];" : "=r"(v.x), "=r"(v.y), "=r"(v.z), "=r"(v.w) : "l"(p)); return v; }
__device__ __forceinline__ void mbar_wait(uint32_t mb, uint32_t ph = 0) {
#pragma unroll 1
  for (int it = 0; it < SPIN_MAX; it++) {
    uint32_t ok;
    asm volatile("{ .reg .pred q; mbarrier.try_wait.parity.shared::cta.b64 q, [%1], %2; selp.u32 %0, 1, 0, q; }" : "=r"(ok) : "r"(mb), "r"(ph) : "memory");
    if (ok) break;
  }
}
__device__ __forceinline__ uint32_t mbar_test(uint32_t mb) {
  uint32_t ok;
  asm volatile("{ .reg .pred q; mbarrier.test_wait.parity.shared::cta.b64 q, [%1], 0; selp.u32 %0, 1, 0, q; }" : "=r"(ok) : "r"(mb) : "memory");
  return ok;
}
__device__ __forceinline__ void mbar_arrive(uint32_t mb) { asm volatile("mbarrier.arrive.shared::cta.b64 _, [%0];" :: "r"(mb) : "memory"); }
__device__ __forceinline__ uint32_t ldg16(const void* p) { uint16_t v; asm volatile("ld.global.u16 %0, [%1];" : "=h"(v) : "l"(p) : "memory"); return v; }
__device__ __forceinline__ uint32_t ldr16(const void* p) { uint16_t v; asm volatile("ld.relaxed.gpu.global.u16 %0, [%1];" : "=h"(v) : "l"(p) : "memory"); return v; }
__device__ __forceinline__ void fence_async() { asm volatile("fence.proxy.async.shared::cta;" ::: "memory"); }
#define SPIN_WHILE(cond, body) _Pragma("unroll 1") for (int _it = 0; _it < SPIN_MAX && __any_sync(0xffffffffu, (cond)); _it++) { body; }

struct LnC { uint32_t m2, rh2, rl2; };
__device__ __forceinline__ float diag_sum(float d0, float d1, int t) {
  float q = __shfl_sync(0xffffffffu, d0, 9 * t) + __shfl_sync(0xffffffffu, d1, 9 * t + 4);
  q += __shfl_xor_sync(0xffffffffu, q, 1);
  return q + __shfl_xor_sync(0xffffffffu, q, 2);
}
__device__ __forceinline__ LnC ln_consts(float s, float q, float& r) {
  const float mean = s * (1.f / DM);
  const float var = fmaxf(fmaf(-mean, mean, q * (1.f / DM)), 0.f);
  float sd;
  asm("sqrt.approx.ftz.f32 %0, %1;" : "=f"(sd) : "f"(bfr(bfr(var) + 1e-5f)));
  asm("rcp.approx.ftz.f32 %0, %1;" : "=f"(r) : "f"(bfr(sd)));
  LnC c;
  c.m2 = pack_bf(mean, mean);
  c.rh2 = pack_bf(r, r);
  const float rl = r - bf_lo(c.rh2);
  c.rl2 = pack_bf(rl, rl);
  return c;
}
__device__ __forceinline__ float quad_sum(float s) { s += __shfl_xor_sync(0xffffffffu, s, 1); return s + __shfl_xor_sync(0xffffffffu, s, 2); }
__device__ __forceinline__ uint32_t bf_fma2(uint32_t a, uint32_t b, uint32_t c) {
  __nv_bfloat162 r = __hfma2(*(const __nv_bfloat162*)&a, *(const __nv_bfloat162*)&b, *(const __nv_bfloat162*)&c);
  return *(uint32_t*)&r;
}
__device__ __forceinline__ uint32_t ln_apply(uint32_t w, uint32_t m2, uint32_t rh2, uint32_t rl2) {
  const uint32_t d = bf_sub2(w, m2);
  return bf_fma2(d, rh2, bf_mul2(d, rl2));
}

__device__ __forceinline__ float2 cis(float mag_log2, float rev) {
  const float m = ex2(mag_log2), ang = rev * 6.283185307179586f;
  return make_float2(m * __cosf(ang), m * __sinf(ang));
}
__device__ __forceinline__ float2 csq(float2 a) { return make_float2(fmaf(a.x, a.x, -a.y * a.y), (a.x + a.x) * a.y); }
__device__ __forceinline__ float2 cmul(float2 a, float2 b) { return make_float2(fmaf(a.x, b.x, -a.y * b.y), fmaf(a.x, b.y, a.y * b.x)); }
__device__ __forceinline__ void pmul(uint32_t xr, uint32_t xi, uint32_t w, uint32_t& yr, uint32_t& yi) {
  const __half2 XR = *(__half2*)&xr, XI = *(__half2*)&xi, W = *(__half2*)&w;
  const __half2 a = __hfma2(__hneg2(XI), __high2half2(W), __hmul2(XR, __low2half2(W)));
  const __half2 b = __hfma2(XI, __low2half2(W), __hmul2(XR, __high2half2(W)));
  yr = *(const uint32_t*)&a; yi = *(const uint32_t*)&b;
}
__device__ __forceinline__ uint32_t pk(float2 a) { return pack_h(a.x, a.y); }

struct KgState { float2 c0, z8; float kl; uint32_t w64, w128, w192; };
__device__ __forceinline__ void kgen_tables_n(const uint32_t (&raw)[7], uint32_t scr, int wt, KgState& k) {
  const uint32_t dst = scr + 16384 + wt * 16;
  const float dt = bfr(ex2(bf_lo(raw[6]) * 1.4426950408889634f));
  const float th = dt * bf_lo(raw[1]);
  const float br = dt * bf_lo(raw[2]), bi = dt * bf_lo(raw[3]);
  const float Cr = bf_lo(raw[4]), Ci = bf_lo(raw[5]);
  k.c0 = make_float2(fmaf(Cr, br, -Ci * bi), fmaf(Cr, bi, Ci * br));
  const uint32_t mx = __reduce_max_sync(0xffffffffu, __float_as_uint(fmaxf(fabsf(k.c0.x), fabsf(k.c0.y))));
  const float a2 = dt * bf_lo(raw[0]) * 1.4426950408889634f;
  const float rh = th * 0.15915494309189535f;
  const float rl = fmaf(th, (float)(0.15915494309189535 - (double)0.15915494309189535f), fmaf(th, 0.15915494309189535f, -rh));
  const float rf = rh - rintf(rh);
  const float2 z1 = cis(a2, rf + rl);
  const float p64 = rf * 64.f;
  const float2 z64 = cis(a2 * 64.f, fmaf(64.f, rl, p64 - rintf(p64)));
  const float2 z2 = csq(z1), z128 = csq(z64), z3 = cmul(z2, z1), z4 = csq(z2), z256 = csq(z128), z6 = csq(z3), z512 = csq(z256);
  k.z8 = csq(z4);
  k.w64 = pk(z64); k.w128 = pk(z128); k.w192 = pk(cmul(z128, z64));
  sts128(dst, 0x00003C00u, pk(z2), pk(z4), pk(z6));
  const float2 z1024 = csq(z512), z768 = cmul(z512, z256);
  sts128(dst + 2048, pk(z1), pk(z3), pk(cmul(z4, z1)), pk(cmul(z4, z3)));
  const float2 z2048 = csq(z1024);
  k.kl = fmaf(k.c0.x, z2048.x, -k.c0.y * z2048.y);
  sts128(dst + 4096, pk(z256), pk(cmul(z256, z2)), pk(cmul(z256, z4)), pk(cmul(z256, z6)));
  sts128(dst + 6144, pk(z512), pk(cmul(z512, z4)), pk(z768), pk(cmul(z768, z4)));
  sts128(dst + 8192, pk(z1024), pk(cmul(z1024, z256)), pk(cmul(z1024, z512)), pk(cmul(z1024, z768)));
  sts32(scr + W_MISC + (wt >> 5) * 4, mx);
}
__device__ __forceinline__ int kgen_tables_m(uint32_t scr, int wt, const KgState& k) {
  const uint32_t dst = scr + wt * 16;
  const uint4 e4 = lds128(scr + W_MISC);
  const float2 z16 = csq(k.z8), z32 = csq(z16);
  const int em = max(min((int)(max(max(e4.x, e4.y), max(e4.z, e4.w)) >> 23), 238), 16);
  const float sc = __uint_as_float((uint32_t)(127 + 4 + 127 - em) << 23);
  sts32(scr + W_MISC + 16 + (wt >> 5) * 4, __reduce_add_sync(0xffffffffu, __float2int_rn(k.kl * sc * 262144.f)));
  const float2 c0 = make_float2(k.c0.x * sc, k.c0.y * sc);
  const float2 c1 = cmul(c0, k.z8), c2 = cmul(c0, z16), c4 = cmul(c0, z32), c3 = cmul(c1, z16), c5 = cmul(c1, z32), c6 = cmul(c2, z32), c7 = cmul(c3, z32);
  uint32_t pr[4], pi[4], yr[4], yi[4];
  pr[0] = pack_h(c0.x, c1.x); pi[0] = pack_h(c0.y, c1.y);
  pr[1] = pack_h(c2.x, c3.x); pi[1] = pack_h(c2.y, c3.y);
  pr[2] = pack_h(c4.x, c5.x); pi[2] = pack_h(c4.y, c5.y);
  pr[3] = pack_h(c6.x, c7.x); pi[3] = pack_h(c6.y, c7.y);
  sts128(dst, pr[0], pr[1], pr[2], pr[3]); sts128(dst + 2048, pi[0], pi[1], pi[2], pi[3]);
#pragma unroll
  for (int q = 1; q < 4; q++) {
    const uint32_t w = q == 1 ? k.w64 : q == 2 ? k.w128 : k.w192;
#pragma unroll
    for (int i = 0; i < 4; i++) pmul(pr[i], pi[i], w, yr[i], yi[i]);
    sts128(dst + q * 4096, yr[0], yr[1], yr[2], yr[3]); sts128(dst + q * 4096 + 2048, yi[0], yi[1], yi[2], yi[3]);
  }
  return em;
}
__device__ __forceinline__ void kgen_build(uint32_t tb, uint32_t sc, int wg, int wt, uint32_t k0, uint32_t k1, uint32_t k2) {
  const uint32_t kt = tb + W_KT;
  const int ix = ((wt >> 2) + (wt & 3) * 32 - 1) & 127;
  const uint32_t a3 = tb + W_CW + 32 + ((ix & 1) ? 0 : 304) + (ix >> 1) * 4;
  const uint32_t v3 = wt ? k2 : k2 >> 16;
  sts32(sc + 4 + wt * 4, __byte_perm(k0, k1, 0x5432));
  sts16(sc + 544 + (wt & ~3) + (wt & 1) * 2 + (wt & 2) * 64, k1 >> 16);
  sts16(a3, v3); sts16(a3 + 6, v3);
  if ((unsigned)(wt - 32) < 18u) sts128(kt + (wt < 36 ? -512 : 64 + 4128 - 576) + wt * 16, 0, 0, 0, 0);
  if (wt == 127) sts32(sc, k0 & 0xFFFF0000u);
  if (wt == 0) { sts32(sc + 516, k1); sts16(sc + 800, k2); }
  bar_sync(1 + wg, 128);
  const uint32_t cw = tb + W_CW + 32 + (wt >> 6) * 48 + wt * 4;
  const uint32_t pv = lds32(sc + wt * 4), nx = lds32(sc + 8 + wt * 4), c2 = lds16(sc + 544 + wt * 2), n2 = lds16(sc + 546 + wt * 2);
  sts128(tb + W_L3 + 1024 + (wt >> 6) * 1024 + wt * 16, lds32(cw), lds32(cw - 8), lds32(cw - 16), lds32(cw - 24));
  const bool odd = wt & 1;
  sts64(kt + 64 + wt * 8, __byte_perm(k0, pv, 0x5410), __byte_perm(k0, 0, 0x1032));
  sts64(kt + 64 + 1024 + wt * 8, __byte_perm(k1, pv, (odd || wt == 0) ? 0x7610 : 0x1010), __byte_perm(k1, nx, odd ? 0x1076 : 0x1010));
  const uint32_t cc = c2 * 0x10001u, nc = __byte_perm(n2, c2, 0x5410), nn = n2 * 0x10001u;
  sts128(kt + 64 + 2048 + wt * 16, cc, cc, odd ? nc : cc, odd ? nn : nc);
  if (wt == 127) { sts128(kt + 64 + 4096, nn, nn, nn, nn); sts128(kt + 64 + 4112, nn, nn << 16, 0, 0); }
}

__device__ __forceinline__ void load_a(uint32_t (&a)[4], uint32_t kp, int j) {
  a[0] = lds32(kp + 64 * j); a[1] = lds32(kp + 64 * j + 512); a[2] = lds32(kp + 64 * j - 32); a[3] = lds32(kp + 64 * j + 480);
}
__device__ __forceinline__ uint32_t band(int d, int lo, int hi) {
  return ((unsigned)(d - lo) <= (unsigned)(hi - lo) ? 1u : 0u) | ((unsigned)(d - 1 - lo) <= (unsigned)(hi - lo) ? 0x10000u : 0u);
}
__device__ __forceinline__ uint32_t hadd2u(uint32_t a, uint32_t b) { __half2 r = __hadd2(*(__half2*)&a, *(__half2*)&b); return *(uint32_t*)&r; }

__device__ __forceinline__ void zero_pads(uint32_t tb, int wt) {
  sts128(tb + W_L3 + (wt >> 6) * 1024 + wt * 16, 0, 0, 0, 0);
  if ((wt & 63) < 3) sts128(tb + W_CW + (wt >> 6) * 304 + (wt & 63) * 16, 0, 0, 0, 0);
}
__device__ __forceinline__ uint32_t tr_base(int lane) {
  return OFF_YT + (2 * (lane >> 3) + (lane & 1)) * YT_PITCH + ((lane >> 1) & 1) * (8 * YT_PITCH + 64) + ((lane >> 2) & 1) * 16;
}

__device__ __forceinline__ uint32_t sc_addr(int tp) { return OFF_YT + (tp < 16 ? tp * YT_PITCH + (tp >> 3) * 64 + 1152 : 8 * YT_PITCH - 512 + tp * 32); }
#define X_NE 3
#define X_SCT 10000
#define X_DELTA 600
#define X_DSTEP 700
#define X_PF0 2750
#define X_PFD 630
#define X_TD 520
#define X_ORD 0
#define X_WS 6
#define X_OR 8
#define X_ABS 5300
#define X_XD 0
#define X_RD 850
#define X_HD 650
#define X_PD 1150
#define X_HU 14
#define X_GF 0
#define X_PROMO 2
#define X_YD2 200
#define X_GO 2
#define X_GW 2
#define X_LAG 1000
#define X_YD 1200
struct TMaps { CUtensorMap m[8]; };
__device__ __forceinline__ uint32_t h2bf(uint32_t w) { const float2 f = h2f(w); return pack_bf(f.x, f.y); }
__device__ __forceinline__ uint32_t keep(uint32_t v) { asm volatile("" : "+r"(v)); return v; }
__device__ __forceinline__ uint2 ldr64(const void* p) { uint2 v; asm volatile("{ .reg .b64 t; ld.relaxed.gpu.global.b64 t, [%2]; mov.b64 {%0, %1}, t; }" : "=r"(v.x), "=r"(v.y) : "l"(p) : "memory"); return v; }
__host__ __device__ __forceinline__ uint32_t down_box(int s, bool five) {
  return five ? OFF_W + W_BYTES + 12288 + (s / 3) * (W_BYTES - 12288) + s * 4096 : s < 6 ? OFF_W + W_BYTES + BOX + (s >> 1) * (W_BYTES - 10240) + s * 5120 : OFF_W + (s - 6) * 5120;
}
__device__ __forceinline__ void load_tile(const CUtensorMap* tmx, int i, int c) {
  asm volatile("mbarrier.arrive.expect_tx.shared::cta.b64 _, [%0], 5120;" :: "r"(MB_UL + i * 8) : "memory");
  tma_box(OFF_W + (i < 4 ? i * W_BYTES : ALT) + W_UP, tmx, MB_UL + i * 8, (i < 4 ? i * 128 + c : 512 + (c >> 1)) * 16, -32);
}
__device__ __forceinline__ void check_tile(uint32_t tb, const CUtensorMap* tmx, int i, int c, int wg, int wt) {
#pragma unroll 1
  for (int it = 0; it < SPIN_MAX; it++) {
    uint32_t r0, r1, r2, r3, ok;
    mbar_wait(MB_UL + i * 8, it & 1);
    if (it == 0) TS(29);
    if (it == 1) TS(13);
    ldsm4(tb + W_UP + 1024 + wt * 32 + (wt & 4) * 4, r0, r1, r2, r3);
    asm volatile("{ .reg .pred q; setp.ne.u32 q, %1, 0; barrier.red.and.pred q, %2, 128, q; selp.u32 %0, 1, 0, q; }" : "=r"(ok) : "r"((r0 & r1 & r2 & r3 & 1u) | (wt & 3)), "r"(1 + wg) : "memory");
    if (ok) break;
    if (wt == 0) load_tile(tmx, i, c);
  }
}
template <bool FAR> __device__ __forceinline__ void load_params(const Params& p, uint32_t ch, int wt, uint32_t dst, bool on) {
  const int o01 = (wt & 16) ? p.off[1] : p.off[0], o23 = (wt & 16) ? p.off[3] : p.off[2], o45 = (wt & 16) ? p.off[5] : p.off[4];
  const int o = (wt & 64) ? ((wt & 32) ? p.off[6] : o45) : ((wt & 32) ? o23 : o01);
  const unsigned char* b = FAR ? p.far[min(wt >> 4, 6)] : p.x + (long long)o * 16;
  asm volatile("{ .reg .pred q; setp.ne.u32 q, %2, 0; @q cp.async.cg.shared.global [%0], [%1], 16; }"
               :: "r"(dst + wt * 16), "l"(b + (wt < 96 ? ch * 256 + (wt & 15) * 16 : (ch >> 3) * 16)), "r"((uint32_t)(on && wt < 97)) : "memory");
}

struct ConvC { uint32_t ca, cb, bands; };
__device__ __forceinline__ ConvC conv_consts(int w, int lane) {
  const int h = w & 1, P = w >> 1, d0 = 8 * h + (lane >> 2) - 2 * (lane & 3);
  ConvC k;
  k.ca = keep((W_KT + (16 + 256 * P + d0) * 4) | ((W_UP + (32 + 64 * P + lane) * 32 + ((h ^ (lane >> 2)) & 1) * 16) << 16));
  k.cb = keep(lane < 8 ? 0xFFFEFFFEu : ~0u);
  k.bands = keep(band(d0, 12, 20) + 2 * band(d0 + 8, 12, 20) + 4 * band(d0 + 16, 12, 20) + 8 * band(d0 + 24, 12, 20)
                 + 16 * band(d0 - 8, 5, 11) + 32 * band(d0, 5, 11) + 64 * band(d0 + 8, 5, 11) + 128 * band(d0 + 16, 5, 11));
  return k;
}
__device__ __forceinline__ void conv_item(uint32_t tb, const ConvC& cv, uint32_t zero, const CUtensorMap* tmx, int ch, int warp, int lane, bool hold, bool more) {
  const bool go = more && warp == 0 && lane == 0;
  const uint32_t kp = tb + (cv.ca & 0xFFFFu);
  const uint32_t dlo = ((tb + W_UP) >> 4) + 64 + (1u << 16), dhi = 16u | (3u << 30);
  const bool P = warp & 2;
  float a32[16], a96[48];
  uint32_t A[40][4];
#define STEP(J) { wgmma96<0>(a96, A[J], dlo + 64 - 2 * (J), dhi); if ((J) == 0) wgmma32_init<0>(a32, A[J], dlo, dhi); else if ((J) < 8) wgmma32<0>(a32, A[J], (dlo ^ zero) - 2 * (J), dhi); }
#define LD(J) load_a(A[J], kp, J);
#define FIRST(J) wg_fence(); STEP(J) wg_commit(); wg_wait<1>(); wg_fence();
  {
    uint32_t win[16], x9[4], x7[4], e[4], f[4];
    const uint32_t bz = keep(cv.bands);
#define BAND(i) keep((bz & (0x10001u << (i))) * (0x3C00u >> (i)))
    e[0] = lds32(kp + (P ? 3232 : 4096)); e[2] = lds32(kp + (P ? 3200 : 4064)); e[1] = keep(bz & 0x100u); e[3] = keep(bz & 0x200u);
    f[3] = lds32(kp + (P ? 3200 : 4128)); f[0] = keep(bz & 0x4000u); f[1] = keep(bz & 0x8000u); f[2] = keep(bz & 0x300u);
    const uint32_t q[12] = {BAND(0), BAND(5), keep(bz & 0x400u), BAND(4), BAND(2), BAND(7), BAND(1), BAND(6), keep(bz & 0x800u), keep(bz & 0x1000u), BAND(3), keep(bz & 0x2000u)};
#undef BAND
    if (ch < 512) check_tile(tb, tmx - 1, warp >> 2, ch & 127, warp >> 2, (warp & 3) * 32 + lane);
    if (X_GO && hold) mbar_wait(MB_GO);
    TS(3);
    wg_fence();
    wgmma64h_init(win, q[0], q[1], q[2], q[3], dlo, dhi);
    wgmma64h(win, q[4], q[5], q[6], q[7], dlo - 2, dhi);
    wgmma64h(win, q[8], q[9], q[10], q[11], dlo - 4, dhi);
    wg_commit();
    wgmma96_init<0>(a96, e, dlo - 64, dhi);
    wgmma96<0>(a96, f, dlo - 50, dhi);
    wg_commit();
    wg_wait<1>();
#pragma unroll
    for (int i = 0; i < 4; i++) {
      const int tl = 2 * ((i & 1) + ((i & 2) ? 0 : 4));
      x9[i] = P ? win[tl + 4] : win[tl]; x7[i] = P ? win[tl + 5] : win[tl + 1];
    }
    const uint32_t l3lo = ((tb + W_L3) >> 4) + (32u << 16);
    wg_fence();
    wgmma96<0>(a96, x9, l3lo, 8);
    wgmma96<0>(a96, x7, l3lo + 128, 8);
    wg_commit();
  }
  LD(32) LD(33) LD(34) LD(35)
  FIRST(32) STEP(33) STEP(34) STEP(35) wg_commit();
  LD(36) LD(37) LD(38)
  FIRST(36) STEP(37) STEP(38) wg_commit();
  LD(39) LD(0)
  TS(17);
  if (X_GO == 1 && go) mbar_arrive(MB_GO);
  FIRST(39) STEP(0) wg_commit();
  LD(1) LD(2) LD(3)
  FIRST(1) STEP(2) STEP(3) wg_commit();
  LD(4) LD(5)
  if (X_GO == 2 && go) mbar_arrive(MB_GO);
  FIRST(4) STEP(5) wg_commit();
  LD(6) LD(7)
  wg_fence(); STEP(6) STEP(7) wg_commit();
#undef STEP
#undef LD
#undef FIRST
  TS(18);
  if (X_GO == 3 && go) mbar_arrive(MB_GO);
  const uint32_t xc = tb + W_KT + (warp & 3) * 1024 + lane * 16;
  wg_wait<0>();
  uint32_t E[16], o[8];
#define ACC(i) ((i) < 16 ? a32[i] : a96[(i) - 16])
  E[0] = pack_h(a32[0], a32[1]);
#pragma unroll
  for (int i = 1; i < 16; i++) E[i] = pack_h(ACC(4 * i) + ACC(4 * i - 2), ACC(4 * i + 1) + ACC(4 * i - 1));
#undef ACC
#pragma unroll
  for (int j = 0; j < 8; j++) o[j] = P ? (j < 2 ? 0u : E[j - 2]) : E[8 + j];
  sts128(xc, o[0], o[1], o[2], o[3]); sts128(xc + 512, o[4], o[5], o[6], o[7]);
#pragma unroll
  for (int j = 0; j < 8; j++) o[j] = P ? E[6 + j] : E[j];
  TS(25);
  if (more) {
    sts128(xc + 4096, o[0], o[1], o[2], o[3]); sts128(xc + 4608, o[4], o[5], o[6], o[7]);
    bar_arrive(12, 192);
    return;
  }
  bar_sync(1 + (warp >> 2), 128);
  const uint4 vv[2] = {lds128(xc + (P ? -2048 : 2048)), lds128(xc + (P ? -1536 : 2560))};
#pragma unroll
  for (int q = 0; q < 2; q++) {
    const uint4 v = vv[q];
    stsm4t(tb + (cv.ca >> 16) + q * 1024, hadd2u(o[4 * q], v.x) & cv.cb, hadd2u(o[4 * q + 1], v.y) & cv.cb, hadd2u(o[4 * q + 2], v.z) & cv.cb, hadd2u(o[4 * q + 3], v.w) & cv.cb);
  }
  fence_async();
  bar_sync(1 + (warp >> 2), 128);
  if (warp == 0 && lane == 0) mbar_arrive(MB_REL);
  if ((warp & 3) == 3 && lane == 0) {
    asm volatile("cp.async.bulk.tensor.2d.global.shared::cta.bulk_group [%0, {%2, %3}], [%1];" :: "l"(tmx), "r"(tb + W_UP + 1024), "r"(ch * 16), "r"(0) : "memory");
    asm volatile("cp.async.bulk.commit_group;" ::: "memory");
  }
}

template <bool FAR> __global__ void __launch_bounds__(NT, 1)
fused_kernel(const __grid_constant__ Params p, const __grid_constant__ TMaps tm) {
  extern __shared__ __align__(1024) unsigned char smem[];
  const int c = blockIdx.x;
  const bool five = (c & 1) == 0;
  const uint32_t pitch = five ? 64 : 80;
  const uint32_t ones = 0x3F803F80u;
  const int tid = threadIdx.x, lane = tid & 31;
  {
    const int w4 = tid >> 7, k5 = !five && w4 == 3;
    load_params<FAR>(p, k5 ? 512 + (c >> 1) : w4 * 128 + c, tid & 127, OFF_W + w4 * W_BYTES + W_KT + k5 * 2048, w4 != 2 && w4 != 4);
  }
  const int warp = (int)uni(tid >> 5), wg = warp >> 2;
  TS(0);
  if (__builtin_expect(wg == 4, 0)) {
    asm volatile("setmaxnreg.dec.sync.aligned.u32 32;");
    const int role = warp;
    const int u0 = (c >> 1) * 9 + (five ? ((c & 2) ? 5 : 0) : ((c & 2) ? 0 : 4));
    const uint32_t t0 = clock() + c * 4;
    if (role == 16) {
      if (lane < 19) asm volatile("mbarrier.init.shared::cta.b64 [%0], %1;" :: "r"(OFF_MISC + lane * 8), "r"((unsigned)(lane - 2) < 4u ? 4 : 1) : "memory");
      if (lane < 2) asm volatile("mbarrier.arrive.expect_tx.shared::cta.b64 _, [%0], %1;" :: "r"(OFF_MISC + lane * 8), "r"(lane ? (five ? 36864 : 51200) : pitch * 1152) : "memory");
      fence_async();
      bar_arrive(5, 576);
      const CUtensorMap* tmb = &tm.m[five ? 3 : 0];
#pragma unroll 1
      for (int u = 0; u < 17; u++) {
        const uint32_t e = p.sched[five][u], kind = e & 3, s = (e >> 2) & 15, dst = e >> 14;
        if (kind == 3) continue;
        while ((int)(clock() - t0) < X_PF0 + (u < X_NE ? u * X_PFD : X_LAG + u * X_TD)) __nanosleep(20);
        if (e & 0x3FC0) mbar_wait(OFF_MISC + ((e >> 6) & 255));
        if (lane == 0) {
          if (kind == 2) asm volatile("cp.async.bulk.tensor.3d.shared::cluster.global.mbarrier::complete_tx::bytes [%0], [%1, {%3, %4, %5}], [%2];"
                                      :: "r"(dst), "l"(tmb + 2), "r"(MB_D), "r"(0), "r"(u0 * 8), "r"(s) : "memory");
          else tma_box(dst, tmb + kind, MB_GU, u0 * 8, s * 96);
        }
        if (u == 5) TS(2);
        if (u == 10) TS(3);
      }
      TS(4);
      TS_DUMP();
#define FINISH0 bar_sync(12, 192);        \
        _Pragma("unroll 1") for (int w = role & 2; w < (role & 2) + 2; w++) { \
          const uint32_t xa = OFF_W + W_KT + lane * 16, mk = lane < 8 ? 0xFFFEFFFEu : ~0u, ya = OFF_W + W_UP + (32 + lane) * 32 + ((w ^ (lane >> 2)) & 1) * 16 + (w & 2) * 1024; \
          const uint4 a = lds128(xa + 4096 + w * 1024), b = lds128(xa + (w ^ 2) * 1024), d = lds128(xa + 4608 + w * 1024), e = lds128(xa + 512 + (w ^ 2) * 1024); \
          stsm4t(ya, hadd2u(a.x, b.x) & mk, hadd2u(a.y, b.y) & mk, hadd2u(a.z, b.z) & mk, hadd2u(a.w, b.w) & mk); \
          stsm4t(ya + 1024, hadd2u(d.x, e.x) & mk, hadd2u(d.y, e.y) & mk, hadd2u(d.z, e.z) & mk, hadd2u(d.w, e.w) & mk); \
        } \
        fence_async();
    } else if (role == 17) {
      if (smem_u32(smem) != SB) __trap();
      if (five) { FINISH0 bar_arrive(13, 64); }
    } else if (role == 18) {
      sts32(MISC_EPOCH, 0);
      bar_arrive(5, 576);
      uint4* q = lane < 2 ? &p.s->R[c * 2 + lane] : lane < 11 ? &p.s->HS[c * 9 + lane - 2] : lane == 11 ? &p.s->HS[1152 + (c & 7)] : (uint4*)&p.s->FLAG[c * 8];
      if (lane < (c < 8 ? 12 : 11)) str128(q, ~0u, ~0u, ~0u, ~0u);
      const uint32_t ep = __shfl_sync(0xffffffffu, ldr32(q), 31) + 1u;
      sts32(MISC_EPOCH, ep | 0x80000000u);
      TSX(21);
      if (lane == 31) str32(q, ep);
      bar_sync(11, 64);
      if (lane == 0) load_tile(&tm.m[6], 3, c);
      TSX(14);
      mbar_wait(MB_KF + (lane & 3) * 8);
      __syncwarp();
      { const uint2 e = lds64(MISC_EM); if (lane < 2) str128(&p.s->SC[c * 2 + lane], e.x, __byte_perm(e.y, ep, 0x6540), 0, 0); }
      TSX(17);
      while ((int)(clock() - t0) < X_SCT) __nanosleep(100);
      TSX(18);
      {
        uint2 v[4];
#pragma unroll 1
        for (int it = 0; it < SPIN_MAX; it++) {
          uint32_t bad = 0;
#pragma unroll
          for (int q = 0; q < 4; q++) v[q] = ldr64(&p.s->SC[lane * 2 + q * 64]);
#pragma unroll
          for (int q = 0; q < 4; q++) bad |= (v[q].y >> 8) ^ (ep & 0xFFFFFFu);
          if (!__any_sync(0xffffffffu, bad)) break;
        }
        TSX(25);
#pragma unroll
        for (int q = 0; q < 4; q++) {
#pragma unroll
          for (int k = 0; k < 4; k++) asm volatile("st.shared.u8 [%0], %1;" :: "r"(sc_addr(4 * k + q) + lane), "r"(v[q].x >> (8 * k)) : "memory");
          if (lane & 1) asm volatile("st.shared.u8 [%0], %1;" :: "r"(sc_addr(16) + q * 16 + (lane >> 1)), "r"(v[q].y) : "memory");
        }
      }
      __syncwarp();
      if (lane == 0) mbar_arrive(MB_SC);
      TSX(27);
    } else {
      uint32_t w[9], d[9];
      float s = 0.f;
#pragma unroll
      for (int i = 0; i < 9; i++) { w[i] = ldnc32(p.w_r + (i < 8 ? lane * 4 + (i & 3) + (i >> 2) * 128 : 256 + lane)); d[i] = ldnc32(p.dskip + lane + 32 * i); }
#pragma unroll
      for (int i = 0; i < 9; i++) { sts32(OFF_WR + lane * 4 + i * 128, w[i]); sts32(OFF_WR + 1152 + lane * 4 + i * 128, d[i]); s += bf_lo(w[i]) + bf_hi(w[i]); }
      sts32(MISC_SW, __float_as_uint(warp_sum(s)));
      TSX(23);
      bar_sync(10, 544);
      if (lane == 0) {
        const uint32_t tp = clock();
        TSX(1);
        while ((int)(clock() - tp) < X_DELTA || (int)(clock() - t0) < X_ABS - c * 4) {}
        TSX(24);
        load_tile(&tm.m[6], 0, c);
        TSX(15);
        load_tile(&tm.m[6], 1, c);
        if (X_GF) mbar_arrive(MB_GF);
        while ((int)(clock() - t0) < X_ABS + X_DSTEP - c * 4) {}
      }
      bar_sync(11, 64);
      if (lane == 0) {
        load_tile(&tm.m[6], 2, c);
        if (!X_GF) mbar_arrive(MB_GF);
      }
      if (five) {
        mbar_wait(MB_KF);
#pragma unroll 1
        for (int it = 0; it < SPIN_MAX; it++) {
          if (lane == 0) load_tile(&tm.m[6], 4, c);
          mbar_wait(MB_UL + 32, it & 1);
          uint32_t m = 1;
#pragma unroll
          for (int q = 0; q < 4; q++) { uint32_t r0, r1, r2, r3; ldsm4(OFF_W + ALT + W_UP + 1024 + lane * 32 + (lane & 4) * 4 + q * 1024, r0, r1, r2, r3); m &= r0 & r1 & r2 & r3; }
          if (__all_sync(0xffffffffu, m || (lane & 3))) break;
        }
        bar_arrive(7, 288);
        FINISH0
        bar_sync(13, 64);
        if (lane == 0) {
          asm volatile("cp.async.bulk.tensor.2d.global.shared::cta.bulk_group [%0, {%2, %3}], [%1];" :: "l"(&tm.m[7]), "r"(OFF_W + W_UP + 1024), "r"(c * 16), "r"(0) : "memory");
          asm volatile("cp.async.bulk.commit_group;" ::: "memory");
          asm volatile("cp.async.bulk.wait_group.read 0;" ::: "memory");
        }
      }
      uint4* rp = &p.s->R[c * 2 + (lane & 1)];
      asm volatile("" : "+l"(rp));
      bar_sync(0, 544);
      if (lane == 0) mbar_arrive(MB_H);
      bar_sync(5, 544);
      const uint4 k = lds128(MISC_RK + (lane & 1) * 16);
      if (lane < 2) str128(rp, k.x, k.y, k.z, k.w);
    }
    return;
  }
  const int wt = tid & 127, g = lane >> 2, t = lane & 3;
  const uint32_t wb = OFF_W + wg * W_BYTES;
  const uint32_t xrow = OFF_YT + (wt >> 3) * YT_PITCH + (wt & 64) + (lane & 7) * 16;
  if (wg == 2) {
    const unsigned char* xp = p.x + (uint32_t)((c * 16 + (wt >> 3)) * 1152 + (lane & 7) * 16);
    { const uint32_t tq = clock(); while ((int)(clock() - tq) < X_XD) {} }
#pragma unroll
    for (int k = 0; k < 9; k++) asm volatile("cp.async.cg.shared.global [%0], [%1], 16;" :: "r"(xrow + k * 128), "l"(xp + k * 128) : "memory");
  }
  asm volatile("cp.async.commit_group;" ::: "memory");
  const ConvC cv = conv_consts(warp & 3, lane);
  zero_pads(wb, wt);
  load_params<FAR>(p, wg * 128 + c, wt, wb + W_KT, wg == 2 || (wg == 3 && !five));
  asm volatile("cp.async.commit_group;" ::: "memory");
  asm volatile("setmaxnreg.inc.sync.aligned.u32 112;");
  {
    uint4 kw;
    uint4* kx = &p.s->KX[(c >> 1) * 128 + wt];
    bool two = wg == 3;
    uint32_t ep;
    int phase = wg == 2 ? 3 : 2;
#pragma unroll 1
    for (;;) {
      const bool first = two && !five;
      if (phase) asm volatile("cp.async.wait_group 1;" ::: "memory"); else asm volatile("cp.async.wait_group 0;" ::: "memory");
      if (phase == 3) {
        TS(21);
        float d[3][4], r;
        uint4 a[9];
#pragma unroll
        for (int k = 0; k < 9; k++) a[k] = lds128(xrow + k * 128);
#pragma unroll
        for (int i = 0; i < 4; i++) d[0][i] = d[1][i] = d[2][i] = 0.f;
#pragma unroll
        for (int k = 0; k < 9; k++) { mma_bf16(d[(2 * k) % 3], a[k].x, ones, a[k].y, ones, a[k].x, a[k].y); mma_bf16(d[(2 * k + 1) % 3], a[k].z, ones, a[k].w, ones, a[k].z, a[k].w); }
#pragma unroll
        for (int i = 0; i < 4; i++) d[0][i] += d[1][i] + d[2][i];
        const LnC lc = ln_consts(d[0][2] + d[0][3], __shfl_sync(0xffffffffu, d[0][0], 9 * t) + __shfl_sync(0xffffffffu, d[0][1], 9 * t + 4), r);
        if (lane < 12) sts16(MISC_LN1 + g * 32 + (warp & 3) * 8 + t * 2, lane < 4 ? lc.m2 : lane < 8 ? lc.rh2 : lc.rl2);
      } else {
        KgState ks;
        uint32_t raw[7];
        bar_sync(1 + wg, 128);
        TS(22);
#pragma unroll
        for (int i = 0; i < 7; i++) raw[i] = lds16(wb + W_KT + first * 2048 + i * 256 + (i < 6 ? wt : (c >> first) & 7) * 2);
        kgen_tables_n(raw, wb, wt, ks);
        TS(20);
        bar_sync(1 + wg, 128);
        const int em = kgen_tables_m(wb, wt, ks);
        asm volatile("st.shared.u8 [%0], %1;" :: "r"(MISC_EM + wg + first), "r"(em + 9) : "memory");
        fence_async();
      }
      if (phase & 2) {
        const uint32_t tr_addr = tr_base(lane) + warp * 32;
        uint4* dst = &p.s->X[c * DM * 2 + warp * 32 + (8 * (t >> 1) + g) * 2 + (t & 1)];
        TS(23);
        bar_sync(5, 576);
        uint32_t x[3][4];
        ldsm4t(tr_addr, x[0][0], x[0][1], x[0][2], x[0][3]);
        const uint4 m = lds128(MISC_LN1 + (t & 1) * 16), rl = lds128(MISC_LN1 + 64 + (t & 1) * 16), rh = lds128(MISC_LN1 + 32 + (t & 1) * 16);
        ldsm4t(tr_addr + 512, x[1][0], x[1][1], x[1][2], x[1][3]);
        if (wg == 1) ldsm4t(tr_addr + 896, x[2][0], x[2][1], x[2][2], x[2][3]);
#pragma unroll
        for (int q = 0; q < 3; q++) {
          if (q < 2 || wg == 1) {
            const uint32_t r0 = ln_apply(x[q][0], m.x, rh.x, rl.x), r1 = ln_apply(x[q][1], m.y, rh.y, rl.y), r2 = ln_apply(x[q][2], m.z, rh.z, rl.z), r3 = ln_apply(x[q][3], m.w, rh.w, rl.w);
            str128(dst + q * 512 - (q == 2 ? 128 : 0), (pack_h(bf_lo(r0), bf_hi(r0)) & 0xFFFEFFFEu) | 1u, pack_h(bf_lo(r1), bf_hi(r1)), pack_h(bf_lo(r2), bf_hi(r2)), pack_h(bf_lo(r3), bf_hi(r3)));
          }
          if (q == 0) { TS(30); bar_arrive(10, 544); }
        }
        TS(1);
      } else bar_sync(1 + wg, 128);
      phase &= 1;
      if (phase) { phase = 0; continue; }
      TS(14);
      float acc[20];
      const uint32_t alo = (wb >> 4) | (8u << 16);
      wg_fence();
      wgmma40_ss_init(acc, alo, alo + 1024, 2048 >> 4);
#pragma unroll
      for (int k = 1; k < 8; k++) wgmma40_ss(acc, alo + k * 16, alo + 1024 + k * 16, 2048 >> 4);
      wg_commit();
      const uint4 k4 = lds128(wb + W_MISC + 16);
      const float k2048 = (float)(int)(k4.x + k4.y + k4.z + k4.w) * (1.f / 262144.f);
      wg_wait<0>();
      const float un = 1.f / 8192.f;
      kw.x = pack_h((acc[0] - acc[3]) * un, (acc[4] - acc[7]) * un);
      kw.y = pack_h((acc[8] - acc[11]) * un, (acc[12] - acc[15]) * un);
      kw.z = pack_h((acc[16] - acc[19]) * un, k2048 * un);
      TS(24);
      ep = 0;
      if (two) SPIN_WHILE(ep == 0, ep = lds32(MISC_EPOCH));
      if (five || !two) break;
      str128(kx, kw.x, kw.y, kw.z, ep);
      two = false;
    }
    if (lane == 0) mbar_arrive(MB_KF + wg * 8);
    mbar_wait(MB_KF + wg * 8);
    if (two) { mbar_wait(MB_KF); zero_pads(OFF_W + ALT, wt); }
    uint32_t tb = wb;
#pragma unroll 1
    for (;;) {
      kgen_build(tb, (tb == wb ? wb : OFF_W + 16384 - 25600) + 25600, wg, wt, kw.x, kw.y, kw.z);
      TS(15);
      if (!two) break;
      two = false;
      kw.w = 0;
      SPIN_WHILE(kw.w != ep, kw = ldr128(kx));
      tb = OFF_W + ALT;
    }
    fence_async();
    TS(31);
    if (tb != wb) bar_arrive(7, 288);
    bar_sync(1 + wg, 128);
  }
  uint32_t tpub;
#pragma unroll 1
  for (int item = 0;; item++) {
    TS(2);
    conv_item(item ? OFF_W + ALT : wb, cv, p.zero, &tm.m[7], item ? 512 + (c >> 1) : wg * 128 + c, warp, lane, five && wg >= X_GW, five && !wg && !item);
    tpub = clock() - (item ? X_YD : wg >= 2 ? X_YD2 : 0);
    if (wg || !five || item) break;
    TS(27);
    bar_sync(7, 288);
  }
  TS(4);

  const int ln = lane ^ p.zero, td = warp * 32 + ln, gg = ln >> 2, tt = ln & 3;
  const int tok = c * 16 + warp;
  const int fu = warp / 3, fk = warp - fu * 3;
  uint32_t wa[12][4];
  {
    uint32_t hw[9], wr[9];
    const uint32_t row = keep(OFF_YT + warp * YT_PITCH + (warp >> 3) * 64 + ln * 16);
    const uint32_t wabase = keep(((ln & 8) ? OFF_W + (fk + 1) * W_BYTES : OFF_G + fk * 192 * pitch) + ((ln >> 4) * 8 + (ln & 7)) * pitch
                                 + (five ? ((fu ^ (ln >> 1)) & 3) : min(fu, 4)) * 16);
    float sw;
    {
      const bool three = wg == 1;
      const int ch = 8 * (tt >> 1) + gg;
      const uint32_t tr_addr = tr_base(ln);
      const uint4* ysrc = &p.s->X[c * DM * 2 + ch * 2 + (tt & 1)];
      uint32_t x[3][4], ud[3][4], s[3];
      uint4 v[3];
#define TL(q) ((q) < 2 ? 2 * warp + (q) : 28 + warp)
      asm volatile("cp.async.bulk.wait_group.read 0;" ::: "memory");
      while ((int)(clock() - tpub) < X_YD) {}
      TS(5);
      v[0] = ldr128(ysrc + TL(0) * 32); v[1] = ldr128(ysrc + TL(1) * 32); v[2] = make_uint4(three, 0, 0, 0);
      mbar_wait(MB_REL);
      const uint4 m = lds128(MISC_LN1 + (tt & 1) * 16), rh = lds128(MISC_LN1 + 32 + (tt & 1) * 16), rl = lds128(MISC_LN1 + 64 + (tt & 1) * 16);
#pragma unroll
      for (int i = 0; i < 9; i++) wr[i] = lds32(OFF_WR + ln * 4 + i * 128);
      sw = __uint_as_float(lds32(MISC_SW));
#pragma unroll
      for (int q = 0; q < 3; q++) {
        if (q < 2 || three) {
          const uint32_t dk = lds16(OFF_WR + 1152 + ch * 2 + TL(q) * 32) * 0x10001u;
          ldsm4t(tr_addr + TL(q) * 32, x[q][0], x[q][1], x[q][2], x[q][3]);
          ud[q][0] = bf_mul2(ln_apply(x[q][0], m.x, rh.x, rl.x), dk); ud[q][1] = bf_mul2(ln_apply(x[q][1], m.y, rh.y, rl.y), dk);
          ud[q][2] = bf_mul2(ln_apply(x[q][2], m.z, rh.z, rl.z), dk); ud[q][3] = bf_mul2(ln_apply(x[q][3], m.w, rh.w, rl.w), dk);
        }
      }
      mbar_wait(MB_SC);
#pragma unroll
      for (int q = 0; q < 3; q++) {
        asm volatile("ld.shared.u8 %0, [%1];" : "=r"(s[q]) : "r"((q < 2 ? sc_addr(warp) + q * 16 : sc_addr(16) + (warp & 3) * 16) + ch) : "memory");
        s[q] = keep(s[q] * 0x800080u);
      }
#define FIN(q) stsm4t(tr_addr + TL(q) * 32, bf_add2(x[q][0], bf_fma2(h2bf(v[q].x), s[q], ud[q][0])), bf_add2(x[q][1], bf_fma2(h2bf(v[q].y), s[q], ud[q][1])), \
                      bf_add2(x[q][2], bf_fma2(h2bf(v[q].z), s[q], ud[q][2])), bf_add2(x[q][3], bf_fma2(h2bf(v[q].w), s[q], ud[q][3])));
      SPIN_WHILE((v[0].x | v[1].x) & 1u, _Pragma("unroll") for (int q = 0; q < 3; q++) if (v[q].x & 1u) v[q] = ldr128(ysrc + TL(q) * 32));
      if (v[2].x & 1u) v[2] = ldr128(ysrc + TL(2) * 32);
      FIN(0) FIN(1)
      if (three) {
        SPIN_WHILE(v[2].x & 1u, if (v[2].x & 1u) v[2] = ldr128(ysrc + TL(2) * 32));
        FIN(2)
      }
#undef FIN
#undef TL
    }
    TS(28);
    bar_sync(0, 544);
    TS(6);
    float d[4] = {0.f, 0.f, 0.f, 0.f}, e[4] = {0.f, 0.f, 0.f, 0.f}, rd;
    {
      const uint4 a = lds128(row), b = lds128(row + 512);
      hw[8] = lds32(row + 1024 - ln * 12);
      hw[0] = a.x; hw[1] = a.y; hw[2] = a.z; hw[3] = a.w; hw[4] = b.x; hw[5] = b.y; hw[6] = b.z; hw[7] = b.w;
    }
    mma_bf16(e, hw[0], hw[1], hw[2], hw[3], ones, ones);
#pragma unroll
    for (int i = 0; i < 8; i += 2) mma_bf16(d, hw[i], wr[i], hw[i + 1], wr[i + 1], hw[i], hw[i + 1]);
    mma_bf16(e, hw[4], hw[5], hw[6], hw[7], ones, ones);
    e[0] += e[2];
    mma_bf16_k8(e, hw[8], wr[8], ones);
    mma_bf16_k8(d, hw[8], wr[8], hw[8]);
    const float hwsum = diag_sum(d[2], d[3], tt);
    LnC l2 = ln_consts(diag_sum(e[0], e[0], tt), diag_sum(d[0], d[1], tt), rd);
    const uint32_t b = pack_bf(0.f, fmaf(-bf_lo(l2.m2), sw, hwsum) * rd);
    uint32_t key = max(min((b ^ (((int)b >> 31) | 0x80000000u)) >> 16, 0xFFFEu), 1u);
    sts16(MISC_RK + warp * 2, key);
    bar_sync(5, 544);
    asm volatile("" : "+r"(l2.m2) :: "memory");
    TS(7);
    const uint32_t tr0 = clock();
    key = (key << 16) | (2047 - tok);
    uint32_t loc = ln < 16 ? (lds16(MISC_RK + ln * 2) << 16) | (2047 - c * 16 - ln) : 0u;
    int rank = __popc(__ballot_sync(0xffffffffu, loc > key));
#pragma unroll
    for (int i = 0; i < 9; i++) wr[i] = keep(ln_apply(hw[i], l2.m2, l2.rh2, l2.rl2));
    const uint2* rsrc = (const uint2*)p.s->R + td;
    while ((int)(clock() - tr0) < X_RD) {}
    uint2 rv = ldr64(rsrc);
    mbar_wait(MB_GU);
    if (warp < (five ? 12 : 15)) {
#pragma unroll
      for (int k = 0; k < X_WS; k++) ldsm4t(wabase + k * 16 * pitch, wa[k][0], wa[k][1], wa[k][2], wa[k][3]);
    }
#define OUT_ROW { uint32_t* o = p.out + tok * 288 + ln * 4; \
      *(uint4*)o = make_uint4(bf_add2(hw[0], wr[0]), bf_add2(hw[1], wr[1]), bf_add2(hw[2], wr[2]), bf_add2(hw[3], wr[3])); \
      *(uint4*)(o + 128) = make_uint4(bf_add2(hw[4], wr[4]), bf_add2(hw[5], wr[5]), bf_add2(hw[6], wr[6]), bf_add2(hw[7], wr[7])); \
      o[256 - ln * 3] = bf_add2(hw[8], wr[8]); }
    if (rank >= X_OR) OUT_ROW
#pragma unroll 1
    for (int base = 0; base < 8; base += 4) {
      uint32_t T[4];
#pragma unroll
      for (int j = 0; j < 4; j++) {
        const uint32_t mx = __reduce_max_sync(0xffffffffu, loc);
        if (loc == mx) loc = 0;
        T[j] = (td >> 2) == c ? ~0u : (td >> 2) < c ? (mx & 0xFFFF0000u) - 1u : mx | 0xFFFFu;
      }
      const uint32_t sh = keep(ln < 16 ? 0x4440u + (rank & 3) : 0x4344u), ca = keep(MISC_CNT + base * 16 + (ln & 15) * 4);
      SPIN_WHILE(rv.x == ~0u, if (rv.x == ~0u) rv = ldr64(rsrc));
      TS(16);
      uint32_t cnt = 0, cn2 = 0;
#pragma unroll
      for (int j = 0; j < 4; j++)
        asm("{ .reg .pred a, b, c, d; setp.gt.u32 a, %2, %6; setp.gt.u32 b, %3, %6; setp.gt.u32 c, %4, %6; setp.gt.u32 d, %5, %6; "
            "@a add.u32 %0, %0, %7; @b add.u32 %1, %1, %7; @c add.u32 %0, %0, %7; @d add.u32 %1, %1, %7; }"
            : "+r"(cnt), "+r"(cn2) : "r"(rv.x), "r"(rv.x << 16), "r"(rv.y), "r"(rv.y << 16), "r"(T[j]), "r"(1u << (8 * j)));
      sts32(MISC_CNT + base * 16 + warp * 4, __reduce_add_sync(0xffffffffu, cnt + cn2));
      bar_sync(0, 512);
      cnt = __reduce_add_sync(0xffffffffu, __byte_perm(lds32(ca), 0, sh));
      if ((rank & ~3) == base && rank + (int)(cnt & 0xFFFFu) < 8) {
        rank += cnt & 0xFFFFu;
        uint4* hs = p.s->HS + rank * 72 + ln;
        str128(hs, wr[0], wr[1], wr[2], wr[3]); str128(hs + 32, wr[4], wr[5], wr[6], wr[7]); str32((uint32_t*)(hs + 64) - ln * 3, wr[8]);
        str128(hs + 576, hw[0], hw[1], hw[2], hw[3]); str128(hs + 608, hw[4], hw[5], hw[6], hw[7]); str32((uint32_t*)(hs + 640) - ln * 3, hw[8]);
        if (ln == 0) str32(&p.s->HS[1152 + rank], key);
        rank = 16;
      }
      if (cnt >= (4u << 16)) break;
    }
    TS(8);
    tpub = clock();
    if (rank < X_OR) OUT_ROW
    if (warp < (five ? 12 : 15)) {
#pragma unroll
      for (int k = X_WS; k < 12; k++) ldsm4t(wabase + k * 16 * pitch, wa[k][0], wa[k][1], wa[k][2], wa[k][3]);
    }
  }
  uint32_t wd[10][4];
  const uint32_t xb = keep(OFF_XS + (ln & 7) * 1168 + (fk * 24 + (ln >> 3)) * 16);
  if (warp >= 7) {
    const uint32_t db = down_box(warp - 7, five) + (ln & 7) * 128;
    mbar_wait(MB_D);
#pragma unroll
    for (int j = 0; j < 4; j++) {
      const uint32_t a = db + (ln >> 4) * 1024 + (((2 * j + ((ln >> 3) & 1)) ^ (ln & 7)) << 4);
      ldsm4t(a, wd[j][0], wd[j][1], wd[j][2], wd[j][3]);
      ldsm4t(a + 2048, wd[4 + j][0], wd[4 + j][1], wd[4 + j][2], wd[4 + j][3]);
    }
#pragma unroll
    for (int j = 0; j < 2; j++) ldsm4t(db + 4096 + (((4 * j + (ln >> 3)) ^ (ln & 7)) << 4), wd[8 + j][0], wd[8 + j][1], wd[8 + j][2], wd[8 + j][3]);
  } else if (warp < 6) {
    const int r = td / 24;
    const uint4* src = &p.s->HS[td + r * 48];
    const uint32_t xs = keep(OFF_XS + (td + r * 49) * 16);
    uint4 a[3];
    uint32_t m = ~0u;
    while ((int)(clock() - tpub) < X_HD) {}
    TS(19);
    SPIN_WHILE(m == ~0u, if (m == ~0u) { a[0] = ldr128(src); a[1] = ldr128(src + 24); a[2] = ldr128(src + 48); } m = max(max(max(a[0].x, a[1].x), max(a[2].x, a[2].y)), max(a[2].z, a[2].w)));
#pragma unroll
    for (int q = 0; q < 3; q++) sts128(xs + q * 384, a[q].x, a[q].y, a[q].z, a[q].w);
  }
  bar_sync(0, 512);
  TS(9);

  if (warp < (five ? 12 : 15)) {
    float d0[4] = {0.f, 0.f, 0.f, 0.f}, d1[4] = {0.f, 0.f, 0.f, 0.f};
#pragma unroll
    for (int k = 0; k < 12; k += 2) {
      uint32_t b0, b1, b2, b3;
      ldsm4(xb + k * 32, b0, b1, b2, b3);
      mma_bf16(d0, wa[k][0], wa[k][1], wa[k][2], wa[k][3], b0, b1);
      mma_bf16(d1, wa[k + 1][0], wa[k + 1][1], wa[k + 1][2], wa[k + 1][3], b2, b3);
    }
    sts128(OFF_RED + td * 16, __float_as_uint(d0[0] + d1[0]), __float_as_uint(d0[1] + d1[1]), __float_as_uint(d0[2] + d1[2]), __float_as_uint(d0[3] + d1[3]));
  }
  TS(26);
  if (warp < 5) {
    const uint32_t rb = OFF_RED + warp * 1536 + ln * 16;
    bar_sync(9, 512);
    const uint4 pa = lds128(rb), pb = lds128(rb + 512), pc = lds128(rb + 1024);
    const float ga = bfr(__uint_as_float(pa.x) + __uint_as_float(pb.x) + __uint_as_float(pc.x));
    const float gb = bfr(__uint_as_float(pa.y) + __uint_as_float(pb.y) + __uint_as_float(pc.y));
    const uint32_t uu = pack_bf(__uint_as_float(pa.z) + __uint_as_float(pb.z) + __uint_as_float(pc.z), __uint_as_float(pa.w) + __uint_as_float(pb.w) + __uint_as_float(pc.w));
    float ra, rb2;
    asm("rcp.approx.ftz.f32 %0, %1;" : "=f"(ra) : "f"(1.f + ex2(ga * -1.4426950408889634f)));
    asm("rcp.approx.ftz.f32 %0, %1;" : "=f"(rb2) : "f"(1.f + ex2(gb * -1.4426950408889634f)));
    const uint32_t act = bf_mul2(pack_bf(ga * ra, gb * rb2), uu);
    sts32(OFF_ACT + td * 4, act);
  } else bar_arrive(9, 512);
  uint4* dst = &p.s->X[c * DM * 2 + (warp - 7) * 64 + tt * 8 + gg];
  asm volatile("" : "+l"(dst));
  bar_sync(8, 512);
  tpub = clock();
  if (warp >= 7) {
    uint32_t b0, b1, b2, b3, b4;
    ldsm4t(OFF_ACT + ln * 16, b0, b1, b2, b3);
    asm volatile("ldmatrix.sync.aligned.m8n8.x1.trans.shared.b16 {%0}, [%1];" : "=r"(b4) : "r"(OFF_ACT + 512 + ln * 16) : "memory");
    float y[4][4];
#pragma unroll
    for (int j = 0; j < 4; j++) {
      y[j][0] = y[j][1] = y[j][2] = y[j][3] = 0.f;
      mma_bf16(y[j], wd[j][0], wd[j][1], wd[j][2], wd[j][3], b0, b1);
    }
#pragma unroll
    for (int j = 0; j < 4; j++) mma_bf16(y[j], wd[4 + j][0], wd[4 + j][1], wd[4 + j][2], wd[4 + j][3], b2, b3);
    if (!five) {
#pragma unroll
      for (int j = 0; j < 4; j++) mma_bf16_k8(y[j], wd[8 + (j >> 1)][2 * (j & 1)], wd[8 + (j >> 1)][2 * (j & 1) + 1], b4);
    }
    str128(dst, (pack_bf(y[0][0], y[0][1]) & ~1u) | 0x10000u, pack_bf(y[0][2], y[0][3]), pack_bf(y[1][0], y[1][1]), pack_bf(y[1][2], y[1][3]));
    str128(dst + 32, (pack_bf(y[2][0], y[2][1]) & ~1u) | 0x10000u, pack_bf(y[2][2], y[2][3]), pack_bf(y[3][0], y[3][1]), pack_bf(y[3][2], y[3][3]));
  }
  TS(10);

  if (c < 72) {
    const uint4* src = &p.s->X[(warp * 4 + tt) * (DM * 2) + c * 8 + gg];
    const int slot = (c & 3) * 2 + (ln >> 4), dw = (c >> 2) * 16 + (ln & 15);
    uint32_t hv = 0, kv = 0, res = 0, rs2 = 0;
    uint32_t* o = p.out;
    if (warp == 0) {
      hv = ~0u;
      SPIN_WHILE(max(hv, kv) == ~0u, hv = ldr32((const uint32_t*)p.s->HS + 2304 + slot * 288 + dw); kv = ldr32(&p.s->HS[1152 + slot]));
      const float r = bf_hi(kv ^ (((int)~kv >> 31) | 0x80000000u));
      float rs;
      asm("rcp.approx.ftz.f32 %0, %1;" : "=f"(rs) : "f"(1.f + ex2(r * -1.4426950408889634f)));
      rs2 = keep(pack_bf(rs, rs));
      res = lds32(OFF_XS + slot * 1168 + dw * 4);
      o += (2047 - (int)(kv & 2047u)) * 288 + dw;
      asm volatile("" : "+l"(o));
    }
    const uint32_t sel = (gg & 1) ? 0x3F800000u : 0x00003F80u;
    const uint32_t q0 = keep((gg >> 1) == 0 ? sel : 0u), q1 = keep((gg >> 1) == 1 ? sel : 0u), q2 = keep((gg >> 1) == 2 ? sel : 0u), q3 = keep((gg >> 1) == 3 ? sel : 0u);
    const uint32_t fa = keep(OFF_FIN + warp * 256 + (gg & 1) * 128 + (gg >> 1) * 32 + tt * 8), fb = keep(OFF_FIN + ln * 8);
    uint4 a0 = make_uint4(0, 0, 0, 0), a1 = a0;
    while ((int)(clock() - tpub) < X_PD) {}
    SPIN_WHILE(!(a0.x & a1.x & 0x10000u), if (!(a0.x & 0x10000u)) a0 = ldr128(src); if (!(a1.x & 0x10000u)) a1 = ldr128(src + 64 * DM * 2));
    float d[4] = {0.f, 0.f, 0.f, 0.f}, e[4] = {0.f, 0.f, 0.f, 0.f};
    mma_bf16(d, q0, q2, q1, q3, a0.x, a0.y); mma_bf16(e, q0, q2, q1, q3, a0.z, a0.w);
    mma_bf16(d, q0, q2, q1, q3, a1.x, a1.y); mma_bf16(e, q0, q2, q1, q3, a1.z, a1.w);
    sts64(fa, __float_as_uint(d[0] + e[2]), __float_as_uint(d[1] + e[3]));
    TS(11);
    if (warp == 0) {
      bar_sync(0, 512);
      float2 s[16];
#pragma unroll
      for (int i = 0; i < 16; i++) { const uint2 q = lds64(fb + i * 256); s[i] = make_float2(__uint_as_float(q.x), __uint_as_float(q.y)); }
#pragma unroll
      for (int k = 1; k < 16; k *= 2)
#pragma unroll
        for (int i = 0; i < 16; i += 2 * k) { s[i].x += s[i + k].x; s[i].y += s[i + k].y; }
      *o = bf_add2(hv, bf_add2(res, bf_mul2(pack_bf(s[0].x, s[0].y), rs2)));
    } else bar_arrive(0, 512);
  }
  TS(12);
  TS_DUMP();
}

typedef CUresult (*EncodeFn)(CUtensorMap*, CUtensorMapDataType, cuuint32_t, void*, const cuuint64_t*, const cuuint64_t*, const cuuint32_t*,
                             const cuuint32_t*, CUtensorMapInterleave, CUtensorMapSwizzle, CUtensorMapL2promotion, CUtensorMapFloatOOBfill);

}

extern "C" void kernel_launch(void* const* d_in, const int* in_sizes, int n_in, void* d_out, int out_size) {
  (void)in_sizes; (void)n_in; (void)out_size;
  static EncodeFn enc = nullptr;
  static Scratch* scratch = nullptr;
  if (!enc) {
    void* fn = nullptr;
    cudaDriverEntryPointQueryResult qr;
    cudaGetDriverEntryPoint("cuTensorMapEncodeTiled", &fn, cudaEnableDefault, &qr);
    enc = (EncodeFn)fn;
    cudaGetSymbolAddress((void**)&scratch, g_S);
    cudaFuncSetAttribute(fused_kernel<false>, cudaFuncAttributeMaxDynamicSharedMemorySize, SMEM_BYTES);
    cudaFuncSetAttribute(fused_kernel<true>, cudaFuncAttributeMaxDynamicSharedMemorySize, SMEM_BYTES);
  }
  TMaps tm;
  for (int i = 0; i < 6; i++) {
    const bool dn = i % 3 == 2;
    const cuuint32_t w = i < 3 ? 40 : 32;
    cuuint64_t gd[3] = {(cuuint64_t)(dn ? 64 : FF), (cuuint64_t)(dn ? FF : DM), 9};
    cuuint64_t gs[2] = {(cuuint64_t)(dn ? DM * 2 : FF * 2), 128};
    cuuint32_t bx[3] = {dn ? 64 : w, dn ? w : 96, i < 3 ? 2u : 3u};
    cuuint32_t es[3] = {1, 1, 1};
    enc(&tm.m[i], CU_TENSOR_MAP_DATA_TYPE_BFLOAT16, dn ? 3 : 2, d_in[11 + i % 3], gd, gs, bx, es, CU_TENSOR_MAP_INTERLEAVE_NONE,
        dn ? CU_TENSOR_MAP_SWIZZLE_128B : i < 3 ? CU_TENSOR_MAP_SWIZZLE_NONE : CU_TENSOR_MAP_SWIZZLE_64B,
        (CUtensorMapL2promotion)X_PROMO, CU_TENSOR_MAP_FLOAT_OOB_FILL_NONE);
  }
  for (int i = 6; i < 8; i++) {
    cuuint64_t gd[2] = {DM * 16, NCTA};
    cuuint64_t gs[1] = {DM * 32};
    cuuint32_t bx[2] = {16, i == 6 ? 160u : 128u};
    cuuint32_t es[2] = {1, 1};
    enc(&tm.m[i], CU_TENSOR_MAP_DATA_TYPE_FLOAT16, 2, scratch->X, gd, gs, bx, es, CU_TENSOR_MAP_INTERLEAVE_NONE, CU_TENSOR_MAP_SWIZZLE_32B,
        CU_TENSOR_MAP_L2_PROMOTION_NONE, CU_TENSOR_MAP_FLOAT_OOB_FILL_NONE);
  }
  Params p;
  p.x = (const unsigned char*)d_in[0];
  bool far = false;
  for (int i = 0; i < 7; i++) {
    p.far[i] = (const unsigned char*)d_in[1 + i];
    const long long d = (long long)((intptr_t)d_in[1 + i] - (intptr_t)d_in[0]);
    p.off[i] = (int)(d / 16);
    if ((long long)p.off[i] * 16 != d) far = true;
  }
  p.dskip = (const uint32_t*)d_in[8];
  p.w_r = (const uint32_t*)d_in[10];
  for (int f = 0; f < 2; f++) {
    static const int kind[17] = {0, 0, 0, 0, 0, 0, 2, 2, 1, 1, 1, 1, 1, 1, 2, 2, 2};
    static const int idx[2][17] = {{3, 4, 5, 0, 1, 2, 6, 8, 0, 1, 2, 3, 4, 5, 0, 2, 4}, {3, 4, 5, 0, 1, 2, 0, -1, 0, 1, 2, 3, 4, 5, 3, -1, 6}};
    static const int blk[2][17] = {{-1, -1, -1, -1, -1, -1, 0, -1, 1, -1, 2, -1, 3, -1, X_HU == 14 ? 16 : -1, -1, X_HU == 16 ? 16 : -1}, {-1, -1, -1, -1, -1, -1, 1, -1, -1, -1, 2, -1, 3, -1, X_HU == 14 ? 16 : -1, -1, X_HU == 16 ? 16 : -1}};
    const int pitch = f ? 64 : 80;
    for (int u = 0; u < 17; u++) {
      const int s = idx[f][u];
      const uint32_t dst = kind[u] == 0 ? OFF_G + s * 96 * pitch : kind[u] == 2 ? down_box(s, f) : OFF_W + W_BYTES + (s >> 1) * W_BYTES + (s & 1) * 96 * pitch;
      const uint32_t mb = u == X_NE ? MB_GF - OFF_MISC : blk[f][u] >= 0 ? MB_KF - OFF_MISC + blk[f][u] * 8 : 0;
      p.sched[f][u] = s < 0 ? 3u : kind[u] | s << 2 | mb << 6 | dst << 14;
    }
  }
  p.out = (uint32_t*)d_out;
  p.zero = 0;
  p.ts = nullptr;
  p.s = scratch;
  if (far) { fused_kernel<true><<<NCTA, NT, SMEM_BYTES, cudaStreamPerThread>>>(p, tm); return; }
  fused_kernel<false><<<NCTA, NT, SMEM_BYTES, cudaStreamPerThread>>>(p, tm);
}
```

```cpp
#include <cuda_runtime.h>
#include <cuda.h>
#include <cuda_bf16.h>
#include <cuda_fp16.h>
#include <stdint.h>
#include <stddef.h>

namespace {

constexpr int NCTA = 128;
constexpr int NT = 640;
constexpr int DM = 576;
constexpr int FF = 4608;
constexpr int SPIN_MAX = 1 << 20;

struct Scratch {
  uint4 X[NCTA * DM * 2];
  uint4 KX[64 * 128];
  uint4 HS[1152 + 8];
  uint4 R[256];
  uint4 SC[256];
  uint32_t FLAG[NCTA * 8];
};
__device__ Scratch g_S;

#define CLKS(i)
#define TS(i)
#define TSX(i)
#define TS_DUMP()

constexpr int SB = 1024;
constexpr int BOX = 15360;
constexpr int OFF_G = SB;
constexpr int OFF_W = OFF_G + 3 * BOX;
constexpr int W_UP = 26624;
constexpr int W_KT = W_UP + 5120;
constexpr int W_L3 = W_KT + 4416;
constexpr int W_CW = W_L3 + 4096;
constexpr int W_MISC = W_CW + 640;
constexpr int W_BYTES = 40960;
constexpr int ALT = -W_UP;
static_assert(W_MISC + 32 <= W_BYTES && OFF_W % 1024 == 0 && W_UP % 256 == 0 && W_BYTES + ALT + 3 * 4096 <= W_UP, "wg block");
constexpr int YT_PITCH = 1184;
constexpr int OFF_YT = OFF_W + 4 * W_BYTES;
constexpr int OFF_WR = OFF_YT + 16 * YT_PITCH + 64;
constexpr int OFF_MISC = OFF_WR + 2304;
constexpr int SMEM_BYTES = OFF_MISC + 1024 - SB;
static_assert(OFF_YT % 16 == 0 && OFF_MISC % 16 == 0, "align");
static_assert(SMEM_BYTES <= 232448, "smem");
constexpr int MB_GU = OFF_MISC;
constexpr int MB_D = OFF_MISC + 8;
constexpr int MB_KF = OFF_MISC + 16;
constexpr int MB_GF = OFF_MISC + 48;
constexpr int MB_SC = OFF_MISC + 56;
constexpr int MB_UL = OFF_MISC + 64;
constexpr int MB_REL = OFF_MISC + 104;
constexpr int MB_GO = OFF_MISC + 112;
constexpr int MB_H = MB_KF + 128;
constexpr int MISC_EPOCH = OFF_MISC + 152;
constexpr int MISC_SW = OFF_MISC + 156;
constexpr int MISC_EM = OFF_MISC + 288;
constexpr int MISC_RK = OFF_MISC + 160;
constexpr int MISC_LN1 = OFF_MISC + 192;
constexpr int OFF_XS = OFF_W + W_BYTES + W_UP;
constexpr int OFF_RED = OFF_W + 2 * W_BYTES + W_UP;
constexpr int OFF_FIN = OFF_W + 3 * W_BYTES + W_UP;
constexpr int OFF_ACT = OFF_FIN + 4096;
constexpr int MISC_CNT = OFF_ACT + 1024;

__device__ __forceinline__ uint32_t smem_u32(const void* p) { return (uint32_t)__cvta_generic_to_shared(p); }
__device__ __forceinline__ uint32_t lds32(uint32_t a) { uint32_t v; asm volatile("ld.shared.b32 %0, [%1];" : "=r"(v) : "r"(a) : "memory"); return v; }
__device__ __forceinline__ uint32_t lds16(uint32_t a) { uint16_t v; asm volatile("ld.shared.u16 %0, [%1];" : "=h"(v) : "r"(a) : "memory"); return v; }
__device__ __forceinline__ uint2 lds64(uint32_t a) { uint2 v; asm volatile("ld.shared.v2.b32 {%0,%1}, [%2];" : "=r"(v.x), "=r"(v.y) : "r"(a) : "memory"); return v; }
__device__ __forceinline__ uint4 lds128(uint32_t a) { uint4 v; asm volatile("ld.shared.v4.b32 {%0,%1,%2,%3}, [%4];" : "=r"(v.x), "=r"(v.y), "=r"(v.z), "=r"(v.w) : "r"(a) : "memory"); return v; }
__device__ __forceinline__ void sts16(uint32_t a, uint32_t v) { asm volatile("st.shared.u16 [%0], %1;" :: "r"(a), "h"((uint16_t)v) : "memory"); }
__device__ __forceinline__ void sts32(uint32_t a, uint32_t v) { asm volatile("st.shared.b32 [%0], %1;" :: "r"(a), "r"(v) : "memory"); }
__device__ __forceinline__ void sts64(uint32_t a, uint32_t x, uint32_t y) { asm volatile("st.shared.v2.b32 [%0], {%1,%2};" :: "r"(a), "r"(x), "r"(y) : "memory"); }
__device__ __forceinline__ void sts128(uint32_t a, uint32_t x, uint32_t y, uint32_t z, uint32_t w) { asm volatile("st.shared.v4.b32 [%0], {%1,%2,%3,%4};" :: "r"(a), "r"(x), "r"(y), "r"(z), "r"(w) : "memory"); }
__device__ __forceinline__ void ldsm4(uint32_t a, uint32_t& r0, uint32_t& r1, uint32_t& r2, uint32_t& r3) {
  asm volatile("ldmatrix.sync.aligned.m8n8.x4.shared.b16 {%0,%1,%2,%3}, [%4];" : "=r"(r0), "=r"(r1), "=r"(r2), "=r"(r3) : "r"(a) : "memory");
}
__device__ __forceinline__ void ldsm2(uint32_t a, uint32_t& r0, uint32_t& r1) {
  asm volatile("ldmatrix.sync.aligned.m8n8.x2.shared.b16 {%0,%1}, [%2];" : "=r"(r0), "=r"(r1) : "r"(a) : "memory");
}
__device__ __forceinline__ void ldsm4t(uint32_t a, uint32_t& r0, uint32_t& r1, uint32_t& r2, uint32_t& r3) {
  asm volatile("ldmatrix.sync.aligned.m8n8.x4.trans.shared.b16 {%0,%1,%2,%3}, [%4];" : "=r"(r0), "=r"(r1), "=r"(r2), "=r"(r3) : "r"(a) : "memory");
}
__device__ __forceinline__ void stsm4t(uint32_t a, uint32_t r0, uint32_t r1, uint32_t r2, uint32_t r3) {
  asm volatile("stmatrix.sync.aligned.m8n8.x4.trans.shared.b16 [%0], {%1,%2,%3,%4};" :: "r"(a), "r"(r0), "r"(r1), "r"(r2), "r"(r3) : "memory");
}
__device__ __forceinline__ uint4 ldr128(const void* p) {
  unsigned long long lo, hi;
  asm volatile("{ .reg .b128 t; ld.relaxed.gpu.global.b128 t, [%2]; mov.b128 {%0, %1}, t; }" : "=l"(lo), "=l"(hi) : "l"(p) : "memory");
  return make_uint4((uint32_t)lo, (uint32_t)(lo >> 32), (uint32_t)hi, (uint32_t)(hi >> 32));
}
__device__ __forceinline__ void str128(void* p, uint32_t x, uint32_t y, uint32_t z, uint32_t w) {
  asm volatile("{ .reg .b128 t; .reg .b64 lo, hi; mov.b64 lo, {%1,%2}; mov.b64 hi, {%3,%4}; mov.b128 t, {lo, hi}; st.relaxed.gpu.global.b128 [%0], t; }"
               :: "l"(p), "r"(x), "r"(y), "r"(z), "r"(w) : "memory");
}
__device__ __forceinline__ void str64(void* p, uint32_t x, uint32_t y) {
  asm volatile("{ .reg .b64 t; mov.b64 t, {%1,%2}; st.relaxed.gpu.global.b64 [%0], t; }" :: "l"(p), "r"(x), "r"(y) : "memory");
}
__device__ __forceinline__ uint32_t ldr32(const void* p) { uint32_t v; asm volatile("ld.relaxed.gpu.global.b32 %0, [%1];" : "=r"(v) : "l"(p) : "memory"); return v; }
__device__ __forceinline__ void str32(void* p, uint32_t v) { asm volatile("st.relaxed.gpu.global.b32 [%0], %1;" :: "l"(p), "r"(v) : "memory"); }
__device__ __forceinline__ void str16(void* p, uint32_t v) { asm volatile("st.relaxed.gpu.global.u16 [%0], %1;" :: "l"(p), "h"((uint16_t)v) : "memory"); }
__device__ __forceinline__ void fence_gpu() { asm volatile("fence.acq_rel.gpu;" ::: "memory"); }
__device__ __forceinline__ void bar_sync(int id, int n) { asm volatile("bar.sync %0, %1;" :: "r"(id), "r"(n) : "memory"); }
__device__ __forceinline__ void bar_arrive(int id, int n) { asm volatile("bar.arrive %0, %1;" :: "r"(id), "r"(n) : "memory"); }

__device__ __forceinline__ float bf_lo(uint32_t w) { return __uint_as_float(w << 16); }
__device__ __forceinline__ float bf_hi(uint32_t w) { return __uint_as_float(w & 0xFFFF0000u); }
__device__ __forceinline__ uint32_t pack_bf(float lo, float hi) { uint32_t r; asm("cvt.rn.bf16x2.f32 %0, %1, %2;" : "=r"(r) : "f"(hi), "f"(lo)); return r; }
__device__ __forceinline__ uint32_t pack_h(float lo, float hi) { uint32_t r; asm("cvt.rn.f16x2.f32 %0, %1, %2;" : "=r"(r) : "f"(hi), "f"(lo)); return r; }
__device__ __forceinline__ uint32_t pack_hv(float lo, float hi) { uint32_t r; asm volatile("cvt.rn.f16x2.f32 %0, %1, %2;" : "=r"(r) : "f"(hi), "f"(lo) : "memory"); return r; }
__device__ __forceinline__ float bfr(float x) { return bf_lo(pack_bf(x, 0.f)); }
__device__ __forceinline__ uint32_t bf_sub2(uint32_t a, uint32_t b) { __nv_bfloat162 r = __hsub2(*(__nv_bfloat162*)&a, *(__nv_bfloat162*)&b); return *(uint32_t*)&r; }
__device__ __forceinline__ uint32_t bf_add2(uint32_t a, uint32_t b) { __nv_bfloat162 r = __hadd2(*(__nv_bfloat162*)&a, *(__nv_bfloat162*)&b); return *(uint32_t*)&r; }
__device__ __forceinline__ uint32_t bf_mul2(uint32_t a, uint32_t b) { __nv_bfloat162 r = __hmul2(*(__nv_bfloat162*)&a, *(__nv_bfloat162*)&b); return *(uint32_t*)&r; }
__device__ __forceinline__ float2 h2f(uint32_t w) { return __half22float2(*(__half2*)&w); }
__device__ __forceinline__ float ex2(float x) { float r; asm("ex2.approx.ftz.f32 %0, %1;" : "=f"(r) : "f"(x)); return r; }
__device__ __forceinline__ float warp_sum(float v) {
#pragma unroll
  for (int o = 16; o > 0; o >>= 1) v += __shfl_xor_sync(0xffffffffu, v, o);
  return v;
}
__device__ __forceinline__ void mma_f16_f32(float* d, uint32_t a0, uint32_t a1, uint32_t a2, uint32_t a3, uint32_t b0, uint32_t b1) {
  asm volatile("mma.sync.aligned.m16n8k16.row.col.f32.f16.f16.f32 {%0,%1,%2,%3}, {%4,%5,%6,%7}, {%8,%9}, {%0,%1,%2,%3};"
               : "+f"(d[0]), "+f"(d[1]), "+f"(d[2]), "+f"(d[3]) : "r"(a0), "r"(a1), "r"(a2), "r"(a3), "r"(b0), "r"(b1));
}
__device__ __forceinline__ void mma_f16_f16(uint32_t& d0, uint32_t& d1, uint32_t a0, uint32_t a1, uint32_t a2, uint32_t a3, uint32_t b0, uint32_t b1) {
  asm volatile("mma.sync.aligned.m16n8k16.row.col.f16.f16.f16.f16 {%0,%1}, {%2,%3,%4,%5}, {%6,%7}, {%0,%1};"
               : "+r"(d0), "+r"(d1) : "r"(a0), "r"(a1), "r"(a2), "r"(a3), "r"(b0), "r"(b1));
}
__device__ __forceinline__ void mma_bf16(float* d, uint32_t a0, uint32_t a1, uint32_t a2, uint32_t a3, uint32_t b0, uint32_t b1) {
  asm volatile("mma.sync.aligned.m16n8k16.row.col.f32.bf16.bf16.f32 {%0,%1,%2,%3}, {%4,%5,%6,%7}, {%8,%9}, {%0,%1,%2,%3};"
               : "+f"(d[0]), "+f"(d[1]), "+f"(d[2]), "+f"(d[3]) : "r"(a0), "r"(a1), "r"(a2), "r"(a3), "r"(b0), "r"(b1));
}
__device__ __forceinline__ void mma_bf16_k8(float* d, uint32_t a0, uint32_t a1, uint32_t b0) {
  asm volatile("mma.sync.aligned.m16n8k8.row.col.f32.bf16.bf16.f32 {%0,%1,%2,%3}, {%4,%5}, {%6}, {%0,%1,%2,%3};"
               : "+f"(d[0]), "+f"(d[1]), "+f"(d[2]), "+f"(d[3]) : "r"(a0), "r"(a1), "r"(b0));
}

__device__ __forceinline__ void wg_fence() { asm volatile("wgmma.fence.sync.aligned;" ::: "memory"); }
__device__ __forceinline__ void wg_commit() { asm volatile("wgmma.commit_group.sync.aligned;" ::: "memory"); }
template <int N> __device__ __forceinline__ void wg_wait() { asm volatile("wgmma.wait_group.sync.aligned %0;" :: "n"(N) : "memory"); }
template <int TB> __device__ __forceinline__ void wgmma32(float* d, const uint32_t* a, uint32_t dlo, uint32_t dhi) {
  asm volatile("{ .reg .b64 dd; mov.b64 dd, {%20, %21}; wgmma.mma_async.sync.aligned.m64n32k16.f32.f16.f16 "
               "{%0,%1,%2,%3,%4,%5,%6,%7,%8,%9,%10,%11,%12,%13,%14,%15}, {%16,%17,%18,%19}, dd, 1, 1, 1, %22; }"
               : "+f"(d[0]), "+f"(d[1]), "+f"(d[2]), "+f"(d[3]), "+f"(d[4]), "+f"(d[5]), "+f"(d[6]), "+f"(d[7]), "+f"(d[8]), "+f"(d[9]), "+f"(d[10]), "+f"(d[11]), "+f"(d[12]), "+f"(d[13]), "+f"(d[14]), "+f"(d[15])
               : "r"(a[0]), "r"(a[1]), "r"(a[2]), "r"(a[3]), "r"(dlo), "r"(dhi), "n"(TB));
}
template <int TB> __device__ __forceinline__ void wgmma96(float* d, const uint32_t* a, uint32_t dlo, uint32_t dhi) {
  asm volatile("{ .reg .b64 dd; mov.b64 dd, {%52, %53}; wgmma.mma_async.sync.aligned.m64n96k16.f32.f16.f16 "
               "{%0,%1,%2,%3,%4,%5,%6,%7,%8,%9,%10,%11,%12,%13,%14,%15,%16,%17,%18,%19,%20,%21,%22,%23,%24,%25,%26,%27,%28,%29,%30,%31,%32,%33,%34,%35,%36,%37,%38,%39,%40,%41,%42,%43,%44,%45,%46,%47}, {%48,%49,%50,%51}, dd, 1, 1, 1, %54; }"
               : "+f"(d[0]), "+f"(d[1]), "+f"(d[2]), "+f"(d[3]), "+f"(d[4]), "+f"(d[5]), "+f"(d[6]), "+f"(d[7]), "+f"(d[8]), "+f"(d[9]), "+f"(d[10]), "+f"(d[11]), "+f"(d[12]), "+f"(d[13]), "+f"(d[14]), "+f"(d[15]), "+f"(d[16]), "+f"(d[17]), "+f"(d[18]), "+f"(d[19]), "+f"(d[20]), "+f"(d[21]), "+f"(d[22]), "+f"(d[23]), "+f"(d[24]), "+f"(d[25]), "+f"(d[26]), "+f"(d[27]), "+f"(d[28]), "+f"(d[29]), "+f"(d[30]), "+f"(d[31]), "+f"(d[32]), "+f"(d[33]), "+f"(d[34]), "+f"(d[35]), "+f"(d[36]), "+f"(d[37]), "+f"(d[38]), "+f"(d[39]), "+f"(d[40]), "+f"(d[41]), "+f"(d[42]), "+f"(d[43]), "+f"(d[44]), "+f"(d[45]), "+f"(d[46]), "+f"(d[47])
               : "r"(a[0]), "r"(a[1]), "r"(a[2]), "r"(a[3]), "r"(dlo), "r"(dhi), "n"(TB));
}
template <int TB> __device__ __forceinline__ void wgmma96_init(float* d, const uint32_t* a, uint32_t dlo, uint32_t dhi) {
  asm volatile("{ .reg .b64 dd; mov.b64 dd, {%52, %53}; wgmma.mma_async.sync.aligned.m64n96k16.f32.f16.f16 "
               "{%0,%1,%2,%3,%4,%5,%6,%7,%8,%9,%10,%11,%12,%13,%14,%15,%16,%17,%18,%19,%20,%21,%22,%23,%24,%25,%26,%27,%28,%29,%30,%31,%32,%33,%34,%35,%36,%37,%38,%39,%40,%41,%42,%43,%44,%45,%46,%47}, {%48,%49,%50,%51}, dd, 0, 1, 1, %54; }"
               : "=f"(d[0]), "=f"(d[1]), "=f"(d[2]), "=f"(d[3]), "=f"(d[4]), "=f"(d[5]), "=f"(d[6]), "=f"(d[7]), "=f"(d[8]), "=f"(d[9]), "=f"(d[10]), "=f"(d[11]), "=f"(d[12]), "=f"(d[13]), "=f"(d[14]), "=f"(d[15]), "=f"(d[16]), "=f"(d[17]), "=f"(d[18]), "=f"(d[19]), "=f"(d[20]), "=f"(d[21]), "=f"(d[22]), "=f"(d[23]), "=f"(d[24]), "=f"(d[25]), "=f"(d[26]), "=f"(d[27]), "=f"(d[28]), "=f"(d[29]), "=f"(d[30]), "=f"(d[31]), "=f"(d[32]), "=f"(d[33]), "=f"(d[34]), "=f"(d[35]), "=f"(d[36]), "=f"(d[37]), "=f"(d[38]), "=f"(d[39]), "=f"(d[40]), "=f"(d[41]), "=f"(d[42]), "=f"(d[43]), "=f"(d[44]), "=f"(d[45]), "=f"(d[46]), "=f"(d[47])
               : "r"(a[0]), "r"(a[1]), "r"(a[2]), "r"(a[3]), "r"(dlo), "r"(dhi), "n"(TB));
}
template <int TB> __device__ __forceinline__ void wgmma32_init(float* d, const uint32_t* a, uint32_t dlo, uint32_t dhi) {
  asm volatile("{ .reg .b64 dd; mov.b64 dd, {%20, %21}; wgmma.mma_async.sync.aligned.m64n32k16.f32.f16.f16 "
               "{%0,%1,%2,%3,%4,%5,%6,%7,%8,%9,%10,%11,%12,%13,%14,%15}, {%16,%17,%18,%19}, dd, 0, 1, 1, %22; }"
               : "=f"(d[0]), "=f"(d[1]), "=f"(d[2]), "=f"(d[3]), "=f"(d[4]), "=f"(d[5]), "=f"(d[6]), "=f"(d[7]), "=f"(d[8]), "=f"(d[9]), "=f"(d[10]), "=f"(d[11]), "=f"(d[12]), "=f"(d[13]), "=f"(d[14]), "=f"(d[15])
               : "r"(a[0]), "r"(a[1]), "r"(a[2]), "r"(a[3]), "r"(dlo), "r"(dhi), "n"(TB));
}
__device__ __forceinline__ void wgmma64h(uint32_t* d, uint32_t a0, uint32_t a1, uint32_t a2, uint32_t a3, uint32_t dlo, uint32_t dhi) {
  asm volatile("{ .reg .b64 dd; mov.b64 dd, {%20, %21}; wgmma.mma_async.sync.aligned.m64n64k16.f16.f16.f16 "
               "{%0,%1,%2,%3,%4,%5,%6,%7,%8,%9,%10,%11,%12,%13,%14,%15}, {%16,%17,%18,%19}, dd, 1, 1, 1, 0; }"
               : "+r"(d[0]), "+r"(d[1]), "+r"(d[2]), "+r"(d[3]), "+r"(d[4]), "+r"(d[5]), "+r"(d[6]), "+r"(d[7]), "+r"(d[8]), "+r"(d[9]), "+r"(d[10]), "+r"(d[11]), "+r"(d[12]), "+r"(d[13]), "+r"(d[14]), "+r"(d[15])
               : "r"(a0), "r"(a1), "r"(a2), "r"(a3), "r"(dlo), "r"(dhi));
}
__device__ __forceinline__ void wgmma64h_init(uint32_t* d, uint32_t a0, uint32_t a1, uint32_t a2, uint32_t a3, uint32_t dlo, uint32_t dhi) {
  asm volatile("{ .reg .b64 dd; mov.b64 dd, {%20, %21}; wgmma.mma_async.sync.aligned.m64n64k16.f16.f16.f16 "
               "{%0,%1,%2,%3,%4,%5,%6,%7,%8,%9,%10,%11,%12,%13,%14,%15}, {%16,%17,%18,%19}, dd, 0, 1, 1, 0; }"
               : "=r"(d[0]), "=r"(d[1]), "=r"(d[2]), "=r"(d[3]), "=r"(d[4]), "=r"(d[5]), "=r"(d[6]), "=r"(d[7]), "=r"(d[8]), "=r"(d[9]), "=r"(d[10]), "=r"(d[11]), "=r"(d[12]), "=r"(d[13]), "=r"(d[14]), "=r"(d[15])
               : "r"(a0), "r"(a1), "r"(a2), "r"(a3), "r"(dlo), "r"(dhi));
}
__device__ __forceinline__ void wgmma40_ss(float* d, uint32_t alo, uint32_t blo, uint32_t hi) {
  asm volatile("{ .reg .b64 da, db; mov.b64 da, {%20, %22}; mov.b64 db, {%21, %22}; "
               "wgmma.mma_async.sync.aligned.m64n40k16.f32.f16.f16 {%0,%1,%2,%3,%4,%5,%6,%7,%8,%9,%10,%11,%12,%13,%14,%15,%16,%17,%18,%19}, da, db, 1, 1, 1, 1, 1; }"
               : "+f"(d[0]), "+f"(d[1]), "+f"(d[2]), "+f"(d[3]), "+f"(d[4]), "+f"(d[5]), "+f"(d[6]), "+f"(d[7]), "+f"(d[8]), "+f"(d[9]), "+f"(d[10]), "+f"(d[11]), "+f"(d[12]), "+f"(d[13]), "+f"(d[14]), "+f"(d[15]), "+f"(d[16]), "+f"(d[17]), "+f"(d[18]), "+f"(d[19])
               : "r"(alo), "r"(blo), "r"(hi));
}
__device__ __forceinline__ void wgmma40_ss_init(float* d, uint32_t alo, uint32_t blo, uint32_t hi) {
  asm volatile("{ .reg .b64 da, db; mov.b64 da, {%20, %22}; mov.b64 db, {%21, %22}; "
               "wgmma.mma_async.sync.aligned.m64n40k16.f32.f16.f16 {%0,%1,%2,%3,%4,%5,%6,%7,%8,%9,%10,%11,%12,%13,%14,%15,%16,%17,%18,%19}, da, db, 0, 1, 1, 1, 1; }"
               : "=f"(d[0]), "=f"(d[1]), "=f"(d[2]), "=f"(d[3]), "=f"(d[4]), "=f"(d[5]), "=f"(d[6]), "=f"(d[7]), "=f"(d[8]), "=f"(d[9]), "=f"(d[10]), "=f"(d[11]), "=f"(d[12]), "=f"(d[13]), "=f"(d[14]), "=f"(d[15]), "=f"(d[16]), "=f"(d[17]), "=f"(d[18]), "=f"(d[19])
               : "r"(alo), "r"(blo), "r"(hi));
}
__device__ __forceinline__ float vzero() { float v; asm volatile("mov.b32 %0, 0;" : "=f"(v)); return v; }
__device__ __forceinline__ void tma_box(uint32_t dst, const CUtensorMap* tm, uint32_t mb, int x, int y) {
  asm volatile("cp.async.bulk.tensor.2d.shared::cluster.global.mbarrier::complete_tx::bytes [%0], [%1, {%3, %4}], [%2];"
               :: "r"(dst), "l"(tm), "r"(mb), "r"(x), "r"(y) : "memory");
}
__device__ __forceinline__ void l2_prefetch(const void* src, uint32_t bytes) {
  asm volatile("cp.async.bulk.prefetch.L2.global [%0], %1;" :: "l"(src), "r"(bytes) : "memory");
}
__device__ __forceinline__ uint32_t uni(uint32_t v) {
  uint32_t r; asm volatile("shfl.sync.idx.b32 %0, %1, 0, 0x1f, 0xffffffff;" : "=r"(r) : "r"(v)); return r;
}
__device__ __forceinline__ int fresh_tid() { int v; asm volatile("mov.u32 %0, %tid.x;" : "=r"(v)); return v; }

struct Params {
  const unsigned char* x;
  Scratch* s;
  int off[7];
  uint32_t zero;
  uint32_t* out;
  const uint32_t* dskip;
  const uint32_t* w_r;
  long long* ts;
  const unsigned char* far[7];
  uint32_t sched[2][17];
};
__device__ __forceinline__ uint32_t ldnc32(const void* p) { uint32_t v; asm volatile("ld.global.nc.b32 %0, [%1];" : "=r"(v) : "l"(p)); return v; }
__device__ __forceinline__ uint32_t ldnc16(const void* p) { uint16_t v; asm volatile("ld.global.nc.u16 %0, [%1];" : "=h"(v) : "l"(p)); return v; }
__device__ __forceinline__ uint4 ldnc128(const void* p) { uint4 v; asm volatile("ld.global.nc.v4.b32 {%0,%1,%2,%3}, [%4];" : "=r"(v.x), "=r"(v.y), "=r"(v.z), "=r"(v.w) : "l"(p)); return v; }
__device__ __forceinline__ void mbar_wait(uint32_t mb, uint32_t ph = 0) {
#pragma unroll 1
  for (int it = 0; it < SPIN_MAX; it++) {
    uint32_t ok;
    asm volatile("{ .reg .pred q; mbarrier.try_wait.parity.shared::cta.b64 q, [%1], %2; selp.u32 %0, 1, 0, q; }" : "=r"(ok) : "r"(mb), "r"(ph) : "memory");
    if (ok) break;
  }
}
__device__ __forceinline__ uint32_t mbar_test(uint32_t mb) {
  uint32_t ok;
  asm volatile("{ .reg .pred q; mbarrier.test_wait.parity.shared::cta.b64 q, [%1], 0; selp.u32 %0, 1, 0, q; }" : "=r"(ok) : "r"(mb) : "memory");
  return ok;
}
__device__ __forceinline__ void mbar_arrive(uint32_t mb) { asm volatile("mbarrier.arrive.shared::cta.b64 _, [%0];" :: "r"(mb) : "memory"); }
__device__ __forceinline__ uint32_t ldg16(const void* p) { uint16_t v; asm volatile("ld.global.u16 %0, [%1];" : "=h"(v) : "l"(p) : "memory"); return v; }
__device__ __forceinline__ uint32_t ldr16(const void* p) { uint16_t v; asm volatile("ld.relaxed.gpu.global.u16 %0, [%1];" : "=h"(v) : "l"(p) : "memory"); return v; }
__device__ __forceinline__ void fence_async() { asm volatile("fence.proxy.async.shared::cta;" ::: "memory"); }
#define SPIN_WHILE(cond, body) _Pragma("unroll 1") for (int _it = 0; _it < SPIN_MAX && __any_sync(0xffffffffu, (cond)); _it++) { body; }

struct LnC { uint32_t m2, rh2, rl2; };
__device__ __forceinline__ float diag_sum(float d0, float d1, int t) {
  float q = __shfl_sync(0xffffffffu, d0, 9 * t) + __shfl_sync(0xffffffffu, d1, 9 * t + 4);
  q += __shfl_xor_sync(0xffffffffu, q, 1);
  return q + __shfl_xor_sync(0xffffffffu, q, 2);
}
__device__ __forceinline__ LnC ln_consts(float s, float q, float& r) {
  const float mean = s * (1.f / DM);
  const float var = fmaxf(fmaf(-mean, mean, q * (1.f / DM)), 0.f);
  float sd;
  asm("sqrt.approx.ftz.f32 %0, %1;" : "=f"(sd) : "f"(bfr(bfr(var) + 1e-5f)));
  asm("rcp.approx.ftz.f32 %0, %1;" : "=f"(r) : "f"(bfr(sd)));
  LnC c;
  c.m2 = pack_bf(mean, mean);
  c.rh2 = pack_bf(r, r);
  const float rl = r - bf_lo(c.rh2);
  c.rl2 = pack_bf(rl, rl);
  return c;
}
__device__ __forceinline__ float quad_sum(float s) { s += __shfl_xor_sync(0xffffffffu, s, 1); return s + __shfl_xor_sync(0xffffffffu, s, 2); }
__device__ __forceinline__ uint32_t bf_fma2(uint32_t a, uint32_t b, uint32_t c) {
  __nv_bfloat162 r = __hfma2(*(const __nv_bfloat162*)&a, *(const __nv_bfloat162*)&b, *(const __nv_bfloat162*)&c);
  return *(uint32_t*)&r;
}
__device__ __forceinline__ uint32_t ln_apply(uint32_t w, uint32_t m2, uint32_t rh2, uint32_t rl2) {
  const uint32_t d = bf_sub2(w, m2);
  return bf_fma2(d, rh2, bf_mul2(d, rl2));
}

__device__ __forceinline__ float2 cis(float mag_log2, float rev) {
  const float m = ex2(mag_log2), ang = rev * 6.283185307179586f;
  return make_float2(m * __cosf(ang), m * __sinf(ang));
}
__device__ __forceinline__ float2 csq(float2 a) { return make_float2(fmaf(a.x, a.x, -a.y * a.y), (a.x + a.x) * a.y); }
__device__ __forceinline__ float2 cmul(float2 a, float2 b) { return make_float2(fmaf(a.x, b.x, -a.y * b.y), fmaf(a.x, b.y, a.y * b.x)); }
__device__ __forceinline__ void pmul(uint32_t xr, uint32_t xi, uint32_t w, uint32_t& yr, uint32_t& yi) {
  const __half2 XR = *(__half2*)&xr, XI = *(__half2*)&xi, W = *(__half2*)&w;
  const __half2 a = __hfma2(__hneg2(XI), __high2half2(W), __hmul2(XR, __low2half2(W)));
  const __half2 b = __hfma2(XI, __low2half2(W), __hmul2(XR, __high2half2(W)));
  yr = *(const uint32_t*)&a; yi = *(const uint32_t*)&b;
}
__device__ __forceinline__ uint32_t pk(float2 a) { return pack_h(a.x, a.y); }

struct KgState { float2 c0, z8; float kl; uint32_t w64, w128, w192; };
__device__ __forceinline__ void kgen_tables_n(const uint32_t (&raw)[7], uint32_t scr, int wt, KgState& k) {
  const uint32_t dst = scr + 16384 + wt * 16;
  const float dt = bfr(ex2(bf_lo(raw[6]) * 1.4426950408889634f));
  const float th = dt * bf_lo(raw[1]);
  const float br = dt * bf_lo(raw[2]), bi = dt * bf_lo(raw[3]);
  const float Cr = bf_lo(raw[4]), Ci = bf_lo(raw[5]);
  k.c0 = make_float2(fmaf(Cr, br, -Ci * bi), fmaf(Cr, bi, Ci * br));
  const uint32_t mx = __reduce_max_sync(0xffffffffu, __float_as_uint(fmaxf(fabsf(k.c0.x), fabsf(k.c0.y))));
  const float a2 = dt * bf_lo(raw[0]) * 1.4426950408889634f;
  const float rh = th * 0.15915494309189535f;
  const float rl = fmaf(th, (float)(0.15915494309189535 - (double)0.15915494309189535f), fmaf(th, 0.15915494309189535f, -rh));
  const float rf = rh - rintf(rh);
  const float2 z1 = cis(a2, rf + rl);
  const float p64 = rf * 64.f;
  const float2 z64 = cis(a2 * 64.f, fmaf(64.f, rl, p64 - rintf(p64)));
  const float2 z2 = csq(z1), z128 = csq(z64), z3 = cmul(z2, z1), z4 = csq(z2), z256 = csq(z128), z6 = csq(z3), z512 = csq(z256);
  k.z8 = csq(z4);
  k.w64 = pk(z64); k.w128 = pk(z128); k.w192 = pk(cmul(z128, z64));
  sts128(dst, 0x00003C00u, pk(z2), pk(z4), pk(z6));
  const float2 z1024 = csq(z512), z768 = cmul(z512, z256);
  sts128(dst + 2048, pk(z1), pk(z3), pk(cmul(z4, z1)), pk(cmul(z4, z3)));
  const float2 z2048 = csq(z1024);
  k.kl = fmaf(k.c0.x, z2048.x, -k.c0.y * z2048.y);
  sts128(dst + 4096, pk(z256), pk(cmul(z256, z2)), pk(cmul(z256, z4)), pk(cmul(z256, z6)));
  sts128(dst + 6144, pk(z512), pk(cmul(z512, z4)), pk(z768), pk(cmul(z768, z4)));
  sts128(dst + 8192, pk(z1024), pk(cmul(z1024, z256)), pk(cmul(z1024, z512)), pk(cmul(z1024, z768)));
  sts32(scr + W_MISC + (wt >> 5) * 4, mx);
}
__device__ __forceinline__ int kgen_tables_m(uint32_t scr, int wt, const KgState& k) {
  const uint32_t dst = scr + wt * 16;
  const uint4 e4 = lds128(scr + W_MISC);
  const float2 z16 = csq(k.z8), z32 = csq(z16);
  const int em = max(min((int)(max(max(e4.x, e4.y), max(e4.z, e4.w)) >> 23), 238), 16);
  const float sc = __uint_as_float((uint32_t)(127 + 4 + 127 - em) << 23);
  sts32(scr + W_MISC + 16 + (wt >> 5) * 4, __reduce_add_sync(0xffffffffu, __float2int_rn(k.kl * sc * 262144.f)));
  const float2 c0 = make_float2(k.c0.x * sc, k.c0.y * sc);
  const float2 c1 = cmul(c0, k.z8), c2 = cmul(c0, z16), c4 = cmul(c0, z32), c3 = cmul(c1, z16), c5 = cmul(c1, z32), c6 = cmul(c2, z32), c7 = cmul(c3, z32);
  uint32_t pr[4], pi[4], yr[4], yi[4];
  pr[0] = pack_h(c0.x, c1.x); pi[0] = pack_h(c0.y, c1.y);
  pr[1] = pack_h(c2.x, c3.x); pi[1] = pack_h(c2.y, c3.y);
  pr[2] = pack_h(c4.x, c5.x); pi[2] = pack_h(c4.y, c5.y);
  pr[3] = pack_h(c6.x, c7.x); pi[3] = pack_h(c6.y, c7.y);
  sts128(dst, pr[0], pr[1], pr[2], pr[3]); sts128(dst + 2048, pi[0], pi[1], pi[2], pi[3]);
#pragma unroll
  for (int q = 1; q < 4; q++) {
    const uint32_t w = q == 1 ? k.w64 : q == 2 ? k.w128 : k.w192;
#pragma unroll
    for (int i = 0; i < 4; i++) pmul(pr[i], pi[i], w, yr[i], yi[i]);
    sts128(dst + q * 4096, yr[0], yr[1], yr[2], yr[3]); sts128(dst + q * 4096 + 2048, yi[0], yi[1], yi[2], yi[3]);
  }
  return em;
}
__device__ __forceinline__ void kgen_build(uint32_t tb, uint32_t sc, int wg, int wt, uint32_t k0, uint32_t k1, uint32_t k2) {
  const uint32_t kt = tb + W_KT;
  const int ix = ((wt >> 2) + (wt & 3) * 32 - 1) & 127;
  const uint32_t a3 = tb + W_CW + 32 + ((ix & 1) ? 0 : 304) + (ix >> 1) * 4;
  const uint32_t v3 = wt ? k2 : k2 >> 16;
  sts32(sc + 4 + wt * 4, __byte_perm(k0, k1, 0x5432));
  sts16(sc + 544 + (wt & ~3) + (wt & 1) * 2 + (wt & 2) * 64, k1 >> 16);
  sts16(a3, v3); sts16(a3 + 6, v3);
  if ((unsigned)(wt - 32) < 18u) sts128(kt + (wt < 36 ? -512 : 64 + 4128 - 576) + wt * 16, 0, 0, 0, 0);
  if (wt == 127) sts32(sc, k0 & 0xFFFF0000u);
  if (wt == 0) { sts32(sc + 516, k1); sts16(sc + 800, k2); }
  bar_sync(1 + wg, 128);
  const uint32_t cw = tb + W_CW + 32 + (wt >> 6) * 48 + wt * 4;
  const uint32_t pv = lds32(sc + wt * 4), nx = lds32(sc + 8 + wt * 4), c2 = lds16(sc + 544 + wt * 2), n2 = lds16(sc + 546 + wt * 2);
  sts128(tb + W_L3 + 1024 + (wt >> 6) * 1024 + wt * 16, lds32(cw), lds32(cw - 8), lds32(cw - 16), lds32(cw - 24));
  const bool odd = wt & 1;
  sts64(kt + 64 + wt * 8, __byte_perm(k0, pv, 0x5410), __byte_perm(k0, 0, 0x1032));
  sts64(kt + 64 + 1024 + wt * 8, __byte_perm(k1, pv, (odd || wt == 0) ? 0x7610 : 0x1010), __byte_perm(k1, nx, odd ? 0x1076 : 0x1010));
  const uint32_t cc = c2 * 0x10001u, nc = __byte_perm(n2, c2, 0x5410), nn = n2 * 0x10001u;
  sts128(kt + 64 + 2048 + wt * 16, cc, cc, odd ? nc : cc, odd ? nn : nc);
  if (wt == 127) { sts128(kt + 64 + 4096, nn, nn, nn, nn); sts128(kt + 64 + 4112, nn, nn << 16, 0, 0); }
}

__device__ __forceinline__ void load_a(uint32_t (&a)[4], uint32_t kp, int j) {
  a[0] = lds32(kp + 64 * j); a[1] = lds32(kp + 64 * j + 512); a[2] = lds32(kp + 64 * j - 32); a[3] = lds32(kp + 64 * j + 480);
}
__device__ __forceinline__ uint32_t band(int d, int lo, int hi) {
  return ((unsigned)(d - lo) <= (unsigned)(hi - lo) ? 1u : 0u) | ((unsigned)(d - 1 - lo) <= (unsigned)(hi - lo) ? 0x10000u : 0u);
}
__device__ __forceinline__ uint32_t hadd2u(uint32_t a, uint32_t b) { __half2 r = __hadd2(*(__half2*)&a, *(__half2*)&b); return *(uint32_t*)&r; }

__device__ __forceinline__ void zero_pads(uint32_t tb, int wt) {
  sts128(tb + W_L3 + (wt >> 6) * 1024 + wt * 16, 0, 0, 0, 0);
  if ((wt & 63) < 3) sts128(tb + W_CW + (wt >> 6) * 304 + (wt & 63) * 16, 0, 0, 0, 0);
}
__device__ __forceinline__ uint32_t tr_base(int lane) {
  return OFF_YT + (2 * (lane >> 3) + (lane & 1)) * YT_PITCH + ((lane >> 1) & 1) * (8 * YT_PITCH + 64) + ((lane >> 2) & 1) * 16;
}

__device__ __forceinline__ uint32_t sc_addr(int tp) { return OFF_YT + (tp < 16 ? tp * YT_PITCH + (tp >> 3) * 64 + 1152 : 8 * YT_PITCH - 512 + tp * 32); }
#define X_NE 3
#define X_SCT 10000
#define X_DELTA 600
#define X_DSTEP 800
#define X_PF0 3000
#define X_PFD 600
#define X_TD 520
#define X_ORD 0
#define X_WS 6
#define X_OR 8
#define X_ABS 5300
#define X_XD 0
#define X_RD 850
#define X_HD 700
#define X_PD 1150
#define X_HU 14
#define X_GF 0
#define X_PROMO 2
#define X_YD2 500
#define X_GO 2
#define X_GW 2
#define X_LAG 1300
#define X_YD 1200
struct TMaps { CUtensorMap m[8]; };
__device__ __forceinline__ uint32_t h2bf(uint32_t w) { const float2 f = h2f(w); return pack_bf(f.x, f.y); }
__device__ __forceinline__ uint32_t keep(uint32_t v) { asm volatile("" : "+r"(v)); return v; }
__device__ __forceinline__ uint2 ldr64(const void* p) { uint2 v; asm volatile("{ .reg .b64 t; ld.relaxed.gpu.global.b64 t, [%2]; mov.b64 {%0, %1}, t; }" : "=r"(v.x), "=r"(v.y) : "l"(p) : "memory"); return v; }
__host__ __device__ __forceinline__ uint32_t down_box(int s, bool five) {
  return five ? OFF_W + W_BYTES + 12288 + (s / 3) * (W_BYTES - 12288) + s * 4096 : s < 6 ? OFF_W + W_BYTES + BOX + (s >> 1) * (W_BYTES - 10240) + s * 5120 : OFF_W + (s - 6) * 5120;
}
__device__ __forceinline__ void load_tile(const CUtensorMap* tmx, int i, int c) {
  asm volatile("mbarrier.arrive.expect_tx.shared::cta.b64 _, [%0], 5120;" :: "r"(MB_UL + i * 8) : "memory");
  tma_box(OFF_W + (i < 4 ? i * W_BYTES : ALT) + W_UP, tmx, MB_UL + i * 8, (i < 4 ? i * 128 + c : 512 + (c >> 1)) * 16, -32);
}
template <bool FAR> __device__ __forceinline__ void load_params(const Params& p, uint32_t ch, int wt, uint32_t dst, bool on) {
  const int o01 = (wt & 16) ? p.off[1] : p.off[0], o23 = (wt & 16) ? p.off[3] : p.off[2], o45 = (wt & 16) ? p.off[5] : p.off[4];
  const int o = (wt & 64) ? ((wt & 32) ? p.off[6] : o45) : ((wt & 32) ? o23 : o01);
  const unsigned char* b = FAR ? p.far[min(wt >> 4, 6)] : p.x + (long long)o * 16;
  asm volatile("{ .reg .pred q; setp.ne.u32 q, %2, 0; @q cp.async.cg.shared.global [%0], [%1], 16; }"
               :: "r"(dst + wt * 16), "l"(b + (wt < 96 ? ch * 256 + (wt & 15) * 16 : (ch >> 3) * 16)), "r"((uint32_t)(on && wt < 97)) : "memory");
}

struct ConvC { uint32_t ca, cb, bands; };
__device__ __forceinline__ ConvC conv_consts(int w, int lane) {
  const int h = w & 1, P = w >> 1, d0 = 8 * h + (lane >> 2) - 2 * (lane & 3);
  ConvC k;
  k.ca = keep((W_KT + (16 + 256 * P + d0) * 4) | ((W_UP + (32 + 64 * P + lane) * 32 + ((h ^ (lane >> 2)) & 1) * 16) << 16));
  k.cb = keep(lane < 8 ? 0xFFFEFFFEu : ~0u);
  k.bands = keep(band(d0, 12, 20) + 2 * band(d0 + 8, 12, 20) + 4 * band(d0 + 16, 12, 20) + 8 * band(d0 + 24, 12, 20)
                 + 16 * band(d0 - 8, 5, 11) + 32 * band(d0, 5, 11) + 64 * band(d0 + 8, 5, 11) + 128 * band(d0 + 16, 5, 11));
  return k;
}
__device__ __forceinline__ void conv_item(uint32_t tb, const ConvC& cv, uint32_t zero, const CUtensorMap* tmx, int ch, int warp, int lane, bool hold, bool more) {
  const bool go = more && warp == 0 && lane == 0;
  const uint32_t kp = tb + (cv.ca & 0xFFFFu);
  const uint32_t dlo = ((tb + W_UP) >> 4) + 64 + (1u << 16), dhi = 16u | (3u << 30);
  const bool P = warp & 2;
  float a32[16], a96[48];
  uint32_t A[40][4];
#define STEP(J) { wgmma96<0>(a96, A[J], dlo + 64 - 2 * (J), dhi); if ((J) == 0) wgmma32_init<0>(a32, A[J], dlo, dhi); else if ((J) < 8) wgmma32<0>(a32, A[J], (dlo ^ zero) - 2 * (J), dhi); }
#define LD(J) load_a(A[J], kp, J);
#define FIRST(J) wg_fence(); STEP(J) wg_commit(); wg_wait<1>(); wg_fence();
  {
    uint32_t win[16], x9[4], x7[4], e[4], f[4];
    const uint32_t bz = keep(cv.bands);
#define BAND(i) keep((bz & (0x10001u << (i))) * (0x3C00u >> (i)))
    e[0] = lds32(kp + (P ? 3232 : 4096)); e[2] = lds32(kp + (P ? 3200 : 4064)); e[1] = keep(bz & 0x100u); e[3] = keep(bz & 0x200u);
    f[3] = lds32(kp + (P ? 3200 : 4128)); f[0] = keep(bz & 0x4000u); f[1] = keep(bz & 0x8000u); f[2] = keep(bz & 0x300u);
    const uint32_t q[12] = {BAND(0), BAND(5), keep(bz & 0x400u), BAND(4), BAND(2), BAND(7), BAND(1), BAND(6), keep(bz & 0x800u), keep(bz & 0x1000u), BAND(3), keep(bz & 0x2000u)};
#undef BAND
    const uint32_t ta = keep(tb + W_UP + 1024 + (warp & 3) * 1024 + lane * 32 + (lane & 4) * 4);
    if (X_GO && hold) mbar_wait(MB_GO);
#pragma unroll 1
    for (int it = 0; it < SPIN_MAX; it++) {
      if (ch < 512) mbar_wait(MB_UL + (warp >> 2) * 8, it & 1);
      if (it == 1) TS(13);
      TS(3);
      wg_fence();
      wgmma64h_init(win, q[0], q[1], q[2], q[3], dlo, dhi);
      wgmma64h(win, q[4], q[5], q[6], q[7], dlo - 2, dhi);
      wgmma64h(win, q[8], q[9], q[10], q[11], dlo - 4, dhi);
      wg_commit();
      wgmma96_init<0>(a96, e, dlo - 64, dhi);
      wgmma96<0>(a96, f, dlo - 50, dhi);
      wg_commit();
      if (ch >= 512) break;
      uint32_t r0, r1, r2, r3, ok;
      ldsm4(ta, r0, r1, r2, r3);
      asm volatile("{ .reg .pred q; setp.ne.u32 q, %1, 0; barrier.red.and.pred q, %2, 128, q; selp.u32 %0, 1, 0, q; }" : "=r"(ok) : "r"((r0 & r1 & r2 & r3 & 1u) | (lane & 3)), "r"(1 + (warp >> 2)) : "memory");
      if (ok) break;
      wg_wait<0>();
      if ((warp & 3) == 0 && lane == 0) load_tile(tmx - 1, warp >> 2, ch & 127);
    }
    wg_wait<1>();
#pragma unroll
    for (int i = 0; i < 4; i++) {
      const int tl = 2 * ((i & 1) + ((i & 2) ? 0 : 4));
      x9[i] = P ? win[tl + 4] : win[tl]; x7[i] = P ? win[tl + 5] : win[tl + 1];
    }
    const uint32_t l3lo = ((tb + W_L3) >> 4) + (32u << 16);
    wg_fence();
    wgmma96<0>(a96, x9, l3lo, 8);
    wgmma96<0>(a96, x7, l3lo + 128, 8);
    wg_commit();
  }
  LD(32) LD(33) LD(34) LD(35)
  FIRST(32) STEP(33) STEP(34) STEP(35) wg_commit();
  LD(36) LD(37) LD(38)
  FIRST(36) STEP(37) STEP(38) wg_commit();
  LD(39) LD(0)
  TS(17);
  if (X_GO == 1 && go) mbar_arrive(MB_GO);
  FIRST(39) STEP(0) wg_commit();
  LD(1) LD(2) LD(3)
  FIRST(1) STEP(2) STEP(3) wg_commit();
  LD(4) LD(5)
  if (X_GO == 2 && go) mbar_arrive(MB_GO);
  FIRST(4) STEP(5) wg_commit();
  LD(6) LD(7)
  wg_fence(); STEP(6) STEP(7) wg_commit();
#undef STEP
#undef LD
#undef FIRST
  TS(18);
  if (X_GO == 3 && go) mbar_arrive(MB_GO);
  const uint32_t xc = tb + W_KT + (warp & 3) * 1024 + lane * 16;
  wg_wait<0>();
  uint32_t E[16], o[8];
#define ACC(i) ((i) < 16 ? a32[i] : a96[(i) - 16])
  E[0] = pack_h(a32[0], a32[1]);
#pragma unroll
  for (int i = 1; i < 16; i++) E[i] = pack_h(ACC(4 * i) + ACC(4 * i - 2), ACC(4 * i + 1) + ACC(4 * i - 1));
#undef ACC
#pragma unroll
  for (int j = 0; j < 8; j++) o[j] = P ? (j < 2 ? 0u : E[j - 2]) : E[8 + j];
  sts128(xc, o[0], o[1], o[2], o[3]); sts128(xc + 512, o[4], o[5], o[6], o[7]);
#pragma unroll
  for (int j = 0; j < 8; j++) o[j] = P ? E[6 + j] : E[j];
  TS(25);
  if (more) {
    sts128(xc + 4096, o[0], o[1], o[2], o[3]); sts128(xc + 4608, o[4], o[5], o[6], o[7]);
    bar_arrive(12, 192);
    return;
  }
  bar_sync(1 + (warp >> 2), 128);
  const uint4 vv[2] = {lds128(xc + (P ? -2048 : 2048)), lds128(xc + (P ? -1536 : 2560))};
#pragma unroll
  for (int q = 0; q < 2; q++) {
    const uint4 v = vv[q];
    stsm4t(tb + (cv.ca >> 16) + q * 1024, hadd2u(o[4 * q], v.x) & cv.cb, hadd2u(o[4 * q + 1], v.y) & cv.cb, hadd2u(o[4 * q + 2], v.z) & cv.cb, hadd2u(o[4 * q + 3], v.w) & cv.cb);
  }
  fence_async();
  bar_sync(1 + (warp >> 2), 128);
  if (warp == 0 && lane == 0) mbar_arrive(MB_REL);
  if ((warp & 3) == 3 && lane == 0) {
    asm volatile("cp.async.bulk.tensor.2d.global.shared::cta.bulk_group [%0, {%2, %3}], [%1];" :: "l"(tmx), "r"(tb + W_UP + 1024), "r"(ch * 16), "r"(0) : "memory");
    asm volatile("cp.async.bulk.commit_group;" ::: "memory");
  }
}

template <bool FAR> __global__ void __launch_bounds__(NT, 1)
fused_kernel(const __grid_constant__ Params p, const __grid_constant__ TMaps tm) {
  extern __shared__ __align__(1024) unsigned char smem[];
  const int c = blockIdx.x;
  const bool five = (c & 1) == 0;
  const uint32_t pitch = five ? 64 : 80;
  const uint32_t ones = 0x3F803F80u;
  const int tid = threadIdx.x, lane = tid & 31;
  {
    const int w4 = tid >> 7, k5 = !five && w4 == 3;
    load_params<FAR>(p, k5 ? 512 + (c >> 1) : w4 * 128 + c, tid & 127, OFF_W + w4 * W_BYTES + W_KT + k5 * 2048, w4 != 2 && w4 != 4);
  }
  const int warp = (int)uni(tid >> 5), wg = warp >> 2;
  TS(0);
  if (__builtin_expect(wg == 4, 0)) {
    asm volatile("setmaxnreg.dec.sync.aligned.u32 32;");
    const int role = warp;
    const int u0 = (c >> 1) * 9 + (five ? ((c & 2) ? 5 : 0) : ((c & 2) ? 0 : 4));
    const uint32_t t0 = clock() + c * 4;
    if (role == 16) {
      if (lane < 19) asm volatile("mbarrier.init.shared::cta.b64 [%0], %1;" :: "r"(OFF_MISC + lane * 8), "r"((unsigned)(lane - 2) < 4u ? 4 : 1) : "memory");
      if (lane < 2) asm volatile("mbarrier.arrive.expect_tx.shared::cta.b64 _, [%0], %1;" :: "r"(OFF_MISC + lane * 8), "r"(lane ? (five ? 36864 : 51200) : pitch * 1152) : "memory");
      fence_async();
      bar_arrive(5, 576);
      const CUtensorMap* tmb = &tm.m[five ? 3 : 0];
#pragma unroll 1
      for (int u = 0; u < 17; u++) {
        const uint32_t e = p.sched[five][u], kind = e & 3, s = (e >> 2) & 15, dst = e >> 14;
        if (kind == 3) continue;
        while ((int)(clock() - t0) < X_PF0 + (u < X_NE ? u * X_PFD : X_LAG + u * X_TD)) __nanosleep(20);
        if (e & 0x3FC0) mbar_wait(OFF_MISC + ((e >> 6) & 255));
        if (lane == 0) {
          if (kind == 2) asm volatile("cp.async.bulk.tensor.3d.shared::cluster.global.mbarrier::complete_tx::bytes [%0], [%1, {%3, %4, %5}], [%2];"
                                      :: "r"(dst), "l"(tmb + 2), "r"(MB_D), "r"(0), "r"(u0 * 8), "r"(s) : "memory");
          else tma_box(dst, tmb + kind, MB_GU, u0 * 8, s * 96);
        }
        if (u == 5) TS(2);
        if (u == 10) TS(3);
      }
      TS(4);
      TS_DUMP();
#define FINISH0 bar_sync(12, 192);        \
        _Pragma("unroll 1") for (int w = role & 2; w < (role & 2) + 2; w++) { \
          const uint32_t xa = OFF_W + W_KT + lane * 16, mk = lane < 8 ? 0xFFFEFFFEu : ~0u, ya = OFF_W + W_UP + (32 + lane) * 32 + ((w ^ (lane >> 2)) & 1) * 16 + (w & 2) * 1024; \
          const uint4 a = lds128(xa + 4096 + w * 1024), b = lds128(xa + (w ^ 2) * 1024), d = lds128(xa + 4608 + w * 1024), e = lds128(xa + 512 + (w ^ 2) * 1024); \
          stsm4t(ya, hadd2u(a.x, b.x) & mk, hadd2u(a.y, b.y) & mk, hadd2u(a.z, b.z) & mk, hadd2u(a.w, b.w) & mk); \
          stsm4t(ya + 1024, hadd2u(d.x, e.x) & mk, hadd2u(d.y, e.y) & mk, hadd2u(d.z, e.z) & mk, hadd2u(d.w, e.w) & mk); \
        } \
        fence_async();
    } else if (role == 17) {
      if (smem_u32(smem) != SB) __trap();
      if (five) { FINISH0 bar_arrive(13, 64); }
    } else if (role == 18) {
      sts32(MISC_EPOCH, 0);
      bar_arrive(5, 576);
      uint4* q = lane < 2 ? &p.s->R[c * 2 + lane] : lane < 11 ? &p.s->HS[c * 9 + lane - 2] : lane == 11 ? &p.s->HS[1152 + (c & 7)] : (uint4*)&p.s->FLAG[c * 8];
      if (lane < (c < 8 ? 12 : 11)) str128(q, ~0u, ~0u, ~0u, ~0u);
      const uint32_t ep = __shfl_sync(0xffffffffu, ldr32(q), 31) + 1u;
      sts32(MISC_EPOCH, ep | 0x80000000u);
      TSX(21);
      if (lane == 31) str32(q, ep);
      bar_sync(11, 64);
      if (lane == 0) load_tile(&tm.m[6], 3, c);
      TSX(14);
      mbar_wait(MB_KF + (lane & 3) * 8);
      __syncwarp();
      { const uint2 e = lds64(MISC_EM); if (lane < 2) str128(&p.s->SC[c * 2 + lane], e.x, __byte_perm(e.y, ep, 0x6540), 0, 0); }
      TSX(17);
      while ((int)(clock() - t0) < X_SCT) __nanosleep(100);
      TSX(18);
      {
        uint2 v[4];
#pragma unroll 1
        for (int it = 0; it < SPIN_MAX; it++) {
          uint32_t bad = 0;
#pragma unroll
          for (int q = 0; q < 4; q++) v[q] = ldr64(&p.s->SC[lane * 2 + q * 64]);
#pragma unroll
          for (int q = 0; q < 4; q++) bad |= (v[q].y >> 8) ^ (ep & 0xFFFFFFu);
          if (!__any_sync(0xffffffffu, bad)) break;
        }
        TSX(25);
#pragma unroll
        for (int q = 0; q < 4; q++) {
#pragma unroll
          for (int k = 0; k < 4; k++) asm volatile("st.shared.u8 [%0], %1;" :: "r"(sc_addr(4 * k + q) + lane), "r"(v[q].x >> (8 * k)) : "memory");
          if (lane & 1) asm volatile("st.shared.u8 [%0], %1;" :: "r"(sc_addr(16) + q * 16 + (lane >> 1)), "r"(v[q].y) : "memory");
        }
      }
      __syncwarp();
      if (lane == 0) mbar_arrive(MB_SC);
      TSX(27);
    } else {
      uint32_t w[9], d[9];
      float s = 0.f;
#pragma unroll
      for (int i = 0; i < 9; i++) { w[i] = ldnc32(p.w_r + (i < 8 ? lane * 4 + (i & 3) + (i >> 2) * 128 : 256 + lane)); d[i] = ldnc32(p.dskip + lane + 32 * i); }
#pragma unroll
      for (int i = 0; i < 9; i++) { sts32(OFF_WR + lane * 4 + i * 128, w[i]); sts32(OFF_WR + 1152 + lane * 4 + i * 128, d[i]); s += bf_lo(w[i]) + bf_hi(w[i]); }
      sts32(MISC_SW, __float_as_uint(warp_sum(s)));
      TSX(23);
      bar_sync(10, 544);
      if (lane == 0) {
        const uint32_t tp = clock();
        TSX(1);
        while ((int)(clock() - tp) < X_DELTA || (int)(clock() - t0) < X_ABS - c * 4) {}
        TSX(24);
        load_tile(&tm.m[6], 0, c);
        TSX(15);
        load_tile(&tm.m[6], 1, c);
        if (X_GF) mbar_arrive(MB_GF);
        while ((int)(clock() - t0) < X_ABS + X_DSTEP - c * 4) {}
      }
      bar_sync(11, 64);
      if (lane == 0) {
        load_tile(&tm.m[6], 2, c);
        if (!X_GF) mbar_arrive(MB_GF);
      }
      if (five) {
        mbar_wait(MB_KF);
#pragma unroll 1
        for (int it = 0; it < SPIN_MAX; it++) {
          if (lane == 0) load_tile(&tm.m[6], 4, c);
          mbar_wait(MB_UL + 32, it & 1);
          uint32_t m = 1;
#pragma unroll
          for (int q = 0; q < 4; q++) { uint32_t r0, r1, r2, r3; ldsm4(OFF_W + ALT + W_UP + 1024 + lane * 32 + (lane & 4) * 4 + q * 1024, r0, r1, r2, r3); m &= r0 & r1 & r2 & r3; }
          if (__all_sync(0xffffffffu, m || (lane & 3))) break;
        }
        bar_arrive(7, 288);
        FINISH0
        bar_sync(13, 64);
        if (lane == 0) {
          asm volatile("cp.async.bulk.tensor.2d.global.shared::cta.bulk_group [%0, {%2, %3}], [%1];" :: "l"(&tm.m[7]), "r"(OFF_W + W_UP + 1024), "r"(c * 16), "r"(0) : "memory");
          asm volatile("cp.async.bulk.commit_group;" ::: "memory");
          asm volatile("cp.async.bulk.wait_group.read 0;" ::: "memory");
        }
      }
      uint4* rp = &p.s->R[c * 2 + (lane & 1)];
      asm volatile("" : "+l"(rp));
      bar_sync(0, 544);
      if (lane == 0) mbar_arrive(MB_H);
      bar_sync(5, 544);
      const uint4 k = lds128(MISC_RK + (lane & 1) * 16);
      if (lane < 2) str128(rp, k.x, k.y, k.z, k.w);
    }
    return;
  }
  const int wt = tid & 127, g = lane >> 2, t = lane & 3;
  const uint32_t wb = OFF_W + wg * W_BYTES;
  const uint32_t xrow = OFF_YT + (wt >> 3) * YT_PITCH + (wt & 64) + (lane & 7) * 16;
  if (wg == 2) {
    const unsigned char* xp = p.x + (uint32_t)((c * 16 + (wt >> 3)) * 1152 + (lane & 7) * 16);
    { const uint32_t tq = clock(); while ((int)(clock() - tq) < X_XD) {} }
#pragma unroll
    for (int k = 0; k < 9; k++) asm volatile("cp.async.cg.shared.global [%0], [%1], 16;" :: "r"(xrow + k * 128), "l"(xp + k * 128) : "memory");
  }
  asm volatile("cp.async.commit_group;" ::: "memory");
  const ConvC cv = conv_consts(warp & 3, lane);
  zero_pads(wb, wt);
  load_params<FAR>(p, wg * 128 + c, wt, wb + W_KT, wg == 2 || (wg == 3 && !five));
  asm volatile("cp.async.commit_group;" ::: "memory");
  asm volatile("setmaxnreg.inc.sync.aligned.u32 112;");
  {
    uint4 kw;
    uint4* kx = &p.s->KX[(c >> 1) * 128 + wt];
    bool two = wg == 3;
    uint32_t ep;
    int phase = wg == 2 ? 3 : 2;
#pragma unroll 1
    for (;;) {
      const bool first = two && !five;
      if (phase) asm volatile("cp.async.wait_group 1;" ::: "memory"); else asm volatile("cp.async.wait_group 0;" ::: "memory");
      if (phase == 3) {
        TS(21);
        float d[3][4], r;
        uint4 a[9];
#pragma unroll
        for (int k = 0; k < 9; k++) a[k] = lds128(xrow + k * 128);
#pragma unroll
        for (int i = 0; i < 4; i++) d[0][i] = d[1][i] = d[2][i] = 0.f;
#pragma unroll
        for (int k = 0; k < 9; k++) { mma_bf16(d[(2 * k) % 3], a[k].x, ones, a[k].y, ones, a[k].x, a[k].y); mma_bf16(d[(2 * k + 1) % 3], a[k].z, ones, a[k].w, ones, a[k].z, a[k].w); }
#pragma unroll
        for (int i = 0; i < 4; i++) d[0][i] += d[1][i] + d[2][i];
        const LnC lc = ln_consts(d[0][2] + d[0][3], __shfl_sync(0xffffffffu, d[0][0], 9 * t) + __shfl_sync(0xffffffffu, d[0][1], 9 * t + 4), r);
        if (lane < 12) sts16(MISC_LN1 + g * 32 + (warp & 3) * 8 + t * 2, lane < 4 ? lc.m2 : lane < 8 ? lc.rh2 : lc.rl2);
      } else {
        KgState ks;
        uint32_t raw[7];
        bar_sync(1 + wg, 128);
        TS(22);
#pragma unroll
        for (int i = 0; i < 7; i++) raw[i] = lds16(wb + W_KT + first * 2048 + i * 256 + (i < 6 ? wt : (c >> first) & 7) * 2);
        kgen_tables_n(raw, wb, wt, ks);
        TS(20);
        bar_sync(1 + wg, 128);
        const int em = kgen_tables_m(wb, wt, ks);
        asm volatile("st.shared.u8 [%0], %1;" :: "r"(MISC_EM + wg + first), "r"(em + 9) : "memory");
        fence_async();
      }
      if (phase & 2) {
        const uint32_t tr_addr = tr_base(lane) + warp * 32;
        uint4* dst = &p.s->X[c * DM * 2 + warp * 32 + (8 * (t >> 1) + g) * 2 + (t & 1)];
        TS(23);
        bar_sync(5, 576);
        uint32_t x[3][4];
        ldsm4t(tr_addr, x[0][0], x[0][1], x[0][2], x[0][3]);
        const uint4 m = lds128(MISC_LN1 + (t & 1) * 16), rl = lds128(MISC_LN1 + 64 + (t & 1) * 16), rh = lds128(MISC_LN1 + 32 + (t & 1) * 16);
        ldsm4t(tr_addr + 512, x[1][0], x[1][1], x[1][2], x[1][3]);
        if (wg == 1) ldsm4t(tr_addr + 896, x[2][0], x[2][1], x[2][2], x[2][3]);
#pragma unroll
        for (int q = 0; q < 3; q++) {
          if (q < 2 || wg == 1) {
            const uint32_t r0 = ln_apply(x[q][0], m.x, rh.x, rl.x), r1 = ln_apply(x[q][1], m.y, rh.y, rl.y), r2 = ln_apply(x[q][2], m.z, rh.z, rl.z), r3 = ln_apply(x[q][3], m.w, rh.w, rl.w);
            str128(dst + q * 512 - (q == 2 ? 128 : 0), (pack_h(bf_lo(r0), bf_hi(r0)) & 0xFFFEFFFEu) | 1u, pack_h(bf_lo(r1), bf_hi(r1)), pack_h(bf_lo(r2), bf_hi(r2)), pack_h(bf_lo(r3), bf_hi(r3)));
          }
          if (q == 0) { TS(30); bar_arrive(10, 544); }
        }
        TS(1);
      } else bar_sync(1 + wg, 128);
      phase &= 1;
      if (phase) { phase = 0; continue; }
      TS(14);
      float acc[20];
      const uint32_t alo = (wb >> 4) | (8u << 16);
      wg_fence();
      wgmma40_ss_init(acc, alo, alo + 1024, 2048 >> 4);
#pragma unroll
      for (int k = 1; k < 8; k++) wgmma40_ss(acc, alo + k * 16, alo + 1024 + k * 16, 2048 >> 4);
      wg_commit();
      const uint4 k4 = lds128(wb + W_MISC + 16);
      const float k2048 = (float)(int)(k4.x + k4.y + k4.z + k4.w) * (1.f / 262144.f);
      wg_wait<0>();
      const float un = 1.f / 8192.f;
      kw.x = pack_h((acc[0] - acc[3]) * un, (acc[4] - acc[7]) * un);
      kw.y = pack_h((acc[8] - acc[11]) * un, (acc[12] - acc[15]) * un);
      kw.z = pack_h((acc[16] - acc[19]) * un, k2048 * un);
      TS(24);
      ep = 0;
      if (two) SPIN_WHILE(ep == 0, ep = lds32(MISC_EPOCH));
      if (five || !two) break;
      str128(kx, kw.x, kw.y, kw.z, ep);
      two = false;
    }
    if (lane == 0) mbar_arrive(MB_KF + wg * 8);
    mbar_wait(MB_KF + wg * 8);
    if (two) { mbar_wait(MB_KF); zero_pads(OFF_W + ALT, wt); }
    uint32_t tb = wb;
#pragma unroll 1
    for (;;) {
      kgen_build(tb, (tb == wb ? wb : OFF_W + 16384 - 25600) + 25600, wg, wt, kw.x, kw.y, kw.z);
      TS(15);
      if (!two) break;
      two = false;
      kw.w = 0;
      SPIN_WHILE(kw.w != ep, kw = ldr128(kx));
      tb = OFF_W + ALT;
    }
    fence_async();
    TS(31);
    if (tb != wb) bar_arrive(7, 288);
    bar_sync(1 + wg, 128);
  }
  uint32_t tpub;
#pragma unroll 1
  for (int item = 0;; item++) {
    TS(2);
    conv_item(item ? OFF_W + ALT : wb, cv, p.zero, &tm.m[7], item ? 512 + (c >> 1) : wg * 128 + c, warp, lane, five && wg >= X_GW, five && !wg && !item);
    tpub = clock() - (item ? X_YD : wg >= 2 ? X_YD2 : 0);
    if (wg || !five || item) break;
    TS(27);
    bar_sync(7, 288);
  }
  TS(4);

  const int ln = lane ^ p.zero, td = warp * 32 + ln, gg = ln >> 2, tt = ln & 3;
  const int tok = c * 16 + warp;
  const int fu = warp / 3, fk = warp - fu * 3;
  uint32_t wa[12][4];
  {
    uint32_t hw[9], wr[9];
    const uint32_t row = keep(OFF_YT + warp * YT_PITCH + (warp >> 3) * 64 + ln * 16);
    const uint32_t wabase = keep(((ln & 8) ? OFF_W + (fk + 1) * W_BYTES : OFF_G + fk * 192 * pitch) + ((ln >> 4) * 8 + (ln & 7)) * pitch
                                 + (five ? ((fu ^ (ln >> 1)) & 3) : min(fu, 4)) * 16);
    float sw;
    {
      const bool three = wg == 1;
      const int ch = 8 * (tt >> 1) + gg;
      const uint32_t tr_addr = tr_base(ln);
      const uint4* ysrc = &p.s->X[c * DM * 2 + ch * 2 + (tt & 1)];
      uint32_t x[3][4], ud[3][4], s[3];
      uint4 v[3];
#define TL(q) ((q) < 2 ? 2 * warp + (q) : 28 + warp)
      asm volatile("cp.async.bulk.wait_group.read 0;" ::: "memory");
      while ((int)(clock() - tpub) < X_YD) {}
      TS(5);
      v[0] = ldr128(ysrc + TL(0) * 32); v[1] = ldr128(ysrc + TL(1) * 32); v[2] = make_uint4(three, 0, 0, 0);
      mbar_wait(MB_REL);
      const uint4 m = lds128(MISC_LN1 + (tt & 1) * 16), rh = lds128(MISC_LN1 + 32 + (tt & 1) * 16), rl = lds128(MISC_LN1 + 64 + (tt & 1) * 16);
#pragma unroll
      for (int i = 0; i < 9; i++) wr[i] = lds32(OFF_WR + ln * 4 + i * 128);
      sw = __uint_as_float(lds32(MISC_SW));
#pragma unroll
      for (int q = 0; q < 3; q++) {
        if (q < 2 || three) {
          const uint32_t dk = lds16(OFF_WR + 1152 + ch * 2 + TL(q) * 32) * 0x10001u;
          ldsm4t(tr_addr + TL(q) * 32, x[q][0], x[q][1], x[q][2], x[q][3]);
          ud[q][0] = bf_mul2(ln_apply(x[q][0], m.x, rh.x, rl.x), dk); ud[q][1] = bf_mul2(ln_apply(x[q][1], m.y, rh.y, rl.y), dk);
          ud[q][2] = bf_mul2(ln_apply(x[q][2], m.z, rh.z, rl.z), dk); ud[q][3] = bf_mul2(ln_apply(x[q][3], m.w, rh.w, rl.w), dk);
        }
      }
      mbar_wait(MB_SC);
#pragma unroll
      for (int q = 0; q < 3; q++) {
        asm volatile("ld.shared.u8 %0, [%1];" : "=r"(s[q]) : "r"((q < 2 ? sc_addr(warp) + q * 16 : sc_addr(16) + (warp & 3) * 16) + ch) : "memory");
        s[q] = keep(s[q] * 0x800080u);
      }
#define FIN(q) stsm4t(tr_addr + TL(q) * 32, bf_add2(x[q][0], bf_fma2(h2bf(v[q].x), s[q], ud[q][0])), bf_add2(x[q][1], bf_fma2(h2bf(v[q].y), s[q], ud[q][1])), \
                      bf_add2(x[q][2], bf_fma2(h2bf(v[q].z), s[q], ud[q][2])), bf_add2(x[q][3], bf_fma2(h2bf(v[q].w), s[q], ud[q][3])));
      SPIN_WHILE((v[0].x | v[1].x) & 1u, _Pragma("unroll") for (int q = 0; q < 3; q++) if (v[q].x & 1u) v[q] = ldr128(ysrc + TL(q) * 32));
      if (v[2].x & 1u) v[2] = ldr128(ysrc + TL(2) * 32);
      FIN(0) FIN(1)
      if (three) {
        SPIN_WHILE(v[2].x & 1u, if (v[2].x & 1u) v[2] = ldr128(ysrc + TL(2) * 32));
        FIN(2)
      }
#undef FIN
#undef TL
    }
    TS(28);
    bar_sync(0, 544);
    TS(6);
    float d[4] = {0.f, 0.f, 0.f, 0.f}, e[4] = {0.f, 0.f, 0.f, 0.f}, rd;
    {
      const uint4 a = lds128(row), b = lds128(row + 512);
      hw[8] = lds32(row + 1024 - ln * 12);
      hw[0] = a.x; hw[1] = a.y; hw[2] = a.z; hw[3] = a.w; hw[4] = b.x; hw[5] = b.y; hw[6] = b.z; hw[7] = b.w;
    }
    mma_bf16(e, hw[0], hw[1], hw[2], hw[3], ones, ones);
#pragma unroll
    for (int i = 0; i < 8; i += 2) mma_bf16(d, hw[i], wr[i], hw[i + 1], wr[i + 1], hw[i], hw[i + 1]);
    mma_bf16(e, hw[4], hw[5], hw[6], hw[7], ones, ones);
    e[0] += e[2];
    mma_bf16_k8(e, hw[8], wr[8], ones);
    mma_bf16_k8(d, hw[8], wr[8], hw[8]);
    const float hwsum = diag_sum(d[2], d[3], tt);
    LnC l2 = ln_consts(diag_sum(e[0], e[0], tt), diag_sum(d[0], d[1], tt), rd);
    const uint32_t b = pack_bf(0.f, fmaf(-bf_lo(l2.m2), sw, hwsum) * rd);
    uint32_t key = max(min((b ^ (((int)b >> 31) | 0x80000000u)) >> 16, 0xFFFEu), 1u);
    sts16(MISC_RK + warp * 2, key);
    bar_sync(5, 544);
    asm volatile("" : "+r"(l2.m2) :: "memory");
    TS(7);
    const uint32_t tr0 = clock();
    key = (key << 16) | (2047 - tok);
    uint32_t loc = ln < 16 ? (lds16(MISC_RK + ln * 2) << 16) | (2047 - c * 16 - ln) : 0u;
    int rank = __popc(__ballot_sync(0xffffffffu, loc > key));
#pragma unroll
    for (int i = 0; i < 9; i++) wr[i] = keep(ln_apply(hw[i], l2.m2, l2.rh2, l2.rl2));
    const uint2* rsrc = (const uint2*)p.s->R + td;
    uint2 rv = make_uint2(~0u, 0u);
    mbar_wait(MB_GU);
    if (warp < (five ? 12 : 15)) {
#pragma unroll
      for (int k = 0; k < X_WS; k++) ldsm4t(wabase + k * 16 * pitch, wa[k][0], wa[k][1], wa[k][2], wa[k][3]);
    }
#define OUT_ROW { uint32_t* o = p.out + tok * 288 + ln * 4; \
      *(uint4*)o = make_uint4(bf_add2(hw[0], wr[0]), bf_add2(hw[1], wr[1]), bf_add2(hw[2], wr[2]), bf_add2(hw[3], wr[3])); \
      *(uint4*)(o + 128) = make_uint4(bf_add2(hw[4], wr[4]), bf_add2(hw[5], wr[5]), bf_add2(hw[6], wr[6]), bf_add2(hw[7], wr[7])); \
      o[256 - ln * 3] = bf_add2(hw[8], wr[8]); }
    if (rank >= X_OR) OUT_ROW
#pragma unroll 1
    for (int base = 0; base < 8; base += 4) {
      uint32_t T[4];
#pragma unroll
      for (int j = 0; j < 4; j++) {
        const uint32_t mx = __reduce_max_sync(0xffffffffu, loc);
        if (loc == mx) loc = 0;
        T[j] = (td >> 2) == c ? ~0u : (td >> 2) < c ? (mx & 0xFFFF0000u) - 1u : mx | 0xFFFFu;
      }
      const uint32_t sh = keep(ln < 16 ? 0x4440u + (rank & 3) : 0x4344u), ca = keep(MISC_CNT + base * 16 + (ln & 15) * 4);
      while ((int)(clock() - tr0) < X_RD) {}
      SPIN_WHILE(rv.x == ~0u, if (rv.x == ~0u) rv = ldr64(rsrc));
      TS(16);
      uint32_t cnt = 0, cn2 = 0;
#pragma unroll
      for (int j = 0; j < 4; j++)
        asm("{ .reg .pred a, b, c, d; setp.gt.u32 a, %2, %6; setp.gt.u32 b, %3, %6; setp.gt.u32 c, %4, %6; setp.gt.u32 d, %5, %6; "
            "@a add.u32 %0, %0, %7; @b add.u32 %1, %1, %7; @c add.u32 %0, %0, %7; @d add.u32 %1, %1, %7; }"
            : "+r"(cnt), "+r"(cn2) : "r"(rv.x), "r"(rv.x << 16), "r"(rv.y), "r"(rv.y << 16), "r"(T[j]), "r"(1u << (8 * j)));
      sts32(MISC_CNT + base * 16 + warp * 4, __reduce_add_sync(0xffffffffu, cnt + cn2));
      bar_sync(0, 512);
      cnt = __reduce_add_sync(0xffffffffu, __byte_perm(lds32(ca), 0, sh));
      if ((rank & ~3) == base && rank + (int)(cnt & 0xFFFFu) < 8) {
        rank += cnt & 0xFFFFu;
        uint4* hs = p.s->HS + rank * 72 + ln;
        str128(hs, wr[0], wr[1], wr[2], wr[3]); str128(hs + 32, wr[4], wr[5], wr[6], wr[7]); str32((uint32_t*)(hs + 64) - ln * 3, wr[8]);
        str128(hs + 576, hw[0], hw[1], hw[2], hw[3]); str128(hs + 608, hw[4], hw[5], hw[6], hw[7]); str32((uint32_t*)(hs + 640) - ln * 3, hw[8]);
        if (ln == 0) str32(&p.s->HS[1152 + rank], key);
        rank = 16;
      }
      if (cnt >= (4u << 16)) break;
    }
    TS(8);
    tpub = clock();
    if (rank < X_OR) OUT_ROW
    if (warp < (five ? 12 : 15)) {
#pragma unroll
      for (int k = X_WS; k < 12; k++) ldsm4t(wabase + k * 16 * pitch, wa[k][0], wa[k][1], wa[k][2], wa[k][3]);
    }
  }
  uint32_t wd[10][4];
  const uint32_t xb = keep(OFF_XS + (ln & 7) * 1168 + (fk * 24 + (ln >> 3)) * 16);
  if (warp >= 7) {
    const uint32_t db = down_box(warp - 7, five) + (ln & 7) * 128;
    mbar_wait(MB_D);
#pragma unroll
    for (int j = 0; j < 4; j++) {
      const uint32_t a = db + (ln >> 4) * 1024 + (((2 * j + ((ln >> 3) & 1)) ^ (ln & 7)) << 4);
      ldsm4t(a, wd[j][0], wd[j][1], wd[j][2], wd[j][3]);
      ldsm4t(a + 2048, wd[4 + j][0], wd[4 + j][1], wd[4 + j][2], wd[4 + j][3]);
    }
#pragma unroll
    for (int j = 0; j < 2; j++) ldsm4t(db + 4096 + (((4 * j + (ln >> 3)) ^ (ln & 7)) << 4), wd[8 + j][0], wd[8 + j][1], wd[8 + j][2], wd[8 + j][3]);
  } else if (warp < 6) {
    const int r = td / 24;
    const uint4* src = &p.s->HS[td + r * 48];
    const uint32_t xs = keep(OFF_XS + (td + r * 49) * 16);
    uint4 a[3];
    uint32_t m = ~0u;
    while ((int)(clock() - tpub) < X_HD) {}
    TS(19);
    SPIN_WHILE(m == ~0u, if (m == ~0u) { a[0] = ldr128(src); a[1] = ldr128(src + 24); a[2] = ldr128(src + 48); } m = max(max(max(a[0].x, a[1].x), max(a[2].x, a[2].y)), max(a[2].z, a[2].w)));
#pragma unroll
    for (int q = 0; q < 3; q++) sts128(xs + q * 384, a[q].x, a[q].y, a[q].z, a[q].w);
  }
  bar_sync(0, 512);
  TS(9);

  if (warp < (five ? 12 : 15)) {
    float d0[4] = {0.f, 0.f, 0.f, 0.f}, d1[4] = {0.f, 0.f, 0.f, 0.f};
#pragma unroll
    for (int k = 0; k < 12; k += 2) {
      uint32_t b0, b1, b2, b3;
      ldsm4(xb + k * 32, b0, b1, b2, b3);
      mma_bf16(d0, wa[k][0], wa[k][1], wa[k][2], wa[k][3], b0, b1);
      mma_bf16(d1, wa[k + 1][0], wa[k + 1][1], wa[k + 1][2], wa[k + 1][3], b2, b3);
    }
    sts128(OFF_RED + td * 16, __float_as_uint(d0[0] + d1[0]), __float_as_uint(d0[1] + d1[1]), __float_as_uint(d0[2] + d1[2]), __float_as_uint(d0[3] + d1[3]));
  }
  TS(26);
  if (warp < 5) {
    const uint32_t rb = OFF_RED + warp * 1536 + ln * 16;
    bar_sync(9, 512);
    const uint4 pa = lds128(rb), pb = lds128(rb + 512), pc = lds128(rb + 1024);
    const float ga = bfr(__uint_as_float(pa.x) + __uint_as_float(pb.x) + __uint_as_float(pc.x));
    const float gb = bfr(__uint_as_float(pa.y) + __uint_as_float(pb.y) + __uint_as_float(pc.y));
    const uint32_t uu = pack_bf(__uint_as_float(pa.z) + __uint_as_float(pb.z) + __uint_as_float(pc.z), __uint_as_float(pa.w) + __uint_as_float(pb.w) + __uint_as_float(pc.w));
    float ra, rb2;
    asm("rcp.approx.ftz.f32 %0, %1;" : "=f"(ra) : "f"(1.f + ex2(ga * -1.4426950408889634f)));
    asm("rcp.approx.ftz.f32 %0, %1;" : "=f"(rb2) : "f"(1.f + ex2(gb * -1.4426950408889634f)));
    const uint32_t act = bf_mul2(pack_bf(ga * ra, gb * rb2), uu);
    sts32(OFF_ACT + td * 4, act);
  } else bar_arrive(9, 512);
  uint4* dst = &p.s->X[c * DM * 2 + (warp - 7) * 64 + tt * 8 + gg];
  asm volatile("" : "+l"(dst));
  bar_sync(8, 512);
  tpub = clock();
  if (warp >= 7) {
    uint32_t b0, b1, b2, b3, b4;
    ldsm4t(OFF_ACT + ln * 16, b0, b1, b2, b3);
    asm volatile("ldmatrix.sync.aligned.m8n8.x1.trans.shared.b16 {%0}, [%1];" : "=r"(b4) : "r"(OFF_ACT + 512 + ln * 16) : "memory");
    float y[4][4];
#pragma unroll
    for (int j = 0; j < 4; j++) {
      y[j][0] = y[j][1] = y[j][2] = y[j][3] = 0.f;
      mma_bf16(y[j], wd[j][0], wd[j][1], wd[j][2], wd[j][3], b0, b1);
    }
#pragma unroll
    for (int j = 0; j < 4; j++) mma_bf16(y[j], wd[4 + j][0], wd[4 + j][1], wd[4 + j][2], wd[4 + j][3], b2, b3);
    if (!five) {
#pragma unroll
      for (int j = 0; j < 4; j++) mma_bf16_k8(y[j], wd[8 + (j >> 1)][2 * (j & 1)], wd[8 + (j >> 1)][2 * (j & 1) + 1], b4);
    }
    str128(dst, (pack_bf(y[0][0], y[0][1]) & ~1u) | 0x10000u, pack_bf(y[0][2], y[0][3]), pack_bf(y[1][0], y[1][1]), pack_bf(y[1][2], y[1][3]));
    str128(dst + 32, (pack_bf(y[2][0], y[2][1]) & ~1u) | 0x10000u, pack_bf(y[2][2], y[2][3]), pack_bf(y[3][0], y[3][1]), pack_bf(y[3][2], y[3][3]));
  }
  TS(10);

  if (c < 72) {
    const uint4* src = &p.s->X[(warp * 4 + tt) * (DM * 2) + c * 8 + gg];
    const int slot = (c & 3) * 2 + (ln >> 4), dw = (c >> 2) * 16 + (ln & 15);
    uint32_t hv = 0, kv = 0, res = 0, rs2 = 0;
    uint32_t* o = p.out;
    if (warp == 0) {
      hv = ~0u;
      SPIN_WHILE(max(hv, kv) == ~0u, hv = ldr32((const uint32_t*)p.s->HS + 2304 + slot * 288 + dw); kv = ldr32(&p.s->HS[1152 + slot]));
      const float r = bf_hi(kv ^ (((int)~kv >> 31) | 0x80000000u));
      float rs;
      asm("rcp.approx.ftz.f32 %0, %1;" : "=f"(rs) : "f"(1.f + ex2(r * -1.4426950408889634f)));
      rs2 = keep(pack_bf(rs, rs));
      res = lds32(OFF_XS + slot * 1168 + dw * 4);
      o += (2047 - (int)(kv & 2047u)) * 288 + dw;
      asm volatile("" : "+l"(o));
    }
    const uint32_t sel = (gg & 1) ? 0x3F800000u : 0x00003F80u;
    const uint32_t q0 = keep((gg >> 1) == 0 ? sel : 0u), q1 = keep((gg >> 1) == 1 ? sel : 0u), q2 = keep((gg >> 1) == 2 ? sel : 0u), q3 = keep((gg >> 1) == 3 ? sel : 0u);
    const uint32_t fa = keep(OFF_FIN + warp * 256 + (gg & 1) * 128 + (gg >> 1) * 32 + tt * 8), fb = keep(OFF_FIN + ln * 8);
    uint4 a0 = make_uint4(0, 0, 0, 0), a1 = a0;
    while ((int)(clock() - tpub) < X_PD) {}
    SPIN_WHILE(!(a0.x & a1.x & 0x10000u), if (!(a0.x & 0x10000u)) a0 = ldr128(src); if (!(a1.x & 0x10000u)) a1 = ldr128(src + 64 * DM * 2));
    float d[4] = {0.f, 0.f, 0.f, 0.f}, e[4] = {0.f, 0.f, 0.f, 0.f};
    mma_bf16(d, q0, q2, q1, q3, a0.x, a0.y); mma_bf16(e, q0, q2, q1, q3, a0.z, a0.w);
    mma_bf16(d, q0, q2, q1, q3, a1.x, a1.y); mma_bf16(e, q0, q2, q1, q3, a1.z, a1.w);
    sts64(fa, __float_as_uint(d[0] + e[2]), __float_as_uint(d[1] + e[3]));
    TS(11);
    if (warp == 0) {
      bar_sync(0, 512);
      float2 s[16];
#pragma unroll
      for (int i = 0; i < 16; i++) { const uint2 q = lds64(fb + i * 256); s[i] = make_float2(__uint_as_float(q.x), __uint_as_float(q.y)); }
#pragma unroll
      for (int k = 1; k < 16; k *= 2)
#pragma unroll
        for (int i = 0; i < 16; i += 2 * k) { s[i].x += s[i + k].x; s[i].y += s[i + k].y; }
      *o = bf_add2(hv, bf_add2(res, bf_mul2(pack_bf(s[0].x, s[0].y), rs2)));
    } else bar_arrive(0, 512);
  }
  TS(12);
  TS_DUMP();
}

typedef CUresult (*EncodeFn)(CUtensorMap*, CUtensorMapDataType, cuuint32_t, void*, const cuuint64_t*, const cuuint64_t*, const cuuint32_t*,
                             const cuuint32_t*, CUtensorMapInterleave, CUtensorMapSwizzle, CUtensorMapL2promotion, CUtensorMapFloatOOBfill);

}

extern "C" void kernel_launch(void* const* d_in, const int* in_sizes, int n_in, void* d_out, int out_size) {
  (void)in_sizes; (void)n_in; (void)out_size;
  static EncodeFn enc = nullptr;
  static Scratch* scratch = nullptr;
  if (!enc) {
    void* fn = nullptr;
    cudaDriverEntryPointQueryResult qr;
    cudaGetDriverEntryPoint("cuTensorMapEncodeTiled", &fn, cudaEnableDefault, &qr);
    enc = (EncodeFn)fn;
    cudaGetSymbolAddress((void**)&scratch, g_S);
    cudaFuncSetAttribute(fused_kernel<false>, cudaFuncAttributeMaxDynamicSharedMemorySize, SMEM_BYTES);
    cudaFuncSetAttribute(fused_kernel<true>, cudaFuncAttributeMaxDynamicSharedMemorySize, SMEM_BYTES);
  }
  TMaps tm;
  for (int i = 0; i < 6; i++) {
    const bool dn = i % 3 == 2;
    const cuuint32_t w = i < 3 ? 40 : 32;
    cuuint64_t gd[3] = {(cuuint64_t)(dn ? 64 : FF), (cuuint64_t)(dn ? FF : DM), 9};
    cuuint64_t gs[2] = {(cuuint64_t)(dn ? DM * 2 : FF * 2), 128};
    cuuint32_t bx[3] = {dn ? 64 : w, dn ? w : 96, i < 3 ? 2u : 3u};
    cuuint32_t es[3] = {1, 1, 1};
    enc(&tm.m[i], CU_TENSOR_MAP_DATA_TYPE_BFLOAT16, dn ? 3 : 2, d_in[11 + i % 3], gd, gs, bx, es, CU_TENSOR_MAP_INTERLEAVE_NONE,
        dn ? CU_TENSOR_MAP_SWIZZLE_128B : i < 3 ? CU_TENSOR_MAP_SWIZZLE_NONE : CU_TENSOR_MAP_SWIZZLE_64B,
        (CUtensorMapL2promotion)X_PROMO, CU_TENSOR_MAP_FLOAT_OOB_FILL_NONE);
  }
  for (int i = 6; i < 8; i++) {
    cuuint64_t gd[2] = {DM * 16, NCTA};
    cuuint64_t gs[1] = {DM * 32};
    cuuint32_t bx[2] = {16, i == 6 ? 160u : 128u};
    cuuint32_t es[2] = {1, 1};
    enc(&tm.m[i], CU_TENSOR_MAP_DATA_TYPE_FLOAT16, 2, scratch->X, gd, gs, bx, es, CU_TENSOR_MAP_INTERLEAVE_NONE, CU_TENSOR_MAP_SWIZZLE_32B,
        CU_TENSOR_MAP_L2_PROMOTION_NONE, CU_TENSOR_MAP_FLOAT_OOB_FILL_NONE);
  }
  Params p;
  p.x = (const unsigned char*)d_in[0];
  bool far = false;
  for (int i = 0; i < 7; i++) {
    p.far[i] = (const unsigned char*)d_in[1 + i];
    const long long d = (long long)((intptr_t)d_in[1 + i] - (intptr_t)d_in[0]);
    p.off[i] = (int)(d / 16);
    if ((long long)p.off[i] * 16 != d) far = true;
  }
  p.dskip = (const uint32_t*)d_in[8];
  p.w_r = (const uint32_t*)d_in[10];
  for (int f = 0; f < 2; f++) {
    static const int kind[17] = {0, 0, 0, 0, 0, 0, 2, 2, 1, 1, 1, 1, 1, 1, 2, 2, 2};
    static const int idx[2][17] = {{3, 4, 5, 0, 1, 2, 6, 8, 0, 1, 2, 3, 4, 5, 0, 2, 4}, {3, 4, 5, 0, 1, 2, 0, -1, 0, 1, 2, 3, 4, 5, 3, -1, 6}};
    static const int blk[2][17] = {{-1, -1, -1, -1, -1, -1, 0, -1, 1, -1, 2, -1, 3, -1, X_HU == 14 ? 16 : -1, -1, X_HU == 16 ? 16 : -1}, {-1, -1, -1, -1, -1, -1, 1, -1, -1, -1, 2, -1, 3, -1, X_HU == 14 ? 16 : -1, -1, X_HU == 16 ? 16 : -1}};
    const int pitch = f ? 64 : 80;
    for (int u = 0; u < 17; u++) {
      const int s = idx[f][u];
      const uint32_t dst = kind[u] == 0 ? OFF_G + s * 96 * pitch : kind[u] == 2 ? down_box(s, f) : OFF_W + W_BYTES + (s >> 1) * W_BYTES + (s & 1) * 96 * pitch;
      const uint32_t mb = u == X_NE ? MB_GF - OFF_MISC : blk[f][u] >= 0 ? MB_KF - OFF_MISC + blk[f][u] * 8 : 0;
      p.sched[f][u] = s < 0 ? 3u : kind[u] | s << 2 | mb << 6 | dst << 14;
    }
  }
  p.out = (uint32_t*)d_out;
  p.zero = 0;
  p.ts = nullptr;
  p.s = scratch;
  if (far) { fused_kernel<true><<<NCTA, NT, SMEM_BYTES, cudaStreamPerThread>>>(p, tm); return; }
  fused_kernel<false><<<NCTA, NT, SMEM_BYTES, cudaStreamPerThread>>>(p, tm);
}
```

```cpp
#include <cuda_runtime.h>
#include <cuda.h>
#include <cuda_bf16.h>
#include <cuda_fp16.h>
#include <stdint.h>
#include <stddef.h>

namespace {

constexpr int NCTA = 128;
constexpr int NT = 640;
constexpr int DM = 576;
constexpr int FF = 4608;
constexpr int SPIN_MAX = 1 << 20;

struct Scratch {
  uint4 X[NCTA * DM * 2];
  uint4 KX[64 * 128];
  uint4 HS[1152 + 8];
  uint4 R[256];
  uint4 SC[256];
  uint32_t FLAG[NCTA * 8];
};
__device__ Scratch g_S;

#define CLKS(i)
#define TS(i)
#define TSX(i)
#define TS_DUMP()

constexpr int SB = 1024;
constexpr int BOX = 15360;
constexpr int OFF_G = SB;
constexpr int OFF_W = OFF_G + 3 * BOX;
constexpr int W_UP = 26624;
constexpr int W_KT = W_UP + 5120;
constexpr int W_L3 = W_KT + 4416;
constexpr int W_CW = W_L3 + 4096;
constexpr int W_MISC = W_CW + 640;
constexpr int W_BYTES = 40960;
constexpr int ALT = -W_UP;
static_assert(W_MISC + 32 <= W_BYTES && OFF_W % 1024 == 0 && W_UP % 256 == 0 && W_BYTES + ALT + 3 * 4096 <= W_UP, "wg block");
constexpr int YT_PITCH = 1184;
constexpr int OFF_YT = OFF_W + 4 * W_BYTES;
constexpr int OFF_WR = OFF_YT + 16 * YT_PITCH + 64;
constexpr int OFF_MISC = OFF_WR + 2304;
constexpr int SMEM_BYTES = OFF_MISC + 1024 - SB;
static_assert(OFF_YT % 16 == 0 && OFF_MISC % 16 == 0, "align");
static_assert(SMEM_BYTES <= 232448, "smem");
constexpr int MB_GU = OFF_MISC;
constexpr int MB_D = OFF_MISC + 8;
constexpr int MB_KF = OFF_MISC + 16;
constexpr int MB_GF = OFF_MISC + 48;
constexpr int MB_SC = OFF_MISC + 56;
constexpr int MB_UL = OFF_MISC + 64;
constexpr int MB_REL = OFF_MISC + 104;
constexpr int MB_GO = OFF_MISC + 112;
constexpr int MB_H = MB_KF + 128;
constexpr int MISC_EPOCH = OFF_MISC + 152;
constexpr int MISC_SW = OFF_MISC + 156;
constexpr int MISC_EM = OFF_MISC + 288;
constexpr int MISC_RK = OFF_MISC + 160;
constexpr int MISC_LN1 = OFF_MISC + 192;
constexpr int OFF_XS = OFF_W + W_BYTES + W_UP;
constexpr int OFF_RED = OFF_W + 2 * W_BYTES + W_UP;
constexpr int OFF_FIN = OFF_W + 3 * W_BYTES + W_UP;
constexpr int OFF_ACT = OFF_FIN + 4096;
constexpr int MISC_CNT = OFF_ACT + 1024;

__device__ __forceinline__ uint32_t smem_u32(const void* p) { return (uint32_t)__cvta_generic_to_shared(p); }
__device__ __forceinline__ uint32_t lds32(uint32_t a) { uint32_t v; asm volatile("ld.shared.b32 %0, [%1];" : "=r"(v) : "r"(a) : "memory"); return v; }
__device__ __forceinline__ uint32_t lds16(uint32_t a) { uint16_t v; asm volatile("ld.shared.u16 %0, [%1];" : "=h"(v) : "r"(a) : "memory"); return v; }
__device__ __forceinline__ uint2 lds64(uint32_t a) { uint2 v; asm volatile("ld.shared.v2.b32 {%0,%1}, [%2];" : "=r"(v.x), "=r"(v.y) : "r"(a) : "memory"); return v; }
__device__ __forceinline__ uint4 lds128(uint32_t a) { uint4 v; asm volatile("ld.shared.v4.b32 {%0,%1,%2,%3}, [%4];" : "=r"(v.x), "=r"(v.y), "=r"(v.z), "=r"(v.w) : "r"(a) : "memory"); return v; }
__device__ __forceinline__ void sts16(uint32_t a, uint32_t v) { asm volatile("st.shared.u16 [%0], %1;" :: "r"(a), "h"((uint16_t)v) : "memory"); }
__device__ __forceinline__ void sts32(uint32_t a, uint32_t v) { asm volatile("st.shared.b32 [%0], %1;" :: "r"(a), "r"(v) : "memory"); }
__device__ __forceinline__ void sts64(uint32_t a, uint32_t x, uint32_t y) { asm volatile("st.shared.v2.b32 [%0], {%1,%2};" :: "r"(a), "r"(x), "r"(y) : "memory"); }
__device__ __forceinline__ void sts128(uint32_t a, uint32_t x, uint32_t y, uint32_t z, uint32_t w) { asm volatile("st.shared.v4.b32 [%0], {%1,%2,%3,%4};" :: "r"(a), "r"(x), "r"(y), "r"(z), "r"(w) : "memory"); }
__device__ __forceinline__ void ldsm4(uint32_t a, uint32_t& r0, uint32_t& r1, uint32_t& r2, uint32_t& r3) {
  asm volatile("ldmatrix.sync.aligned.m8n8.x4.shared.b16 {%0,%1,%2,%3}, [%4];" : "=r"(r0), "=r"(r1), "=r"(r2), "=r"(r3) : "r"(a) : "memory");
}
__device__ __forceinline__ void ldsm2(uint32_t a, uint32_t& r0, uint32_t& r1) {
  asm volatile("ldmatrix.sync.aligned.m8n8.x2.shared.b16 {%0,%1}, [%2];" : "=r"(r0), "=r"(r1) : "r"(a) : "memory");
}
__device__ __forceinline__ void ldsm4t(uint32_t a, uint32_t& r0, uint32_t& r1, uint32_t& r2, uint32_t& r3) {
  asm volatile("ldmatrix.sync.aligned.m8n8.x4.trans.shared.b16 {%0,%1,%2,%3}, [%4];" : "=r"(r0), "=r"(r1), "=r"(r2), "=r"(r3) : "r"(a) : "memory");
}
__device__ __forceinline__ void stsm4t(uint32_t a, uint32_t r0, uint32_t r1, uint32_t r2, uint32_t r3) {
  asm volatile("stmatrix.sync.aligned.m8n8.x4.trans.shared.b16 [%0], {%1,%2,%3,%4};" :: "r"(a), "r"(r0), "r"(r1), "r"(r2), "r"(r3) : "memory");
}
__device__ __forceinline__ uint4 ldr128(const void* p) {
  unsigned long long lo, hi;
  asm volatile("{ .reg .b128 t; ld.relaxed.gpu.global.b128 t, [%2]; mov.b128 {%0, %1}, t; }" : "=l"(lo), "=l"(hi) : "l"(p) : "memory");
  return make_uint4((uint32_t)lo, (uint32_t)(lo >> 32), (uint32_t)hi, (uint32_t)(hi >> 32));
}
__device__ __forceinline__ void str128(void* p, uint32_t x, uint32_t y, uint32_t z, uint32_t w) {
  asm volatile("{ .reg .b128 t; .reg .b64 lo, hi; mov.b64 lo, {%1,%2}; mov.b64 hi, {%3,%4}; mov.b128 t, {lo, hi}; st.relaxed.gpu.global.b128 [%0], t; }"
               :: "l"(p), "r"(x), "r"(y), "r"(z), "r"(w) : "memory");
}
__device__ __forceinline__ void str64(void* p, uint32_t x, uint32_t y) {
  asm volatile("{ .reg .b64 t; mov.b64 t, {%1,%2}; st.relaxed.gpu.global.b64 [%0], t; }" :: "l"(p), "r"(x), "r"(y) : "memory");
}
__device__ __forceinline__ uint32_t ldr32(const void* p) { uint32_t v; asm volatile("ld.relaxed.gpu.global.b32 %0, [%1];" : "=r"(v) : "l"(p) : "memory"); return v; }
__device__ __forceinline__ void str32(void* p, uint32_t v) { asm volatile("st.relaxed.gpu.global.b32 [%0], %1;" :: "l"(p), "r"(v) : "memory"); }
__device__ __forceinline__ void str16(void* p, uint32_t v) { asm volatile("st.relaxed.gpu.global.u16 [%0], %1;" :: "l"(p), "h"((uint16_t)v) : "memory"); }
__device__ __forceinline__ void fence_gpu() { asm volatile("fence.acq_rel.gpu;" ::: "memory"); }
__device__ __forceinline__ void bar_sync(int id, int n) { asm volatile("bar.sync %0, %1;" :: "r"(id), "r"(n) : "memory"); }
__device__ __forceinline__ void bar_arrive(int id, int n) { asm volatile("bar.arrive %0, %1;" :: "r"(id), "r"(n) : "memory"); }

__device__ __forceinline__ float bf_lo(uint32_t w) { return __uint_as_float(w << 16); }
__device__ __forceinline__ float bf_hi(uint32_t w) { return __uint_as_float(w & 0xFFFF0000u); }
__device__ __forceinline__ uint32_t pack_bf(float lo, float hi) { uint32_t r; asm("cvt.rn.bf16x2.f32 %0, %1, %2;" : "=r"(r) : "f"(hi), "f"(lo)); return r; }
__device__ __forceinline__ uint32_t pack_h(float lo, float hi) { uint32_t r; asm("cvt.rn.f16x2.f32 %0, %1, %2;" : "=r"(r) : "f"(hi), "f"(lo)); return r; }
__device__ __forceinline__ uint32_t pack_hv(float lo, float hi) { uint32_t r; asm volatile("cvt.rn.f16x2.f32 %0, %1, %2;" : "=r"(r) : "f"(hi), "f"(lo) : "memory"); return r; }
__device__ __forceinline__ float bfr(float x) { return bf_lo(pack_bf(x, 0.f)); }
__device__ __forceinline__ uint32_t bf_sub2(uint32_t a, uint32_t b) { __nv_bfloat162 r = __hsub2(*(__nv_bfloat162*)&a, *(__nv_bfloat162*)&b); return *(uint32_t*)&r; }
__device__ __forceinline__ uint32_t bf_add2(uint32_t a, uint32_t b) { __nv_bfloat162 r = __hadd2(*(__nv_bfloat162*)&a, *(__nv_bfloat162*)&b); return *(uint32_t*)&r; }
__device__ __forceinline__ uint32_t bf_mul2(uint32_t a, uint32_t b) { __nv_bfloat162 r = __hmul2(*(__nv_bfloat162*)&a, *(__nv_bfloat162*)&b); return *(uint32_t*)&r; }
__device__ __forceinline__ float2 h2f(uint32_t w) { return __half22float2(*(__half2*)&w); }
__device__ __forceinline__ float ex2(float x) { float r; asm("ex2.approx.ftz.f32 %0, %1;" : "=f"(r) : "f"(x)); return r; }
__device__ __forceinline__ float warp_sum(float v) {
#pragma unroll
  for (int o = 16; o > 0; o >>= 1) v += __shfl_xor_sync(0xffffffffu, v, o);
  return v;
}
__device__ __forceinline__ void mma_f16_f32(float* d, uint32_t a0, uint32_t a1, uint32_t a2, uint32_t a3, uint32_t b0, uint32_t b1) {
  asm volatile("mma.sync.aligned.m16n8k16.row.col.f32.f16.f16.f32 {%0,%1,%2,%3}, {%4,%5,%6,%7}, {%8,%9}, {%0,%1,%2,%3};"
               : "+f"(d[0]), "+f"(d[1]), "+f"(d[2]), "+f"(d[3]) : "r"(a0), "r"(a1), "r"(a2), "r"(a3), "r"(b0), "r"(b1));
}
__device__ __forceinline__ void mma_f16_f16(uint32_t& d0, uint32_t& d1, uint32_t a0, uint32_t a1, uint32_t a2, uint32_t a3, uint32_t b0, uint32_t b1) {
  asm volatile("mma.sync.aligned.m16n8k16.row.col.f16.f16.f16.f16 {%0,%1}, {%2,%3,%4,%5}, {%6,%7}, {%0,%1};"
               : "+r"(d0), "+r"(d1) : "r"(a0), "r"(a1), "r"(a2), "r"(a3), "r"(b0), "r"(b1));
}
__device__ __forceinline__ void mma_bf16(float* d, uint32_t a0, uint32_t a1, uint32_t a2, uint32_t a3, uint32_t b0, uint32_t b1) {
  asm volatile("mma.sync.aligned.m16n8k16.row.col.f32.bf16.bf16.f32 {%0,%1,%2,%3}, {%4,%5,%6,%7}, {%8,%9}, {%0,%1,%2,%3};"
               : "+f"(d[0]), "+f"(d[1]), "+f"(d[2]), "+f"(d[3]) : "r"(a0), "r"(a1), "r"(a2), "r"(a3), "r"(b0), "r"(b1));
}
__device__ __forceinline__ void mma_bf16_k8(float* d, uint32_t a0, uint32_t a1, uint32_t b0) {
  asm volatile("mma.sync.aligned.m16n8k8.row.col.f32.bf16.bf16.f32 {%0,%1,%2,%3}, {%4,%5}, {%6}, {%0,%1,%2,%3};"
               : "+f"(d[0]), "+f"(d[1]), "+f"(d[2]), "+f"(d[3]) : "r"(a0), "r"(a1), "r"(b0));
}

__device__ __forceinline__ void wg_fence() { asm volatile("wgmma.fence.sync.aligned;" ::: "memory"); }
__device__ __forceinline__ void wg_commit() { asm volatile("wgmma.commit_group.sync.aligned;" ::: "memory"); }
template <int N> __device__ __forceinline__ void wg_wait() { asm volatile("wgmma.wait_group.sync.aligned %0;" :: "n"(N) : "memory"); }
template <int TB> __device__ __forceinline__ void wgmma32(float* d, const uint32_t* a, uint32_t dlo, uint32_t dhi) {
  asm volatile("{ .reg .b64 dd; mov.b64 dd, {%20, %21}; wgmma.mma_async.sync.aligned.m64n32k16.f32.f16.f16 "
               "{%0,%1,%2,%3,%4,%5,%6,%7,%8,%9,%10,%11,%12,%13,%14,%15}, {%16,%17,%18,%19}, dd, 1, 1, 1, %22; }"
               : "+f"(d[0]), "+f"(d[1]), "+f"(d[2]), "+f"(d[3]), "+f"(d[4]), "+f"(d[5]), "+f"(d[6]), "+f"(d[7]), "+f"(d[8]), "+f"(d[9]), "+f"(d[10]), "+f"(d[11]), "+f"(d[12]), "+f"(d[13]), "+f"(d[14]), "+f"(d[15])
               : "r"(a[0]), "r"(a[1]), "r"(a[2]), "r"(a[3]), "r"(dlo), "r"(dhi), "n"(TB));
}
template <int TB> __device__ __forceinline__ void wgmma96(float* d, const uint32_t* a, uint32_t dlo, uint32_t dhi) {
  asm volatile("{ .reg .b64 dd; mov.b64 dd, {%52, %53}; wgmma.mma_async.sync.aligned.m64n96k16.f32.f16.f16 "
               "{%0,%1,%2,%3,%4,%5,%6,%7,%8,%9,%10,%11,%12,%13,%14,%15,%16,%17,%18,%19,%20,%21,%22,%23,%24,%25,%26,%27,%28,%29,%30,%31,%32,%33,%34,%35,%36,%37,%38,%39,%40,%41,%42,%43,%44,%45,%46,%47}, {%48,%49,%50,%51}, dd, 1, 1, 1, %54; }"
               : "+f"(d[0]), "+f"(d[1]), "+f"(d[2]), "+f"(d[3]), "+f"(d[4]), "+f"(d[5]), "+f"(d[6]), "+f"(d[7]), "+f"(d[8]), "+f"(d[9]), "+f"(d[10]), "+f"(d[11]), "+f"(d[12]), "+f"(d[13]), "+f"(d[14]), "+f"(d[15]), "+f"(d[16]), "+f"(d[17]), "+f"(d[18]), "+f"(d[19]), "+f"(d[20]), "+f"(d[21]), "+f"(d[22]), "+f"(d[23]), "+f"(d[24]), "+f"(d[25]), "+f"(d[26]), "+f"(d[27]), "+f"(d[28]), "+f"(d[29]), "+f"(d[30]), "+f"(d[31]), "+f"(d[32]), "+f"(d[33]), "+f"(d[34]), "+f"(d[35]), "+f"(d[36]), "+f"(d[37]), "+f"(d[38]), "+f"(d[39]), "+f"(d[40]), "+f"(d[41]), "+f"(d[42]), "+f"(d[43]), "+f"(d[44]), "+f"(d[45]), "+f"(d[46]), "+f"(d[47])
               : "r"(a[0]), "r"(a[1]), "r"(a[2]), "r"(a[3]), "r"(dlo), "r"(dhi), "n"(TB));
}
template <int TB> __device__ __forceinline__ void wgmma96_init(float* d, const uint32_t* a, uint32_t dlo, uint32_t dhi) {
  asm volatile("{ .reg .b64 dd; mov.b64 dd, {%52, %53}; wgmma.mma_async.sync.aligned.m64n96k16.f32.f16.f16 "
               "{%0,%1,%2,%3,%4,%5,%6,%7,%8,%9,%10,%11,%12,%13,%14,%15,%16,%17,%18,%19,%20,%21,%22,%23,%24,%25,%26,%27,%28,%29,%30,%31,%32,%33,%34,%35,%36,%37,%38,%39,%40,%41,%42,%43,%44,%45,%46,%47}, {%48,%49,%50,%51}, dd, 0, 1, 1, %54; }"
               : "=f"(d[0]), "=f"(d[1]), "=f"(d[2]), "=f"(d[3]), "=f"(d[4]), "=f"(d[5]), "=f"(d[6]), "=f"(d[7]), "=f"(d[8]), "=f"(d[9]), "=f"(d[10]), "=f"(d[11]), "=f"(d[12]), "=f"(d[13]), "=f"(d[14]), "=f"(d[15]), "=f"(d[16]), "=f"(d[17]), "=f"(d[18]), "=f"(d[19]), "=f"(d[20]), "=f"(d[21]), "=f"(d[22]), "=f"(d[23]), "=f"(d[24]), "=f"(d[25]), "=f"(d[26]), "=f"(d[27]), "=f"(d[28]), "=f"(d[29]), "=f"(d[30]), "=f"(d[31]), "=f"(d[32]), "=f"(d[33]), "=f"(d[34]), "=f"(d[35]), "=f"(d[36]), "=f"(d[37]), "=f"(d[38]), "=f"(d[39]), "=f"(d[40]), "=f"(d[41]), "=f"(d[42]), "=f"(d[43]), "=f"(d[44]), "=f"(d[45]), "=f"(d[46]), "=f"(d[47])
               : "r"(a[0]), "r"(a[1]), "r"(a[2]), "r"(a[3]), "r"(dlo), "r"(dhi), "n"(TB));
}
template <int TB> __device__ __forceinline__ void wgmma32_init(float* d, const uint32_t* a, uint32_t dlo, uint32_t dhi) {
  asm volatile("{ .reg .b64 dd; mov.b64 dd, {%20, %21}; wgmma.mma_async.sync.aligned.m64n32k16.f32.f16.f16 "
               "{%0,%1,%2,%3,%4,%5,%6,%7,%8,%9,%10,%11,%12,%13,%14,%15}, {%16,%17,%18,%19}, dd, 0, 1, 1, %22; }"
               : "=f"(d[0]), "=f"(d[1]), "=f"(d[2]), "=f"(d[3]), "=f"(d[4]), "=f"(d[5]), "=f"(d[6]), "=f"(d[7]), "=f"(d[8]), "=f"(d[9]), "=f"(d[10]), "=f"(d[11]), "=f"(d[12]), "=f"(d[13]), "=f"(d[14]), "=f"(d[15])
               : "r"(a[0]), "r"(a[1]), "r"(a[2]), "r"(a[3]), "r"(dlo), "r"(dhi), "n"(TB));
}
__device__ __forceinline__ void wgmma64h(uint32_t* d, uint32_t a0, uint32_t a1, uint32_t a2, uint32_t a3, uint32_t dlo, uint32_t dhi) {
  asm volatile("{ .reg .b64 dd; mov.b64 dd, {%20, %21}; wgmma.mma_async.sync.aligned.m64n64k16.f16.f16.f16 "
               "{%0,%1,%2,%3,%4,%5,%6,%7,%8,%9,%10,%11,%12,%13,%14,%15}, {%16,%17,%18,%19}, dd, 1, 1, 1, 0; }"
               : "+r"(d[0]), "+r"(d[1]), "+r"(d[2]), "+r"(d[3]), "+r"(d[4]), "+r"(d[5]), "+r"(d[6]), "+r"(d[7]), "+r"(d[8]), "+r"(d[9]), "+r"(d[10]), "+r"(d[11]), "+r"(d[12]), "+r"(d[13]), "+r"(d[14]), "+r"(d[15])
               : "r"(a0), "r"(a1), "r"(a2), "r"(a3), "r"(dlo), "r"(dhi));
}
__device__ __forceinline__ void wgmma64h_init(uint32_t* d, uint32_t a0, uint32_t a1, uint32_t a2, uint32_t a3, uint32_t dlo, uint32_t dhi) {
  asm volatile("{ .reg .b64 dd; mov.b64 dd, {%20, %21}; wgmma.mma_async.sync.aligned.m64n64k16.f16.f16.f16 "
               "{%0,%1,%2,%3,%4,%5,%6,%7,%8,%9,%10,%11,%12,%13,%14,%15}, {%16,%17,%18,%19}, dd, 0, 1, 1, 0; }"
               : "=r"(d[0]), "=r"(d[1]), "=r"(d[2]), "=r"(d[3]), "=r"(d[4]), "=r"(d[5]), "=r"(d[6]), "=r"(d[7]), "=r"(d[8]), "=r"(d[9]), "=r"(d[10]), "=r"(d[11]), "=r"(d[12]), "=r"(d[13]), "=r"(d[14]), "=r"(d[15])
               : "r"(a0), "r"(a1), "r"(a2), "r"(a3), "r"(dlo), "r"(dhi));
}
__device__ __forceinline__ void wgmma40_ss(float* d, uint32_t alo, uint32_t blo, uint32_t hi) {
  asm volatile("{ .reg .b64 da, db; mov.b64 da, {%20, %22}; mov.b64 db, {%21, %22}; "
               "wgmma.mma_async.sync.aligned.m64n40k16.f32.f16.f16 {%0,%1,%2,%3,%4,%5,%6,%7,%8,%9,%10,%11,%12,%13,%14,%15,%16,%17,%18,%19}, da, db, 1, 1, 1, 1, 1; }"
               : "+f"(d[0]), "+f"(d[1]), "+f"(d[2]), "+f"(d[3]), "+f"(d[4]), "+f"(d[5]), "+f"(d[6]), "+f"(d[7]), "+f"(d[8]), "+f"(d[9]), "+f"(d[10]), "+f"(d[11]), "+f"(d[12]), "+f"(d[13]), "+f"(d[14]), "+f"(d[15]), "+f"(d[16]), "+f"(d[17]), "+f"(d[18]), "+f"(d[19])
               : "r"(alo), "r"(blo), "r"(hi));
}
__device__ __forceinline__ void wgmma40_ss_init(float* d, uint32_t alo, uint32_t blo, uint32_t hi) {
  asm volatile("{ .reg .b64 da, db; mov.b64 da, {%20, %22}; mov.b64 db, {%21, %22}; "
               "wgmma.mma_async.sync.aligned.m64n40k16.f32.f16.f16 {%0,%1,%2,%3,%4,%5,%6,%7,%8,%9,%10,%11,%12,%13,%14,%15,%16,%17,%18,%19}, da, db, 0, 1, 1, 1, 1; }"
               : "=f"(d[0]), "=f"(d[1]), "=f"(d[2]), "=f"(d[3]), "=f"(d[4]), "=f"(d[5]), "=f"(d[6]), "=f"(d[7]), "=f"(d[8]), "=f"(d[9]), "=f"(d[10]), "=f"(d[11]), "=f"(d[12]), "=f"(d[13]), "=f"(d[14]), "=f"(d[15]), "=f"(d[16]), "=f"(d[17]), "=f"(d[18]), "=f"(d[19])
               : "r"(alo), "r"(blo), "r"(hi));
}
__device__ __forceinline__ float vzero() { float v; asm volatile("mov.b32 %0, 0;" : "=f"(v)); return v; }
__device__ __forceinline__ void tma_box(uint32_t dst, const CUtensorMap* tm, uint32_t mb, int x, int y) {
  asm volatile("cp.async.bulk.tensor.2d.shared::cluster.global.mbarrier::complete_tx::bytes [%0], [%1, {%3, %4}], [%2];"
               :: "r"(dst), "l"(tm), "r"(mb), "r"(x), "r"(y) : "memory");
}
__device__ __forceinline__ void l2_prefetch(const void* src, uint32_t bytes) {
  asm volatile("cp.async.bulk.prefetch.L2.global [%0], %1;" :: "l"(src), "r"(bytes) : "memory");
}
__device__ __forceinline__ uint32_t uni(uint32_t v) {
  uint32_t r; asm volatile("shfl.sync.idx.b32 %0, %1, 0, 0x1f, 0xffffffff;" : "=r"(r) : "r"(v)); return r;
}
__device__ __forceinline__ int fresh_tid() { int v; asm volatile("mov.u32 %0, %tid.x;" : "=r"(v)); return v; }

struct Params {
  const unsigned char* x;
  Scratch* s;
  int off[7];
  uint32_t zero;
  uint32_t* out;
  const uint32_t* dskip;
  const uint32_t* w_r;
  long long* ts;
  const unsigned char* far[7];
  uint32_t sched[2][17];
};
__device__ __forceinline__ uint32_t ldnc32(const void* p) { uint32_t v; asm volatile("ld.global.nc.b32 %0, [%1];" : "=r"(v) : "l"(p)); return v; }
__device__ __forceinline__ uint32_t ldnc16(const void* p) { uint16_t v; asm volatile("ld.global.nc.u16 %0, [%1];" : "=h"(v) : "l"(p)); return v; }
__device__ __forceinline__ uint4 ldnc128(const void* p) { uint4 v; asm volatile("ld.global.nc.v4.b32 {%0,%1,%2,%3}, [%4];" : "=r"(v.x), "=r"(v.y), "=r"(v.z), "=r"(v.w) : "l"(p)); return v; }
__device__ __forceinline__ void mbar_wait(uint32_t mb, uint32_t ph = 0) {
#pragma unroll 1
  for (int it = 0; it < SPIN_MAX; it++) {
    uint32_t ok;
    asm volatile("{ .reg .pred q; mbarrier.try_wait.parity.shared::cta.b64 q, [%1], %2; selp.u32 %0, 1, 0, q; }" : "=r"(ok) : "r"(mb), "r"(ph) : "memory");
    if (ok) break;
  }
}
__device__ __forceinline__ uint32_t mbar_test(uint32_t mb) {
  uint32_t ok;
  asm volatile("{ .reg .pred q; mbarrier.test_wait.parity.shared::cta.b64 q, [%1], 0; selp.u32 %0, 1, 0, q; }" : "=r"(ok) : "r"(mb) : "memory");
  return ok;
}
__device__ __forceinline__ void mbar_arrive(uint32_t mb) { asm volatile("mbarrier.arrive.shared::cta.b64 _, [%0];" :: "r"(mb) : "memory"); }
__device__ __forceinline__ uint32_t ldg16(const void* p) { uint16_t v; asm volatile("ld.global.u16 %0, [%1];" : "=h"(v) : "l"(p) : "memory"); return v; }
__device__ __forceinline__ uint32_t ldr16(const void* p) { uint16_t v; asm volatile("ld.relaxed.gpu.global.u16 %0, [%1];" : "=h"(v) : "l"(p) : "memory"); return v; }
__device__ __forceinline__ void fence_async() { asm volatile("fence.proxy.async.shared::cta;" ::: "memory"); }
#define SPIN_WHILE(cond, body) _Pragma("unroll 1") for (int _it = 0; _it < SPIN_MAX && __any_sync(0xffffffffu, (cond)); _it++) { body; }

struct LnC { uint32_t m2, rh2, rl2; };
__device__ __forceinline__ float diag_sum(float d0, float d1, int t) {
  float q = __shfl_sync(0xffffffffu, d0, 9 * t) + __shfl_sync(0xffffffffu, d1, 9 * t + 4);
  q += __shfl_xor_sync(0xffffffffu, q, 1);
  return q + __shfl_xor_sync(0xffffffffu, q, 2);
}
__device__ __forceinline__ LnC ln_consts(float s, float q, float& r) {
  const float mean = s * (1.f / DM);
  const float var = fmaxf(fmaf(-mean, mean, q * (1.f / DM)), 0.f);
  float sd;
  asm("sqrt.approx.ftz.f32 %0, %1;" : "=f"(sd) : "f"(bfr(bfr(var) + 1e-5f)));
  asm("rcp.approx.ftz.f32 %0, %1;" : "=f"(r) : "f"(bfr(sd)));
  LnC c;
  c.m2 = pack_bf(mean, mean);
  c.rh2 = pack_bf(r, r);
  const float rl = r - bf_lo(c.rh2);
  c.rl2 = pack_bf(rl, rl);
  return c;
}
__device__ __forceinline__ float quad_sum(float s) { s += __shfl_xor_sync(0xffffffffu, s, 1); return s + __shfl_xor_sync(0xffffffffu, s, 2); }
__device__ __forceinline__ uint32_t bf_fma2(uint32_t a, uint32_t b, uint32_t c) {
  __nv_bfloat162 r = __hfma2(*(const __nv_bfloat162*)&a, *(const __nv_bfloat162*)&b, *(const __nv_bfloat162*)&c);
  return *(uint32_t*)&r;
}
__device__ __forceinline__ uint32_t ln_apply(uint32_t w, uint32_t m2, uint32_t rh2, uint32_t rl2) {
  const uint32_t d = bf_sub2(w, m2);
  return bf_fma2(d, rh2, bf_mul2(d, rl2));
}

__device__ __forceinline__ float2 cis(float mag_log2, float rev) {
  const float m = ex2(mag_log2), ang = rev * 6.283185307179586f;
  return make_float2(m * __cosf(ang), m * __sinf(ang));
}
__device__ __forceinline__ float2 csq(float2 a) { return make_float2(fmaf(a.x, a.x, -a.y * a.y), (a.x + a.x) * a.y); }
__device__ __forceinline__ float2 cmul(float2 a, float2 b) { return make_float2(fmaf(a.x, b.x, -a.y * b.y), fmaf(a.x, b.y, a.y * b.x)); }
__device__ __forceinline__ void pmul(uint32_t xr, uint32_t xi, uint32_t w, uint32_t& yr, uint32_t& yi) {
  const __half2 XR = *(__half2*)&xr, XI = *(__half2*)&xi, W = *(__half2*)&w;
  const __half2 a = __hfma2(__hneg2(XI), __high2half2(W), __hmul2(XR, __low2half2(W)));
  const __half2 b = __hfma2(XI, __low2half2(W), __hmul2(XR, __high2half2(W)));
  yr = *(const uint32_t*)&a; yi = *(const uint32_t*)&b;
}
__device__ __forceinline__ uint32_t pk(float2 a) { return pack_h(a.x, a.y); }

struct KgState { float2 c0, z8; float kl; uint32_t w64, w128, w192; };
__device__ __forceinline__ void kgen_tables_n(const uint32_t (&raw)[7], uint32_t scr, int wt, KgState& k) {
  const uint32_t dst = scr + 16384 + wt * 16;
  const float dt = bfr(ex2(bf_lo(raw[6]) * 1.4426950408889634f));
  const float th = dt * bf_lo(raw[1]);
  const float br = dt * bf_lo(raw[2]), bi = dt * bf_lo(raw[3]);
  const float Cr = bf_lo(raw[4]), Ci = bf_lo(raw[5]);
  k.c0 = make_float2(fmaf(Cr, br, -Ci * bi), fmaf(Cr, bi, Ci * br));
  const uint32_t mx = __reduce_max_sync(0xffffffffu, __float_as_uint(fmaxf(fabsf(k.c0.x), fabsf(k.c0.y))));
  const float a2 = dt * bf_lo(raw[0]) * 1.4426950408889634f;
  const float rh = th * 0.15915494309189535f;
  const float rl = fmaf(th, (float)(0.15915494309189535 - (double)0.15915494309189535f), fmaf(th, 0.15915494309189535f, -rh));
  const float rf = rh - rintf(rh);
  const float2 z1 = cis(a2, rf + rl);
  const float p64 = rf * 64.f;
  const float2 z64 = cis(a2 * 64.f, fmaf(64.f, rl, p64 - rintf(p64)));
  const float2 z2 = csq(z1), z128 = csq(z64), z3 = cmul(z2, z1), z4 = csq(z2), z256 = csq(z128), z6 = csq(z3), z512 = csq(z256);
  k.z8 = csq(z4);
  k.w64 = pk(z64); k.w128 = pk(z128); k.w192 = pk(cmul(z128, z64));
  sts128(dst, 0x00003C00u, pk(z2), pk(z4), pk(z6));
  const float2 z1024 = csq(z512), z768 = cmul(z512, z256);
  sts128(dst + 2048, pk(z1), pk(z3), pk(cmul(z4, z1)), pk(cmul(z4, z3)));
  const float2 z2048 = csq(z1024);
  k.kl = fmaf(k.c0.x, z2048.x, -k.c0.y * z2048.y);
  sts128(dst + 4096, pk(z256), pk(cmul(z256, z2)), pk(cmul(z256, z4)), pk(cmul(z256, z6)));
  sts128(dst + 6144, pk(z512), pk(cmul(z512, z4)), pk(z768), pk(cmul(z768, z4)));
  sts128(dst + 8192, pk(z1024), pk(cmul(z1024, z256)), pk(cmul(z1024, z512)), pk(cmul(z1024, z768)));
  sts32(scr + W_MISC + (wt >> 5) * 4, mx);
}
__device__ __forceinline__ int kgen_tables_m(uint32_t scr, int wt, const KgState& k) {
  const uint32_t dst = scr + wt * 16;
  const uint4 e4 = lds128(scr + W_MISC);
  const float2 z16 = csq(k.z8), z32 = csq(z16);
  const int em = max(min((int)(max(max(e4.x, e4.y), max(e4.z, e4.w)) >> 23), 238), 16);
  const float sc = __uint_as_float((uint32_t)(127 + 4 + 127 - em) << 23);
  sts32(scr + W_MISC + 16 + (wt >> 5) * 4, __reduce_add_sync(0xffffffffu, __float2int_rn(k.kl * sc * 262144.f)));
  const float2 c0 = make_float2(k.c0.x * sc, k.c0.y * sc);
  const float2 c1 = cmul(c0, k.z8), c2 = cmul(c0, z16), c4 = cmul(c0, z32), c3 = cmul(c1, z16), c5 = cmul(c1, z32), c6 = cmul(c2, z32), c7 = cmul(c3, z32);
  uint32_t pr[4], pi[4], yr[4], yi[4];
  pr[0] = pack_h(c0.x, c1.x); pi[0] = pack_h(c0.y, c1.y);
  pr[1] = pack_h(c2.x, c3.x); pi[1] = pack_h(c2.y, c3.y);
  pr[2] = pack_h(c4.x, c5.x); pi[2] = pack_h(c4.y, c5.y);
  pr[3] = pack_h(c6.x, c7.x); pi[3] = pack_h(c6.y, c7.y);
  sts128(dst, pr[0], pr[1], pr[2], pr[3]); sts128(dst + 2048, pi[0], pi[1], pi[2], pi[3]);
#pragma unroll
  for (int q = 1; q < 4; q++) {
    const uint32_t w = q == 1 ? k.w64 : q == 2 ? k.w128 : k.w192;
#pragma unroll
    for (int i = 0; i < 4; i++) pmul(pr[i], pi[i], w, yr[i], yi[i]);
    sts128(dst + q * 4096, yr[0], yr[1], yr[2], yr[3]); sts128(dst + q * 4096 + 2048, yi[0], yi[1], yi[2], yi[3]);
  }
  return em;
}
__device__ __forceinline__ void kgen_build(uint32_t tb, uint32_t sc, int wg, int wt, uint32_t k0, uint32_t k1, uint32_t k2) {
  const uint32_t kt = tb + W_KT;
  const int ix = ((wt >> 2) + (wt & 3) * 32 - 1) & 127;
  const uint32_t a3 = tb + W_CW + 32 + ((ix & 1) ? 0 : 304) + (ix >> 1) * 4;
  const uint32_t v3 = wt ? k2 : k2 >> 16;
  sts32(sc + 4 + wt * 4, __byte_perm(k0, k1, 0x5432));
  sts16(sc + 544 + (wt & ~3) + (wt & 1) * 2 + (wt & 2) * 64, k1 >> 16);
  sts16(a3, v3); sts16(a3 + 6, v3);
  if ((unsigned)(wt - 32) < 18u) sts128(kt + (wt < 36 ? -512 : 64 + 4128 - 576) + wt * 16, 0, 0, 0, 0);
  if (wt == 127) sts32(sc, k0 & 0xFFFF0000u);
  if (wt == 0) { sts32(sc + 516, k1); sts16(sc + 800, k2); }
  bar_sync(1 + wg, 128);
  const uint32_t cw = tb + W_CW + 32 + (wt >> 6) * 48 + wt * 4;
  const uint32_t pv = lds32(sc + wt * 4), nx = lds32(sc + 8 + wt * 4), c2 = lds16(sc + 544 + wt * 2), n2 = lds16(sc + 546 + wt * 2);
  sts128(tb + W_L3 + 1024 + (wt >> 6) * 1024 + wt * 16, lds32(cw), lds32(cw - 8), lds32(cw - 16), lds32(cw - 24));
  const bool odd = wt & 1;
  sts64(kt + 64 + wt * 8, __byte_perm(k0, pv, 0x5410), __byte_perm(k0, 0, 0x1032));
  sts64(kt + 64 + 1024 + wt * 8, __byte_perm(k1, pv, (odd || wt == 0) ? 0x7610 : 0x1010), __byte_perm(k1, nx, odd ? 0x1076 : 0x1010));
  const uint32_t cc = c2 * 0x10001u, nc = __byte_perm(n2, c2, 0x5410), nn = n2 * 0x10001u;
  sts128(kt + 64 + 2048 + wt * 16, cc, cc, odd ? nc : cc, odd ? nn : nc);
  if (wt == 127) { sts128(kt + 64 + 4096, nn, nn, nn, nn); sts128(kt + 64 + 4112, nn, nn << 16, 0, 0); }
}

__device__ __forceinline__ void load_a(uint32_t (&a)[4], uint32_t kp, int j) {
  a[0] = lds32(kp + 64 * j); a[1] = lds32(kp + 64 * j + 512); a[2] = lds32(kp + 64 * j - 32); a[3] = lds32(kp + 64 * j + 480);
}
__device__ __forceinline__ uint32_t band(int d, int lo, int hi) {
  return ((unsigned)(d - lo) <= (unsigned)(hi - lo) ? 1u : 0u) | ((unsigned)(d - 1 - lo) <= (unsigned)(hi - lo) ? 0x10000u : 0u);
}
__device__ __forceinline__ uint32_t hadd2u(uint32_t a, uint32_t b) { __half2 r = __hadd2(*(__half2*)&a, *(__half2*)&b); return *(uint32_t*)&r; }

__device__ __forceinline__ void zero_pads(uint32_t tb, int wt) {
  sts128(tb + W_L3 + (wt >> 6) * 1024 + wt * 16, 0, 0, 0, 0);
  if ((wt & 63) < 3) sts128(tb + W_CW + (wt >> 6) * 304 + (wt & 63) * 16, 0, 0, 0, 0);
}
__device__ __forceinline__ uint32_t tr_base(int lane) {
  return OFF_YT + (2 * (lane >> 3) + (lane & 1)) * YT_PITCH + ((lane >> 1) & 1) * (8 * YT_PITCH + 64) + ((lane >> 2) & 1) * 16;
}

__device__ __forceinline__ uint32_t sc_addr(int tp) { return OFF_YT + (tp < 16 ? tp * YT_PITCH + (tp >> 3) * 64 + 1152 : 8 * YT_PITCH - 512 + tp * 32); }
#define X_NE 2
#define X_SCT 10000
#define X_DELTA 400
#define X_DSTEP 1950
#define X_PF0 2500
#define X_PFD 600
#define X_TD 520
#define X_WS 6
#define X_OR 8
#define X_ABS 5000
#define X_XD 0
#define X_RD 800
#define X_HD 500
#define X_PD 1150
#define X_PROMO 2
#define X_YD2 500
#define X_GO 2
#define X_GW 2
#define X_NS 4900
#define X_LAG 1800
#define X_YD 1400
struct TMaps { CUtensorMap m[8]; };
__device__ __forceinline__ uint32_t h2bf(uint32_t w) { const float2 f = h2f(w); return pack_bf(f.x, f.y); }
__device__ __forceinline__ uint32_t keep(uint32_t v) { asm volatile("" : "+r"(v)); return v; }
__device__ __forceinline__ uint2 ldr64(const void* p) { uint2 v; asm volatile("{ .reg .b64 t; ld.relaxed.gpu.global.b64 t, [%2]; mov.b64 {%0, %1}, t; }" : "=r"(v.x), "=r"(v.y) : "l"(p) : "memory"); return v; }
__host__ __device__ __forceinline__ uint32_t down_box(int s, bool five) {
  return five ? OFF_W + W_BYTES + 12288 + (s / 3) * (W_BYTES - 12288) + s * 4096 : s < 6 ? OFF_W + W_BYTES + BOX + (s >> 1) * (W_BYTES - 10240) + s * 5120 : OFF_W + (s - 6) * 5120;
}
__device__ __forceinline__ void load_tile(const CUtensorMap* tmx, int i, int c) {
  asm volatile("mbarrier.arrive.expect_tx.shared::cta.b64 _, [%0], 5120;" :: "r"(MB_UL + i * 8) : "memory");
  tma_box(OFF_W + (i < 4 ? i * W_BYTES : ALT) + W_UP, tmx, MB_UL + i * 8, (i < 4 ? i * 128 + c : 512 + (c >> 1)) * 16, -32);
}
template <bool FAR> __device__ __forceinline__ void load_params(const Params& p, uint32_t ch, int wt, uint32_t dst, bool on) {
  const int o01 = (wt & 16) ? p.off[1] : p.off[0], o23 = (wt & 16) ? p.off[3] : p.off[2], o45 = (wt & 16) ? p.off[5] : p.off[4];
  const int o = (wt & 64) ? ((wt & 32) ? p.off[6] : o45) : ((wt & 32) ? o23 : o01);
  const unsigned char* b = FAR ? p.far[min(wt >> 4, 6)] : p.x + (long long)o * 16;
  asm volatile("{ .reg .pred q; setp.ne.u32 q, %2, 0; @q cp.async.cg.shared.global [%0], [%1], 16; }"
               :: "r"(dst + wt * 16), "l"(b + (wt < 96 ? ch * 256 + (wt & 15) * 16 : (ch >> 3) * 16)), "r"((uint32_t)(on && wt < 97)) : "memory");
}

struct ConvC { uint32_t ca, cb, bands; };
__device__ __forceinline__ ConvC conv_consts(int w, int lane) {
  const int h = w & 1, P = w >> 1, d0 = 8 * h + (lane >> 2) - 2 * (lane & 3);
  ConvC k;
  k.ca = keep((W_KT + (16 + 256 * P + d0) * 4) | ((W_UP + (32 + 64 * P + lane) * 32 + ((h ^ (lane >> 2)) & 1) * 16) << 16));
  k.cb = keep(lane < 8 ? 0xFFFEFFFEu : ~0u);
  k.bands = keep(band(d0, 12, 20) + 2 * band(d0 + 8, 12, 20) + 4 * band(d0 + 16, 12, 20) + 8 * band(d0 + 24, 12, 20)
                 + 16 * band(d0 - 8, 5, 11) + 32 * band(d0, 5, 11) + 64 * band(d0 + 8, 5, 11) + 128 * band(d0 + 16, 5, 11));
  return k;
}
__device__ __forceinline__ void conv_item(uint32_t tb, const ConvC& cv, uint32_t zero, const CUtensorMap* tmx, int ch, int warp, int lane, bool hold, bool more) {
  const bool go = more && warp == 0 && lane == 0;
  const uint32_t kp = tb + (cv.ca & 0xFFFFu);
  const uint32_t dlo = ((tb + W_UP) >> 4) + 64 + (1u << 16), dhi = 16u | (3u << 30);
  const bool P = warp & 2;
  float a32[16], a96[48];
  uint32_t A[40][4];
#define STEP(J) { wgmma96<0>(a96, A[J], dlo + 64 - 2 * (J), dhi); if ((J) == 0) wgmma32_init<0>(a32, A[J], dlo, dhi); else if ((J) < 8) wgmma32<0>(a32, A[J], (dlo ^ zero) - 2 * (J), dhi); }
#define LD(J) load_a(A[J], kp, J);
#define FIRST(J) wg_fence(); STEP(J) wg_commit(); wg_wait<1>(); wg_fence();
  {
    uint32_t win[16], x9[4], x7[4], e[4], f[4];
    const uint32_t bz = keep(cv.bands);
#define BAND(i) keep((bz & (0x10001u << (i))) * (0x3C00u >> (i)))
    e[0] = lds32(kp + (P ? 3232 : 4096)); e[2] = lds32(kp + (P ? 3200 : 4064)); e[1] = keep(bz & 0x100u); e[3] = keep(bz & 0x200u);
    f[3] = lds32(kp + (P ? 3200 : 4128)); f[0] = keep(bz & 0x4000u); f[1] = keep(bz & 0x8000u); f[2] = keep(bz & 0x300u);
    const uint32_t q[12] = {BAND(0), BAND(5), keep(bz & 0x400u), BAND(4), BAND(2), BAND(7), BAND(1), BAND(6), keep(bz & 0x800u), keep(bz & 0x1000u), BAND(3), keep(bz & 0x2000u)};
#undef BAND
    const uint32_t ta = keep(tb + W_UP + 1024 + (warp & 3) * 1024 + lane * 32 + (lane & 4) * 4);
    if (X_GO && hold) mbar_wait(MB_GO);
#pragma unroll 1
    for (int it = 0; it < SPIN_MAX; it++) {
      if (ch < 512) mbar_wait(MB_UL + (warp >> 2) * 8, it & 1);
      if (it == 1) TS(13);
      TS(3);
      wg_fence();
      wgmma64h_init(win, q[0], q[1], q[2], q[3], dlo, dhi);
      wgmma64h(win, q[4], q[5], q[6], q[7], dlo - 2, dhi);
      wgmma64h(win, q[8], q[9], q[10], q[11], dlo - 4, dhi);
      wg_commit();
      wgmma96_init<0>(a96, e, dlo - 64, dhi);
      wgmma96<0>(a96, f, dlo - 50, dhi);
      wg_commit();
      if (ch >= 512) break;
      uint32_t r0, r1, r2, r3, ok;
      ldsm4(ta, r0, r1, r2, r3);
      asm volatile("{ .reg .pred q; setp.ne.u32 q, %1, 0; barrier.red.and.pred q, %2, 128, q; selp.u32 %0, 1, 0, q; }" : "=r"(ok) : "r"((r0 & r1 & r2 & r3 & 1u) | (lane & 3)), "r"(1 + (warp >> 2)) : "memory");
      if (ok) break;
      wg_wait<0>();
      if ((warp & 3) == 0 && lane == 0) load_tile(tmx - 1, warp >> 2, ch & 127);
    }
    wg_wait<1>();
#pragma unroll
    for (int i = 0; i < 4; i++) {
      const int tl = 2 * ((i & 1) + ((i & 2) ? 0 : 4));
      x9[i] = P ? win[tl + 4] : win[tl]; x7[i] = P ? win[tl + 5] : win[tl + 1];
    }
    const uint32_t l3lo = ((tb + W_L3) >> 4) + (32u << 16);
    wg_fence();
    wgmma96<0>(a96, x9, l3lo, 8);
    wgmma96<0>(a96, x7, l3lo + 128, 8);
    wg_commit();
  }
  LD(32) LD(33) LD(34) LD(35)
  FIRST(32) STEP(33) STEP(34) STEP(35) wg_commit();
  LD(36) LD(37) LD(38)
  FIRST(36) STEP(37) STEP(38) wg_commit();
  LD(39) LD(0)
  TS(17);
  if (X_GO == 1 && go) mbar_arrive(MB_GO);
  FIRST(39) STEP(0) wg_commit();
  LD(1) LD(2) LD(3)
  FIRST(1) STEP(2) STEP(3) wg_commit();
  LD(4) LD(5)
  if (X_GO == 2 && go) mbar_arrive(MB_GO);
  FIRST(4) STEP(5) wg_commit();
  LD(6) LD(7)
  wg_fence(); STEP(6) STEP(7) wg_commit();
#undef STEP
#undef LD
#undef FIRST
  TS(18);
  if (X_GO == 3 && go) mbar_arrive(MB_GO);
  const uint32_t xc = tb + W_KT + (warp & 3) * 1024 + lane * 16;
  wg_wait<0>();
  uint32_t E[16], o[8];
#define ACC(i) ((i) < 16 ? a32[i] : a96[(i) - 16])
  E[0] = pack_h(a32[0], a32[1]);
#pragma unroll
  for (int i = 1; i < 16; i++) E[i] = pack_h(ACC(4 * i) + ACC(4 * i - 2), ACC(4 * i + 1) + ACC(4 * i - 1));
#undef ACC
#pragma unroll
  for (int j = 0; j < 8; j++) o[j] = P ? (j < 2 ? 0u : E[j - 2]) : E[8 + j];
  sts128(xc, o[0], o[1], o[2], o[3]); sts128(xc + 512, o[4], o[5], o[6], o[7]);
#pragma unroll
  for (int j = 0; j < 8; j++) o[j] = P ? E[6 + j] : E[j];
  TS(25);
  if (more) {
    sts128(xc + 4096, o[0], o[1], o[2], o[3]); sts128(xc + 4608, o[4], o[5], o[6], o[7]);
    bar_arrive(12, 192);
    return;
  }
  bar_sync(1 + (warp >> 2), 128);
  const uint4 vv[2] = {lds128(xc + (P ? -2048 : 2048)), lds128(xc + (P ? -1536 : 2560))};
#pragma unroll
  for (int q = 0; q < 2; q++) {
    const uint4 v = vv[q];
    stsm4t(tb + (cv.ca >> 16) + q * 1024, hadd2u(o[4 * q], v.x) & cv.cb, hadd2u(o[4 * q + 1], v.y) & cv.cb, hadd2u(o[4 * q + 2], v.z) & cv.cb, hadd2u(o[4 * q + 3], v.w) & cv.cb);
  }
  fence_async();
  bar_sync(1 + (warp >> 2), 128);
  if (warp == 0 && lane == 0) mbar_arrive(MB_REL);
  if ((warp & 3) == 3 && lane == 0) {
    asm volatile("cp.async.bulk.tensor.2d.global.shared::cta.bulk_group [%0, {%2, %3}], [%1];" :: "l"(tmx), "r"(tb + W_UP + 1024), "r"(ch * 16), "r"(0) : "memory");
    asm volatile("cp.async.bulk.commit_group;" ::: "memory");
  }
}

template <bool FAR> __global__ void __launch_bounds__(NT, 1)
fused_kernel(const __grid_constant__ Params p, const __grid_constant__ TMaps tm) {
  extern __shared__ __align__(1024) unsigned char smem[];
  const int c = blockIdx.x;
  const bool five = (c & 1) == 0;
  const uint32_t pitch = five ? 64 : 80;
  const uint32_t ones = 0x3F803F80u;
  const int tid = threadIdx.x, lane = tid & 31;
  {
    const int w4 = tid >> 7, k5 = !five && w4 == 3;
    load_params<FAR>(p, k5 ? 512 + (c >> 1) : w4 * 128 + c, tid & 127, OFF_W + w4 * W_BYTES + W_KT + k5 * 2048, w4 != 2 && w4 != 4);
  }
  const int warp = (int)uni(tid >> 5), wg = warp >> 2;
  TS(0);
  if (__builtin_expect(wg == 4, 0)) {
    asm volatile("setmaxnreg.dec.sync.aligned.u32 32;");
    const int role = warp;
    const int u0 = (c >> 1) * 9 + (five ? ((c & 2) ? 5 : 0) : ((c & 2) ? 0 : 4));
    const uint32_t t0 = clock() + c * 4;
    if (role == 16) {
      if (lane < 19) asm volatile("mbarrier.init.shared::cta.b64 [%0], %1;" :: "r"(OFF_MISC + lane * 8), "r"((unsigned)(lane - 2) < 4u ? 4 : 1) : "memory");
      if (lane < 2) asm volatile("mbarrier.arrive.expect_tx.shared::cta.b64 _, [%0], %1;" :: "r"(OFF_MISC + lane * 8), "r"(lane ? (five ? 36864 : 51200) : pitch * 1152) : "memory");
      fence_async();
      bar_arrive(5, 576);
      const CUtensorMap* tmb = &tm.m[five ? 3 : 0];
#pragma unroll 1
      for (int u = 0; u < 17; u++) {
        const uint32_t e = p.sched[five][u], kind = e & 3, s = (e >> 2) & 15, dst = e >> 14;
        if (kind == 3) continue;
        while ((int)(clock() - t0) < X_PF0 + (u < X_NE ? u * X_PFD : X_LAG + u * X_TD)) __nanosleep(20);
        if (e & 0x3FC0) mbar_wait(OFF_MISC + ((e >> 6) & 255));
        if (lane == 0) {
          if (kind == 2) asm volatile("cp.async.bulk.tensor.3d.shared::cluster.global.mbarrier::complete_tx::bytes [%0], [%1, {%3, %4, %5}], [%2];"
                                      :: "r"(dst), "l"(tmb + 2), "r"(MB_D), "r"(0), "r"(u0 * 8), "r"(s) : "memory");
          else tma_box(dst, tmb + kind, MB_GU, u0 * 8, s * 96);
        }
        if (u == 5) TS(2);
        if (u == 10) TS(3);
      }
      TS(4);
      TS_DUMP();
#define FINISH0 bar_sync(12, 192);        \
        _Pragma("unroll 1") for (int w = role & 2; w < (role & 2) + 2; w++) { \
          const uint32_t xa = OFF_W + W_KT + lane * 16, mk = lane < 8 ? 0xFFFEFFFEu : ~0u, ya = OFF_W + W_UP + (32 + lane) * 32 + ((w ^ (lane >> 2)) & 1) * 16 + (w & 2) * 1024; \
          const uint4 a = lds128(xa + 4096 + w * 1024), b = lds128(xa + (w ^ 2) * 1024), d = lds128(xa + 4608 + w * 1024), e = lds128(xa + 512 + (w ^ 2) * 1024); \
          stsm4t(ya, hadd2u(a.x, b.x) & mk, hadd2u(a.y, b.y) & mk, hadd2u(a.z, b.z) & mk, hadd2u(a.w, b.w) & mk); \
          stsm4t(ya + 1024, hadd2u(d.x, e.x) & mk, hadd2u(d.y, e.y) & mk, hadd2u(d.z, e.z) & mk, hadd2u(d.w, e.w) & mk); \
        } \
        fence_async();
    } else if (role == 17) {
      if (smem_u32(smem) != SB) __trap();
      bar_sync(10, 576);
      if (X_NS && lane == 0) {
        fence_async();
        while ((int)(clock() - t0) < X_NS - c * 4) {}
        asm volatile("cp.async.bulk.global.shared::cta.bulk_group [%0], [%1], 10240;" :: "l"(&p.s->X[c * DM * 2 + 512]), "r"(OFF_G) : "memory");
        asm volatile("cp.async.bulk.commit_group;" ::: "memory");
        asm volatile("cp.async.bulk.wait_group 0;" ::: "memory");
      }
      if (lane == 0) mbar_arrive(MB_GF);
      bar_arrive(11, 96);
      if (five) { FINISH0 bar_arrive(13, 64); }
    } else if (role == 18) {
      sts32(MISC_EPOCH, 0);
      bar_arrive(5, 576);
      uint4* q = lane < 2 ? &p.s->R[c * 2 + lane] : lane < 11 ? &p.s->HS[c * 9 + lane - 2] : lane == 11 ? &p.s->HS[1152 + (c & 7)] : (uint4*)&p.s->FLAG[c * 8];
      if (lane < (c < 8 ? 12 : 11)) str128(q, ~0u, ~0u, ~0u, ~0u);
      const uint32_t ep = __shfl_sync(0xffffffffu, ldr32(q), 31) + 1u;
      sts32(MISC_EPOCH, ep | 0x80000000u);
      TSX(21);
      if (lane == 31) str32(q, ep);
      bar_sync(11, 96);
      if (lane == 0) load_tile(&tm.m[6], 3, c);
      TSX(14);
      mbar_wait(MB_KF + (lane & 3) * 8);
      __syncwarp();
      { const uint2 e = lds64(MISC_EM); if (lane < 2) str128(&p.s->SC[c * 2 + lane], e.x, __byte_perm(e.y, ep, 0x6540), 0, 0); }
      TSX(17);
      while ((int)(clock() - t0) < X_SCT) __nanosleep(100);
      TSX(18);
      {
        uint2 v[4];
#pragma unroll 1
        for (int it = 0; it < SPIN_MAX; it++) {
          uint32_t bad = 0;
#pragma unroll
          for (int q = 0; q < 4; q++) v[q] = ldr64(&p.s->SC[lane * 2 + q * 64]);
#pragma unroll
          for (int q = 0; q < 4; q++) bad |= (v[q].y >> 8) ^ (ep & 0xFFFFFFu);
          if (!__any_sync(0xffffffffu, bad)) break;
        }
        TSX(25);
#pragma unroll
        for (int q = 0; q < 4; q++) {
#pragma unroll
          for (int k = 0; k < 4; k++) asm volatile("st.shared.u8 [%0], %1;" :: "r"(sc_addr(4 * k + q) + lane), "r"(v[q].x >> (8 * k)) : "memory");
          if (lane & 1) asm volatile("st.shared.u8 [%0], %1;" :: "r"(sc_addr(16) + q * 16 + (lane >> 1)), "r"(v[q].y) : "memory");
        }
      }
      __syncwarp();
      if (lane == 0) mbar_arrive(MB_SC);
      TSX(27);
    } else {
      uint32_t w[9], d[9];
      float s = 0.f;
#pragma unroll
      for (int i = 0; i < 9; i++) { w[i] = ldnc32(p.w_r + (i < 8 ? lane * 4 + (i & 3) + (i >> 2) * 128 : 256 + lane)); d[i] = ldnc32(p.dskip + lane + 32 * i); }
#pragma unroll
      for (int i = 0; i < 9; i++) { sts32(OFF_WR + lane * 4 + i * 128, w[i]); sts32(OFF_WR + 1152 + lane * 4 + i * 128, d[i]); s += bf_lo(w[i]) + bf_hi(w[i]); }
      sts32(MISC_SW, __float_as_uint(warp_sum(s)));
      TSX(23);
      bar_sync(10, 576);
      if (lane == 0) {
        const uint32_t tp = clock();
        TSX(1);
        while ((int)(clock() - tp) < X_DELTA || (int)(clock() - t0) < X_ABS - c * 4) {}
        TSX(24);
        load_tile(&tm.m[6], 0, c);
        TSX(15);
        load_tile(&tm.m[6], 1, c);
        while ((int)(clock() - t0) < X_ABS + X_DSTEP - c * 4) {}
      }
      bar_sync(11, 96);
      if (lane == 0) {
        load_tile(&tm.m[6], 2, c);
      }
      if (five) {
        mbar_wait(MB_KF);
#pragma unroll 1
        for (int it = 0; it < SPIN_MAX; it++) {
          if (lane == 0) load_tile(&tm.m[6], 4, c);
          mbar_wait(MB_UL + 32, it & 1);
          uint32_t m = 1;
#pragma unroll
          for (int q = 0; q < 4; q++) { uint32_t r0, r1, r2, r3; ldsm4(OFF_W + ALT + W_UP + 1024 + lane * 32 + (lane & 4) * 4 + q * 1024, r0, r1, r2, r3); m &= r0 & r1 & r2 & r3; }
          if (__all_sync(0xffffffffu, m || (lane & 3))) break;
        }
        bar_arrive(7, 288);
        FINISH0
        bar_sync(13, 64);
        if (lane == 0) {
          asm volatile("cp.async.bulk.tensor.2d.global.shared::cta.bulk_group [%0, {%2, %3}], [%1];" :: "l"(&tm.m[7]), "r"(OFF_W + W_UP + 1024), "r"(c * 16), "r"(0) : "memory");
          asm volatile("cp.async.bulk.commit_group;" ::: "memory");
          asm volatile("cp.async.bulk.wait_group.read 0;" ::: "memory");
        }
      }
      uint4* rp = &p.s->R[c * 2 + (lane & 1)];
      asm volatile("" : "+l"(rp));
      bar_sync(0, 544);
      if (lane == 0) mbar_arrive(MB_H);
      bar_sync(5, 544);
      const uint4 k = lds128(MISC_RK + (lane & 1) * 16);
      if (lane < 2) str128(rp, k.x, k.y, k.z, k.w);
    }
    return;
  }
  const int wt = tid & 127, g = lane >> 2, t = lane & 3;
  const uint32_t wb = OFF_W + wg * W_BYTES;
  const uint32_t xrow = OFF_YT + (wt >> 3) * YT_PITCH + (wt & 64) + (lane & 7) * 16;
  if (wg == 2) {
    const unsigned char* xp = p.x + (uint32_t)((c * 16 + (wt >> 3)) * 1152 + (lane & 7) * 16);
    { const uint32_t tq = clock(); while ((int)(clock() - tq) < X_XD) {} }
#pragma unroll
    for (int k = 0; k < 9; k++) asm volatile("cp.async.cg.shared.global [%0], [%1], 16;" :: "r"(xrow + k * 128), "l"(xp + k * 128) : "memory");
  }
  asm volatile("cp.async.commit_group;" ::: "memory");
  const ConvC cv = conv_consts(warp & 3, lane);
  zero_pads(wb, wt);
  load_params<FAR>(p, wg * 128 + c, wt, wb + W_KT, wg == 2 || (wg == 3 && !five));
  asm volatile("cp.async.commit_group;" ::: "memory");
  asm volatile("setmaxnreg.inc.sync.aligned.u32 112;");
  {
    uint4 kw;
    uint4* kx = &p.s->KX[(c >> 1) * 128 + wt];
    bool two = wg == 3;
    uint32_t ep;
    int phase = wg == 2 ? 3 : 2;
#pragma unroll 1
    for (;;) {
      const bool first = two && !five;
      if (phase) asm volatile("cp.async.wait_group 1;" ::: "memory"); else asm volatile("cp.async.wait_group 0;" ::: "memory");
      if (phase == 3) {
        TS(21);
        float d[3][4], r;
        uint4 a[9];
#pragma unroll
        for (int k = 0; k < 9; k++) a[k] = lds128(xrow + k * 128);
#pragma unroll
        for (int i = 0; i < 4; i++) d[0][i] = d[1][i] = d[2][i] = 0.f;
#pragma unroll
        for (int k = 0; k < 9; k++) { mma_bf16(d[(2 * k) % 3], a[k].x, ones, a[k].y, ones, a[k].x, a[k].y); mma_bf16(d[(2 * k + 1) % 3], a[k].z, ones, a[k].w, ones, a[k].z, a[k].w); }
#pragma unroll
        for (int i = 0; i < 4; i++) d[0][i] += d[1][i] + d[2][i];
        const LnC lc = ln_consts(d[0][2] + d[0][3], __shfl_sync(0xffffffffu, d[0][0], 9 * t) + __shfl_sync(0xffffffffu, d[0][1], 9 * t + 4), r);
        if (lane < 12) sts16(MISC_LN1 + g * 32 + (warp & 3) * 8 + t * 2, lane < 4 ? lc.m2 : lane < 8 ? lc.rh2 : lc.rl2);
      } else {
        KgState ks;
        uint32_t raw[7];
        bar_sync(1 + wg, 128);
        TS(22);
#pragma unroll
        for (int i = 0; i < 7; i++) raw[i] = lds16(wb + W_KT + first * 2048 + i * 256 + (i < 6 ? wt : (c >> first) & 7) * 2);
        kgen_tables_n(raw, wb, wt, ks);
        TS(20);
        bar_sync(1 + wg, 128);
        const int em = kgen_tables_m(wb, wt, ks);
        asm volatile("st.shared.u8 [%0], %1;" :: "r"(MISC_EM + wg + first), "r"(em + 9) : "memory");
        fence_async();
      }
      if (phase & 2) {
        const uint32_t tr_addr = tr_base(lane) + warp * 32;
        uint4* dst = &p.s->X[c * DM * 2 + warp * 32 + (8 * (t >> 1) + g) * 2 + (t & 1)];
        TS(23);
        bar_sync(5, 576);
        uint32_t x[3][4];
        ldsm4t(tr_addr, x[0][0], x[0][1], x[0][2], x[0][3]);
        const uint4 m = lds128(MISC_LN1 + (t & 1) * 16), rl = lds128(MISC_LN1 + 64 + (t & 1) * 16), rh = lds128(MISC_LN1 + 32 + (t & 1) * 16);
        ldsm4t(tr_addr + 512, x[1][0], x[1][1], x[1][2], x[1][3]);
        if (wg == 1) ldsm4t(tr_addr + 896, x[2][0], x[2][1], x[2][2], x[2][3]);
#pragma unroll
        for (int q = 0; q < 3; q++) {
          if (q < 2 || wg == 1) {
            const uint32_t r0 = ln_apply(x[q][0], m.x, rh.x, rl.x), r1 = ln_apply(x[q][1], m.y, rh.y, rl.y), r2 = ln_apply(x[q][2], m.z, rh.z, rl.z), r3 = ln_apply(x[q][3], m.w, rh.w, rl.w);
            const uint32_t w0 = (pack_h(bf_lo(r0), bf_hi(r0)) & 0xFFFEFFFEu) | 1u, w1 = pack_h(bf_lo(r1), bf_hi(r1)), w2 = pack_h(bf_lo(r2), bf_hi(r2)), w3 = pack_h(bf_lo(r3), bf_hi(r3));
            if (q == 0 || !X_NS) str128(dst + q * 512 - (q == 2 ? 128 : 0), w0, w1, w2, w3);
            else sts128(OFF_G + warp * 512 + (8 * (t >> 1) + g) * 32 + (t & 1) * 16 + (q == 2 ? 6144 : 0), w0, w1, w2, w3);
          }
          if (q == 0) TS(30);
        }
        bar_arrive(10, 576);
        TS(1);
      } else bar_sync(1 + wg, 128);
      phase &= 1;
      if (phase) { phase = 0; continue; }
      TS(14);
      float acc[20];
      const uint32_t alo = (wb >> 4) | (8u << 16);
      wg_fence();
      wgmma40_ss_init(acc, alo, alo + 1024, 2048 >> 4);
#pragma unroll
      for (int k = 1; k < 8; k++) wgmma40_ss(acc, alo + k * 16, alo + 1024 + k * 16, 2048 >> 4);
      wg_commit();
      const uint4 k4 = lds128(wb + W_MISC + 16);
      const float k2048 = (float)(int)(k4.x + k4.y + k4.z + k4.w) * (1.f / 262144.f);
      wg_wait<0>();
      const float un = 1.f / 8192.f;
      kw.x = pack_h((acc[0] - acc[3]) * un, (acc[4] - acc[7]) * un);
      kw.y = pack_h((acc[8] - acc[11]) * un, (acc[12] - acc[15]) * un);
      kw.z = pack_h((acc[16] - acc[19]) * un, k2048 * un);
      TS(24);
      ep = 0;
      if (two) SPIN_WHILE(ep == 0, ep = lds32(MISC_EPOCH));
      if (five || !two) break;
      str128(kx, kw.x, kw.y, kw.z, ep);
      two = false;
    }
    if (lane == 0) mbar_arrive(MB_KF + wg * 8);
    mbar_wait(MB_KF + wg * 8);
    if (two) { mbar_wait(MB_KF); zero_pads(OFF_W + ALT, wt); }
    uint32_t tb = wb;
#pragma unroll 1
    for (;;) {
      kgen_build(tb, (tb == wb ? wb : OFF_W + 16384 - 25600) + 25600, wg, wt, kw.x, kw.y, kw.z);
      TS(15);
      if (!two) break;
      two = false;
      kw.w = 0;
      SPIN_WHILE(kw.w != ep, kw = ldr128(kx));
      tb = OFF_W + ALT;
    }
    fence_async();
    TS(31);
    if (tb != wb) bar_arrive(7, 288);
    bar_sync(1 + wg, 128);
  }
  uint32_t tpub;
#pragma unroll 1
  for (int item = 0;; item++) {
    TS(2);
    conv_item(item ? OFF_W + ALT : wb, cv, p.zero, &tm.m[7], item ? 512 + (c >> 1) : wg * 128 + c, warp, lane, five && wg >= X_GW, five && !wg && !item);
    tpub = clock() - (item ? X_YD : wg >= 2 ? X_YD2 : 0);
    if (wg || !five || item) break;
    TS(27);
    bar_sync(7, 288);
  }
  TS(4);

  const int ln = lane ^ p.zero, td = warp * 32 + ln, gg = ln >> 2, tt = ln & 3;
  const int tok = c * 16 + warp;
  const int fu = warp / 3, fk = warp - fu * 3;
  uint32_t wa[12][4];
  {
    uint32_t hw[9], wr[9];
    const uint32_t row = keep(OFF_YT + warp * YT_PITCH + (warp >> 3) * 64 + ln * 16);
    const uint32_t wabase = keep(((ln & 8) ? OFF_W + (fk + 1) * W_BYTES : OFF_G + fk * 192 * pitch) + ((ln >> 4) * 8 + (ln & 7)) * pitch
                                 + (five ? ((fu ^ (ln >> 1)) & 3) : min(fu, 4)) * 16);
    float sw;
    {
      const bool three = wg == 1;
      const int ch = 8 * (tt >> 1) + gg;
      const uint32_t tr_addr = tr_base(ln);
      const uint4* ysrc = &p.s->X[c * DM * 2 + ch * 2 + (tt & 1)];
      uint32_t x[3][4], ud[3][4], s[3];
      uint4 v[3];
#define TL(q) ((q) < 2 ? 2 * warp + (q) : 28 + warp)
      asm volatile("cp.async.bulk.wait_group.read 0;" ::: "memory");
      while ((int)(clock() - tpub) < X_YD) {}
      TS(5);
      v[0] = ldr128(ysrc + TL(0) * 32); v[1] = ldr128(ysrc + TL(1) * 32); v[2] = make_uint4(three, 0, 0, 0);
      mbar_wait(MB_REL);
      const uint4 m = lds128(MISC_LN1 + (tt & 1) * 16), rh = lds128(MISC_LN1 + 32 + (tt & 1) * 16), rl = lds128(MISC_LN1 + 64 + (tt & 1) * 16);
#pragma unroll
      for (int i = 0; i < 9; i++) wr[i] = lds32(OFF_WR + ln * 4 + i * 128);
      sw = __uint_as_float(lds32(MISC_SW));
#pragma unroll
      for (int q = 0; q < 3; q++) {
        if (q < 2 || three) {
          const uint32_t dk = lds16(OFF_WR + 1152 + ch * 2 + TL(q) * 32) * 0x10001u;
          ldsm4t(tr_addr + TL(q) * 32, x[q][0], x[q][1], x[q][2], x[q][3]);
          ud[q][0] = bf_mul2(ln_apply(x[q][0], m.x, rh.x, rl.x), dk); ud[q][1] = bf_mul2(ln_apply(x[q][1], m.y, rh.y, rl.y), dk);
          ud[q][2] = bf_mul2(ln_apply(x[q][2], m.z, rh.z, rl.z), dk); ud[q][3] = bf_mul2(ln_apply(x[q][3], m.w, rh.w, rl.w), dk);
        }
      }
      mbar_wait(MB_SC);
#pragma unroll
      for (int q = 0; q < 3; q++) {
        asm volatile("ld.shared.u8 %0, [%1];" : "=r"(s[q]) : "r"((q < 2 ? sc_addr(warp) + q * 16 : sc_addr(16) + (warp & 3) * 16) + ch) : "memory");
        s[q] = keep(s[q] * 0x800080u);
      }
#define FIN(q) stsm4t(tr_addr + TL(q) * 32, bf_add2(x[q][0], bf_fma2(h2bf(v[q].x), s[q], ud[q][0])), bf_add2(x[q][1], bf_fma2(h2bf(v[q].y), s[q], ud[q][1])), \
                      bf_add2(x[q][2], bf_fma2(h2bf(v[q].z), s[q], ud[q][2])), bf_add2(x[q][3], bf_fma2(h2bf(v[q].w), s[q], ud[q][3])));
      SPIN_WHILE((v[0].x | v[1].x) & 1u, _Pragma("unroll") for (int q = 0; q < 3; q++) if (v[q].x & 1u) v[q] = ldr128(ysrc + TL(q) * 32));
      if (v[2].x & 1u) v[2] = ldr128(ysrc + TL(2) * 32);
      FIN(0) FIN(1)
      if (three) {
        SPIN_WHILE(v[2].x & 1u, if (v[2].x & 1u) v[2] = ldr128(ysrc + TL(2) * 32));
        FIN(2)
      }
#undef FIN
#undef TL
    }
    TS(28);
    bar_sync(0, 544);
    TS(6);
    float d[4] = {0.f, 0.f, 0.f, 0.f}, e[4] = {0.f, 0.f, 0.f, 0.f}, rd;
    {
      const uint4 a = lds128(row), b = lds128(row + 512);
      hw[8] = lds32(row + 1024 - ln * 12);
      hw[0] = a.x; hw[1] = a.y; hw[2] = a.z; hw[3] = a.w; hw[4] = b.x; hw[5] = b.y; hw[6] = b.z; hw[7] = b.w;
    }
    mma_bf16(e, hw[0], hw[1], hw[2], hw[3], ones, ones);
#pragma unroll
    for (int i = 0; i < 8; i += 2) mma_bf16(d, hw[i], wr[i], hw[i + 1], wr[i + 1], hw[i], hw[i + 1]);
    mma_bf16(e, hw[4], hw[5], hw[6], hw[7], ones, ones);
    e[0] += e[2];
    mma_bf16_k8(e, hw[8], wr[8], ones);
    mma_bf16_k8(d, hw[8], wr[8], hw[8]);
    const float hwsum = diag_sum(d[2], d[3], tt);
    LnC l2 = ln_consts(diag_sum(e[0], e[0], tt), diag_sum(d[0], d[1], tt), rd);
    const uint32_t b = pack_bf(0.f, fmaf(-bf_lo(l2.m2), sw, hwsum) * rd);
    uint32_t key = max(min((b ^ (((int)b >> 31) | 0x80000000u)) >> 16, 0xFFFEu), 1u);
    sts16(MISC_RK + warp * 2, key);
    bar_sync(5, 544);
    asm volatile("" : "+r"(l2.m2) :: "memory");
    TS(7);
    const uint32_t tr0 = clock();
    key = (key << 16) | (2047 - tok);
    uint32_t loc = ln < 16 ? (lds16(MISC_RK + ln * 2) << 16) | (2047 - c * 16 - ln) : 0u;
    int rank = __popc(__ballot_sync(0xffffffffu, loc > key));
#pragma unroll
    for (int i = 0; i < 9; i++) wr[i] = keep(ln_apply(hw[i], l2.m2, l2.rh2, l2.rl2));
    const uint2* rsrc = (const uint2*)p.s->R + td;
    uint2 rv = make_uint2(~0u, 0u);
    mbar_wait(MB_GU);
    if (warp < (five ? 12 : 15)) {
#pragma unroll
      for (int k = 0; k < X_WS; k++) ldsm4t(wabase + k * 16 * pitch, wa[k][0], wa[k][1], wa[k][2], wa[k][3]);
    }
#define OUT_ROW { uint32_t* o = p.out + tok * 288 + ln * 4; \
      *(uint4*)o = make_uint4(bf_add2(hw[0], wr[0]), bf_add2(hw[1], wr[1]), bf_add2(hw[2], wr[2]), bf_add2(hw[3], wr[3])); \
      *(uint4*)(o + 128) = make_uint4(bf_add2(hw[4], wr[4]), bf_add2(hw[5], wr[5]), bf_add2(hw[6], wr[6]), bf_add2(hw[7], wr[7])); \
      o[256 - ln * 3] = bf_add2(hw[8], wr[8]); }
    if (rank >= X_OR) OUT_ROW
#pragma unroll 1
    for (int base = 0; base < 8; base += 4) {
      uint32_t T[4];
#pragma unroll
      for (int j = 0; j < 4; j++) {
        const uint32_t mx = __reduce_max_sync(0xffffffffu, loc);
        if (loc == mx) loc = 0;
        T[j] = (td >> 2) == c ? ~0u : (td >> 2) < c ? (mx & 0xFFFF0000u) - 1u : mx | 0xFFFFu;
      }
      const uint32_t sh = keep(ln < 16 ? 0x4440u + (rank & 3) : 0x4344u), ca = keep(MISC_CNT + base * 16 + (ln & 15) * 4);
      while ((int)(clock() - tr0) < X_RD) {}
      SPIN_WHILE(rv.x == ~0u, if (rv.x == ~0u) rv = ldr64(rsrc));
      TS(16);
      uint32_t cnt = 0, cn2 = 0;
#pragma unroll
      for (int j = 0; j < 4; j++)
        asm("{ .reg .pred a, b, c, d; setp.gt.u32 a, %2, %6; setp.gt.u32 b, %3, %6; setp.gt.u32 c, %4, %6; setp.gt.u32 d, %5, %6; "
            "@a add.u32 %0, %0, %7; @b add.u32 %1, %1, %7; @c add.u32 %0, %0, %7; @d add.u32 %1, %1, %7; }"
            : "+r"(cnt), "+r"(cn2) : "r"(rv.x), "r"(rv.x << 16), "r"(rv.y), "r"(rv.y << 16), "r"(T[j]), "r"(1u << (8 * j)));
      sts32(MISC_CNT + base * 16 + warp * 4, __reduce_add_sync(0xffffffffu, cnt + cn2));
      bar_sync(0, 512);
      cnt = __reduce_add_sync(0xffffffffu, __byte_perm(lds32(ca), 0, sh));
      if ((rank & ~3) == base && rank + (int)(cnt & 0xFFFFu) < 8) {
        rank += cnt & 0xFFFFu;
        uint4* hs = p.s->HS + rank * 72 + ln;
        str128(hs, wr[0], wr[1], wr[2], wr[3]); str128(hs + 32, wr[4], wr[5], wr[6], wr[7]); str32((uint32_t*)(hs + 64) - ln * 3, wr[8]);
        str128(hs + 576, hw[0], hw[1], hw[2], hw[3]); str128(hs + 608, hw[4], hw[5], hw[6], hw[7]); str32((uint32_t*)(hs + 640) - ln * 3, hw[8]);
        if (ln == 0) str32(&p.s->HS[1152 + rank], key);
        rank = 16;
      }
      if (cnt >= (4u << 16)) break;
    }
    TS(8);
    tpub = clock();
    if (rank < X_OR) OUT_ROW
    if (warp < (five ? 12 : 15)) {
#pragma unroll
      for (int k = X_WS; k < 12; k++) ldsm4t(wabase + k * 16 * pitch, wa[k][0], wa[k][1], wa[k][2], wa[k][3]);
    }
  }
  uint32_t wd[10][4];
  const uint32_t xb = keep(OFF_XS + (ln & 7) * 1168 + (fk * 24 + (ln >> 3)) * 16);
  if (warp >= 7) {
    const uint32_t db = down_box(warp - 7, five) + (ln & 7) * 128;
    mbar_wait(MB_D);
#pragma unroll
    for (int j = 0; j < 4; j++) {
      const uint32_t a = db + (ln >> 4) * 1024 + (((2 * j + ((ln >> 3) & 1)) ^ (ln & 7)) << 4);
      ldsm4t(a, wd[j][0], wd[j][1], wd[j][2], wd[j][3]);
      ldsm4t(a + 2048, wd[4 + j][0], wd[4 + j][1], wd[4 + j][2], wd[4 + j][3]);
    }
#pragma unroll
    for (int j = 0; j < 2; j++) ldsm4t(db + 4096 + (((4 * j + (ln >> 3)) ^ (ln & 7)) << 4), wd[8 + j][0], wd[8 + j][1], wd[8 + j][2], wd[8 + j][3]);
  } else if (warp < 6) {
    const int r = td / 24;
    const uint4* src = &p.s->HS[td + r * 48];
    const uint32_t xs = keep(OFF_XS + (td + r * 49) * 16);
    uint4 a[3];
    uint32_t m = ~0u;
    while ((int)(clock() - tpub) < X_HD) {}
    TS(19);
    SPIN_WHILE(m == ~0u, if (m == ~0u) { a[0] = ldr128(src); a[1] = ldr128(src + 24); a[2] = ldr128(src + 48); } m = max(max(max(a[0].x, a[1].x), max(a[2].x, a[2].y)), max(a[2].z, a[2].w)));
#pragma unroll
    for (int q = 0; q < 3; q++) sts128(xs + q * 384, a[q].x, a[q].y, a[q].z, a[q].w);
  }
  bar_sync(0, 512);
  TS(9);

  if (warp < (five ? 12 : 15)) {
    float d0[4] = {0.f, 0.f, 0.f, 0.f}, d1[4] = {0.f, 0.f, 0.f, 0.f};
#pragma unroll
    for (int k = 0; k < 12; k += 2) {
      uint32_t b0, b1, b2, b3;
      ldsm4(xb + k * 32, b0, b1, b2, b3);
      mma_bf16(d0, wa[k][0], wa[k][1], wa[k][2], wa[k][3], b0, b1);
      mma_bf16(d1, wa[k + 1][0], wa[k + 1][1], wa[k + 1][2], wa[k + 1][3], b2, b3);
    }
    sts128(OFF_RED + td * 16, __float_as_uint(d0[0] + d1[0]), __float_as_uint(d0[1] + d1[1]), __float_as_uint(d0[2] + d1[2]), __float_as_uint(d0[3] + d1[3]));
  }
  TS(26);
  if (warp < 5) {
    const uint32_t rb = OFF_RED + warp * 1536 + ln * 16;
    bar_sync(9, 512);
    const uint4 pa = lds128(rb), pb = lds128(rb + 512), pc = lds128(rb + 1024);
    const float ga = bfr(__uint_as_float(pa.x) + __uint_as_float(pb.x) + __uint_as_float(pc.x));
    const float gb = bfr(__uint_as_float(pa.y) + __uint_as_float(pb.y) + __uint_as_float(pc.y));
    const uint32_t uu = pack_bf(__uint_as_float(pa.z) + __uint_as_float(pb.z) + __uint_as_float(pc.z), __uint_as_float(pa.w) + __uint_as_float(pb.w) + __uint_as_float(pc.w));
    float ra, rb2;
    asm("rcp.approx.ftz.f32 %0, %1;" : "=f"(ra) : "f"(1.f + ex2(ga * -1.4426950408889634f)));
    asm("rcp.approx.ftz.f32 %0, %1;" : "=f"(rb2) : "f"(1.f + ex2(gb * -1.4426950408889634f)));
    const uint32_t act = bf_mul2(pack_bf(ga * ra, gb * rb2), uu);
    sts32(OFF_ACT + td * 4, act);
  } else bar_arrive(9, 512);
  uint4* dst = &p.s->X[c * DM * 2 + (warp - 7) * 64 + tt * 8 + gg];
  asm volatile("" : "+l"(dst));
  bar_sync(8, 512);
  tpub = clock();
  if (warp >= 7) {
    uint32_t b0, b1, b2, b3, b4;
    ldsm4t(OFF_ACT + ln * 16, b0, b1, b2, b3);
    asm volatile("ldmatrix.sync.aligned.m8n8.x1.trans.shared.b16 {%0}, [%1];" : "=r"(b4) : "r"(OFF_ACT + 512 + ln * 16) : "memory");
    float y[4][4];
#pragma unroll
    for (int j = 0; j < 4; j++) {
      y[j][0] = y[j][1] = y[j][2] = y[j][3] = 0.f;
      mma_bf16(y[j], wd[j][0], wd[j][1], wd[j][2], wd[j][3], b0, b1);
    }
#pragma unroll
    for (int j = 0; j < 4; j++) mma_bf16(y[j], wd[4 + j][0], wd[4 + j][1], wd[4 + j][2], wd[4 + j][3], b2, b3);
    if (!five) {
#pragma unroll
      for (int j = 0; j < 4; j++) mma_bf16_k8(y[j], wd[8 + (j >> 1)][2 * (j & 1)], wd[8 + (j >> 1)][2 * (j & 1) + 1], b4);
    }
    str128(dst, (pack_bf(y[0][0], y[0][1]) & ~1u) | 0x10000u, pack_bf(y[0][2], y[0][3]), pack_bf(y[1][0], y[1][1]), pack_bf(y[1][2], y[1][3]));
    str128(dst + 32, (pack_bf(y[2][0], y[2][1]) & ~1u) | 0x10000u, pack_bf(y[2][2], y[2][3]), pack_bf(y[3][0], y[3][1]), pack_bf(y[3][2], y[3][3]));
  }
  TS(10);

  if (c < 72) {
    const uint4* src = &p.s->X[(warp * 4 + tt) * (DM * 2) + c * 8 + gg];
    const int slot = (c & 3) * 2 + (ln >> 4), dw = (c >> 2) * 16 + (ln & 15);
    uint32_t hv = 0, kv = 0, res = 0, rs2 = 0;
    uint32_t* o = p.out;
    if (warp == 0) {
      hv = ~0u;
      SPIN_WHILE(max(hv, kv) == ~0u, hv = ldr32((const uint32_t*)p.s->HS + 2304 + slot * 288 + dw); kv = ldr32(&p.s->HS[1152 + slot]));
      const float r = bf_hi(kv ^ (((int)~kv >> 31) | 0x80000000u));
      float rs;
      asm("rcp.approx.ftz.f32 %0, %1;" : "=f"(rs) : "f"(1.f + ex2(r * -1.4426950408889634f)));
      rs2 = keep(pack_bf(rs, rs));
      res = lds32(OFF_XS + slot * 1168 + dw * 4);
      o += (2047 - (int)(kv & 2047u)) * 288 + dw;
      asm volatile("" : "+l"(o));
    }
    const uint32_t sel = (gg & 1) ? 0x3F800000u : 0x00003F80u;
    const uint32_t q0 = keep((gg >> 1) == 0 ? sel : 0u), q1 = keep((gg >> 1) == 1 ? sel : 0u), q2 = keep((gg >> 1) == 2 ? sel : 0u), q3 = keep((gg >> 1) == 3 ? sel : 0u);
    const uint32_t fa = keep(OFF_FIN + warp * 256 + (gg & 1) * 128 + (gg >> 1) * 32 + tt * 8), fb = keep(OFF_FIN + ln * 8);
    uint4 a0 = make_uint4(0, 0, 0, 0), a1 = a0;
    while ((int)(clock() - tpub) < X_PD) {}
    SPIN_WHILE(!(a0.x & a1.x & 0x10000u), if (!(a0.x & 0x10000u)) a0 = ldr128(src); if (!(a1.x & 0x10000u)) a1 = ldr128(src + 64 * DM * 2));
    float d[4] = {0.f, 0.f, 0.f, 0.f}, e[4] = {0.f, 0.f, 0.f, 0.f};
    mma_bf16(d, q0, q2, q1, q3, a0.x, a0.y); mma_bf16(e, q0, q2, q1, q3, a0.z, a0.w);
    mma_bf16(d, q0, q2, q1, q3, a1.x, a1.y); mma_bf16(e, q0, q2, q1, q3, a1.z, a1.w);
    sts64(fa, __float_as_uint(d[0] + e[2]), __float_as_uint(d[1] + e[3]));
    TS(11);
    if (warp == 0) {
      bar_sync(0, 512);
      float2 s[16];
#pragma unroll
      for (int i = 0; i < 16; i++) { const uint2 q = lds64(fb + i * 256); s[i] = make_float2(__uint_as_float(q.x), __uint_as_float(q.y)); }
#pragma unroll
      for (int k = 1; k < 16; k *= 2)
#pragma unroll
        for (int i = 0; i < 16; i += 2 * k) { s[i].x += s[i + k].x; s[i].y += s[i + k].y; }
      *o = bf_add2(hv, bf_add2(res, bf_mul2(pack_bf(s[0].x, s[0].y), rs2)));
    } else bar_arrive(0, 512);
  }
  TS(12);
  TS_DUMP();
}

typedef CUresult (*EncodeFn)(CUtensorMap*, CUtensorMapDataType, cuuint32_t, void*, const cuuint64_t*, const cuuint64_t*, const cuuint32_t*,
                             const cuuint32_t*, CUtensorMapInterleave, CUtensorMapSwizzle, CUtensorMapL2promotion, CUtensorMapFloatOOBfill);

}

extern "C" void kernel_launch(void* const* d_in, const int* in_sizes, int n_in, void* d_out, int out_size) {
  (void)in_sizes; (void)n_in; (void)out_size;
  static EncodeFn enc = nullptr;
  static Scratch* scratch = nullptr;
  if (!enc) {
    void* fn = nullptr;
    cudaDriverEntryPointQueryResult qr;
    cudaGetDriverEntryPoint("cuTensorMapEncodeTiled", &fn, cudaEnableDefault, &qr);
    enc = (EncodeFn)fn;
    cudaGetSymbolAddress((void**)&scratch, g_S);
    cudaFuncSetAttribute(fused_kernel<false>, cudaFuncAttributeMaxDynamicSharedMemorySize, SMEM_BYTES);
    cudaFuncSetAttribute(fused_kernel<true>, cudaFuncAttributeMaxDynamicSharedMemorySize, SMEM_BYTES);
  }
  TMaps tm;
  for (int i = 0; i < 6; i++) {
    const bool dn = i % 3 == 2;
    const cuuint32_t w = i < 3 ? 40 : 32;
    cuuint64_t gd[3] = {(cuuint64_t)(dn ? 64 : FF), (cuuint64_t)(dn ? FF : DM), 9};
    cuuint64_t gs[2] = {(cuuint64_t)(dn ? DM * 2 : FF * 2), 128};
    cuuint32_t bx[3] = {dn ? 64 : w, dn ? w : 96, i < 3 ? 2u : 3u};
    cuuint32_t es[3] = {1, 1, 1};
    enc(&tm.m[i], CU_TENSOR_MAP_DATA_TYPE_BFLOAT16, dn ? 3 : 2, d_in[11 + i % 3], gd, gs, bx, es, CU_TENSOR_MAP_INTERLEAVE_NONE,
        dn ? CU_TENSOR_MAP_SWIZZLE_128B : i < 3 ? CU_TENSOR_MAP_SWIZZLE_NONE : CU_TENSOR_MAP_SWIZZLE_64B,
        (CUtensorMapL2promotion)X_PROMO, CU_TENSOR_MAP_FLOAT_OOB_FILL_NONE);
  }
  for (int i = 6; i < 8; i++) {
    cuuint64_t gd[2] = {DM * 16, NCTA};
    cuuint64_t gs[1] = {DM * 32};
    cuuint32_t bx[2] = {16, i == 6 ? 160u : 128u};
    cuuint32_t es[2] = {1, 1};
    enc(&tm.m[i], CU_TENSOR_MAP_DATA_TYPE_FLOAT16, 2, scratch->X, gd, gs, bx, es, CU_TENSOR_MAP_INTERLEAVE_NONE, CU_TENSOR_MAP_SWIZZLE_32B,
        CU_TENSOR_MAP_L2_PROMOTION_NONE, CU_TENSOR_MAP_FLOAT_OOB_FILL_NONE);
  }
  Params p;
  p.x = (const unsigned char*)d_in[0];
  bool far = false;
  for (int i = 0; i < 7; i++) {
    p.far[i] = (const unsigned char*)d_in[1 + i];
    const long long d = (long long)((intptr_t)d_in[1 + i] - (intptr_t)d_in[0]);
    p.off[i] = (int)(d / 16);
    if ((long long)p.off[i] * 16 != d) far = true;
  }
  p.dskip = (const uint32_t*)d_in[8];
  p.w_r = (const uint32_t*)d_in[10];
  for (int f = 0; f < 2; f++) {
    static const int kind[17] = {0, 0, 0, 0, 2, 2, 0, 0, 1, 1, 1, 1, 1, 1, 2, 2, 2};
    static const int idx[2][17] = {{2, 3, 4, 5, 6, 8, 0, 1, 0, 1, 2, 3, 4, 5, 0, 2, 4}, {2, 3, 4, 5, 0, -1, 0, 1, 0, 1, 2, 3, 4, 5, 3, -1, 6}};
    static const int blk[2][17] = {{-1, -1, -1, -1, 0, -1, 4, -1, 1, -1, 2, -1, 3, -1, 16, -1, -1}, {-1, -1, -1, -1, 1, -1, 4, -1, -1, -1, 2, -1, 3, -1, 16, -1, -1}};
    const int pitch = f ? 64 : 80;
    for (int u = 0; u < 17; u++) {
      const int s = idx[f][u];
      const uint32_t dst = kind[u] == 0 ? OFF_G + s * 96 * pitch : kind[u] == 2 ? down_box(s, f) : OFF_W + W_BYTES + (s >> 1) * W_BYTES + (s & 1) * 96 * pitch;
      const uint32_t mb = blk[f][u] >= 0 ? MB_KF - OFF_MISC + blk[f][u] * 8 : 0;
      p.sched[f][u] = s < 0 ? 3u : kind[u] | s << 2 | mb << 6 | dst << 14;
    }
  }
  p.out = (uint32_t*)d_out;
  p.zero = 0;
  p.ts = nullptr;
  p.s = scratch;
  if (far) { fused_kernel<true><<<NCTA, NT, SMEM_BYTES, cudaStreamPerThread>>>(p, tm); return; }
  fused_kernel<false><<<NCTA, NT, SMEM_BYTES, cudaStreamPerThread>>>(p, tm);
}
```

```cpp
#include <cuda_runtime.h>
#include <cuda.h>
#include <cuda_bf16.h>
#include <cuda_fp16.h>
#include <stdint.h>
#include <stddef.h>

namespace {

constexpr int NCTA = 128;
constexpr int NT = 640;
constexpr int DM = 576;
constexpr int FF = 4608;
constexpr int SPIN_MAX = 1 << 20;

struct Scratch {
  uint4 X[NCTA * DM * 2];
  uint4 KX[64 * 128];
  uint4 HS[1152 + 8];
  uint4 R[256];
  uint4 SC[256];
  uint32_t FLAG[NCTA * 8];
};
__device__ Scratch g_S;

#define CLKS(i)
#define TS(i)
#define TSX(i)
#define TS_DUMP()

constexpr int SB = 1024;
constexpr int BOX = 15360;
constexpr int OFF_G = SB;
constexpr int OFF_W = OFF_G + 3 * BOX;
constexpr int W_UP = 26624;
constexpr int W_KT = W_UP + 5120;
constexpr int W_L3 = W_KT + 4416;
constexpr int W_CW = W_L3 + 4096;
constexpr int W_MISC = W_CW + 640;
constexpr int W_BYTES = 40960;
constexpr int ALT = -W_UP;
static_assert(W_MISC + 32 <= W_BYTES && OFF_W % 1024 == 0 && W_UP % 256 == 0 && W_BYTES + ALT + 3 * 4096 <= W_UP, "wg block");
constexpr int YT_PITCH = 1184;
constexpr int OFF_YT = OFF_W + 4 * W_BYTES;
constexpr int OFF_WR = OFF_YT + 16 * YT_PITCH + 64;
constexpr int OFF_MISC = OFF_WR + 2304;
constexpr int SMEM_BYTES = OFF_MISC + 1024 - SB;
static_assert(OFF_YT % 16 == 0 && OFF_MISC % 16 == 0, "align");
static_assert(SMEM_BYTES <= 232448, "smem");
constexpr int MB_GU = OFF_MISC;
constexpr int MB_D = OFF_MISC + 8;
constexpr int MB_KF = OFF_MISC + 16;
constexpr int MB_GF = OFF_MISC + 48;
constexpr int MB_SC = OFF_MISC + 56;
constexpr int MB_UL = OFF_MISC + 64;
constexpr int MB_REL = OFF_MISC + 104;
constexpr int MB_GO = OFF_MISC + 112;
constexpr int MB_H = MB_KF + 128;
constexpr int MISC_EPOCH = OFF_MISC + 152;
constexpr int MISC_SW = OFF_MISC + 156;
constexpr int MISC_EM = OFF_MISC + 288;
constexpr int MISC_RK = OFF_MISC + 160;
constexpr int MISC_LN1 = OFF_MISC + 192;
constexpr int OFF_XS = OFF_W + W_BYTES + W_UP;
constexpr int OFF_RED = OFF_W + 2 * W_BYTES + W_UP;
constexpr int OFF_FIN = OFF_W + 3 * W_BYTES + W_UP;
constexpr int OFF_ACT = OFF_FIN + 4096;
constexpr int MISC_CNT = OFF_ACT + 1024;

__device__ __forceinline__ uint32_t smem_u32(const void* p) { return (uint32_t)__cvta_generic_to_shared(p); }
__device__ __forceinline__ uint32_t lds32(uint32_t a) { uint32_t v; asm volatile("ld.shared.b32 %0, [%1];" : "=r"(v) : "r"(a) : "memory"); return v; }
__device__ __forceinline__ uint32_t lds16(uint32_t a) { uint16_t v; asm volatile("ld.shared.u16 %0, [%1];" : "=h"(v) : "r"(a) : "memory"); return v; }
__device__ __forceinline__ uint2 lds64(uint32_t a) { uint2 v; asm volatile("ld.shared.v2.b32 {%0,%1}, [%2];" : "=r"(v.x), "=r"(v.y) : "r"(a) : "memory"); return v; }
__device__ __forceinline__ uint4 lds128(uint32_t a) { uint4 v; asm volatile("ld.shared.v4.b32 {%0,%1,%2,%3}, [%4];" : "=r"(v.x), "=r"(v.y), "=r"(v.z), "=r"(v.w) : "r"(a) : "memory"); return v; }
__device__ __forceinline__ void sts16(uint32_t a, uint32_t v) { asm volatile("st.shared.u16 [%0], %1;" :: "r"(a), "h"((uint16_t)v) : "memory"); }
__device__ __forceinline__ void sts32(uint32_t a, uint32_t v) { asm volatile("st.shared.b32 [%0], %1;" :: "r"(a), "r"(v) : "memory"); }
__device__ __forceinline__ void sts64(uint32_t a, uint32_t x, uint32_t y) { asm volatile("st.shared.v2.b32 [%0], {%1,%2};" :: "r"(a), "r"(x), "r"(y) : "memory"); }
__device__ __forceinline__ void sts128(uint32_t a, uint32_t x, uint32_t y, uint32_t z, uint32_t w) { asm volatile("st.shared.v4.b32 [%0], {%1,%2,%3,%4};" :: "r"(a), "r"(x), "r"(y), "r"(z), "r"(w) : "memory"); }
__device__ __forceinline__ void ldsm4(uint32_t a, uint32_t& r0, uint32_t& r1, uint32_t& r2, uint32_t& r3) {
  asm volatile("ldmatrix.sync.aligned.m8n8.x4.shared.b16 {%0,%1,%2,%3}, [%4];" : "=r"(r0), "=r"(r1), "=r"(r2), "=r"(r3) : "r"(a) : "memory");
}
__device__ __forceinline__ void ldsm2(uint32_t a, uint32_t& r0, uint32_t& r1) {
  asm volatile("ldmatrix.sync.aligned.m8n8.x2.shared.b16 {%0,%1}, [%2];" : "=r"(r0), "=r"(r1) : "r"(a) : "memory");
}
__device__ __forceinline__ void ldsm4t(uint32_t a, uint32_t& r0, uint32_t& r1, uint32_t& r2, uint32_t& r3) {
  asm volatile("ldmatrix.sync.aligned.m8n8.x4.trans.shared.b16 {%0,%1,%2,%3}, [%4];" : "=r"(r0), "=r"(r1), "=r"(r2), "=r"(r3) : "r"(a) : "memory");
}
__device__ __forceinline__ void stsm4t(uint32_t a, uint32_t r0, uint32_t r1, uint32_t r2, uint32_t r3) {
  asm volatile("stmatrix.sync.aligned.m8n8.x4.trans.shared.b16 [%0], {%1,%2,%3,%4};" :: "r"(a), "r"(r0), "r"(r1), "r"(r2), "r"(r3) : "memory");
}
__device__ __forceinline__ uint4 ldr128(const void* p) {
  unsigned long long lo, hi;
  asm volatile("{ .reg .b128 t; ld.relaxed.gpu.global.b128 t, [%2]; mov.b128 {%0, %1}, t; }" : "=l"(lo), "=l"(hi) : "l"(p) : "memory");
  return make_uint4((uint32_t)lo, (uint32_t)(lo >> 32), (uint32_t)hi, (uint32_t)(hi >> 32));
}
__device__ __forceinline__ void str128(void* p, uint32_t x, uint32_t y, uint32_t z, uint32_t w) {
  asm volatile("{ .reg .b128 t; .reg .b64 lo, hi; mov.b64 lo, {%1,%2}; mov.b64 hi, {%3,%4}; mov.b128 t, {lo, hi}; st.relaxed.gpu.global.b128 [%0], t; }"
               :: "l"(p), "r"(x), "r"(y), "r"(z), "r"(w) : "memory");
}
__device__ __forceinline__ void str64(void* p, uint32_t x, uint32_t y) {
  asm volatile("{ .reg .b64 t; mov.b64 t, {%1,%2}; st.relaxed.gpu.global.b64 [%0], t; }" :: "l"(p), "r"(x), "r"(y) : "memory");
}
__device__ __forceinline__ uint32_t ldr32(const void* p) { uint32_t v; asm volatile("ld.relaxed.gpu.global.b32 %0, [%1];" : "=r"(v) : "l"(p) : "memory"); return v; }
__device__ __forceinline__ void str32(void* p, uint32_t v) { asm volatile("st.relaxed.gpu.global.b32 [%0], %1;" :: "l"(p), "r"(v) : "memory"); }
__device__ __forceinline__ void str16(void* p, uint32_t v) { asm volatile("st.relaxed.gpu.global.u16 [%0], %1;" :: "l"(p), "h"((uint16_t)v) : "memory"); }
__device__ __forceinline__ void fence_gpu() { asm volatile("fence.acq_rel.gpu;" ::: "memory"); }
__device__ __forceinline__ void bar_sync(int id, int n) { asm volatile("bar.sync %0, %1;" :: "r"(id), "r"(n) : "memory"); }
__device__ __forceinline__ void bar_arrive(int id, int n) { asm volatile("bar.arrive %0, %1;" :: "r"(id), "r"(n) : "memory"); }

__device__ __forceinline__ float bf_lo(uint32_t w) { return __uint_as_float(w << 16); }
__device__ __forceinline__ float bf_hi(uint32_t w) { return __uint_as_float(w & 0xFFFF0000u); }
__device__ __forceinline__ uint32_t pack_bf(float lo, float hi) { uint32_t r; asm("cvt.rn.bf16x2.f32 %0, %1, %2;" : "=r"(r) : "f"(hi), "f"(lo)); return r; }
__device__ __forceinline__ uint32_t pack_h(float lo, float hi) { uint32_t r; asm("cvt.rn.f16x2.f32 %0, %1, %2;" : "=r"(r) : "f"(hi), "f"(lo)); return r; }
__device__ __forceinline__ uint32_t pack_hv(float lo, float hi) { uint32_t r; asm volatile("cvt.rn.f16x2.f32 %0, %1, %2;" : "=r"(r) : "f"(hi), "f"(lo) : "memory"); return r; }
__device__ __forceinline__ float bfr(float x) { return bf_lo(pack_bf(x, 0.f)); }
__device__ __forceinline__ uint32_t bf_sub2(uint32_t a, uint32_t b) { __nv_bfloat162 r = __hsub2(*(__nv_bfloat162*)&a, *(__nv_bfloat162*)&b); return *(uint32_t*)&r; }
__device__ __forceinline__ uint32_t bf_add2(uint32_t a, uint32_t b) { __nv_bfloat162 r = __hadd2(*(__nv_bfloat162*)&a, *(__nv_bfloat162*)&b); return *(uint32_t*)&r; }
__device__ __forceinline__ uint32_t bf_mul2(uint32_t a, uint32_t b) { __nv_bfloat162 r = __hmul2(*(__nv_bfloat162*)&a, *(__nv_bfloat162*)&b); return *(uint32_t*)&r; }
__device__ __forceinline__ float2 h2f(uint32_t w) { return __half22float2(*(__half2*)&w); }
__device__ __forceinline__ float ex2(float x) { float r; asm("ex2.approx.ftz.f32 %0, %1;" : "=f"(r) : "f"(x)); return r; }
__device__ __forceinline__ float warp_sum(float v) {
#pragma unroll
  for (int o = 16; o > 0; o >>= 1) v += __shfl_xor_sync(0xffffffffu, v, o);
  return v;
}
__device__ __forceinline__ void mma_f16_f32(float* d, uint32_t a0, uint32_t a1, uint32_t a2, uint32_t a3, uint32_t b0, uint32_t b1) {
  asm volatile("mma.sync.aligned.m16n8k16.row.col.f32.f16.f16.f32 {%0,%1,%2,%3}, {%4,%5,%6,%7}, {%8,%9}, {%0,%1,%2,%3};"
               : "+f"(d[0]), "+f"(d[1]), "+f"(d[2]), "+f"(d[3]) : "r"(a0), "r"(a1), "r"(a2), "r"(a3), "r"(b0), "r"(b1));
}
__device__ __forceinline__ void mma_f16_f16(uint32_t& d0, uint32_t& d1, uint32_t a0, uint32_t a1, uint32_t a2, uint32_t a3, uint32_t b0, uint32_t b1) {
  asm volatile("mma.sync.aligned.m16n8k16.row.col.f16.f16.f16.f16 {%0,%1}, {%2,%3,%4,%5}, {%6,%7}, {%0,%1};"
               : "+r"(d0), "+r"(d1) : "r"(a0), "r"(a1), "r"(a2), "r"(a3), "r"(b0), "r"(b1));
}
__device__ __forceinline__ void mma_bf16(float* d, uint32_t a0, uint32_t a1, uint32_t a2, uint32_t a3, uint32_t b0, uint32_t b1) {
  asm volatile("mma.sync.aligned.m16n8k16.row.col.f32.bf16.bf16.f32 {%0,%1,%2,%3}, {%4,%5,%6,%7}, {%8,%9}, {%0,%1,%2,%3};"
               : "+f"(d[0]), "+f"(d[1]), "+f"(d[2]), "+f"(d[3]) : "r"(a0), "r"(a1), "r"(a2), "r"(a3), "r"(b0), "r"(b1));
}
__device__ __forceinline__ void mma_bf16_k8(float* d, uint32_t a0, uint32_t a1, uint32_t b0) {
  asm volatile("mma.sync.aligned.m16n8k8.row.col.f32.bf16.bf16.f32 {%0,%1,%2,%3}, {%4,%5}, {%6}, {%0,%1,%2,%3};"
               : "+f"(d[0]), "+f"(d[1]), "+f"(d[2]), "+f"(d[3]) : "r"(a0), "r"(a1), "r"(b0));
}

__device__ __forceinline__ void wg_fence() { asm volatile("wgmma.fence.sync.aligned;" ::: "memory"); }
__device__ __forceinline__ void wg_commit() { asm volatile("wgmma.commit_group.sync.aligned;" ::: "memory"); }
template <int N> __device__ __forceinline__ void wg_wait() { asm volatile("wgmma.wait_group.sync.aligned %0;" :: "n"(N) : "memory"); }
template <int TB> __device__ __forceinline__ void wgmma32(float* d, const uint32_t* a, uint32_t dlo, uint32_t dhi) {
  asm volatile("{ .reg .b64 dd; mov.b64 dd, {%20, %21}; wgmma.mma_async.sync.aligned.m64n32k16.f32.f16.f16 "
               "{%0,%1,%2,%3,%4,%5,%6,%7,%8,%9,%10,%11,%12,%13,%14,%15}, {%16,%17,%18,%19}, dd, 1, 1, 1, %22; }"
               : "+f"(d[0]), "+f"(d[1]), "+f"(d[2]), "+f"(d[3]), "+f"(d[4]), "+f"(d[5]), "+f"(d[6]), "+f"(d[7]), "+f"(d[8]), "+f"(d[9]), "+f"(d[10]), "+f"(d[11]), "+f"(d[12]), "+f"(d[13]), "+f"(d[14]), "+f"(d[15])
               : "r"(a[0]), "r"(a[1]), "r"(a[2]), "r"(a[3]), "r"(dlo), "r"(dhi), "n"(TB));
}
template <int TB> __device__ __forceinline__ void wgmma96(float* d, const uint32_t* a, uint32_t dlo, uint32_t dhi) {
  asm volatile("{ .reg .b64 dd; mov.b64 dd, {%52, %53}; wgmma.mma_async.sync.aligned.m64n96k16.f32.f16.f16 "
               "{%0,%1,%2,%3,%4,%5,%6,%7,%8,%9,%10,%11,%12,%13,%14,%15,%16,%17,%18,%19,%20,%21,%22,%23,%24,%25,%26,%27,%28,%29,%30,%31,%32,%33,%34,%35,%36,%37,%38,%39,%40,%41,%42,%43,%44,%45,%46,%47}, {%48,%49,%50,%51}, dd, 1, 1, 1, %54; }"
               : "+f"(d[0]), "+f"(d[1]), "+f"(d[2]), "+f"(d[3]), "+f"(d[4]), "+f"(d[5]), "+f"(d[6]), "+f"(d[7]), "+f"(d[8]), "+f"(d[9]), "+f"(d[10]), "+f"(d[11]), "+f"(d[12]), "+f"(d[13]), "+f"(d[14]), "+f"(d[15]), "+f"(d[16]), "+f"(d[17]), "+f"(d[18]), "+f"(d[19]), "+f"(d[20]), "+f"(d[21]), "+f"(d[22]), "+f"(d[23]), "+f"(d[24]), "+f"(d[25]), "+f"(d[26]), "+f"(d[27]), "+f"(d[28]), "+f"(d[29]), "+f"(d[30]), "+f"(d[31]), "+f"(d[32]), "+f"(d[33]), "+f"(d[34]), "+f"(d[35]), "+f"(d[36]), "+f"(d[37]), "+f"(d[38]), "+f"(d[39]), "+f"(d[40]), "+f"(d[41]), "+f"(d[42]), "+f"(d[43]), "+f"(d[44]), "+f"(d[45]), "+f"(d[46]), "+f"(d[47])
               : "r"(a[0]), "r"(a[1]), "r"(a[2]), "r"(a[3]), "r"(dlo), "r"(dhi), "n"(TB));
}
template <int TB> __device__ __forceinline__ void wgmma96_init(float* d, const uint32_t* a, uint32_t dlo, uint32_t dhi) {
  asm volatile("{ .reg .b64 dd; mov.b64 dd, {%52, %53}; wgmma.mma_async.sync.aligned.m64n96k16.f32.f16.f16 "
               "{%0,%1,%2,%3,%4,%5,%6,%7,%8,%9,%10,%11,%12,%13,%14,%15,%16,%17,%18,%19,%20,%21,%22,%23,%24,%25,%26,%27,%28,%29,%30,%31,%32,%33,%34,%35,%36,%37,%38,%39,%40,%41,%42,%43,%44,%45,%46,%47}, {%48,%49,%50,%51}, dd, 0, 1, 1, %54; }"
               : "=f"(d[0]), "=f"(d[1]), "=f"(d[2]), "=f"(d[3]), "=f"(d[4]), "=f"(d[5]), "=f"(d[6]), "=f"(d[7]), "=f"(d[8]), "=f"(d[9]), "=f"(d[10]), "=f"(d[11]), "=f"(d[12]), "=f"(d[13]), "=f"(d[14]), "=f"(d[15]), "=f"(d[16]), "=f"(d[17]), "=f"(d[18]), "=f"(d[19]), "=f"(d[20]), "=f"(d[21]), "=f"(d[22]), "=f"(d[23]), "=f"(d[24]), "=f"(d[25]), "=f"(d[26]), "=f"(d[27]), "=f"(d[28]), "=f"(d[29]), "=f"(d[30]), "=f"(d[31]), "=f"(d[32]), "=f"(d[33]), "=f"(d[34]), "=f"(d[35]), "=f"(d[36]), "=f"(d[37]), "=f"(d[38]), "=f"(d[39]), "=f"(d[40]), "=f"(d[41]), "=f"(d[42]), "=f"(d[43]), "=f"(d[44]), "=f"(d[45]), "=f"(d[46]), "=f"(d[47])
               : "r"(a[0]), "r"(a[1]), "r"(a[2]), "r"(a[3]), "r"(dlo), "r"(dhi), "n"(TB));
}
template <int TB> __device__ __forceinline__ void wgmma32_init(float* d, const uint32_t* a, uint32_t dlo, uint32_t dhi) {
  asm volatile("{ .reg .b64 dd; mov.b64 dd, {%20, %21}; wgmma.mma_async.sync.aligned.m64n32k16.f32.f16.f16 "
               "{%0,%1,%2,%3,%4,%5,%6,%7,%8,%9,%10,%11,%12,%13,%14,%15}, {%16,%17,%18,%19}, dd, 0, 1, 1, %22; }"
               : "=f"(d[0]), "=f"(d[1]), "=f"(d[2]), "=f"(d[3]), "=f"(d[4]), "=f"(d[5]), "=f"(d[6]), "=f"(d[7]), "=f"(d[8]), "=f"(d[9]), "=f"(d[10]), "=f"(d[11]), "=f"(d[12]), "=f"(d[13]), "=f"(d[14]), "=f"(d[15])
               : "r"(a[0]), "r"(a[1]), "r"(a[2]), "r"(a[3]), "r"(dlo), "r"(dhi), "n"(TB));
}
__device__ __forceinline__ void wgmma64h(uint32_t* d, uint32_t a0, uint32_t a1, uint32_t a2, uint32_t a3, uint32_t dlo, uint32_t dhi) {
  asm volatile("{ .reg .b64 dd; mov.b64 dd, {%20, %21}; wgmma.mma_async.sync.aligned.m64n64k16.f16.f16.f16 "
               "{%0,%1,%2,%3,%4,%5,%6,%7,%8,%9,%10,%11,%12,%13,%14,%15}, {%16,%17,%18,%19}, dd, 1, 1, 1, 0; }"
               : "+r"(d[0]), "+r"(d[1]), "+r"(d[2]), "+r"(d[3]), "+r"(d[4]), "+r"(d[5]), "+r"(d[6]), "+r"(d[7]), "+r"(d[8]), "+r"(d[9]), "+r"(d[10]), "+r"(d[11]), "+r"(d[12]), "+r"(d[13]), "+r"(d[14]), "+r"(d[15])
               : "r"(a0), "r"(a1), "r"(a2), "r"(a3), "r"(dlo), "r"(dhi));
}
__device__ __forceinline__ void wgmma64h_init(uint32_t* d, uint32_t a0, uint32_t a1, uint32_t a2, uint32_t a3, uint32_t dlo, uint32_t dhi) {
  asm volatile("{ .reg .b64 dd; mov.b64 dd, {%20, %21}; wgmma.mma_async.sync.aligned.m64n64k16.f16.f16.f16 "
               "{%0,%1,%2,%3,%4,%5,%6,%7,%8,%9,%10,%11,%12,%13,%14,%15}, {%16,%17,%18,%19}, dd, 0, 1, 1, 0; }"
               : "=r"(d[0]), "=r"(d[1]), "=r"(d[2]), "=r"(d[3]), "=r"(d[4]), "=r"(d[5]), "=r"(d[6]), "=r"(d[7]), "=r"(d[8]), "=r"(d[9]), "=r"(d[10]), "=r"(d[11]), "=r"(d[12]), "=r"(d[13]), "=r"(d[14]), "=r"(d[15])
               : "r"(a0), "r"(a1), "r"(a2), "r"(a3), "r"(dlo), "r"(dhi));
}
__device__ __forceinline__ void wgmma40_ss(float* d, uint32_t alo, uint32_t blo, uint32_t hi) {
  asm volatile("{ .reg .b64 da, db; mov.b64 da, {%20, %22}; mov.b64 db, {%21, %22}; "
               "wgmma.mma_async.sync.aligned.m64n40k16.f32.f16.f16 {%0,%1,%2,%3,%4,%5,%6,%7,%8,%9,%10,%11,%12,%13,%14,%15,%16,%17,%18,%19}, da, db, 1, 1, 1, 1, 1; }"
               : "+f"(d[0]), "+f"(d[1]), "+f"(d[2]), "+f"(d[3]), "+f"(d[4]), "+f"(d[5]), "+f"(d[6]), "+f"(d[7]), "+f"(d[8]), "+f"(d[9]), "+f"(d[10]), "+f"(d[11]), "+f"(d[12]), "+f"(d[13]), "+f"(d[14]), "+f"(d[15]), "+f"(d[16]), "+f"(d[17]), "+f"(d[18]), "+f"(d[19])
               : "r"(alo), "r"(blo), "r"(hi));
}
__device__ __forceinline__ void wgmma40_ss_init(float* d, uint32_t alo, uint32_t blo, uint32_t hi) {
  asm volatile("{ .reg .b64 da, db; mov.b64 da, {%20, %22}; mov.b64 db, {%21, %22}; "
               "wgmma.mma_async.sync.aligned.m64n40k16.f32.f16.f16 {%0,%1,%2,%3,%4,%5,%6,%7,%8,%9,%10,%11,%12,%13,%14,%15,%16,%17,%18,%19}, da, db, 0, 1, 1, 1, 1; }"
               : "=f"(d[0]), "=f"(d[1]), "=f"(d[2]), "=f"(d[3]), "=f"(d[4]), "=f"(d[5]), "=f"(d[6]), "=f"(d[7]), "=f"(d[8]), "=f"(d[9]), "=f"(d[10]), "=f"(d[11]), "=f"(d[12]), "=f"(d[13]), "=f"(d[14]), "=f"(d[15]), "=f"(d[16]), "=f"(d[17]), "=f"(d[18]), "=f"(d[19])
               : "r"(alo), "r"(blo), "r"(hi));
}
__device__ __forceinline__ float vzero() { float v; asm volatile("mov.b32 %0, 0;" : "=f"(v)); return v; }
__device__ __forceinline__ void tma_box(uint32_t dst, const CUtensorMap* tm, uint32_t mb, int x, int y) {
  asm volatile("cp.async.bulk.tensor.2d.shared::cluster.global.mbarrier::complete_tx::bytes [%0], [%1, {%3, %4}], [%2];"
               :: "r"(dst), "l"(tm), "r"(mb), "r"(x), "r"(y) : "memory");
}
__device__ __forceinline__ void l2_prefetch(const void* src, uint32_t bytes) {
  asm volatile("cp.async.bulk.prefetch.L2.global [%0], %1;" :: "l"(src), "r"(bytes) : "memory");
}
__device__ __forceinline__ uint32_t uni(uint32_t v) {
  uint32_t r; asm volatile("shfl.sync.idx.b32 %0, %1, 0, 0x1f, 0xffffffff;" : "=r"(r) : "r"(v)); return r;
}
__device__ __forceinline__ int fresh_tid() { int v; asm volatile("mov.u32 %0, %tid.x;" : "=r"(v)); return v; }

struct Params {
  const unsigned char* x;
  Scratch* s;
  int off[7];
  uint32_t zero;
  uint32_t* out;
  const uint32_t* dskip;
  const uint32_t* w_r;
  long long* ts;
  const unsigned char* far[7];
  uint32_t sched[2][17];
};
__device__ __forceinline__ uint32_t ldnc32(const void* p) { uint32_t v; asm volatile("ld.global.nc.b32 %0, [%1];" : "=r"(v) : "l"(p)); return v; }
__device__ __forceinline__ uint32_t ldnc16(const void* p) { uint16_t v; asm volatile("ld.global.nc.u16 %0, [%1];" : "=h"(v) : "l"(p)); return v; }
__device__ __forceinline__ uint4 ldnc128(const void* p) { uint4 v; asm volatile("ld.global.nc.v4.b32 {%0,%1,%2,%3}, [%4];" : "=r"(v.x), "=r"(v.y), "=r"(v.z), "=r"(v.w) : "l"(p)); return v; }
__device__ __forceinline__ void mbar_wait(uint32_t mb, uint32_t ph = 0) {
#pragma unroll 1
  for (int it = 0; it < SPIN_MAX; it++) {
    uint32_t ok;
    asm volatile("{ .reg .pred q; mbarrier.try_wait.parity.shared::cta.b64 q, [%1], %2; selp.u32 %0, 1, 0, q; }" : "=r"(ok) : "r"(mb), "r"(ph) : "memory");
    if (ok) break;
  }
}
__device__ __forceinline__ uint32_t mbar_test(uint32_t mb) {
  uint32_t ok;
  asm volatile("{ .reg .pred q; mbarrier.test_wait.parity.shared::cta.b64 q, [%1], 0; selp.u32 %0, 1, 0, q; }" : "=r"(ok) : "r"(mb) : "memory");
  return ok;
}
__device__ __forceinline__ void mbar_arrive(uint32_t mb) { asm volatile("mbarrier.arrive.shared::cta.b64 _, [%0];" :: "r"(mb) : "memory"); }
__device__ __forceinline__ uint32_t ldg16(const void* p) { uint16_t v; asm volatile("ld.global.u16 %0, [%1];" : "=h"(v) : "l"(p) : "memory"); return v; }
__device__ __forceinline__ uint32_t ldr16(const void* p) { uint16_t v; asm volatile("ld.relaxed.gpu.global.u16 %0, [%1];" : "=h"(v) : "l"(p) : "memory"); return v; }
__device__ __forceinline__ void fence_async() { asm volatile("fence.proxy.async.shared::cta;" ::: "memory"); }
#define SPIN_WHILE(cond, body) _Pragma("unroll 1") for (int _it = 0; _it < SPIN_MAX && __any_sync(0xffffffffu, (cond)); _it++) { body; }

struct LnC { uint32_t m2, rh2, rl2; };
__device__ __forceinline__ float diag_sum(float d0, float d1, int t) {
  float q = __shfl_sync(0xffffffffu, d0, 9 * t) + __shfl_sync(0xffffffffu, d1, 9 * t + 4);
  q += __shfl_xor_sync(0xffffffffu, q, 1);
  return q + __shfl_xor_sync(0xffffffffu, q, 2);
}
__device__ __forceinline__ LnC ln_consts(float s, float q, float& r) {
  const float mean = s * (1.f / DM);
  const float var = fmaxf(fmaf(-mean, mean, q * (1.f / DM)), 0.f);
  float sd;
  asm("sqrt.approx.ftz.f32 %0, %1;" : "=f"(sd) : "f"(bfr(bfr(var) + 1e-5f)));
  asm("rcp.approx.ftz.f32 %0, %1;" : "=f"(r) : "f"(bfr(sd)));
  LnC c;
  c.m2 = pack_bf(mean, mean);
  c.rh2 = pack_bf(r, r);
  const float rl = r - bf_lo(c.rh2);
  c.rl2 = pack_bf(rl, rl);
  return c;
}
__device__ __forceinline__ float quad_sum(float s) { s += __shfl_xor_sync(0xffffffffu, s, 1); return s + __shfl_xor_sync(0xffffffffu, s, 2); }
__device__ __forceinline__ uint32_t bf_fma2(uint32_t a, uint32_t b, uint32_t c) {
  __nv_bfloat162 r = __hfma2(*(const __nv_bfloat162*)&a, *(const __nv_bfloat162*)&b, *(const __nv_bfloat162*)&c);
  return *(uint32_t*)&r;
}
__device__ __forceinline__ uint32_t ln_apply(uint32_t w, uint32_t m2, uint32_t rh2, uint32_t rl2) {
  const uint32_t d = bf_sub2(w, m2);
  return bf_fma2(d, rh2, bf_mul2(d, rl2));
}

__device__ __forceinline__ float2 cis(float mag_log2, float rev) {
  const float m = ex2(mag_log2), ang = rev * 6.283185307179586f;
  return make_float2(m * __cosf(ang), m * __sinf(ang));
}
__device__ __forceinline__ float2 csq(float2 a) { return make_float2(fmaf(a.x, a.x, -a.y * a.y), (a.x + a.x) * a.y); }
__device__ __forceinline__ float2 cmul(float2 a, float2 b) { return make_float2(fmaf(a.x, b.x, -a.y * b.y), fmaf(a.x, b.y, a.y * b.x)); }
__device__ __forceinline__ void pmul(uint32_t xr, uint32_t xi, uint32_t w, uint32_t& yr, uint32_t& yi) {
  const __half2 XR = *(__half2*)&xr, XI = *(__half2*)&xi, W = *(__half2*)&w;
  const __half2 a = __hfma2(__hneg2(XI), __high2half2(W), __hmul2(XR, __low2half2(W)));
  const __half2 b = __hfma2(XI, __low2half2(W), __hmul2(XR, __high2half2(W)));
  yr = *(const uint32_t*)&a; yi = *(const uint32_t*)&b;
}
__device__ __forceinline__ uint32_t pk(float2 a) { return pack_h(a.x, a.y); }

struct KgState { float2 c0, z8; float kl; uint32_t w64, w128, w192; };
__device__ __forceinline__ void kgen_tables_n(const uint32_t (&raw)[7], uint32_t scr, int wt, KgState& k) {
  const uint32_t dst = scr + 16384 + wt * 16;
  const float dt = bfr(ex2(bf_lo(raw[6]) * 1.4426950408889634f));
  const float th = dt * bf_lo(raw[1]);
  const float br = dt * bf_lo(raw[2]), bi = dt * bf_lo(raw[3]);
  const float Cr = bf_lo(raw[4]), Ci = bf_lo(raw[5]);
  k.c0 = make_float2(fmaf(Cr, br, -Ci * bi), fmaf(Cr, bi, Ci * br));
  const uint32_t mx = __reduce_max_sync(0xffffffffu, __float_as_uint(fmaxf(fabsf(k.c0.x), fabsf(k.c0.y))));
  const float a2 = dt * bf_lo(raw[0]) * 1.4426950408889634f;
  const float rh = th * 0.15915494309189535f;
  const float rl = fmaf(th, (float)(0.15915494309189535 - (double)0.15915494309189535f), fmaf(th, 0.15915494309189535f, -rh));
  const float rf = rh - rintf(rh);
  const float2 z1 = cis(a2, rf + rl);
  const float p64 = rf * 64.f;
  const float2 z64 = cis(a2 * 64.f, fmaf(64.f, rl, p64 - rintf(p64)));
  const float2 z2 = csq(z1), z128 = csq(z64), z3 = cmul(z2, z1), z4 = csq(z2), z256 = csq(z128), z6 = csq(z3), z512 = csq(z256);
  k.z8 = csq(z4);
  k.w64 = pk(z64); k.w128 = pk(z128); k.w192 = pk(cmul(z128, z64));
  sts128(dst, 0x00003C00u, pk(z2), pk(z4), pk(z6));
  const float2 z1024 = csq(z512), z768 = cmul(z512, z256);
  sts128(dst + 2048, pk(z1), pk(z3), pk(cmul(z4, z1)), pk(cmul(z4, z3)));
  const float2 z2048 = csq(z1024);
  k.kl = fmaf(k.c0.x, z2048.x, -k.c0.y * z2048.y);
  sts128(dst + 4096, pk(z256), pk(cmul(z256, z2)), pk(cmul(z256, z4)), pk(cmul(z256, z6)));
  sts128(dst + 6144, pk(z512), pk(cmul(z512, z4)), pk(z768), pk(cmul(z768, z4)));
  sts128(dst + 8192, pk(z1024), pk(cmul(z1024, z256)), pk(cmul(z1024, z512)), pk(cmul(z1024, z768)));
  sts32(scr + W_MISC + (wt >> 5) * 4, mx);
}
__device__ __forceinline__ int kgen_tables_m(uint32_t scr, int wt, const KgState& k) {
  const uint32_t dst = scr + wt * 16;
  const uint4 e4 = lds128(scr + W_MISC);
  const float2 z16 = csq(k.z8), z32 = csq(z16);
  const int em = max(min((int)(max(max(e4.x, e4.y), max(e4.z, e4.w)) >> 23), 238), 16);
  const float sc = __uint_as_float((uint32_t)(127 + 4 + 127 - em) << 23);
  sts32(scr + W_MISC + 16 + (wt >> 5) * 4, __reduce_add_sync(0xffffffffu, __float2int_rn(k.kl * sc * 262144.f)));
  const float2 c0 = make_float2(k.c0.x * sc, k.c0.y * sc);
  const float2 c1 = cmul(c0, k.z8), c2 = cmul(c0, z16), c4 = cmul(c0, z32), c3 = cmul(c1, z16), c5 = cmul(c1, z32), c6 = cmul(c2, z32), c7 = cmul(c3, z32);
  uint32_t pr[4], pi[4], yr[4], yi[4];
  pr[0] = pack_h(c0.x, c1.x); pi[0] = pack_h(c0.y, c1.y);
  pr[1] = pack_h(c2.x, c3.x); pi[1] = pack_h(c2.y, c3.y);
  pr[2] = pack_h(c4.x, c5.x); pi[2] = pack_h(c4.y, c5.y);
  pr[3] = pack_h(c6.x, c7.x); pi[3] = pack_h(c6.y, c7.y);
  sts128(dst, pr[0], pr[1], pr[2], pr[3]); sts128(dst + 2048, pi[0], pi[1], pi[2], pi[3]);
#pragma unroll
  for (int q = 1; q < 4; q++) {
    const uint32_t w = q == 1 ? k.w64 : q == 2 ? k.w128 : k.w192;
#pragma unroll
    for (int i = 0; i < 4; i++) pmul(pr[i], pi[i], w, yr[i], yi[i]);
    sts128(dst + q * 4096, yr[0], yr[1], yr[2], yr[3]); sts128(dst + q * 4096 + 2048, yi[0], yi[1], yi[2], yi[3]);
  }
  return em;
}
__device__ __forceinline__ void kgen_build(uint32_t tb, uint32_t sc, int wg, int wt, uint32_t k0, uint32_t k1, uint32_t k2) {
  const uint32_t kt = tb + W_KT;
  const int ix = ((wt >> 2) + (wt & 3) * 32 - 1) & 127;
  const uint32_t a3 = tb + W_CW + 32 + ((ix & 1) ? 0 : 304) + (ix >> 1) * 4;
  const uint32_t v3 = wt ? k2 : k2 >> 16;
  sts32(sc + 4 + wt * 4, __byte_perm(k0, k1, 0x5432));
  sts16(sc + 544 + (wt & ~3) + (wt & 1) * 2 + (wt & 2) * 64, k1 >> 16);
  sts16(a3, v3); sts16(a3 + 6, v3);
  if ((unsigned)(wt - 32) < 18u) sts128(kt + (wt < 36 ? -512 : 64 + 4128 - 576) + wt * 16, 0, 0, 0, 0);
  if (wt == 127) sts32(sc, k0 & 0xFFFF0000u);
  if (wt == 0) { sts32(sc + 516, k1); sts16(sc + 800, k2); }
  bar_sync(1 + wg, 128);
  const uint32_t cw = tb + W_CW + 32 + (wt >> 6) * 48 + wt * 4;
  const uint32_t pv = lds32(sc + wt * 4), nx = lds32(sc + 8 + wt * 4), c2 = lds16(sc + 544 + wt * 2), n2 = lds16(sc + 546 + wt * 2);
  sts128(tb + W_L3 + 1024 + (wt >> 6) * 1024 + wt * 16, lds32(cw), lds32(cw - 8), lds32(cw - 16), lds32(cw - 24));
  const bool odd = wt & 1;
  sts64(kt + 64 + wt * 8, __byte_perm(k0, pv, 0x5410), __byte_perm(k0, 0, 0x1032));
  sts64(kt + 64 + 1024 + wt * 8, __byte_perm(k1, pv, (odd || wt == 0) ? 0x7610 : 0x1010), __byte_perm(k1, nx, odd ? 0x1076 : 0x1010));
  const uint32_t cc = c2 * 0x10001u, nc = __byte_perm(n2, c2, 0x5410), nn = n2 * 0x10001u;
  sts128(kt + 64 + 2048 + wt * 16, cc, cc, odd ? nc : cc, odd ? nn : nc);
  if (wt == 127) { sts128(kt + 64 + 4096, nn, nn, nn, nn); sts128(kt + 64 + 4112, nn, nn << 16, 0, 0); }
}

__device__ __forceinline__ void load_a(uint32_t (&a)[4], uint32_t kp, int j) {
  a[0] = lds32(kp + 64 * j); a[1] = lds32(kp + 64 * j + 512); a[2] = lds32(kp + 64 * j - 32); a[3] = lds32(kp + 64 * j + 480);
}
__device__ __forceinline__ uint32_t band(int d, int lo, int hi) {
  return ((unsigned)(d - lo) <= (unsigned)(hi - lo) ? 1u : 0u) | ((unsigned)(d - 1 - lo) <= (unsigned)(hi - lo) ? 0x10000u : 0u);
}
__device__ __forceinline__ uint32_t hadd2u(uint32_t a, uint32_t b) { __half2 r = __hadd2(*(__half2*)&a, *(__half2*)&b); return *(uint32_t*)&r; }

__device__ __forceinline__ void zero_pads(uint32_t tb, int wt) {
  sts128(tb + W_L3 + (wt >> 6) * 1024 + wt * 16, 0, 0, 0, 0);
  if ((wt & 63) < 3) sts128(tb + W_CW + (wt >> 6) * 304 + (wt & 63) * 16, 0, 0, 0, 0);
}
__device__ __forceinline__ uint32_t tr_base(int lane) {
  return OFF_YT + (2 * (lane >> 3) + (lane & 1)) * YT_PITCH + ((lane >> 1) & 1) * (8 * YT_PITCH + 64) + ((lane >> 2) & 1) * 16;
}

__device__ __forceinline__ uint32_t sc_addr(int tp) { return OFF_YT + (tp < 16 ? tp * YT_PITCH + (tp >> 3) * 64 + 1152 : 8 * YT_PITCH - 512 + tp * 32); }
#define X_NE 2
#define X_SCT 10000
#define X_DELTA 400
#define X_DSTEP 2000
#define X_PF0 2500
#define X_PFD 600
#define X_TD 520
#define X_WS 6
#define X_OR 8
#define X_ABS 5100
#define X_XD 0
#define X_RD 900
#define X_HD 500
#define X_PD 1150
#define X_PROMO 2
#define X_YD2 500
#define X_GO 2
#define X_GW 2
#define X_NS 4700
#define X_XS 0
#define X_LAG 1800
#define X_YD 1550
struct TMaps { CUtensorMap m[8]; };
__device__ __forceinline__ uint32_t h2bf(uint32_t w) { const float2 f = h2f(w); return pack_bf(f.x, f.y); }
__device__ __forceinline__ uint32_t keep(uint32_t v) { asm volatile("" : "+r"(v)); return v; }
__device__ __forceinline__ uint2 ldr64(const void* p) { uint2 v; asm volatile("{ .reg .b64 t; ld.relaxed.gpu.global.b64 t, [%2]; mov.b64 {%0, %1}, t; }" : "=r"(v.x), "=r"(v.y) : "l"(p) : "memory"); return v; }
__host__ __device__ __forceinline__ uint32_t down_box(int s, bool five) {
  return five ? OFF_W + W_BYTES + 12288 + (s / 3) * (W_BYTES - 12288) + s * 4096 : s < 6 ? OFF_W + W_BYTES + BOX + (s >> 1) * (W_BYTES - 10240) + s * 5120 : OFF_W + (s - 6) * 5120;
}
__device__ __forceinline__ void load_tile(const CUtensorMap* tmx, int i, int c) {
  asm volatile("mbarrier.arrive.expect_tx.shared::cta.b64 _, [%0], 5120;" :: "r"(MB_UL + i * 8) : "memory");
  tma_box(OFF_W + (i < 4 ? i * W_BYTES : ALT) + W_UP, tmx, MB_UL + i * 8, (i < 4 ? i * 128 + c : 512 + (c >> 1)) * 16, -32);
}
template <bool FAR> __device__ __forceinline__ void load_params(const Params& p, uint32_t ch, int wt, uint32_t dst, bool on) {
  const int o01 = (wt & 16) ? p.off[1] : p.off[0], o23 = (wt & 16) ? p.off[3] : p.off[2], o45 = (wt & 16) ? p.off[5] : p.off[4];
  const int o = (wt & 64) ? ((wt & 32) ? p.off[6] : o45) : ((wt & 32) ? o23 : o01);
  const unsigned char* b = FAR ? p.far[min(wt >> 4, 6)] : p.x + (long long)o * 16;
  asm volatile("{ .reg .pred q; setp.ne.u32 q, %2, 0; @q cp.async.cg.shared.global [%0], [%1], 16; }"
               :: "r"(dst + wt * 16), "l"(b + (wt < 96 ? ch * 256 + (wt & 15) * 16 : (ch >> 3) * 16)), "r"((uint32_t)(on && wt < 97)) : "memory");
}

struct ConvC { uint32_t ca, cb, bands; };
__device__ __forceinline__ ConvC conv_consts(int w, int lane) {
  const int h = w & 1, P = w >> 1, d0 = 8 * h + (lane >> 2) - 2 * (lane & 3);
  ConvC k;
  k.ca = keep((W_KT + (16 + 256 * P + d0) * 4) | ((W_UP + (32 + 64 * P + lane) * 32 + ((h ^ (lane >> 2)) & 1) * 16) << 16));
  k.cb = keep(lane < 8 ? 0xFFFEFFFEu : ~0u);
  k.bands = keep(band(d0, 12, 20) + 2 * band(d0 + 8, 12, 20) + 4 * band(d0 + 16, 12, 20) + 8 * band(d0 + 24, 12, 20)
                 + 16 * band(d0 - 8, 5, 11) + 32 * band(d0, 5, 11) + 64 * band(d0 + 8, 5, 11) + 128 * band(d0 + 16, 5, 11));
  return k;
}
__device__ __forceinline__ void conv_item(uint32_t tb, const ConvC& cv, uint32_t zero, const CUtensorMap* tmx, int ch, int warp, int lane, bool hold, bool more) {
  const bool go = more && warp == 0 && lane == 0;
  const uint32_t kp = tb + (cv.ca & 0xFFFFu);
  const uint32_t dlo = ((tb + W_UP) >> 4) + 64 + (1u << 16), dhi = 16u | (3u << 30);
  const bool P = warp & 2;
  float a32[16], a96[48];
  uint32_t A[40][4];
#define STEP(J) { wgmma96<0>(a96, A[J], dlo + 64 - 2 * (J), dhi); if ((J) == 0) wgmma32_init<0>(a32, A[J], dlo, dhi); else if ((J) < 8) wgmma32<0>(a32, A[J], (dlo ^ zero) - 2 * (J), dhi); }
#define LD(J) load_a(A[J], kp, J);
#define FIRST(J) wg_fence(); STEP(J) wg_commit(); wg_wait<1>(); wg_fence();
  {
    uint32_t win[16], x9[4], x7[4], e[4], f[4];
    const uint32_t bz = keep(cv.bands);
#define BAND(i) keep((bz & (0x10001u << (i))) * (0x3C00u >> (i)))
    e[0] = lds32(kp + (P ? 3232 : 4096)); e[2] = lds32(kp + (P ? 3200 : 4064)); e[1] = keep(bz & 0x100u); e[3] = keep(bz & 0x200u);
    f[3] = lds32(kp + (P ? 3200 : 4128)); f[0] = keep(bz & 0x4000u); f[1] = keep(bz & 0x8000u); f[2] = keep(bz & 0x300u);
    const uint32_t q[12] = {BAND(0), BAND(5), keep(bz & 0x400u), BAND(4), BAND(2), BAND(7), BAND(1), BAND(6), keep(bz & 0x800u), keep(bz & 0x1000u), BAND(3), keep(bz & 0x2000u)};
#undef BAND
    const uint32_t ta = keep(tb + W_UP + 1024 + (warp & 3) * 1024 + lane * 32 + (lane & 4) * 4);
    if (X_GO && hold) mbar_wait(MB_GO);
#pragma unroll 1
    for (int it = 0; it < SPIN_MAX; it++) {
      if (ch < 512) mbar_wait(MB_UL + (warp >> 2) * 8, it & 1);
      if (it == 1) TS(13);
      TS(3);
      wg_fence();
      wgmma64h_init(win, q[0], q[1], q[2], q[3], dlo, dhi);
      wgmma64h(win, q[4], q[5], q[6], q[7], dlo - 2, dhi);
      wgmma64h(win, q[8], q[9], q[10], q[11], dlo - 4, dhi);
      wg_commit();
      wgmma96_init<0>(a96, e, dlo - 64, dhi);
      wgmma96<0>(a96, f, dlo - 50, dhi);
      wg_commit();
      if (ch >= 512) break;
      uint32_t r0, r1, r2, r3, ok;
      ldsm4(ta, r0, r1, r2, r3);
      asm volatile("{ .reg .pred q; setp.ne.u32 q, %1, 0; barrier.red.and.pred q, %2, 128, q; selp.u32 %0, 1, 0, q; }" : "=r"(ok) : "r"((r0 & r1 & r2 & r3 & 1u) | (lane & 3)), "r"(1 + (warp >> 2)) : "memory");
      if (ok) break;
      wg_wait<0>();
      if ((warp & 3) == 0 && lane == 0) load_tile(tmx - 1, warp >> 2, ch & 127);
    }
    wg_wait<1>();
#pragma unroll
    for (int i = 0; i < 4; i++) {
      const int tl = 2 * ((i & 1) + ((i & 2) ? 0 : 4));
      x9[i] = P ? win[tl + 4] : win[tl]; x7[i] = P ? win[tl + 5] : win[tl + 1];
    }
    const uint32_t l3lo = ((tb + W_L3) >> 4) + (32u << 16);
    wg_fence();
    wgmma96<0>(a96, x9, l3lo, 8);
    wgmma96<0>(a96, x7, l3lo + 128, 8);
    wg_commit();
  }
  LD(32) LD(33) LD(34) LD(35)
  FIRST(32) STEP(33) STEP(34) STEP(35) wg_commit();
  LD(36) LD(37) LD(38)
  FIRST(36) STEP(37) STEP(38) wg_commit();
  LD(39) LD(0)
  TS(17);
  if (X_GO == 1 && go) mbar_arrive(MB_GO);
  FIRST(39) STEP(0) wg_commit();
  LD(1) LD(2) LD(3)
  FIRST(1) STEP(2) STEP(3) wg_commit();
  LD(4) LD(5)
  if (X_GO == 2 && go) mbar_arrive(MB_GO);
  FIRST(4) STEP(5) wg_commit();
  LD(6) LD(7)
  wg_fence(); STEP(6) STEP(7) wg_commit();
#undef STEP
#undef LD
#undef FIRST
  TS(18);
  if (X_GO == 3 && go) mbar_arrive(MB_GO);
  const uint32_t xc = tb + W_KT + (warp & 3) * 1024 + lane * 16;
  wg_wait<0>();
  uint32_t E[16], o[8];
#define ACC(i) ((i) < 16 ? a32[i] : a96[(i) - 16])
  E[0] = pack_h(a32[0], a32[1]);
#pragma unroll
  for (int i = 1; i < 16; i++) E[i] = pack_h(ACC(4 * i) + ACC(4 * i - 2), ACC(4 * i + 1) + ACC(4 * i - 1));
#undef ACC
#pragma unroll
  for (int j = 0; j < 8; j++) o[j] = P ? (j < 2 ? 0u : E[j - 2]) : E[8 + j];
  sts128(xc, o[0], o[1], o[2], o[3]); sts128(xc + 512, o[4], o[5], o[6], o[7]);
#pragma unroll
  for (int j = 0; j < 8; j++) o[j] = P ? E[6 + j] : E[j];
  TS(25);
  if (more) {
    sts128(xc + 4096, o[0], o[1], o[2], o[3]); sts128(xc + 4608, o[4], o[5], o[6], o[7]);
    bar_arrive(12, 192);
    return;
  }
  bar_sync(1 + (warp >> 2), 128);
  const uint4 vv[2] = {lds128(xc + (P ? -2048 : 2048)), lds128(xc + (P ? -1536 : 2560))};
#pragma unroll
  for (int q = 0; q < 2; q++) {
    const uint4 v = vv[q];
    stsm4t(tb + (cv.ca >> 16) + q * 1024, hadd2u(o[4 * q], v.x) & cv.cb, hadd2u(o[4 * q + 1], v.y) & cv.cb, hadd2u(o[4 * q + 2], v.z) & cv.cb, hadd2u(o[4 * q + 3], v.w) & cv.cb);
  }
  fence_async();
  bar_sync(1 + (warp >> 2), 128);
  if (warp == 0 && lane == 0) mbar_arrive(MB_REL);
  if ((warp & 3) == 3 && lane == 0) {
    asm volatile("cp.async.bulk.tensor.2d.global.shared::cta.bulk_group [%0, {%2, %3}], [%1];" :: "l"(tmx), "r"(tb + W_UP + 1024), "r"(ch * 16), "r"(0) : "memory");
    asm volatile("cp.async.bulk.commit_group;" ::: "memory");
  }
}

template <bool FAR> __global__ void __launch_bounds__(NT, 1)
fused_kernel(const __grid_constant__ Params p, const __grid_constant__ TMaps tm) {
  extern __shared__ __align__(1024) unsigned char smem[];
  const int c = blockIdx.x;
  const bool five = (c & 1) == 0;
  const uint32_t pitch = five ? 64 : 80;
  const uint32_t ones = 0x3F803F80u;
  const int tid = threadIdx.x, lane = tid & 31;
  {
    const int w4 = tid >> 7, k5 = !five && w4 == 3;
    load_params<FAR>(p, k5 ? 512 + (c >> 1) : w4 * 128 + c, tid & 127, OFF_W + w4 * W_BYTES + W_KT + k5 * 2048, w4 != 2 && w4 != 4);
  }
  const int warp = (int)uni(tid >> 5), wg = warp >> 2;
  TS(0);
  if (__builtin_expect(wg == 4, 0)) {
    asm volatile("setmaxnreg.dec.sync.aligned.u32 32;");
    const int role = warp;
    const int u0 = (c >> 1) * 9 + (five ? ((c & 2) ? 5 : 0) : ((c & 2) ? 0 : 4));
    const uint32_t t0 = clock() + c * 4;
    if (role == 16) {
      if (lane < 19) asm volatile("mbarrier.init.shared::cta.b64 [%0], %1;" :: "r"(OFF_MISC + lane * 8), "r"((unsigned)(lane - 2) < 4u ? 4 : 1) : "memory");
      if (lane < 2) asm volatile("mbarrier.arrive.expect_tx.shared::cta.b64 _, [%0], %1;" :: "r"(OFF_MISC + lane * 8), "r"(lane ? (five ? 36864 : 51200) : pitch * 1152) : "memory");
      fence_async();
      bar_arrive(5, 576);
      const CUtensorMap* tmb = &tm.m[five ? 3 : 0];
#pragma unroll 1
      for (int u = 0; u < 17; u++) {
        const uint32_t e = p.sched[five][u], kind = e & 3, s = (e >> 2) & 15, dst = e >> 14;
        if (kind == 3) continue;
        while ((int)(clock() - t0) < X_PF0 + (u < X_NE ? u * X_PFD : X_LAG + u * X_TD)) __nanosleep(20);
        if (e & 0x3FC0) mbar_wait(OFF_MISC + ((e >> 6) & 255));
        if (lane == 0) {
          if (kind == 2) asm volatile("cp.async.bulk.tensor.3d.shared::cluster.global.mbarrier::complete_tx::bytes [%0], [%1, {%3, %4, %5}], [%2];"
                                      :: "r"(dst), "l"(tmb + 2), "r"(MB_D), "r"(0), "r"(u0 * 8), "r"(s) : "memory");
          else tma_box(dst, tmb + kind, MB_GU, u0 * 8, s * 96);
        }
        if (u == 5) TS(2);
        if (u == 10) TS(3);
      }
      TS(4);
      TS_DUMP();
#define FINISH0 bar_sync(12, 192);        \
        _Pragma("unroll 1") for (int w = role & 2; w < (role & 2) + 2; w++) { \
          const uint32_t xa = OFF_W + W_KT + lane * 16, mk = lane < 8 ? 0xFFFEFFFEu : ~0u, ya = OFF_W + W_UP + (32 + lane) * 32 + ((w ^ (lane >> 2)) & 1) * 16 + (w & 2) * 1024; \
          const uint4 a = lds128(xa + 4096 + w * 1024), b = lds128(xa + (w ^ 2) * 1024), d = lds128(xa + 4608 + w * 1024), e = lds128(xa + 512 + (w ^ 2) * 1024); \
          stsm4t(ya, hadd2u(a.x, b.x) & mk, hadd2u(a.y, b.y) & mk, hadd2u(a.z, b.z) & mk, hadd2u(a.w, b.w) & mk); \
          stsm4t(ya + 1024, hadd2u(d.x, e.x) & mk, hadd2u(d.y, e.y) & mk, hadd2u(d.z, e.z) & mk, hadd2u(d.w, e.w) & mk); \
        } \
        fence_async();
    } else if (role == 17) {
      if (smem_u32(smem) != SB) __trap();
      bar_sync(10, 576);
      if (lane == 0) {
        fence_async();
        while ((int)(clock() - t0) < X_NS - c * 4) {}
        asm volatile("cp.async.bulk.global.shared::cta.bulk_group [%0], [%1], 10240;" :: "l"(&p.s->X[c * DM * 2 + 512]), "r"(OFF_G) : "memory");
        asm volatile("cp.async.bulk.commit_group;" ::: "memory");
        asm volatile("cp.async.bulk.wait_group 0;" ::: "memory");
      }
      if (lane == 0) mbar_arrive(MB_GF);
      bar_arrive(11, 96);
      if (five) { FINISH0 bar_arrive(13, 64); }
    } else if (role == 18) {
      sts32(MISC_EPOCH, 0);
      bar_arrive(5, 576);
      uint4* q = lane < 2 ? &p.s->R[c * 2 + lane] : lane < 11 ? &p.s->HS[c * 9 + lane - 2] : lane == 11 ? &p.s->HS[1152 + (c & 7)] : (uint4*)&p.s->FLAG[c * 8];
      if (lane < (c < 8 ? 12 : 11)) str128(q, ~0u, ~0u, ~0u, ~0u);
      const uint32_t ep = __shfl_sync(0xffffffffu, ldr32(q), 31) + 1u;
      sts32(MISC_EPOCH, ep | 0x80000000u);
      TSX(21);
      if (lane == 31) str32(q, ep);
      bar_sync(11, 96);
      if (lane == 0) load_tile(&tm.m[6], 3, c);
      TSX(14);
      mbar_wait(MB_KF + (lane & 3) * 8);
      __syncwarp();
      { const uint2 e = lds64(MISC_EM); if (lane < 2) str128(&p.s->SC[c * 2 + lane], e.x, __byte_perm(e.y, ep, 0x6540), 0, 0); }
      TSX(17);
      while ((int)(clock() - t0) < X_SCT) __nanosleep(100);
      TSX(18);
      {
        uint2 v[4];
#pragma unroll 1
        for (int it = 0; it < SPIN_MAX; it++) {
          uint32_t bad = 0;
#pragma unroll
          for (int q = 0; q < 4; q++) v[q] = ldr64(&p.s->SC[lane * 2 + q * 64]);
#pragma unroll
          for (int q = 0; q < 4; q++) bad |= (v[q].y >> 8) ^ (ep & 0xFFFFFFu);
          if (!__any_sync(0xffffffffu, bad)) break;
        }
        TSX(25);
#pragma unroll
        for (int q = 0; q < 4; q++) {
#pragma unroll
          for (int k = 0; k < 4; k++) asm volatile("st.shared.u8 [%0], %1;" :: "r"(sc_addr(4 * k + q) + lane), "r"(v[q].x >> (8 * k)) : "memory");
          if (lane & 1) asm volatile("st.shared.u8 [%0], %1;" :: "r"(sc_addr(16) + q * 16 + (lane >> 1)), "r"(v[q].y) : "memory");
        }
      }
      __syncwarp();
      if (lane == 0) mbar_arrive(MB_SC);
      TSX(27);
    } else {
      uint32_t w[9], d[9];
      float s = 0.f;
#pragma unroll
      for (int i = 0; i < 9; i++) { w[i] = ldnc32(p.w_r + (i < 8 ? lane * 4 + (i & 3) + (i >> 2) * 128 : 256 + lane)); d[i] = ldnc32(p.dskip + lane + 32 * i); }
#pragma unroll
      for (int i = 0; i < 9; i++) { sts32(OFF_WR + lane * 4 + i * 128, w[i]); sts32(OFF_WR + 1152 + lane * 4 + i * 128, d[i]); s += bf_lo(w[i]) + bf_hi(w[i]); }
      sts32(MISC_SW, __float_as_uint(warp_sum(s)));
      TSX(23);
      bar_sync(10, 576);
      if (lane == 0) {
        const uint32_t tp = clock();
        TSX(1);
        while ((int)(clock() - tp) < X_DELTA || (int)(clock() - t0) < X_ABS - c * 4) {}
        TSX(24);
        load_tile(&tm.m[6], 0, c);
        TSX(15);
        load_tile(&tm.m[6], 1, c);
        while ((int)(clock() - t0) < X_ABS + X_DSTEP - c * 4) {}
      }
      bar_sync(11, 96);
      if (lane == 0) {
        load_tile(&tm.m[6], 2, c);
      }
      if (five) {
        mbar_wait(MB_KF);
#pragma unroll 1
        for (int it = 0; it < SPIN_MAX; it++) {
          if (lane == 0) load_tile(&tm.m[6], 4, c);
          mbar_wait(MB_UL + 32, it & 1);
          uint32_t m = 1;
#pragma unroll
          for (int q = 0; q < 4; q++) { uint32_t r0, r1, r2, r3; ldsm4(OFF_W + ALT + W_UP + 1024 + lane * 32 + (lane & 4) * 4 + q * 1024, r0, r1, r2, r3); m &= r0 & r1 & r2 & r3; }
          if (__all_sync(0xffffffffu, m || (lane & 3))) break;
        }
        bar_arrive(7, 288);
        FINISH0
        bar_sync(13, 64);
        if (lane == 0) {
          asm volatile("cp.async.bulk.tensor.2d.global.shared::cta.bulk_group [%0, {%2, %3}], [%1];" :: "l"(&tm.m[7]), "r"(OFF_W + W_UP + 1024), "r"(c * 16), "r"(0) : "memory");
          asm volatile("cp.async.bulk.commit_group;" ::: "memory");
          asm volatile("cp.async.bulk.wait_group.read 0;" ::: "memory");
        }
      }
      uint4* rp = &p.s->R[c * 2 + (lane & 1)];
      asm volatile("" : "+l"(rp));
      bar_sync(0, 544);
      if (lane == 0) mbar_arrive(MB_H);
      bar_sync(5, 544);
      const uint4 k = lds128(MISC_RK + (lane & 1) * 16);
      if (lane < 2) str128(rp, k.x, k.y, k.z, k.w);
    }
    return;
  }
  const int wt = tid & 127, g = lane >> 2, t = lane & 3;
  const uint32_t wb = OFF_W + wg * W_BYTES;
  const uint32_t xrow = OFF_YT + (wt >> 3) * YT_PITCH + (wt & 64) + (lane & 7) * 16;
  if (wg == 2) {
    const unsigned char* xp = p.x + (uint32_t)((c * 16 + (wt >> 3)) * 1152 + (lane & 7) * 16);
    { const uint32_t tq = clock(); while ((int)(clock() - tq) < X_XD) {} }
#pragma unroll
    for (int k = 0; k < 9; k++) asm volatile("cp.async.cg.shared.global [%0], [%1], 16;" :: "r"(xrow + k * 128), "l"(xp + k * 128) : "memory");
  }
  asm volatile("cp.async.commit_group;" ::: "memory");
  const ConvC cv = conv_consts(warp & 3, lane);
  zero_pads(wb, wt);
  load_params<FAR>(p, wg * 128 + c, wt, wb + W_KT, wg == 2 || (wg == 3 && !five));
  asm volatile("cp.async.commit_group;" ::: "memory");
  asm volatile("setmaxnreg.inc.sync.aligned.u32 112;");
  {
    uint4 kw;
    uint4* kx = &p.s->KX[(c >> 1) * 128 + wt];
    bool two = wg == 3;
    uint32_t ep;
    int phase = wg == 2 ? 3 : 2;
#pragma unroll 1
    for (;;) {
      const bool first = two && !five;
      if (phase) asm volatile("cp.async.wait_group 1;" ::: "memory"); else asm volatile("cp.async.wait_group 0;" ::: "memory");
      if (phase == 3) {
        TS(21);
        float d[3][4], r;
        uint4 a[9];
#pragma unroll
        for (int k = 0; k < 9; k++) a[k] = lds128(xrow + k * 128);
#pragma unroll
        for (int i = 0; i < 4; i++) d[0][i] = d[1][i] = d[2][i] = 0.f;
#pragma unroll
        for (int k = 0; k < 9; k++) { mma_bf16(d[(2 * k) % 3], a[k].x, ones, a[k].y, ones, a[k].x, a[k].y); mma_bf16(d[(2 * k + 1) % 3], a[k].z, ones, a[k].w, ones, a[k].z, a[k].w); }
#pragma unroll
        for (int i = 0; i < 4; i++) d[0][i] += d[1][i] + d[2][i];
        const LnC lc = ln_consts(d[0][2] + d[0][3], __shfl_sync(0xffffffffu, d[0][0], 9 * t) + __shfl_sync(0xffffffffu, d[0][1], 9 * t + 4), r);
        if (lane < 12) sts16(MISC_LN1 + g * 32 + (warp & 3) * 8 + t * 2, lane < 4 ? lc.m2 : lane < 8 ? lc.rh2 : lc.rl2);
      } else {
        KgState ks;
        uint32_t raw[7];
        bar_sync(1 + wg, 128);
        TS(22);
#pragma unroll
        for (int i = 0; i < 7; i++) raw[i] = lds16(wb + W_KT + first * 2048 + i * 256 + (i < 6 ? wt : (c >> first) & 7) * 2);
        kgen_tables_n(raw, wb, wt, ks);
        TS(20);
        bar_sync(1 + wg, 128);
        const int em = kgen_tables_m(wb, wt, ks);
        asm volatile("st.shared.u8 [%0], %1;" :: "r"(MISC_EM + wg + first), "r"(em + 9) : "memory");
        fence_async();
      }
      if (phase & 2) {
        const uint32_t tr_addr = tr_base(lane) + warp * 32;
        uint4* dst = &p.s->X[c * DM * 2 + warp * 32 + (8 * (t >> 1) + g) * 2 + (t & 1)];
        TS(23);
        bar_sync(5, 576);
        uint32_t x[3][4];
        ldsm4t(tr_addr, x[0][0], x[0][1], x[0][2], x[0][3]);
        const uint4 m = lds128(MISC_LN1 + (t & 1) * 16), rl = lds128(MISC_LN1 + 64 + (t & 1) * 16), rh = lds128(MISC_LN1 + 32 + (t & 1) * 16);
        ldsm4t(tr_addr + 512, x[1][0], x[1][1], x[1][2], x[1][3]);
        if (wg == 3) ldsm4t(tr_addr + 640, x[2][0], x[2][1], x[2][2], x[2][3]);
#pragma unroll
        for (int q = 0; q < 3; q++) {
          if (q < 2 || wg == 3) {
            const uint32_t r0 = ln_apply(x[q][0], m.x, rh.x, rl.x), r1 = ln_apply(x[q][1], m.y, rh.y, rl.y), r2 = ln_apply(x[q][2], m.z, rh.z, rl.z), r3 = ln_apply(x[q][3], m.w, rh.w, rl.w);
            const uint32_t w0 = (pack_h(bf_lo(r0), bf_hi(r0)) & 0xFFFEFFFEu) | 1u, w1 = pack_h(bf_lo(r1), bf_hi(r1)), w2 = pack_h(bf_lo(r2), bf_hi(r2)), w3 = pack_h(bf_lo(r3), bf_hi(r3));
            if (q == 0) str128(dst, w0, w1, w2, w3);
            else sts128(OFF_G + warp * 512 + (8 * (t >> 1) + g) * 32 + (t & 1) * 16 + (q == 2 ? 2048 : 0), w0, w1, w2, w3);
          }
          if (q == 0) TS(30);
        }
        bar_arrive(10, 576);
        TS(1);
      } else bar_sync(1 + wg, 128);
      phase &= 1;
      if (phase) { phase = 0; continue; }
      TS(14);
      float acc[20];
      const uint32_t alo = (wb >> 4) | (8u << 16);
      wg_fence();
      wgmma40_ss_init(acc, alo, alo + 1024, 2048 >> 4);
#pragma unroll
      for (int k = 1; k < 8; k++) wgmma40_ss(acc, alo + k * 16, alo + 1024 + k * 16, 2048 >> 4);
      wg_commit();
      const uint4 k4 = lds128(wb + W_MISC + 16);
      const float k2048 = (float)(int)(k4.x + k4.y + k4.z + k4.w) * (1.f / 262144.f);
      wg_wait<0>();
      const float un = 1.f / 8192.f;
      kw.x = pack_h((acc[0] - acc[3]) * un, (acc[4] - acc[7]) * un);
      kw.y = pack_h((acc[8] - acc[11]) * un, (acc[12] - acc[15]) * un);
      kw.z = pack_h((acc[16] - acc[19]) * un, k2048 * un);
      TS(24);
      ep = 0;
      if (two) SPIN_WHILE(ep == 0, ep = lds32(MISC_EPOCH));
      if (five || !two) break;
      str128(kx, kw.x, kw.y, kw.z, ep);
      two = false;
    }
    if (lane == 0) mbar_arrive(MB_KF + wg * 8);
    mbar_wait(MB_KF + wg * 8);
    if (two) { mbar_wait(MB_KF); zero_pads(OFF_W + ALT, wt); }
    uint32_t tb = wb;
#pragma unroll 1
    for (;;) {
      kgen_build(tb, (tb == wb ? wb : OFF_W + 16384 - 25600) + 25600, wg, wt, kw.x, kw.y, kw.z);
      TS(15);
      if (!two) break;
      two = false;
      kw.w = 0;
      SPIN_WHILE(kw.w != ep, kw = ldr128(kx));
      tb = OFF_W + ALT;
    }
    fence_async();
    TS(31);
    if (tb != wb) bar_arrive(7, 288);
    bar_sync(1 + wg, 128);
  }
  uint32_t tpub;
#pragma unroll 1
  for (int item = 0;; item++) {
    TS(2);
    conv_item(item ? OFF_W + ALT : wb, cv, p.zero, &tm.m[7], item ? 512 + (c >> 1) : wg * 128 + c, warp, lane, five && wg >= X_GW, five && !wg && !item);
    tpub = clock() - (item ? X_YD : wg >= 2 ? X_YD2 : 0);
    if (wg || !five || item) break;
    TS(27);
    bar_sync(7, 288);
  }
  TS(4);

  const int ln = lane ^ p.zero, td = warp * 32 + ln, gg = ln >> 2, tt = ln & 3;
  const int tok = c * 16 + warp;
  const int fu = warp / 3, fk = warp - fu * 3;
  uint32_t wa[12][4];
  {
    uint32_t hw[9], wr[9];
    const uint32_t row = keep(OFF_YT + warp * YT_PITCH + (warp >> 3) * 64 + ln * 16);
    const uint32_t wabase = keep(((ln & 8) ? OFF_W + (fk + 1) * W_BYTES : OFF_G + fk * 192 * pitch) + ((ln >> 4) * 8 + (ln & 7)) * pitch
                                 + (five ? ((fu ^ (ln >> 1)) & 3) : min(fu, 4)) * 16);
    float sw;
    {
      const bool three = wg == 1;
      const int ch = 8 * (tt >> 1) + gg;
      const uint32_t tr_addr = tr_base(ln);
      const uint4* ysrc = &p.s->X[c * DM * 2 + ch * 2 + (tt & 1)];
      uint32_t x[3][4], ud[3][4], s[3];
      uint4 v[3];
#define TL(q) ((q) < 2 ? 2 * warp + (q) : 28 + warp)
      asm volatile("cp.async.bulk.wait_group.read 0;" ::: "memory");
      while ((int)(clock() - tpub) < X_YD) {}
      TS(5);
      v[0] = ldr128(ysrc + TL(0) * 32); v[1] = ldr128(ysrc + TL(1) * 32); v[2] = make_uint4(three, 0, 0, 0);
      mbar_wait(MB_REL);
      const uint4 m = lds128(MISC_LN1 + (tt & 1) * 16), rh = lds128(MISC_LN1 + 32 + (tt & 1) * 16), rl = lds128(MISC_LN1 + 64 + (tt & 1) * 16);
#pragma unroll
      for (int i = 0; i < 9; i++) wr[i] = lds32(OFF_WR + ln * 4 + i * 128);
      sw = __uint_as_float(lds32(MISC_SW));
#pragma unroll
      for (int q = 0; q < 3; q++) {
        if (q < 2 || three) {
          const uint32_t dk = lds16(OFF_WR + 1152 + ch * 2 + TL(q) * 32) * 0x10001u;
          ldsm4t(tr_addr + TL(q) * 32, x[q][0], x[q][1], x[q][2], x[q][3]);
          ud[q][0] = bf_mul2(ln_apply(x[q][0], m.x, rh.x, rl.x), dk); ud[q][1] = bf_mul2(ln_apply(x[q][1], m.y, rh.y, rl.y), dk);
          ud[q][2] = bf_mul2(ln_apply(x[q][2], m.z, rh.z, rl.z), dk); ud[q][3] = bf_mul2(ln_apply(x[q][3], m.w, rh.w, rl.w), dk);
        }
      }
      mbar_wait(MB_SC);
#pragma unroll
      for (int q = 0; q < 3; q++) {
        asm volatile("ld.shared.u8 %0, [%1];" : "=r"(s[q]) : "r"((q < 2 ? sc_addr(warp) + q * 16 : sc_addr(16) + (warp & 3) * 16) + ch) : "memory");
        s[q] = keep(s[q] * 0x800080u);
      }
#define FIN(q) stsm4t(tr_addr + TL(q) * 32, bf_add2(x[q][0], bf_fma2(h2bf(v[q].x), s[q], ud[q][0])), bf_add2(x[q][1], bf_fma2(h2bf(v[q].y), s[q], ud[q][1])), \
                      bf_add2(x[q][2], bf_fma2(h2bf(v[q].z), s[q], ud[q][2])), bf_add2(x[q][3], bf_fma2(h2bf(v[q].w), s[q], ud[q][3])));
      SPIN_WHILE((v[0].x | v[1].x) & 1u, _Pragma("unroll") for (int q = 0; q < 3; q++) if (v[q].x & 1u) v[q] = ldr128(ysrc + TL(q) * 32));
      if (v[2].x & 1u) v[2] = ldr128(ysrc + TL(2) * 32);
      FIN(0) FIN(1)
      if (three) {
        SPIN_WHILE(v[2].x & 1u, if (v[2].x & 1u) v[2] = ldr128(ysrc + TL(2) * 32));
        FIN(2)
      }
#undef FIN
#undef TL
    }
    TS(28);
    bar_sync(0, 544);
    TS(6);
    float d[4] = {0.f, 0.f, 0.f, 0.f}, e[4] = {0.f, 0.f, 0.f, 0.f}, rd;
    {
      const uint4 a = lds128(row), b = lds128(row + 512);
      hw[8] = lds32(row + 1024 - ln * 12);
      hw[0] = a.x; hw[1] = a.y; hw[2] = a.z; hw[3] = a.w; hw[4] = b.x; hw[5] = b.y; hw[6] = b.z; hw[7] = b.w;
    }
    mma_bf16(e, hw[0], hw[1], hw[2], hw[3], ones, ones);
#pragma unroll
    for (int i = 0; i < 8; i += 2) mma_bf16(d, hw[i], wr[i], hw[i + 1], wr[i + 1], hw[i], hw[i + 1]);
    mma_bf16(e, hw[4], hw[5], hw[6], hw[7], ones, ones);
    e[0] += e[2];
    mma_bf16_k8(e, hw[8], wr[8], ones);
    mma_bf16_k8(d, hw[8], wr[8], hw[8]);
    const float hwsum = diag_sum(d[2], d[3], tt);
    LnC l2 = ln_consts(diag_sum(e[0], e[0], tt), diag_sum(d[0], d[1], tt), rd);
    const uint32_t b = pack_bf(0.f, fmaf(-bf_lo(l2.m2), sw, hwsum) * rd);
    uint32_t key = max(min((b ^ (((int)b >> 31) | 0x80000000u)) >> 16, 0xFFFEu), 1u);
    sts16(MISC_RK + warp * 2, key);
    bar_sync(5, 544);
    asm volatile("" : "+r"(l2.m2) :: "memory");
    TS(7);
    const uint32_t tr0 = clock();
    key = (key << 16) | (2047 - tok);
    uint32_t loc = ln < 16 ? (lds16(MISC_RK + ln * 2) << 16) | (2047 - c * 16 - ln) : 0u;
    int rank = __popc(__ballot_sync(0xffffffffu, loc > key));
#pragma unroll
    for (int i = 0; i < 9; i++) wr[i] = keep(ln_apply(hw[i], l2.m2, l2.rh2, l2.rl2));
    const uint2* rsrc = (const uint2*)p.s->R + td;
    uint2 rv = make_uint2(~0u, 0u);
    mbar_wait(MB_GU);
    if (warp < (five ? 12 : 15)) {
#pragma unroll
      for (int k = 0; k < X_WS; k++) ldsm4t(wabase + k * 16 * pitch, wa[k][0], wa[k][1], wa[k][2], wa[k][3]);
    }
#define OUT_ROW { uint32_t* o = p.out + tok * 288 + ln * 4; \
      *(uint4*)o = make_uint4(bf_add2(hw[0], wr[0]), bf_add2(hw[1], wr[1]), bf_add2(hw[2], wr[2]), bf_add2(hw[3], wr[3])); \
      *(uint4*)(o + 128) = make_uint4(bf_add2(hw[4], wr[4]), bf_add2(hw[5], wr[5]), bf_add2(hw[6], wr[6]), bf_add2(hw[7], wr[7])); \
      o[256 - ln * 3] = bf_add2(hw[8], wr[8]); }
    if (rank >= X_OR) OUT_ROW
#pragma unroll 1
    for (int base = 0; base < 8; base += 4) {
      uint32_t T[4];
#pragma unroll
      for (int j = 0; j < 4; j++) {
        const uint32_t mx = __reduce_max_sync(0xffffffffu, loc);
        if (loc == mx) loc = 0;
        T[j] = (td >> 2) == c ? ~0u : (td >> 2) < c ? (mx & 0xFFFF0000u) - 1u : mx | 0xFFFFu;
      }
      const uint32_t sh = keep(ln < 16 ? 0x4440u + (rank & 3) : 0x4344u), ca = keep(MISC_CNT + base * 16 + (ln & 15) * 4);
      while ((int)(clock() - tr0) < X_RD) {}
      SPIN_WHILE(rv.x == ~0u, if (rv.x == ~0u) rv = ldr64(rsrc));
      TS(16);
      uint32_t cnt = 0, cn2 = 0;
#pragma unroll
      for (int j = 0; j < 4; j++)
        asm("{ .reg .pred a, b, c, d; setp.gt.u32 a, %2, %6; setp.gt.u32 b, %3, %6; setp.gt.u32 c, %4, %6; setp.gt.u32 d, %5, %6; "
            "@a add.u32 %0, %0, %7; @b add.u32 %1, %1, %7; @c add.u32 %0, %0, %7; @d add.u32 %1, %1, %7; }"
            : "+r"(cnt), "+r"(cn2) : "r"(rv.x), "r"(rv.x << 16), "r"(rv.y), "r"(rv.y << 16), "r"(T[j]), "r"(1u << (8 * j)));
      sts32(MISC_CNT + base * 16 + warp * 4, __reduce_add_sync(0xffffffffu, cnt + cn2));
      bar_sync(0, 512);
      cnt = __reduce_add_sync(0xffffffffu, __byte_perm(lds32(ca), 0, sh));
      if ((rank & ~3) == base && rank + (int)(cnt & 0xFFFFu) < 8) {
        rank += cnt & 0xFFFFu;
        uint4* hs = p.s->HS + rank * 72 + ln;
        str128(hs, wr[0], wr[1], wr[2], wr[3]); str128(hs + 32, wr[4], wr[5], wr[6], wr[7]); str32((uint32_t*)(hs + 64) - ln * 3, wr[8]);
        str128(hs + 576, hw[0], hw[1], hw[2], hw[3]); str128(hs + 608, hw[4], hw[5], hw[6], hw[7]); str32((uint32_t*)(hs + 640) - ln * 3, hw[8]);
        if (ln == 0) str32(&p.s->HS[1152 + rank], key);
        rank = 16;
      }
      if (cnt >= (4u << 16)) break;
    }
    TS(8);
    tpub = clock();
    if (rank < X_OR) OUT_ROW
    if (warp < (five ? 12 : 15)) {
#pragma unroll
      for (int k = X_WS; k < 12; k++) ldsm4t(wabase + k * 16 * pitch, wa[k][0], wa[k][1], wa[k][2], wa[k][3]);
    }
  }
  uint32_t wd[10][4];
  const uint32_t xb = keep(OFF_XS + (ln & 7) * 1168 + (fk * 24 + (ln >> 3)) * 16);
  if (warp >= 7) {
    const uint32_t db = down_box(warp - 7, five) + (ln & 7) * 128;
    mbar_wait(MB_D);
#pragma unroll
    for (int j = 0; j < 4; j++) {
      const uint32_t a = db + (ln >> 4) * 1024 + (((2 * j + ((ln >> 3) & 1)) ^ (ln & 7)) << 4);
      ldsm4t(a, wd[j][0], wd[j][1], wd[j][2], wd[j][3]);
      ldsm4t(a + 2048, wd[4 + j][0], wd[4 + j][1], wd[4 + j][2], wd[4 + j][3]);
    }
#pragma unroll
    for (int j = 0; j < 2; j++) ldsm4t(db + 4096 + (((4 * j + (ln >> 3)) ^ (ln & 7)) << 4), wd[8 + j][0], wd[8 + j][1], wd[8 + j][2], wd[8 + j][3]);
  } else if (warp < 6) {
    const int r = td / 24;
    const uint4* src = &p.s->HS[td + r * 48];
    const uint32_t xs = keep(OFF_XS + (td + r * 49) * 16);
    uint4 a[3];
    uint32_t m = ~0u;
    while ((int)(clock() - tpub) < X_HD) {}
    TS(19);
    SPIN_WHILE(m == ~0u, if (m == ~0u) { a[0] = ldr128(src); a[1] = ldr128(src + 24); a[2] = ldr128(src + 48); } m = max(max(max(a[0].x, a[1].x), max(a[2].x, a[2].y)), max(a[2].z, a[2].w)));
#pragma unroll
    for (int q = 0; q < 3; q++) sts128(xs + q * 384, a[q].x, a[q].y, a[q].z, a[q].w);
  }
  bar_sync(0, 512);
  TS(9);

  if (warp < (five ? 12 : 15)) {
    float d0[4] = {0.f, 0.f, 0.f, 0.f}, d1[4] = {0.f, 0.f, 0.f, 0.f};
#pragma unroll
    for (int k = 0; k < 12; k += 2) {
      uint32_t b0, b1, b2, b3;
      ldsm4(xb + k * 32, b0, b1, b2, b3);
      mma_bf16(d0, wa[k][0], wa[k][1], wa[k][2], wa[k][3], b0, b1);
      mma_bf16(d1, wa[k + 1][0], wa[k + 1][1], wa[k + 1][2], wa[k + 1][3], b2, b3);
    }
    sts128(OFF_RED + td * 16, __float_as_uint(d0[0] + d1[0]), __float_as_uint(d0[1] + d1[1]), __float_as_uint(d0[2] + d1[2]), __float_as_uint(d0[3] + d1[3]));
  }
  TS(26);
  if (warp < 5) {
    const uint32_t rb = OFF_RED + warp * 1536 + ln * 16;
    bar_sync(9, 512);
    const uint4 pa = lds128(rb), pb = lds128(rb + 512), pc = lds128(rb + 1024);
    const float ga = bfr(__uint_as_float(pa.x) + __uint_as_float(pb.x) + __uint_as_float(pc.x));
    const float gb = bfr(__uint_as_float(pa.y) + __uint_as_float(pb.y) + __uint_as_float(pc.y));
    const uint32_t uu = pack_bf(__uint_as_float(pa.z) + __uint_as_float(pb.z) + __uint_as_float(pc.z), __uint_as_float(pa.w) + __uint_as_float(pb.w) + __uint_as_float(pc.w));
    float ra, rb2;
    asm("rcp.approx.ftz.f32 %0, %1;" : "=f"(ra) : "f"(1.f + ex2(ga * -1.4426950408889634f)));
    asm("rcp.approx.ftz.f32 %0, %1;" : "=f"(rb2) : "f"(1.f + ex2(gb * -1.4426950408889634f)));
    const uint32_t act = bf_mul2(pack_bf(ga * ra, gb * rb2), uu);
    sts32(OFF_ACT + td * 4, act);
  } else bar_arrive(9, 512);
  uint4* dst = &p.s->X[c * DM * 2 + (warp - 7) * 64 + tt * 8 + gg];
  asm volatile("" : "+l"(dst));
  bar_sync(8, 512);
  tpub = clock();
  if (warp >= 7) {
    uint32_t b0, b1, b2, b3, b4;
    ldsm4t(OFF_ACT + ln * 16, b0, b1, b2, b3);
    asm volatile("ldmatrix.sync.aligned.m8n8.x1.trans.shared.b16 {%0}, [%1];" : "=r"(b4) : "r"(OFF_ACT + 512 + ln * 16) : "memory");
    float y[4][4];
#pragma unroll
    for (int j = 0; j < 4; j++) {
      y[j][0] = y[j][1] = y[j][2] = y[j][3] = 0.f;
      mma_bf16(y[j], wd[j][0], wd[j][1], wd[j][2], wd[j][3], b0, b1);
    }
#pragma unroll
    for (int j = 0; j < 4; j++) mma_bf16(y[j], wd[4 + j][0], wd[4 + j][1], wd[4 + j][2], wd[4 + j][3], b2, b3);
    if (!five) {
#pragma unroll
      for (int j = 0; j < 4; j++) mma_bf16_k8(y[j], wd[8 + (j >> 1)][2 * (j & 1)], wd[8 + (j >> 1)][2 * (j & 1) + 1], b4);
    }
    str128(dst, (pack_bf(y[0][0], y[0][1]) & ~1u) | 0x10000u, pack_bf(y[0][2], y[0][3]), pack_bf(y[1][0], y[1][1]), pack_bf(y[1][2], y[1][3]));
    str128(dst + 32, (pack_bf(y[2][0], y[2][1]) & ~1u) | 0x10000u, pack_bf(y[2][2], y[2][3]), pack_bf(y[3][0], y[3][1]), pack_bf(y[3][2], y[3][3]));
  }
  TS(10);

  if (c < 72) {
    const uint4* src = &p.s->X[(warp * 4 + tt) * (DM * 2) + c * 8 + gg];
    const int slot = (c & 3) * 2 + (ln >> 4), dw = (c >> 2) * 16 + (ln & 15);
    uint32_t hv = 0, kv = 0, res = 0, rs2 = 0;
    uint32_t* o = p.out;
    if (warp == 0) {
      hv = ~0u;
      SPIN_WHILE(max(hv, kv) == ~0u, hv = ldr32((const uint32_t*)p.s->HS + 2304 + slot * 288 + dw); kv = ldr32(&p.s->HS[1152 + slot]));
      const float r = bf_hi(kv ^ (((int)~kv >> 31) | 0x80000000u));
      float rs;
      asm("rcp.approx.ftz.f32 %0, %1;" : "=f"(rs) : "f"(1.f + ex2(r * -1.4426950408889634f)));
      rs2 = keep(pack_bf(rs, rs));
      res = lds32(OFF_XS + slot * 1168 + dw * 4);
      o += (2047 - (int)(kv & 2047u)) * 288 + dw;
      asm volatile("" : "+l"(o));
    }
    const uint32_t sel = (gg & 1) ? 0x3F800000u : 0x00003F80u;
    const uint32_t q0 = keep((gg >> 1) == 0 ? sel : 0u), q1 = keep((gg >> 1) == 1 ? sel : 0u), q2 = keep((gg >> 1) == 2 ? sel : 0u), q3 = keep((gg >> 1) == 3 ? sel : 0u);
    const uint32_t fa = keep(OFF_FIN + warp * 256 + (gg & 1) * 128 + (gg >> 1) * 32 + tt * 8), fb = keep(OFF_FIN + ln * 8);
    uint4 a0 = make_uint4(0, 0, 0, 0), a1 = a0;
    while ((int)(clock() - tpub) < X_PD) {}
    SPIN_WHILE(!(a0.x & a1.x & 0x10000u), if (!(a0.x & 0x10000u)) a0 = ldr128(src); if (!(a1.x & 0x10000u)) a1 = ldr128(src + 64 * DM * 2));
    float d[4] = {0.f, 0.f, 0.f, 0.f}, e[4] = {0.f, 0.f, 0.f, 0.f};
    mma_bf16(d, q0, q2, q1, q3, a0.x, a0.y); mma_bf16(e, q0, q2, q1, q3, a0.z, a0.w);
    mma_bf16(d, q0, q2, q1, q3, a1.x, a1.y); mma_bf16(e, q0, q2, q1, q3, a1.z, a1.w);
    sts64(fa, __float_as_uint(d[0] + e[2]), __float_as_uint(d[1] + e[3]));
    TS(11);
    if (warp == 0) {
      bar_sync(0, 512);
      float2 s[16];
#pragma unroll
      for (int i = 0; i < 16; i++) { const uint2 q = lds64(fb + i * 256); s[i] = make_float2(__uint_as_float(q.x), __uint_as_float(q.y)); }
#pragma unroll
      for (int k = 1; k < 16; k *= 2)
#pragma unroll
        for (int i = 0; i < 16; i += 2 * k) { s[i].x += s[i + k].x; s[i].y += s[i + k].y; }
      *o = bf_add2(hv, bf_add2(res, bf_mul2(pack_bf(s[0].x, s[0].y), rs2)));
    } else bar_arrive(0, 512);
  }
  TS(12);
  TS_DUMP();
}

typedef CUresult (*EncodeFn)(CUtensorMap*, CUtensorMapDataType, cuuint32_t, void*, const cuuint64_t*, const cuuint64_t*, const cuuint32_t*,
                             const cuuint32_t*, CUtensorMapInterleave, CUtensorMapSwizzle, CUtensorMapL2promotion, CUtensorMapFloatOOBfill);

}

extern "C" void kernel_launch(void* const* d_in, const int* in_sizes, int n_in, void* d_out, int out_size) {
  (void)in_sizes; (void)n_in; (void)out_size;
  static EncodeFn enc = nullptr;
  static Scratch* scratch = nullptr;
  if (!enc) {
    void* fn = nullptr;
    cudaDriverEntryPointQueryResult qr;
    cudaGetDriverEntryPoint("cuTensorMapEncodeTiled", &fn, cudaEnableDefault, &qr);
    enc = (EncodeFn)fn;
    cudaGetSymbolAddress((void**)&scratch, g_S);
    cudaFuncSetAttribute(fused_kernel<false>, cudaFuncAttributeMaxDynamicSharedMemorySize, SMEM_BYTES);
    cudaFuncSetAttribute(fused_kernel<true>, cudaFuncAttributeMaxDynamicSharedMemorySize, SMEM_BYTES);
  }
  TMaps tm;
  for (int i = 0; i < 6; i++) {
    const bool dn = i % 3 == 2;
    const cuuint32_t w = i < 3 ? 40 : 32;
    cuuint64_t gd[3] = {(cuuint64_t)(dn ? 64 : FF), (cuuint64_t)(dn ? FF : DM), 9};
    cuuint64_t gs[2] = {(cuuint64_t)(dn ? DM * 2 : FF * 2), 128};
    cuuint32_t bx[3] = {dn ? 64 : w, dn ? w : 96, i < 3 ? 2u : 3u};
    cuuint32_t es[3] = {1, 1, 1};
    enc(&tm.m[i], CU_TENSOR_MAP_DATA_TYPE_BFLOAT16, dn ? 3 : 2, d_in[11 + i % 3], gd, gs, bx, es, CU_TENSOR_MAP_INTERLEAVE_NONE,
        dn ? CU_TENSOR_MAP_SWIZZLE_128B : i < 3 ? CU_TENSOR_MAP_SWIZZLE_NONE : CU_TENSOR_MAP_SWIZZLE_64B,
        (CUtensorMapL2promotion)X_PROMO, CU_TENSOR_MAP_FLOAT_OOB_FILL_NONE);
  }
  for (int i = 6; i < 8; i++) {
    cuuint64_t gd[2] = {DM * 16, NCTA};
    cuuint64_t gs[1] = {DM * 32};
    cuuint32_t bx[2] = {16, i == 6 ? 160u : 128u};
    cuuint32_t es[2] = {1, 1};
    enc(&tm.m[i], CU_TENSOR_MAP_DATA_TYPE_FLOAT16, 2, scratch->X, gd, gs, bx, es, CU_TENSOR_MAP_INTERLEAVE_NONE, CU_TENSOR_MAP_SWIZZLE_32B,
        CU_TENSOR_MAP_L2_PROMOTION_NONE, CU_TENSOR_MAP_FLOAT_OOB_FILL_NONE);
  }
  Params p;
  p.x = (const unsigned char*)d_in[0];
  bool far = false;
  for (int i = 0; i < 7; i++) {
    p.far[i] = (const unsigned char*)d_in[1 + i];
    const long long d = (long long)((intptr_t)d_in[1 + i] - (intptr_t)d_in[0]);
    p.off[i] = (int)(d / 16);
    if ((long long)p.off[i] * 16 != d) far = true;
  }
  p.dskip = (const uint32_t*)d_in[8];
  p.w_r = (const uint32_t*)d_in[10];
  for (int f = 0; f < 2; f++) {
    static const int kind[17] = {0, 0, 0, 0, 2, 2, 0, 0, 1, 1, 1, 1, 1, 1, 2, 2, 2};
    static const int idx[2][17] = {{2, 3, 4, 5, 6, 8, 0, 1, 0, 1, 2, 3, 4, 5, 0, 2, 4}, {2, 3, 4, 5, 0, -1, 0, 1, 0, 1, 2, 3, 4, 5, 3, -1, 6}};
    static const int blk[2][17] = {{-1, -1, -1, -1, 0, -1, 4, -1, 1, -1, 2, -1, 3, -1, 16, -1, -1}, {-1, -1, -1, -1, 1, -1, 4, -1, -1, -1, 2, -1, 3, -1, 16, -1, -1}};
    const int pitch = f ? 64 : 80;
    for (int u = 0; u < 17; u++) {
      const int s = idx[f][u];
      const uint32_t dst = kind[u] == 0 ? OFF_G + s * 96 * pitch : kind[u] == 2 ? down_box(s, f) : OFF_W + W_BYTES + (s >> 1) * W_BYTES + (s & 1) * 96 * pitch;
      const uint32_t mb = blk[f][u] >= 0 ? MB_KF - OFF_MISC + blk[f][u] * 8 : 0;
      p.sched[f][u] = s < 0 ? 3u : kind[u] | s << 2 | mb << 6 | dst << 14;
    }
  }
  p.out = (uint32_t*)d_out;
  p.zero = 0;
  p.ts = nullptr;
  p.s = scratch;
  if (far) { fused_kernel<true><<<NCTA, NT, SMEM_BYTES, cudaStreamPerThread>>>(p, tm); return; }
  fused_kernel<false><<<NCTA, NT, SMEM_BYTES, cudaStreamPerThread>>>(p, tm);
}
```

```cpp
#include <cuda_runtime.h>
#include <cuda.h>
#include <cuda_bf16.h>
#include <cuda_fp16.h>
#include <stdint.h>
#include <stddef.h>

namespace {

constexpr int NCTA = 128;
constexpr int NT = 640;
constexpr int DM = 576;
constexpr int FF = 4608;
constexpr int SPIN_MAX = 1 << 20;

struct Scratch {
  uint4 X[NCTA * DM * 2];
  uint4 KX[64 * 128];
  uint4 HS[1152 + 8];
  uint4 R[256];
  uint4 SC[256];
  uint32_t FLAG[NCTA * 8];
};
__device__ Scratch g_S;

#define CLKS(i)
#define TS(i)
#define TSX(i)
#define TS_DUMP()

constexpr int SB = 1024;
constexpr int BOX = 15360;
constexpr int OFF_G = SB;
constexpr int OFF_W = OFF_G + 3 * BOX;
constexpr int W_KT = 26624;
constexpr int W_L3 = W_KT + 4416;
constexpr int W_CW = W_L3 + 4096;
constexpr int W_MISC = W_CW + 640;
constexpr int W_BYTES = 35840;
constexpr int TILE = 10240;
constexpr int OFF_T = OFF_W + 4 * W_BYTES;
constexpr int ALT = TILE - W_KT;
static_assert(W_MISC + 32 <= W_BYTES && OFF_W % 1024 == 0 && W_BYTES % 1024 == 0 && W_BYTES + ALT <= 20480, "wg block");
constexpr int YT_PITCH = 1184;
constexpr int OFF_YT = OFF_T + 2 * TILE;
constexpr int OFF_WR = OFF_YT + 16 * YT_PITCH + 64;
constexpr int OFF_MISC = OFF_WR + 2304;
constexpr int SMEM_BYTES = OFF_MISC + 1024 - SB;
static_assert(OFF_YT % 16 == 0 && OFF_MISC % 16 == 0, "align");
static_assert(SMEM_BYTES <= 232448, "smem");
constexpr int MB_GU = OFF_MISC;
constexpr int MB_D = OFF_MISC + 8;
constexpr int MB_KF = OFF_MISC + 16;
constexpr int MB_GF = OFF_MISC + 48;
constexpr int MB_SC = OFF_MISC + 56;
constexpr int MB_UL = OFF_MISC + 64;
constexpr int MB_REL = OFF_MISC + 104;
constexpr int MB_GO = OFF_MISC + 112;
constexpr int MB_H = MB_KF + 128;
constexpr int MISC_EPOCH = OFF_MISC + 152;
constexpr int MISC_SW = OFF_MISC + 156;
constexpr int MISC_RT = OFF_MISC + 160;
constexpr int MISC_EM = OFF_MISC + 288;
constexpr int OFF_PART = OFF_W + 20480;
constexpr int OFF_RK = OFF_PART + 3840;
constexpr int MISC_LN1 = OFF_MISC + 192;
constexpr int OFF_XS = OFF_T;
constexpr int OFF_RED = OFF_T + TILE;
constexpr int OFF_FIN = OFF_W + 3 * W_BYTES + W_KT;
constexpr int OFF_ACT = OFF_FIN + 4096;
constexpr int MISC_CNT = OFF_ACT + 1024;

__device__ __forceinline__ uint32_t smem_u32(const void* p) { return (uint32_t)__cvta_generic_to_shared(p); }
__device__ __forceinline__ uint32_t lds32(uint32_t a) { uint32_t v; asm volatile("ld.shared.b32 %0, [%1];" : "=r"(v) : "r"(a) : "memory"); return v; }
__device__ __forceinline__ uint32_t lds16(uint32_t a) { uint16_t v; asm volatile("ld.shared.u16 %0, [%1];" : "=h"(v) : "r"(a) : "memory"); return v; }
__device__ __forceinline__ uint2 lds64(uint32_t a) { uint2 v; asm volatile("ld.shared.v2.b32 {%0,%1}, [%2];" : "=r"(v.x), "=r"(v.y) : "r"(a) : "memory"); return v; }
__device__ __forceinline__ uint4 lds128(uint32_t a) { uint4 v; asm volatile("ld.shared.v4.b32 {%0,%1,%2,%3}, [%4];" : "=r"(v.x), "=r"(v.y), "=r"(v.z), "=r"(v.w) : "r"(a) : "memory"); return v; }
__device__ __forceinline__ void sts16(uint32_t a, uint32_t v) { asm volatile("st.shared.u16 [%0], %1;" :: "r"(a), "h"((uint16_t)v) : "memory"); }
__device__ __forceinline__ void sts32(uint32_t a, uint32_t v) { asm volatile("st.shared.b32 [%0], %1;" :: "r"(a), "r"(v) : "memory"); }
__device__ __forceinline__ void sts64(uint32_t a, uint32_t x, uint32_t y) { asm volatile("st.shared.v2.b32 [%0], {%1,%2};" :: "r"(a), "r"(x), "r"(y) : "memory"); }
__device__ __forceinline__ void sts128(uint32_t a, uint32_t x, uint32_t y, uint32_t z, uint32_t w) { asm volatile("st.shared.v4.b32 [%0], {%1,%2,%3,%4};" :: "r"(a), "r"(x), "r"(y), "r"(z), "r"(w) : "memory"); }
__device__ __forceinline__ void ldsm4(uint32_t a, uint32_t& r0, uint32_t& r1, uint32_t& r2, uint32_t& r3) {
  asm volatile("ldmatrix.sync.aligned.m8n8.x4.shared.b16 {%0,%1,%2,%3}, [%4];" : "=r"(r0), "=r"(r1), "=r"(r2), "=r"(r3) : "r"(a) : "memory");
}
__device__ __forceinline__ void ldsm2(uint32_t a, uint32_t& r0, uint32_t& r1) {
  asm volatile("ldmatrix.sync.aligned.m8n8.x2.shared.b16 {%0,%1}, [%2];" : "=r"(r0), "=r"(r1) : "r"(a) : "memory");
}
__device__ __forceinline__ void ldsm4t(uint32_t a, uint32_t& r0, uint32_t& r1, uint32_t& r2, uint32_t& r3) {
  asm volatile("ldmatrix.sync.aligned.m8n8.x4.trans.shared.b16 {%0,%1,%2,%3}, [%4];" : "=r"(r0), "=r"(r1), "=r"(r2), "=r"(r3) : "r"(a) : "memory");
}
__device__ __forceinline__ void stsm4t(uint32_t a, uint32_t r0, uint32_t r1, uint32_t r2, uint32_t r3) {
  asm volatile("stmatrix.sync.aligned.m8n8.x4.trans.shared.b16 [%0], {%1,%2,%3,%4};" :: "r"(a), "r"(r0), "r"(r1), "r"(r2), "r"(r3) : "memory");
}
__device__ __forceinline__ uint4 ldr128(const void* p) {
  unsigned long long lo, hi;
  asm volatile("{ .reg .b128 t; ld.relaxed.gpu.global.b128 t, [%2]; mov.b128 {%0, %1}, t; }" : "=l"(lo), "=l"(hi) : "l"(p) : "memory");
  return make_uint4((uint32_t)lo, (uint32_t)(lo >> 32), (uint32_t)hi, (uint32_t)(hi >> 32));
}
__device__ __forceinline__ void str128(void* p, uint32_t x, uint32_t y, uint32_t z, uint32_t w) {
  asm volatile("{ .reg .b128 t; .reg .b64 lo, hi; mov.b64 lo, {%1,%2}; mov.b64 hi, {%3,%4}; mov.b128 t, {lo, hi}; st.relaxed.gpu.global.b128 [%0], t; }"
               :: "l"(p), "r"(x), "r"(y), "r"(z), "r"(w) : "memory");
}
__device__ __forceinline__ void str64(void* p, uint32_t x, uint32_t y) {
  asm volatile("{ .reg .b64 t; mov.b64 t, {%1,%2}; st.relaxed.gpu.global.b64 [%0], t; }" :: "l"(p), "r"(x), "r"(y) : "memory");
}
__device__ __forceinline__ uint32_t ldr32(const void* p) { uint32_t v; asm volatile("ld.relaxed.gpu.global.b32 %0, [%1];" : "=r"(v) : "l"(p) : "memory"); return v; }
__device__ __forceinline__ void str32(void* p, uint32_t v) { asm volatile("st.relaxed.gpu.global.b32 [%0], %1;" :: "l"(p), "r"(v) : "memory"); }
__device__ __forceinline__ void str16(void* p, uint32_t v) { asm volatile("st.relaxed.gpu.global.u16 [%0], %1;" :: "l"(p), "h"((uint16_t)v) : "memory"); }
__device__ __forceinline__ void fence_gpu() { asm volatile("fence.acq_rel.gpu;" ::: "memory"); }
__device__ __forceinline__ void bar_sync(int id, int n) { asm volatile("bar.sync %0, %1;" :: "r"(id), "r"(n) : "memory"); }
__device__ __forceinline__ void bar_arrive(int id, int n) { asm volatile("bar.arrive %0, %1;" :: "r"(id), "r"(n) : "memory"); }

__device__ __forceinline__ float bf_lo(uint32_t w) { return __uint_as_float(w << 16); }
__device__ __forceinline__ float bf_hi(uint32_t w) { return __uint_as_float(w & 0xFFFF0000u); }
__device__ __forceinline__ uint32_t pack_bf(float lo, float hi) { uint32_t r; asm("cvt.rn.bf16x2.f32 %0, %1, %2;" : "=r"(r) : "f"(hi), "f"(lo)); return r; }
__device__ __forceinline__ uint32_t pack_h(float lo, float hi) { uint32_t r; asm("cvt.rn.f16x2.f32 %0, %1, %2;" : "=r"(r) : "f"(hi), "f"(lo)); return r; }
__device__ __forceinline__ uint32_t pack_hv(float lo, float hi) { uint32_t r; asm volatile("cvt.rn.f16x2.f32 %0, %1, %2;" : "=r"(r) : "f"(hi), "f"(lo) : "memory"); return r; }
__device__ __forceinline__ float bfr(float x) { return bf_lo(pack_bf(x, 0.f)); }
__device__ __forceinline__ uint32_t bf_sub2(uint32_t a, uint32_t b) { __nv_bfloat162 r = __hsub2(*(__nv_bfloat162*)&a, *(__nv_bfloat162*)&b); return *(uint32_t*)&r; }
__device__ __forceinline__ uint32_t bf_add2(uint32_t a, uint32_t b) { __nv_bfloat162 r = __hadd2(*(__nv_bfloat162*)&a, *(__nv_bfloat162*)&b); return *(uint32_t*)&r; }
__device__ __forceinline__ uint32_t bf_mul2(uint32_t a, uint32_t b) { __nv_bfloat162 r = __hmul2(*(__nv_bfloat162*)&a, *(__nv_bfloat162*)&b); return *(uint32_t*)&r; }
__device__ __forceinline__ float2 h2f(uint32_t w) { return __half22float2(*(__half2*)&w); }
__device__ __forceinline__ float ex2(float x) { float r; asm("ex2.approx.ftz.f32 %0, %1;" : "=f"(r) : "f"(x)); return r; }
__device__ __forceinline__ float warp_sum(float v) {
#pragma unroll
  for (int o = 16; o > 0; o >>= 1) v += __shfl_xor_sync(0xffffffffu, v, o);
  return v;
}
__device__ __forceinline__ void mma_f16_f32(float* d, uint32_t a0, uint32_t a1, uint32_t a2, uint32_t a3, uint32_t b0, uint32_t b1) {
  asm volatile("mma.sync.aligned.m16n8k16.row.col.f32.f16.f16.f32 {%0,%1,%2,%3}, {%4,%5,%6,%7}, {%8,%9}, {%0,%1,%2,%3};"
               : "+f"(d[0]), "+f"(d[1]), "+f"(d[2]), "+f"(d[3]) : "r"(a0), "r"(a1), "r"(a2), "r"(a3), "r"(b0), "r"(b1));
}
__device__ __forceinline__ void mma_f16_f16(uint32_t& d0, uint32_t& d1, uint32_t a0, uint32_t a1, uint32_t a2, uint32_t a3, uint32_t b0, uint32_t b1) {
  asm volatile("mma.sync.aligned.m16n8k16.row.col.f16.f16.f16.f16 {%0,%1}, {%2,%3,%4,%5}, {%6,%7}, {%0,%1};"
               : "+r"(d0), "+r"(d1) : "r"(a0), "r"(a1), "r"(a2), "r"(a3), "r"(b0), "r"(b1));
}
__device__ __forceinline__ void mma_bf16(float* d, uint32_t a0, uint32_t a1, uint32_t a2, uint32_t a3, uint32_t b0, uint32_t b1) {
  asm volatile("mma.sync.aligned.m16n8k16.row.col.f32.bf16.bf16.f32 {%0,%1,%2,%3}, {%4,%5,%6,%7}, {%8,%9}, {%0,%1,%2,%3};"
               : "+f"(d[0]), "+f"(d[1]), "+f"(d[2]), "+f"(d[3]) : "r"(a0), "r"(a1), "r"(a2), "r"(a3), "r"(b0), "r"(b1));
}
__device__ __forceinline__ void mma_bf16_k8(float* d, uint32_t a0, uint32_t a1, uint32_t b0) {
  asm volatile("mma.sync.aligned.m16n8k8.row.col.f32.bf16.bf16.f32 {%0,%1,%2,%3}, {%4,%5}, {%6}, {%0,%1,%2,%3};"
               : "+f"(d[0]), "+f"(d[1]), "+f"(d[2]), "+f"(d[3]) : "r"(a0), "r"(a1), "r"(b0));
}

__device__ __forceinline__ void wg_fence() { asm volatile("wgmma.fence.sync.aligned;" ::: "memory"); }
__device__ __forceinline__ void wg_commit() { asm volatile("wgmma.commit_group.sync.aligned;" ::: "memory"); }
template <int N> __device__ __forceinline__ void wg_wait() { asm volatile("wgmma.wait_group.sync.aligned %0;" :: "n"(N) : "memory"); }
template <int TB> __device__ __forceinline__ void wgmma32(float* d, const uint32_t* a, uint32_t dlo, uint32_t dhi) {
  asm volatile("{ .reg .b64 dd; mov.b64 dd, {%20, %21}; wgmma.mma_async.sync.aligned.m64n32k16.f32.f16.f16 "
               "{%0,%1,%2,%3,%4,%5,%6,%7,%8,%9,%10,%11,%12,%13,%14,%15}, {%16,%17,%18,%19}, dd, 1, 1, 1, %22; }"
               : "+f"(d[0]), "+f"(d[1]), "+f"(d[2]), "+f"(d[3]), "+f"(d[4]), "+f"(d[5]), "+f"(d[6]), "+f"(d[7]), "+f"(d[8]), "+f"(d[9]), "+f"(d[10]), "+f"(d[11]), "+f"(d[12]), "+f"(d[13]), "+f"(d[14]), "+f"(d[15])
               : "r"(a[0]), "r"(a[1]), "r"(a[2]), "r"(a[3]), "r"(dlo), "r"(dhi), "n"(TB));
}
template <int TB> __device__ __forceinline__ void wgmma64(float* d, const uint32_t* a, uint32_t dlo, uint32_t dhi) {
  asm volatile("{ .reg .b64 dd; mov.b64 dd, {%36, %37}; wgmma.mma_async.sync.aligned.m64n64k16.f32.f16.f16 "
               "{%0,%1,%2,%3,%4,%5,%6,%7,%8,%9,%10,%11,%12,%13,%14,%15,%16,%17,%18,%19,%20,%21,%22,%23,%24,%25,%26,%27,%28,%29,%30,%31}, {%32,%33,%34,%35}, dd, 1, 1, 1, %38; }"
               : "+f"(d[0]), "+f"(d[1]), "+f"(d[2]), "+f"(d[3]), "+f"(d[4]), "+f"(d[5]), "+f"(d[6]), "+f"(d[7]), "+f"(d[8]), "+f"(d[9]), "+f"(d[10]), "+f"(d[11]), "+f"(d[12]), "+f"(d[13]), "+f"(d[14]), "+f"(d[15]), "+f"(d[16]), "+f"(d[17]), "+f"(d[18]), "+f"(d[19]), "+f"(d[20]), "+f"(d[21]), "+f"(d[22]), "+f"(d[23]), "+f"(d[24]), "+f"(d[25]), "+f"(d[26]), "+f"(d[27]), "+f"(d[28]), "+f"(d[29]), "+f"(d[30]), "+f"(d[31])
               : "r"(a[0]), "r"(a[1]), "r"(a[2]), "r"(a[3]), "r"(dlo), "r"(dhi), "n"(TB));
}
template <int TB> __device__ __forceinline__ void wgmma64_init(float* d, const uint32_t* a, uint32_t dlo, uint32_t dhi) {
  asm volatile("{ .reg .b64 dd; mov.b64 dd, {%36, %37}; wgmma.mma_async.sync.aligned.m64n64k16.f32.f16.f16 "
               "{%0,%1,%2,%3,%4,%5,%6,%7,%8,%9,%10,%11,%12,%13,%14,%15,%16,%17,%18,%19,%20,%21,%22,%23,%24,%25,%26,%27,%28,%29,%30,%31}, {%32,%33,%34,%35}, dd, 0, 1, 1, %38; }"
               : "=f"(d[0]), "=f"(d[1]), "=f"(d[2]), "=f"(d[3]), "=f"(d[4]), "=f"(d[5]), "=f"(d[6]), "=f"(d[7]), "=f"(d[8]), "=f"(d[9]), "=f"(d[10]), "=f"(d[11]), "=f"(d[12]), "=f"(d[13]), "=f"(d[14]), "=f"(d[15]), "=f"(d[16]), "=f"(d[17]), "=f"(d[18]), "=f"(d[19]), "=f"(d[20]), "=f"(d[21]), "=f"(d[22]), "=f"(d[23]), "=f"(d[24]), "=f"(d[25]), "=f"(d[26]), "=f"(d[27]), "=f"(d[28]), "=f"(d[29]), "=f"(d[30]), "=f"(d[31])
               : "r"(a[0]), "r"(a[1]), "r"(a[2]), "r"(a[3]), "r"(dlo), "r"(dhi), "n"(TB));
}
template <int TB> __device__ __forceinline__ void wgmma32_init(float* d, const uint32_t* a, uint32_t dlo, uint32_t dhi) {
  asm volatile("{ .reg .b64 dd; mov.b64 dd, {%20, %21}; wgmma.mma_async.sync.aligned.m64n32k16.f32.f16.f16 "
               "{%0,%1,%2,%3,%4,%5,%6,%7,%8,%9,%10,%11,%12,%13,%14,%15}, {%16,%17,%18,%19}, dd, 0, 1, 1, %22; }"
               : "=f"(d[0]), "=f"(d[1]), "=f"(d[2]), "=f"(d[3]), "=f"(d[4]), "=f"(d[5]), "=f"(d[6]), "=f"(d[7]), "=f"(d[8]), "=f"(d[9]), "=f"(d[10]), "=f"(d[11]), "=f"(d[12]), "=f"(d[13]), "=f"(d[14]), "=f"(d[15])
               : "r"(a[0]), "r"(a[1]), "r"(a[2]), "r"(a[3]), "r"(dlo), "r"(dhi), "n"(TB));
}
__device__ __forceinline__ void wgmma64h(uint32_t* d, uint32_t a0, uint32_t a1, uint32_t a2, uint32_t a3, uint32_t dlo, uint32_t dhi) {
  asm volatile("{ .reg .b64 dd; mov.b64 dd, {%20, %21}; wgmma.mma_async.sync.aligned.m64n64k16.f16.f16.f16 "
               "{%0,%1,%2,%3,%4,%5,%6,%7,%8,%9,%10,%11,%12,%13,%14,%15}, {%16,%17,%18,%19}, dd, 1, 1, 1, 0; }"
               : "+r"(d[0]), "+r"(d[1]), "+r"(d[2]), "+r"(d[3]), "+r"(d[4]), "+r"(d[5]), "+r"(d[6]), "+r"(d[7]), "+r"(d[8]), "+r"(d[9]), "+r"(d[10]), "+r"(d[11]), "+r"(d[12]), "+r"(d[13]), "+r"(d[14]), "+r"(d[15])
               : "r"(a0), "r"(a1), "r"(a2), "r"(a3), "r"(dlo), "r"(dhi));
}
__device__ __forceinline__ void wgmma64h_init(uint32_t* d, uint32_t a0, uint32_t a1, uint32_t a2, uint32_t a3, uint32_t dlo, uint32_t dhi) {
  asm volatile("{ .reg .b64 dd; mov.b64 dd, {%20, %21}; wgmma.mma_async.sync.aligned.m64n64k16.f16.f16.f16 "
               "{%0,%1,%2,%3,%4,%5,%6,%7,%8,%9,%10,%11,%12,%13,%14,%15}, {%16,%17,%18,%19}, dd, 0, 1, 1, 0; }"
               : "=r"(d[0]), "=r"(d[1]), "=r"(d[2]), "=r"(d[3]), "=r"(d[4]), "=r"(d[5]), "=r"(d[6]), "=r"(d[7]), "=r"(d[8]), "=r"(d[9]), "=r"(d[10]), "=r"(d[11]), "=r"(d[12]), "=r"(d[13]), "=r"(d[14]), "=r"(d[15])
               : "r"(a0), "r"(a1), "r"(a2), "r"(a3), "r"(dlo), "r"(dhi));
}
__device__ __forceinline__ void wgmma40_ss(float* d, uint32_t alo, uint32_t blo, uint32_t hi) {
  asm volatile("{ .reg .b64 da, db; mov.b64 da, {%20, %22}; mov.b64 db, {%21, %22}; "
               "wgmma.mma_async.sync.aligned.m64n40k16.f32.f16.f16 {%0,%1,%2,%3,%4,%5,%6,%7,%8,%9,%10,%11,%12,%13,%14,%15,%16,%17,%18,%19}, da, db, 1, 1, 1, 1, 1; }"
               : "+f"(d[0]), "+f"(d[1]), "+f"(d[2]), "+f"(d[3]), "+f"(d[4]), "+f"(d[5]), "+f"(d[6]), "+f"(d[7]), "+f"(d[8]), "+f"(d[9]), "+f"(d[10]), "+f"(d[11]), "+f"(d[12]), "+f"(d[13]), "+f"(d[14]), "+f"(d[15]), "+f"(d[16]), "+f"(d[17]), "+f"(d[18]), "+f"(d[19])
               : "r"(alo), "r"(blo), "r"(hi));
}
__device__ __forceinline__ void wgmma40_ss_init(float* d, uint32_t alo, uint32_t blo, uint32_t hi) {
  asm volatile("{ .reg .b64 da, db; mov.b64 da, {%20, %22}; mov.b64 db, {%21, %22}; "
               "wgmma.mma_async.sync.aligned.m64n40k16.f32.f16.f16 {%0,%1,%2,%3,%4,%5,%6,%7,%8,%9,%10,%11,%12,%13,%14,%15,%16,%17,%18,%19}, da, db, 0, 1, 1, 1, 1; }"
               : "=f"(d[0]), "=f"(d[1]), "=f"(d[2]), "=f"(d[3]), "=f"(d[4]), "=f"(d[5]), "=f"(d[6]), "=f"(d[7]), "=f"(d[8]), "=f"(d[9]), "=f"(d[10]), "=f"(d[11]), "=f"(d[12]), "=f"(d[13]), "=f"(d[14]), "=f"(d[15]), "=f"(d[16]), "=f"(d[17]), "=f"(d[18]), "=f"(d[19])
               : "r"(alo), "r"(blo), "r"(hi));
}
__device__ __forceinline__ float vzero() { float v; asm volatile("mov.b32 %0, 0;" : "=f"(v)); return v; }
__device__ __forceinline__ void tma_box(uint32_t dst, const CUtensorMap* tm, uint32_t mb, int x, int y) {
  asm volatile("cp.async.bulk.tensor.2d.shared::cluster.global.mbarrier::complete_tx::bytes [%0], [%1, {%3, %4}], [%2];"
               :: "r"(dst), "l"(tm), "r"(mb), "r"(x), "r"(y) : "memory");
}
__device__ __forceinline__ void l2_prefetch(const void* src, uint32_t bytes) {
  asm volatile("cp.async.bulk.prefetch.L2.global [%0], %1;" :: "l"(src), "r"(bytes) : "memory");
}
__device__ __forceinline__ uint32_t uni(uint32_t v) {
  uint32_t r; asm volatile("shfl.sync.idx.b32 %0, %1, 0, 0x1f, 0xffffffff;" : "=r"(r) : "r"(v)); return r;
}
__device__ __forceinline__ int fresh_tid() { int v; asm volatile("mov.u32 %0, %tid.x;" : "=r"(v)); return v; }

struct Params {
  const unsigned char* x;
  Scratch* s;
  int off[7];
  uint32_t zero;
  uint32_t* out;
  const uint32_t* dskip;
  const uint32_t* w_r;
  long long* ts;
  const unsigned char* far[7];
  uint32_t sched[2][17];
};
__device__ __forceinline__ uint32_t ldnc32(const void* p) { uint32_t v; asm volatile("ld.global.nc.b32 %0, [%1];" : "=r"(v) : "l"(p)); return v; }
__device__ __forceinline__ uint32_t ldnc16(const void* p) { uint16_t v; asm volatile("ld.global.nc.u16 %0, [%1];" : "=h"(v) : "l"(p)); return v; }
__device__ __forceinline__ uint4 ldnc128(const void* p) { uint4 v; asm volatile("ld.global.nc.v4.b32 {%0,%1,%2,%3}, [%4];" : "=r"(v.x), "=r"(v.y), "=r"(v.z), "=r"(v.w) : "l"(p)); return v; }
__device__ __forceinline__ void mbar_wait(uint32_t mb, uint32_t ph = 0) {
#pragma unroll 1
  for (int it = 0; it < SPIN_MAX; it++) {
    uint32_t ok;
    asm volatile("{ .reg .pred q; mbarrier.try_wait.parity.shared::cta.b64 q, [%1], %2; selp.u32 %0, 1, 0, q; }" : "=r"(ok) : "r"(mb), "r"(ph) : "memory");
    if (ok) break;
  }
}
__device__ __forceinline__ uint32_t mbar_test(uint32_t mb) {
  uint32_t ok;
  asm volatile("{ .reg .pred q; mbarrier.test_wait.parity.shared::cta.b64 q, [%1], 0; selp.u32 %0, 1, 0, q; }" : "=r"(ok) : "r"(mb) : "memory");
  return ok;
}
__device__ __forceinline__ void mbar_arrive(uint32_t mb) { asm volatile("mbarrier.arrive.shared::cta.b64 _, [%0];" :: "r"(mb) : "memory"); }
__device__ __forceinline__ uint32_t ldg16(const void* p) { uint16_t v; asm volatile("ld.global.u16 %0, [%1];" : "=h"(v) : "l"(p) : "memory"); return v; }
__device__ __forceinline__ uint32_t ldr16(const void* p) { uint16_t v; asm volatile("ld.relaxed.gpu.global.u16 %0, [%1];" : "=h"(v) : "l"(p) : "memory"); return v; }
__device__ __forceinline__ void fence_async() { asm volatile("fence.proxy.async.shared::cta;" ::: "memory"); }
#define SPIN_WHILE(cond, body) _Pragma("unroll 1") for (int _it = 0; _it < SPIN_MAX && __any_sync(0xffffffffu, (cond)); _it++) { body; }

struct LnC { uint32_t m2, rh2, rl2; };
__device__ __forceinline__ float diag_sum(float d0, float d1, int t) {
  float q = __shfl_sync(0xffffffffu, d0, 9 * t) + __shfl_sync(0xffffffffu, d1, 9 * t + 4);
  q += __shfl_xor_sync(0xffffffffu, q, 1);
  return q + __shfl_xor_sync(0xffffffffu, q, 2);
}
__device__ __forceinline__ LnC ln_consts(float s, float q, float& r) {
  const float mean = s * (1.f / DM);
  const float var = fmaxf(fmaf(-mean, mean, q * (1.f / DM)), 0.f);
  float sd;
  asm("sqrt.approx.ftz.f32 %0, %1;" : "=f"(sd) : "f"(bfr(bfr(var) + 1e-5f)));
  asm("rcp.approx.ftz.f32 %0, %1;" : "=f"(r) : "f"(bfr(sd)));
  LnC c;
  c.m2 = pack_bf(mean, mean);
  c.rh2 = pack_bf(r, r);
  const float rl = r - bf_lo(c.rh2);
  c.rl2 = pack_bf(rl, rl);
  return c;
}
__device__ __forceinline__ float quad_sum(float s) { s += __shfl_xor_sync(0xffffffffu, s, 1); return s + __shfl_xor_sync(0xffffffffu, s, 2); }
__device__ __forceinline__ uint32_t bf_fma2(uint32_t a, uint32_t b, uint32_t c) {
  __nv_bfloat162 r = __hfma2(*(const __nv_bfloat162*)&a, *(const __nv_bfloat162*)&b, *(const __nv_bfloat162*)&c);
  return *(uint32_t*)&r;
}
__device__ __forceinline__ uint32_t ln_apply(uint32_t w, uint32_t m2, uint32_t rh2, uint32_t rl2) {
  const uint32_t d = bf_sub2(w, m2);
  return bf_fma2(d, rh2, bf_mul2(d, rl2));
}

__device__ __forceinline__ float2 cis(float mag_log2, float rev) {
  const float m = ex2(mag_log2), ang = rev * 6.283185307179586f;
  return make_float2(m * __cosf(ang), m * __sinf(ang));
}
__device__ __forceinline__ float2 csq(float2 a) { return make_float2(fmaf(a.x, a.x, -a.y * a.y), (a.x + a.x) * a.y); }
__device__ __forceinline__ float2 cmul(float2 a, float2 b) { return make_float2(fmaf(a.x, b.x, -a.y * b.y), fmaf(a.x, b.y, a.y * b.x)); }
__device__ __forceinline__ void pmul(uint32_t xr, uint32_t xi, uint32_t w, uint32_t& yr, uint32_t& yi) {
  const __half2 XR = *(__half2*)&xr, XI = *(__half2*)&xi, W = *(__half2*)&w;
  const __half2 a = __hfma2(__hneg2(XI), __high2half2(W), __hmul2(XR, __low2half2(W)));
  const __half2 b = __hfma2(XI, __low2half2(W), __hmul2(XR, __high2half2(W)));
  yr = *(const uint32_t*)&a; yi = *(const uint32_t*)&b;
}
__device__ __forceinline__ uint32_t pk(float2 a) { return pack_h(a.x, a.y); }

struct KgState { float2 c0, z8; float kl; uint32_t w64, w128, w192; };
__device__ __forceinline__ void kgen_tables_n(const uint32_t (&raw)[7], uint32_t scr, int wt, KgState& k) {
  const uint32_t dst = scr + 16384 + wt * 16;
  const float dt = bfr(ex2(bf_lo(raw[6]) * 1.4426950408889634f));
  const float th = dt * bf_lo(raw[1]);
  const float br = dt * bf_lo(raw[2]), bi = dt * bf_lo(raw[3]);
  const float Cr = bf_lo(raw[4]), Ci = bf_lo(raw[5]);
  k.c0 = make_float2(fmaf(Cr, br, -Ci * bi), fmaf(Cr, bi, Ci * br));
  const uint32_t mx = __reduce_max_sync(0xffffffffu, __float_as_uint(fmaxf(fabsf(k.c0.x), fabsf(k.c0.y))));
  const float a2 = dt * bf_lo(raw[0]) * 1.4426950408889634f;
  const float rh = th * 0.15915494309189535f;
  const float rl = fmaf(th, (float)(0.15915494309189535 - (double)0.15915494309189535f), fmaf(th, 0.15915494309189535f, -rh));
  const float rf = rh - rintf(rh);
  const float2 z1 = cis(a2, rf + rl);
  const float p64 = rf * 64.f;
  const float2 z64 = cis(a2 * 64.f, fmaf(64.f, rl, p64 - rintf(p64)));
  const float2 z2 = csq(z1), z128 = csq(z64), z3 = cmul(z2, z1), z4 = csq(z2), z256 = csq(z128), z6 = csq(z3), z512 = csq(z256);
  k.z8 = csq(z4);
  k.w64 = pk(z64); k.w128 = pk(z128); k.w192 = pk(cmul(z128, z64));
  sts128(dst, 0x00003C00u, pk(z2), pk(z4), pk(z6));
  const float2 z1024 = csq(z512), z768 = cmul(z512, z256);
  sts128(dst + 2048, pk(z1), pk(z3), pk(cmul(z4, z1)), pk(cmul(z4, z3)));
  const float2 z2048 = csq(z1024);
  k.kl = fmaf(k.c0.x, z2048.x, -k.c0.y * z2048.y);
  sts128(dst + 4096, pk(z256), pk(cmul(z256, z2)), pk(cmul(z256, z4)), pk(cmul(z256, z6)));
  sts128(dst + 6144, pk(z512), pk(cmul(z512, z4)), pk(z768), pk(cmul(z768, z4)));
  sts128(dst + 8192, pk(z1024), pk(cmul(z1024, z256)), pk(cmul(z1024, z512)), pk(cmul(z1024, z768)));
  sts32(scr + W_MISC + (wt >> 5) * 4, mx);
}
__device__ __forceinline__ int kgen_tables_m(uint32_t scr, int wt, const KgState& k) {
  const uint32_t dst = scr + wt * 16;
  const uint4 e4 = lds128(scr + W_MISC);
  const float2 z16 = csq(k.z8), z32 = csq(z16);
  const int em = max(min((int)(max(max(e4.x, e4.y), max(e4.z, e4.w)) >> 23), 238), 16);
  const float sc = __uint_as_float((uint32_t)(127 + 4 + 127 - em) << 23);
  sts32(scr + W_MISC + 16 + (wt >> 5) * 4, __reduce_add_sync(0xffffffffu, __float2int_rn(k.kl * sc * 262144.f)));
  const float2 c0 = make_float2(k.c0.x * sc, k.c0.y * sc);
  const float2 c1 = cmul(c0, k.z8), c2 = cmul(c0, z16), c4 = cmul(c0, z32), c3 = cmul(c1, z16), c5 = cmul(c1, z32), c6 = cmul(c2, z32), c7 = cmul(c3, z32);
  uint32_t pr[4], pi[4], yr[4], yi[4];
  pr[0] = pack_h(c0.x, c1.x); pi[0] = pack_h(c0.y, c1.y);
  pr[1] = pack_h(c2.x, c3.x); pi[1] = pack_h(c2.y, c3.y);
  pr[2] = pack_h(c4.x, c5.x); pi[2] = pack_h(c4.y, c5.y);
  pr[3] = pack_h(c6.x, c7.x); pi[3] = pack_h(c6.y, c7.y);
  sts128(dst, pr[0], pr[1], pr[2], pr[3]); sts128(dst + 2048, pi[0], pi[1], pi[2], pi[3]);
#pragma unroll
  for (int q = 1; q < 4; q++) {
    const uint32_t w = q == 1 ? k.w64 : q == 2 ? k.w128 : k.w192;
#pragma unroll
    for (int i = 0; i < 4; i++) pmul(pr[i], pi[i], w, yr[i], yi[i]);
    sts128(dst + q * 4096, yr[0], yr[1], yr[2], yr[3]); sts128(dst + q * 4096 + 2048, yi[0], yi[1], yi[2], yi[3]);
  }
  return em;
}
__device__ __forceinline__ void kgen_build(uint32_t tb, int wg, int wt, uint32_t k0, uint32_t k1, uint32_t k2) {
  const uint32_t kt = tb + W_KT, sc = tb + W_L3 + 3072;
  const int ix = ((wt >> 2) + (wt & 3) * 32 - 1) & 127;
  const uint32_t a3 = tb + W_CW + 32 + ((ix & 1) ? 0 : 304) + (ix >> 1) * 4;
  const uint32_t v3 = wt ? k2 : k2 >> 16;
  sts32(sc + 4 + wt * 4, __byte_perm(k0, k1, 0x5432));
  sts16(sc + 544 + (wt & ~3) + (wt & 1) * 2 + (wt & 2) * 64, k1 >> 16);
  sts16(a3, v3); sts16(a3 + 6, v3);
  if ((unsigned)(wt - 32) < 18u) sts128(kt + (wt < 36 ? -512 : 64 + 4128 - 576) + wt * 16, 0, 0, 0, 0);
  if (wt == 127) sts32(sc, k0 & 0xFFFF0000u);
  if (wt == 0) { sts32(sc + 516, k1); sts16(sc + 800, k2); }
  bar_sync(1 + wg, 128);
  const uint32_t cw = tb + W_CW + 32 + (wt >> 6) * 48 + wt * 4;
  const uint32_t pv = lds32(sc + wt * 4), nx = lds32(sc + 8 + wt * 4), c2 = lds16(sc + 544 + wt * 2), n2 = lds16(sc + 546 + wt * 2);
  sts128(tb + W_L3 + 512 + (wt >> 6) * 512 + wt * 16, lds32(cw), lds32(cw - 8), lds32(cw - 16), lds32(cw - 24));
  const bool odd = wt & 1;
  sts64(kt + 64 + wt * 8, __byte_perm(k0, pv, 0x5410), __byte_perm(k0, 0, 0x1032));
  sts64(kt + 64 + 1024 + wt * 8, __byte_perm(k1, pv, (odd || wt == 0) ? 0x7610 : 0x1010), __byte_perm(k1, nx, odd ? 0x1076 : 0x1010));
  const uint32_t cc = c2 * 0x10001u, nc = __byte_perm(n2, c2, 0x5410), nn = n2 * 0x10001u;
  sts128(kt + 64 + 2048 + wt * 16, cc, cc, odd ? nc : cc, odd ? nn : nc);
  if (wt == 127) { sts128(kt + 64 + 4096, nn, nn, nn, nn); sts128(kt + 64 + 4112, nn, nn << 16, 0, 0); }
}

__device__ __forceinline__ void load_a(uint32_t (&a)[4], uint32_t kp, int j) {
  a[0] = lds32(kp + 64 * j); a[1] = lds32(kp + 64 * j + 512); a[2] = lds32(kp + 64 * j - 32); a[3] = lds32(kp + 64 * j + 480);
}
__device__ __forceinline__ uint32_t band(int d, int lo, int hi) {
  return ((unsigned)(d - lo) <= (unsigned)(hi - lo) ? 1u : 0u) | ((unsigned)(d - 1 - lo) <= (unsigned)(hi - lo) ? 0x10000u : 0u);
}
__device__ __forceinline__ uint32_t hadd2u(uint32_t a, uint32_t b) { __half2 r = __hadd2(*(__half2*)&a, *(__half2*)&b); return *(uint32_t*)&r; }

__device__ __forceinline__ void zero_pads(uint32_t tb, int wt) {
  if (!(wt & 32)) sts128(tb + W_L3 + (wt >> 6) * 512 + wt * 16, 0, 0, 0, 0);
  if ((wt & 63) < 3) sts128(tb + W_CW + (wt >> 6) * 304 + (wt & 63) * 16, 0, 0, 0, 0);
}
__device__ __forceinline__ uint32_t tr_base(int lane) {
  return OFF_YT + (2 * (lane >> 3) + (lane & 1)) * YT_PITCH + ((lane >> 1) & 1) * (8 * YT_PITCH + 64) + ((lane >> 2) & 1) * 16;
}

__device__ __forceinline__ uint32_t sc_addr(int tp) { return OFF_YT + (tp < 16 ? tp * YT_PITCH + (tp >> 3) * 64 + 1152 : 8 * YT_PITCH - 512 + tp * 32); }
#define X_PS 1
#define X_PW 15
#define X_HU 16
#define X_HB 0
#define X_NE 2
#define X_SCT 10000
#define X_DELTA 400
#define X_DSTEP 2000
#define X_PF0 2500
#define X_PFD 600
#define X_TD 450
#define X_WS 6
#define X_OR 8
#define X_ABS 5100
#define X_XD 0
#define X_RD 900
#define X_HD 500
#define X_PD 1150
#define X_PROMO 2
#define X_YD2 500
#define X_GO 2
#define X_GW 2
#define X_NS 4700
#define X_XS 0
#define X_LAG 1800
#define X_YD 1550
struct TMaps { CUtensorMap m[10]; };
__device__ __forceinline__ uint32_t h2bf(uint32_t w) { const float2 f = h2f(w); return pack_bf(f.x, f.y); }
__device__ __forceinline__ uint32_t keep(uint32_t v) { asm volatile("" : "+r"(v)); return v; }
__device__ __forceinline__ uint2 ldr64(const void* p) { uint2 v; asm volatile("{ .reg .b64 t; ld.relaxed.gpu.global.b64 t, [%2]; mov.b64 {%0, %1}, t; }" : "=r"(v.x), "=r"(v.y) : "l"(p) : "memory"); return v; }
__host__ __device__ __forceinline__ uint32_t down_box(int s, bool five) {
  return five ? OFF_W + W_BYTES + 12288 + (s / 3) * (W_BYTES - 12288) + s * 4096 : s < 6 ? OFF_W + W_BYTES + BOX + (s >> 1) * (W_BYTES - 10240) + s * 5120 : OFF_W + (s - 6) * 5120;
}
__device__ __forceinline__ void load_tile(const CUtensorMap* tmx, int i, int c, int again = 0) {
  asm volatile("mbarrier.arrive.expect_tx.shared::cta.b64 _, [%0], 8704;" :: "r"(MB_UL + i * 16 + again) : "memory");
  asm volatile("cp.async.bulk.tensor.3d.shared::cluster.global.mbarrier::complete_tx::bytes [%0], [%1, {%3, %4, %5}], [%2];"
               :: "r"(i < 2 ? OFF_T + i * TILE : OFF_W), "l"(tmx), "r"(MB_UL + i * 16 + again), "r"(0), "r"(c), "r"(-8) : "memory");
}
template <bool FAR> __device__ __forceinline__ void load_params(const Params& p, uint32_t ch, int wt, uint32_t dst, bool on) {
  const int o01 = (wt & 16) ? p.off[1] : p.off[0], o23 = (wt & 16) ? p.off[3] : p.off[2], o45 = (wt & 16) ? p.off[5] : p.off[4];
  const int o = (wt & 64) ? ((wt & 32) ? p.off[6] : o45) : ((wt & 32) ? o23 : o01);
  const unsigned char* b = FAR ? p.far[min(wt >> 4, 6)] : p.x + (long long)o * 16;
  asm volatile("{ .reg .pred q; setp.ne.u32 q, %2, 0; @q cp.async.cg.shared.global [%0], [%1], 16; }"
               :: "r"(dst + wt * 16), "l"(b + (wt < 96 ? ch * 256 + (wt & 15) * 16 : (ch >> 3) * 16)), "r"((uint32_t)(on && wt < 97)) : "memory");
}

struct ConvC { uint32_t ca, cb, bands; };
__device__ __forceinline__ ConvC conv_consts(int w, int lane) {
  const int h = w & 1, P = (w >> 1) & 1, d0 = 8 * h + (lane >> 2) - 2 * (lane & 3);
  ConvC k;
  k.ca = keep((W_KT + (16 + 256 * P + d0) * 4) | (((8 + 64 * P + lane) * 64 + (((h + ((w >> 1) & 2)) ^ (lane >> 1)) & 3) * 16) << 16));
  k.cb = keep(lane < 8 ? 0xFFFEFFFEu : ~0u);
  k.bands = keep(band(d0, 12, 20) + 2 * band(d0 + 8, 12, 20) + 4 * band(d0 + 16, 12, 20) + 8 * band(d0 + 24, 12, 20)
                 + 16 * band(d0 - 8, 5, 11) + 32 * band(d0, 5, 11) + 64 * band(d0 + 8, 5, 11) + 128 * band(d0 + 16, 5, 11));
  return k;
}
struct ConvPre { uint32_t e0, e2, f2, a[3][4]; };
__device__ __forceinline__ uint32_t lds32_if(uint32_t a, bool on) {
  uint32_t v; asm volatile("{ .reg .pred q; setp.ne.u32 q, %2, 0; mov.b32 %0, 0; @q ld.shared.b32 %0, [%1]; }" : "=r"(v) : "r"(a), "r"((uint32_t)on) : "memory"); return v;
}
__device__ __forceinline__ void conv_pre(ConvPre& r, uint32_t kp, int part, bool on, bool P) {
  if (part & 1) { r.e0 = lds32_if(kp + 4096, on && !P); r.e2 = lds32_if(kp + 4064, on && !P); r.f2 = lds32_if(kp + 4128, on && !P); }
#pragma unroll
  for (int j = 0; j < 3; j++) if (part & (j < X_PS ? 1 : 2)) {
    r.a[j][0] = lds32_if(kp + 2048 + 64 * j, on); r.a[j][1] = lds32_if(kp + 2560 + 64 * j, on); r.a[j][2] = lds32_if(kp + 2016 + 64 * j, on); r.a[j][3] = lds32_if(kp + 2528 + 64 * j, on);
  }
}
__device__ __forceinline__ void conv_item(uint32_t tb, uint32_t tl, int bid, int bn, ConvPre& pre, const ConvC& cv, uint32_t zero, const CUtensorMap* tmx, int ch, int warp, int lane, bool hold, bool more) {
  const bool go = more && warp == 0 && lane == 0;
  const uint32_t kp = tb + (cv.ca & 0xFFFFu);
  const uint32_t dlo = (tl >> 4) + 32 + ((warp >> 1) & 2) + (1u << 16), dhi = 32u | (2u << 30);
  const bool P = warp & 2;
  float a32[16], b32[16], a64[32];
  uint32_t A[40][4];
#define STEP(J) { wgmma64<0>(a64, A[J], dlo + 256 - 4 * (J), dhi); \
    if ((J) == 32) wgmma32_init<0>(b32, A[J], dlo, dhi); else wgmma32<0>(b32, A[J], ((J) < 8 ? dlo ^ zero : dlo) + 128 - 4 * (J), dhi); \
    if ((J) == 0) wgmma32_init<0>(a32, A[J], dlo, dhi); else if ((J) < 8) wgmma32<0>(a32, A[J], (dlo ^ zero) - 4 * (J), dhi); }
#define LD(J) load_a(A[J], kp, J);
#define FIRST(J) wg_fence(); STEP(J) wg_commit(); wg_wait<1>(); wg_fence();
  {
    uint32_t win[16], x9[4], x7[4], e[4], f[4];
    const uint32_t bz = keep(cv.bands);
#define BAND(i) keep((bz & (0x10001u << (i))) * (0x3C00u >> (i)))
    e[0] = pre.e0; e[2] = pre.e2; e[1] = keep(bz & 0x100u); e[3] = keep(bz & 0x200u);
    f[2] = pre.f2; f[0] = keep(bz & 0x4000u); f[1] = keep(bz & 0x8000u); f[3] = keep(bz & 0x300u);
#pragma unroll
    for (int j = 0; j < 12; j++) A[32 + j / 4][j & 3] = pre.a[j / 4][j & 3];
    const uint32_t q[12] = {BAND(0), BAND(5), keep(bz & 0x400u), BAND(4), BAND(2), BAND(7), BAND(1), BAND(6), keep(bz & 0x800u), keep(bz & 0x1000u), BAND(3), keep(bz & 0x2000u)};
#undef BAND
    const uint32_t ta = keep(tl + 512 + (warp & 3) * 2048 + lane * 64 + (lane & 6) * 8);
    if (X_GO && hold) mbar_wait(MB_GO);
    uint32_t mbl = MB_UL + (warp & 8) * 2, ph = 0;
#pragma unroll 1
    for (int it = 0; it < SPIN_MAX; it++) {
      if (ch < 512) mbar_wait(mbl, ph);
      if (it == 1) TS(13);
      TS(3);
      wg_fence();
      wgmma64h_init(win, q[0], q[1], q[2], q[3], dlo, dhi);
      wgmma64h(win, q[4], q[5], q[6], q[7], dlo - 4, dhi);
      wgmma64h(win, q[8], q[9], q[10], q[11], dlo - 8, dhi);
      wg_commit();
      wgmma64_init<0>(a64, e, dlo, dhi);
      wgmma64<0>(a64, f, dlo - 4, dhi);
      wg_commit();
      if (ch >= 512) break;
      uint32_t r0, r1, r2, r3, ok;
      if (warp & 4) {
        mbar_wait(mbl + 8);
        if (__all_sync(0xffffffffu, it || lds32(MISC_RT + (warp & 8)) == 0)) break;
        wg_wait<0>();
        continue;
      }
      ldsm4(ta, r0, r1, r2, r3);
      ok = r0 & r1 & r2 & r3;
      ldsm4(ta ^ 32, r0, r1, r2, r3);
      asm volatile("{ .reg .pred q; setp.ne.u32 q, %1, 0; barrier.red.and.pred q, %2, 128, q; selp.u32 %0, 1, 0, q; }" : "=r"(ok) : "r"((ok & r0 & r1 & r2 & r3 & 1u) | (lane & 3)), "r"(1 + (warp >> 2)) : "memory");
      if (ok) { if ((warp & 3) == 0 && lane == 0) { sts32(MISC_RT + warp, it); mbar_arrive(MB_UL + 8 + warp * 2); } break; }
      wg_wait<0>();
      if ((warp & 3) == 0 && lane == 0) load_tile(tmx - 1, warp >> 3, ch, 56);
      mbl = MB_UL + 56 + (warp & 8) * 2; ph = it & 1;
    }
    wg_wait<1>();
#pragma unroll
    for (int i = 0; i < 4; i++) {
      const int tl = 2 * ((i & 1) + ((i & 2) ? 0 : 4));
      x9[i] = P ? win[tl + 4] : win[tl]; x7[i] = P ? win[tl + 5] : win[tl + 1];
    }
    const uint32_t l3lo = ((tb + W_L3) >> 4) + (32u << 16);
    wg_fence();
    wgmma64<0>(a64, x9, l3lo, 8);
    wgmma64<0>(a64, x7, l3lo + 96, 8);
    wg_commit();
  }
  STEP(32) STEP(33) STEP(34) wg_commit(); wg_wait<1>();
  LD(35) LD(36) LD(37) LD(38)
  FIRST(35) STEP(36) STEP(37) STEP(38) wg_commit();
  LD(39) LD(0)
  TS(17);
  if (X_GO == 1 && go) mbar_arrive(MB_GO);
  FIRST(39) STEP(0) wg_commit();
  LD(1) LD(2) LD(3)
  FIRST(1) STEP(2) STEP(3) wg_commit();
  LD(4) LD(5)
  if (X_GO == 2 && go) mbar_arrive(MB_GO);
  FIRST(4) STEP(5) wg_commit();
  LD(6) LD(7)
  wg_fence(); STEP(6) STEP(7) wg_commit();
#undef STEP
#undef LD
#undef FIRST
  TS(18);
  if (X_GO == 3 && go) mbar_arrive(MB_GO);
  const uint32_t xc = tb + W_KT + (warp & 3) * 1024 + lane * 16;
  if (more) bar_sync(7, 288);
  wg_wait<1>();
  conv_pre(pre, kp + ALT, 1, more, P);
  wg_wait<0>();
  conv_pre(pre, kp + ALT, 2, more, P);
  uint32_t E[16], o[8];
#define ACC(i) ((i) < 16 ? a32[i] : (i) < 32 ? b32[(i) - 16] : a64[(i) - 32])
  E[0] = pack_h(a32[0], a32[1]);
#pragma unroll
  for (int i = 1; i < 16; i++) E[i] = pack_h(ACC(4 * i) + ACC(4 * i - 2), ACC(4 * i + 1) + ACC(4 * i - 1));
#undef ACC
#pragma unroll
  for (int j = 0; j < 8; j++) o[j] = P ? (j < 2 ? 0u : E[j - 2]) : E[8 + j];
  sts128(xc, o[0], o[1], o[2], o[3]); sts128(xc + 512, o[4], o[5], o[6], o[7]);
#pragma unroll
  for (int j = 0; j < 8; j++) o[j] = P ? E[6 + j] : E[j];
  TS(25);
  if (more) {
    sts128(xc + 4096, o[0], o[1], o[2], o[3]); sts128(xc + 4608, o[4], o[5], o[6], o[7]);
    bar_arrive(12, 192);
    return;
  }
  bar_sync(1 + (warp >> 2), 128);
  const uint4 vv[2] = {lds128(xc + (P ? -2048 : 2048)), lds128(xc + (P ? -1536 : 2560))};
#pragma unroll
  for (int q = 0; q < 2; q++) {
    const uint4 v = vv[q];
    stsm4t(tl + (cv.ca >> 16) + q * 2048, hadd2u(o[4 * q], v.x) & cv.cb, hadd2u(o[4 * q + 1], v.y) & cv.cb, hadd2u(o[4 * q + 2], v.z) & cv.cb, hadd2u(o[4 * q + 3], v.w) & cv.cb);
  }
  fence_async();
  bar_sync(bid, bn);
  if (warp == 0 && lane == 0) mbar_arrive(MB_REL);
  if ((warp & 7) == (ch < 512 ? 7 : 3) && lane == 0) {
    asm volatile("cp.async.bulk.tensor.3d.global.shared::cta.bulk_group [%0, {%3, %2, %3}], [%1];" :: "l"(tmx), "r"(tl + 512), "r"(ch), "r"(0) : "memory");
    asm volatile("cp.async.bulk.commit_group;" ::: "memory");
  }
}

template <bool FAR> __global__ void __launch_bounds__(NT, 1)
fused_kernel(const __grid_constant__ Params p, const __grid_constant__ TMaps tm) {
  extern __shared__ __align__(1024) unsigned char smem[];
  const int c = blockIdx.x;
  const bool five = (c & 1) == 0;
  const uint32_t pitch = five ? 64 : 80;
  const uint32_t ones = 0x3F803F80u;
  const int tid = threadIdx.x, lane = tid & 31;
  {
    const int w4 = tid >> 7, k5 = !five && w4 == 3;
    load_params<FAR>(p, k5 ? 512 + (c >> 1) : (w4 & 2) * 128 + 2 * c + (w4 & 1), tid & 127, OFF_W + w4 * W_BYTES + W_KT + k5 * 2048, w4 != 2 && w4 != 4);
  }
  const int warp = (int)uni(tid >> 5), wg = warp >> 2;
  TS(0);
  if (__builtin_expect(wg == 4, 0)) {
    asm volatile("setmaxnreg.dec.sync.aligned.u32 32;");
    const int role = warp;
    const int u0 = (c >> 1) * 9 + (five ? ((c & 2) ? 5 : 0) : ((c & 2) ? 0 : 4));
    const uint32_t t0 = clock() + c * 4;
    if (role == 16) {
      if (lane < 19) asm volatile("mbarrier.init.shared::cta.b64 [%0], %1;" :: "r"(OFF_MISC + lane * 8), "r"((unsigned)(lane - 2) < 4u ? 4 : 1) : "memory");
      if (lane < 2) asm volatile("mbarrier.arrive.expect_tx.shared::cta.b64 _, [%0], %1;" :: "r"(OFF_MISC + lane * 8), "r"(lane ? (five ? 36864 : 51200) : pitch * 1152) : "memory");
      fence_async();
      bar_arrive(5, 576);
      const CUtensorMap* tmb = &tm.m[five ? 3 : 0];
#pragma unroll 1
      for (int u = 0; u < 17; u++) {
        const uint32_t e = p.sched[five][u], kind = e & 3, s = (e >> 2) & 15, dst = e >> 14;
        if (kind == 3) continue;
        while ((int)(clock() - t0) < X_PF0 + (u < X_NE ? u * X_PFD : X_LAG + u * X_TD)) __nanosleep(20);
        if (e & 0x3FC0) mbar_wait(OFF_MISC + ((e >> 6) & 255));
        if (lane == 0) {
          if (kind == 2) asm volatile("cp.async.bulk.tensor.3d.shared::cluster.global.mbarrier::complete_tx::bytes [%0], [%1, {%3, %4, %5}], [%2];"
                                      :: "r"(dst), "l"(tmb + 2), "r"(MB_D), "r"(0), "r"(u0 * 8), "r"(s) : "memory");
          else tma_box(dst, tmb + kind, MB_GU, u0 * 8, s * 96);
        }
        if (u == 5) TS(2);
        if (u == 10) TS(3);
      }
      TS(4);
      TS_DUMP();
#define FINISH0 bar_sync(12, 192);        \
        _Pragma("unroll 1") for (int w = role & 2; w < (role & 2) + 2; w++) { \
          const uint32_t xa = OFF_W + W_KT + lane * 16, mk = lane < 8 ? 0xFFFEFFFEu : ~0u, ya = OFF_T + (8 + lane) * 64 + (((w & 1) ^ (lane >> 1)) & 3) * 16 + (w & 2) * 2048; \
          const uint4 a = lds128(xa + 4096 + w * 1024), b = lds128(xa + (w ^ 2) * 1024), d = lds128(xa + 4608 + w * 1024), e = lds128(xa + 512 + (w ^ 2) * 1024); \
          stsm4t(ya, hadd2u(a.x, b.x) & mk, hadd2u(a.y, b.y) & mk, hadd2u(a.z, b.z) & mk, hadd2u(a.w, b.w) & mk); \
          stsm4t(ya + 2048, hadd2u(d.x, e.x) & mk, hadd2u(d.y, e.y) & mk, hadd2u(d.z, e.z) & mk, hadd2u(d.w, e.w) & mk); \
        } \
        fence_async();
    } else if (role == 17) {
      if (smem_u32(smem) != SB) __trap();
      bar_sync(10, 576);
      if (lane == 0) {
        fence_async();
        while ((int)(clock() - t0) < X_NS - c * 4) {}
        asm volatile("cp.async.bulk.global.shared::cta.bulk_group [%0], [%1], 10240;" :: "l"(&p.s->X[c * DM * 2 + 512]), "r"(OFF_G) : "memory");
        asm volatile("cp.async.bulk.commit_group;" ::: "memory");
        asm volatile("cp.async.bulk.wait_group 0;" ::: "memory");
      }
      if (lane == 0) mbar_arrive(MB_GF);
      bar_arrive(11, 96);
      if (five) { FINISH0 bar_arrive(13, 192); }
    } else if (role == 18) {
      sts32(MISC_EPOCH, 0);
      bar_arrive(5, 576);
      uint4* q = lane < 2 ? &p.s->R[c * 2 + lane] : lane < 11 ? &p.s->HS[c * 9 + lane - 2] : lane == 11 ? &p.s->HS[1152 + (c & 7)] : (uint4*)&p.s->FLAG[c * 8];
      if (lane < (c < 8 ? 12 : 11)) str128(q, ~0u, ~0u, ~0u, ~0u);
      const uint32_t ep = __shfl_sync(0xffffffffu, ldr32(q), 31) + 1u;
      sts32(MISC_EPOCH, ep | 0x80000000u);
      TSX(21);
      if (lane == 31) str32(q, ep);
      bar_sync(11, 96);
      TSX(14);
      mbar_wait(MB_KF + (lane & 3) * 8);
      __syncwarp();
      { const uint2 e = lds64(MISC_EM); if (lane < 2) str128(&p.s->SC[c * 2 + lane], e.x, __byte_perm(e.y, ep, 0x6540), 0, 0); }
      TSX(17);
      while ((int)(clock() - t0) < X_SCT) __nanosleep(100);
      TSX(18);
      {
        uint2 v[4];
#pragma unroll 1
        for (int it = 0; it < SPIN_MAX; it++) {
          uint32_t bad = 0;
#pragma unroll
          for (int q = 0; q < 4; q++) v[q] = ldr64(&p.s->SC[lane * 2 + q * 64]);
#pragma unroll
          for (int q = 0; q < 4; q++) bad |= (v[q].y >> 8) ^ (ep & 0xFFFFFFu);
          if (!__any_sync(0xffffffffu, bad)) break;
        }
        TSX(25);
#pragma unroll
        for (int q = 0; q < 4; q++) {
          const uint32_t sa = (lane >> 4) * YT_PITCH + (lane & 15) * 2;
          sts16(sc_addr(2 * q) + sa, v[q].x); sts16(sc_addr(8 + 2 * q) + sa, v[q].x >> 16);
          if (lane & 1) asm volatile("st.shared.u8 [%0], %1;" :: "r"(sc_addr(16) + q * 16 + (lane >> 1)), "r"(v[q].y) : "memory");
        }
      }
      __syncwarp();
      if (lane == 0) mbar_arrive(MB_SC);
      TSX(27);
    } else {
      uint32_t w[9], d[9];
      float s = 0.f;
#pragma unroll
      for (int i = 0; i < 9; i++) { w[i] = ldnc32(p.w_r + lane + 32 * i); d[i] = ldnc32(p.dskip + lane + 32 * i); }
#pragma unroll
      for (int i = 0; i < 9; i++) { sts32(OFF_WR + lane * 4 + i * 128, w[i]); sts32(OFF_WR + 1152 + lane * 4 + i * 128, d[i]); s += bf_lo(w[i]) + bf_hi(w[i]); }
      sts32(MISC_SW, __float_as_uint(warp_sum(s)));
      TSX(23);
      bar_sync(10, 576);
      if (lane == 0) {
        const uint32_t tp = clock();
        TSX(1);
        while ((int)(clock() - tp) < X_DELTA || (int)(clock() - t0) < X_ABS - c * 4) {}
        TSX(24);
        load_tile(&tm.m[6], 0, c);
        TSX(15);
        while ((int)(clock() - t0) < X_ABS + X_DSTEP - c * 4) {}
      }
      bar_sync(11, 96);
      if (lane == 0) {
        load_tile(&tm.m[6], 1, 128 + c);
      }
      if (five) {
        mbar_wait(MB_KF);
#pragma unroll 1
        for (int it = 0; it < SPIN_MAX; it++) {
          if (lane == 0) load_tile(&tm.m[8], 2, 512 + (c >> 1));
          mbar_wait(MB_UL + 32, it & 1);
          uint32_t m = 1;
#pragma unroll
          for (int q = 0; q < 4; q++) { uint32_t r0, r1, r2, r3; ldsm4(OFF_W + 512 + lane * 64 + (lane & 6) * 8 + q * 2048, r0, r1, r2, r3); m &= r0 & r1 & r2 & r3; }
          if (__all_sync(0xffffffffu, m || (lane & 3))) break;
        }
        bar_arrive(7, 288);
        FINISH0
        bar_arrive(13, 192);
      }
      bar_sync(0, 544);
      if (lane == 0) mbar_arrive(MB_H);
    }
    return;
  }
  const int wt = tid & 127, g = lane >> 2, t = lane & 3;
  const uint32_t wb = OFF_W + wg * W_BYTES;
  const uint32_t xrow = OFF_YT + (wt >> 3) * YT_PITCH + (wt & 64) + (lane & 7) * 16;
  if (wg == 2) {
    const unsigned char* xp = p.x + (uint32_t)((c * 16 + (wt >> 3)) * 1152 + (lane & 7) * 16);
    { const uint32_t tq = clock(); while ((int)(clock() - tq) < X_XD) {} }
#pragma unroll
    for (int k = 0; k < 9; k++) asm volatile("cp.async.cg.shared.global [%0], [%1], 16;" :: "r"(xrow + k * 128), "l"(xp + k * 128) : "memory");
  }
  asm volatile("cp.async.commit_group;" ::: "memory");
  const ConvC cv = conv_consts(warp, lane);
  zero_pads(wb, wt);
  load_params<FAR>(p, 254 + 2 * c + wg, wt, wb + W_KT, wg == 2 || (wg == 3 && !five));
  asm volatile("cp.async.commit_group;" ::: "memory");
  asm volatile("setmaxnreg.inc.sync.aligned.u32 112;");
  {
    uint4 kw;
    uint4* kx = &p.s->KX[(c >> 1) * 128 + wt];
    bool two = wg == 3;
    uint32_t ep;
    int phase = wg == 2 ? 3 : 2;
#pragma unroll 1
    for (;;) {
      const bool first = two && !five;
      if (phase) asm volatile("cp.async.wait_group 1;" ::: "memory"); else asm volatile("cp.async.wait_group 0;" ::: "memory");
      if (phase == 3) {
        TS(21);
        float d[3][4], r;
        uint4 a[9];
#pragma unroll
        for (int k = 0; k < 9; k++) a[k] = lds128(xrow + k * 128);
#pragma unroll
        for (int i = 0; i < 4; i++) d[0][i] = d[1][i] = d[2][i] = 0.f;
#pragma unroll
        for (int k = 0; k < 9; k++) { mma_bf16(d[(2 * k) % 3], a[k].x, ones, a[k].y, ones, a[k].x, a[k].y); mma_bf16(d[(2 * k + 1) % 3], a[k].z, ones, a[k].w, ones, a[k].z, a[k].w); }
#pragma unroll
        for (int i = 0; i < 4; i++) d[0][i] += d[1][i] + d[2][i];
        const LnC lc = ln_consts(d[0][2] + d[0][3], __shfl_sync(0xffffffffu, d[0][0], 9 * t) + __shfl_sync(0xffffffffu, d[0][1], 9 * t + 4), r);
        if (lane < 12) sts16(MISC_LN1 + g * 32 + (warp & 3) * 8 + t * 2, lane < 4 ? lc.m2 : lane < 8 ? lc.rh2 : lc.rl2);
      } else {
        KgState ks;
        uint32_t raw[7];
        bar_sync(1 + wg, 128);
        TS(22);
#pragma unroll
        for (int i = 0; i < 7; i++) raw[i] = lds16(wb + W_KT + first * 2048 + i * 256 + (i < 6 ? wt : (first ? c >> 1 : 2 * c + (wg & 1)) & 7) * 2);
        kgen_tables_n(raw, wb, wt, ks);
        TS(20);
        bar_sync(1 + wg, 128);
        const int em = kgen_tables_m(wb, wt, ks);
        asm volatile("st.shared.u8 [%0], %1;" :: "r"(MISC_EM + wg + first), "r"(em + 9) : "memory");
        fence_async();
      }
      if (phase & 2) {
        const uint32_t tr_addr = tr_base(lane) + warp * 32;
        uint4* dst = &p.s->X[c * DM * 2 + warp * 32 + (8 * (t >> 1) + g) * 2 + (t & 1)];
        TS(23);
        bar_sync(5, 576);
        uint32_t x[3][4];
        ldsm4t(tr_addr, x[0][0], x[0][1], x[0][2], x[0][3]);
        const uint4 m = lds128(MISC_LN1 + (t & 1) * 16), rl = lds128(MISC_LN1 + 64 + (t & 1) * 16), rh = lds128(MISC_LN1 + 32 + (t & 1) * 16);
        ldsm4t(tr_addr + 512, x[1][0], x[1][1], x[1][2], x[1][3]);
        if (wg == 3) ldsm4t(tr_addr + 640, x[2][0], x[2][1], x[2][2], x[2][3]);
#pragma unroll
        for (int q = 0; q < 3; q++) {
          if (q < 2 || wg == 3) {
            const uint32_t r0 = ln_apply(x[q][0], m.x, rh.x, rl.x), r1 = ln_apply(x[q][1], m.y, rh.y, rl.y), r2 = ln_apply(x[q][2], m.z, rh.z, rl.z), r3 = ln_apply(x[q][3], m.w, rh.w, rl.w);
            const uint32_t w0 = (pack_h(bf_lo(r0), bf_hi(r0)) & 0xFFFEFFFEu) | 1u, w1 = pack_h(bf_lo(r1), bf_hi(r1)), w2 = pack_h(bf_lo(r2), bf_hi(r2)), w3 = pack_h(bf_lo(r3), bf_hi(r3));
            if (q == 0) str128(dst, w0, w1, w2, w3);
            else sts128(OFF_G + warp * 512 + (8 * (t >> 1) + g) * 32 + (t & 1) * 16 + (q == 2 ? 2048 : 0), w0, w1, w2, w3);
          }
          if (q == 0) TS(30);
        }
        bar_arrive(10, 576);
        TS(1);
      } else bar_sync(1 + wg, 128);
      phase &= 1;
      if (phase) { phase = 0; continue; }
      TS(14);
      float acc[20];
      const uint32_t alo = (wb >> 4) | (8u << 16);
      wg_fence();
      wgmma40_ss_init(acc, alo, alo + 1024, 2048 >> 4);
#pragma unroll
      for (int k = 1; k < 8; k++) wgmma40_ss(acc, alo + k * 16, alo + 1024 + k * 16, 2048 >> 4);
      wg_commit();
      const uint4 k4 = lds128(wb + W_MISC + 16);
      const float k2048 = (float)(int)(k4.x + k4.y + k4.z + k4.w) * (1.f / 262144.f);
      wg_wait<0>();
      const float un = 1.f / 8192.f;
      kw.x = pack_h((acc[0] - acc[3]) * un, (acc[4] - acc[7]) * un);
      kw.y = pack_h((acc[8] - acc[11]) * un, (acc[12] - acc[15]) * un);
      kw.z = pack_h((acc[16] - acc[19]) * un, k2048 * un);
      TS(24);
      ep = 0;
      if (two) SPIN_WHILE(ep == 0, ep = lds32(MISC_EPOCH));
      if (five || !two) break;
      str128(kx, kw.x, kw.y, kw.z, ep);
      two = false;
    }
    if (lane == 0) mbar_arrive(MB_KF + wg * 8);
    if (two) { mbar_wait(MB_KF); zero_pads(OFF_W + ALT, wt); }
    uint32_t tb = wb;
#pragma unroll 1
    for (;;) {
      kgen_build(tb, wg, wt, kw.x, kw.y, kw.z);
      TS(15);
      if (!two) break;
      two = false;
      kw.w = 0;
      SPIN_WHILE(kw.w != ep, kw = ldr128(kx));
      tb = OFF_W + ALT;
    }
    fence_async();
    TS(31);
    if (tb != wb) bar_arrive(7, 288);
    bar_sync(1 + wg, 128);
  }
  uint32_t tpub;
  ConvPre pre;
  conv_pre(pre, wb + (cv.ca & 0xFFFFu), 3, true, warp & 2);
#pragma unroll 1
  for (int item = 0;; item++) {
    TS(2);
    conv_item(item ? OFF_W + ALT : wb, item ? OFF_W : OFF_T + (wg >> 1) * TILE, item ? 1 : 13 + (wg >> 1), item ? 128 : five && wg == 1 ? 192 : 256, pre, cv, p.zero,
              &tm.m[item ? 9 : 7], item ? 512 + (c >> 1) : (wg >> 1) * 128 + c, warp, lane, five && wg >= X_GW, five && !wg && !item);
    tpub = clock() - (item ? X_YD : wg >= 2 ? X_YD2 : 0);
    if (wg || !five || item) break;
    TS(27);
  }
  TS(4);

  const int ln = lane ^ p.zero, td = warp * 32 + ln, gg = ln >> 2, tt = ln & 3;
  const int tok = c * 16 + warp;
  const int fu = warp / 3, fk = warp - fu * 3;
  uint32_t wa[12][4];
  {
    uint32_t hw[9], wr[9];
    const uint32_t row = keep(OFF_YT + warp * YT_PITCH + (warp >> 3) * 64 + ln * 16);
    const uint32_t wabase = keep(((ln & 8) ? OFF_W + (fk + 1) * W_BYTES : OFF_G + fk * 192 * pitch) + ((ln >> 4) * 8 + (ln & 7)) * pitch
                                 + (five ? ((fu ^ (ln >> 1)) & 3) : min(fu, 4)) * 16);
    float sw;
    {
      const bool three = wg == 1;
      const int ch = 8 * (tt >> 1) + gg;
      const uint32_t tr_addr = tr_base(ln);
      const uint4* ysrc = &p.s->X[c * DM * 2 + ch * 2 + (tt & 1)];
      uint32_t x[3][4], ud[3][4], s[3];
      uint4 v[3];
#define TL(q) ((q) < 2 ? 2 * warp + (q) : 28 + warp)
      asm volatile("cp.async.bulk.wait_group.read 0;" ::: "memory");
      while ((int)(clock() - tpub) < X_YD) {}
      TS(5);
      v[0] = ldr128(ysrc + TL(0) * 32); v[1] = ldr128(ysrc + TL(1) * 32); v[2] = make_uint4(three, 0, 0, 0);
      mbar_wait(MB_REL);
      const uint4 m = lds128(MISC_LN1 + (tt & 1) * 16), rh = lds128(MISC_LN1 + 32 + (tt & 1) * 16), rl = lds128(MISC_LN1 + 64 + (tt & 1) * 16);
#pragma unroll
      for (int i = 0; i < 6; i++) if (i < 4 || three) wr[i] = (gg & 2) ? ones : lds32(OFF_WR + TL(i >> 1) * 32 + (i & 1) * 16 + tt * 4);
      const uint32_t ha = keep(OFF_YT + (ln & 7) * YT_PITCH + (ln >> 4) * (8 * YT_PITCH + 64) + (ln & 8) * 2);
      const uint32_t pa = keep(OFF_PART + warp * 4 + ((gg & 2) * 8 + (gg & 4) * 2 + 2 * tt + (gg & 1)) * 80), pb = keep(OFF_PART + 2560 + warp * 4 + gg * 80);
      float dl[4] = {0.f, 0.f, 0.f, 0.f}, dh[4] = {0.f, 0.f, 0.f, 0.f};
      sw = __uint_as_float(lds32(MISC_SW));
#pragma unroll
      for (int q = 0; q < 3; q++) {
        if (q < 2 || three) {
          const uint32_t dk = lds16(OFF_WR + 1152 + ch * 2 + TL(q) * 32) * 0x10001u;
          ldsm4t(tr_addr + TL(q) * 32, x[q][0], x[q][1], x[q][2], x[q][3]);
          ud[q][0] = bf_mul2(ln_apply(x[q][0], m.x, rh.x, rl.x), dk); ud[q][1] = bf_mul2(ln_apply(x[q][1], m.y, rh.y, rl.y), dk);
          ud[q][2] = bf_mul2(ln_apply(x[q][2], m.z, rh.z, rl.z), dk); ud[q][3] = bf_mul2(ln_apply(x[q][3], m.w, rh.w, rl.w), dk);
        }
      }
      mbar_wait(MB_SC);
#pragma unroll
      for (int q = 0; q < 3; q++) {
        asm volatile("ld.shared.u8 %0, [%1];" : "=r"(s[q]) : "r"((q < 2 ? sc_addr(warp) + q * 16 : sc_addr(16) + (warp & 3) * 16) + ch) : "memory");
        s[q] = keep(s[q] * 0x800080u);
      }
#define FIN(q) stsm4t(tr_addr + TL(q) * 32, bf_add2(x[q][0], bf_fma2(h2bf(v[q].x), s[q], ud[q][0])), bf_add2(x[q][1], bf_fma2(h2bf(v[q].y), s[q], ud[q][1])), \
                      bf_add2(x[q][2], bf_fma2(h2bf(v[q].z), s[q], ud[q][2])), bf_add2(x[q][3], bf_fma2(h2bf(v[q].w), s[q], ud[q][3])));
      SPIN_WHILE((v[0].x | v[1].x) & 1u, _Pragma("unroll") for (int q = 0; q < 3; q++) if (v[q].x & 1u) v[q] = ldr128(ysrc + TL(q) * 32));
      if (v[2].x & 1u) v[2] = ldr128(ysrc + TL(2) * 32);
#define STAT(q) { uint32_t r0, r1, r2, r3; ldsm4(ha + TL(q) * 32, r0, r1, r2, r3); \
        mma_bf16(dl, r0, wr[2 * q], r1, wr[2 * q + 1], r0, r1); mma_bf16(dh, r2, wr[2 * q], r3, wr[2 * q + 1], r2, r3); }
      FIN(0) FIN(1)
      __syncwarp();
      STAT(0) STAT(1)
      if (three) {
        SPIN_WHILE(v[2].x & 1u, if (v[2].x & 1u) v[2] = ldr128(ysrc + TL(2) * 32));
        FIN(2)
        __syncwarp();
        STAT(2)
      }
      if (gg & 1) { dl[0] = dl[1]; dl[2] = dl[3]; dh[0] = dh[1]; dh[2] = dh[3]; }
      sts32(pa, __float_as_uint((gg & 4) ? dh[2] : dl[2]));
      if (tt == (gg >> 1)) { sts32(pb, __float_as_uint(dl[0])); sts32(pb + 640, __float_as_uint(dh[0])); }
#undef STAT
#undef FIN
#undef TL
    }
    const uint32_t ra = keep(OFF_PART + (ln & 15) * 80 + (ln & 16) * 2);
    uint16_t* rp = (uint16_t*)p.s->R + c * 16 + (ln & 15);
    asm volatile("" : "+l"(rp));
    TS(28);
    bar_sync(0, 544);
    TS(6);
    if (warp == X_PW) {
      float z[3], rd;
#pragma unroll
      for (int k = 2; k >= 0; k--) {
        const uint4 a = lds128(ra + k * 1280), b = lds128(ra + k * 1280 + 16);
        z[k] = ((__uint_as_float(a.x) + __uint_as_float(a.y)) + (__uint_as_float(a.z) + __uint_as_float(a.w))) + ((__uint_as_float(b.x) + __uint_as_float(b.y)) + (__uint_as_float(b.z) + __uint_as_float(b.w)));
      }
#pragma unroll
      for (int k = 2; k >= 0; k--) z[k] += __shfl_xor_sync(0xffffffffu, z[k], 16);
      const LnC l = ln_consts(z[1], z[2], rd);
      const uint32_t b = pack_bf(0.f, fmaf(-bf_lo(l.m2), sw, z[0]) * rd);
      const uint32_t k16 = max(min((b ^ (((int)b >> 31) | 0x80000000u)) >> 16, 0xFFFEu), 1u);
      if (ln < 16) str16(rp, k16);
      sts64(OFF_RK + (ln & 15) * 8, __byte_perm(l.m2, l.rh2, 0x5410), __byte_perm(l.rl2, k16, 0x5410));
    }
    bar_sync(5, 512);
    TS(7);
    const uint32_t tr0 = clock();
    {
      const uint4 a = lds128(row), b = lds128(row + 512);
      hw[8] = lds32(row + 1024 - ln * 12);
      hw[0] = a.x; hw[1] = a.y; hw[2] = a.z; hw[3] = a.w; hw[4] = b.x; hw[5] = b.y; hw[6] = b.z; hw[7] = b.w;
    }
    const uint2 lk = lds64(OFF_RK + warp * 8);
    LnC l2;
    l2.m2 = __byte_perm(lk.x, 0, 0x1010); l2.rh2 = __byte_perm(lk.x, 0, 0x3232); l2.rl2 = __byte_perm(lk.y, 0, 0x1010);
    const uint32_t key = (lk.y & 0xFFFF0000u) | (2047 - tok);
    uint32_t loc = ln < 16 ? (lds32(OFF_RK + 4 + ln * 8) & 0xFFFF0000u) | (2047 - c * 16 - ln) : 0u;
    int rank = __popc(__ballot_sync(0xffffffffu, loc > key));
#pragma unroll
    for (int i = 0; i < 9; i++) wr[i] = keep(ln_apply(hw[i], l2.m2, l2.rh2, l2.rl2));
    const uint2* rsrc = (const uint2*)p.s->R + td;
    uint2 rv;
    bool rbad = true;
    mbar_wait(MB_GU);
    if (warp < (five ? 12 : 15)) {
#pragma unroll
      for (int k = 0; k < X_WS; k++) ldsm4t(wabase + k * 16 * pitch, wa[k][0], wa[k][1], wa[k][2], wa[k][3]);
    }
#define OUT_ROW { uint32_t* o = p.out + tok * 288 + ln * 4; \
      *(uint4*)o = make_uint4(bf_add2(hw[0], wr[0]), bf_add2(hw[1], wr[1]), bf_add2(hw[2], wr[2]), bf_add2(hw[3], wr[3])); \
      *(uint4*)(o + 128) = make_uint4(bf_add2(hw[4], wr[4]), bf_add2(hw[5], wr[5]), bf_add2(hw[6], wr[6]), bf_add2(hw[7], wr[7])); \
      o[256 - ln * 3] = bf_add2(hw[8], wr[8]); }
    if (rank >= X_OR) OUT_ROW
#pragma unroll 1
    for (int base = 0; base < 8; base += 4) {
      uint32_t T[4];
#pragma unroll
      for (int j = 0; j < 4; j++) {
        const uint32_t mx = __reduce_max_sync(0xffffffffu, loc);
        if (loc == mx) loc = 0;
        T[j] = (td >> 2) == c ? ~0u : (td >> 2) < c ? (mx & 0xFFFF0000u) - 1u : mx | 0xFFFFu;
      }
      const uint32_t sh = keep(ln < 16 ? 0x4440u + (rank & 3) : 0x4344u), ca = keep(MISC_CNT + base * 16 + (ln & 15) * 4);
      while ((int)(clock() - tr0) < X_RD) {}
      SPIN_WHILE(rbad, if (rbad) rv = ldr64(rsrc); const uint32_t m = __vmaxu2(rv.x, rv.y); rbad = max(m, m << 16) >= 0xFFFF0000u);
      TS(16);
      uint32_t cnt = 0, cn2 = 0;
#pragma unroll
      for (int j = 0; j < 4; j++)
        asm("{ .reg .pred a, b, c, d; setp.gt.u32 a, %2, %6; setp.gt.u32 b, %3, %6; setp.gt.u32 c, %4, %6; setp.gt.u32 d, %5, %6; "
            "@a add.u32 %0, %0, %7; @b add.u32 %1, %1, %7; @c add.u32 %0, %0, %7; @d add.u32 %1, %1, %7; }"
            : "+r"(cnt), "+r"(cn2) : "r"(rv.x), "r"(rv.x << 16), "r"(rv.y), "r"(rv.y << 16), "r"(T[j]), "r"(1u << (8 * j)));
      sts32(MISC_CNT + base * 16 + warp * 4, __reduce_add_sync(0xffffffffu, cnt + cn2));
      bar_sync(0, 512);
      cnt = __reduce_add_sync(0xffffffffu, __byte_perm(lds32(ca), 0, sh));
      if ((rank & ~3) == base && rank + (int)(cnt & 0xFFFFu) < 8) {
        rank += cnt & 0xFFFFu;
        uint4* hs = p.s->HS + rank * 72 + ln;
        str128(hs, wr[0], wr[1], wr[2], wr[3]); str128(hs + 32, wr[4], wr[5], wr[6], wr[7]); str32((uint32_t*)(hs + 64) - ln * 3, wr[8]);
        str128(hs + 576, hw[0], hw[1], hw[2], hw[3]); str128(hs + 608, hw[4], hw[5], hw[6], hw[7]); str32((uint32_t*)(hs + 640) - ln * 3, hw[8]);
        if (ln == 0) str32(&p.s->HS[1152 + rank], key);
        rank = 16;
      }
      if (cnt >= (4u << 16)) break;
    }
    TS(8);
    tpub = clock();
    if (rank < X_OR) OUT_ROW
    if (warp < (five ? 12 : 15)) {
#pragma unroll
      for (int k = X_WS; k < 12; k++) ldsm4t(wabase + k * 16 * pitch, wa[k][0], wa[k][1], wa[k][2], wa[k][3]);
    }
  }
  uint32_t wd[10][4];
  const uint32_t xb = keep(OFF_XS + (ln & 7) * 1168 + (fk * 24 + (ln >> 3)) * 16);
  if (warp >= 7) {
    const uint32_t db = down_box(warp - 7, five) + (ln & 7) * 128;
    mbar_wait(MB_D);
#pragma unroll
    for (int j = 0; j < 4; j++) {
      const uint32_t a = db + (ln >> 4) * 1024 + (((2 * j + ((ln >> 3) & 1)) ^ (ln & 7)) << 4);
      ldsm4t(a, wd[j][0], wd[j][1], wd[j][2], wd[j][3]);
      ldsm4t(a + 2048, wd[4 + j][0], wd[4 + j][1], wd[4 + j][2], wd[4 + j][3]);
    }
#pragma unroll
    for (int j = 0; j < 2; j++) ldsm4t(db + 4096 + (((4 * j + (ln >> 3)) ^ (ln & 7)) << 4), wd[8 + j][0], wd[8 + j][1], wd[8 + j][2], wd[8 + j][3]);
  } else if (warp < 6) {
    const int r = td / 24;
    const uint4* src = &p.s->HS[td + r * 48];
    const uint32_t xs = keep(OFF_XS + (td + r * 49) * 16);
    uint4 a[3];
    uint32_t m = ~0u;
    while ((int)(clock() - tpub) < X_HD) {}
    TS(19);
    SPIN_WHILE(m == ~0u, if (m == ~0u) { a[0] = ldr128(src); a[1] = ldr128(src + 24); a[2] = ldr128(src + 48); } m = max(max(max(a[0].x, a[1].x), max(a[2].x, a[2].y)), max(a[2].z, a[2].w)));
#pragma unroll
    for (int q = 0; q < 3; q++) sts128(xs + q * 384, a[q].x, a[q].y, a[q].z, a[q].w);
  }
  bar_sync(0, 512);
  TS(9);

  if (warp < (five ? 12 : 15)) {
    float d0[4] = {0.f, 0.f, 0.f, 0.f}, d1[4] = {0.f, 0.f, 0.f, 0.f};
#pragma unroll
    for (int k = 0; k < 12; k += 2) {
      uint32_t b0, b1, b2, b3;
      ldsm4(xb + k * 32, b0, b1, b2, b3);
      mma_bf16(d0, wa[k][0], wa[k][1], wa[k][2], wa[k][3], b0, b1);
      mma_bf16(d1, wa[k + 1][0], wa[k + 1][1], wa[k + 1][2], wa[k + 1][3], b2, b3);
    }
    sts128(OFF_RED + td * 16, __float_as_uint(d0[0] + d1[0]), __float_as_uint(d0[1] + d1[1]), __float_as_uint(d0[2] + d1[2]), __float_as_uint(d0[3] + d1[3]));
  }
  TS(26);
  if (warp < 5) {
    const uint32_t rb = OFF_RED + warp * 1536 + ln * 16;
    bar_sync(9, 512);
    const uint4 pa = lds128(rb), pb = lds128(rb + 512), pc = lds128(rb + 1024);
    const float ga = bfr(__uint_as_float(pa.x) + __uint_as_float(pb.x) + __uint_as_float(pc.x));
    const float gb = bfr(__uint_as_float(pa.y) + __uint_as_float(pb.y) + __uint_as_float(pc.y));
    const uint32_t uu = pack_bf(__uint_as_float(pa.z) + __uint_as_float(pb.z) + __uint_as_float(pc.z), __uint_as_float(pa.w) + __uint_as_float(pb.w) + __uint_as_float(pc.w));
    float ra, rb2;
    asm("rcp.approx.ftz.f32 %0, %1;" : "=f"(ra) : "f"(1.f + ex2(ga * -1.4426950408889634f)));
    asm("rcp.approx.ftz.f32 %0, %1;" : "=f"(rb2) : "f"(1.f + ex2(gb * -1.4426950408889634f)));
    const uint32_t act = bf_mul2(pack_bf(ga * ra, gb * rb2), uu);
    sts32(OFF_ACT + td * 4, act);
  } else bar_arrive(9, 512);
  uint4* dst = &p.s->X[c * DM * 2 + (warp - 7) * 64 + tt * 8 + gg];
  asm volatile("" : "+l"(dst));
  bar_sync(8, 512);
  tpub = clock();
  if (warp >= 7) {
    uint32_t b0, b1, b2, b3, b4;
    ldsm4t(OFF_ACT + ln * 16, b0, b1, b2, b3);
    asm volatile("ldmatrix.sync.aligned.m8n8.x1.trans.shared.b16 {%0}, [%1];" : "=r"(b4) : "r"(OFF_ACT + 512 + ln * 16) : "memory");
    float y[4][4];
#pragma unroll
    for (int j = 0; j < 4; j++) {
      y[j][0] = y[j][1] = y[j][2] = y[j][3] = 0.f;
      mma_bf16(y[j], wd[j][0], wd[j][1], wd[j][2], wd[j][3], b0, b1);
    }
#pragma unroll
    for (int j = 0; j < 4; j++) mma_bf16(y[j], wd[4 + j][0], wd[4 + j][1], wd[4 + j][2], wd[4 + j][3], b2, b3);
    if (!five) {
#pragma unroll
      for (int j = 0; j < 4; j++) mma_bf16_k8(y[j], wd[8 + (j >> 1)][2 * (j & 1)], wd[8 + (j >> 1)][2 * (j & 1) + 1], b4);
    }
    str128(dst, (pack_bf(y[0][0], y[0][1]) & ~1u) | 0x10000u, pack_bf(y[0][2], y[0][3]), pack_bf(y[1][0], y[1][1]), pack_bf(y[1][2], y[1][3]));
    str128(dst + 32, (pack_bf(y[2][0], y[2][1]) & ~1u) | 0x10000u, pack_bf(y[2][2], y[2][3]), pack_bf(y[3][0], y[3][1]), pack_bf(y[3][2], y[3][3]));
  }
  TS(10);

  if (c < 72) {
    const uint4* src = &p.s->X[(warp * 4 + tt) * (DM * 2) + c * 8 + gg];
    const int slot = (c & 3) * 2 + (ln >> 4), dw = (c >> 2) * 16 + (ln & 15);
    uint32_t hv = 0, kv = 0, res = 0, rs2 = 0;
    uint32_t* o = p.out;
    if (warp == 0) {
      hv = ~0u;
      SPIN_WHILE(max(hv, kv) == ~0u, hv = ldr32((const uint32_t*)p.s->HS + 2304 + slot * 288 + dw); kv = ldr32(&p.s->HS[1152 + slot]));
      const float r = bf_hi(kv ^ (((int)~kv >> 31) | 0x80000000u));
      float rs;
      asm("rcp.approx.ftz.f32 %0, %1;" : "=f"(rs) : "f"(1.f + ex2(r * -1.4426950408889634f)));
      rs2 = keep(pack_bf(rs, rs));
      res = lds32(OFF_XS + slot * 1168 + dw * 4);
      o += (2047 - (int)(kv & 2047u)) * 288 + dw;
      asm volatile("" : "+l"(o));
    }
    const uint32_t sel = (gg & 1) ? 0x3F800000u : 0x00003F80u;
    const uint32_t q0 = keep((gg >> 1) == 0 ? sel : 0u), q1 = keep((gg >> 1) == 1 ? sel : 0u), q2 = keep((gg >> 1) == 2 ? sel : 0u), q3 = keep((gg >> 1) == 3 ? sel : 0u);
    const uint32_t fa = keep(OFF_FIN + warp * 256 + (gg & 1) * 128 + (gg >> 1) * 32 + tt * 8), fb = keep(OFF_FIN + ln * 8);
    uint4 a0 = make_uint4(0, 0, 0, 0), a1 = a0;
    while ((int)(clock() - tpub) < X_PD) {}
    SPIN_WHILE(!(a0.x & a1.x & 0x10000u), if (!(a0.x & 0x10000u)) a0 = ldr128(src); if (!(a1.x & 0x10000u)) a1 = ldr128(src + 64 * DM * 2));
    float d[4] = {0.f, 0.f, 0.f, 0.f}, e[4] = {0.f, 0.f, 0.f, 0.f};
    mma_bf16(d, q0, q2, q1, q3, a0.x, a0.y); mma_bf16(e, q0, q2, q1, q3, a0.z, a0.w);
    mma_bf16(d, q0, q2, q1, q3, a1.x, a1.y); mma_bf16(e, q0, q2, q1, q3, a1.z, a1.w);
    sts64(fa, __float_as_uint(d[0] + e[2]), __float_as_uint(d[1] + e[3]));
    TS(11);
    if (warp == 0) {
      bar_sync(0, 512);
      float2 s[16];
#pragma unroll
      for (int i = 0; i < 16; i++) { const uint2 q = lds64(fb + i * 256); s[i] = make_float2(__uint_as_float(q.x), __uint_as_float(q.y)); }
#pragma unroll
      for (int k = 1; k < 16; k *= 2)
#pragma unroll
        for (int i = 0; i < 16; i += 2 * k) { s[i].x += s[i + k].x; s[i].y += s[i + k].y; }
      *o = bf_add2(hv, bf_add2(res, bf_mul2(pack_bf(s[0].x, s[0].y), rs2)));
    } else bar_arrive(0, 512);
  }
  TS(12);
  TS_DUMP();
}

typedef CUresult (*EncodeFn)(CUtensorMap*, CUtensorMapDataType, cuuint32_t, void*, const cuuint64_t*, const cuuint64_t*, const cuuint32_t*,
                             const cuuint32_t*, CUtensorMapInterleave, CUtensorMapSwizzle, CUtensorMapL2promotion, CUtensorMapFloatOOBfill);

}

extern "C" void kernel_launch(void* const* d_in, const int* in_sizes, int n_in, void* d_out, int out_size) {
  (void)in_sizes; (void)n_in; (void)out_size;
  static EncodeFn enc = nullptr;
  static Scratch* scratch = nullptr;
  if (!enc) {
    void* fn = nullptr;
    cudaDriverEntryPointQueryResult qr;
    cudaGetDriverEntryPoint("cuTensorMapEncodeTiled", &fn, cudaEnableDefault, &qr);
    enc = (EncodeFn)fn;
    cudaGetSymbolAddress((void**)&scratch, g_S);
    cudaFuncSetAttribute(fused_kernel<false>, cudaFuncAttributeMaxDynamicSharedMemorySize, SMEM_BYTES);
    cudaFuncSetAttribute(fused_kernel<true>, cudaFuncAttributeMaxDynamicSharedMemorySize, SMEM_BYTES);
  }
  TMaps tm;
  for (int i = 0; i < 6; i++) {
    const bool dn = i % 3 == 2;
    const cuuint32_t w = i < 3 ? 40 : 32;
    cuuint64_t gd[3] = {(cuuint64_t)(dn ? 64 : FF), (cuuint64_t)(dn ? FF : DM), 9};
    cuuint64_t gs[2] = {(cuuint64_t)(dn ? DM * 2 : FF * 2), 128};
    cuuint32_t bx[3] = {dn ? 64 : w, dn ? w : 96, i < 3 ? 2u : 3u};
    cuuint32_t es[3] = {1, 1, 1};
    enc(&tm.m[i], CU_TENSOR_MAP_DATA_TYPE_BFLOAT16, dn ? 3 : 2, d_in[11 + i % 3], gd, gs, bx, es, CU_TENSOR_MAP_INTERLEAVE_NONE,
        dn ? CU_TENSOR_MAP_SWIZZLE_128B : i < 3 ? CU_TENSOR_MAP_SWIZZLE_NONE : CU_TENSOR_MAP_SWIZZLE_64B,
        (CUtensorMapL2promotion)X_PROMO, CU_TENSOR_MAP_FLOAT_OOB_FILL_NONE);
  }
  for (int i = 6; i < 10; i++) {
    cuuint64_t gd[3] = {i < 8 ? 32u : 16u, i < 8 ? DM / 2u : DM, NCTA};
    cuuint64_t gs[2] = {i < 8 ? 64u : 32u, DM * 32};
    cuuint32_t bx[3] = {32, 1, (i & 1) ? 128u : 136u};
    cuuint32_t es[3] = {1, 1, 1};
    enc(&tm.m[i], CU_TENSOR_MAP_DATA_TYPE_FLOAT16, 3, scratch->X, gd, gs, bx, es, CU_TENSOR_MAP_INTERLEAVE_NONE, CU_TENSOR_MAP_SWIZZLE_64B,
        CU_TENSOR_MAP_L2_PROMOTION_NONE, CU_TENSOR_MAP_FLOAT_OOB_FILL_NONE);
  }
  Params p;
  p.x = (const unsigned char*)d_in[0];
  bool far = false;
  for (int i = 0; i < 7; i++) {
    p.far[i] = (const unsigned char*)d_in[1 + i];
    const long long d = (long long)((intptr_t)d_in[1 + i] - (intptr_t)d_in[0]);
    p.off[i] = (int)(d / 16);
    if ((long long)p.off[i] * 16 != d) far = true;
  }
  p.dskip = (const uint32_t*)d_in[8];
  p.w_r = (const uint32_t*)d_in[10];
  for (int f = 0; f < 2; f++) {
    static const int kind[17] = {0, 0, 0, 0, 2, 2, 0, 0, 1, 1, 1, 1, 1, 1, 2, 2, 2};
    static const int idx[2][17] = {{2, 3, 4, 5, 6, 8, 0, 1, 0, 1, 2, 3, 4, 5, 0, 2, 4}, {2, 3, 4, 5, 0, -1, 0, 1, 0, 1, 2, 3, 4, 5, 3, -1, 6}};
    static const int blk[2][17] = {{-1, -1, -1, -1, 0, -1, 4, -1, 1, -1, 2, -1, 3, -1, 16, -1, -1}, {-1, -1, -1, -1, 1, -1, 4, -1, -1, -1, 2, -1, 3, -1, 16, -1, -1}};
    const int pitch = f ? 64 : 80;
    for (int u = 0; u < 17; u++) {
      const int s = idx[f][u];
      const uint32_t dst = kind[u] == 0 ? OFF_G + s * 96 * pitch : kind[u] == 2 ? down_box(s, f) : OFF_W + W_BYTES + (s >> 1) * W_BYTES + (s & 1) * 96 * pitch;
      const uint32_t mb = u >= 14 ? (u >= X_HU ? MB_H - OFF_MISC : X_HB) : blk[f][u] >= 0 ? MB_KF - OFF_MISC + blk[f][u] * 8 : 0;
      p.sched[f][u] = s < 0 ? 3u : kind[u] | s << 2 | mb << 6 | dst << 14;
    }
  }
  p.out = (uint32_t*)d_out;
  p.zero = 0;
  p.ts = nullptr;
  p.s = scratch;
  if (far) { fused_kernel<true><<<NCTA, NT, SMEM_BYTES, cudaStreamPerThread>>>(p, tm); return; }
  fused_kernel<false><<<NCTA, NT, SMEM_BYTES, cudaStreamPerThread>>>(p, tm);
}
```

```cpp
#include <cuda_runtime.h>
#include <cuda.h>
#include <cuda_bf16.h>
#include <cuda_fp16.h>
#include <stdint.h>
#include <stddef.h>

namespace {

constexpr int NCTA = 128;
constexpr int NT = 640;
constexpr int DM = 576;
constexpr int FF = 4608;
constexpr int SPIN_MAX = 1 << 20;

struct Scratch {
  uint4 X[NCTA * DM * 2];
  uint4 KX[64 * 128];
  uint4 HS[1152 + 8];
  uint4 R[256];
  uint4 SC[256];
  uint32_t FLAG[NCTA * 8];
};
__device__ Scratch g_S;

#define CLKS(i)
#define TS(i)
#define TSX(i)
#define TS_DUMP()

constexpr int SB = 1024;
constexpr int BOX = 15360;
constexpr int OFF_G = SB;
constexpr int OFF_W = OFF_G + 3 * BOX;
constexpr int W_KT = 26624;
constexpr int W_L3 = W_KT + 4416;
constexpr int W_CW = W_L3 + 4096;
constexpr int W_MISC = W_CW + 640;
constexpr int W_BYTES = 35840;
constexpr int TILE = 10240;
constexpr int OFF_T = OFF_W + 4 * W_BYTES;
constexpr int ALT = TILE - W_KT;
static_assert(W_MISC + 32 <= W_BYTES && OFF_W % 1024 == 0 && W_BYTES % 1024 == 0 && W_BYTES + ALT <= 20480, "wg block");
constexpr int YT_PITCH = 1184;
constexpr int OFF_YT = OFF_T + 2 * TILE;
constexpr int OFF_WR = OFF_YT + 16 * YT_PITCH + 64;
constexpr int OFF_MISC = OFF_WR + 2304;
constexpr int SMEM_BYTES = OFF_MISC + 1024 - SB;
static_assert(OFF_YT % 16 == 0 && OFF_MISC % 16 == 0, "align");
static_assert(SMEM_BYTES <= 232448, "smem");
constexpr int MB_GU = OFF_MISC;
constexpr int MB_D = OFF_MISC + 8;
constexpr int MB_KF = OFF_MISC + 16;
constexpr int MB_GF = OFF_MISC + 48;
constexpr int MB_SC = OFF_MISC + 56;
constexpr int MB_UL = OFF_MISC + 64;
constexpr int MB_REL = OFF_MISC + 104;
constexpr int MB_GO = OFF_MISC + 112;
constexpr int MB_H = MB_KF + 128;
constexpr int MISC_EPOCH = OFF_MISC + 152;
constexpr int MISC_SW = OFF_MISC + 156;
constexpr int MISC_RT = OFF_MISC + 160;
constexpr int MISC_T0 = OFF_MISC + 296;
constexpr int MISC_EM = OFF_MISC + 288;
constexpr int OFF_PART = OFF_W + 20480;
constexpr int OFF_RK = OFF_PART + 3840;
constexpr int MISC_LN1 = OFF_MISC + 192;
constexpr int OFF_XS = OFF_T;
constexpr int OFF_RED = OFF_T + TILE;
constexpr int OFF_FIN = OFF_W + 3 * W_BYTES + W_KT;
constexpr int OFF_ACT = OFF_FIN + 4096;
constexpr int MISC_CNT = OFF_ACT + 1024;

__device__ __forceinline__ uint32_t smem_u32(const void* p) { return (uint32_t)__cvta_generic_to_shared(p); }
__device__ __forceinline__ uint32_t lds32(uint32_t a) { uint32_t v; asm volatile("ld.shared.b32 %0, [%1];" : "=r"(v) : "r"(a) : "memory"); return v; }
__device__ __forceinline__ uint32_t lds16(uint32_t a) { uint16_t v; asm volatile("ld.shared.u16 %0, [%1];" : "=h"(v) : "r"(a) : "memory"); return v; }
__device__ __forceinline__ uint2 lds64(uint32_t a) { uint2 v; asm volatile("ld.shared.v2.b32 {%0,%1}, [%2];" : "=r"(v.x), "=r"(v.y) : "r"(a) : "memory"); return v; }
__device__ __forceinline__ uint4 lds128(uint32_t a) { uint4 v; asm volatile("ld.shared.v4.b32 {%0,%1,%2,%3}, [%4];" : "=r"(v.x), "=r"(v.y), "=r"(v.z), "=r"(v.w) : "r"(a) : "memory"); return v; }
__device__ __forceinline__ void sts16(uint32_t a, uint32_t v) { asm volatile("st.shared.u16 [%0], %1;" :: "r"(a), "h"((uint16_t)v) : "memory"); }
__device__ __forceinline__ void sts32(uint32_t a, uint32_t v) { asm volatile("st.shared.b32 [%0], %1;" :: "r"(a), "r"(v) : "memory"); }
__device__ __forceinline__ void sts64(uint32_t a, uint32_t x, uint32_t y) { asm volatile("st.shared.v2.b32 [%0], {%1,%2};" :: "r"(a), "r"(x), "r"(y) : "memory"); }
__device__ __forceinline__ void sts128(uint32_t a, uint32_t x, uint32_t y, uint32_t z, uint32_t w) { asm volatile("st.shared.v4.b32 [%0], {%1,%2,%3,%4};" :: "r"(a), "r"(x), "r"(y), "r"(z), "r"(w) : "memory"); }
__device__ __forceinline__ void ldsm4(uint32_t a, uint32_t& r0, uint32_t& r1, uint32_t& r2, uint32_t& r3) {
  asm volatile("ldmatrix.sync.aligned.m8n8.x4.shared.b16 {%0,%1,%2,%3}, [%4];" : "=r"(r0), "=r"(r1), "=r"(r2), "=r"(r3) : "r"(a) : "memory");
}
__device__ __forceinline__ void ldsm2(uint32_t a, uint32_t& r0, uint32_t& r1) {
  asm volatile("ldmatrix.sync.aligned.m8n8.x2.shared.b16 {%0,%1}, [%2];" : "=r"(r0), "=r"(r1) : "r"(a) : "memory");
}
__device__ __forceinline__ void ldsm4t(uint32_t a, uint32_t& r0, uint32_t& r1, uint32_t& r2, uint32_t& r3) {
  asm volatile("ldmatrix.sync.aligned.m8n8.x4.trans.shared.b16 {%0,%1,%2,%3}, [%4];" : "=r"(r0), "=r"(r1), "=r"(r2), "=r"(r3) : "r"(a) : "memory");
}
__device__ __forceinline__ void stsm4t(uint32_t a, uint32_t r0, uint32_t r1, uint32_t r2, uint32_t r3) {
  asm volatile("stmatrix.sync.aligned.m8n8.x4.trans.shared.b16 [%0], {%1,%2,%3,%4};" :: "r"(a), "r"(r0), "r"(r1), "r"(r2), "r"(r3) : "memory");
}
__device__ __forceinline__ uint4 ldr128(const void* p) {
  unsigned long long lo, hi;
  asm volatile("{ .reg .b128 t; ld.relaxed.gpu.global.b128 t, [%2]; mov.b128 {%0, %1}, t; }" : "=l"(lo), "=l"(hi) : "l"(p) : "memory");
  return make_uint4((uint32_t)lo, (uint32_t)(lo >> 32), (uint32_t)hi, (uint32_t)(hi >> 32));
}
__device__ __forceinline__ void str128(void* p, uint32_t x, uint32_t y, uint32_t z, uint32_t w) {
  asm volatile("{ .reg .b128 t; .reg .b64 lo, hi; mov.b64 lo, {%1,%2}; mov.b64 hi, {%3,%4}; mov.b128 t, {lo, hi}; st.relaxed.gpu.global.b128 [%0], t; }"
               :: "l"(p), "r"(x), "r"(y), "r"(z), "r"(w) : "memory");
}
__device__ __forceinline__ void str64(void* p, uint32_t x, uint32_t y) {
  asm volatile("{ .reg .b64 t; mov.b64 t, {%1,%2}; st.relaxed.gpu.global.b64 [%0], t; }" :: "l"(p), "r"(x), "r"(y) : "memory");
}
__device__ __forceinline__ uint32_t ldr32(const void* p) { uint32_t v; asm volatile("ld.relaxed.gpu.global.b32 %0, [%1];" : "=r"(v) : "l"(p) : "memory"); return v; }
__device__ __forceinline__ void str32(void* p, uint32_t v) { asm volatile("st.relaxed.gpu.global.b32 [%0], %1;" :: "l"(p), "r"(v) : "memory"); }
__device__ __forceinline__ void str16(void* p, uint32_t v) { asm volatile("st.relaxed.gpu.global.u16 [%0], %1;" :: "l"(p), "h"((uint16_t)v) : "memory"); }
__device__ __forceinline__ void fence_gpu() { asm volatile("fence.acq_rel.gpu;" ::: "memory"); }
__device__ __forceinline__ void bar_sync(int id, int n) { asm volatile("bar.sync %0, %1;" :: "r"(id), "r"(n) : "memory"); }
__device__ __forceinline__ void bar_arrive(int id, int n) { asm volatile("bar.arrive %0, %1;" :: "r"(id), "r"(n) : "memory"); }

__device__ __forceinline__ float bf_lo(uint32_t w) { return __uint_as_float(w << 16); }
__device__ __forceinline__ float bf_hi(uint32_t w) { return __uint_as_float(w & 0xFFFF0000u); }
__device__ __forceinline__ uint32_t pack_bf(float lo, float hi) { uint32_t r; asm("cvt.rn.bf16x2.f32 %0, %1, %2;" : "=r"(r) : "f"(hi), "f"(lo)); return r; }
__device__ __forceinline__ uint32_t pack_h(float lo, float hi) { uint32_t r; asm("cvt.rn.f16x2.f32 %0, %1, %2;" : "=r"(r) : "f"(hi), "f"(lo)); return r; }
__device__ __forceinline__ uint32_t pack_hv(float lo, float hi) { uint32_t r; asm volatile("cvt.rn.f16x2.f32 %0, %1, %2;" : "=r"(r) : "f"(hi), "f"(lo) : "memory"); return r; }
__device__ __forceinline__ float bfr(float x) { return bf_lo(pack_bf(x, 0.f)); }
__device__ __forceinline__ uint32_t bf_sub2(uint32_t a, uint32_t b) { __nv_bfloat162 r = __hsub2(*(__nv_bfloat162*)&a, *(__nv_bfloat162*)&b); return *(uint32_t*)&r; }
__device__ __forceinline__ uint32_t bf_add2(uint32_t a, uint32_t b) { __nv_bfloat162 r = __hadd2(*(__nv_bfloat162*)&a, *(__nv_bfloat162*)&b); return *(uint32_t*)&r; }
__device__ __forceinline__ uint32_t bf_mul2(uint32_t a, uint32_t b) { __nv_bfloat162 r = __hmul2(*(__nv_bfloat162*)&a, *(__nv_bfloat162*)&b); return *(uint32_t*)&r; }
__device__ __forceinline__ float2 h2f(uint32_t w) { return __half22float2(*(__half2*)&w); }
__device__ __forceinline__ float ex2(float x) { float r; asm("ex2.approx.ftz.f32 %0, %1;" : "=f"(r) : "f"(x)); return r; }
__device__ __forceinline__ float warp_sum(float v) {
#pragma unroll
  for (int o = 16; o > 0; o >>= 1) v += __shfl_xor_sync(0xffffffffu, v, o);
  return v;
}
__device__ __forceinline__ void mma_f16_f32(float* d, uint32_t a0, uint32_t a1, uint32_t a2, uint32_t a3, uint32_t b0, uint32_t b1) {
  asm volatile("mma.sync.aligned.m16n8k16.row.col.f32.f16.f16.f32 {%0,%1,%2,%3}, {%4,%5,%6,%7}, {%8,%9}, {%0,%1,%2,%3};"
               : "+f"(d[0]), "+f"(d[1]), "+f"(d[2]), "+f"(d[3]) : "r"(a0), "r"(a1), "r"(a2), "r"(a3), "r"(b0), "r"(b1));
}
__device__ __forceinline__ void mma_f16_f16(uint32_t& d0, uint32_t& d1, uint32_t a0, uint32_t a1, uint32_t a2, uint32_t a3, uint32_t b0, uint32_t b1) {
  asm volatile("mma.sync.aligned.m16n8k16.row.col.f16.f16.f16.f16 {%0,%1}, {%2,%3,%4,%5}, {%6,%7}, {%0,%1};"
               : "+r"(d0), "+r"(d1) : "r"(a0), "r"(a1), "r"(a2), "r"(a3), "r"(b0), "r"(b1));
}
__device__ __forceinline__ void mma_bf16(float* d, uint32_t a0, uint32_t a1, uint32_t a2, uint32_t a3, uint32_t b0, uint32_t b1) {
  asm volatile("mma.sync.aligned.m16n8k16.row.col.f32.bf16.bf16.f32 {%0,%1,%2,%3}, {%4,%5,%6,%7}, {%8,%9}, {%0,%1,%2,%3};"
               : "+f"(d[0]), "+f"(d[1]), "+f"(d[2]), "+f"(d[3]) : "r"(a0), "r"(a1), "r"(a2), "r"(a3), "r"(b0), "r"(b1));
}
__device__ __forceinline__ void mma_bf16_k8(float* d, uint32_t a0, uint32_t a1, uint32_t b0) {
  asm volatile("mma.sync.aligned.m16n8k8.row.col.f32.bf16.bf16.f32 {%0,%1,%2,%3}, {%4,%5}, {%6}, {%0,%1,%2,%3};"
               : "+f"(d[0]), "+f"(d[1]), "+f"(d[2]), "+f"(d[3]) : "r"(a0), "r"(a1), "r"(b0));
}

__device__ __forceinline__ void wg_fence() { asm volatile("wgmma.fence.sync.aligned;" ::: "memory"); }
__device__ __forceinline__ void wg_commit() { asm volatile("wgmma.commit_group.sync.aligned;" ::: "memory"); }
template <int N> __device__ __forceinline__ void wg_wait() { asm volatile("wgmma.wait_group.sync.aligned %0;" :: "n"(N) : "memory"); }
template <int TB> __device__ __forceinline__ void wgmma32(float* d, const uint32_t* a, uint32_t dlo, uint32_t dhi) {
  asm volatile("{ .reg .b64 dd; mov.b64 dd, {%20, %21}; wgmma.mma_async.sync.aligned.m64n32k16.f32.f16.f16 "
               "{%0,%1,%2,%3,%4,%5,%6,%7,%8,%9,%10,%11,%12,%13,%14,%15}, {%16,%17,%18,%19}, dd, 1, 1, 1, %22; }"
               : "+f"(d[0]), "+f"(d[1]), "+f"(d[2]), "+f"(d[3]), "+f"(d[4]), "+f"(d[5]), "+f"(d[6]), "+f"(d[7]), "+f"(d[8]), "+f"(d[9]), "+f"(d[10]), "+f"(d[11]), "+f"(d[12]), "+f"(d[13]), "+f"(d[14]), "+f"(d[15])
               : "r"(a[0]), "r"(a[1]), "r"(a[2]), "r"(a[3]), "r"(dlo), "r"(dhi), "n"(TB));
}
template <int TB> __device__ __forceinline__ void wgmma64(float* d, const uint32_t* a, uint32_t dlo, uint32_t dhi) {
  asm volatile("{ .reg .b64 dd; mov.b64 dd, {%36, %37}; wgmma.mma_async.sync.aligned.m64n64k16.f32.f16.f16 "
               "{%0,%1,%2,%3,%4,%5,%6,%7,%8,%9,%10,%11,%12,%13,%14,%15,%16,%17,%18,%19,%20,%21,%22,%23,%24,%25,%26,%27,%28,%29,%30,%31}, {%32,%33,%34,%35}, dd, 1, 1, 1, %38; }"
               : "+f"(d[0]), "+f"(d[1]), "+f"(d[2]), "+f"(d[3]), "+f"(d[4]), "+f"(d[5]), "+f"(d[6]), "+f"(d[7]), "+f"(d[8]), "+f"(d[9]), "+f"(d[10]), "+f"(d[11]), "+f"(d[12]), "+f"(d[13]), "+f"(d[14]), "+f"(d[15]), "+f"(d[16]), "+f"(d[17]), "+f"(d[18]), "+f"(d[19]), "+f"(d[20]), "+f"(d[21]), "+f"(d[22]), "+f"(d[23]), "+f"(d[24]), "+f"(d[25]), "+f"(d[26]), "+f"(d[27]), "+f"(d[28]), "+f"(d[29]), "+f"(d[30]), "+f"(d[31])
               : "r"(a[0]), "r"(a[1]), "r"(a[2]), "r"(a[3]), "r"(dlo), "r"(dhi), "n"(TB));
}
template <int TB> __device__ __forceinline__ void wgmma64_init(float* d, const uint32_t* a, uint32_t dlo, uint32_t dhi) {
  asm volatile("{ .reg .b64 dd; mov.b64 dd, {%36, %37}; wgmma.mma_async.sync.aligned.m64n64k16.f32.f16.f16 "
               "{%0,%1,%2,%3,%4,%5,%6,%7,%8,%9,%10,%11,%12,%13,%14,%15,%16,%17,%18,%19,%20,%21,%22,%23,%24,%25,%26,%27,%28,%29,%30,%31}, {%32,%33,%34,%35}, dd, 0, 1, 1, %38; }"
               : "=f"(d[0]), "=f"(d[1]), "=f"(d[2]), "=f"(d[3]), "=f"(d[4]), "=f"(d[5]), "=f"(d[6]), "=f"(d[7]), "=f"(d[8]), "=f"(d[9]), "=f"(d[10]), "=f"(d[11]), "=f"(d[12]), "=f"(d[13]), "=f"(d[14]), "=f"(d[15]), "=f"(d[16]), "=f"(d[17]), "=f"(d[18]), "=f"(d[19]), "=f"(d[20]), "=f"(d[21]), "=f"(d[22]), "=f"(d[23]), "=f"(d[24]), "=f"(d[25]), "=f"(d[26]), "=f"(d[27]), "=f"(d[28]), "=f"(d[29]), "=f"(d[30]), "=f"(d[31])
               : "r"(a[0]), "r"(a[1]), "r"(a[2]), "r"(a[3]), "r"(dlo), "r"(dhi), "n"(TB));
}
template <int TB> __device__ __forceinline__ void wgmma32_init(float* d, const uint32_t* a, uint32_t dlo, uint32_t dhi) {
  asm volatile("{ .reg .b64 dd; mov.b64 dd, {%20, %21}; wgmma.mma_async.sync.aligned.m64n32k16.f32.f16.f16 "
               "{%0,%1,%2,%3,%4,%5,%6,%7,%8,%9,%10,%11,%12,%13,%14,%15}, {%16,%17,%18,%19}, dd, 0, 1, 1, %22; }"
               : "=f"(d[0]), "=f"(d[1]), "=f"(d[2]), "=f"(d[3]), "=f"(d[4]), "=f"(d[5]), "=f"(d[6]), "=f"(d[7]), "=f"(d[8]), "=f"(d[9]), "=f"(d[10]), "=f"(d[11]), "=f"(d[12]), "=f"(d[13]), "=f"(d[14]), "=f"(d[15])
               : "r"(a[0]), "r"(a[1]), "r"(a[2]), "r"(a[3]), "r"(dlo), "r"(dhi), "n"(TB));
}
__device__ __forceinline__ void wgmma64h(uint32_t* d, uint32_t a0, uint32_t a1, uint32_t a2, uint32_t a3, uint32_t dlo, uint32_t dhi) {
  asm volatile("{ .reg .b64 dd; mov.b64 dd, {%20, %21}; wgmma.mma_async.sync.aligned.m64n64k16.f16.f16.f16 "
               "{%0,%1,%2,%3,%4,%5,%6,%7,%8,%9,%10,%11,%12,%13,%14,%15}, {%16,%17,%18,%19}, dd, 1, 1, 1, 0; }"
               : "+r"(d[0]), "+r"(d[1]), "+r"(d[2]), "+r"(d[3]), "+r"(d[4]), "+r"(d[5]), "+r"(d[6]), "+r"(d[7]), "+r"(d[8]), "+r"(d[9]), "+r"(d[10]), "+r"(d[11]), "+r"(d[12]), "+r"(d[13]), "+r"(d[14]), "+r"(d[15])
               : "r"(a0), "r"(a1), "r"(a2), "r"(a3), "r"(dlo), "r"(dhi));
}
__device__ __forceinline__ void wgmma64h_init(uint32_t* d, uint32_t a0, uint32_t a1, uint32_t a2, uint32_t a3, uint32_t dlo, uint32_t dhi) {
  asm volatile("{ .reg .b64 dd; mov.b64 dd, {%20, %21}; wgmma.mma_async.sync.aligned.m64n64k16.f16.f16.f16 "
               "{%0,%1,%2,%3,%4,%5,%6,%7,%8,%9,%10,%11,%12,%13,%14,%15}, {%16,%17,%18,%19}, dd, 0, 1, 1, 0; }"
               : "=r"(d[0]), "=r"(d[1]), "=r"(d[2]), "=r"(d[3]), "=r"(d[4]), "=r"(d[5]), "=r"(d[6]), "=r"(d[7]), "=r"(d[8]), "=r"(d[9]), "=r"(d[10]), "=r"(d[11]), "=r"(d[12]), "=r"(d[13]), "=r"(d[14]), "=r"(d[15])
               : "r"(a0), "r"(a1), "r"(a2), "r"(a3), "r"(dlo), "r"(dhi));
}
__device__ __forceinline__ void wgmma40_ss(float* d, uint32_t alo, uint32_t blo, uint32_t hi) {
  asm volatile("{ .reg .b64 da, db; mov.b64 da, {%20, %22}; mov.b64 db, {%21, %22}; "
               "wgmma.mma_async.sync.aligned.m64n40k16.f32.f16.f16 {%0,%1,%2,%3,%4,%5,%6,%7,%8,%9,%10,%11,%12,%13,%14,%15,%16,%17,%18,%19}, da, db, 1, 1, 1, 1, 1; }"
               : "+f"(d[0]), "+f"(d[1]), "+f"(d[2]), "+f"(d[3]), "+f"(d[4]), "+f"(d[5]), "+f"(d[6]), "+f"(d[7]), "+f"(d[8]), "+f"(d[9]), "+f"(d[10]), "+f"(d[11]), "+f"(d[12]), "+f"(d[13]), "+f"(d[14]), "+f"(d[15]), "+f"(d[16]), "+f"(d[17]), "+f"(d[18]), "+f"(d[19])
               : "r"(alo), "r"(blo), "r"(hi));
}
__device__ __forceinline__ void wgmma40_ss_init(float* d, uint32_t alo, uint32_t blo, uint32_t hi) {
  asm volatile("{ .reg .b64 da, db; mov.b64 da, {%20, %22}; mov.b64 db, {%21, %22}; "
               "wgmma.mma_async.sync.aligned.m64n40k16.f32.f16.f16 {%0,%1,%2,%3,%4,%5,%6,%7,%8,%9,%10,%11,%12,%13,%14,%15,%16,%17,%18,%19}, da, db, 0, 1, 1, 1, 1; }"
               : "=f"(d[0]), "=f"(d[1]), "=f"(d[2]), "=f"(d[3]), "=f"(d[4]), "=f"(d[5]), "=f"(d[6]), "=f"(d[7]), "=f"(d[8]), "=f"(d[9]), "=f"(d[10]), "=f"(d[11]), "=f"(d[12]), "=f"(d[13]), "=f"(d[14]), "=f"(d[15]), "=f"(d[16]), "=f"(d[17]), "=f"(d[18]), "=f"(d[19])
               : "r"(alo), "r"(blo), "r"(hi));
}
__device__ __forceinline__ float vzero() { float v; asm volatile("mov.b32 %0, 0;" : "=f"(v)); return v; }
__device__ __forceinline__ void tma_box(uint32_t dst, const CUtensorMap* tm, uint32_t mb, int x, int y) {
  asm volatile("cp.async.bulk.tensor.2d.shared::cluster.global.mbarrier::complete_tx::bytes [%0], [%1, {%3, %4}], [%2];"
               :: "r"(dst), "l"(tm), "r"(mb), "r"(x), "r"(y) : "memory");
}
__device__ __forceinline__ void l2_prefetch(const void* src, uint32_t bytes) {
  asm volatile("cp.async.bulk.prefetch.L2.global [%0], %1;" :: "l"(src), "r"(bytes) : "memory");
}
__device__ __forceinline__ uint32_t uni(uint32_t v) {
  uint32_t r; asm volatile("shfl.sync.idx.b32 %0, %1, 0, 0x1f, 0xffffffff;" : "=r"(r) : "r"(v)); return r;
}
__device__ __forceinline__ int fresh_tid() { int v; asm volatile("mov.u32 %0, %tid.x;" : "=r"(v)); return v; }

struct Params {
  const unsigned char* x;
  Scratch* s;
  int off[7];
  uint32_t zero;
  uint32_t* out;
  const uint32_t* dskip;
  const uint32_t* w_r;
  long long* ts;
  const unsigned char* far[7];
  uint32_t sched[2][17];
};
__device__ __forceinline__ uint32_t ldnc32(const void* p) { uint32_t v; asm volatile("ld.global.nc.b32 %0, [%1];" : "=r"(v) : "l"(p)); return v; }
__device__ __forceinline__ uint32_t ldnc16(const void* p) { uint16_t v; asm volatile("ld.global.nc.u16 %0, [%1];" : "=h"(v) : "l"(p)); return v; }
__device__ __forceinline__ uint4 ldnc128(const void* p) { uint4 v; asm volatile("ld.global.nc.v4.b32 {%0,%1,%2,%3}, [%4];" : "=r"(v.x), "=r"(v.y), "=r"(v.z), "=r"(v.w) : "l"(p)); return v; }
__device__ __forceinline__ void mbar_wait(uint32_t mb, uint32_t ph = 0) {
#pragma unroll 1
  for (int it = 0; it < SPIN_MAX; it++) {
    uint32_t ok;
    asm volatile("{ .reg .pred q; mbarrier.try_wait.parity.shared::cta.b64 q, [%1], %2; selp.u32 %0, 1, 0, q; }" : "=r"(ok) : "r"(mb), "r"(ph) : "memory");
    if (ok) break;
  }
}
__device__ __forceinline__ uint32_t mbar_test(uint32_t mb) {
  uint32_t ok;
  asm volatile("{ .reg .pred q; mbarrier.test_wait.parity.shared::cta.b64 q, [%1], 0; selp.u32 %0, 1, 0, q; }" : "=r"(ok) : "r"(mb) : "memory");
  return ok;
}
__device__ __forceinline__ void mbar_arrive(uint32_t mb) { asm volatile("mbarrier.arrive.shared::cta.b64 _, [%0];" :: "r"(mb) : "memory"); }
__device__ __forceinline__ uint32_t ldg16(const void* p) { uint16_t v; asm volatile("ld.global.u16 %0, [%1];" : "=h"(v) : "l"(p) : "memory"); return v; }
__device__ __forceinline__ uint32_t ldr16(const void* p) { uint16_t v; asm volatile("ld.relaxed.gpu.global.u16 %0, [%1];" : "=h"(v) : "l"(p) : "memory"); return v; }
__device__ __forceinline__ void fence_async() { asm volatile("fence.proxy.async.shared::cta;" ::: "memory"); }
#define SPIN_WHILE(cond, body) _Pragma("unroll 1") for (int _it = 0; _it < SPIN_MAX && __any_sync(0xffffffffu, (cond)); _it++) { body; }

struct LnC { uint32_t m2, rh2, rl2; };
__device__ __forceinline__ float diag_sum(float d0, float d1, int t) {
  float q = __shfl_sync(0xffffffffu, d0, 9 * t) + __shfl_sync(0xffffffffu, d1, 9 * t + 4);
  q += __shfl_xor_sync(0xffffffffu, q, 1);
  return q + __shfl_xor_sync(0xffffffffu, q, 2);
}
__device__ __forceinline__ LnC ln_consts(float s, float q, float& r) {
  const float mean = s * (1.f / DM);
  const float var = fmaxf(fmaf(-mean, mean, q * (1.f / DM)), 0.f);
  float sd;
  asm("sqrt.approx.ftz.f32 %0, %1;" : "=f"(sd) : "f"(bfr(bfr(var) + 1e-5f)));
  asm("rcp.approx.ftz.f32 %0, %1;" : "=f"(r) : "f"(bfr(sd)));
  LnC c;
  c.m2 = pack_bf(mean, mean);
  c.rh2 = pack_bf(r, r);
  const float rl = r - bf_lo(c.rh2);
  c.rl2 = pack_bf(rl, rl);
  return c;
}
__device__ __forceinline__ float quad_sum(float s) { s += __shfl_xor_sync(0xffffffffu, s, 1); return s + __shfl_xor_sync(0xffffffffu, s, 2); }
__device__ __forceinline__ uint32_t bf_fma2(uint32_t a, uint32_t b, uint32_t c) {
  __nv_bfloat162 r = __hfma2(*(const __nv_bfloat162*)&a, *(const __nv_bfloat162*)&b, *(const __nv_bfloat162*)&c);
  return *(uint32_t*)&r;
}
__device__ __forceinline__ uint32_t ln_apply(uint32_t w, uint32_t m2, uint32_t rh2, uint32_t rl2) {
  const uint32_t d = bf_sub2(w, m2);
  return bf_fma2(d, rh2, bf_mul2(d, rl2));
}

__device__ __forceinline__ float2 cis(float mag_log2, float rev) {
  const float m = ex2(mag_log2), ang = rev * 6.283185307179586f;
  return make_float2(m * __cosf(ang), m * __sinf(ang));
}
__device__ __forceinline__ float2 csq(float2 a) { return make_float2(fmaf(a.x, a.x, -a.y * a.y), (a.x + a.x) * a.y); }
__device__ __forceinline__ float2 cmul(float2 a, float2 b) { return make_float2(fmaf(a.x, b.x, -a.y * b.y), fmaf(a.x, b.y, a.y * b.x)); }
__device__ __forceinline__ void pmul(uint32_t xr, uint32_t xi, uint32_t w, uint32_t& yr, uint32_t& yi) {
  const __half2 XR = *(__half2*)&xr, XI = *(__half2*)&xi, W = *(__half2*)&w;
  const __half2 a = __hfma2(__hneg2(XI), __high2half2(W), __hmul2(XR, __low2half2(W)));
  const __half2 b = __hfma2(XI, __low2half2(W), __hmul2(XR, __high2half2(W)));
  yr = *(const uint32_t*)&a; yi = *(const uint32_t*)&b;
}
__device__ __forceinline__ uint32_t pk(float2 a) { return pack_h(a.x, a.y); }

struct KgState { float2 c0, z8; float kl; uint32_t w64, w128, w192; };
__device__ __forceinline__ void kgen_tables_n(const uint32_t (&raw)[7], uint32_t scr, int wt, KgState& k) {
  const uint32_t dst = scr + 16384 + wt * 16;
  const float dt = bfr(ex2(bf_lo(raw[6]) * 1.4426950408889634f));
  const float th = dt * bf_lo(raw[1]);
  const float br = dt * bf_lo(raw[2]), bi = dt * bf_lo(raw[3]);
  const float Cr = bf_lo(raw[4]), Ci = bf_lo(raw[5]);
  k.c0 = make_float2(fmaf(Cr, br, -Ci * bi), fmaf(Cr, bi, Ci * br));
  const uint32_t mx = __reduce_max_sync(0xffffffffu, __float_as_uint(fmaxf(fabsf(k.c0.x), fabsf(k.c0.y))));
  const float a2 = dt * bf_lo(raw[0]) * 1.4426950408889634f;
  const float rh = th * 0.15915494309189535f;
  const float rl = fmaf(th, (float)(0.15915494309189535 - (double)0.15915494309189535f), fmaf(th, 0.15915494309189535f, -rh));
  const float rf = rh - rintf(rh);
  const float2 z1 = cis(a2, rf + rl);
  const float p64 = rf * 64.f;
  const float2 z64 = cis(a2 * 64.f, fmaf(64.f, rl, p64 - rintf(p64)));
  const float2 z2 = csq(z1), z128 = csq(z64), z3 = cmul(z2, z1), z4 = csq(z2), z256 = csq(z128), z6 = csq(z3), z512 = csq(z256);
  k.z8 = csq(z4);
  k.w64 = pk(z64); k.w128 = pk(z128); k.w192 = pk(cmul(z128, z64));
  sts128(dst, 0x00003C00u, pk(z2), pk(z4), pk(z6));
  const float2 z1024 = csq(z512), z768 = cmul(z512, z256);
  sts128(dst + 2048, pk(z1), pk(z3), pk(cmul(z4, z1)), pk(cmul(z4, z3)));
  const float2 z2048 = csq(z1024);
  k.kl = fmaf(k.c0.x, z2048.x, -k.c0.y * z2048.y);
  sts128(dst + 4096, pk(z256), pk(cmul(z256, z2)), pk(cmul(z256, z4)), pk(cmul(z256, z6)));
  sts128(dst + 6144, pk(z512), pk(cmul(z512, z4)), pk(z768), pk(cmul(z768, z4)));
  sts128(dst + 8192, pk(z1024), pk(cmul(z1024, z256)), pk(cmul(z1024, z512)), pk(cmul(z1024, z768)));
  sts32(scr + W_MISC + (wt >> 5) * 4, mx);
}
__device__ __forceinline__ int kgen_tables_m(uint32_t scr, int wt, const KgState& k) {
  const uint32_t dst = scr + wt * 16;
  const uint4 e4 = lds128(scr + W_MISC);
  const float2 z16 = csq(k.z8), z32 = csq(z16);
  const int em = max(min((int)(max(max(e4.x, e4.y), max(e4.z, e4.w)) >> 23), 238), 16);
  const float sc = __uint_as_float((uint32_t)(127 + 4 + 127 - em) << 23);
  sts32(scr + W_MISC + 16 + (wt >> 5) * 4, __reduce_add_sync(0xffffffffu, __float2int_rn(k.kl * sc * 262144.f)));
  const float2 c0 = make_float2(k.c0.x * sc, k.c0.y * sc);
  const float2 c1 = cmul(c0, k.z8), c2 = cmul(c0, z16), c4 = cmul(c0, z32), c3 = cmul(c1, z16), c5 = cmul(c1, z32), c6 = cmul(c2, z32), c7 = cmul(c3, z32);
  uint32_t pr[4], pi[4], yr[4], yi[4];
  pr[0] = pack_h(c0.x, c1.x); pi[0] = pack_h(c0.y, c1.y);
  pr[1] = pack_h(c2.x, c3.x); pi[1] = pack_h(c2.y, c3.y);
  pr[2] = pack_h(c4.x, c5.x); pi[2] = pack_h(c4.y, c5.y);
  pr[3] = pack_h(c6.x, c7.x); pi[3] = pack_h(c6.y, c7.y);
  sts128(dst, pr[0], pr[1], pr[2], pr[3]); sts128(dst + 2048, pi[0], pi[1], pi[2], pi[3]);
#pragma unroll
  for (int q = 1; q < 4; q++) {
    const uint32_t w = q == 1 ? k.w64 : q == 2 ? k.w128 : k.w192;
#pragma unroll
    for (int i = 0; i < 4; i++) pmul(pr[i], pi[i], w, yr[i], yi[i]);
    sts128(dst + q * 4096, yr[0], yr[1], yr[2], yr[3]); sts128(dst + q * 4096 + 2048, yi[0], yi[1], yi[2], yi[3]);
  }
  return em;
}
__device__ __forceinline__ void kgen_build(uint32_t tb, int wg, int wt, uint32_t k0, uint32_t k1, uint32_t k2) {
  const uint32_t kt = tb + W_KT, sc = tb + W_L3 + 3072;
  const int ix = ((wt >> 2) + (wt & 3) * 32 - 1) & 127;
  const uint32_t a3 = tb + W_CW + 32 + ((ix & 1) ? 0 : 304) + (ix >> 1) * 4;
  const uint32_t v3 = wt ? k2 : k2 >> 16;
  sts32(sc + 4 + wt * 4, __byte_perm(k0, k1, 0x5432));
  sts16(sc + 544 + (wt & ~3) + (wt & 1) * 2 + (wt & 2) * 64, k1 >> 16);
  sts16(a3, v3); sts16(a3 + 6, v3);
  if ((unsigned)(wt - 32) < 18u) sts128(kt + (wt < 36 ? -512 : 64 + 4128 - 576) + wt * 16, 0, 0, 0, 0);
  if (wt == 127) sts32(sc, k0 & 0xFFFF0000u);
  if (wt == 0) { sts32(sc + 516, k1); sts16(sc + 800, k2); }
  bar_sync(1 + wg, 128);
  const uint32_t cw = tb + W_CW + 32 + (wt >> 6) * 48 + wt * 4;
  const uint32_t pv = lds32(sc + wt * 4), nx = lds32(sc + 8 + wt * 4), c2 = lds16(sc + 544 + wt * 2), n2 = lds16(sc + 546 + wt * 2);
  sts128(tb + W_L3 + 512 + (wt >> 6) * 512 + wt * 16, lds32(cw), lds32(cw - 8), lds32(cw - 16), lds32(cw - 24));
  const bool odd = wt & 1;
  sts64(kt + 64 + wt * 8, __byte_perm(k0, pv, 0x5410), __byte_perm(k0, 0, 0x1032));
  sts64(kt + 64 + 1024 + wt * 8, __byte_perm(k1, pv, (odd || wt == 0) ? 0x7610 : 0x1010), __byte_perm(k1, nx, odd ? 0x1076 : 0x1010));
  const uint32_t cc = c2 * 0x10001u, nc = __byte_perm(n2, c2, 0x5410), nn = n2 * 0x10001u;
  sts128(kt + 64 + 2048 + wt * 16, cc, cc, odd ? nc : cc, odd ? nn : nc);
  if (wt == 127) { sts128(kt + 64 + 4096, nn, nn, nn, nn); sts128(kt + 64 + 4112, nn, nn << 16, 0, 0); }
}

__device__ __forceinline__ void load_a(uint32_t (&a)[4], uint32_t kp, int j) {
  a[0] = lds32(kp + 64 * j); a[1] = lds32(kp + 64 * j + 512); a[2] = lds32(kp + 64 * j - 32); a[3] = lds32(kp + 64 * j + 480);
}
__device__ __forceinline__ uint32_t band(int d, int lo, int hi) {
  return ((unsigned)(d - lo) <= (unsigned)(hi - lo) ? 1u : 0u) | ((unsigned)(d - 1 - lo) <= (unsigned)(hi - lo) ? 0x10000u : 0u);
}
__device__ __forceinline__ uint32_t hadd2u(uint32_t a, uint32_t b) { __half2 r = __hadd2(*(__half2*)&a, *(__half2*)&b); return *(uint32_t*)&r; }

__device__ __forceinline__ void zero_pads(uint32_t tb, int wt) {
  if (!(wt & 32)) sts128(tb + W_L3 + (wt >> 6) * 512 + wt * 16, 0, 0, 0, 0);
  if ((wt & 63) < 3) sts128(tb + W_CW + (wt >> 6) * 304 + (wt & 63) * 16, 0, 0, 0, 0);
}
__device__ __forceinline__ uint32_t tr_base(int lane) {
  return OFF_YT + (2 * (lane >> 3) + (lane & 1)) * YT_PITCH + ((lane >> 1) & 1) * (8 * YT_PITCH + 64) + ((lane >> 2) & 1) * 16;
}

__device__ __forceinline__ uint32_t sc_addr(int tp) { return OFF_YT + (tp < 16 ? tp * YT_PITCH + (tp >> 3) * 64 + 1152 : 8 * YT_PITCH - 512 + tp * 32); }
#define X_PS 1
#define X_PW 15
#define X_HU 16
#define X_HB 0
#define X_NE 2
#define X_SCT 10000
#define X_DELTA 400
#define X_DSTEP 2000
#define X_PF0 2500
#define X_PFD 600
#define X_TD 450
#define X_WS 6
#define X_OR 8
#define X_ABS 5100
#define X_XD 0
#define X_RD 900
#define X_HD 500
#define X_PD 1150
#define X_PROMO 2
#define X_YD2 1000
#define X_GO 2
#define X_GW 2
#define X_NS 4700
#define X_XS 13600
#define X_LAG 1800
#define X_YD 1550
struct TMaps { CUtensorMap m[10]; };
__device__ __forceinline__ uint32_t h2bf(uint32_t w) { const float2 f = h2f(w); return pack_bf(f.x, f.y); }
__device__ __forceinline__ uint32_t keep(uint32_t v) { asm volatile("" : "+r"(v)); return v; }
__device__ __forceinline__ uint2 ldr64(const void* p) { uint2 v; asm volatile("{ .reg .b64 t; ld.relaxed.gpu.global.b64 t, [%2]; mov.b64 {%0, %1}, t; }" : "=r"(v.x), "=r"(v.y) : "l"(p) : "memory"); return v; }
__host__ __device__ __forceinline__ uint32_t down_box(int s, bool five) {
  return five ? OFF_W + W_BYTES + 12288 + (s / 3) * (W_BYTES - 12288) + s * 4096 : s < 6 ? OFF_W + W_BYTES + BOX + (s >> 1) * (W_BYTES - 10240) + s * 5120 : OFF_W + (s - 6) * 5120;
}
__device__ __forceinline__ void load_tile(const CUtensorMap* tmx, int i, int c, int again = 0) {
  asm volatile("mbarrier.arrive.expect_tx.shared::cta.b64 _, [%0], 8704;" :: "r"(MB_UL + i * 16 + again) : "memory");
  asm volatile("cp.async.bulk.tensor.3d.shared::cluster.global.mbarrier::complete_tx::bytes [%0], [%1, {%3, %4, %5}], [%2];"
               :: "r"(i < 2 ? OFF_T + i * TILE : OFF_W), "l"(tmx), "r"(MB_UL + i * 16 + again), "r"(0), "r"(c), "r"(-8) : "memory");
}
template <bool FAR> __device__ __forceinline__ void load_params(const Params& p, uint32_t ch, int wt, uint32_t dst, bool on) {
  const int o01 = (wt & 16) ? p.off[1] : p.off[0], o23 = (wt & 16) ? p.off[3] : p.off[2], o45 = (wt & 16) ? p.off[5] : p.off[4];
  const int o = (wt & 64) ? ((wt & 32) ? p.off[6] : o45) : ((wt & 32) ? o23 : o01);
  const unsigned char* b = FAR ? p.far[min(wt >> 4, 6)] : p.x + (long long)o * 16;
  asm volatile("{ .reg .pred q; setp.ne.u32 q, %2, 0; @q cp.async.cg.shared.global [%0], [%1], 16; }"
               :: "r"(dst + wt * 16), "l"(b + (wt < 96 ? ch * 256 + (wt & 15) * 16 : (ch >> 3) * 16)), "r"((uint32_t)(on && wt < 97)) : "memory");
}

struct ConvC { uint32_t ca, cb, bands; };
__device__ __forceinline__ ConvC conv_consts(int w, int lane) {
  const int h = w & 1, P = (w >> 1) & 1, d0 = 8 * h + (lane >> 2) - 2 * (lane & 3);
  ConvC k;
  k.ca = keep((W_KT + (16 + 256 * P + d0) * 4) | (((8 + 64 * P + lane) * 64 + (((h + ((w >> 1) & 2)) ^ (lane >> 1)) & 3) * 16) << 16));
  k.cb = keep(lane < 8 ? 0xFFFEFFFEu : ~0u);
  k.bands = keep(band(d0, 12, 20) + 2 * band(d0 + 8, 12, 20) + 4 * band(d0 + 16, 12, 20) + 8 * band(d0 + 24, 12, 20)
                 + 16 * band(d0 - 8, 5, 11) + 32 * band(d0, 5, 11) + 64 * band(d0 + 8, 5, 11) + 128 * band(d0 + 16, 5, 11));
  return k;
}
struct ConvPre { uint32_t e0, e2, f2, a[3][4]; };
__device__ __forceinline__ uint32_t lds32_if(uint32_t a, bool on) {
  uint32_t v; asm volatile("{ .reg .pred q; setp.ne.u32 q, %2, 0; mov.b32 %0, 0; @q ld.shared.b32 %0, [%1]; }" : "=r"(v) : "r"(a), "r"((uint32_t)on) : "memory"); return v;
}
__device__ __forceinline__ void conv_pre(ConvPre& r, uint32_t kp, int part, bool on, bool P) {
  if (part & 1) { r.e0 = lds32_if(kp + 4096, on && !P); r.e2 = lds32_if(kp + 4064, on && !P); r.f2 = lds32_if(kp + 4128, on && !P); }
#pragma unroll
  for (int j = 0; j < 3; j++) if (part & (j < X_PS ? 1 : 2)) {
    r.a[j][0] = lds32_if(kp + 2048 + 64 * j, on); r.a[j][1] = lds32_if(kp + 2560 + 64 * j, on); r.a[j][2] = lds32_if(kp + 2016 + 64 * j, on); r.a[j][3] = lds32_if(kp + 2528 + 64 * j, on);
  }
}
__device__ __forceinline__ void conv_item(uint32_t tb, uint32_t tl, int bid, int bn, ConvPre& pre, const ConvC& cv, uint32_t zero, const CUtensorMap* tmx, int ch, int warp, int lane, bool hold, bool more) {
  const bool go = more && warp == 0 && lane == 0;
  const uint32_t kp = tb + (cv.ca & 0xFFFFu);
  const uint32_t dlo = (tl >> 4) + 32 + ((warp >> 1) & 2) + (1u << 16), dhi = 32u | (2u << 30);
  const bool P = warp & 2;
  float a32[16], b32[16], a64[32];
  uint32_t A[40][4];
#define STEP(J) { wgmma64<0>(a64, A[J], dlo + 256 - 4 * (J), dhi); \
    if ((J) == 32) wgmma32_init<0>(b32, A[J], dlo, dhi); else wgmma32<0>(b32, A[J], ((J) < 8 ? dlo ^ zero : dlo) + 128 - 4 * (J), dhi); \
    if ((J) == 0) wgmma32_init<0>(a32, A[J], dlo, dhi); else if ((J) < 8) wgmma32<0>(a32, A[J], (dlo ^ zero) - 4 * (J), dhi); }
#define LD(J) load_a(A[J], kp, J);
#define FIRST(J) wg_fence(); STEP(J) wg_commit(); wg_wait<1>(); wg_fence();
  {
    uint32_t win[16], x9[4], x7[4], e[4], f[4];
    const uint32_t bz = keep(cv.bands);
#define BAND(i) keep((bz & (0x10001u << (i))) * (0x3C00u >> (i)))
    e[0] = pre.e0; e[2] = pre.e2; e[1] = keep(bz & 0x100u); e[3] = keep(bz & 0x200u);
    f[2] = pre.f2; f[0] = keep(bz & 0x4000u); f[1] = keep(bz & 0x8000u); f[3] = keep(bz & 0x300u);
#pragma unroll
    for (int j = 0; j < 12; j++) A[32 + j / 4][j & 3] = pre.a[j / 4][j & 3];
    const uint32_t q[12] = {BAND(0), BAND(5), keep(bz & 0x400u), BAND(4), BAND(2), BAND(7), BAND(1), BAND(6), keep(bz & 0x800u), keep(bz & 0x1000u), BAND(3), keep(bz & 0x2000u)};
#undef BAND
    const uint32_t ta = keep(tl + 512 + (warp & 3) * 2048 + lane * 64 + (lane & 6) * 8);
    if (X_GO && hold) mbar_wait(MB_GO);
    uint32_t mbl = MB_UL + (warp & 8) * 2, ph = 0;
#pragma unroll 1
    for (int it = 0; it < SPIN_MAX; it++) {
      if (ch < 512) mbar_wait(mbl, ph);
      if (it == 1) TS(13);
      TS(3);
      wg_fence();
      wgmma64h_init(win, q[0], q[1], q[2], q[3], dlo, dhi);
      wgmma64h(win, q[4], q[5], q[6], q[7], dlo - 4, dhi);
      wgmma64h(win, q[8], q[9], q[10], q[11], dlo - 8, dhi);
      wg_commit();
      wgmma64_init<0>(a64, e, dlo, dhi);
      wgmma64<0>(a64, f, dlo - 4, dhi);
      wg_commit();
      if (ch >= 512) break;
      uint32_t r0, r1, r2, r3, ok;
      if (warp & 4) {
        mbar_wait(mbl + 8);
        if (__all_sync(0xffffffffu, it || lds32(MISC_RT + (warp & 8)) == 0)) break;
        wg_wait<0>();
        continue;
      }
      ldsm4(ta, r0, r1, r2, r3);
      ok = r0 & r1 & r2 & r3;
      ldsm4(ta ^ 32, r0, r1, r2, r3);
      asm volatile("{ .reg .pred q; setp.ne.u32 q, %1, 0; barrier.red.and.pred q, %2, 128, q; selp.u32 %0, 1, 0, q; }" : "=r"(ok) : "r"((ok & r0 & r1 & r2 & r3 & 1u) | (lane & 3)), "r"(1 + (warp >> 2)) : "memory");
      if (ok) { if ((warp & 3) == 0 && lane == 0) { sts32(MISC_RT + warp, it); mbar_arrive(MB_UL + 8 + warp * 2); } break; }
      wg_wait<0>();
      if ((warp & 3) == 0 && lane == 0) load_tile(tmx - 1, warp >> 3, ch, 56);
      mbl = MB_UL + 56 + (warp & 8) * 2; ph = it & 1;
    }
    wg_wait<1>();
#pragma unroll
    for (int i = 0; i < 4; i++) {
      const int tl = 2 * ((i & 1) + ((i & 2) ? 0 : 4));
      x9[i] = P ? win[tl + 4] : win[tl]; x7[i] = P ? win[tl + 5] : win[tl + 1];
    }
    const uint32_t l3lo = ((tb + W_L3) >> 4) + (32u << 16);
    wg_fence();
    wgmma64<0>(a64, x9, l3lo, 8);
    wgmma64<0>(a64, x7, l3lo + 96, 8);
    wg_commit();
  }
  STEP(32) STEP(33) STEP(34) wg_commit(); wg_wait<1>();
  LD(35) LD(36) LD(37) LD(38)
  FIRST(35) STEP(36) STEP(37) STEP(38) wg_commit();
  LD(39) LD(0)
  TS(17);
  if (X_GO == 1 && go) mbar_arrive(MB_GO);
  FIRST(39) STEP(0) wg_commit();
  LD(1) LD(2) LD(3)
  FIRST(1) STEP(2) STEP(3) wg_commit();
  LD(4) LD(5)
  if (X_GO == 2 && go) mbar_arrive(MB_GO);
  FIRST(4) STEP(5) wg_commit();
  LD(6) LD(7)
  wg_fence(); STEP(6) STEP(7) wg_commit();
#undef STEP
#undef LD
#undef FIRST
  TS(18);
  if (X_GO == 3 && go) mbar_arrive(MB_GO);
  const uint32_t xc = tb + W_KT + (warp & 3) * 1024 + lane * 16;
  if (more) bar_sync(7, 288);
  wg_wait<1>();
  conv_pre(pre, kp + ALT, 1, more, P);
  wg_wait<0>();
  conv_pre(pre, kp + ALT, 2, more, P);
  uint32_t E[16], o[8];
#define ACC(i) ((i) < 16 ? a32[i] : (i) < 32 ? b32[(i) - 16] : a64[(i) - 32])
  E[0] = pack_h(a32[0], a32[1]);
#pragma unroll
  for (int i = 1; i < 16; i++) E[i] = pack_h(ACC(4 * i) + ACC(4 * i - 2), ACC(4 * i + 1) + ACC(4 * i - 1));
#undef ACC
#pragma unroll
  for (int j = 0; j < 8; j++) o[j] = P ? (j < 2 ? 0u : E[j - 2]) : E[8 + j];
  sts128(xc, o[0], o[1], o[2], o[3]); sts128(xc + 512, o[4], o[5], o[6], o[7]);
#pragma unroll
  for (int j = 0; j < 8; j++) o[j] = P ? E[6 + j] : E[j];
  TS(25);
  if (more) {
    sts128(xc + 4096, o[0], o[1], o[2], o[3]); sts128(xc + 4608, o[4], o[5], o[6], o[7]);
    bar_arrive(12, 192);
    return;
  }
  bar_sync(1 + (warp >> 2), 128);
  const uint4 vv[2] = {lds128(xc + (P ? -2048 : 2048)), lds128(xc + (P ? -1536 : 2560))};
#pragma unroll
  for (int q = 0; q < 2; q++) {
    const uint4 v = vv[q];
    stsm4t(tl + (cv.ca >> 16) + q * 2048, hadd2u(o[4 * q], v.x) & cv.cb, hadd2u(o[4 * q + 1], v.y) & cv.cb, hadd2u(o[4 * q + 2], v.z) & cv.cb, hadd2u(o[4 * q + 3], v.w) & cv.cb);
  }
  fence_async();
  bar_sync(bid, bn);
  if (warp == 0 && lane == 0) mbar_arrive(MB_REL);
  if ((warp & 7) == (ch < 512 ? 7 : 3) && lane == 0) {
    asm volatile("cp.async.bulk.tensor.3d.global.shared::cta.bulk_group [%0, {%3, %2, %3}], [%1];" :: "l"(tmx), "r"(tl + 512), "r"(ch), "r"(0) : "memory");
    asm volatile("cp.async.bulk.commit_group;" ::: "memory");
  }
}

template <bool FAR> __global__ void __launch_bounds__(NT, 1)
fused_kernel(const __grid_constant__ Params p, const __grid_constant__ TMaps tm) {
  extern __shared__ __align__(1024) unsigned char smem[];
  const int c = blockIdx.x;
  const bool five = (c & 1) == 0;
  const uint32_t pitch = five ? 64 : 80;
  const uint32_t ones = 0x3F803F80u;
  const int tid = threadIdx.x, lane = tid & 31;
  {
    const int w4 = tid >> 7, k5 = !five && w4 == 3;
    load_params<FAR>(p, k5 ? 512 + (c >> 1) : (w4 & 2) * 128 + 2 * c + (w4 & 1), tid & 127, OFF_W + w4 * W_BYTES + W_KT + k5 * 2048, w4 != 2 && w4 != 4);
  }
  const int warp = (int)uni(tid >> 5), wg = warp >> 2;
  TS(0);
  if (__builtin_expect(wg == 4, 0)) {
    asm volatile("setmaxnreg.dec.sync.aligned.u32 32;");
    const int role = warp;
    const int u0 = (c >> 1) * 9 + (five ? ((c & 2) ? 5 : 0) : ((c & 2) ? 0 : 4));
    const uint32_t t0 = clock() + c * 4;
    if (role == 16) {
      if (lane < 19) asm volatile("mbarrier.init.shared::cta.b64 [%0], %1;" :: "r"(OFF_MISC + lane * 8), "r"((unsigned)(lane - 2) < 4u ? 4 : 1) : "memory");
      if (lane < 2) asm volatile("mbarrier.arrive.expect_tx.shared::cta.b64 _, [%0], %1;" :: "r"(OFF_MISC + lane * 8), "r"(lane ? (five ? 36864 : 51200) : pitch * 1152) : "memory");
      fence_async();
      bar_arrive(5, 576);
      const CUtensorMap* tmb = &tm.m[five ? 3 : 0];
#pragma unroll 1
      for (int u = 0; u < 17; u++) {
        const uint32_t e = p.sched[five][u], kind = e & 3, s = (e >> 2) & 15, dst = e >> 14;
        if (kind == 3) continue;
        while ((int)(clock() - t0) < X_PF0 + (u < X_NE ? u * X_PFD : X_LAG + u * X_TD)) __nanosleep(20);
        if (e & 0x3FC0) mbar_wait(OFF_MISC + ((e >> 6) & 255));
        if (lane == 0) {
          if (kind == 2) asm volatile("cp.async.bulk.tensor.3d.shared::cluster.global.mbarrier::complete_tx::bytes [%0], [%1, {%3, %4, %5}], [%2];"
                                      :: "r"(dst), "l"(tmb + 2), "r"(MB_D), "r"(0), "r"(u0 * 8), "r"(s) : "memory");
          else tma_box(dst, tmb + kind, MB_GU, u0 * 8, s * 96);
        }
        if (u == 5) TS(2);
        if (u == 10) TS(3);
      }
      TS(4);
      TS_DUMP();
#define FINISH0 bar_sync(12, 192);        \
        _Pragma("unroll 1") for (int w = role & 2; w < (role & 2) + 2; w++) { \
          const uint32_t xa = OFF_W + W_KT + lane * 16, mk = lane < 8 ? 0xFFFEFFFEu : ~0u, ya = OFF_T + (8 + lane) * 64 + (((w & 1) ^ (lane >> 1)) & 3) * 16 + (w & 2) * 2048; \
          const uint4 a = lds128(xa + 4096 + w * 1024), b = lds128(xa + (w ^ 2) * 1024), d = lds128(xa + 4608 + w * 1024), e = lds128(xa + 512 + (w ^ 2) * 1024); \
          stsm4t(ya, hadd2u(a.x, b.x) & mk, hadd2u(a.y, b.y) & mk, hadd2u(a.z, b.z) & mk, hadd2u(a.w, b.w) & mk); \
          stsm4t(ya + 2048, hadd2u(d.x, e.x) & mk, hadd2u(d.y, e.y) & mk, hadd2u(d.z, e.z) & mk, hadd2u(d.w, e.w) & mk); \
        } \
        fence_async();
    } else if (role == 17) {
      if (smem_u32(smem) != SB) __trap();
      bar_sync(10, 576);
      if (lane == 0) {
        fence_async();
        while ((int)(clock() - t0) < X_NS - c * 4) {}
        asm volatile("cp.async.bulk.global.shared::cta.bulk_group [%0], [%1], 10240;" :: "l"(&p.s->X[c * DM * 2 + 512]), "r"(OFF_G) : "memory");
        asm volatile("cp.async.bulk.commit_group;" ::: "memory");
        asm volatile("cp.async.bulk.wait_group 0;" ::: "memory");
      }
      if (lane == 0) mbar_arrive(MB_GF);
      bar_arrive(11, 96);
      if (five) { FINISH0 bar_arrive(13, 192); }
    } else if (role == 18) {
      sts32(MISC_EPOCH, 0);
      sts32(MISC_T0, t0 - c * 4);
      bar_arrive(5, 576);
      uint4* q = lane < 2 ? &p.s->R[c * 2 + lane] : lane < 11 ? &p.s->HS[c * 9 + lane - 2] : lane == 11 ? &p.s->HS[1152 + (c & 7)] : (uint4*)&p.s->FLAG[c * 8];
      if (lane < (c < 8 ? 12 : 11)) str128(q, ~0u, ~0u, ~0u, ~0u);
      const uint32_t ep = __shfl_sync(0xffffffffu, ldr32(q), 31) + 1u;
      sts32(MISC_EPOCH, ep | 0x80000000u);
      TSX(21);
      if (lane == 31) str32(q, ep);
      bar_sync(11, 96);
      TSX(14);
      mbar_wait(MB_KF + (lane & 3) * 8);
      __syncwarp();
      { const uint2 e = lds64(MISC_EM); if (lane < 2) str128(&p.s->SC[c * 2 + lane], e.x, __byte_perm(e.y, ep, 0x6540), 0, 0); }
      TSX(17);
      while ((int)(clock() - t0) < X_SCT) __nanosleep(100);
      TSX(18);
      {
        uint2 v[4];
#pragma unroll 1
        for (int it = 0; it < SPIN_MAX; it++) {
          uint32_t bad = 0;
#pragma unroll
          for (int q = 0; q < 4; q++) v[q] = ldr64(&p.s->SC[lane * 2 + q * 64]);
#pragma unroll
          for (int q = 0; q < 4; q++) bad |= (v[q].y >> 8) ^ (ep & 0xFFFFFFu);
          if (!__any_sync(0xffffffffu, bad)) break;
        }
        TSX(25);
#pragma unroll
        for (int q = 0; q < 4; q++) {
          const uint32_t sa = (lane >> 4) * YT_PITCH + (lane & 15) * 2;
          sts16(sc_addr(2 * q) + sa, v[q].x); sts16(sc_addr(8 + 2 * q) + sa, v[q].x >> 16);
          if (lane & 1) asm volatile("st.shared.u8 [%0], %1;" :: "r"(sc_addr(16) + q * 16 + (lane >> 1)), "r"(v[q].y) : "memory");
        }
      }
      __syncwarp();
      if (lane == 0) mbar_arrive(MB_SC);
      TSX(27);
    } else {
      uint32_t w[9], d[9];
      float s = 0.f;
#pragma unroll
      for (int i = 0; i < 9; i++) { w[i] = ldnc32(p.w_r + lane + 32 * i); d[i] = ldnc32(p.dskip + lane + 32 * i); }
#pragma unroll
      for (int i = 0; i < 9; i++) { sts32(OFF_WR + lane * 4 + i * 128, w[i]); sts32(OFF_WR + 1152 + lane * 4 + i * 128, d[i]); s += bf_lo(w[i]) + bf_hi(w[i]); }
      sts32(MISC_SW, __float_as_uint(warp_sum(s)));
      TSX(23);
      bar_sync(10, 576);
      if (lane == 0) {
        const uint32_t tp = clock();
        TSX(1);
        while ((int)(clock() - tp) < X_DELTA || (int)(clock() - t0) < X_ABS - c * 4) {}
        TSX(24);
        load_tile(&tm.m[6], 0, c);
        TSX(15);
        while ((int)(clock() - t0) < X_ABS + X_DSTEP - c * 4) {}
      }
      bar_sync(11, 96);
      if (lane == 0) {
        load_tile(&tm.m[6], 1, 128 + c);
      }
      if (five) {
        mbar_wait(MB_KF);
#pragma unroll 1
        for (int it = 0; it < SPIN_MAX; it++) {
          if (lane == 0) load_tile(&tm.m[8], 2, 512 + (c >> 1));
          mbar_wait(MB_UL + 32, it & 1);
          uint32_t m = 1;
#pragma unroll
          for (int q = 0; q < 4; q++) { uint32_t r0, r1, r2, r3; ldsm4(OFF_W + 512 + lane * 64 + (lane & 6) * 8 + q * 2048, r0, r1, r2, r3); m &= r0 & r1 & r2 & r3; }
          if (__all_sync(0xffffffffu, m || (lane & 3))) break;
        }
        bar_arrive(7, 288);
        FINISH0
        bar_arrive(13, 192);
      }
      bar_sync(0, 544);
      if (lane == 0) mbar_arrive(MB_H);
    }
    return;
  }
  const int wt = tid & 127, g = lane >> 2, t = lane & 3;
  const uint32_t wb = OFF_W + wg * W_BYTES;
  const uint32_t xrow = OFF_YT + (wt >> 3) * YT_PITCH + (wt & 64) + (lane & 7) * 16;
  if (wg == 2) {
    const unsigned char* xp = p.x + (uint32_t)((c * 16 + (wt >> 3)) * 1152 + (lane & 7) * 16);
    { const uint32_t tq = clock(); while ((int)(clock() - tq) < X_XD) {} }
#pragma unroll
    for (int k = 0; k < 9; k++) asm volatile("cp.async.cg.shared.global [%0], [%1], 16;" :: "r"(xrow + k * 128), "l"(xp + k * 128) : "memory");
  }
  asm volatile("cp.async.commit_group;" ::: "memory");
  const ConvC cv = conv_consts(warp, lane);
  zero_pads(wb, wt);
  load_params<FAR>(p, 254 + 2 * c + wg, wt, wb + W_KT, wg == 2 || (wg == 3 && !five));
  asm volatile("cp.async.commit_group;" ::: "memory");
  asm volatile("setmaxnreg.inc.sync.aligned.u32 112;");
  {
    uint4 kw;
    uint4* kx = &p.s->KX[(c >> 1) * 128 + wt];
    bool two = wg == 3;
    uint32_t ep;
    int phase = wg == 2 ? 3 : 2;
#pragma unroll 1
    for (;;) {
      const bool first = two && !five;
      if (phase) asm volatile("cp.async.wait_group 1;" ::: "memory"); else asm volatile("cp.async.wait_group 0;" ::: "memory");
      if (phase == 3) {
        TS(21);
        float d[3][4], r;
        uint4 a[9];
#pragma unroll
        for (int k = 0; k < 9; k++) a[k] = lds128(xrow + k * 128);
#pragma unroll
        for (int i = 0; i < 4; i++) d[0][i] = d[1][i] = d[2][i] = 0.f;
#pragma unroll
        for (int k = 0; k < 9; k++) { mma_bf16(d[(2 * k) % 3], a[k].x, ones, a[k].y, ones, a[k].x, a[k].y); mma_bf16(d[(2 * k + 1) % 3], a[k].z, ones, a[k].w, ones, a[k].z, a[k].w); }
#pragma unroll
        for (int i = 0; i < 4; i++) d[0][i] += d[1][i] + d[2][i];
        const LnC lc = ln_consts(d[0][2] + d[0][3], __shfl_sync(0xffffffffu, d[0][0], 9 * t) + __shfl_sync(0xffffffffu, d[0][1], 9 * t + 4), r);
        if (lane < 12) sts16(MISC_LN1 + g * 32 + (warp & 3) * 8 + t * 2, lane < 4 ? lc.m2 : lane < 8 ? lc.rh2 : lc.rl2);
      } else {
        KgState ks;
        uint32_t raw[7];
        bar_sync(1 + wg, 128);
        TS(22);
#pragma unroll
        for (int i = 0; i < 7; i++) raw[i] = lds16(wb + W_KT + first * 2048 + i * 256 + (i < 6 ? wt : (first ? c >> 1 : 2 * c + (wg & 1)) & 7) * 2);
        kgen_tables_n(raw, wb, wt, ks);
        TS(20);
        bar_sync(1 + wg, 128);
        const int em = kgen_tables_m(wb, wt, ks);
        asm volatile("st.shared.u8 [%0], %1;" :: "r"(MISC_EM + wg + first), "r"(em + 9) : "memory");
        fence_async();
      }
      if (phase & 2) {
        const uint32_t tr_addr = tr_base(lane) + warp * 32;
        uint4* dst = &p.s->X[c * DM * 2 + warp * 32 + (8 * (t >> 1) + g) * 2 + (t & 1)];
        TS(23);
        bar_sync(5, 576);
        uint32_t x[3][4];
        ldsm4t(tr_addr, x[0][0], x[0][1], x[0][2], x[0][3]);
        const uint4 m = lds128(MISC_LN1 + (t & 1) * 16), rl = lds128(MISC_LN1 + 64 + (t & 1) * 16), rh = lds128(MISC_LN1 + 32 + (t & 1) * 16);
        ldsm4t(tr_addr + 512, x[1][0], x[1][1], x[1][2], x[1][3]);
        if (wg == 3) ldsm4t(tr_addr + 640, x[2][0], x[2][1], x[2][2], x[2][3]);
#pragma unroll
        for (int q = 0; q < 3; q++) {
          if (q < 2 || wg == 3) {
            const uint32_t r0 = ln_apply(x[q][0], m.x, rh.x, rl.x), r1 = ln_apply(x[q][1], m.y, rh.y, rl.y), r2 = ln_apply(x[q][2], m.z, rh.z, rl.z), r3 = ln_apply(x[q][3], m.w, rh.w, rl.w);
            const uint32_t w0 = (pack_h(bf_lo(r0), bf_hi(r0)) & 0xFFFEFFFEu) | 1u, w1 = pack_h(bf_lo(r1), bf_hi(r1)), w2 = pack_h(bf_lo(r2), bf_hi(r2)), w3 = pack_h(bf_lo(r3), bf_hi(r3));
            if (q == 0) str128(dst, w0, w1, w2, w3);
            else sts128(OFF_G + warp * 512 + (8 * (t >> 1) + g) * 32 + (t & 1) * 16 + (q == 2 ? 2048 : 0), w0, w1, w2, w3);
          }
          if (q == 0) TS(30);
        }
        bar_arrive(10, 576);
        TS(1);
      } else bar_sync(1 + wg, 128);
      phase &= 1;
      if (phase) { phase = 0; continue; }
      TS(14);
      float acc[20];
      const uint32_t alo = (wb >> 4) | (8u << 16);
      wg_fence();
      wgmma40_ss_init(acc, alo, alo + 1024, 2048 >> 4);
#pragma unroll
      for (int k = 1; k < 8; k++) wgmma40_ss(acc, alo + k * 16, alo + 1024 + k * 16, 2048 >> 4);
      wg_commit();
      const uint4 k4 = lds128(wb + W_MISC + 16);
      const float k2048 = (float)(int)(k4.x + k4.y + k4.z + k4.w) * (1.f / 262144.f);
      wg_wait<0>();
      const float un = 1.f / 8192.f;
      kw.x = pack_h((acc[0] - acc[3]) * un, (acc[4] - acc[7]) * un);
      kw.y = pack_h((acc[8] - acc[11]) * un, (acc[12] - acc[15]) * un);
      kw.z = pack_h((acc[16] - acc[19]) * un, k2048 * un);
      TS(24);
      ep = 0;
      if (two) SPIN_WHILE(ep == 0, ep = lds32(MISC_EPOCH));
      if (five || !two) break;
      str128(kx, kw.x, kw.y, kw.z, ep);
      two = false;
    }
    if (lane == 0) mbar_arrive(MB_KF + wg * 8);
    if (two) { mbar_wait(MB_KF); zero_pads(OFF_W + ALT, wt); }
    uint32_t tb = wb;
#pragma unroll 1
    for (;;) {
      kgen_build(tb, wg, wt, kw.x, kw.y, kw.z);
      TS(15);
      if (!two) break;
      two = false;
      kw.w = 0;
      SPIN_WHILE(kw.w != ep, kw = ldr128(kx));
      tb = OFF_W + ALT;
    }
    fence_async();
    TS(31);
    if (tb != wb) bar_arrive(7, 288);
    bar_sync(1 + wg, 128);
  }
  uint32_t tpub;
  ConvPre pre;
  conv_pre(pre, wb + (cv.ca & 0xFFFFu), 3, true, warp & 2);
#pragma unroll 1
  for (int item = 0;; item++) {
    TS(2);
    conv_item(item ? OFF_W + ALT : wb, item ? OFF_W : OFF_T + (wg >> 1) * TILE, item ? 1 : 13 + (wg >> 1), item ? 128 : five && wg == 1 ? 192 : 256, pre, cv, p.zero,
              &tm.m[item ? 9 : 7], item ? 512 + (c >> 1) : (wg >> 1) * 128 + c, warp, lane, five && wg >= X_GW, five && !wg && !item);
    tpub = clock() - (item ? X_YD : wg >= 2 ? X_YD2 : 0);
    if (wg || !five || item) break;
    TS(27);
  }
  TS(4);

  const int ln = lane ^ p.zero, td = warp * 32 + ln, gg = ln >> 2, tt = ln & 3;
  const int tok = c * 16 + warp;
  const int fu = warp / 3, fk = warp - fu * 3;
  uint32_t wa[12][4];
  {
    uint32_t hw[9], wr[9];
    const uint32_t row = keep(OFF_YT + warp * YT_PITCH + (warp >> 3) * 64 + ln * 16);
    const uint32_t wabase = keep(((ln & 8) ? OFF_W + (fk + 1) * W_BYTES : OFF_G + fk * 192 * pitch) + ((ln >> 4) * 8 + (ln & 7)) * pitch
                                 + (five ? ((fu ^ (ln >> 1)) & 3) : min(fu, 4)) * 16);
    float sw;
    {
      const bool three = wg == 1;
      const int ch = 8 * (tt >> 1) + gg;
      const uint32_t tr_addr = tr_base(ln);
      const uint4* ysrc = &p.s->X[c * DM * 2 + ch * 2 + (tt & 1)];
      uint32_t x[3][4], ud[3][4], s[3];
      uint4 v[3];
#define TL(q) ((q) < 2 ? 2 * warp + (q) : 28 + warp)
      asm volatile("cp.async.bulk.wait_group.read 0;" ::: "memory");
      if (wg >= 2) { const uint32_t ts = lds32(MISC_T0); while ((int)(clock() - ts) < X_XS) {} }
      while ((int)(clock() - tpub) < X_YD) {}
      TS(5);
      v[0] = ldr128(ysrc + TL(0) * 32); v[1] = ldr128(ysrc + TL(1) * 32); v[2] = make_uint4(three, 0, 0, 0);
      mbar_wait(MB_REL);
      const uint4 m = lds128(MISC_LN1 + (tt & 1) * 16), rh = lds128(MISC_LN1 + 32 + (tt & 1) * 16), rl = lds128(MISC_LN1 + 64 + (tt & 1) * 16);
#pragma unroll
      for (int i = 0; i < 6; i++) if (i < 4 || three) wr[i] = (gg & 2) ? ones : lds32(OFF_WR + TL(i >> 1) * 32 + (i & 1) * 16 + tt * 4);
      const uint32_t ha = keep(OFF_YT + (ln & 7) * YT_PITCH + (ln >> 4) * (8 * YT_PITCH + 64) + (ln & 8) * 2);
      const uint32_t pa = keep(OFF_PART + warp * 4 + ((gg & 2) * 8 + (gg & 4) * 2 + 2 * tt + (gg & 1)) * 80), pb = keep(OFF_PART + 2560 + warp * 4 + gg * 80);
      float dl[4] = {0.f, 0.f, 0.f, 0.f}, dh[4] = {0.f, 0.f, 0.f, 0.f};
      sw = __uint_as_float(lds32(MISC_SW));
#pragma unroll
      for (int q = 0; q < 3; q++) {
        if (q < 2 || three) {
          const uint32_t dk = lds16(OFF_WR + 1152 + ch * 2 + TL(q) * 32) * 0x10001u;
          ldsm4t(tr_addr + TL(q) * 32, x[q][0], x[q][1], x[q][2], x[q][3]);
          ud[q][0] = bf_mul2(ln_apply(x[q][0], m.x, rh.x, rl.x), dk); ud[q][1] = bf_mul2(ln_apply(x[q][1], m.y, rh.y, rl.y), dk);
          ud[q][2] = bf_mul2(ln_apply(x[q][2], m.z, rh.z, rl.z), dk); ud[q][3] = bf_mul2(ln_apply(x[q][3], m.w, rh.w, rl.w), dk);
        }
      }
      mbar_wait(MB_SC);
#pragma unroll
      for (int q = 0; q < 3; q++) {
        asm volatile("ld.shared.u8 %0, [%1];" : "=r"(s[q]) : "r"((q < 2 ? sc_addr(warp) + q * 16 : sc_addr(16) + (warp & 3) * 16) + ch) : "memory");
        s[q] = keep(s[q] * 0x800080u);
      }
#define FIN(q) stsm4t(tr_addr + TL(q) * 32, bf_add2(x[q][0], bf_fma2(h2bf(v[q].x), s[q], ud[q][0])), bf_add2(x[q][1], bf_fma2(h2bf(v[q].y), s[q], ud[q][1])), \
                      bf_add2(x[q][2], bf_fma2(h2bf(v[q].z), s[q], ud[q][2])), bf_add2(x[q][3], bf_fma2(h2bf(v[q].w), s[q], ud[q][3])));
      SPIN_WHILE((v[0].x | v[1].x) & 1u, _Pragma("unroll") for (int q = 0; q < 3; q++) if (v[q].x & 1u) v[q] = ldr128(ysrc + TL(q) * 32));
      if (v[2].x & 1u) v[2] = ldr128(ysrc + TL(2) * 32);
#define STAT(q) { uint32_t r0, r1, r2, r3; ldsm4(ha + TL(q) * 32, r0, r1, r2, r3); \
        mma_bf16(dl, r0, wr[2 * q], r1, wr[2 * q + 1], r0, r1); mma_bf16(dh, r2, wr[2 * q], r3, wr[2 * q + 1], r2, r3); }
      FIN(0) FIN(1)
      __syncwarp();
      STAT(0) STAT(1)
      if (three) {
        SPIN_WHILE(v[2].x & 1u, if (v[2].x & 1u) v[2] = ldr128(ysrc + TL(2) * 32));
        FIN(2)
        __syncwarp();
        STAT(2)
      }
      if (gg & 1) { dl[0] = dl[1]; dl[2] = dl[3]; dh[0] = dh[1]; dh[2] = dh[3]; }
      sts32(pa, __float_as_uint((gg & 4) ? dh[2] : dl[2]));
      if (tt == (gg >> 1)) { sts32(pb, __float_as_uint(dl[0])); sts32(pb + 640, __float_as_uint(dh[0])); }
#undef STAT
#undef FIN
#undef TL
    }
    const uint32_t ra = keep(OFF_PART + (ln & 15) * 80 + (ln & 16) * 2);
    uint16_t* rp = (uint16_t*)p.s->R + c * 16 + (ln & 15);
    asm volatile("" : "+l"(rp));
    TS(28);
    bar_sync(0, 544);
    TS(6);
    if (warp == X_PW) {
      float z[3], rd;
#pragma unroll
      for (int k = 2; k >= 0; k--) {
        const uint4 a = lds128(ra + k * 1280), b = lds128(ra + k * 1280 + 16);
        z[k] = ((__uint_as_float(a.x) + __uint_as_float(a.y)) + (__uint_as_float(a.z) + __uint_as_float(a.w))) + ((__uint_as_float(b.x) + __uint_as_float(b.y)) + (__uint_as_float(b.z) + __uint_as_float(b.w)));
      }
#pragma unroll
      for (int k = 2; k >= 0; k--) z[k] += __shfl_xor_sync(0xffffffffu, z[k], 16);
      const LnC l = ln_consts(z[1], z[2], rd);
      const uint32_t b = pack_bf(0.f, fmaf(-bf_lo(l.m2), sw, z[0]) * rd);
      const uint32_t k16 = max(min((b ^ (((int)b >> 31) | 0x80000000u)) >> 16, 0xFFFEu), 1u);
      if (ln < 16) str16(rp, k16);
      sts64(OFF_RK + (ln & 15) * 8, __byte_perm(l.m2, l.rh2, 0x5410), __byte_perm(l.rl2, k16, 0x5410));
    }
    bar_sync(5, 512);
    TS(7);
    const uint32_t tr0 = clock();
    {
      const uint4 a = lds128(row), b = lds128(row + 512);
      hw[8] = lds32(row + 1024 - ln * 12);
      hw[0] = a.x; hw[1] = a.y; hw[2] = a.z; hw[3] = a.w; hw[4] = b.x; hw[5] = b.y; hw[6] = b.z; hw[7] = b.w;
    }
    const uint2 lk = lds64(OFF_RK + warp * 8);
    LnC l2;
    l2.m2 = __byte_perm(lk.x, 0, 0x1010); l2.rh2 = __byte_perm(lk.x, 0, 0x3232); l2.rl2 = __byte_perm(lk.y, 0, 0x1010);
    const uint32_t key = (lk.y & 0xFFFF0000u) | (2047 - tok);
    uint32_t loc = ln < 16 ? (lds32(OFF_RK + 4 + ln * 8) & 0xFFFF0000u) | (2047 - c * 16 - ln) : 0u;
    int rank = __popc(__ballot_sync(0xffffffffu, loc > key));
#pragma unroll
    for (int i = 0; i < 9; i++) wr[i] = keep(ln_apply(hw[i], l2.m2, l2.rh2, l2.rl2));
    const uint2* rsrc = (const uint2*)p.s->R + td;
    uint2 rv;
    bool rbad = true;
    mbar_wait(MB_GU);
    if (warp < (five ? 12 : 15)) {
#pragma unroll
      for (int k = 0; k < X_WS; k++) ldsm4t(wabase + k * 16 * pitch, wa[k][0], wa[k][1], wa[k][2], wa[k][3]);
    }
#define OUT_ROW { uint32_t* o = p.out + tok * 288 + ln * 4; \
      *(uint4*)o = make_uint4(bf_add2(hw[0], wr[0]), bf_add2(hw[1], wr[1]), bf_add2(hw[2], wr[2]), bf_add2(hw[3], wr[3])); \
      *(uint4*)(o + 128) = make_uint4(bf_add2(hw[4], wr[4]), bf_add2(hw[5], wr[5]), bf_add2(hw[6], wr[6]), bf_add2(hw[7], wr[7])); \
      o[256 - ln * 3] = bf_add2(hw[8], wr[8]); }
    if (rank >= X_OR) OUT_ROW
#pragma unroll 1
    for (int base = 0; base < 8; base += 4) {
      uint32_t T[4];
#pragma unroll
      for (int j = 0; j < 4; j++) {
        const uint32_t mx = __reduce_max_sync(0xffffffffu, loc);
        if (loc == mx) loc = 0;
        T[j] = (td >> 2) == c ? ~0u : (td >> 2) < c ? (mx & 0xFFFF0000u) - 1u : mx | 0xFFFFu;
      }
      const uint32_t sh = keep(ln < 16 ? 0x4440u + (rank & 3) : 0x4344u), ca = keep(MISC_CNT + base * 16 + (ln & 15) * 4);
      TS(29);
      while ((int)(clock() - tr0) < X_RD) {}
      SPIN_WHILE(rbad, if (rbad) rv = ldr64(rsrc); const uint32_t m = __vmaxu2(rv.x, rv.y); rbad = max(m, m << 16) >= 0xFFFF0000u);
      TS(16);
      uint32_t cnt = 0, cn2 = 0;
#pragma unroll
      for (int j = 0; j < 4; j++)
        asm("{ .reg .pred a, b, c, d; setp.gt.u32 a, %2, %6; setp.gt.u32 b, %3, %6; setp.gt.u32 c, %4, %6; setp.gt.u32 d, %5, %6; "
            "@a add.u32 %0, %0, %7; @b add.u32 %1, %1, %7; @c add.u32 %0, %0, %7; @d add.u32 %1, %1, %7; }"
            : "+r"(cnt), "+r"(cn2) : "r"(rv.x), "r"(rv.x << 16), "r"(rv.y), "r"(rv.y << 16), "r"(T[j]), "r"(1u << (8 * j)));
      sts32(MISC_CNT + base * 16 + warp * 4, __reduce_add_sync(0xffffffffu, cnt + cn2));
      bar_sync(0, 512);
      cnt = __reduce_add_sync(0xffffffffu, __byte_perm(lds32(ca), 0, sh));
      if ((rank & ~3) == base && rank + (int)(cnt & 0xFFFFu) < 8) {
        rank += cnt & 0xFFFFu;
        uint4* hs = p.s->HS + rank * 72 + ln;
        str128(hs, wr[0], wr[1], wr[2], wr[3]); str128(hs + 32, wr[4], wr[5], wr[6], wr[7]); str32((uint32_t*)(hs + 64) - ln * 3, wr[8]);
        str128(hs + 576, hw[0], hw[1], hw[2], hw[3]); str128(hs + 608, hw[4], hw[5], hw[6], hw[7]); str32((uint32_t*)(hs + 640) - ln * 3, hw[8]);
        if (ln == 0) str32(&p.s->HS[1152 + rank], key);
        rank = 16;
      }
      if (cnt >= (4u << 16)) break;
    }
    TS(8);
    tpub = clock();
    if (rank < X_OR) OUT_ROW
    if (warp < (five ? 12 : 15)) {
#pragma unroll
      for (int k = X_WS; k < 12; k++) ldsm4t(wabase + k * 16 * pitch, wa[k][0], wa[k][1], wa[k][2], wa[k][3]);
    }
  }
  uint32_t wd[10][4];
  const uint32_t xb = keep(OFF_XS + (ln & 7) * 1168 + (fk * 24 + (ln >> 3)) * 16);
  if (warp >= 7) {
    const uint32_t db = down_box(warp - 7, five) + (ln & 7) * 128;
    mbar_wait(MB_D);
#pragma unroll
    for (int j = 0; j < 4; j++) {
      const uint32_t a = db + (ln >> 4) * 1024 + (((2 * j + ((ln >> 3) & 1)) ^ (ln & 7)) << 4);
      ldsm4t(a, wd[j][0], wd[j][1], wd[j][2], wd[j][3]);
      ldsm4t(a + 2048, wd[4 + j][0], wd[4 + j][1], wd[4 + j][2], wd[4 + j][3]);
    }
#pragma unroll
    for (int j = 0; j < 2; j++) ldsm4t(db + 4096 + (((4 * j + (ln >> 3)) ^ (ln & 7)) << 4), wd[8 + j][0], wd[8 + j][1], wd[8 + j][2], wd[8 + j][3]);
  } else if (warp < 6) {
    const int r = td / 24;
    const uint4* src = &p.s->HS[td + r * 48];
    const uint32_t xs = keep(OFF_XS + (td + r * 49) * 16);
    uint4 a[3];
    uint32_t m = ~0u;
    while ((int)(clock() - tpub) < X_HD) {}
    TS(19);
    SPIN_WHILE(m == ~0u, if (m == ~0u) { a[0] = ldr128(src); a[1] = ldr128(src + 24); a[2] = ldr128(src + 48); } m = max(max(max(a[0].x, a[1].x), max(a[2].x, a[2].y)), max(a[2].z, a[2].w)));
#pragma unroll
    for (int q = 0; q < 3; q++) sts128(xs + q * 384, a[q].x, a[q].y, a[q].z, a[q].w);
  }
  bar_sync(0, 512);
  TS(9);

  if (warp < (five ? 12 : 15)) {
    float d0[4] = {0.f, 0.f, 0.f, 0.f}, d1[4] = {0.f, 0.f, 0.f, 0.f};
#pragma unroll
    for (int k = 0; k < 12; k += 2) {
      uint32_t b0, b1, b2, b3;
      ldsm4(xb + k * 32, b0, b1, b2, b3);
      mma_bf16(d0, wa[k][0], wa[k][1], wa[k][2], wa[k][3], b0, b1);
      mma_bf16(d1, wa[k + 1][0], wa[k + 1][1], wa[k + 1][2], wa[k + 1][3], b2, b3);
    }
    sts128(OFF_RED + td * 16, __float_as_uint(d0[0] + d1[0]), __float_as_uint(d0[1] + d1[1]), __float_as_uint(d0[2] + d1[2]), __float_as_uint(d0[3] + d1[3]));
  }
  TS(26);
  if (warp < 5) {
    const uint32_t rb = OFF_RED + warp * 1536 + ln * 16;
    bar_sync(9, 512);
    const uint4 pa = lds128(rb), pb = lds128(rb + 512), pc = lds128(rb + 1024);
    const float ga = bfr(__uint_as_float(pa.x) + __uint_as_float(pb.x) + __uint_as_float(pc.x));
    const float gb = bfr(__uint_as_float(pa.y) + __uint_as_float(pb.y) + __uint_as_float(pc.y));
    const uint32_t uu = pack_bf(__uint_as_float(pa.z) + __uint_as_float(pb.z) + __uint_as_float(pc.z), __uint_as_float(pa.w) + __uint_as_float(pb.w) + __uint_as_float(pc.w));
    float ra, rb2;
    asm("rcp.approx.ftz.f32 %0, %1;" : "=f"(ra) : "f"(1.f + ex2(ga * -1.4426950408889634f)));
    asm("rcp.approx.ftz.f32 %0, %1;" : "=f"(rb2) : "f"(1.f + ex2(gb * -1.4426950408889634f)));
    const uint32_t act = bf_mul2(pack_bf(ga * ra, gb * rb2), uu);
    sts32(OFF_ACT + td * 4, act);
  } else bar_arrive(9, 512);
  uint4* dst = &p.s->X[c * DM * 2 + (warp - 7) * 64 + tt * 8 + gg];
  asm volatile("" : "+l"(dst));
  bar_sync(8, 512);
  tpub = clock();
  if (warp >= 7) {
    uint32_t b0, b1, b2, b3, b4;
    ldsm4t(OFF_ACT + ln * 16, b0, b1, b2, b3);
    asm volatile("ldmatrix.sync.aligned.m8n8.x1.trans.shared.b16 {%0}, [%1];" : "=r"(b4) : "r"(OFF_ACT + 512 + ln * 16) : "memory");
    float y[4][4];
#pragma unroll
    for (int j = 0; j < 4; j++) {
      y[j][0] = y[j][1] = y[j][2] = y[j][3] = 0.f;
      mma_bf16(y[j], wd[j][0], wd[j][1], wd[j][2], wd[j][3], b0, b1);
    }
#pragma unroll
    for (int j = 0; j < 4; j++) mma_bf16(y[j], wd[4 + j][0], wd[4 + j][1], wd[4 + j][2], wd[4 + j][3], b2, b3);
    if (!five) {
#pragma unroll
      for (int j = 0; j < 4; j++) mma_bf16_k8(y[j], wd[8 + (j >> 1)][2 * (j & 1)], wd[8 + (j >> 1)][2 * (j & 1) + 1], b4);
    }
    str128(dst, (pack_bf(y[0][0], y[0][1]) & ~1u) | 0x10000u, pack_bf(y[0][2], y[0][3]), pack_bf(y[1][0], y[1][1]), pack_bf(y[1][2], y[1][3]));
    str128(dst + 32, (pack_bf(y[2][0], y[2][1]) & ~1u) | 0x10000u, pack_bf(y[2][2], y[2][3]), pack_bf(y[3][0], y[3][1]), pack_bf(y[3][2], y[3][3]));
  }
  TS(10);

  if (c < 72) {
    const uint4* src = &p.s->X[(warp * 4 + tt) * (DM * 2) + c * 8 + gg];
    const int slot = (c & 3) * 2 + (ln >> 4), dw = (c >> 2) * 16 + (ln & 15);
    uint32_t hv = 0, kv = 0, res = 0, rs2 = 0;
    uint32_t* o = p.out;
    if (warp == 0) {
      hv = ~0u;
      SPIN_WHILE(max(hv, kv) == ~0u, hv = ldr32((const uint32_t*)p.s->HS + 2304 + slot * 288 + dw); kv = ldr32(&p.s->HS[1152 + slot]));
      const float r = bf_hi(kv ^ (((int)~kv >> 31) | 0x80000000u));
      float rs;
      asm("rcp.approx.ftz.f32 %0, %1;" : "=f"(rs) : "f"(1.f + ex2(r * -1.4426950408889634f)));
      rs2 = keep(pack_bf(rs, rs));
      res = lds32(OFF_XS + slot * 1168 + dw * 4);
      o += (2047 - (int)(kv & 2047u)) * 288 + dw;
      asm volatile("" : "+l"(o));
    }
    const uint32_t sel = (gg & 1) ? 0x3F800000u : 0x00003F80u;
    const uint32_t q0 = keep((gg >> 1) == 0 ? sel : 0u), q1 = keep((gg >> 1) == 1 ? sel : 0u), q2 = keep((gg >> 1) == 2 ? sel : 0u), q3 = keep((gg >> 1) == 3 ? sel : 0u);
    const uint32_t fa = keep(OFF_FIN + warp * 256 + (gg & 1) * 128 + (gg >> 1) * 32 + tt * 8), fb = keep(OFF_FIN + ln * 8);
    uint4 a0 = make_uint4(0, 0, 0, 0), a1 = a0;
    while ((int)(clock() - tpub) < X_PD) {}
    SPIN_WHILE(!(a0.x & a1.x & 0x10000u), if (!(a0.x & 0x10000u)) a0 = ldr128(src); if (!(a1.x & 0x10000u)) a1 = ldr128(src + 64 * DM * 2));
    float d[4] = {0.f, 0.f, 0.f, 0.f}, e[4] = {0.f, 0.f, 0.f, 0.f};
    mma_bf16(d, q0, q2, q1, q3, a0.x, a0.y); mma_bf16(e, q0, q2, q1, q3, a0.z, a0.w);
    mma_bf16(d, q0, q2, q1, q3, a1.x, a1.y); mma_bf16(e, q0, q2, q1, q3, a1.z, a1.w);
    sts64(fa, __float_as_uint(d[0] + e[2]), __float_as_uint(d[1] + e[3]));
    TS(11);
    if (warp == 0) {
      bar_sync(0, 512);
      float2 s[16];
#pragma unroll
      for (int i = 0; i < 16; i++) { const uint2 q = lds64(fb + i * 256); s[i] = make_float2(__uint_as_float(q.x), __uint_as_float(q.y)); }
#pragma unroll
      for (int k = 1; k < 16; k *= 2)
#pragma unroll
        for (int i = 0; i < 16; i += 2 * k) { s[i].x += s[i + k].x; s[i].y += s[i + k].y; }
      *o = bf_add2(hv, bf_add2(res, bf_mul2(pack_bf(s[0].x, s[0].y), rs2)));
    } else bar_arrive(0, 512);
  }
  TS(12);
  TS_DUMP();
}

typedef CUresult (*EncodeFn)(CUtensorMap*, CUtensorMapDataType, cuuint32_t, void*, const cuuint64_t*, const cuuint64_t*, const cuuint32_t*,
                             const cuuint32_t*, CUtensorMapInterleave, CUtensorMapSwizzle, CUtensorMapL2promotion, CUtensorMapFloatOOBfill);

}

extern "C" void kernel_launch(void* const* d_in, const int* in_sizes, int n_in, void* d_out, int out_size) {
  (void)in_sizes; (void)n_in; (void)out_size;
  static EncodeFn enc = nullptr;
  static Scratch* scratch = nullptr;
  if (!enc) {
    void* fn = nullptr;
    cudaDriverEntryPointQueryResult qr;
    cudaGetDriverEntryPoint("cuTensorMapEncodeTiled", &fn, cudaEnableDefault, &qr);
    enc = (EncodeFn)fn;
    cudaGetSymbolAddress((void**)&scratch, g_S);
    cudaFuncSetAttribute(fused_kernel<false>, cudaFuncAttributeMaxDynamicSharedMemorySize, SMEM_BYTES);
    cudaFuncSetAttribute(fused_kernel<true>, cudaFuncAttributeMaxDynamicSharedMemorySize, SMEM_BYTES);
  }
  TMaps tm;
  for (int i = 0; i < 6; i++) {
    const bool dn = i % 3 == 2;
    const cuuint32_t w = i < 3 ? 40 : 32;
    cuuint64_t gd[3] = {(cuuint64_t)(dn ? 64 : FF), (cuuint64_t)(dn ? FF : DM), 9};
    cuuint64_t gs[2] = {(cuuint64_t)(dn ? DM * 2 : FF * 2), 128};
    cuuint32_t bx[3] = {dn ? 64 : w, dn ? w : 96, i < 3 ? 2u : 3u};
    cuuint32_t es[3] = {1, 1, 1};
    enc(&tm.m[i], CU_TENSOR_MAP_DATA_TYPE_BFLOAT16, dn ? 3 : 2, d_in[11 + i % 3], gd, gs, bx, es, CU_TENSOR_MAP_INTERLEAVE_NONE,
        dn ? CU_TENSOR_MAP_SWIZZLE_128B : i < 3 ? CU_TENSOR_MAP_SWIZZLE_NONE : CU_TENSOR_MAP_SWIZZLE_64B,
        (CUtensorMapL2promotion)X_PROMO, CU_TENSOR_MAP_FLOAT_OOB_FILL_NONE);
  }
  for (int i = 6; i < 10; i++) {
    cuuint64_t gd[3] = {i < 8 ? 32u : 16u, i < 8 ? DM / 2u : DM, NCTA};
    cuuint64_t gs[2] = {i < 8 ? 64u : 32u, DM * 32};
    cuuint32_t bx[3] = {32, 1, (i & 1) ? 128u : 136u};
    cuuint32_t es[3] = {1, 1, 1};
    enc(&tm.m[i], CU_TENSOR_MAP_DATA_TYPE_FLOAT16, 3, scratch->X, gd, gs, bx, es, CU_TENSOR_MAP_INTERLEAVE_NONE, CU_TENSOR_MAP_SWIZZLE_64B,
        CU_TENSOR_MAP_L2_PROMOTION_NONE, CU_TENSOR_MAP_FLOAT_OOB_FILL_NONE);
  }
  Params p;
  p.x = (const unsigned char*)d_in[0];
  bool far = false;
  for (int i = 0; i < 7; i++) {
    p.far[i] = (const unsigned char*)d_in[1 + i];
    const long long d = (long long)((intptr_t)d_in[1 + i] - (intptr_t)d_in[0]);
    p.off[i] = (int)(d / 16);
    if ((long long)p.off[i] * 16 != d) far = true;
  }
  p.dskip = (const uint32_t*)d_in[8];
  p.w_r = (const uint32_t*)d_in[10];
  for (int f = 0; f < 2; f++) {
    static const int kind[17] = {0, 0, 0, 0, 2, 2, 0, 0, 1, 1, 1, 1, 1, 1, 2, 2, 2};
    static const int idx[2][17] = {{2, 3, 4, 5, 6, 8, 0, 1, 0, 1, 2, 3, 4, 5, 0, 2, 4}, {2, 3, 4, 5, 0, -1, 0, 1, 0, 1, 2, 3, 4, 5, 3, -1, 6}};
    static const int blk[2][17] = {{-1, -1, -1, -1, 0, -1, 4, -1, 1, -1, 2, -1, 3, -1, 16, -1, -1}, {-1, -1, -1, -1, 1, -1, 4, -1, -1, -1, 2, -1, 3, -1, 16, -1, -1}};
    const int pitch = f ? 64 : 80;
    for (int u = 0; u < 17; u++) {
      const int s = idx[f][u];
      const uint32_t dst = kind[u] == 0 ? OFF_G + s * 96 * pitch : kind[u] == 2 ? down_box(s, f) : OFF_W + W_BYTES + (s >> 1) * W_BYTES + (s & 1) * 96 * pitch;
      const uint32_t mb = u >= 14 ? (u >= X_HU ? MB_H - OFF_MISC : X_HB) : blk[f][u] >= 0 ? MB_KF - OFF_MISC + blk[f][u] * 8 : 0;
      p.sched[f][u] = s < 0 ? 3u : kind[u] | s << 2 | mb << 6 | dst << 14;
    }
  }
  p.out = (uint32_t*)d_out;
  p.zero = 0;
  p.ts = nullptr;
  p.s = scratch;
  if (far) { fused_kernel<true><<<NCTA, NT, SMEM_BYTES, cudaStreamPerThread>>>(p, tm); return; }
  fused_kernel<false><<<NCTA, NT, SMEM_BYTES, cudaStreamPerThread>>>(p, tm);
}
```

```cpp
#include <cuda_runtime.h>
#include <cuda.h>
#include <cuda_bf16.h>
#include <cuda_fp16.h>
#include <stdint.h>
#include <stddef.h>

namespace {

constexpr int NCTA = 128;
constexpr int NT = 640;
constexpr int DM = 576;
constexpr int FF = 4608;
constexpr int SPIN_MAX = 1 << 20;

struct Scratch {
  uint4 X[NCTA * DM * 2];
  uint4 KX[64 * 128];
  uint4 HS[1152 + 8];
  uint4 R[256];
  uint4 SC[256];
  uint32_t FLAG[NCTA * 8];
};
__device__ Scratch g_S;

#define CLKS(i)
#define TS(i)
#define TSX(i)
#define TS_DUMP()

constexpr int SB = 1024;
constexpr int BOX = 15360;
constexpr int OFF_G = SB;
constexpr int OFF_W = OFF_G + 3 * BOX;
constexpr int W_KT = 26624;
constexpr int W_L3 = W_KT + 4416;
constexpr int W_CW = W_L3 + 4096;
constexpr int W_MISC = W_CW + 640;
constexpr int W_BYTES = 35840;
constexpr int TILE = 10240;
constexpr int OFF_T = OFF_W + 4 * W_BYTES;
constexpr int ALT = TILE - W_KT;
static_assert(W_MISC + 32 <= W_BYTES && OFF_W % 1024 == 0 && W_BYTES % 1024 == 0 && W_BYTES + ALT <= 20480, "wg block");
constexpr int YT_PITCH = 1184;
constexpr int OFF_YT = OFF_T + 2 * TILE;
constexpr int OFF_WR = OFF_YT + 16 * YT_PITCH + 64;
constexpr int OFF_MISC = OFF_WR + 2304;
constexpr int SMEM_BYTES = OFF_MISC + 1024 - SB;
static_assert(OFF_YT % 16 == 0 && OFF_MISC % 16 == 0, "align");
static_assert(SMEM_BYTES <= 232448, "smem");
constexpr int MB_GU = OFF_MISC;
constexpr int MB_D = OFF_MISC + 8;
constexpr int MB_KF = OFF_MISC + 16;
constexpr int MB_GF = OFF_MISC + 48;
constexpr int MB_SC = OFF_MISC + 56;
constexpr int MB_UL = OFF_MISC + 64;
constexpr int MB_REL = OFF_MISC + 104;
constexpr int MB_GO = OFF_MISC + 112;
constexpr int MB_H = MB_KF + 128;
constexpr int MISC_EPOCH = OFF_MISC + 152;
constexpr int MISC_SW = OFF_MISC + 156;
constexpr int MISC_RT = OFF_MISC + 160;
constexpr int MISC_T0 = OFF_MISC + 296;
constexpr int MISC_EM = OFF_MISC + 288;
constexpr int OFF_PART = OFF_W + 20480;
constexpr int OFF_RK = OFF_PART + 3840;
constexpr int MISC_LN1 = OFF_MISC + 192;
constexpr int OFF_XS = OFF_T;
constexpr int OFF_RED = OFF_T + TILE;
constexpr int OFF_FIN = OFF_W + 3 * W_BYTES + W_KT;
constexpr int OFF_ACT = OFF_FIN + 4096;
constexpr int MISC_CNT = OFF_ACT + 1024;

__device__ __forceinline__ uint32_t smem_u32(const void* p) { return (uint32_t)__cvta_generic_to_shared(p); }
__device__ __forceinline__ uint32_t lds32(uint32_t a) { uint32_t v; asm volatile("ld.shared.b32 %0, [%1];" : "=r"(v) : "r"(a) : "memory"); return v; }
__device__ __forceinline__ uint32_t lds16(uint32_t a) { uint16_t v; asm volatile("ld.shared.u16 %0, [%1];" : "=h"(v) : "r"(a) : "memory"); return v; }
__device__ __forceinline__ uint2 lds64(uint32_t a) { uint2 v; asm volatile("ld.shared.v2.b32 {%0,%1}, [%2];" : "=r"(v.x), "=r"(v.y) : "r"(a) : "memory"); return v; }
__device__ __forceinline__ uint4 lds128(uint32_t a) { uint4 v; asm volatile("ld.shared.v4.b32 {%0,%1,%2,%3}, [%4];" : "=r"(v.x), "=r"(v.y), "=r"(v.z), "=r"(v.w) : "r"(a) : "memory"); return v; }
__device__ __forceinline__ void sts16(uint32_t a, uint32_t v) { asm volatile("st.shared.u16 [%0], %1;" :: "r"(a), "h"((uint16_t)v) : "memory"); }
__device__ __forceinline__ void sts32(uint32_t a, uint32_t v) { asm volatile("st.shared.b32 [%0], %1;" :: "r"(a), "r"(v) : "memory"); }
__device__ __forceinline__ void sts64(uint32_t a, uint32_t x, uint32_t y) { asm volatile("st.shared.v2.b32 [%0], {%1,%2};" :: "r"(a), "r"(x), "r"(y) : "memory"); }
__device__ __forceinline__ void sts128(uint32_t a, uint32_t x, uint32_t y, uint32_t z, uint32_t w) { asm volatile("st.shared.v4.b32 [%0], {%1,%2,%3,%4};" :: "r"(a), "r"(x), "r"(y), "r"(z), "r"(w) : "memory"); }
__device__ __forceinline__ void ldsm4(uint32_t a, uint32_t& r0, uint32_t& r1, uint32_t& r2, uint32_t& r3) {
  asm volatile("ldmatrix.sync.aligned.m8n8.x4.shared.b16 {%0,%1,%2,%3}, [%4];" : "=r"(r0), "=r"(r1), "=r"(r2), "=r"(r3) : "r"(a) : "memory");
}
__device__ __forceinline__ void ldsm2(uint32_t a, uint32_t& r0, uint32_t& r1) {
  asm volatile("ldmatrix.sync.aligned.m8n8.x2.shared.b16 {%0,%1}, [%2];" : "=r"(r0), "=r"(r1) : "r"(a) : "memory");
}
__device__ __forceinline__ void ldsm4t(uint32_t a, uint32_t& r0, uint32_t& r1, uint32_t& r2, uint32_t& r3) {
  asm volatile("ldmatrix.sync.aligned.m8n8.x4.trans.shared.b16 {%0,%1,%2,%3}, [%4];" : "=r"(r0), "=r"(r1), "=r"(r2), "=r"(r3) : "r"(a) : "memory");
}
__device__ __forceinline__ void stsm4t(uint32_t a, uint32_t r0, uint32_t r1, uint32_t r2, uint32_t r3) {
  asm volatile("stmatrix.sync.aligned.m8n8.x4.trans.shared.b16 [%0], {%1,%2,%3,%4};" :: "r"(a), "r"(r0), "r"(r1), "r"(r2), "r"(r3) : "memory");
}
__device__ __forceinline__ uint4 ldr128(const void* p) {
  unsigned long long lo, hi;
  asm volatile("{ .reg .b128 t; ld.relaxed.gpu.global.b128 t, [%2]; mov.b128 {%0, %1}, t; }" : "=l"(lo), "=l"(hi) : "l"(p) : "memory");
  return make_uint4((uint32_t)lo, (uint32_t)(lo >> 32), (uint32_t)hi, (uint32_t)(hi >> 32));
}
__device__ __forceinline__ void str128(void* p, uint32_t x, uint32_t y, uint32_t z, uint32_t w) {
  asm volatile("{ .reg .b128 t; .reg .b64 lo, hi; mov.b64 lo, {%1,%2}; mov.b64 hi, {%3,%4}; mov.b128 t, {lo, hi}; st.relaxed.gpu.global.b128 [%0], t; }"
               :: "l"(p), "r"(x), "r"(y), "r"(z), "r"(w) : "memory");
}
__device__ __forceinline__ void str64(void* p, uint32_t x, uint32_t y) {
  asm volatile("{ .reg .b64 t; mov.b64 t, {%1,%2}; st.relaxed.gpu.global.b64 [%0], t; }" :: "l"(p), "r"(x), "r"(y) : "memory");
}
__device__ __forceinline__ uint32_t ldr32(const void* p) { uint32_t v; asm volatile("ld.relaxed.gpu.global.b32 %0, [%1];" : "=r"(v) : "l"(p) : "memory"); return v; }
__device__ __forceinline__ void str32(void* p, uint32_t v) { asm volatile("st.relaxed.gpu.global.b32 [%0], %1;" :: "l"(p), "r"(v) : "memory"); }
__device__ __forceinline__ void str16(void* p, uint32_t v) { asm volatile("st.relaxed.gpu.global.u16 [%0], %1;" :: "l"(p), "h"((uint16_t)v) : "memory"); }
__device__ __forceinline__ void fence_gpu() { asm volatile("fence.acq_rel.gpu;" ::: "memory"); }
__device__ __forceinline__ void bar_sync(int id, int n) { asm volatile("bar.sync %0, %1;" :: "r"(id), "r"(n) : "memory"); }
__device__ __forceinline__ void bar_arrive(int id, int n) { asm volatile("bar.arrive %0, %1;" :: "r"(id), "r"(n) : "memory"); }

__device__ __forceinline__ float bf_lo(uint32_t w) { return __uint_as_float(w << 16); }
__device__ __forceinline__ float bf_hi(uint32_t w) { return __uint_as_float(w & 0xFFFF0000u); }
__device__ __forceinline__ uint32_t pack_bf(float lo, float hi) { uint32_t r; asm("cvt.rn.bf16x2.f32 %0, %1, %2;" : "=r"(r) : "f"(hi), "f"(lo)); return r; }
__device__ __forceinline__ uint32_t pack_h(float lo, float hi) { uint32_t r; asm("cvt.rn.f16x2.f32 %0, %1, %2;" : "=r"(r) : "f"(hi), "f"(lo)); return r; }
__device__ __forceinline__ uint32_t pack_hv(float lo, float hi) { uint32_t r; asm volatile("cvt.rn.f16x2.f32 %0, %1, %2;" : "=r"(r) : "f"(hi), "f"(lo) : "memory"); return r; }
__device__ __forceinline__ float bfr(float x) { return bf_lo(pack_bf(x, 0.f)); }
__device__ __forceinline__ uint32_t bf_sub2(uint32_t a, uint32_t b) { __nv_bfloat162 r = __hsub2(*(__nv_bfloat162*)&a, *(__nv_bfloat162*)&b); return *(uint32_t*)&r; }
__device__ __forceinline__ uint32_t bf_add2(uint32_t a, uint32_t b) { __nv_bfloat162 r = __hadd2(*(__nv_bfloat162*)&a, *(__nv_bfloat162*)&b); return *(uint32_t*)&r; }
__device__ __forceinline__ uint32_t bf_mul2(uint32_t a, uint32_t b) { __nv_bfloat162 r = __hmul2(*(__nv_bfloat162*)&a, *(__nv_bfloat162*)&b); return *(uint32_t*)&r; }
__device__ __forceinline__ float2 h2f(uint32_t w) { return __half22float2(*(__half2*)&w); }
__device__ __forceinline__ float ex2(float x) { float r; asm("ex2.approx.ftz.f32 %0, %1;" : "=f"(r) : "f"(x)); return r; }
__device__ __forceinline__ float warp_sum(float v) {
#pragma unroll
  for (int o = 16; o > 0; o >>= 1) v += __shfl_xor_sync(0xffffffffu, v, o);
  return v;
}
__device__ __forceinline__ void mma_f16_f32(float* d, uint32_t a0, uint32_t a1, uint32_t a2, uint32_t a3, uint32_t b0, uint32_t b1) {
  asm volatile("mma.sync.aligned.m16n8k16.row.col.f32.f16.f16.f32 {%0,%1,%2,%3}, {%4,%5,%6,%7}, {%8,%9}, {%0,%1,%2,%3};"
               : "+f"(d[0]), "+f"(d[1]), "+f"(d[2]), "+f"(d[3]) : "r"(a0), "r"(a1), "r"(a2), "r"(a3), "r"(b0), "r"(b1));
}
__device__ __forceinline__ void mma_f16_f16(uint32_t& d0, uint32_t& d1, uint32_t a0, uint32_t a1, uint32_t a2, uint32_t a3, uint32_t b0, uint32_t b1) {
  asm volatile("mma.sync.aligned.m16n8k16.row.col.f16.f16.f16.f16 {%0,%1}, {%2,%3,%4,%5}, {%6,%7}, {%0,%1};"
               : "+r"(d0), "+r"(d1) : "r"(a0), "r"(a1), "r"(a2), "r"(a3), "r"(b0), "r"(b1));
}
__device__ __forceinline__ void mma_bf16(float* d, uint32_t a0, uint32_t a1, uint32_t a2, uint32_t a3, uint32_t b0, uint32_t b1) {
  asm volatile("mma.sync.aligned.m16n8k16.row.col.f32.bf16.bf16.f32 {%0,%1,%2,%3}, {%4,%5,%6,%7}, {%8,%9}, {%0,%1,%2,%3};"
               : "+f"(d[0]), "+f"(d[1]), "+f"(d[2]), "+f"(d[3]) : "r"(a0), "r"(a1), "r"(a2), "r"(a3), "r"(b0), "r"(b1));
}
__device__ __forceinline__ void mma_bf16_k8(float* d, uint32_t a0, uint32_t a1, uint32_t b0) {
  asm volatile("mma.sync.aligned.m16n8k8.row.col.f32.bf16.bf16.f32 {%0,%1,%2,%3}, {%4,%5}, {%6}, {%0,%1,%2,%3};"
               : "+f"(d[0]), "+f"(d[1]), "+f"(d[2]), "+f"(d[3]) : "r"(a0), "r"(a1), "r"(b0));
}

__device__ __forceinline__ void wg_fence() { asm volatile("wgmma.fence.sync.aligned;" ::: "memory"); }
__device__ __forceinline__ void wg_commit() { asm volatile("wgmma.commit_group.sync.aligned;" ::: "memory"); }
template <int N> __device__ __forceinline__ void wg_wait() { asm volatile("wgmma.wait_group.sync.aligned %0;" :: "n"(N) : "memory"); }
template <int TB> __device__ __forceinline__ void wgmma32(float* d, const uint32_t* a, uint32_t dlo, uint32_t dhi) {
  asm volatile("{ .reg .b64 dd; mov.b64 dd, {%20, %21}; wgmma.mma_async.sync.aligned.m64n32k16.f32.f16.f16 "
               "{%0,%1,%2,%3,%4,%5,%6,%7,%8,%9,%10,%11,%12,%13,%14,%15}, {%16,%17,%18,%19}, dd, 1, 1, 1, %22; }"
               : "+f"(d[0]), "+f"(d[1]), "+f"(d[2]), "+f"(d[3]), "+f"(d[4]), "+f"(d[5]), "+f"(d[6]), "+f"(d[7]), "+f"(d[8]), "+f"(d[9]), "+f"(d[10]), "+f"(d[11]), "+f"(d[12]), "+f"(d[13]), "+f"(d[14]), "+f"(d[15])
               : "r"(a[0]), "r"(a[1]), "r"(a[2]), "r"(a[3]), "r"(dlo), "r"(dhi), "n"(TB));
}
template <int TB> __device__ __forceinline__ void wgmma64(float* d, const uint32_t* a, uint32_t dlo, uint32_t dhi) {
  asm volatile("{ .reg .b64 dd; mov.b64 dd, {%36, %37}; wgmma.mma_async.sync.aligned.m64n64k16.f32.f16.f16 "
               "{%0,%1,%2,%3,%4,%5,%6,%7,%8,%9,%10,%11,%12,%13,%14,%15,%16,%17,%18,%19,%20,%21,%22,%23,%24,%25,%26,%27,%28,%29,%30,%31}, {%32,%33,%34,%35}, dd, 1, 1, 1, %38; }"
               : "+f"(d[0]), "+f"(d[1]), "+f"(d[2]), "+f"(d[3]), "+f"(d[4]), "+f"(d[5]), "+f"(d[6]), "+f"(d[7]), "+f"(d[8]), "+f"(d[9]), "+f"(d[10]), "+f"(d[11]), "+f"(d[12]), "+f"(d[13]), "+f"(d[14]), "+f"(d[15]), "+f"(d[16]), "+f"(d[17]), "+f"(d[18]), "+f"(d[19]), "+f"(d[20]), "+f"(d[21]), "+f"(d[22]), "+f"(d[23]), "+f"(d[24]), "+f"(d[25]), "+f"(d[26]), "+f"(d[27]), "+f"(d[28]), "+f"(d[29]), "+f"(d[30]), "+f"(d[31])
               : "r"(a[0]), "r"(a[1]), "r"(a[2]), "r"(a[3]), "r"(dlo), "r"(dhi), "n"(TB));
}
template <int TB> __device__ __forceinline__ void wgmma64_init(float* d, const uint32_t* a, uint32_t dlo, uint32_t dhi) {
  asm volatile("{ .reg .b64 dd; mov.b64 dd, {%36, %37}; wgmma.mma_async.sync.aligned.m64n64k16.f32.f16.f16 "
               "{%0,%1,%2,%3,%4,%5,%6,%7,%8,%9,%10,%11,%12,%13,%14,%15,%16,%17,%18,%19,%20,%21,%22,%23,%24,%25,%26,%27,%28,%29,%30,%31}, {%32,%33,%34,%35}, dd, 0, 1, 1, %38; }"
               : "=f"(d[0]), "=f"(d[1]), "=f"(d[2]), "=f"(d[3]), "=f"(d[4]), "=f"(d[5]), "=f"(d[6]), "=f"(d[7]), "=f"(d[8]), "=f"(d[9]), "=f"(d[10]), "=f"(d[11]), "=f"(d[12]), "=f"(d[13]), "=f"(d[14]), "=f"(d[15]), "=f"(d[16]), "=f"(d[17]), "=f"(d[18]), "=f"(d[19]), "=f"(d[20]), "=f"(d[21]), "=f"(d[22]), "=f"(d[23]), "=f"(d[24]), "=f"(d[25]), "=f"(d[26]), "=f"(d[27]), "=f"(d[28]), "=f"(d[29]), "=f"(d[30]), "=f"(d[31])
               : "r"(a[0]), "r"(a[1]), "r"(a[2]), "r"(a[3]), "r"(dlo), "r"(dhi), "n"(TB));
}
template <int TB> __device__ __forceinline__ void wgmma32_init(float* d, const uint32_t* a, uint32_t dlo, uint32_t dhi) {
  asm volatile("{ .reg .b64 dd; mov.b64 dd, {%20, %21}; wgmma.mma_async.sync.aligned.m64n32k16.f32.f16.f16 "
               "{%0,%1,%2,%3,%4,%5,%6,%7,%8,%9,%10,%11,%12,%13,%14,%15}, {%16,%17,%18,%19}, dd, 0, 1, 1, %22; }"
               : "=f"(d[0]), "=f"(d[1]), "=f"(d[2]), "=f"(d[3]), "=f"(d[4]), "=f"(d[5]), "=f"(d[6]), "=f"(d[7]), "=f"(d[8]), "=f"(d[9]), "=f"(d[10]), "=f"(d[11]), "=f"(d[12]), "=f"(d[13]), "=f"(d[14]), "=f"(d[15])
               : "r"(a[0]), "r"(a[1]), "r"(a[2]), "r"(a[3]), "r"(dlo), "r"(dhi), "n"(TB));
}
__device__ __forceinline__ void wgmma64h(uint32_t* d, uint32_t a0, uint32_t a1, uint32_t a2, uint32_t a3, uint32_t dlo, uint32_t dhi) {
  asm volatile("{ .reg .b64 dd; mov.b64 dd, {%20, %21}; wgmma.mma_async.sync.aligned.m64n64k16.f16.f16.f16 "
               "{%0,%1,%2,%3,%4,%5,%6,%7,%8,%9,%10,%11,%12,%13,%14,%15}, {%16,%17,%18,%19}, dd, 1, 1, 1, 0; }"
               : "+r"(d[0]), "+r"(d[1]), "+r"(d[2]), "+r"(d[3]), "+r"(d[4]), "+r"(d[5]), "+r"(d[6]), "+r"(d[7]), "+r"(d[8]), "+r"(d[9]), "+r"(d[10]), "+r"(d[11]), "+r"(d[12]), "+r"(d[13]), "+r"(d[14]), "+r"(d[15])
               : "r"(a0), "r"(a1), "r"(a2), "r"(a3), "r"(dlo), "r"(dhi));
}
__device__ __forceinline__ void wgmma64h_init(uint32_t* d, uint32_t a0, uint32_t a1, uint32_t a2, uint32_t a3, uint32_t dlo, uint32_t dhi) {
  asm volatile("{ .reg .b64 dd; mov.b64 dd, {%20, %21}; wgmma.mma_async.sync.aligned.m64n64k16.f16.f16.f16 "
               "{%0,%1,%2,%3,%4,%5,%6,%7,%8,%9,%10,%11,%12,%13,%14,%15}, {%16,%17,%18,%19}, dd, 0, 1, 1, 0; }"
               : "=r"(d[0]), "=r"(d[1]), "=r"(d[2]), "=r"(d[3]), "=r"(d[4]), "=r"(d[5]), "=r"(d[6]), "=r"(d[7]), "=r"(d[8]), "=r"(d[9]), "=r"(d[10]), "=r"(d[11]), "=r"(d[12]), "=r"(d[13]), "=r"(d[14]), "=r"(d[15])
               : "r"(a0), "r"(a1), "r"(a2), "r"(a3), "r"(dlo), "r"(dhi));
}
__device__ __forceinline__ void wgmma40_ss(float* d, uint32_t alo, uint32_t blo, uint32_t hi) {
  asm volatile("{ .reg .b64 da, db; mov.b64 da, {%20, %22}; mov.b64 db, {%21, %22}; "
               "wgmma.mma_async.sync.aligned.m64n40k16.f32.f16.f16 {%0,%1,%2,%3,%4,%5,%6,%7,%8,%9,%10,%11,%12,%13,%14,%15,%16,%17,%18,%19}, da, db, 1, 1, 1, 1, 1; }"
               : "+f"(d[0]), "+f"(d[1]), "+f"(d[2]), "+f"(d[3]), "+f"(d[4]), "+f"(d[5]), "+f"(d[6]), "+f"(d[7]), "+f"(d[8]), "+f"(d[9]), "+f"(d[10]), "+f"(d[11]), "+f"(d[12]), "+f"(d[13]), "+f"(d[14]), "+f"(d[15]), "+f"(d[16]), "+f"(d[17]), "+f"(d[18]), "+f"(d[19])
               : "r"(alo), "r"(blo), "r"(hi));
}
__device__ __forceinline__ void wgmma40_ss_init(float* d, uint32_t alo, uint32_t blo, uint32_t hi) {
  asm volatile("{ .reg .b64 da, db; mov.b64 da, {%20, %22}; mov.b64 db, {%21, %22}; "
               "wgmma.mma_async.sync.aligned.m64n40k16.f32.f16.f16 {%0,%1,%2,%3,%4,%5,%6,%7,%8,%9,%10,%11,%12,%13,%14,%15,%16,%17,%18,%19}, da, db, 0, 1, 1, 1, 1; }"
               : "=f"(d[0]), "=f"(d[1]), "=f"(d[2]), "=f"(d[3]), "=f"(d[4]), "=f"(d[5]), "=f"(d[6]), "=f"(d[7]), "=f"(d[8]), "=f"(d[9]), "=f"(d[10]), "=f"(d[11]), "=f"(d[12]), "=f"(d[13]), "=f"(d[14]), "=f"(d[15]), "=f"(d[16]), "=f"(d[17]), "=f"(d[18]), "=f"(d[19])
               : "r"(alo), "r"(blo), "r"(hi));
}
__device__ __forceinline__ float vzero() { float v; asm volatile("mov.b32 %0, 0;" : "=f"(v)); return v; }
__device__ __forceinline__ void tma_box(uint32_t dst, const CUtensorMap* tm, uint32_t mb, int x, int y) {
  asm volatile("cp.async.bulk.tensor.2d.shared::cluster.global.mbarrier::complete_tx::bytes [%0], [%1, {%3, %4}], [%2];"
               :: "r"(dst), "l"(tm), "r"(mb), "r"(x), "r"(y) : "memory");
}
__device__ __forceinline__ void l2_prefetch(const void* src, uint32_t bytes) {
  asm volatile("cp.async.bulk.prefetch.L2.global [%0], %1;" :: "l"(src), "r"(bytes) : "memory");
}
__device__ __forceinline__ uint32_t uni(uint32_t v) {
  uint32_t r; asm volatile("shfl.sync.idx.b32 %0, %1, 0, 0x1f, 0xffffffff;" : "=r"(r) : "r"(v)); return r;
}
__device__ __forceinline__ int fresh_tid() { int v; asm volatile("mov.u32 %0, %tid.x;" : "=r"(v)); return v; }

struct Params {
  const unsigned char* x;
  Scratch* s;
  int off[7];
  uint32_t zero;
  uint32_t* out;
  const uint16_t* dskip;
  const uint32_t* w_r;
  long long* ts;
  const unsigned char* far[7];
  uint32_t sched[2][17];
};
__device__ __forceinline__ uint32_t ldnc32(const void* p) { uint32_t v; asm volatile("ld.global.nc.b32 %0, [%1];" : "=r"(v) : "l"(p)); return v; }
__device__ __forceinline__ uint32_t ldnc16(const void* p) { uint16_t v; asm volatile("ld.global.nc.u16 %0, [%1];" : "=h"(v) : "l"(p)); return v; }
__device__ __forceinline__ uint4 ldnc128(const void* p) { uint4 v; asm volatile("ld.global.nc.v4.b32 {%0,%1,%2,%3}, [%4];" : "=r"(v.x), "=r"(v.y), "=r"(v.z), "=r"(v.w) : "l"(p)); return v; }
__device__ __forceinline__ void mbar_wait(uint32_t mb, uint32_t ph = 0) {
#pragma unroll 1
  for (int it = 0; it < SPIN_MAX; it++) {
    uint32_t ok;
    asm volatile("{ .reg .pred q; mbarrier.try_wait.parity.shared::cta.b64 q, [%1], %2; selp.u32 %0, 1, 0, q; }" : "=r"(ok) : "r"(mb), "r"(ph) : "memory");
    if (ok) break;
  }
}
__device__ __forceinline__ uint32_t mbar_test(uint32_t mb) {
  uint32_t ok;
  asm volatile("{ .reg .pred q; mbarrier.test_wait.parity.shared::cta.b64 q, [%1], 0; selp.u32 %0, 1, 0, q; }" : "=r"(ok) : "r"(mb) : "memory");
  return ok;
}
__device__ __forceinline__ void mbar_arrive(uint32_t mb) { asm volatile("mbarrier.arrive.shared::cta.b64 _, [%0];" :: "r"(mb) : "memory"); }
__device__ __forceinline__ uint32_t ldg16(const void* p) { uint16_t v; asm volatile("ld.global.u16 %0, [%1];" : "=h"(v) : "l"(p) : "memory"); return v; }
__device__ __forceinline__ uint32_t ldr16(const void* p) { uint16_t v; asm volatile("ld.relaxed.gpu.global.u16 %0, [%1];" : "=h"(v) : "l"(p) : "memory"); return v; }
__device__ __forceinline__ void fence_async() { asm volatile("fence.proxy.async.shared::cta;" ::: "memory"); }
#define SPIN_WHILE(cond, body) _Pragma("unroll 1") for (int _it = 0; _it < SPIN_MAX && __any_sync(0xffffffffu, (cond)); _it++) { body; }

struct LnC { uint32_t m2, rh2, rl2; };
__device__ __forceinline__ float diag_sum(float d0, float d1, int t) {
  float q = __shfl_sync(0xffffffffu, d0, 9 * t) + __shfl_sync(0xffffffffu, d1, 9 * t + 4);
  q += __shfl_xor_sync(0xffffffffu, q, 1);
  return q + __shfl_xor_sync(0xffffffffu, q, 2);
}
__device__ __forceinline__ LnC ln_consts(float s, float q, float& r) {
  const float mean = s * (1.f / DM);
  const float var = fmaxf(fmaf(-mean, mean, q * (1.f / DM)), 0.f);
  float sd;
  asm("sqrt.approx.ftz.f32 %0, %1;" : "=f"(sd) : "f"(bfr(bfr(var) + 1e-5f)));
  asm("rcp.approx.ftz.f32 %0, %1;" : "=f"(r) : "f"(bfr(sd)));
  LnC c;
  c.m2 = pack_bf(mean, mean);
  c.rh2 = pack_bf(r, r);
  const float rl = r - bf_lo(c.rh2);
  c.rl2 = pack_bf(rl, rl);
  return c;
}
__device__ __forceinline__ float quad_sum(float s) { s += __shfl_xor_sync(0xffffffffu, s, 1); return s + __shfl_xor_sync(0xffffffffu, s, 2); }
__device__ __forceinline__ uint32_t bf_fma2(uint32_t a, uint32_t b, uint32_t c) {
  __nv_bfloat162 r = __hfma2(*(const __nv_bfloat162*)&a, *(const __nv_bfloat162*)&b, *(const __nv_bfloat162*)&c);
  return *(uint32_t*)&r;
}
__device__ __forceinline__ uint32_t ln_apply(uint32_t w, uint32_t m2, uint32_t rh2, uint32_t rl2) {
  const uint32_t d = bf_sub2(w, m2);
  return bf_fma2(d, rh2, bf_mul2(d, rl2));
}

__device__ __forceinline__ float2 cis(float mag_log2, float rev) {
  const float m = ex2(mag_log2), ang = rev * 6.283185307179586f;
  return make_float2(m * __cosf(ang), m * __sinf(ang));
}
__device__ __forceinline__ float2 csq(float2 a) { return make_float2(fmaf(a.x, a.x, -a.y * a.y), (a.x + a.x) * a.y); }
__device__ __forceinline__ float2 cmul(float2 a, float2 b) { return make_float2(fmaf(a.x, b.x, -a.y * b.y), fmaf(a.x, b.y, a.y * b.x)); }
__device__ __forceinline__ void pmul(uint32_t xr, uint32_t xi, uint32_t w, uint32_t& yr, uint32_t& yi) {
  const __half2 XR = *(__half2*)&xr, XI = *(__half2*)&xi, W = *(__half2*)&w;
  const __half2 a = __hfma2(__hneg2(XI), __high2half2(W), __hmul2(XR, __low2half2(W)));
  const __half2 b = __hfma2(XI, __low2half2(W), __hmul2(XR, __high2half2(W)));
  yr = *(const uint32_t*)&a; yi = *(const uint32_t*)&b;
}
__device__ __forceinline__ uint32_t pk(float2 a) { return pack_h(a.x, a.y); }

struct KgState { float2 c0, z8; float kl; uint32_t w64, w128, w192; };
__device__ __forceinline__ void kgen_tables_n(const uint32_t (&raw)[7], uint32_t scr, int wt, KgState& k) {
  const uint32_t dst = scr + 16384 + wt * 16;
  const float dt = bfr(ex2(bf_lo(raw[6]) * 1.4426950408889634f));
  const float th = dt * bf_lo(raw[1]);
  const float br = dt * bf_lo(raw[2]), bi = dt * bf_lo(raw[3]);
  const float Cr = bf_lo(raw[4]), Ci = bf_lo(raw[5]);
  k.c0 = make_float2(fmaf(Cr, br, -Ci * bi), fmaf(Cr, bi, Ci * br));
  const uint32_t mx = __reduce_max_sync(0xffffffffu, __float_as_uint(fmaxf(fabsf(k.c0.x), fabsf(k.c0.y))));
  const float a2 = dt * bf_lo(raw[0]) * 1.4426950408889634f;
  const float rh = th * 0.15915494309189535f;
  const float rl = fmaf(th, (float)(0.15915494309189535 - (double)0.15915494309189535f), fmaf(th, 0.15915494309189535f, -rh));
  const float rf = rh - rintf(rh);
  const float2 z1 = cis(a2, rf + rl);
  const float p64 = rf * 64.f;
  const float2 z64 = cis(a2 * 64.f, fmaf(64.f, rl, p64 - rintf(p64)));
  const float2 z2 = csq(z1), z128 = csq(z64), z3 = cmul(z2, z1), z4 = csq(z2), z256 = csq(z128), z6 = csq(z3), z512 = csq(z256);
  k.z8 = csq(z4);
  k.w64 = pk(z64); k.w128 = pk(z128); k.w192 = pk(cmul(z128, z64));
  sts128(dst, 0x00003C00u, pk(z2), pk(z4), pk(z6));
  const float2 z1024 = csq(z512), z768 = cmul(z512, z256);
  sts128(dst + 2048, pk(z1), pk(z3), pk(cmul(z4, z1)), pk(cmul(z4, z3)));
  const float2 z2048 = csq(z1024);
  k.kl = fmaf(k.c0.x, z2048.x, -k.c0.y * z2048.y);
  sts128(dst + 4096, pk(z256), pk(cmul(z256, z2)), pk(cmul(z256, z4)), pk(cmul(z256, z6)));
  sts128(dst + 6144, pk(z512), pk(cmul(z512, z4)), pk(z768), pk(cmul(z768, z4)));
  sts128(dst + 8192, pk(z1024), pk(cmul(z1024, z256)), pk(cmul(z1024, z512)), pk(cmul(z1024, z768)));
  sts32(scr + W_MISC + (wt >> 5) * 4, mx);
}
__device__ __forceinline__ int kgen_tables_m(uint32_t scr, int wt, const KgState& k) {
  const uint32_t dst = scr + wt * 16;
  const uint4 e4 = lds128(scr + W_MISC);
  const float2 z16 = csq(k.z8), z32 = csq(z16);
  const int em = max(min((int)(max(max(e4.x, e4.y), max(e4.z, e4.w)) >> 23), 238), 16);
  const float sc = __uint_as_float((uint32_t)(127 + 4 + 127 - em) << 23);
  sts32(scr + W_MISC + 16 + (wt >> 5) * 4, __reduce_add_sync(0xffffffffu, __float2int_rn(k.kl * sc * 262144.f)));
  const float2 c0 = make_float2(k.c0.x * sc, k.c0.y * sc);
  const float2 c1 = cmul(c0, k.z8), c2 = cmul(c0, z16), c4 = cmul(c0, z32), c3 = cmul(c1, z16), c5 = cmul(c1, z32), c6 = cmul(c2, z32), c7 = cmul(c3, z32);
  uint32_t pr[4], pi[4], yr[4], yi[4];
  pr[0] = pack_h(c0.x, c1.x); pi[0] = pack_h(c0.y, c1.y);
  pr[1] = pack_h(c2.x, c3.x); pi[1] = pack_h(c2.y, c3.y);
  pr[2] = pack_h(c4.x, c5.x); pi[2] = pack_h(c4.y, c5.y);
  pr[3] = pack_h(c6.x, c7.x); pi[3] = pack_h(c6.y, c7.y);
  sts128(dst, pr[0], pr[1], pr[2], pr[3]); sts128(dst + 2048, pi[0], pi[1], pi[2], pi[3]);
#pragma unroll
  for (int q = 1; q < 4; q++) {
    const uint32_t w = q == 1 ? k.w64 : q == 2 ? k.w128 : k.w192;
#pragma unroll
    for (int i = 0; i < 4; i++) pmul(pr[i], pi[i], w, yr[i], yi[i]);
    sts128(dst + q * 4096, yr[0], yr[1], yr[2], yr[3]); sts128(dst + q * 4096 + 2048, yi[0], yi[1], yi[2], yi[3]);
  }
  return em;
}
__device__ __forceinline__ void kgen_build(uint32_t tb, int wg, int wt, uint32_t k0, uint32_t k1, uint32_t k2) {
  const uint32_t kt = tb + W_KT, sc = tb + W_L3 + 3072;
  const int ix = ((wt >> 2) + (wt & 3) * 32 - 1) & 127;
  const uint32_t a3 = tb + W_CW + 32 + ((ix & 1) ? 0 : 304) + (ix >> 1) * 4;
  const uint32_t v3 = wt ? k2 : k2 >> 16;
  sts32(sc + 4 + wt * 4, __byte_perm(k0, k1, 0x5432));
  sts16(sc + 544 + (wt & ~3) + (wt & 1) * 2 + (wt & 2) * 64, k1 >> 16);
  sts16(a3, v3); sts16(a3 + 6, v3);
  if ((unsigned)(wt - 32) < 18u) sts128(kt + (wt < 36 ? -512 : 64 + 4128 - 576) + wt * 16, 0, 0, 0, 0);
  if (wt == 127) sts32(sc, k0 & 0xFFFF0000u);
  if (wt == 0) { sts32(sc + 516, k1); sts16(sc + 800, k2); }
  bar_sync(1 + wg, 128);
  const uint32_t cw = tb + W_CW + 32 + (wt >> 6) * 48 + wt * 4;
  const uint32_t pv = lds32(sc + wt * 4), nx = lds32(sc + 8 + wt * 4), c2 = lds16(sc + 544 + wt * 2), n2 = lds16(sc + 546 + wt * 2);
  sts128(tb + W_L3 + 512 + (wt >> 6) * 512 + wt * 16, lds32(cw), lds32(cw - 8), lds32(cw - 16), lds32(cw - 24));
  const bool odd = wt & 1;
  sts64(kt + 64 + wt * 8, __byte_perm(k0, pv, 0x5410), __byte_perm(k0, 0, 0x1032));
  sts64(kt + 64 + 1024 + wt * 8, __byte_perm(k1, pv, (odd || wt == 0) ? 0x7610 : 0x1010), __byte_perm(k1, nx, odd ? 0x1076 : 0x1010));
  const uint32_t cc = c2 * 0x10001u, nc = __byte_perm(n2, c2, 0x5410), nn = n2 * 0x10001u;
  sts128(kt + 64 + 2048 + wt * 16, cc, cc, odd ? nc : cc, odd ? nn : nc);
  if (wt == 127) { sts128(kt + 64 + 4096, nn, nn, nn, nn); sts128(kt + 64 + 4112, nn, nn << 16, 0, 0); }
}

__device__ __forceinline__ void load_a(uint32_t (&a)[4], uint32_t kp, int j) {
  a[0] = lds32(kp + 64 * j); a[1] = lds32(kp + 64 * j + 512); a[2] = lds32(kp + 64 * j - 32); a[3] = lds32(kp + 64 * j + 480);
}
__device__ __forceinline__ uint32_t band(int d, int lo, int hi) {
  return ((unsigned)(d - lo) <= (unsigned)(hi - lo) ? 1u : 0u) | ((unsigned)(d - 1 - lo) <= (unsigned)(hi - lo) ? 0x10000u : 0u);
}
__device__ __forceinline__ uint32_t hadd2u(uint32_t a, uint32_t b) { __half2 r = __hadd2(*(__half2*)&a, *(__half2*)&b); return *(uint32_t*)&r; }

__device__ __forceinline__ void zero_pads(uint32_t tb, int wt) {
  if (!(wt & 32)) sts128(tb + W_L3 + (wt >> 6) * 512 + wt * 16, 0, 0, 0, 0);
  if ((wt & 63) < 3) sts128(tb + W_CW + (wt >> 6) * 304 + (wt & 63) * 16, 0, 0, 0, 0);
}
__device__ __forceinline__ uint32_t tr_base(int lane) {
  return OFF_YT + (2 * (lane >> 3) + (lane & 1)) * YT_PITCH + ((lane >> 1) & 1) * (8 * YT_PITCH + 64) + ((lane >> 2) & 1) * 16;
}

__device__ __forceinline__ uint32_t sc_addr(int tp) { return OFF_YT + (tp < 16 ? tp * YT_PITCH + (tp >> 3) * 64 + 1152 : 8 * YT_PITCH - 512 + tp * 32); }
#define X_PS 1
#define X_PW 15
#define X_HU 16
#define X_HB 0
#define X_REL 1
#define X_PAD0 0
#define X_PAD1 0
#define PAD(n) _Pragma("unroll") for (int _i = 0; _i < (n); _i++) asm volatile("pmevent 0;");
#define X_HW 0
#define X_LA 9
#define X_NE 2
#define X_SCT 10000
#define X_DELTA 400
#define X_DSTEP 2000
#define X_PF0 2500
#define X_PFD 600
#define X_TD 450
#define X_WS 6
#define X_OR 8
#define X_ABS 5100
#define X_XD 0
#define X_RD 700
#define X_HD 500
#define X_PD 1150
#define X_PROMO 2
#define X_YD2 1000
#define X_GO 2
#define X_GW 2
#define X_NS 4700
#define X_XS 13600
#define X_LAG 1800
#define X_YD 1550
struct TMaps { CUtensorMap m[10]; };
__device__ __forceinline__ uint32_t h2bf(uint32_t w) { const float2 f = h2f(w); return pack_bf(f.x, f.y); }
__device__ __forceinline__ uint32_t keep(uint32_t v) { asm volatile("" : "+r"(v)); return v; }
__device__ __forceinline__ uint2 ldr64(const void* p) { uint2 v; asm volatile("{ .reg .b64 t; ld.relaxed.gpu.global.b64 t, [%2]; mov.b64 {%0, %1}, t; }" : "=r"(v.x), "=r"(v.y) : "l"(p) : "memory"); return v; }
__host__ __device__ __forceinline__ uint32_t down_box(int s, bool five) {
  return five ? OFF_W + W_BYTES + 12288 + (s / 3) * (W_BYTES - 12288) + s * 4096 : s < 6 ? OFF_W + W_BYTES + BOX + (s >> 1) * (W_BYTES - 10240) + s * 5120 : OFF_W + (s - 6) * 5120;
}
__device__ __forceinline__ void load_tile(const CUtensorMap* tmx, int i, int c, int again = 0) {
  asm volatile("mbarrier.arrive.expect_tx.shared::cta.b64 _, [%0], 8704;" :: "r"(MB_UL + i * 16 + again) : "memory");
  asm volatile("cp.async.bulk.tensor.3d.shared::cluster.global.mbarrier::complete_tx::bytes [%0], [%1, {%3, %4, %5}], [%2];"
               :: "r"(i < 2 ? OFF_T + i * TILE : OFF_W), "l"(tmx), "r"(MB_UL + i * 16 + again), "r"(0), "r"(c), "r"(-8) : "memory");
}
template <bool FAR> __device__ __forceinline__ void load_params(const Params& p, uint32_t ch, int wt, uint32_t dst, bool on) {
  const int o01 = (wt & 16) ? p.off[1] : p.off[0], o23 = (wt & 16) ? p.off[3] : p.off[2], o45 = (wt & 16) ? p.off[5] : p.off[4];
  const int o = (wt & 64) ? ((wt & 32) ? p.off[6] : o45) : ((wt & 32) ? o23 : o01);
  const unsigned char* b = FAR ? p.far[min(wt >> 4, 6)] : p.x + (long long)o * 16;
  asm volatile("{ .reg .pred q; setp.ne.u32 q, %2, 0; @q cp.async.cg.shared.global [%0], [%1], 16; }"
               :: "r"(dst + wt * 16), "l"(b + (wt < 96 ? ch * 256 + (wt & 15) * 16 : (ch >> 3) * 16)), "r"((uint32_t)(on && wt < 97)) : "memory");
}

struct ConvC { uint32_t ca, cb, bands; };
__device__ __forceinline__ ConvC conv_consts(int w, int lane) {
  const int h = w & 1, P = (w >> 1) & 1, d0 = 8 * h + (lane >> 2) - 2 * (lane & 3);
  ConvC k;
  k.ca = keep((W_KT + (16 + 256 * P + d0) * 4) | (((8 + 64 * P + lane) * 64 + (((h + ((w >> 1) & 2)) ^ (lane >> 1)) & 3) * 16) << 16));
  k.cb = keep(lane < 8 ? 0xFFFEFFFEu : ~0u);
  k.bands = keep(band(d0, 12, 20) + 2 * band(d0 + 8, 12, 20) + 4 * band(d0 + 16, 12, 20) + 8 * band(d0 + 24, 12, 20)
                 + 16 * band(d0 - 8, 5, 11) + 32 * band(d0, 5, 11) + 64 * band(d0 + 8, 5, 11) + 128 * band(d0 + 16, 5, 11));
  return k;
}
struct ConvPre { uint32_t e0, e2, f2, a[3][4]; };
__device__ __forceinline__ uint32_t lds32_if(uint32_t a, bool on) {
  uint32_t v; asm volatile("{ .reg .pred q; setp.ne.u32 q, %2, 0; mov.b32 %0, 0; @q ld.shared.b32 %0, [%1]; }" : "=r"(v) : "r"(a), "r"((uint32_t)on) : "memory"); return v;
}
__device__ __forceinline__ void conv_pre(ConvPre& r, uint32_t kp, int part, bool on, bool P) {
  if (part & 1) { r.e0 = lds32_if(kp + 4096, on && !P); r.e2 = lds32_if(kp + 4064, on && !P); r.f2 = lds32_if(kp + 4128, on && !P); }
#pragma unroll
  for (int j = 0; j < 3; j++) if (part & (j < X_PS ? 1 : 2)) {
    r.a[j][0] = lds32_if(kp + 2048 + 64 * j, on); r.a[j][1] = lds32_if(kp + 2560 + 64 * j, on); r.a[j][2] = lds32_if(kp + 2016 + 64 * j, on); r.a[j][3] = lds32_if(kp + 2528 + 64 * j, on);
  }
}
__device__ __forceinline__ void conv_item(uint32_t tb, uint32_t tl, int bid, int bn, ConvPre& pre, const ConvC& cv, uint32_t zero, const CUtensorMap* tmx, int ch, int warp, int lane, bool hold, bool more) {
  const bool go = more && warp == 0 && lane == 0;
  const uint32_t kp = tb + (cv.ca & 0xFFFFu);
  const uint32_t dlo = (tl >> 4) + 32 + ((warp >> 1) & 2) + (1u << 16), dhi = 32u | (2u << 30);
  const bool P = warp & 2;
  float a32[16], b32[16], a64[32];
  uint32_t A[40][4];
#define STEP(J) { wgmma64<0>(a64, A[J], dlo + 256 - 4 * (J), dhi); \
    if ((J) == 32) wgmma32_init<0>(b32, A[J], dlo, dhi); else wgmma32<0>(b32, A[J], ((J) < 8 ? dlo ^ zero : dlo) + 128 - 4 * (J), dhi); \
    if ((J) == 0) wgmma32_init<0>(a32, A[J], dlo, dhi); else if ((J) < 8) wgmma32<0>(a32, A[J], (dlo ^ zero) - 4 * (J), dhi); }
#define LD(J) load_a(A[J], kp, J);
#define FIRST(J) wg_fence(); STEP(J) wg_commit(); wg_wait<1>(); wg_fence();
  {
    uint32_t win[16], x9[4], x7[4], e[4], f[4];
    const uint32_t bz = keep(cv.bands);
#define BAND(i) keep((bz & (0x10001u << (i))) * (0x3C00u >> (i)))
    e[0] = pre.e0; e[2] = pre.e2; e[1] = keep(bz & 0x100u); e[3] = keep(bz & 0x200u);
    f[2] = pre.f2; f[0] = keep(bz & 0x4000u); f[1] = keep(bz & 0x8000u); f[3] = keep(bz & 0x300u);
#pragma unroll
    for (int j = 0; j < 12; j++) A[32 + j / 4][j & 3] = pre.a[j / 4][j & 3];
    const uint32_t q[12] = {BAND(0), BAND(5), keep(bz & 0x400u), BAND(4), BAND(2), BAND(7), BAND(1), BAND(6), keep(bz & 0x800u), keep(bz & 0x1000u), BAND(3), keep(bz & 0x2000u)};
#undef BAND
    const uint32_t ta = keep(tl + 512 + (warp & 3) * 2048 + lane * 64 + (lane & 6) * 8);
    if (X_GO && hold) mbar_wait(MB_GO);
    uint32_t mbl = MB_UL + (warp & 8) * 2, ph = 0;
#pragma unroll 1
    for (int it = 0; it < SPIN_MAX; it++) {
      if (ch < 512) mbar_wait(mbl, ph);
      if (it == 1) TS(13);
      TS(3);
      wg_fence();
      wgmma64h_init(win, q[0], q[1], q[2], q[3], dlo, dhi);
      wgmma64h(win, q[4], q[5], q[6], q[7], dlo - 4, dhi);
      wgmma64h(win, q[8], q[9], q[10], q[11], dlo - 8, dhi);
      wg_commit();
      wgmma64_init<0>(a64, e, dlo, dhi);
      wgmma64<0>(a64, f, dlo - 4, dhi);
      wg_commit();
      if (ch >= 512) break;
      uint32_t r0, r1, r2, r3, ok;
      if (warp & 4) {
        mbar_wait(mbl + 8);
        if (__all_sync(0xffffffffu, it || lds32(MISC_RT + (warp & 8)) == 0)) break;
        wg_wait<0>();
        continue;
      }
      ldsm4(ta, r0, r1, r2, r3);
      ok = r0 & r1 & r2 & r3;
      ldsm4(ta ^ 32, r0, r1, r2, r3);
      asm volatile("{ .reg .pred q; setp.ne.u32 q, %1, 0; barrier.red.and.pred q, %2, 128, q; selp.u32 %0, 1, 0, q; }" : "=r"(ok) : "r"((ok & r0 & r1 & r2 & r3 & 1u) | (lane & 3)), "r"(1 + (warp >> 2)) : "memory");
      if (ok) { if ((warp & 3) == 0 && lane == 0) { sts32(MISC_RT + warp, it); mbar_arrive(MB_UL + 8 + warp * 2); } break; }
      wg_wait<0>();
      if ((warp & 3) == 0 && lane == 0) load_tile(tmx - 1, warp >> 3, ch, 56);
      mbl = MB_UL + 56 + (warp & 8) * 2; ph = it & 1;
    }
    wg_wait<1>();
#pragma unroll
    for (int i = 0; i < 4; i++) {
      const int tl = 2 * ((i & 1) + ((i & 2) ? 0 : 4));
      x9[i] = P ? win[tl + 4] : win[tl]; x7[i] = P ? win[tl + 5] : win[tl + 1];
    }
    const uint32_t l3lo = ((tb + W_L3) >> 4) + (32u << 16);
    wg_fence();
    wgmma64<0>(a64, x9, l3lo, 8);
    wgmma64<0>(a64, x7, l3lo + 96, 8);
    wg_commit();
  }
  STEP(32) STEP(33) STEP(34) wg_commit(); wg_wait<1>();
  LD(35) LD(36) LD(37) LD(38)
  FIRST(35) STEP(36) STEP(37) STEP(38) wg_commit();
  LD(39) LD(0)
  TS(17);
  if (X_GO == 1 && go) mbar_arrive(MB_GO);
  FIRST(39) STEP(0) wg_commit();
  LD(1) LD(2) LD(3)
  FIRST(1) STEP(2) STEP(3) wg_commit();
  LD(4) LD(5)
  if (X_GO == 2 && go) mbar_arrive(MB_GO);
  FIRST(4) STEP(5) wg_commit();
  LD(6) LD(7)
  wg_fence(); STEP(6) STEP(7) wg_commit();
#undef STEP
#undef LD
#undef FIRST
  TS(18);
  if (X_GO == 3 && go) mbar_arrive(MB_GO);
  const uint32_t xc = tb + W_KT + (warp & 3) * 1024 + lane * 16;
  if (more) bar_sync(7, 288);
  wg_wait<1>();
  conv_pre(pre, kp + ALT, 1, more, P);
  wg_wait<0>();
  conv_pre(pre, kp + ALT, 2, more, P);
  uint32_t E[16], o[8];
#define ACC(i) ((i) < 16 ? a32[i] : (i) < 32 ? b32[(i) - 16] : a64[(i) - 32])
  E[0] = pack_h(a32[0], a32[1]);
#pragma unroll
  for (int i = 1; i < 16; i++) E[i] = pack_h(ACC(4 * i) + ACC(4 * i - 2), ACC(4 * i + 1) + ACC(4 * i - 1));
#undef ACC
#pragma unroll
  for (int j = 0; j < 8; j++) o[j] = P ? (j < 2 ? 0u : E[j - 2]) : E[8 + j];
  sts128(xc, o[0], o[1], o[2], o[3]); sts128(xc + 512, o[4], o[5], o[6], o[7]);
#pragma unroll
  for (int j = 0; j < 8; j++) o[j] = P ? E[6 + j] : E[j];
  TS(25);
  if (more) {
    sts128(xc + 4096, o[0], o[1], o[2], o[3]); sts128(xc + 4608, o[4], o[5], o[6], o[7]);
    bar_arrive(12, 192);
    return;
  }
  bar_sync(1 + (warp >> 2), 128);
  const uint4 vv[2] = {lds128(xc + (P ? -2048 : 2048)), lds128(xc + (P ? -1536 : 2560))};
#pragma unroll
  for (int q = 0; q < 2; q++) {
    const uint4 v = vv[q];
    stsm4t(tl + (cv.ca >> 16) + q * 2048, hadd2u(o[4 * q], v.x) & cv.cb, hadd2u(o[4 * q + 1], v.y) & cv.cb, hadd2u(o[4 * q + 2], v.z) & cv.cb, hadd2u(o[4 * q + 3], v.w) & cv.cb);
  }
  fence_async();
  bar_sync(bid, bn);
  if (warp == 0 && lane == 0) mbar_arrive(MB_REL);
  if ((warp & 7) == (ch < 512 ? 7 : 3) && lane == 0) {
    asm volatile("cp.async.bulk.tensor.3d.global.shared::cta.bulk_group [%0, {%3, %2, %3}], [%1];" :: "l"(tmx), "r"(tl + 512), "r"(ch), "r"(0) : "memory");
    asm volatile("cp.async.bulk.commit_group;" ::: "memory");
  }
}

template <bool FAR> __global__ void __launch_bounds__(NT, 1)
fused_kernel(const __grid_constant__ Params p, const __grid_constant__ TMaps tm) {
  extern __shared__ __align__(1024) unsigned char smem[];
  const int c = blockIdx.x;
  const bool five = (c & 1) == 0;
  const uint32_t pitch = five ? 64 : 80;
  const uint32_t ones = 0x3F803F80u;
  const int tid = threadIdx.x, lane = tid & 31;
  {
    const int w4 = tid >> 7, k5 = !five && w4 == 3;
    load_params<FAR>(p, k5 ? 512 + (c >> 1) : (w4 & 2) * 128 + 2 * c + (w4 & 1), tid & 127, OFF_W + w4 * W_BYTES + W_KT + k5 * 2048, w4 != 2 && w4 != 4);
  }
  const int warp = (int)uni(tid >> 5), wg = warp >> 2;
  TS(0);
  if (__builtin_expect(wg == 4, 0)) {
    asm volatile("setmaxnreg.dec.sync.aligned.u32 32;");
    const int role = warp;
    const int u0 = (c >> 1) * 9 + (five ? ((c & 2) ? 5 : 0) : ((c & 2) ? 0 : 4));
    const uint32_t t0 = clock() + c * 4;
    if (role == 16) {
      if (lane < 19) asm volatile("mbarrier.init.shared::cta.b64 [%0], %1;" :: "r"(OFF_MISC + lane * 8), "r"((unsigned)(lane - 2) < 4u ? 4 : 1) : "memory");
      if (lane < 2) asm volatile("mbarrier.arrive.expect_tx.shared::cta.b64 _, [%0], %1;" :: "r"(OFF_MISC + lane * 8), "r"(lane ? (five ? 36864 : 51200) : pitch * 1152) : "memory");
      fence_async();
      bar_arrive(5, 608);
      const CUtensorMap* tmb = &tm.m[five ? 3 : 0];
#pragma unroll 1
      for (int u = 0; u < 17; u++) {
        const uint32_t e = p.sched[five][u], kind = e & 3, s = (e >> 2) & 15, dst = e >> 14;
        if (kind == 3) continue;
        while ((int)(clock() - t0) < X_PF0 + (u < X_NE ? u * X_PFD : X_LAG + u * X_TD)) __nanosleep(20);
        if (e & 0x3FC0) mbar_wait(OFF_MISC + ((e >> 6) & 255));
        if (lane == 0) {
          if (kind == 2) asm volatile("cp.async.bulk.tensor.3d.shared::cluster.global.mbarrier::complete_tx::bytes [%0], [%1, {%3, %4, %5}], [%2];"
                                      :: "r"(dst), "l"(tmb + 2), "r"(MB_D), "r"(0), "r"(u0 * 8), "r"(s) : "memory");
          else tma_box(dst, tmb + kind, MB_GU, u0 * 8, s * 96);
        }
        if (u == 5) TS(2);
        if (u == 10) TS(3);
      }
      TS(4);
      TS_DUMP();
#define FINISH0 bar_sync(12, 192);        \
        _Pragma("unroll 1") for (int w = role & 2; w < (role & 2) + 2; w++) { \
          const uint32_t xa = OFF_W + W_KT + lane * 16, mk = lane < 8 ? 0xFFFEFFFEu : ~0u, ya = OFF_T + (8 + lane) * 64 + (((w & 1) ^ (lane >> 1)) & 3) * 16 + (w & 2) * 2048; \
          const uint4 a = lds128(xa + 4096 + w * 1024), b = lds128(xa + (w ^ 2) * 1024), d = lds128(xa + 4608 + w * 1024), e = lds128(xa + 512 + (w ^ 2) * 1024); \
          stsm4t(ya, hadd2u(a.x, b.x) & mk, hadd2u(a.y, b.y) & mk, hadd2u(a.z, b.z) & mk, hadd2u(a.w, b.w) & mk); \
          stsm4t(ya + 2048, hadd2u(d.x, e.x) & mk, hadd2u(d.y, e.y) & mk, hadd2u(d.z, e.z) & mk, hadd2u(d.w, e.w) & mk); \
        } \
        fence_async();
    } else if (role == 17) {
      if (smem_u32(smem) != SB) __trap();
      bar_sync(10, 576);
      if (lane == 0) {
        fence_async();
        while ((int)(clock() - t0) < X_NS - c * 4) {}
        asm volatile("cp.async.bulk.global.shared::cta.bulk_group [%0], [%1], 10240;" :: "l"(&p.s->X[c * DM * 2 + 512]), "r"(OFF_G) : "memory");
        asm volatile("cp.async.bulk.commit_group;" ::: "memory");
        asm volatile("cp.async.bulk.wait_group 0;" ::: "memory");
      }
      if (lane == 0) mbar_arrive(MB_GF);
      bar_arrive(11, 96);
      if (five) { FINISH0 bar_arrive(13, 192); }
    } else if (role == 18) {
      sts32(MISC_EPOCH, 0);
      sts32(MISC_T0, t0 - c * 4);
      bar_arrive(5, 608);
      uint4* q = lane < 2 ? &p.s->R[c * 2 + lane] : lane < 11 ? &p.s->HS[c * 9 + lane - 2] : lane == 11 ? &p.s->HS[1152 + (c & 7)] : (uint4*)&p.s->FLAG[c * 8];
      if (lane < (c < 8 ? 12 : 11)) str128(q, ~0u, ~0u, ~0u, ~0u);
      const uint32_t ep = __shfl_sync(0xffffffffu, ldr32(q), 31) + 1u;
      sts32(MISC_EPOCH, ep | 0x80000000u);
      TSX(21);
      if (lane == 31) str32(q, ep);
      bar_sync(11, 96);
      TSX(14);
      mbar_wait(MB_KF + (lane & 3) * 8);
      __syncwarp();
      { const uint2 e = lds64(MISC_EM); if (lane < 2) str128(&p.s->SC[c * 2 + lane], e.x, __byte_perm(e.y, ep, 0x6540), 0, 0); }
      TSX(17);
      while ((int)(clock() - t0) < X_SCT) __nanosleep(100);
      TSX(18);
      {
        uint2 v[4];
#pragma unroll 1
        for (int it = 0; it < SPIN_MAX; it++) {
          uint32_t bad = 0;
#pragma unroll
          for (int q = 0; q < 4; q++) v[q] = ldr64(&p.s->SC[lane * 2 + q * 64]);
#pragma unroll
          for (int q = 0; q < 4; q++) bad |= (v[q].y >> 8) ^ (ep & 0xFFFFFFu);
          if (!__any_sync(0xffffffffu, bad)) break;
        }
        TSX(25);
#pragma unroll
        for (int q = 0; q < 4; q++) {
          const uint32_t sa = (lane >> 4) * YT_PITCH + (lane & 15) * 2;
          sts16(sc_addr(2 * q) + sa, v[q].x); sts16(sc_addr(8 + 2 * q) + sa, v[q].x >> 16);
          if (lane & 1) asm volatile("st.shared.u8 [%0], %1;" :: "r"(sc_addr(16) + q * 16 + (lane >> 1)), "r"(v[q].y) : "memory");
        }
      }
      __syncwarp();
      if (lane == 0) mbar_arrive(MB_SC);
      TSX(27);
    } else {
      uint32_t w[9];
      const uint32_t dk = ldnc16(p.dskip + ((lane & 4) ? 512 + (c >> 1) : (lane & 2) * 128 + 2 * c + (lane & 1)));
      float s = 0.f;
#pragma unroll
      for (int i = 0; i < 9; i++) w[i] = ldnc32(p.w_r + lane + 32 * i);
      sts16(OFF_WR + 1152 + lane * 2, dk);
      bar_arrive(5, 608);
#pragma unroll
      for (int i = 0; i < 9; i++) { sts32(OFF_WR + lane * 4 + i * 128, w[i]); s += bf_lo(w[i]) + bf_hi(w[i]); }
      sts32(MISC_SW, __float_as_uint(warp_sum(s)));
      TSX(23);
      bar_sync(10, 576);
      if (lane == 0) {
        const uint32_t tp = clock();
        TSX(1);
        while ((int)(clock() - tp) < X_DELTA || (int)(clock() - t0) < X_ABS - c * 4) {}
        TSX(24);
        load_tile(&tm.m[6], 0, c);
        TSX(15);
        while ((int)(clock() - t0) < X_ABS + X_DSTEP - c * 4) {}
      }
      bar_sync(11, 96);
      if (lane == 0) {
        load_tile(&tm.m[6], 1, 128 + c);
      }
      if (five) {
        mbar_wait(MB_KF);
#pragma unroll 1
        for (int it = 0; it < SPIN_MAX; it++) {
          if (lane == 0) load_tile(&tm.m[8], 2, 512 + (c >> 1));
          mbar_wait(MB_UL + 32, it & 1);
          uint32_t m = 1;
#pragma unroll
          for (int q = 0; q < 4; q++) { uint32_t r0, r1, r2, r3; ldsm4(OFF_W + 512 + lane * 64 + (lane & 6) * 8 + q * 2048, r0, r1, r2, r3); m &= r0 & r1 & r2 & r3; }
          if (__all_sync(0xffffffffu, m || (lane & 3))) break;
        }
        bar_arrive(7, 288);
        FINISH0
        bar_arrive(13, 192);
      }
      bar_sync(0, 544);
      if (lane == 0) mbar_arrive(MB_H);
    }
    return;
  }
  const int wt = tid & 127, g = lane >> 2, t = lane & 3;
  const uint32_t wb = OFF_W + wg * W_BYTES;
  const uint32_t xrow = OFF_YT + (wt >> 3) * YT_PITCH + (wt & 64) + (lane & 7) * 16;
  if (wg == 2) {
    const unsigned char* xp = p.x + (uint32_t)((c * 16 + (wt >> 3)) * 1152 + (lane & 7) * 16);
    { const uint32_t tq = clock(); while ((int)(clock() - tq) < X_XD) {} }
#pragma unroll
    for (int k = 0; k < 9; k++) asm volatile("cp.async.cg.shared.global [%0], [%1], 16;" :: "r"(xrow + k * 128), "l"(xp + k * 128) : "memory");
  }
  asm volatile("cp.async.commit_group;" ::: "memory");
  const ConvC cv = conv_consts(warp, lane);
  zero_pads(wb, wt);
  load_params<FAR>(p, 254 + 2 * c + wg, wt, wb + W_KT, wg == 2 || (wg == 3 && !five));
  asm volatile("cp.async.commit_group;" ::: "memory");
  asm volatile("setmaxnreg.inc.sync.aligned.u32 112;");
  PAD(X_PAD0)
  {
    uint4 kw;
    uint4* kx = &p.s->KX[(c >> 1) * 128 + wt];
    bool two = wg == 3;
    uint32_t ep;
    int em = 0;
    int phase = wg == 2 ? 3 : 2;
#pragma unroll 1
    for (;;) {
      const bool first = two && !five;
      if (phase) asm volatile("cp.async.wait_group 1;" ::: "memory"); else asm volatile("cp.async.wait_group 0;" ::: "memory");
      if (phase == 3) {
        TS(21);
        float d[3][4], r;
        uint4 a[9];
#pragma unroll
        for (int k = 0; k < 9; k++) a[k] = lds128(xrow + k * 128);
#pragma unroll
        for (int i = 0; i < 4; i++) d[0][i] = d[1][i] = d[2][i] = 0.f;
#pragma unroll
        for (int k = 0; k < 9; k++) { mma_bf16(d[(2 * k) % 3], a[k].x, ones, a[k].y, ones, a[k].x, a[k].y); mma_bf16(d[(2 * k + 1) % 3], a[k].z, ones, a[k].w, ones, a[k].z, a[k].w); }
#pragma unroll
        for (int i = 0; i < 4; i++) d[0][i] += d[1][i] + d[2][i];
        const LnC lc = ln_consts(d[0][2] + d[0][3], __shfl_sync(0xffffffffu, d[0][0], 9 * t) + __shfl_sync(0xffffffffu, d[0][1], 9 * t + 4), r);
        if (lane < 12) sts16(MISC_LN1 + g * 32 + (warp & 3) * 8 + t * 2, lane < 4 ? lc.m2 : lane < 8 ? lc.rh2 : lc.rl2);
      } else {
        KgState ks;
        uint32_t raw[7];
        bar_sync(1 + wg, 128);
        TS(22);
#pragma unroll
        for (int i = 0; i < 7; i++) raw[i] = lds16(wb + W_KT + first * 2048 + i * 256 + (i < 6 ? wt : (first ? c >> 1 : 2 * c + (wg & 1)) & 7) * 2);
        kgen_tables_n(raw, wb, wt, ks);
        TS(20);
        bar_sync(1 + wg, 128);
        em = kgen_tables_m(wb, wt, ks);
        fence_async();
      }
      if (phase & 2) {
        const uint32_t tr_addr = tr_base(lane) + warp * 32;
        uint4* dst = &p.s->X[c * DM * 2 + warp * 32 + (8 * (t >> 1) + g) * 2 + (t & 1)];
        TS(23);
        bar_sync(5, 608);
        uint32_t x[3][4];
        ldsm4t(tr_addr, x[0][0], x[0][1], x[0][2], x[0][3]);
        const uint4 m = lds128(MISC_LN1 + (t & 1) * 16), rl = lds128(MISC_LN1 + 64 + (t & 1) * 16), rh = lds128(MISC_LN1 + 32 + (t & 1) * 16);
        ldsm4t(tr_addr + 512, x[1][0], x[1][1], x[1][2], x[1][3]);
        if (wg == 3) ldsm4t(tr_addr + 640, x[2][0], x[2][1], x[2][2], x[2][3]);
#pragma unroll
        for (int q = 0; q < 3; q++) {
          if (q < 2 || wg == 3) {
            const uint32_t r0 = ln_apply(x[q][0], m.x, rh.x, rl.x), r1 = ln_apply(x[q][1], m.y, rh.y, rl.y), r2 = ln_apply(x[q][2], m.z, rh.z, rl.z), r3 = ln_apply(x[q][3], m.w, rh.w, rl.w);
            const uint32_t w0 = (pack_h(bf_lo(r0), bf_hi(r0)) & 0xFFFEFFFEu) | 1u, w1 = pack_h(bf_lo(r1), bf_hi(r1)), w2 = pack_h(bf_lo(r2), bf_hi(r2)), w3 = pack_h(bf_lo(r3), bf_hi(r3));
            if (q == 0) str128(dst, w0, w1, w2, w3);
            else sts128(OFF_G + warp * 512 + (8 * (t >> 1) + g) * 32 + (t & 1) * 16 + (q == 2 ? 2048 : 0), w0, w1, w2, w3);
          }
          if (q == 0) TS(30);
        }
        bar_arrive(10, 576);
        TS(1);
      } else bar_sync(1 + wg, 128);
      phase &= 1;
      if (phase) { phase = 0; continue; }
      TS(14);
      float acc[20];
      const uint32_t alo = (wb >> 4) | (8u << 16);
      wg_fence();
      wgmma40_ss_init(acc, alo, alo + 1024, 2048 >> 4);
#pragma unroll
      for (int k = 1; k < 8; k++) wgmma40_ss(acc, alo + k * 16, alo + 1024 + k * 16, 2048 >> 4);
      wg_commit();
      const uint4 k4 = lds128(wb + W_MISC + 16);
      const float k2048 = (float)(int)(k4.x + k4.y + k4.z + k4.w) * (1.f / 262144.f);
      const uint32_t dk = lds16(OFF_WR + 1152 + (wg + first) * 2);
      const int ef = max(em, min((int)((dk >> 7) & 255u) - 7, 238));
      asm volatile("st.shared.u8 [%0], %1;" :: "r"(MISC_EM + wg + first), "r"(ef + 9) : "memory");
      const float un = __uint_as_float((uint32_t)max(114 + em - ef, 0) << 23), d0 = wt ? 0.f : bf_lo(dk) * __uint_as_float((uint32_t)(245 - ef) << 23);
      wg_wait<0>();
      kw.x = pack_h(fmaf(acc[0] - acc[3], un, d0), (acc[4] - acc[7]) * un);
      kw.y = pack_h((acc[8] - acc[11]) * un, (acc[12] - acc[15]) * un);
      kw.z = pack_h((acc[16] - acc[19]) * un, k2048 * un);
      TS(24);
      ep = 0;
      if (two) SPIN_WHILE(ep == 0, ep = lds32(MISC_EPOCH));
      if (five || !two) break;
      str128(kx, kw.x, kw.y, kw.z, ep);
      two = false;
    }
    if (lane == 0) mbar_arrive(MB_KF + wg * 8);
    if (two) { mbar_wait(MB_KF); zero_pads(OFF_W + ALT, wt); }
    uint32_t tb = wb;
#pragma unroll 1
    for (;;) {
      kgen_build(tb, wg, wt, kw.x, kw.y, kw.z);
      TS(15);
      if (!two) break;
      two = false;
      kw.w = 0;
      SPIN_WHILE(kw.w != ep, kw = ldr128(kx));
      tb = OFF_W + ALT;
    }
    fence_async();
    TS(31);
    if (tb != wb) bar_arrive(7, 288);
    bar_sync(1 + wg, 128);
  }
  uint32_t tpub;
  ConvPre pre;
  conv_pre(pre, wb + (cv.ca & 0xFFFFu), 3, true, warp & 2);
#pragma unroll 1
  for (int item = 0;; item++) {
    TS(2);
    conv_item(item ? OFF_W + ALT : wb, item ? OFF_W : OFF_T + (wg >> 1) * TILE, item ? 1 : 13 + (wg >> 1), item ? 128 : five && wg == 1 ? 192 : 256, pre, cv, p.zero,
              &tm.m[item ? 9 : 7], item ? 512 + (c >> 1) : (wg >> 1) * 128 + c, warp, lane, five && wg >= X_GW, five && !wg && !item);
    tpub = clock() - (item ? X_YD : wg >= 2 ? X_YD2 : 0);
    if (wg || !five || item) break;
    TS(27);
  }
  TS(4);
  PAD(X_PAD1)

  const int ln = lane ^ p.zero, td = warp * 32 + ln, gg = ln >> 2, tt = ln & 3;
  const int tok = c * 16 + warp;
  const int fu = warp / 3, fk = warp - fu * 3;
  uint32_t wa[12][4];
  {
    uint32_t hw[9], wr[9];
    const uint32_t row = keep(OFF_YT + warp * YT_PITCH + (warp >> 3) * 64 + ln * 16);
    const uint32_t wabase = keep(((ln & 8) ? OFF_W + (fk + 1) * W_BYTES : OFF_G + fk * 192 * pitch) + ((ln >> 4) * 8 + (ln & 7)) * pitch
                                 + (five ? ((fu ^ (ln >> 1)) & 3) : min(fu, 4)) * 16);
    float sw;
    {
      const bool three = wg == 1;
      const int ch = 8 * (tt >> 1) + gg;
      const uint32_t tr_addr = tr_base(ln);
      const uint4* ysrc = &p.s->X[c * DM * 2 + ch * 2 + (tt & 1)];
      uint32_t x[3][4], s[3];
      uint4 v[3];
#define TL(q) ((q) < 2 ? 2 * warp + (q) : 28 + warp)
      asm volatile("cp.async.bulk.wait_group.read 0;" ::: "memory");
      if (wg >= 2) { const uint32_t ts = lds32(MISC_T0); while ((int)(clock() - ts) < X_XS) {} }
      while ((int)(clock() - tpub) < X_YD) {}
      TS(5);
      v[0] = ldr128(ysrc + TL(0) * 32); v[1] = ldr128(ysrc + TL(1) * 32); v[2] = make_uint4(three, 0, 0, 0);
      if (X_REL == 1 || (X_REL == 2 && wg != 1)) mbar_wait(MB_REL);
#pragma unroll
      for (int i = 0; i < 6; i++) if (i < 4 || three) wr[i] = (gg & 2) ? ones : lds32(OFF_WR + TL(i >> 1) * 32 + (i & 1) * 16 + tt * 4);
      const uint32_t ha = keep(OFF_YT + (ln & 7) * YT_PITCH + (ln >> 4) * (8 * YT_PITCH + 64) + (ln & 8) * 2);
      const uint32_t pa = keep(OFF_PART + warp * 4 + ((gg & 2) * 8 + (gg & 4) * 2 + 2 * tt + (gg & 1)) * 80), pb = keep(OFF_PART + 2560 + warp * 4 + gg * 80);
      float dl[4] = {0.f, 0.f, 0.f, 0.f}, dh[4] = {0.f, 0.f, 0.f, 0.f};
      sw = __uint_as_float(lds32(MISC_SW));
#pragma unroll
      for (int q = 0; q < 3; q++) {
        if (q < 2 || three) {
          ldsm4t(tr_addr + TL(q) * 32, x[q][0], x[q][1], x[q][2], x[q][3]);
        }
      }
      mbar_wait(MB_SC);
#pragma unroll
      for (int q = 0; q < 3; q++) {
        asm volatile("ld.shared.u8 %0, [%1];" : "=r"(s[q]) : "r"((q < 2 ? sc_addr(warp) + q * 16 : sc_addr(16) + (warp & 3) * 16) + ch) : "memory");
        s[q] = keep(s[q] * 0x800080u);
      }
#define FIN(q) stsm4t(tr_addr + TL(q) * 32, bf_fma2(h2bf(v[q].x), s[q], x[q][0]), bf_fma2(h2bf(v[q].y), s[q], x[q][1]), bf_fma2(h2bf(v[q].z), s[q], x[q][2]), bf_fma2(h2bf(v[q].w), s[q], x[q][3]));
      SPIN_WHILE((v[0].x | v[1].x) & 1u, _Pragma("unroll") for (int q = 0; q < 3; q++) if (v[q].x & 1u) v[q] = ldr128(ysrc + TL(q) * 32));
      if (v[2].x & 1u) v[2] = ldr128(ysrc + TL(2) * 32);
#define STAT(q) { uint32_t r0, r1, r2, r3; ldsm4(ha + TL(q) * 32, r0, r1, r2, r3); \
        mma_bf16(dl, r0, wr[2 * q], r1, wr[2 * q + 1], r0, r1); mma_bf16(dh, r2, wr[2 * q], r3, wr[2 * q + 1], r2, r3); }
      FIN(0) FIN(1)
      __syncwarp();
      STAT(0) STAT(1)
      if (three) {
        SPIN_WHILE(v[2].x & 1u, if (v[2].x & 1u) v[2] = ldr128(ysrc + TL(2) * 32));
        FIN(2)
        __syncwarp();
        STAT(2)
      }
      if (gg & 1) { dl[0] = dl[1]; dl[2] = dl[3]; dh[0] = dh[1]; dh[2] = dh[3]; }
      sts32(pa, __float_as_uint((gg & 4) ? dh[2] : dl[2]));
      if (tt == (gg >> 1)) { sts32(pb, __float_as_uint(dl[0])); sts32(pb + 640, __float_as_uint(dh[0])); }
#undef STAT
#undef FIN
#undef TL
    }
    const uint32_t ra = keep(OFF_PART + (ln & 15) * 80 + (ln & 16) * 2);
    uint16_t* rp = (uint16_t*)p.s->R + c * 16 + (ln & 15);
    const uint2* rsrc = (const uint2*)p.s->R + td;
    asm volatile("" : "+l"(rp), "+l"(rsrc));
    uint2 rv = make_uint2(~0u, 0u);
    TS(28);
    bar_sync(0, 544);
    TS(6);
    if (warp == X_PW) {
      float z[3], rd;
#pragma unroll
      for (int k = 2; k >= 0; k--) {
        const uint4 a = lds128(ra + k * 1280), b = lds128(ra + k * 1280 + 16);
        z[k] = ((__uint_as_float(a.x) + __uint_as_float(a.y)) + (__uint_as_float(a.z) + __uint_as_float(a.w))) + ((__uint_as_float(b.x) + __uint_as_float(b.y)) + (__uint_as_float(b.z) + __uint_as_float(b.w)));
      }
#pragma unroll
      for (int k = 2; k >= 0; k--) z[k] += __shfl_xor_sync(0xffffffffu, z[k], 16);
      const LnC l = ln_consts(z[1], z[2], rd);
      const uint32_t b = pack_bf(0.f, fmaf(-bf_lo(l.m2), sw, z[0]) * rd);
      const uint32_t k16 = max(min((b ^ (((int)b >> 31) | 0x80000000u)) >> 16, 0xFFFEu), 1u);
      if (ln < 16) str16(rp, k16);
      sts64(OFF_RK + (ln & 15) * 8, __byte_perm(l.m2, l.rh2, 0x5410), __byte_perm(l.rl2, k16, 0x5410));
    }
    mbar_wait(MB_GU);
#define LD_HW { const uint4 a = lds128(row), b = lds128(row + 512); hw[8] = lds32(row + 1024 - ln * 12); \
      hw[0] = a.x; hw[1] = a.y; hw[2] = a.z; hw[3] = a.w; hw[4] = b.x; hw[5] = b.y; hw[6] = b.z; hw[7] = b.w; }
    if (!X_HW) LD_HW
    const uint32_t tr0 = clock();
    bar_sync(5, 512);
    TS(7);
    const uint2 lk = lds64(OFF_RK + warp * 8);
    LnC l2;
    l2.m2 = __byte_perm(lk.x, 0, 0x1010); l2.rh2 = __byte_perm(lk.x, 0, 0x3232); l2.rl2 = __byte_perm(lk.y, 0, 0x1010);
    const uint32_t key = (lk.y & 0xFFFF0000u) | (2047 - tok);
    uint32_t loc = ln < 16 ? (lds32(OFF_RK + 4 + ln * 8) & 0xFFFF0000u) | (2047 - c * 16 - ln) : 0u;
    if (X_HW) LD_HW
    int rank = __popc(__ballot_sync(0xffffffffu, loc > key));
#pragma unroll
    for (int i = 0; i < X_LA; i++) wr[i] = keep(ln_apply(hw[i], l2.m2, l2.rh2, l2.rl2));
#define OUT_ROW { uint32_t* o = p.out + tok * 288 + ln * 4; \
      *(uint4*)o = make_uint4(bf_add2(hw[0], wr[0]), bf_add2(hw[1], wr[1]), bf_add2(hw[2], wr[2]), bf_add2(hw[3], wr[3])); \
      *(uint4*)(o + 128) = make_uint4(bf_add2(hw[4], wr[4]), bf_add2(hw[5], wr[5]), bf_add2(hw[6], wr[6]), bf_add2(hw[7], wr[7])); \
      o[256 - ln * 3] = bf_add2(hw[8], wr[8]); }
#pragma unroll 1
    for (int base = 0; base < 8; base += 4) {
      uint32_t T[4];
#pragma unroll
      for (int j = 0; j < 4; j++) {
        const uint32_t mx = __reduce_max_sync(0xffffffffu, loc);
        if (loc == mx) loc = 0;
        T[j] = (td >> 2) == c ? ~0u : (td >> 2) < c ? (mx & 0xFFFF0000u) - 1u : mx | 0xFFFFu;
      }
      const uint32_t sh = keep(ln < 16 ? 0x4440u + (rank & 3) : 0x4344u), ca = keep(MISC_CNT + base * 16 + (ln & 15) * 4);
      TS(29);
      if (base == 0) {
        while ((int)(clock() - tr0) < X_RD) {}
        rv = ldr64(rsrc);
#pragma unroll
        for (int i = X_LA; i < 9; i++) wr[i] = keep(ln_apply(keep(hw[i]), l2.m2, l2.rh2, l2.rl2));
        if (rank >= X_OR) OUT_ROW
        if (warp < (five ? 12 : 15)) {
#pragma unroll
          for (int k = 0; k < X_WS; k++) ldsm4t(wabase + k * 16 * pitch, wa[k][0], wa[k][1], wa[k][2], wa[k][3]);
        }
      }
#pragma unroll 1
      for (int it = 0; it < SPIN_MAX; it++) {
        const uint32_t m = __vmaxu2(rv.x, rv.y);
        const bool bad = max(m, m << 16) >= 0xFFFF0000u && T[0] != ~0u;
        if (!__any_sync(0xffffffffu, bad)) break;
        if (bad) rv = ldr64(rsrc);
      }
      TS(16);
      uint32_t cnt = 0, cn2 = 0;
#pragma unroll
      for (int j = 0; j < 4; j++)
        asm("{ .reg .pred a, b, c, d; setp.gt.u32 a, %2, %6; setp.gt.u32 b, %3, %6; setp.gt.u32 c, %4, %6; setp.gt.u32 d, %5, %6; "
            "@a add.u32 %0, %0, %7; @b add.u32 %1, %1, %7; @c add.u32 %0, %0, %7; @d add.u32 %1, %1, %7; }"
            : "+r"(cnt), "+r"(cn2) : "r"(rv.x), "r"(rv.x << 16), "r"(rv.y), "r"(rv.y << 16), "r"(T[j]), "r"(1u << (8 * j)));
      sts32(MISC_CNT + base * 16 + warp * 4, __reduce_add_sync(0xffffffffu, cnt + cn2));
      bar_sync(0, 512);
      cnt = __reduce_add_sync(0xffffffffu, __byte_perm(lds32(ca), 0, sh));
      if ((rank & ~3) == base && rank + (int)(cnt & 0xFFFFu) < 8) {
        rank += cnt & 0xFFFFu;
        uint4* hs = p.s->HS + rank * 72 + ln;
        str128(hs, wr[0], wr[1], wr[2], wr[3]); str128(hs + 32, wr[4], wr[5], wr[6], wr[7]); str32((uint32_t*)(hs + 64) - ln * 3, wr[8]);
        str128(hs + 576, hw[0], hw[1], hw[2], hw[3]); str128(hs + 608, hw[4], hw[5], hw[6], hw[7]); str32((uint32_t*)(hs + 640) - ln * 3, hw[8]);
        if (ln == 0) str32(&p.s->HS[1152 + rank], key);
        rank = 16;
      }
      if (cnt >= (4u << 16)) break;
    }
    TS(8);
    tpub = clock();
    if (rank < X_OR) OUT_ROW
    if (warp < (five ? 12 : 15)) {
#pragma unroll
      for (int k = X_WS; k < 12; k++) ldsm4t(wabase + k * 16 * pitch, wa[k][0], wa[k][1], wa[k][2], wa[k][3]);
    }
  }
  uint32_t wd[10][4];
  const uint32_t xb = keep(OFF_XS + (ln & 7) * 1168 + (fk * 24 + (ln >> 3)) * 16);
  if (warp >= 7) {
    const uint32_t db = down_box(warp - 7, five) + (ln & 7) * 128;
    mbar_wait(MB_D);
#pragma unroll
    for (int j = 0; j < 4; j++) {
      const uint32_t a = db + (ln >> 4) * 1024 + (((2 * j + ((ln >> 3) & 1)) ^ (ln & 7)) << 4);
      ldsm4t(a, wd[j][0], wd[j][1], wd[j][2], wd[j][3]);
      ldsm4t(a + 2048, wd[4 + j][0], wd[4 + j][1], wd[4 + j][2], wd[4 + j][3]);
    }
#pragma unroll
    for (int j = 0; j < 2; j++) ldsm4t(db + 4096 + (((4 * j + (ln >> 3)) ^ (ln & 7)) << 4), wd[8 + j][0], wd[8 + j][1], wd[8 + j][2], wd[8 + j][3]);
  } else if (warp < 6) {
    const int r = td / 24;
    const uint4* src = &p.s->HS[td + r * 48];
    const uint32_t xs = keep(OFF_XS + (td + r * 49) * 16);
    uint4 a[3];
    uint32_t m = ~0u;
    while ((int)(clock() - tpub) < X_HD) {}
    TS(19);
    SPIN_WHILE(m == ~0u, if (m == ~0u) { a[0] = ldr128(src); a[1] = ldr128(src + 24); a[2] = ldr128(src + 48); } m = max(max(max(a[0].x, a[1].x), max(a[2].x, a[2].y)), max(a[2].z, a[2].w)));
#pragma unroll
    for (int q = 0; q < 3; q++) sts128(xs + q * 384, a[q].x, a[q].y, a[q].z, a[q].w);
  }
  bar_sync(0, 512);
  TS(9);

  if (warp < (five ? 12 : 15)) {
    float d0[4] = {0.f, 0.f, 0.f, 0.f}, d1[4] = {0.f, 0.f, 0.f, 0.f};
#pragma unroll
    for (int k = 0; k < 12; k += 2) {
      uint32_t b0, b1, b2, b3;
      ldsm4(xb + k * 32, b0, b1, b2, b3);
      mma_bf16(d0, wa[k][0], wa[k][1], wa[k][2], wa[k][3], b0, b1);
      mma_bf16(d1, wa[k + 1][0], wa[k + 1][1], wa[k + 1][2], wa[k + 1][3], b2, b3);
    }
    sts128(OFF_RED + td * 16, __float_as_uint(d0[0] + d1[0]), __float_as_uint(d0[1] + d1[1]), __float_as_uint(d0[2] + d1[2]), __float_as_uint(d0[3] + d1[3]));
  }
  TS(26);
  if (warp < 5) {
    const uint32_t rb = OFF_RED + warp * 1536 + ln * 16;
    bar_sync(9, 512);
    const uint4 pa = lds128(rb), pb = lds128(rb + 512), pc = lds128(rb + 1024);
    const float ga = bfr(__uint_as_float(pa.x) + __uint_as_float(pb.x) + __uint_as_float(pc.x));
    const float gb = bfr(__uint_as_float(pa.y) + __uint_as_float(pb.y) + __uint_as_float(pc.y));
    const uint32_t uu = pack_bf(__uint_as_float(pa.z) + __uint_as_float(pb.z) + __uint_as_float(pc.z), __uint_as_float(pa.w) + __uint_as_float(pb.w) + __uint_as_float(pc.w));
    float ra, rb2;
    asm("rcp.approx.ftz.f32 %0, %1;" : "=f"(ra) : "f"(1.f + ex2(ga * -1.4426950408889634f)));
    asm("rcp.approx.ftz.f32 %0, %1;" : "=f"(rb2) : "f"(1.f + ex2(gb * -1.4426950408889634f)));
    const uint32_t act = bf_mul2(pack_bf(ga * ra, gb * rb2), uu);
    sts32(OFF_ACT + td * 4, act);
  } else bar_arrive(9, 512);
  uint4* dst = &p.s->X[c * DM * 2 + (warp - 7) * 64 + tt * 8 + gg];
  asm volatile("" : "+l"(dst));
  bar_sync(8, 512);
  tpub = clock();
  if (warp >= 7) {
    uint32_t b0, b1, b2, b3, b4;
    ldsm4t(OFF_ACT + ln * 16, b0, b1, b2, b3);
    asm volatile("ldmatrix.sync.aligned.m8n8.x1.trans.shared.b16 {%0}, [%1];" : "=r"(b4) : "r"(OFF_ACT + 512 + ln * 16) : "memory");
    float y[4][4];
#pragma unroll
    for (int j = 0; j < 4; j++) {
      y[j][0] = y[j][1] = y[j][2] = y[j][3] = 0.f;
      mma_bf16(y[j], wd[j][0], wd[j][1], wd[j][2], wd[j][3], b0, b1);
    }
#pragma unroll
    for (int j = 0; j < 4; j++) mma_bf16(y[j], wd[4 + j][0], wd[4 + j][1], wd[4 + j][2], wd[4 + j][3], b2, b3);
    if (!five) {
#pragma unroll
      for (int j = 0; j < 4; j++) mma_bf16_k8(y[j], wd[8 + (j >> 1)][2 * (j & 1)], wd[8 + (j >> 1)][2 * (j & 1) + 1], b4);
    }
    str128(dst, (pack_bf(y[0][0], y[0][1]) & ~1u) | 0x10000u, pack_bf(y[0][2], y[0][3]), pack_bf(y[1][0], y[1][1]), pack_bf(y[1][2], y[1][3]));
    str128(dst + 32, (pack_bf(y[2][0], y[2][1]) & ~1u) | 0x10000u, pack_bf(y[2][2], y[2][3]), pack_bf(y[3][0], y[3][1]), pack_bf(y[3][2], y[3][3]));
  }
  TS(10);

  if (c < 72) {
    const uint4* src = &p.s->X[(warp * 4 + tt) * (DM * 2) + c * 8 + gg];
    const int slot = (c & 3) * 2 + (ln >> 4), dw = (c >> 2) * 16 + (ln & 15);
    uint32_t hv = 0, kv = 0, res = 0, rs2 = 0;
    uint32_t* o = p.out;
    if (warp == 0) {
      hv = ~0u;
      SPIN_WHILE(max(hv, kv) == ~0u, hv = ldr32((const uint32_t*)p.s->HS + 2304 + slot * 288 + dw); kv = ldr32(&p.s->HS[1152 + slot]));
      const float r = bf_hi(kv ^ (((int)~kv >> 31) | 0x80000000u));
      float rs;
      asm("rcp.approx.ftz.f32 %0, %1;" : "=f"(rs) : "f"(1.f + ex2(r * -1.4426950408889634f)));
      rs2 = keep(pack_bf(rs, rs));
      res = lds32(OFF_XS + slot * 1168 + dw * 4);
      o += (2047 - (int)(kv & 2047u)) * 288 + dw;
      asm volatile("" : "+l"(o));
    }
    const uint32_t sel = (gg & 1) ? 0x3F800000u : 0x00003F80u;
    const uint32_t q0 = keep((gg >> 1) == 0 ? sel : 0u), q1 = keep((gg >> 1) == 1 ? sel : 0u), q2 = keep((gg >> 1) == 2 ? sel : 0u), q3 = keep((gg >> 1) == 3 ? sel : 0u);
    const uint32_t fa = keep(OFF_FIN + warp * 256 + (gg & 1) * 128 + (gg >> 1) * 32 + tt * 8), fb = keep(OFF_FIN + ln * 8);
    uint4 a0 = make_uint4(0, 0, 0, 0), a1 = a0;
    while ((int)(clock() - tpub) < X_PD) {}
    SPIN_WHILE(!(a0.x & a1.x & 0x10000u), if (!(a0.x & 0x10000u)) a0 = ldr128(src); if (!(a1.x & 0x10000u)) a1 = ldr128(src + 64 * DM * 2));
    float d[4] = {0.f, 0.f, 0.f, 0.f}, e[4] = {0.f, 0.f, 0.f, 0.f};
    mma_bf16(d, q0, q2, q1, q3, a0.x, a0.y); mma_bf16(e, q0, q2, q1, q3, a0.z, a0.w);
    mma_bf16(d, q0, q2, q1, q3, a1.x, a1.y); mma_bf16(e, q0, q2, q1, q3, a1.z, a1.w);
    sts64(fa, __float_as_uint(d[0] + e[2]), __float_as_uint(d[1] + e[3]));
    TS(11);
    if (warp == 0) {
      bar_sync(0, 512);
      float2 s[16];
#pragma unroll
      for (int i = 0; i < 16; i++) { const uint2 q = lds64(fb + i * 256); s[i] = make_float2(__uint_as_float(q.x), __uint_as_float(q.y)); }
#pragma unroll
      for (int k = 1; k < 16; k *= 2)
#pragma unroll
        for (int i = 0; i < 16; i += 2 * k) { s[i].x += s[i + k].x; s[i].y += s[i + k].y; }
      *o = bf_add2(hv, bf_add2(res, bf_mul2(pack_bf(s[0].x, s[0].y), rs2)));
    } else bar_arrive(0, 512);
  }
  TS(12);
  TS_DUMP();
}

typedef CUresult (*EncodeFn)(CUtensorMap*, CUtensorMapDataType, cuuint32_t, void*, const cuuint64_t*, const cuuint64_t*, const cuuint32_t*,
                             const cuuint32_t*, CUtensorMapInterleave, CUtensorMapSwizzle, CUtensorMapL2promotion, CUtensorMapFloatOOBfill);

}

extern "C" void kernel_launch(void* const* d_in, const int* in_sizes, int n_in, void* d_out, int out_size) {
  (void)in_sizes; (void)n_in; (void)out_size;
  static EncodeFn enc = nullptr;
  static Scratch* scratch = nullptr;
  if (!enc) {
    void* fn = nullptr;
    cudaDriverEntryPointQueryResult qr;
    cudaGetDriverEntryPoint("cuTensorMapEncodeTiled", &fn, cudaEnableDefault, &qr);
    enc = (EncodeFn)fn;
    cudaGetSymbolAddress((void**)&scratch, g_S);
    cudaFuncSetAttribute(fused_kernel<false>, cudaFuncAttributeMaxDynamicSharedMemorySize, SMEM_BYTES);
    cudaFuncSetAttribute(fused_kernel<true>, cudaFuncAttributeMaxDynamicSharedMemorySize, SMEM_BYTES);
  }
  TMaps tm;
  for (int i = 0; i < 6; i++) {
    const bool dn = i % 3 == 2;
    const cuuint32_t w = i < 3 ? 40 : 32;
    cuuint64_t gd[3] = {(cuuint64_t)(dn ? 64 : FF), (cuuint64_t)(dn ? FF : DM), 9};
    cuuint64_t gs[2] = {(cuuint64_t)(dn ? DM * 2 : FF * 2), 128};
    cuuint32_t bx[3] = {dn ? 64 : w, dn ? w : 96, i < 3 ? 2u : 3u};
    cuuint32_t es[3] = {1, 1, 1};
    enc(&tm.m[i], CU_TENSOR_MAP_DATA_TYPE_BFLOAT16, dn ? 3 : 2, d_in[11 + i % 3], gd, gs, bx, es, CU_TENSOR_MAP_INTERLEAVE_NONE,
        dn ? CU_TENSOR_MAP_SWIZZLE_128B : i < 3 ? CU_TENSOR_MAP_SWIZZLE_NONE : CU_TENSOR_MAP_SWIZZLE_64B,
        (CUtensorMapL2promotion)X_PROMO, CU_TENSOR_MAP_FLOAT_OOB_FILL_NONE);
  }
  for (int i = 6; i < 10; i++) {
    cuuint64_t gd[3] = {i < 8 ? 32u : 16u, i < 8 ? DM / 2u : DM, NCTA};
    cuuint64_t gs[2] = {i < 8 ? 64u : 32u, DM * 32};
    cuuint32_t bx[3] = {32, 1, (i & 1) ? 128u : 136u};
    cuuint32_t es[3] = {1, 1, 1};
    enc(&tm.m[i], CU_TENSOR_MAP_DATA_TYPE_FLOAT16, 3, scratch->X, gd, gs, bx, es, CU_TENSOR_MAP_INTERLEAVE_NONE, CU_TENSOR_MAP_SWIZZLE_64B,
        CU_TENSOR_MAP_L2_PROMOTION_NONE, CU_TENSOR_MAP_FLOAT_OOB_FILL_NONE);
  }
  Params p;
  p.x = (const unsigned char*)d_in[0];
  bool far = false;
  for (int i = 0; i < 7; i++) {
    p.far[i] = (const unsigned char*)d_in[1 + i];
    const long long d = (long long)((intptr_t)d_in[1 + i] - (intptr_t)d_in[0]);
    p.off[i] = (int)(d / 16);
    if ((long long)p.off[i] * 16 != d) far = true;
  }
  p.dskip = (const uint16_t*)d_in[8];
  p.w_r = (const uint32_t*)d_in[10];
  for (int f = 0; f < 2; f++) {
    static const int kind[17] = {0, 0, 0, 0, 2, 2, 0, 0, 1, 1, 1, 1, 1, 1, 2, 2, 2};
    static const int idx[2][17] = {{2, 3, 4, 5, 6, 8, 0, 1, 0, 1, 2, 3, 4, 5, 0, 2, 4}, {2, 3, 4, 5, 0, -1, 0, 1, 0, 1, 2, 3, 4, 5, 3, -1, 6}};
    static const int blk[2][17] = {{-1, -1, -1, -1, 0, -1, 4, -1, 1, -1, 2, -1, 3, -1, 16, -1, -1}, {-1, -1, -1, -1, 1, -1, 4, -1, -1, -1, 2, -1, 3, -1, 16, -1, -1}};
    const int pitch = f ? 64 : 80;
    for (int u = 0; u < 17; u++) {
      const int s = idx[f][u];
      const uint32_t dst = kind[u] == 0 ? OFF_G + s * 96 * pitch : kind[u] == 2 ? down_box(s, f) : OFF_W + W_BYTES + (s >> 1) * W_BYTES + (s & 1) * 96 * pitch;
      const uint32_t mb = u >= 14 ? (u >= X_HU ? MB_H - OFF_MISC : X_HB) : blk[f][u] >= 0 ? MB_KF - OFF_MISC + blk[f][u] * 8 : 0;
      p.sched[f][u] = s < 0 ? 3u : kind[u] | s << 2 | mb << 6 | dst << 14;
    }
  }
  p.out = (uint32_t*)d_out;
  p.zero = 0;
  p.ts = nullptr;
  p.s = scratch;
  if (far) { fused_kernel<true><<<NCTA, NT, SMEM_BYTES, cudaStreamPerThread>>>(p, tm); return; }
  fused_kernel<false><<<NCTA, NT, SMEM_BYTES, cudaStreamPerThread>>>(p, tm);
}
```

```cpp
#include <cuda_runtime.h>
#include <cuda.h>
#include <cuda_bf16.h>
#include <cuda_fp16.h>
#include <stdint.h>
#include <stddef.h>

namespace {

constexpr int NCTA = 128;
constexpr int NT = 640;
constexpr int DM = 576;
constexpr int FF = 4608;
constexpr int SPIN_MAX = 1 << 20;

struct Scratch {
  uint4 X[NCTA * DM * 2];
  uint4 KX[64 * 128];
  uint4 HS[1152 + 8];
  uint4 R[256];
  uint4 SC[256];
  uint32_t FLAG[NCTA * 8];
};
__device__ Scratch g_S;

#define CLKS(i)
#define TS(i)
#define TSX(i)
#define TS_DUMP()

constexpr int SB = 1024;
constexpr int BOX = 15360;
constexpr int OFF_G = SB;
constexpr int OFF_W = OFF_G + 3 * BOX;
constexpr int W_KT = 26624;
constexpr int W_L3 = W_KT + 4416;
constexpr int W_CW = W_L3 + 4096;
constexpr int W_MISC = W_CW + 640;
constexpr int W_BYTES = 35840;
constexpr int TILE = 10240;
constexpr int OFF_T = OFF_W + 4 * W_BYTES;
constexpr int ALT = TILE - W_KT;
static_assert(W_MISC + 32 <= W_BYTES && OFF_W % 1024 == 0 && W_BYTES % 1024 == 0 && W_BYTES + ALT <= 20480, "wg block");
constexpr int YT_PITCH = 1184;
constexpr int OFF_YT = OFF_T + 2 * TILE;
constexpr int OFF_WR = OFF_YT + 16 * YT_PITCH + 64;
constexpr int OFF_MISC = OFF_WR + 2304;
constexpr int SMEM_BYTES = OFF_MISC + 1024 - SB;
static_assert(OFF_YT % 16 == 0 && OFF_MISC % 16 == 0, "align");
static_assert(SMEM_BYTES <= 232448, "smem");
constexpr int MB_GU = OFF_MISC;
constexpr int MB_D = OFF_MISC + 8;
constexpr int MB_KF = OFF_MISC + 16;
constexpr int MB_GF = OFF_MISC + 48;
constexpr int MB_SC = OFF_MISC + 56;
constexpr int MB_UL = OFF_MISC + 64;
constexpr int MB_REL = OFF_MISC + 104;
constexpr int MB_GO = OFF_MISC + 112;
constexpr int MB_H = MB_KF + 128;
constexpr int MISC_EPOCH = OFF_MISC + 152;
constexpr int MISC_SW = OFF_MISC + 156;
constexpr int MISC_RT = OFF_MISC + 160;
constexpr int MISC_T0 = OFF_MISC + 296;
constexpr int MISC_EM = OFF_MISC + 288;
constexpr int OFF_PART = OFF_W + 20480;
constexpr int OFF_RK = OFF_PART + 3840;
constexpr int MISC_LN1 = OFF_MISC + 192;
constexpr int OFF_XS = OFF_T;
constexpr int OFF_RED = OFF_T + TILE;
constexpr int OFF_FIN = OFF_W + 3 * W_BYTES + W_KT;
constexpr int OFF_ACT = OFF_FIN + 4096;
constexpr int MISC_CNT = OFF_ACT + 1024;

__device__ __forceinline__ uint32_t smem_u32(const void* p) { return (uint32_t)__cvta_generic_to_shared(p); }
__device__ __forceinline__ uint32_t lds32(uint32_t a) { uint32_t v; asm volatile("ld.shared.b32 %0, [%1];" : "=r"(v) : "r"(a) : "memory"); return v; }
__device__ __forceinline__ uint32_t lds16(uint32_t a) { uint16_t v; asm volatile("ld.shared.u16 %0, [%1];" : "=h"(v) : "r"(a) : "memory"); return v; }
__device__ __forceinline__ uint2 lds64(uint32_t a) { uint2 v; asm volatile("ld.shared.v2.b32 {%0,%1}, [%2];" : "=r"(v.x), "=r"(v.y) : "r"(a) : "memory"); return v; }
__device__ __forceinline__ uint4 lds128(uint32_t a) { uint4 v; asm volatile("ld.shared.v4.b32 {%0,%1,%2,%3}, [%4];" : "=r"(v.x), "=r"(v.y), "=r"(v.z), "=r"(v.w) : "r"(a) : "memory"); return v; }
__device__ __forceinline__ void sts16(uint32_t a, uint32_t v) { asm volatile("st.shared.u16 [%0], %1;" :: "r"(a), "h"((uint16_t)v) : "memory"); }
__device__ __forceinline__ void sts32(uint32_t a, uint32_t v) { asm volatile("st.shared.b32 [%0], %1;" :: "r"(a), "r"(v) : "memory"); }
__device__ __forceinline__ void sts64(uint32_t a, uint32_t x, uint32_t y) { asm volatile("st.shared.v2.b32 [%0], {%1,%2};" :: "r"(a), "r"(x), "r"(y) : "memory"); }
__device__ __forceinline__ void sts128(uint32_t a, uint32_t x, uint32_t y, uint32_t z, uint32_t w) { asm volatile("st.shared.v4.b32 [%0], {%1,%2,%3,%4};" :: "r"(a), "r"(x), "r"(y), "r"(z), "r"(w) : "memory"); }
__device__ __forceinline__ void ldsm4(uint32_t a, uint32_t& r0, uint32_t& r1, uint32_t& r2, uint32_t& r3) {
  asm volatile("ldmatrix.sync.aligned.m8n8.x4.shared.b16 {%0,%1,%2,%3}, [%4];" : "=r"(r0), "=r"(r1), "=r"(r2), "=r"(r3) : "r"(a) : "memory");
}
__device__ __forceinline__ void ldsm2(uint32_t a, uint32_t& r0, uint32_t& r1) {
  asm volatile("ldmatrix.sync.aligned.m8n8.x2.shared.b16 {%0,%1}, [%2];" : "=r"(r0), "=r"(r1) : "r"(a) : "memory");
}
__device__ __forceinline__ void ldsm4t(uint32_t a, uint32_t& r0, uint32_t& r1, uint32_t& r2, uint32_t& r3) {
  asm volatile("ldmatrix.sync.aligned.m8n8.x4.trans.shared.b16 {%0,%1,%2,%3}, [%4];" : "=r"(r0), "=r"(r1), "=r"(r2), "=r"(r3) : "r"(a) : "memory");
}
__device__ __forceinline__ void stsm4t(uint32_t a, uint32_t r0, uint32_t r1, uint32_t r2, uint32_t r3) {
  asm volatile("stmatrix.sync.aligned.m8n8.x4.trans.shared.b16 [%0], {%1,%2,%3,%4};" :: "r"(a), "r"(r0), "r"(r1), "r"(r2), "r"(r3) : "memory");
}
__device__ __forceinline__ uint4 ldr128(const void* p) {
  unsigned long long lo, hi;
  asm volatile("{ .reg .b128 t; ld.relaxed.gpu.global.b128 t, [%2]; mov.b128 {%0, %1}, t; }" : "=l"(lo), "=l"(hi) : "l"(p) : "memory");
  return make_uint4((uint32_t)lo, (uint32_t)(lo >> 32), (uint32_t)hi, (uint32_t)(hi >> 32));
}
__device__ __forceinline__ void str128(void* p, uint32_t x, uint32_t y, uint32_t z, uint32_t w) {
  asm volatile("{ .reg .b128 t; .reg .b64 lo, hi; mov.b64 lo, {%1,%2}; mov.b64 hi, {%3,%4}; mov.b128 t, {lo, hi}; st.relaxed.gpu.global.b128 [%0], t; }"
               :: "l"(p), "r"(x), "r"(y), "r"(z), "r"(w) : "memory");
}
__device__ __forceinline__ void str64(void* p, uint32_t x, uint32_t y) {
  asm volatile("{ .reg .b64 t; mov.b64 t, {%1,%2}; st.relaxed.gpu.global.b64 [%0], t; }" :: "l"(p), "r"(x), "r"(y) : "memory");
}
__device__ __forceinline__ uint32_t ldr32(const void* p) { uint32_t v; asm volatile("ld.relaxed.gpu.global.b32 %0, [%1];" : "=r"(v) : "l"(p) : "memory"); return v; }
__device__ __forceinline__ void str32(void* p, uint32_t v) { asm volatile("st.relaxed.gpu.global.b32 [%0], %1;" :: "l"(p), "r"(v) : "memory"); }
__device__ __forceinline__ void str16(void* p, uint32_t v) { asm volatile("st.relaxed.gpu.global.u16 [%0], %1;" :: "l"(p), "h"((uint16_t)v) : "memory"); }
__device__ __forceinline__ void fence_gpu() { asm volatile("fence.acq_rel.gpu;" ::: "memory"); }
__device__ __forceinline__ void bar_sync(int id, int n) { asm volatile("bar.sync %0, %1;" :: "r"(id), "r"(n) : "memory"); }
__device__ __forceinline__ void bar_arrive(int id, int n) { asm volatile("bar.arrive %0, %1;" :: "r"(id), "r"(n) : "memory"); }

__device__ __forceinline__ float bf_lo(uint32_t w) { return __uint_as_float(w << 16); }
__device__ __forceinline__ float bf_hi(uint32_t w) { return __uint_as_float(w & 0xFFFF0000u); }
__device__ __forceinline__ uint32_t pack_bf(float lo, float hi) { uint32_t r; asm("cvt.rn.bf16x2.f32 %0, %1, %2;" : "=r"(r) : "f"(hi), "f"(lo)); return r; }
__device__ __forceinline__ uint32_t pack_h(float lo, float hi) { uint32_t r; asm("cvt.rn.f16x2.f32 %0, %1, %2;" : "=r"(r) : "f"(hi), "f"(lo)); return r; }
__device__ __forceinline__ uint32_t pack_hv(float lo, float hi) { uint32_t r; asm volatile("cvt.rn.f16x2.f32 %0, %1, %2;" : "=r"(r) : "f"(hi), "f"(lo) : "memory"); return r; }
__device__ __forceinline__ float bfr(float x) { return bf_lo(pack_bf(x, 0.f)); }
__device__ __forceinline__ uint32_t bf_sub2(uint32_t a, uint32_t b) { __nv_bfloat162 r = __hsub2(*(__nv_bfloat162*)&a, *(__nv_bfloat162*)&b); return *(uint32_t*)&r; }
__device__ __forceinline__ uint32_t bf_add2(uint32_t a, uint32_t b) { __nv_bfloat162 r = __hadd2(*(__nv_bfloat162*)&a, *(__nv_bfloat162*)&b); return *(uint32_t*)&r; }
__device__ __forceinline__ uint32_t bf_mul2(uint32_t a, uint32_t b) { __nv_bfloat162 r = __hmul2(*(__nv_bfloat162*)&a, *(__nv_bfloat162*)&b); return *(uint32_t*)&r; }
__device__ __forceinline__ float2 h2f(uint32_t w) { return __half22float2(*(__half2*)&w); }
__device__ __forceinline__ float ex2(float x) { float r; asm("ex2.approx.ftz.f32 %0, %1;" : "=f"(r) : "f"(x)); return r; }
__device__ __forceinline__ float warp_sum(float v) {
#pragma unroll
  for (int o = 16; o > 0; o >>= 1) v += __shfl_xor_sync(0xffffffffu, v, o);
  return v;
}
__device__ __forceinline__ void mma_f16_f32(float* d, uint32_t a0, uint32_t a1, uint32_t a2, uint32_t a3, uint32_t b0, uint32_t b1) {
  asm volatile("mma.sync.aligned.m16n8k16.row.col.f32.f16.f16.f32 {%0,%1,%2,%3}, {%4,%5,%6,%7}, {%8,%9}, {%0,%1,%2,%3};"
               : "+f"(d[0]), "+f"(d[1]), "+f"(d[2]), "+f"(d[3]) : "r"(a0), "r"(a1), "r"(a2), "r"(a3), "r"(b0), "r"(b1));
}
__device__ __forceinline__ void mma_f16_f16(uint32_t& d0, uint32_t& d1, uint32_t a0, uint32_t a1, uint32_t a2, uint32_t a3, uint32_t b0, uint32_t b1) {
  asm volatile("mma.sync.aligned.m16n8k16.row.col.f16.f16.f16.f16 {%0,%1}, {%2,%3,%4,%5}, {%6,%7}, {%0,%1};"
               : "+r"(d0), "+r"(d1) : "r"(a0), "r"(a1), "r"(a2), "r"(a3), "r"(b0), "r"(b1));
}
__device__ __forceinline__ void mma_bf16(float* d, uint32_t a0, uint32_t a1, uint32_t a2, uint32_t a3, uint32_t b0, uint32_t b1) {
  asm volatile("mma.sync.aligned.m16n8k16.row.col.f32.bf16.bf16.f32 {%0,%1,%2,%3}, {%4,%5,%6,%7}, {%8,%9}, {%0,%1,%2,%3};"
               : "+f"(d[0]), "+f"(d[1]), "+f"(d[2]), "+f"(d[3]) : "r"(a0), "r"(a1), "r"(a2), "r"(a3), "r"(b0), "r"(b1));
}
__device__ __forceinline__ void mma_bf16_k8(float* d, uint32_t a0, uint32_t a1, uint32_t b0) {
  asm volatile("mma.sync.aligned.m16n8k8.row.col.f32.bf16.bf16.f32 {%0,%1,%2,%3}, {%4,%5}, {%6}, {%0,%1,%2,%3};"
               : "+f"(d[0]), "+f"(d[1]), "+f"(d[2]), "+f"(d[3]) : "r"(a0), "r"(a1), "r"(b0));
}

__device__ __forceinline__ void wg_fence() { asm volatile("wgmma.fence.sync.aligned;" ::: "memory"); }
__device__ __forceinline__ void wg_commit() { asm volatile("wgmma.commit_group.sync.aligned;" ::: "memory"); }
template <int N> __device__ __forceinline__ void wg_wait() { asm volatile("wgmma.wait_group.sync.aligned %0;" :: "n"(N) : "memory"); }
template <int TB> __device__ __forceinline__ void wgmma32(float* d, const uint32_t* a, uint32_t dlo, uint32_t dhi) {
  asm volatile("{ .reg .b64 dd; mov.b64 dd, {%20, %21}; wgmma.mma_async.sync.aligned.m64n32k16.f32.f16.f16 "
               "{%0,%1,%2,%3,%4,%5,%6,%7,%8,%9,%10,%11,%12,%13,%14,%15}, {%16,%17,%18,%19}, dd, 1, 1, 1, %22; }"
               : "+f"(d[0]), "+f"(d[1]), "+f"(d[2]), "+f"(d[3]), "+f"(d[4]), "+f"(d[5]), "+f"(d[6]), "+f"(d[7]), "+f"(d[8]), "+f"(d[9]), "+f"(d[10]), "+f"(d[11]), "+f"(d[12]), "+f"(d[13]), "+f"(d[14]), "+f"(d[15])
               : "r"(a[0]), "r"(a[1]), "r"(a[2]), "r"(a[3]), "r"(dlo), "r"(dhi), "n"(TB));
}
template <int TB> __device__ __forceinline__ void wgmma64(float* d, const uint32_t* a, uint32_t dlo, uint32_t dhi) {
  asm volatile("{ .reg .b64 dd; mov.b64 dd, {%36, %37}; wgmma.mma_async.sync.aligned.m64n64k16.f32.f16.f16 "
               "{%0,%1,%2,%3,%4,%5,%6,%7,%8,%9,%10,%11,%12,%13,%14,%15,%16,%17,%18,%19,%20,%21,%22,%23,%24,%25,%26,%27,%28,%29,%30,%31}, {%32,%33,%34,%35}, dd, 1, 1, 1, %38; }"
               : "+f"(d[0]), "+f"(d[1]), "+f"(d[2]), "+f"(d[3]), "+f"(d[4]), "+f"(d[5]), "+f"(d[6]), "+f"(d[7]), "+f"(d[8]), "+f"(d[9]), "+f"(d[10]), "+f"(d[11]), "+f"(d[12]), "+f"(d[13]), "+f"(d[14]), "+f"(d[15]), "+f"(d[16]), "+f"(d[17]), "+f"(d[18]), "+f"(d[19]), "+f"(d[20]), "+f"(d[21]), "+f"(d[22]), "+f"(d[23]), "+f"(d[24]), "+f"(d[25]), "+f"(d[26]), "+f"(d[27]), "+f"(d[28]), "+f"(d[29]), "+f"(d[30]), "+f"(d[31])
               : "r"(a[0]), "r"(a[1]), "r"(a[2]), "r"(a[3]), "r"(dlo), "r"(dhi), "n"(TB));
}
template <int TB> __device__ __forceinline__ void wgmma64_init(float* d, const uint32_t* a, uint32_t dlo, uint32_t dhi) {
  asm volatile("{ .reg .b64 dd; mov.b64 dd, {%36, %37}; wgmma.mma_async.sync.aligned.m64n64k16.f32.f16.f16 "
               "{%0,%1,%2,%3,%4,%5,%6,%7,%8,%9,%10,%11,%12,%13,%14,%15,%16,%17,%18,%19,%20,%21,%22,%23,%24,%25,%26,%27,%28,%29,%30,%31}, {%32,%33,%34,%35}, dd, 0, 1, 1, %38; }"
               : "=f"(d[0]), "=f"(d[1]), "=f"(d[2]), "=f"(d[3]), "=f"(d[4]), "=f"(d[5]), "=f"(d[6]), "=f"(d[7]), "=f"(d[8]), "=f"(d[9]), "=f"(d[10]), "=f"(d[11]), "=f"(d[12]), "=f"(d[13]), "=f"(d[14]), "=f"(d[15]), "=f"(d[16]), "=f"(d[17]), "=f"(d[18]), "=f"(d[19]), "=f"(d[20]), "=f"(d[21]), "=f"(d[22]), "=f"(d[23]), "=f"(d[24]), "=f"(d[25]), "=f"(d[26]), "=f"(d[27]), "=f"(d[28]), "=f"(d[29]), "=f"(d[30]), "=f"(d[31])
               : "r"(a[0]), "r"(a[1]), "r"(a[2]), "r"(a[3]), "r"(dlo), "r"(dhi), "n"(TB));
}
template <int TB> __device__ __forceinline__ void wgmma32_init(float* d, const uint32_t* a, uint32_t dlo, uint32_t dhi) {
  asm volatile("{ .reg .b64 dd; mov.b64 dd, {%20, %21}; wgmma.mma_async.sync.aligned.m64n32k16.f32.f16.f16 "
               "{%0,%1,%2,%3,%4,%5,%6,%7,%8,%9,%10,%11,%12,%13,%14,%15}, {%16,%17,%18,%19}, dd, 0, 1, 1, %22; }"
               : "=f"(d[0]), "=f"(d[1]), "=f"(d[2]), "=f"(d[3]), "=f"(d[4]), "=f"(d[5]), "=f"(d[6]), "=f"(d[7]), "=f"(d[8]), "=f"(d[9]), "=f"(d[10]), "=f"(d[11]), "=f"(d[12]), "=f"(d[13]), "=f"(d[14]), "=f"(d[15])
               : "r"(a[0]), "r"(a[1]), "r"(a[2]), "r"(a[3]), "r"(dlo), "r"(dhi), "n"(TB));
}
__device__ __forceinline__ void wgmma64h(uint32_t* d, uint32_t a0, uint32_t a1, uint32_t a2, uint32_t a3, uint32_t dlo, uint32_t dhi) {
  asm volatile("{ .reg .b64 dd; mov.b64 dd, {%20, %21}; wgmma.mma_async.sync.aligned.m64n64k16.f16.f16.f16 "
               "{%0,%1,%2,%3,%4,%5,%6,%7,%8,%9,%10,%11,%12,%13,%14,%15}, {%16,%17,%18,%19}, dd, 1, 1, 1, 0; }"
               : "+r"(d[0]), "+r"(d[1]), "+r"(d[2]), "+r"(d[3]), "+r"(d[4]), "+r"(d[5]), "+r"(d[6]), "+r"(d[7]), "+r"(d[8]), "+r"(d[9]), "+r"(d[10]), "+r"(d[11]), "+r"(d[12]), "+r"(d[13]), "+r"(d[14]), "+r"(d[15])
               : "r"(a0), "r"(a1), "r"(a2), "r"(a3), "r"(dlo), "r"(dhi));
}
__device__ __forceinline__ void wgmma64h_init(uint32_t* d, uint32_t a0, uint32_t a1, uint32_t a2, uint32_t a3, uint32_t dlo, uint32_t dhi) {
  asm volatile("{ .reg .b64 dd; mov.b64 dd, {%20, %21}; wgmma.mma_async.sync.aligned.m64n64k16.f16.f16.f16 "
               "{%0,%1,%2,%3,%4,%5,%6,%7,%8,%9,%10,%11,%12,%13,%14,%15}, {%16,%17,%18,%19}, dd, 0, 1, 1, 0; }"
               : "=r"(d[0]), "=r"(d[1]), "=r"(d[2]), "=r"(d[3]), "=r"(d[4]), "=r"(d[5]), "=r"(d[6]), "=r"(d[7]), "=r"(d[8]), "=r"(d[9]), "=r"(d[10]), "=r"(d[11]), "=r"(d[12]), "=r"(d[13]), "=r"(d[14]), "=r"(d[15])
               : "r"(a0), "r"(a1), "r"(a2), "r"(a3), "r"(dlo), "r"(dhi));
}
__device__ __forceinline__ void wgmma40_ss(float* d, uint32_t alo, uint32_t blo, uint32_t hi) {
  asm volatile("{ .reg .b64 da, db; mov.b64 da, {%20, %22}; mov.b64 db, {%21, %22}; "
               "wgmma.mma_async.sync.aligned.m64n40k16.f32.f16.f16 {%0,%1,%2,%3,%4,%5,%6,%7,%8,%9,%10,%11,%12,%13,%14,%15,%16,%17,%18,%19}, da, db, 1, 1, 1, 1, 1; }"
               : "+f"(d[0]), "+f"(d[1]), "+f"(d[2]), "+f"(d[3]), "+f"(d[4]), "+f"(d[5]), "+f"(d[6]), "+f"(d[7]), "+f"(d[8]), "+f"(d[9]), "+f"(d[10]), "+f"(d[11]), "+f"(d[12]), "+f"(d[13]), "+f"(d[14]), "+f"(d[15]), "+f"(d[16]), "+f"(d[17]), "+f"(d[18]), "+f"(d[19])
               : "r"(alo), "r"(blo), "r"(hi));
}
__device__ __forceinline__ void wgmma40_ss_init(float* d, uint32_t alo, uint32_t blo, uint32_t hi) {
  asm volatile("{ .reg .b64 da, db; mov.b64 da, {%20, %22}; mov.b64 db, {%21, %22}; "
               "wgmma.mma_async.sync.aligned.m64n40k16.f32.f16.f16 {%0,%1,%2,%3,%4,%5,%6,%7,%8,%9,%10,%11,%12,%13,%14,%15,%16,%17,%18,%19}, da, db, 0, 1, 1, 1, 1; }"
               : "=f"(d[0]), "=f"(d[1]), "=f"(d[2]), "=f"(d[3]), "=f"(d[4]), "=f"(d[5]), "=f"(d[6]), "=f"(d[7]), "=f"(d[8]), "=f"(d[9]), "=f"(d[10]), "=f"(d[11]), "=f"(d[12]), "=f"(d[13]), "=f"(d[14]), "=f"(d[15]), "=f"(d[16]), "=f"(d[17]), "=f"(d[18]), "=f"(d[19])
               : "r"(alo), "r"(blo), "r"(hi));
}
__device__ __forceinline__ float vzero() { float v; asm volatile("mov.b32 %0, 0;" : "=f"(v)); return v; }
__device__ __forceinline__ void tma_box(uint32_t dst, const CUtensorMap* tm, uint32_t mb, int x, int y) {
  asm volatile("cp.async.bulk.tensor.2d.shared::cluster.global.mbarrier::complete_tx::bytes [%0], [%1, {%3, %4}], [%2];"
               :: "r"(dst), "l"(tm), "r"(mb), "r"(x), "r"(y) : "memory");
}
__device__ __forceinline__ void l2_prefetch(const void* src, uint32_t bytes) {
  asm volatile("cp.async.bulk.prefetch.L2.global [%0], %1;" :: "l"(src), "r"(bytes) : "memory");
}
__device__ __forceinline__ uint32_t uni(uint32_t v) {
  uint32_t r; asm volatile("shfl.sync.idx.b32 %0, %1, 0, 0x1f, 0xffffffff;" : "=r"(r) : "r"(v)); return r;
}
__device__ __forceinline__ int fresh_tid() { int v; asm volatile("mov.u32 %0, %tid.x;" : "=r"(v)); return v; }

struct Params {
  const unsigned char* x;
  Scratch* s;
  int off[7];
  uint32_t zero;
  uint32_t* out;
  const uint16_t* dskip;
  const uint32_t* w_r;
  long long* ts;
  const unsigned char* far[7];
  uint32_t sched[2][17];
};
__device__ __forceinline__ uint32_t ldnc32(const void* p) { uint32_t v; asm volatile("ld.global.nc.b32 %0, [%1];" : "=r"(v) : "l"(p)); return v; }
__device__ __forceinline__ uint32_t ldnc16(const void* p) { uint16_t v; asm volatile("ld.global.nc.u16 %0, [%1];" : "=h"(v) : "l"(p)); return v; }
__device__ __forceinline__ uint4 ldnc128(const void* p) { uint4 v; asm volatile("ld.global.nc.v4.b32 {%0,%1,%2,%3}, [%4];" : "=r"(v.x), "=r"(v.y), "=r"(v.z), "=r"(v.w) : "l"(p)); return v; }
__device__ __forceinline__ void mbar_wait(uint32_t mb, uint32_t ph = 0) {
#pragma unroll 1
  for (int it = 0; it < SPIN_MAX; it++) {
    uint32_t ok;
    asm volatile("{ .reg .pred q; mbarrier.try_wait.parity.shared::cta.b64 q, [%1], %2; selp.u32 %0, 1, 0, q; }" : "=r"(ok) : "r"(mb), "r"(ph) : "memory");
    if (ok) break;
  }
}
__device__ __forceinline__ uint32_t mbar_test(uint32_t mb) {
  uint32_t ok;
  asm volatile("{ .reg .pred q; mbarrier.test_wait.parity.shared::cta.b64 q, [%1], 0; selp.u32 %0, 1, 0, q; }" : "=r"(ok) : "r"(mb) : "memory");
  return ok;
}
__device__ __forceinline__ void mbar_arrive(uint32_t mb) { asm volatile("mbarrier.arrive.shared::cta.b64 _, [%0];" :: "r"(mb) : "memory"); }
__device__ __forceinline__ uint32_t ldg16(const void* p) { uint16_t v; asm volatile("ld.global.u16 %0, [%1];" : "=h"(v) : "l"(p) : "memory"); return v; }
__device__ __forceinline__ uint32_t ldr16(const void* p) { uint16_t v; asm volatile("ld.relaxed.gpu.global.u16 %0, [%1];" : "=h"(v) : "l"(p) : "memory"); return v; }
__device__ __forceinline__ void fence_async() { asm volatile("fence.proxy.async.shared::cta;" ::: "memory"); }
#define SPIN_WHILE(cond, body) _Pragma("unroll 1") for (int _it = 0; _it < SPIN_MAX && __any_sync(0xffffffffu, (cond)); _it++) { body; }

struct LnC { uint32_t m2, rh2, rl2; };
__device__ __forceinline__ float diag_sum(float d0, float d1, int t) {
  float q = __shfl_sync(0xffffffffu, d0, 9 * t) + __shfl_sync(0xffffffffu, d1, 9 * t + 4);
  q += __shfl_xor_sync(0xffffffffu, q, 1);
  return q + __shfl_xor_sync(0xffffffffu, q, 2);
}
__device__ __forceinline__ LnC ln_consts(float s, float q, float& r) {
  const float mean = s * (1.f / DM);
  const float var = fmaxf(fmaf(-mean, mean, q * (1.f / DM)), 0.f);
  float sd;
  asm("sqrt.approx.ftz.f32 %0, %1;" : "=f"(sd) : "f"(bfr(bfr(var) + 1e-5f)));
  asm("rcp.approx.ftz.f32 %0, %1;" : "=f"(r) : "f"(bfr(sd)));
  LnC c;
  c.m2 = pack_bf(mean, mean);
  c.rh2 = pack_bf(r, r);
  const float rl = r - bf_lo(c.rh2);
  c.rl2 = pack_bf(rl, rl);
  return c;
}
__device__ __forceinline__ float quad_sum(float s) { s += __shfl_xor_sync(0xffffffffu, s, 1); return s + __shfl_xor_sync(0xffffffffu, s, 2); }
__device__ __forceinline__ uint32_t bf_fma2(uint32_t a, uint32_t b, uint32_t c) {
  __nv_bfloat162 r = __hfma2(*(const __nv_bfloat162*)&a, *(const __nv_bfloat162*)&b, *(const __nv_bfloat162*)&c);
  return *(uint32_t*)&r;
}
__device__ __forceinline__ uint32_t ln_apply(uint32_t w, uint32_t m2, uint32_t rh2, uint32_t rl2) {
  const uint32_t d = bf_sub2(w, m2);
  return bf_fma2(d, rh2, bf_mul2(d, rl2));
}

__device__ __forceinline__ float2 cis(float mag_log2, float rev) {
  const float m = ex2(mag_log2), ang = rev * 6.283185307179586f;
  return make_float2(m * __cosf(ang), m * __sinf(ang));
}
__device__ __forceinline__ float2 csq(float2 a) { return make_float2(fmaf(a.x, a.x, -a.y * a.y), (a.x + a.x) * a.y); }
__device__ __forceinline__ float2 cmul(float2 a, float2 b) { return make_float2(fmaf(a.x, b.x, -a.y * b.y), fmaf(a.x, b.y, a.y * b.x)); }
__device__ __forceinline__ void pmul(uint32_t xr, uint32_t xi, uint32_t w, uint32_t& yr, uint32_t& yi) {
  const __half2 XR = *(__half2*)&xr, XI = *(__half2*)&xi, W = *(__half2*)&w;
  const __half2 a = __hfma2(__hneg2(XI), __high2half2(W), __hmul2(XR, __low2half2(W)));
  const __half2 b = __hfma2(XI, __low2half2(W), __hmul2(XR, __high2half2(W)));
  yr = *(const uint32_t*)&a; yi = *(const uint32_t*)&b;
}
__device__ __forceinline__ uint32_t pk(float2 a) { return pack_h(a.x, a.y); }

struct KgState { float2 c0, z8; float kl; uint32_t w64, w128, w192; };
__device__ __forceinline__ void kgen_tables_n(const uint32_t (&raw)[7], uint32_t scr, int wt, KgState& k) {
  const uint32_t dst = scr + 16384 + wt * 16;
  const float dt = bfr(ex2(bf_lo(raw[6]) * 1.4426950408889634f));
  const float th = dt * bf_lo(raw[1]);
  const float br = dt * bf_lo(raw[2]), bi = dt * bf_lo(raw[3]);
  const float Cr = bf_lo(raw[4]), Ci = bf_lo(raw[5]);
  k.c0 = make_float2(fmaf(Cr, br, -Ci * bi), fmaf(Cr, bi, Ci * br));
  const uint32_t mx = __reduce_max_sync(0xffffffffu, __float_as_uint(fmaxf(fabsf(k.c0.x), fabsf(k.c0.y))));
  const float a2 = dt * bf_lo(raw[0]) * 1.4426950408889634f;
  const float rh = th * 0.15915494309189535f;
  const float rl = fmaf(th, (float)(0.15915494309189535 - (double)0.15915494309189535f), fmaf(th, 0.15915494309189535f, -rh));
  const float rf = rh - rintf(rh);
  const float2 z1 = cis(a2, rf + rl);
  const float p64 = rf * 64.f;
  const float2 z64 = cis(a2 * 64.f, fmaf(64.f, rl, p64 - rintf(p64)));
  const float2 z2 = csq(z1), z128 = csq(z64), z3 = cmul(z2, z1), z4 = csq(z2), z256 = csq(z128), z6 = csq(z3), z512 = csq(z256);
  k.z8 = csq(z4);
  k.w64 = pk(z64); k.w128 = pk(z128); k.w192 = pk(cmul(z128, z64));
  sts128(dst, 0x00003C00u, pk(z2), pk(z4), pk(z6));
  const float2 z1024 = csq(z512), z768 = cmul(z512, z256);
  sts128(dst + 2048, pk(z1), pk(z3), pk(cmul(z4, z1)), pk(cmul(z4, z3)));
  const float2 z2048 = csq(z1024);
  k.kl = fmaf(k.c0.x, z2048.x, -k.c0.y * z2048.y);
  sts128(dst + 4096, pk(z256), pk(cmul(z256, z2)), pk(cmul(z256, z4)), pk(cmul(z256, z6)));
  sts128(dst + 6144, pk(z512), pk(cmul(z512, z4)), pk(z768), pk(cmul(z768, z4)));
  sts128(dst + 8192, pk(z1024), pk(cmul(z1024, z256)), pk(cmul(z1024, z512)), pk(cmul(z1024, z768)));
  sts32(scr + W_MISC + (wt >> 5) * 4, mx);
}
__device__ __forceinline__ int kgen_tables_m(uint32_t scr, int wt, const KgState& k) {
  const uint32_t dst = scr + wt * 16;
  const uint4 e4 = lds128(scr + W_MISC);
  const float2 z16 = csq(k.z8), z32 = csq(z16);
  const int em = max(min((int)(max(max(e4.x, e4.y), max(e4.z, e4.w)) >> 23), 238), 16);
  const float sc = __uint_as_float((uint32_t)(127 + 4 + 127 - em) << 23);
  sts32(scr + W_MISC + 16 + (wt >> 5) * 4, __reduce_add_sync(0xffffffffu, __float2int_rn(k.kl * sc * 262144.f)));
  const float2 c0 = make_float2(k.c0.x * sc, k.c0.y * sc);
  const float2 c1 = cmul(c0, k.z8), c2 = cmul(c0, z16), c4 = cmul(c0, z32), c3 = cmul(c1, z16), c5 = cmul(c1, z32), c6 = cmul(c2, z32), c7 = cmul(c3, z32);
  uint32_t pr[4], pi[4], yr[4], yi[4];
  pr[0] = pack_h(c0.x, c1.x); pi[0] = pack_h(c0.y, c1.y);
  pr[1] = pack_h(c2.x, c3.x); pi[1] = pack_h(c2.y, c3.y);
  pr[2] = pack_h(c4.x, c5.x); pi[2] = pack_h(c4.y, c5.y);
  pr[3] = pack_h(c6.x, c7.x); pi[3] = pack_h(c6.y, c7.y);
  sts128(dst, pr[0], pr[1], pr[2], pr[3]); sts128(dst + 2048, pi[0], pi[1], pi[2], pi[3]);
#pragma unroll
  for (int q = 1; q < 4; q++) {
    const uint32_t w = q == 1 ? k.w64 : q == 2 ? k.w128 : k.w192;
#pragma unroll
    for (int i = 0; i < 4; i++) pmul(pr[i], pi[i], w, yr[i], yi[i]);
    sts128(dst + q * 4096, yr[0], yr[1], yr[2], yr[3]); sts128(dst + q * 4096 + 2048, yi[0], yi[1], yi[2], yi[3]);
  }
  return em;
}
__device__ __forceinline__ void kgen_build(uint32_t tb, int wg, int wt, uint32_t k0, uint32_t k1, uint32_t k2) {
  const uint32_t kt = tb + W_KT, sc = tb + W_L3 + 3072;
  const int ix = ((wt >> 2) + (wt & 3) * 32 - 1) & 127;
  const uint32_t a3 = tb + W_CW + 32 + ((ix & 1) ? 0 : 304) + (ix >> 1) * 4;
  const uint32_t v3 = wt ? k2 : k2 >> 16;
  sts32(sc + 4 + wt * 4, __byte_perm(k0, k1, 0x5432));
  sts16(sc + 544 + (wt & ~3) + (wt & 1) * 2 + (wt & 2) * 64, k1 >> 16);
  sts16(a3, v3); sts16(a3 + 6, v3);
  if ((unsigned)(wt - 32) < 18u) sts128(kt + (wt < 36 ? -512 : 64 + 4128 - 576) + wt * 16, 0, 0, 0, 0);
  if (wt == 127) sts32(sc, k0 & 0xFFFF0000u);
  if (wt == 0) { sts32(sc + 516, k1); sts16(sc + 800, k2); }
  bar_sync(1 + wg, 128);
  const uint32_t cw = tb + W_CW + 32 + (wt >> 6) * 48 + wt * 4;
  const uint32_t pv = lds32(sc + wt * 4), nx = lds32(sc + 8 + wt * 4), c2 = lds16(sc + 544 + wt * 2), n2 = lds16(sc + 546 + wt * 2);
  sts128(tb + W_L3 + 512 + (wt >> 6) * 512 + wt * 16, lds32(cw), lds32(cw - 8), lds32(cw - 16), lds32(cw - 24));
  const bool odd = wt & 1;
  sts64(kt + 64 + wt * 8, __byte_perm(k0, pv, 0x5410), __byte_perm(k0, 0, 0x1032));
  sts64(kt + 64 + 1024 + wt * 8, __byte_perm(k1, pv, (odd || wt == 0) ? 0x7610 : 0x1010), __byte_perm(k1, nx, odd ? 0x1076 : 0x1010));
  const uint32_t cc = c2 * 0x10001u, nc = __byte_perm(n2, c2, 0x5410), nn = n2 * 0x10001u;
  sts128(kt + 64 + 2048 + wt * 16, cc, cc, odd ? nc : cc, odd ? nn : nc);
  if (wt == 127) { sts128(kt + 64 + 4096, nn, nn, nn, nn); sts128(kt + 64 + 4112, nn, nn << 16, 0, 0); }
}

__device__ __forceinline__ void load_a(uint32_t (&a)[4], uint32_t kp, int j) {
  a[0] = lds32(kp + 64 * j); a[1] = lds32(kp + 64 * j + 512); a[2] = lds32(kp + 64 * j - 32); a[3] = lds32(kp + 64 * j + 480);
}
__device__ __forceinline__ uint32_t band(int d, int lo, int hi) {
  return ((unsigned)(d - lo) <= (unsigned)(hi - lo) ? 1u : 0u) | ((unsigned)(d - 1 - lo) <= (unsigned)(hi - lo) ? 0x10000u : 0u);
}
__device__ __forceinline__ uint32_t hadd2u(uint32_t a, uint32_t b) { __half2 r = __hadd2(*(__half2*)&a, *(__half2*)&b); return *(uint32_t*)&r; }

__device__ __forceinline__ void zero_pads(uint32_t tb, int wt) {
  if (!(wt & 32)) sts128(tb + W_L3 + (wt >> 6) * 512 + wt * 16, 0, 0, 0, 0);
  if ((wt & 63) < 3) sts128(tb + W_CW + (wt >> 6) * 304 + (wt & 63) * 16, 0, 0, 0, 0);
}
__device__ __forceinline__ uint32_t tr_base(int lane) {
  return OFF_YT + (2 * (lane >> 3) + (lane & 1)) * YT_PITCH + ((lane >> 1) & 1) * (8 * YT_PITCH + 64) + ((lane >> 2) & 1) * 16;
}

__device__ __forceinline__ uint32_t sc_addr(int tp) { return OFF_YT + (tp < 16 ? tp * YT_PITCH + (tp >> 3) * 64 + 1152 : 8 * YT_PITCH - 512 + tp * 32); }
#define X_PS 1
#define X_PW 15
#define X_HU 16
#define X_HB 0
#define X_REL 1
#define X_PAD0 0
#define X_PAD1 0
#define PAD(n) _Pragma("unroll") for (int _i = 0; _i < (n); _i++) asm volatile("pmevent 0;");
#define X_HW 0
#define X_LA 9
#define X_G 2
#define X_NE 2
#define X_SCT 10000
#define X_DELTA 400
#define X_DSTEP 2000
#define X_PF0 2500
#define X_PFD 600
#define X_TD 450
#define X_WS 6
#define X_OR 8
#define X_ABS 5100
#define X_XD 0
#define X_RD 650
#define X_HD 400
#define X_PD 1150
#define X_PROMO 2
#define X_YD2 1000
#define X_GO 2
#define X_GW 2
#define X_NS 4700
#define X_XS 13600
#define X_LAG 1800
#define X_YD 1550
struct TMaps { CUtensorMap m[10]; };
__device__ __forceinline__ uint32_t h2bf(uint32_t w) { const float2 f = h2f(w); return pack_bf(f.x, f.y); }
__device__ __forceinline__ uint32_t keep(uint32_t v) { asm volatile("" : "+r"(v)); return v; }
__device__ __forceinline__ uint2 ldr64(const void* p) { uint2 v; asm volatile("{ .reg .b64 t; ld.relaxed.gpu.global.b64 t, [%2]; mov.b64 {%0, %1}, t; }" : "=r"(v.x), "=r"(v.y) : "l"(p) : "memory"); return v; }
__host__ __device__ __forceinline__ uint32_t down_box(int s, bool five) {
  return five ? OFF_W + W_BYTES + 12288 + (s / 3) * (W_BYTES - 12288) + s * 4096 : s < 6 ? OFF_W + W_BYTES + BOX + (s >> 1) * (W_BYTES - 10240) + s * 5120 : OFF_W + (s - 6) * 5120;
}
__device__ __forceinline__ void load_tile(const CUtensorMap* tmx, int i, int c, int again = 0) {
  asm volatile("mbarrier.arrive.expect_tx.shared::cta.b64 _, [%0], 8704;" :: "r"(MB_UL + i * 16 + again) : "memory");
  asm volatile("cp.async.bulk.tensor.3d.shared::cluster.global.mbarrier::complete_tx::bytes [%0], [%1, {%3, %4, %5}], [%2];"
               :: "r"(i < 2 ? OFF_T + i * TILE : OFF_W), "l"(tmx), "r"(MB_UL + i * 16 + again), "r"(0), "r"(c), "r"(-8) : "memory");
}
template <bool FAR> __device__ __forceinline__ void load_params(const Params& p, uint32_t ch, int wt, uint32_t dst, bool on) {
  const int o01 = (wt & 16) ? p.off[1] : p.off[0], o23 = (wt & 16) ? p.off[3] : p.off[2], o45 = (wt & 16) ? p.off[5] : p.off[4];
  const int o = (wt & 64) ? ((wt & 32) ? p.off[6] : o45) : ((wt & 32) ? o23 : o01);
  const unsigned char* b = FAR ? p.far[min(wt >> 4, 6)] : p.x + (long long)o * 16;
  asm volatile("{ .reg .pred q; setp.ne.u32 q, %2, 0; @q cp.async.cg.shared.global [%0], [%1], 16; }"
               :: "r"(dst + wt * 16), "l"(b + (wt < 96 ? ch * 256 + (wt & 15) * 16 : (ch >> 3) * 16)), "r"((uint32_t)(on && wt < 97)) : "memory");
}

struct ConvC { uint32_t ca, cb, bands; };
__device__ __forceinline__ ConvC conv_consts(int w, int lane) {
  const int h = w & 1, P = (w >> 1) & 1, d0 = 8 * h + (lane >> 2) - 2 * (lane & 3);
  ConvC k;
  k.ca = keep((W_KT + (16 + 256 * P + d0) * 4) | (((8 + 64 * P + lane) * 64 + (((h + ((w >> 1) & 2)) ^ (lane >> 1)) & 3) * 16) << 16));
  k.cb = keep(lane < 8 ? 0xFFFEFFFEu : ~0u);
  k.bands = keep(band(d0, 12, 20) + 2 * band(d0 + 8, 12, 20) + 4 * band(d0 + 16, 12, 20) + 8 * band(d0 + 24, 12, 20)
                 + 16 * band(d0 - 8, 5, 11) + 32 * band(d0, 5, 11) + 64 * band(d0 + 8, 5, 11) + 128 * band(d0 + 16, 5, 11));
  return k;
}
struct ConvPre { uint32_t e0, e2, f2, a[3][4]; };
__device__ __forceinline__ uint32_t lds32_if(uint32_t a, bool on) {
  uint32_t v; asm volatile("{ .reg .pred q; setp.ne.u32 q, %2, 0; mov.b32 %0, 0; @q ld.shared.b32 %0, [%1]; }" : "=r"(v) : "r"(a), "r"((uint32_t)on) : "memory"); return v;
}
__device__ __forceinline__ void conv_pre(ConvPre& r, uint32_t kp, int part, bool on, bool P) {
  if (part & 1) { r.e0 = lds32_if(kp + 4096, on && !P); r.e2 = lds32_if(kp + 4064, on && !P); r.f2 = lds32_if(kp + 4128, on && !P); }
#pragma unroll
  for (int j = 0; j < 3; j++) if (part & (j < X_PS ? 1 : 2)) {
    r.a[j][0] = lds32_if(kp + 2048 + 64 * j, on); r.a[j][1] = lds32_if(kp + 2560 + 64 * j, on); r.a[j][2] = lds32_if(kp + 2016 + 64 * j, on); r.a[j][3] = lds32_if(kp + 2528 + 64 * j, on);
  }
}
__device__ __forceinline__ void conv_item(uint32_t tb, uint32_t tl, int bid, int bn, ConvPre& pre, const ConvC& cv, uint32_t zero, const CUtensorMap* tmx, int ch, int warp, int lane, bool hold, bool more) {
  const bool go = more && warp == 0 && lane == 0;
  const uint32_t kp = tb + (cv.ca & 0xFFFFu);
  const uint32_t dlo = (tl >> 4) + 32 + ((warp >> 1) & 2) + (1u << 16), dhi = 32u | (2u << 30);
  const bool P = warp & 2;
  float a32[16], b32[16], a64[32];
  uint32_t A[40][4];
#define STEP(J) { wgmma64<0>(a64, A[J], dlo + 256 - 4 * (J), dhi); \
    if ((J) == 32) wgmma32_init<0>(b32, A[J], dlo, dhi); else wgmma32<0>(b32, A[J], ((J) < 8 ? dlo ^ zero : dlo) + 128 - 4 * (J), dhi); \
    if ((J) == 0) wgmma32_init<0>(a32, A[J], dlo, dhi); else if ((J) < 8) wgmma32<0>(a32, A[J], (dlo ^ zero) - 4 * (J), dhi); }
#define LD(J) load_a(A[J], kp, J);
#define FIRST(J) wg_fence(); STEP(J) wg_commit(); wg_wait<1>(); wg_fence();
  {
    uint32_t win[16], x9[4], x7[4], e[4], f[4];
    const uint32_t bz = keep(cv.bands);
#define BAND(i) keep((bz & (0x10001u << (i))) * (0x3C00u >> (i)))
    e[0] = pre.e0; e[2] = pre.e2; e[1] = keep(bz & 0x100u); e[3] = keep(bz & 0x200u);
    f[2] = pre.f2; f[0] = keep(bz & 0x4000u); f[1] = keep(bz & 0x8000u); f[3] = keep(bz & 0x300u);
#pragma unroll
    for (int j = 0; j < 12; j++) A[32 + j / 4][j & 3] = pre.a[j / 4][j & 3];
    const uint32_t q[12] = {BAND(0), BAND(5), keep(bz & 0x400u), BAND(4), BAND(2), BAND(7), BAND(1), BAND(6), keep(bz & 0x800u), keep(bz & 0x1000u), BAND(3), keep(bz & 0x2000u)};
#undef BAND
    const uint32_t ta = keep(tl + 512 + (warp & 3) * 2048 + lane * 64 + (lane & 6) * 8);
    if (X_GO && hold) mbar_wait(MB_GO);
    uint32_t mbl = MB_UL + (warp & 8) * 2, ph = 0;
#pragma unroll 1
    for (int it = 0; it < SPIN_MAX; it++) {
      if (ch < 512) mbar_wait(mbl, ph);
      if (it == 1) TS(13);
      TS(3);
      wg_fence();
      wgmma64h_init(win, q[0], q[1], q[2], q[3], dlo, dhi);
      wgmma64h(win, q[4], q[5], q[6], q[7], dlo - 4, dhi);
      wgmma64h(win, q[8], q[9], q[10], q[11], dlo - 8, dhi);
      wg_commit();
      wgmma64_init<0>(a64, e, dlo, dhi);
      wgmma64<0>(a64, f, dlo - 4, dhi);
      wg_commit();
      if (ch >= 512) break;
      uint32_t r0, r1, r2, r3, ok;
      if (warp & 4) {
        mbar_wait(mbl + 8);
        if (__all_sync(0xffffffffu, it || lds32(MISC_RT + (warp & 8)) == 0)) break;
        wg_wait<0>();
        continue;
      }
      ldsm4(ta, r0, r1, r2, r3);
      ok = r0 & r1 & r2 & r3;
      ldsm4(ta ^ 32, r0, r1, r2, r3);
      asm volatile("{ .reg .pred q; setp.ne.u32 q, %1, 0; barrier.red.and.pred q, %2, 128, q; selp.u32 %0, 1, 0, q; }" : "=r"(ok) : "r"((ok & r0 & r1 & r2 & r3 & 1u) | (lane & 3)), "r"(1 + (warp >> 2)) : "memory");
      if (ok) { if ((warp & 3) == 0 && lane == 0) { sts32(MISC_RT + warp, it); mbar_arrive(MB_UL + 8 + warp * 2); } break; }
      wg_wait<0>();
      if ((warp & 3) == 0 && lane == 0) load_tile(tmx - 1, warp >> 3, ch, 56);
      mbl = MB_UL + 56 + (warp & 8) * 2; ph = it & 1;
    }
    wg_wait<1>();
#pragma unroll
    for (int i = 0; i < 4; i++) {
      const int tl = 2 * ((i & 1) + ((i & 2) ? 0 : 4));
      x9[i] = P ? win[tl + 4] : win[tl]; x7[i] = P ? win[tl + 5] : win[tl + 1];
    }
    const uint32_t l3lo = ((tb + W_L3) >> 4) + (32u << 16);
    wg_fence();
    wgmma64<0>(a64, x9, l3lo, 8);
    wgmma64<0>(a64, x7, l3lo + 96, 8);
    wg_commit();
  }
  STEP(32) STEP(33) STEP(34) wg_commit(); wg_wait<1>();
  LD(35) LD(36) LD(37) LD(38)
  FIRST(35) STEP(36) STEP(37) STEP(38) wg_commit();
  LD(39) LD(0)
  TS(17);
  if (X_GO == 1 && go) mbar_arrive(MB_GO);
  FIRST(39) STEP(0) wg_commit();
  LD(1) LD(2) LD(3)
  FIRST(1) STEP(2) STEP(3) wg_commit();
  LD(4) LD(5)
  if (X_GO == 2 && go) mbar_arrive(MB_GO);
  FIRST(4) STEP(5) wg_commit();
  LD(6) LD(7)
  wg_fence(); STEP(6) STEP(7) wg_commit();
#undef STEP
#undef LD
#undef FIRST
  TS(18);
  if (X_GO == 3 && go) mbar_arrive(MB_GO);
  const uint32_t xc = tb + W_KT + (warp & 3) * 1024 + lane * 16;
  if (more) bar_sync(7, 288);
  wg_wait<1>();
  conv_pre(pre, kp + ALT, 1, more, P);
  wg_wait<0>();
  conv_pre(pre, kp + ALT, 2, more, P);
  uint32_t E[16], o[8];
#define ACC(i) ((i) < 16 ? a32[i] : (i) < 32 ? b32[(i) - 16] : a64[(i) - 32])
  E[0] = pack_h(a32[0], a32[1]);
#pragma unroll
  for (int i = 1; i < 16; i++) E[i] = pack_h(ACC(4 * i) + ACC(4 * i - 2), ACC(4 * i + 1) + ACC(4 * i - 1));
#undef ACC
#pragma unroll
  for (int j = 0; j < 8; j++) o[j] = P ? (j < 2 ? 0u : E[j - 2]) : E[8 + j];
  sts128(xc, o[0], o[1], o[2], o[3]); sts128(xc + 512, o[4], o[5], o[6], o[7]);
#pragma unroll
  for (int j = 0; j < 8; j++) o[j] = P ? E[6 + j] : E[j];
  TS(25);
  if (more) {
    sts128(xc + 4096, o[0], o[1], o[2], o[3]); sts128(xc + 4608, o[4], o[5], o[6], o[7]);
    bar_arrive(12, 192);
    return;
  }
  bar_sync(1 + (warp >> 2), 128);
  const uint4 vv[2] = {lds128(xc + (P ? -2048 : 2048)), lds128(xc + (P ? -1536 : 2560))};
#pragma unroll
  for (int q = 0; q < 2; q++) {
    const uint4 v = vv[q];
    stsm4t(tl + (cv.ca >> 16) + q * 2048, hadd2u(o[4 * q], v.x) & cv.cb, hadd2u(o[4 * q + 1], v.y) & cv.cb, hadd2u(o[4 * q + 2], v.z) & cv.cb, hadd2u(o[4 * q + 3], v.w) & cv.cb);
  }
  fence_async();
  bar_sync(bid, bn);
  if (warp == 0 && lane == 0) mbar_arrive(MB_REL);
  if ((warp & 7) == (ch < 512 ? 7 : 3) && lane == 0) {
    asm volatile("cp.async.bulk.tensor.3d.global.shared::cta.bulk_group [%0, {%3, %2, %3}], [%1];" :: "l"(tmx), "r"(tl + 512), "r"(ch), "r"(0) : "memory");
    asm volatile("cp.async.bulk.commit_group;" ::: "memory");
  }
}

template <bool FAR> __global__ void __launch_bounds__(NT, 1)
fused_kernel(const __grid_constant__ Params p, const __grid_constant__ TMaps tm) {
  extern __shared__ __align__(1024) unsigned char smem[];
  const int c = blockIdx.x;
  const bool five = (c & 1) == 0;
  const uint32_t pitch = five ? 64 : 80;
  const uint32_t ones = 0x3F803F80u;
  const int tid = threadIdx.x, lane = tid & 31;
  {
    const int w4 = tid >> 7, k5 = !five && w4 == 3;
    load_params<FAR>(p, k5 ? 512 + (c >> 1) : (w4 & 2) * 128 + 2 * c + (w4 & 1), tid & 127, OFF_W + w4 * W_BYTES + W_KT + k5 * 2048, w4 != 2 && w4 != 4);
  }
  const int warp = (int)uni(tid >> 5), wg = warp >> 2;
  TS(0);
  if (__builtin_expect(wg == 4, 0)) {
    asm volatile("setmaxnreg.dec.sync.aligned.u32 32;");
    const int role = warp;
    const int u0 = (c >> 1) * 9 + (five ? ((c & 2) ? 5 : 0) : ((c & 2) ? 0 : 4));
    const uint32_t t0 = clock() + c * 4;
    if (role == 16) {
      if (lane < 19) asm volatile("mbarrier.init.shared::cta.b64 [%0], %1;" :: "r"(OFF_MISC + lane * 8), "r"((unsigned)(lane - 2) < 4u ? 4 : 1) : "memory");
      if (lane < 2) asm volatile("mbarrier.arrive.expect_tx.shared::cta.b64 _, [%0], %1;" :: "r"(OFF_MISC + lane * 8), "r"(lane ? (five ? 36864 : 51200) : pitch * 1152) : "memory");
      fence_async();
      bar_arrive(5, 608);
      const CUtensorMap* tmb = &tm.m[five ? 3 : 0];
#pragma unroll 1
      for (int u = 0; u < 17; u++) {
        const uint32_t e = p.sched[five][u], kind = e & 3, s = (e >> 2) & 15, dst = e >> 14;
        if (kind == 3) continue;
        while ((int)(clock() - t0) < X_PF0 + (u < X_NE ? u * X_PFD : X_LAG + u * X_TD)) __nanosleep(20);
        if (e & 0x3FC0) mbar_wait(OFF_MISC + ((e >> 6) & 255));
        if (lane == 0) {
          if (kind == 2) asm volatile("cp.async.bulk.tensor.3d.shared::cluster.global.mbarrier::complete_tx::bytes [%0], [%1, {%3, %4, %5}], [%2];"
                                      :: "r"(dst), "l"(tmb + 2), "r"(MB_D), "r"(0), "r"(u0 * 8), "r"(s) : "memory");
          else tma_box(dst, tmb + kind, MB_GU, u0 * 8, s * 96);
        }
        if (u == 5) TS(2);
        if (u == 10) TS(3);
      }
      TS(4);
      TS_DUMP();
#define FINISH0 bar_sync(12, 192);        \
        _Pragma("unroll 1") for (int w = role & 2; w < (role & 2) + 2; w++) { \
          const uint32_t xa = OFF_W + W_KT + lane * 16, mk = lane < 8 ? 0xFFFEFFFEu : ~0u, ya = OFF_T + (8 + lane) * 64 + (((w & 1) ^ (lane >> 1)) & 3) * 16 + (w & 2) * 2048; \
          const uint4 a = lds128(xa + 4096 + w * 1024), b = lds128(xa + (w ^ 2) * 1024), d = lds128(xa + 4608 + w * 1024), e = lds128(xa + 512 + (w ^ 2) * 1024); \
          stsm4t(ya, hadd2u(a.x, b.x) & mk, hadd2u(a.y, b.y) & mk, hadd2u(a.z, b.z) & mk, hadd2u(a.w, b.w) & mk); \
          stsm4t(ya + 2048, hadd2u(d.x, e.x) & mk, hadd2u(d.y, e.y) & mk, hadd2u(d.z, e.z) & mk, hadd2u(d.w, e.w) & mk); \
        } \
        fence_async();
    } else if (role == 17) {
      if (smem_u32(smem) != SB) __trap();
      bar_sync(10, 576);
      if (lane == 0) {
        fence_async();
        while ((int)(clock() - t0) < X_NS - c * 4) {}
        asm volatile("cp.async.bulk.global.shared::cta.bulk_group [%0], [%1], 10240;" :: "l"(&p.s->X[c * DM * 2 + 512]), "r"(OFF_G) : "memory");
        asm volatile("cp.async.bulk.commit_group;" ::: "memory");
        asm volatile("cp.async.bulk.wait_group 0;" ::: "memory");
      }
      if (lane == 0) mbar_arrive(MB_GF);
      bar_arrive(11, 96);
      if (five) { FINISH0 bar_arrive(13, 192); }
    } else if (role == 18) {
      sts32(MISC_EPOCH, 0);
      sts32(MISC_T0, t0 - c * 4);
      bar_arrive(5, 608);
      uint4* q = lane < 2 ? &p.s->R[c * 2 + lane] : lane < 11 ? &p.s->HS[c * 9 + lane - 2] : lane == 11 ? &p.s->HS[1152 + (c & 7)] : (uint4*)&p.s->FLAG[c * 8];
      if (lane < (c < 8 ? 12 : 11)) str128(q, ~0u, ~0u, ~0u, ~0u);
      const uint32_t ep = __shfl_sync(0xffffffffu, ldr32(q), 31) + 1u;
      sts32(MISC_EPOCH, ep | 0x80000000u);
      TSX(21);
      if (lane == 31) str32(q, ep);
      bar_sync(11, 96);
      TSX(14);
      mbar_wait(MB_KF + (lane & 3) * 8);
      __syncwarp();
      { const uint2 e = lds64(MISC_EM); if (lane < 2) str128(&p.s->SC[c * 2 + lane], e.x, __byte_perm(e.y, ep, 0x6540), 0, 0); }
      TSX(17);
      while ((int)(clock() - t0) < X_SCT) __nanosleep(100);
      TSX(18);
      {
        uint2 v[4];
#pragma unroll 1
        for (int it = 0; it < SPIN_MAX; it++) {
          uint32_t bad = 0;
#pragma unroll
          for (int q = 0; q < 4; q++) v[q] = ldr64(&p.s->SC[lane * 2 + q * 64]);
#pragma unroll
          for (int q = 0; q < 4; q++) bad |= (v[q].y >> 8) ^ (ep & 0xFFFFFFu);
          if (!__any_sync(0xffffffffu, bad)) break;
        }
        TSX(25);
#pragma unroll
        for (int q = 0; q < 4; q++) {
          const uint32_t sa = (lane >> 4) * YT_PITCH + (lane & 15) * 2;
          sts16(sc_addr(2 * q) + sa, v[q].x); sts16(sc_addr(8 + 2 * q) + sa, v[q].x >> 16);
          if (lane & 1) asm volatile("st.shared.u8 [%0], %1;" :: "r"(sc_addr(16) + q * 16 + (lane >> 1)), "r"(v[q].y) : "memory");
        }
      }
      __syncwarp();
      if (lane == 0) mbar_arrive(MB_SC);
      TSX(27);
    } else {
      uint32_t w[9];
      const uint32_t dk = ldnc16(p.dskip + ((lane & 4) ? 512 + (c >> 1) : (lane & 2) * 128 + 2 * c + (lane & 1)));
      float s = 0.f;
#pragma unroll
      for (int i = 0; i < 9; i++) w[i] = ldnc32(p.w_r + lane + 32 * i);
      sts16(OFF_WR + 1152 + lane * 2, dk);
      bar_arrive(5, 608);
#pragma unroll
      for (int i = 0; i < 9; i++) { sts32(OFF_WR + lane * 4 + i * 128, w[i]); s += bf_lo(w[i]) + bf_hi(w[i]); }
      sts32(MISC_SW, __float_as_uint(warp_sum(s)));
      TSX(23);
      bar_sync(10, 576);
      if (lane == 0) {
        const uint32_t tp = clock();
        TSX(1);
        while ((int)(clock() - tp) < X_DELTA || (int)(clock() - t0) < X_ABS - c * 4) {}
        TSX(24);
        load_tile(&tm.m[6], 0, c);
        TSX(15);
        while ((int)(clock() - t0) < X_ABS + X_DSTEP - c * 4) {}
      }
      bar_sync(11, 96);
      if (lane == 0) {
        load_tile(&tm.m[6], 1, 128 + c);
      }
      if (five) {
        mbar_wait(MB_KF);
#pragma unroll 1
        for (int it = 0; it < SPIN_MAX; it++) {
          if (lane == 0) load_tile(&tm.m[8], 2, 512 + (c >> 1));
          mbar_wait(MB_UL + 32, it & 1);
          uint32_t m = 1;
#pragma unroll
          for (int q = 0; q < 4; q++) { uint32_t r0, r1, r2, r3; ldsm4(OFF_W + 512 + lane * 64 + (lane & 6) * 8 + q * 2048, r0, r1, r2, r3); m &= r0 & r1 & r2 & r3; }
          if (__all_sync(0xffffffffu, m || (lane & 3))) break;
        }
        bar_arrive(7, 288);
        FINISH0
        bar_arrive(13, 192);
      }
      bar_sync(0, 544);
      if (lane == 0) mbar_arrive(MB_H);
    }
    return;
  }
  const int wt = tid & 127, g = lane >> 2, t = lane & 3;
  const uint32_t wb = OFF_W + wg * W_BYTES;
  const uint32_t xrow = OFF_YT + (wt >> 3) * YT_PITCH + (wt & 64) + (lane & 7) * 16;
  if (wg == 2) {
    const unsigned char* xp = p.x + (uint32_t)((c * 16 + (wt >> 3)) * 1152 + (lane & 7) * 16);
    { const uint32_t tq = clock(); while ((int)(clock() - tq) < X_XD) {} }
#pragma unroll
    for (int k = 0; k < 9; k++) asm volatile("cp.async.cg.shared.global [%0], [%1], 16;" :: "r"(xrow + k * 128), "l"(xp + k * 128) : "memory");
  }
  asm volatile("cp.async.commit_group;" ::: "memory");
  const ConvC cv = conv_consts(warp, lane);
  zero_pads(wb, wt);
  load_params<FAR>(p, 254 + 2 * c + wg, wt, wb + W_KT, wg == 2 || (wg == 3 && !five));
  asm volatile("cp.async.commit_group;" ::: "memory");
  asm volatile("setmaxnreg.inc.sync.aligned.u32 112;");
  PAD(X_PAD0)
  {
    uint4 kw;
    uint4* kx = &p.s->KX[(c >> 1) * 128 + wt];
    bool two = wg == 3;
    uint32_t ep;
    int em = 0;
    int phase = wg == 2 ? 3 : 2;
#pragma unroll 1
    for (;;) {
      const bool first = two && !five;
      if (phase) asm volatile("cp.async.wait_group 1;" ::: "memory"); else asm volatile("cp.async.wait_group 0;" ::: "memory");
      if (phase == 3) {
        TS(21);
        float d[3][4], r;
        uint4 a[9];
#pragma unroll
        for (int k = 0; k < 9; k++) a[k] = lds128(xrow + k * 128);
#pragma unroll
        for (int i = 0; i < 4; i++) d[0][i] = d[1][i] = d[2][i] = 0.f;
#pragma unroll
        for (int k = 0; k < 9; k++) { mma_bf16(d[(2 * k) % 3], a[k].x, ones, a[k].y, ones, a[k].x, a[k].y); mma_bf16(d[(2 * k + 1) % 3], a[k].z, ones, a[k].w, ones, a[k].z, a[k].w); }
#pragma unroll
        for (int i = 0; i < 4; i++) d[0][i] += d[1][i] + d[2][i];
        const LnC lc = ln_consts(d[0][2] + d[0][3], __shfl_sync(0xffffffffu, d[0][0], 9 * t) + __shfl_sync(0xffffffffu, d[0][1], 9 * t + 4), r);
        if (lane < 12) sts16(MISC_LN1 + g * 32 + (warp & 3) * 8 + t * 2, lane < 4 ? lc.m2 : lane < 8 ? lc.rh2 : lc.rl2);
      } else {
        KgState ks;
        uint32_t raw[7];
        bar_sync(1 + wg, 128);
        TS(22);
#pragma unroll
        for (int i = 0; i < 7; i++) raw[i] = lds16(wb + W_KT + first * 2048 + i * 256 + (i < 6 ? wt : (first ? c >> 1 : 2 * c + (wg & 1)) & 7) * 2);
        kgen_tables_n(raw, wb, wt, ks);
        TS(20);
        bar_sync(1 + wg, 128);
        em = kgen_tables_m(wb, wt, ks);
        fence_async();
      }
      if (phase & 2) {
        const uint32_t tr_addr = tr_base(lane) + warp * 32;
        uint4* dst = &p.s->X[c * DM * 2 + warp * 32 + (8 * (t >> 1) + g) * 2 + (t & 1)];
        TS(23);
        bar_sync(5, 608);
        uint32_t x[3][4];
        ldsm4t(tr_addr, x[0][0], x[0][1], x[0][2], x[0][3]);
        const uint4 m = lds128(MISC_LN1 + (t & 1) * 16), rl = lds128(MISC_LN1 + 64 + (t & 1) * 16), rh = lds128(MISC_LN1 + 32 + (t & 1) * 16);
        ldsm4t(tr_addr + 512, x[1][0], x[1][1], x[1][2], x[1][3]);
        if (wg == 3) ldsm4t(tr_addr + 640, x[2][0], x[2][1], x[2][2], x[2][3]);
#pragma unroll
        for (int q = 0; q < 3; q++) {
          if (q < 2 || wg == 3) {
            const uint32_t r0 = ln_apply(x[q][0], m.x, rh.x, rl.x), r1 = ln_apply(x[q][1], m.y, rh.y, rl.y), r2 = ln_apply(x[q][2], m.z, rh.z, rl.z), r3 = ln_apply(x[q][3], m.w, rh.w, rl.w);
            const uint32_t w0 = (pack_h(bf_lo(r0), bf_hi(r0)) & 0xFFFEFFFEu) | 1u, w1 = pack_h(bf_lo(r1), bf_hi(r1)), w2 = pack_h(bf_lo(r2), bf_hi(r2)), w3 = pack_h(bf_lo(r3), bf_hi(r3));
            if (q == 0) str128(dst, w0, w1, w2, w3);
            else sts128(OFF_G + warp * 512 + (8 * (t >> 1) + g) * 32 + (t & 1) * 16 + (q == 2 ? 2048 : 0), w0, w1, w2, w3);
          }
          if (q == 0) TS(30);
        }
        bar_arrive(10, 576);
        TS(1);
      } else bar_sync(1 + wg, 128);
      phase &= 1;
      if (phase) { phase = 0; continue; }
      TS(14);
      float acc[20];
      const uint32_t alo = (wb >> 4) | (8u << 16);
      wg_fence();
      wgmma40_ss_init(acc, alo, alo + 1024, 2048 >> 4);
#pragma unroll
      for (int k = 1; k < 8; k++) wgmma40_ss(acc, alo + k * 16, alo + 1024 + k * 16, 2048 >> 4);
      wg_commit();
      const uint4 k4 = lds128(wb + W_MISC + 16);
      const float k2048 = (float)(int)(k4.x + k4.y + k4.z + k4.w) * (1.f / 262144.f);
      const uint32_t dk = lds16(OFF_WR + 1152 + (wg + first) * 2);
      const int ef = max(em, min((int)((dk >> 7) & 255u) - 7, 238));
      asm volatile("st.shared.u8 [%0], %1;" :: "r"(MISC_EM + wg + first), "r"(ef + 9) : "memory");
      const float un = __uint_as_float((uint32_t)max(114 + em - ef, 0) << 23), d0 = wt ? 0.f : bf_lo(dk) * __uint_as_float((uint32_t)(245 - ef) << 23);
      wg_wait<0>();
      kw.x = pack_h(fmaf(acc[0] - acc[3], un, d0), (acc[4] - acc[7]) * un);
      kw.y = pack_h((acc[8] - acc[11]) * un, (acc[12] - acc[15]) * un);
      kw.z = pack_h((acc[16] - acc[19]) * un, k2048 * un);
      TS(24);
      ep = 0;
      if (two) SPIN_WHILE(ep == 0, ep = lds32(MISC_EPOCH));
      if (five || !two) break;
      str128(kx, kw.x, kw.y, kw.z, ep);
      two = false;
    }
    if (lane == 0) mbar_arrive(MB_KF + wg * 8);
    if (two) { mbar_wait(MB_KF); zero_pads(OFF_W + ALT, wt); }
    uint32_t tb = wb;
#pragma unroll 1
    for (;;) {
      kgen_build(tb, wg, wt, kw.x, kw.y, kw.z);
      TS(15);
      if (!two) break;
      two = false;
      kw.w = 0;
      SPIN_WHILE(kw.w != ep, kw = ldr128(kx));
      tb = OFF_W + ALT;
    }
    fence_async();
    TS(31);
    if (tb != wb) bar_arrive(7, 288);
    bar_sync(1 + wg, 128);
  }
  uint32_t tpub;
  ConvPre pre;
  conv_pre(pre, wb + (cv.ca & 0xFFFFu), 3, true, warp & 2);
#pragma unroll 1
  for (int item = 0;; item++) {
    TS(2);
    conv_item(item ? OFF_W + ALT : wb, item ? OFF_W : OFF_T + (wg >> 1) * TILE, item ? 1 : 13 + (wg >> 1), item ? 128 : five && wg == 1 ? 192 : 256, pre, cv, p.zero,
              &tm.m[item ? 9 : 7], item ? 512 + (c >> 1) : (wg >> 1) * 128 + c, warp, lane, five && wg >= X_GW, five && !wg && !item);
    tpub = clock() - (item ? X_YD : wg >= 2 ? X_YD2 : 0);
    if (wg || !five || item) break;
    TS(27);
  }
  TS(4);
  PAD(X_PAD1)

  const int ln = lane ^ p.zero, td = warp * 32 + ln, gg = ln >> 2, tt = ln & 3;
  const int tok = c * 16 + warp;
  const int fu = warp / 3, fk = warp - fu * 3;
  uint32_t wa[12][4];
  uint4 ha[3];
  const uint4* hsrc = &p.s->HS[td + (td / 24) * 48];
  {
    uint32_t hw[9], wr[9];
    const uint32_t row = keep(OFF_YT + warp * YT_PITCH + (warp >> 3) * 64 + ln * 16);
    const uint32_t wabase = keep(((ln & 8) ? OFF_W + (fk + 1) * W_BYTES : OFF_G + fk * 192 * pitch) + ((ln >> 4) * 8 + (ln & 7)) * pitch
                                 + (five ? ((fu ^ (ln >> 1)) & 3) : min(fu, 4)) * 16);
    float sw;
    {
      const bool three = wg == 1;
      const int ch = 8 * (tt >> 1) + gg;
      const uint32_t tr_addr = tr_base(ln);
      const uint4* ysrc = &p.s->X[c * DM * 2 + ch * 2 + (tt & 1)];
      uint32_t x[3][4], s[3];
      uint4 v[3];
#define TL(q) ((q) < 2 ? 2 * warp + (q) : 28 + warp)
      asm volatile("cp.async.bulk.wait_group.read 0;" ::: "memory");
      if (wg >= 2) { const uint32_t ts = lds32(MISC_T0); while ((int)(clock() - ts) < X_XS) {} }
      while ((int)(clock() - tpub) < X_YD) {}
      TS(5);
      v[0] = ldr128(ysrc + TL(0) * 32); v[1] = ldr128(ysrc + TL(1) * 32); v[2] = make_uint4(three, 0, 0, 0);
      if (X_REL == 1 || (X_REL == 2 && wg != 1)) mbar_wait(MB_REL);
#pragma unroll
      for (int i = 0; i < 6; i++) if (i < 4 || three) wr[i] = (gg & 2) ? ones : lds32(OFF_WR + TL(i >> 1) * 32 + (i & 1) * 16 + tt * 4);
      const uint32_t ha = keep(OFF_YT + (ln & 7) * YT_PITCH + (ln >> 4) * (8 * YT_PITCH + 64) + (ln & 8) * 2);
      const uint32_t pa = keep(OFF_PART + warp * 4 + ((gg & 2) * 8 + (gg & 4) * 2 + 2 * tt + (gg & 1)) * 80), pb = keep(OFF_PART + 2560 + warp * 4 + gg * 80);
      float dl[4] = {0.f, 0.f, 0.f, 0.f}, dh[4] = {0.f, 0.f, 0.f, 0.f};
      sw = __uint_as_float(lds32(MISC_SW));
#pragma unroll
      for (int q = 0; q < 3; q++) {
        if (q < 2 || three) {
          ldsm4t(tr_addr + TL(q) * 32, x[q][0], x[q][1], x[q][2], x[q][3]);
        }
      }
      mbar_wait(MB_SC);
#pragma unroll
      for (int q = 0; q < 3; q++) {
        asm volatile("ld.shared.u8 %0, [%1];" : "=r"(s[q]) : "r"((q < 2 ? sc_addr(warp) + q * 16 : sc_addr(16) + (warp & 3) * 16) + ch) : "memory");
        s[q] = keep(s[q] * 0x800080u);
      }
#define FIN(q) stsm4t(tr_addr + TL(q) * 32, bf_fma2(h2bf(v[q].x), s[q], x[q][0]), bf_fma2(h2bf(v[q].y), s[q], x[q][1]), bf_fma2(h2bf(v[q].z), s[q], x[q][2]), bf_fma2(h2bf(v[q].w), s[q], x[q][3]));
      SPIN_WHILE((v[0].x | v[1].x) & 1u, _Pragma("unroll") for (int q = 0; q < 3; q++) if (v[q].x & 1u) v[q] = ldr128(ysrc + TL(q) * 32));
      if (v[2].x & 1u) v[2] = ldr128(ysrc + TL(2) * 32);
#define STAT(q) { uint32_t r0, r1, r2, r3; ldsm4(ha + TL(q) * 32, r0, r1, r2, r3); \
        mma_bf16(dl, r0, wr[2 * q], r1, wr[2 * q + 1], r0, r1); mma_bf16(dh, r2, wr[2 * q], r3, wr[2 * q + 1], r2, r3); }
      FIN(0) FIN(1)
      __syncwarp();
      STAT(0) STAT(1)
      if (three) {
        SPIN_WHILE(v[2].x & 1u, if (v[2].x & 1u) v[2] = ldr128(ysrc + TL(2) * 32));
        FIN(2)
        __syncwarp();
        STAT(2)
      }
      if (gg & 1) { dl[0] = dl[1]; dl[2] = dl[3]; dh[0] = dh[1]; dh[2] = dh[3]; }
      sts32(pa, __float_as_uint((gg & 4) ? dh[2] : dl[2]));
      if (tt == (gg >> 1)) { sts32(pb, __float_as_uint(dl[0])); sts32(pb + 640, __float_as_uint(dh[0])); }
#undef STAT
#undef FIN
#undef TL
    }
    const uint32_t ra = keep(OFF_PART + (ln & 15) * 80 + (ln & 16) * 2);
    uint16_t* rp = (uint16_t*)p.s->R + c * 16 + (ln & 15);
    const uint2* rsrc = (const uint2*)p.s->R + td;
    asm volatile("" : "+l"(rp), "+l"(rsrc), "+l"(hsrc));
    uint2 rv = make_uint2(~0u, 0u);
    TS(28);
    bar_sync(0, 544);
    TS(6);
    if (warp == X_PW) {
      float z[3], rd;
#pragma unroll
      for (int k = 2; k >= 0; k--) {
        const uint4 a = lds128(ra + k * 1280), b = lds128(ra + k * 1280 + 16);
        z[k] = ((__uint_as_float(a.x) + __uint_as_float(a.y)) + (__uint_as_float(a.z) + __uint_as_float(a.w))) + ((__uint_as_float(b.x) + __uint_as_float(b.y)) + (__uint_as_float(b.z) + __uint_as_float(b.w)));
      }
#pragma unroll
      for (int k = 2; k >= 0; k--) z[k] += __shfl_xor_sync(0xffffffffu, z[k], 16);
      const LnC l = ln_consts(z[1], z[2], rd);
      const uint32_t b = pack_bf(0.f, fmaf(-bf_lo(l.m2), sw, z[0]) * rd);
      const uint32_t k16 = max(min((b ^ (((int)b >> 31) | 0x80000000u)) >> 16, 0xFFFEu), 1u);
      if (ln < 16) str16(rp, k16);
      sts64(OFF_RK + (ln & 15) * 8, __byte_perm(l.m2, l.rh2, 0x5410), __byte_perm(l.rl2, k16, 0x5410));
    }
    mbar_wait(MB_GU);
#define LD_HW { const uint4 a = lds128(row), b = lds128(row + 512); hw[8] = lds32(row + 1024 - ln * 12); \
      hw[0] = a.x; hw[1] = a.y; hw[2] = a.z; hw[3] = a.w; hw[4] = b.x; hw[5] = b.y; hw[6] = b.z; hw[7] = b.w; }
    if (!X_HW) LD_HW
    const uint32_t tr0 = clock();
    bar_sync(5, 512);
    TS(7);
    const uint2 lk = lds64(OFF_RK + warp * 8);
    LnC l2;
    l2.m2 = __byte_perm(lk.x, 0, 0x1010); l2.rh2 = __byte_perm(lk.x, 0, 0x3232); l2.rl2 = __byte_perm(lk.y, 0, 0x1010);
    const uint32_t key = (lk.y & 0xFFFF0000u) | (2047 - tok);
    uint32_t loc = ln < 16 ? (lds32(OFF_RK + 4 + ln * 8) & 0xFFFF0000u) | (2047 - c * 16 - ln) : 0u;
    if (X_HW) LD_HW
    int rank = __popc(__ballot_sync(0xffffffffu, loc > key));
#pragma unroll
    for (int i = 0; i < X_LA; i++) wr[i] = keep(ln_apply(hw[i], l2.m2, l2.rh2, l2.rl2));
#define OUT_ROW { uint32_t* o = p.out + tok * 288 + ln * 4; \
      *(uint4*)o = make_uint4(bf_add2(hw[0], wr[0]), bf_add2(hw[1], wr[1]), bf_add2(hw[2], wr[2]), bf_add2(hw[3], wr[3])); \
      *(uint4*)(o + 128) = make_uint4(bf_add2(hw[4], wr[4]), bf_add2(hw[5], wr[5]), bf_add2(hw[6], wr[6]), bf_add2(hw[7], wr[7])); \
      o[256 - ln * 3] = bf_add2(hw[8], wr[8]); }
#pragma unroll 1
    for (int base = 0; base < 8; base += X_G) {
      uint32_t T[X_G];
#pragma unroll
      for (int j = 0; j < X_G; j++) {
        const uint32_t mx = __reduce_max_sync(0xffffffffu, loc);
        if (loc == mx) loc = 0;
        T[j] = (td >> 2) == c ? ~0u : (td >> 2) < c ? (mx & 0xFFFF0000u) - 1u : mx | 0xFFFFu;
      }
      const uint32_t sh = keep(ln < 16 ? 0x4440u + ((rank - base) & 3) : 0x4044u + (X_G - 1) * 256), ca = keep(MISC_CNT + base * 32 + (ln & 15) * 4);
      TS(29);
      if (base == 0) {
        while ((int)(clock() - tr0) < X_RD) {}
        rv = ldr64(rsrc);
#pragma unroll
        for (int i = X_LA; i < 9; i++) wr[i] = keep(ln_apply(keep(hw[i]), l2.m2, l2.rh2, l2.rl2));
        if (rank >= X_OR) OUT_ROW
        if (warp < (five ? 12 : 15)) {
#pragma unroll
          for (int k = 0; k < X_WS; k++) ldsm4t(wabase + k * 16 * pitch, wa[k][0], wa[k][1], wa[k][2], wa[k][3]);
        }
      }
#pragma unroll 1
      for (int it = 0; it < SPIN_MAX; it++) {
        const uint32_t m = __vmaxu2(rv.x, rv.y);
        const bool bad = max(m, m << 16) >= 0xFFFF0000u && T[0] != ~0u;
        if (!__any_sync(0xffffffffu, bad)) break;
        if (bad) rv = ldr64(rsrc);
      }
      TS(16);
      uint32_t cnt = 0, cn2 = 0;
#pragma unroll
      for (int j = 0; j < X_G; j++)
        asm("{ .reg .pred a, b, c, d; setp.gt.u32 a, %2, %6; setp.gt.u32 b, %3, %6; setp.gt.u32 c, %4, %6; setp.gt.u32 d, %5, %6; "
            "@a add.u32 %0, %0, %7; @b add.u32 %1, %1, %7; @c add.u32 %0, %0, %7; @d add.u32 %1, %1, %7; }"
            : "+r"(cnt), "+r"(cn2) : "r"(rv.x), "r"(rv.x << 16), "r"(rv.y), "r"(rv.y << 16), "r"(T[j]), "r"(1u << (8 * j)));
      sts32(MISC_CNT + base * 32 + warp * 4, __reduce_add_sync(0xffffffffu, cnt + cn2));
      bar_sync(0, 512);
      cnt = __reduce_add_sync(0xffffffffu, __byte_perm(lds32(ca), 0, sh));
      if (base == 0) tpub = clock();
      if ((unsigned)(rank - base) < X_G && rank + (int)(cnt & 0xFFFFu) < 8) {
        rank += cnt & 0xFFFFu;
        uint4* hs = p.s->HS + rank * 72 + ln;
        str128(hs, wr[0], wr[1], wr[2], wr[3]); str128(hs + 32, wr[4], wr[5], wr[6], wr[7]); str32((uint32_t*)(hs + 64) - ln * 3, wr[8]);
        str128(hs + 576, hw[0], hw[1], hw[2], hw[3]); str128(hs + 608, hw[4], hw[5], hw[6], hw[7]); str32((uint32_t*)(hs + 640) - ln * 3, hw[8]);
        if (ln == 0) str32(&p.s->HS[1152 + rank], key);
        rank = 16;
      }
      if ((int)(cnt >> 16) + base + X_G >= 8) break;
    }
    TS(8);
    if (warp < (five ? 12 : 15)) {
#pragma unroll
      for (int k = X_WS; k < 12; k++) ldsm4t(wabase + k * 16 * pitch, wa[k][0], wa[k][1], wa[k][2], wa[k][3]);
    }
    if (warp < 6) while ((int)(clock() - tpub) < X_HD) {}
    TS(19);
    if (warp < 6) { ha[0] = ldr128(hsrc); ha[1] = ldr128(hsrc + 24); ha[2] = ldr128(hsrc + 48); }
    if (rank < X_OR) OUT_ROW
  }
  uint32_t wd[10][4];
  const uint32_t xb = keep(OFF_XS + (ln & 7) * 1168 + (fk * 24 + (ln >> 3)) * 16);
  if (warp >= 7) {
    const uint32_t db = down_box(warp - 7, five) + (ln & 7) * 128;
    mbar_wait(MB_D);
#pragma unroll
    for (int j = 0; j < 4; j++) {
      const uint32_t a = db + (ln >> 4) * 1024 + (((2 * j + ((ln >> 3) & 1)) ^ (ln & 7)) << 4);
      ldsm4t(a, wd[j][0], wd[j][1], wd[j][2], wd[j][3]);
      ldsm4t(a + 2048, wd[4 + j][0], wd[4 + j][1], wd[4 + j][2], wd[4 + j][3]);
    }
#pragma unroll
    for (int j = 0; j < 2; j++) ldsm4t(db + 4096 + (((4 * j + (ln >> 3)) ^ (ln & 7)) << 4), wd[8 + j][0], wd[8 + j][1], wd[8 + j][2], wd[8 + j][3]);
  } else if (warp < 6) {
    const uint32_t xs = keep(OFF_XS + (td + (td / 24) * 49) * 16);
#pragma unroll 1
    for (int it = 0; it < SPIN_MAX; it++) {
      const bool bad = max(max(max(ha[0].x, ha[1].x), max(ha[2].x, ha[2].y)), max(ha[2].z, ha[2].w)) == ~0u;
      if (!__any_sync(0xffffffffu, bad)) break;
      if (bad) { ha[0] = ldr128(hsrc); ha[1] = ldr128(hsrc + 24); ha[2] = ldr128(hsrc + 48); }
    }
#pragma unroll
    for (int q = 0; q < 3; q++) sts128(xs + q * 384, ha[q].x, ha[q].y, ha[q].z, ha[q].w);
  }
  bar_sync(0, 512);
  TS(9);

  if (warp < (five ? 12 : 15)) {
    float d0[4] = {0.f, 0.f, 0.f, 0.f}, d1[4] = {0.f, 0.f, 0.f, 0.f};
#pragma unroll
    for (int k = 0; k < 12; k += 2) {
      uint32_t b0, b1, b2, b3;
      ldsm4(xb + k * 32, b0, b1, b2, b3);
      mma_bf16(d0, wa[k][0], wa[k][1], wa[k][2], wa[k][3], b0, b1);
      mma_bf16(d1, wa[k + 1][0], wa[k + 1][1], wa[k + 1][2], wa[k + 1][3], b2, b3);
    }
    sts128(OFF_RED + td * 16, __float_as_uint(d0[0] + d1[0]), __float_as_uint(d0[1] + d1[1]), __float_as_uint(d0[2] + d1[2]), __float_as_uint(d0[3] + d1[3]));
  }
  TS(26);
  if (warp < 5) {
    const uint32_t rb = OFF_RED + warp * 1536 + ln * 16;
    bar_sync(9, 512);
    const uint4 pa = lds128(rb), pb = lds128(rb + 512), pc = lds128(rb + 1024);
    const float ga = bfr(__uint_as_float(pa.x) + __uint_as_float(pb.x) + __uint_as_float(pc.x));
    const float gb = bfr(__uint_as_float(pa.y) + __uint_as_float(pb.y) + __uint_as_float(pc.y));
    const uint32_t uu = pack_bf(__uint_as_float(pa.z) + __uint_as_float(pb.z) + __uint_as_float(pc.z), __uint_as_float(pa.w) + __uint_as_float(pb.w) + __uint_as_float(pc.w));
    float ra, rb2;
    asm("rcp.approx.ftz.f32 %0, %1;" : "=f"(ra) : "f"(1.f + ex2(ga * -1.4426950408889634f)));
    asm("rcp.approx.ftz.f32 %0, %1;" : "=f"(rb2) : "f"(1.f + ex2(gb * -1.4426950408889634f)));
    const uint32_t act = bf_mul2(pack_bf(ga * ra, gb * rb2), uu);
    sts32(OFF_ACT + td * 4, act);
  } else bar_arrive(9, 512);
  uint4* dst = &p.s->X[c * DM * 2 + (warp - 7) * 64 + tt * 8 + gg];
  asm volatile("" : "+l"(dst));
  bar_sync(8, 512);
  tpub = clock();
  if (warp >= 7) {
    uint32_t b0, b1, b2, b3, b4;
    ldsm4t(OFF_ACT + ln * 16, b0, b1, b2, b3);
    asm volatile("ldmatrix.sync.aligned.m8n8.x1.trans.shared.b16 {%0}, [%1];" : "=r"(b4) : "r"(OFF_ACT + 512 + ln * 16) : "memory");
    float y[4][4];
#pragma unroll
    for (int j = 0; j < 4; j++) {
      y[j][0] = y[j][1] = y[j][2] = y[j][3] = 0.f;
      mma_bf16(y[j], wd[j][0], wd[j][1], wd[j][2], wd[j][3], b0, b1);
    }
#pragma unroll
    for (int j = 0; j < 4; j++) mma_bf16(y[j], wd[4 + j][0], wd[4 + j][1], wd[4 + j][2], wd[4 + j][3], b2, b3);
    if (!five) {
#pragma unroll
      for (int j = 0; j < 4; j++) mma_bf16_k8(y[j], wd[8 + (j >> 1)][2 * (j & 1)], wd[8 + (j >> 1)][2 * (j & 1) + 1], b4);
    }
    str128(dst, (pack_bf(y[0][0], y[0][1]) & ~1u) | 0x10000u, pack_bf(y[0][2], y[0][3]), pack_bf(y[1][0], y[1][1]), pack_bf(y[1][2], y[1][3]));
    str128(dst + 32, (pack_bf(y[2][0], y[2][1]) & ~1u) | 0x10000u, pack_bf(y[2][2], y[2][3]), pack_bf(y[3][0], y[3][1]), pack_bf(y[3][2], y[3][3]));
  }
  TS(10);

  if (c < 72) {
    const uint4* src = &p.s->X[(warp * 4 + tt) * (DM * 2) + c * 8 + gg];
    const int slot = (c & 3) * 2 + (ln >> 4), dw = (c >> 2) * 16 + (ln & 15);
    uint32_t hv = 0, kv = 0, res = 0, rs2 = 0;
    uint32_t* o = p.out;
    if (warp == 0) {
      hv = ~0u;
      SPIN_WHILE(max(hv, kv) == ~0u, hv = ldr32((const uint32_t*)p.s->HS + 2304 + slot * 288 + dw); kv = ldr32(&p.s->HS[1152 + slot]));
      const float r = bf_hi(kv ^ (((int)~kv >> 31) | 0x80000000u));
      float rs;
      asm("rcp.approx.ftz.f32 %0, %1;" : "=f"(rs) : "f"(1.f + ex2(r * -1.4426950408889634f)));
      rs2 = keep(pack_bf(rs, rs));
      res = lds32(OFF_XS + slot * 1168 + dw * 4);
      o += (2047 - (int)(kv & 2047u)) * 288 + dw;
      asm volatile("" : "+l"(o));
    }
    const uint32_t sel = (gg & 1) ? 0x3F800000u : 0x00003F80u;
    const uint32_t q0 = keep((gg >> 1) == 0 ? sel : 0u), q1 = keep((gg >> 1) == 1 ? sel : 0u), q2 = keep((gg >> 1) == 2 ? sel : 0u), q3 = keep((gg >> 1) == 3 ? sel : 0u);
    const uint32_t fa = keep(OFF_FIN + warp * 256 + (gg & 1) * 128 + (gg >> 1) * 32 + tt * 8), fb = keep(OFF_FIN + ln * 8);
    uint4 a0 = make_uint4(0, 0, 0, 0), a1 = a0;
    while ((int)(clock() - tpub) < X_PD) {}
    SPIN_WHILE(!(a0.x & a1.x & 0x10000u), if (!(a0.x & 0x10000u)) a0 = ldr128(src); if (!(a1.x & 0x10000u)) a1 = ldr128(src + 64 * DM * 2));
    float d[4] = {0.f, 0.f, 0.f, 0.f}, e[4] = {0.f, 0.f, 0.f, 0.f};
    mma_bf16(d, q0, q2, q1, q3, a0.x, a0.y); mma_bf16(e, q0, q2, q1, q3, a0.z, a0.w);
    mma_bf16(d, q0, q2, q1, q3, a1.x, a1.y); mma_bf16(e, q0, q2, q1, q3, a1.z, a1.w);
    sts64(fa, __float_as_uint(d[0] + e[2]), __float_as_uint(d[1] + e[3]));
    TS(11);
    if (warp == 0) {
      bar_sync(0, 512);
      float2 s[16];
#pragma unroll
      for (int i = 0; i < 16; i++) { const uint2 q = lds64(fb + i * 256); s[i] = make_float2(__uint_as_float(q.x), __uint_as_float(q.y)); }
#pragma unroll
      for (int k = 1; k < 16; k *= 2)
#pragma unroll
        for (int i = 0; i < 16; i += 2 * k) { s[i].x += s[i + k].x; s[i].y += s[i + k].y; }
      *o = bf_add2(hv, bf_add2(res, bf_mul2(pack_bf(s[0].x, s[0].y), rs2)));
    } else bar_arrive(0, 512);
  }
  TS(12);
  TS_DUMP();
}

typedef CUresult (*EncodeFn)(CUtensorMap*, CUtensorMapDataType, cuuint32_t, void*, const cuuint64_t*, const cuuint64_t*, const cuuint32_t*,
                             const cuuint32_t*, CUtensorMapInterleave, CUtensorMapSwizzle, CUtensorMapL2promotion, CUtensorMapFloatOOBfill);

}

extern "C" void kernel_launch(void* const* d_in, const int* in_sizes, int n_in, void* d_out, int out_size) {
  (void)in_sizes; (void)n_in; (void)out_size;
  static EncodeFn enc = nullptr;
  static Scratch* scratch = nullptr;
  if (!enc) {
    void* fn = nullptr;
    cudaDriverEntryPointQueryResult qr;
    cudaGetDriverEntryPoint("cuTensorMapEncodeTiled", &fn, cudaEnableDefault, &qr);
    enc = (EncodeFn)fn;
    cudaGetSymbolAddress((void**)&scratch, g_S);
    cudaFuncSetAttribute(fused_kernel<false>, cudaFuncAttributeMaxDynamicSharedMemorySize, SMEM_BYTES);
    cudaFuncSetAttribute(fused_kernel<true>, cudaFuncAttributeMaxDynamicSharedMemorySize, SMEM_BYTES);
  }
  TMaps tm;
  for (int i = 0; i < 6; i++) {
    const bool dn = i % 3 == 2;
    const cuuint32_t w = i < 3 ? 40 : 32;
    cuuint64_t gd[3] = {(cuuint64_t)(dn ? 64 : FF), (cuuint64_t)(dn ? FF : DM), 9};
    cuuint64_t gs[2] = {(cuuint64_t)(dn ? DM * 2 : FF * 2), 128};
    cuuint32_t bx[3] = {dn ? 64 : w, dn ? w : 96, i < 3 ? 2u : 3u};
    cuuint32_t es[3] = {1, 1, 1};
    enc(&tm.m[i], CU_TENSOR_MAP_DATA_TYPE_BFLOAT16, dn ? 3 : 2, d_in[11 + i % 3], gd, gs, bx, es, CU_TENSOR_MAP_INTERLEAVE_NONE,
        dn ? CU_TENSOR_MAP_SWIZZLE_128B : i < 3 ? CU_TENSOR_MAP_SWIZZLE_NONE : CU_TENSOR_MAP_SWIZZLE_64B,
        (CUtensorMapL2promotion)X_PROMO, CU_TENSOR_MAP_FLOAT_OOB_FILL_NONE);
  }
  for (int i = 6; i < 10; i++) {
    cuuint64_t gd[3] = {i < 8 ? 32u : 16u, i < 8 ? DM / 2u : DM, NCTA};
    cuuint64_t gs[2] = {i < 8 ? 64u : 32u, DM * 32};
    cuuint32_t bx[3] = {32, 1, (i & 1) ? 128u : 136u};
    cuuint32_t es[3] = {1, 1, 1};
    enc(&tm.m[i], CU_TENSOR_MAP_DATA_TYPE_FLOAT16, 3, scratch->X, gd, gs, bx, es, CU_TENSOR_MAP_INTERLEAVE_NONE, CU_TENSOR_MAP_SWIZZLE_64B,
        CU_TENSOR_MAP_L2_PROMOTION_NONE, CU_TENSOR_MAP_FLOAT_OOB_FILL_NONE);
  }
  Params p;
  p.x = (const unsigned char*)d_in[0];
  bool far = false;
  for (int i = 0; i < 7; i++) {
    p.far[i] = (const unsigned char*)d_in[1 + i];
    const long long d = (long long)((intptr_t)d_in[1 + i] - (intptr_t)d_in[0]);
    p.off[i] = (int)(d / 16);
    if ((long long)p.off[i] * 16 != d) far = true;
  }
  p.dskip = (const uint16_t*)d_in[8];
  p.w_r = (const uint32_t*)d_in[10];
  for (int f = 0; f < 2; f++) {
    static const int kind[17] = {0, 0, 0, 0, 2, 2, 0, 0, 1, 1, 1, 1, 1, 1, 2, 2, 2};
    static const int idx[2][17] = {{2, 3, 4, 5, 6, 8, 0, 1, 0, 1, 2, 3, 4, 5, 0, 2, 4}, {2, 3, 4, 5, 0, -1, 0, 1, 0, 1, 2, 3, 4, 5, 3, -1, 6}};
    static const int blk[2][17] = {{-1, -1, -1, -1, 0, -1, 4, -1, 1, -1, 2, -1, 3, -1, 16, -1, -1}, {-1, -1, -1, -1, 1, -1, 4, -1, -1, -1, 2, -1, 3, -1, 16, -1, -1}};
    const int pitch = f ? 64 : 80;
    for (int u = 0; u < 17; u++) {
      const int s = idx[f][u];
      const uint32_t dst = kind[u] == 0 ? OFF_G + s * 96 * pitch : kind[u] == 2 ? down_box(s, f) : OFF_W + W_BYTES + (s >> 1) * W_BYTES + (s & 1) * 96 * pitch;
      const uint32_t mb = u >= 14 ? (u >= X_HU ? MB_H - OFF_MISC : X_HB) : blk[f][u] >= 0 ? MB_KF - OFF_MISC + blk[f][u] * 8 : 0;
      p.sched[f][u] = s < 0 ? 3u : kind[u] | s << 2 | mb << 6 | dst << 14;
    }
  }
  p.out = (uint32_t*)d_out;
  p.zero = 0;
  p.ts = nullptr;
  p.s = scratch;
  if (far) { fused_kernel<true><<<NCTA, NT, SMEM_BYTES, cudaStreamPerThread>>>(p, tm); return; }
  fused_kernel<false><<<NCTA, NT, SMEM_BYTES, cudaStreamPerThread>>>(p, tm);
}
```

```cpp
#include <cuda_runtime.h>
#include <cuda.h>
#include <cuda_bf16.h>
#include <cuda_fp16.h>
#include <stdint.h>
#include <stddef.h>

namespace {

constexpr int NCTA = 128;
constexpr int NT = 640;
constexpr int DM = 576;
constexpr int FF = 4608;
constexpr int SPIN_MAX = 1 << 20;

struct Scratch {
  uint4 X[NCTA * DM * 2];
  uint4 KX[64 * 128];
  uint4 HS[1152 + 8];
  uint4 R[256];
  uint4 SC[256];
  uint32_t FLAG[NCTA * 8];
};
__device__ Scratch g_S;

#define CLKS(i)
#define TS(i)
#define TSX(i)
#define TS_DUMP()

constexpr int SB = 1024;
constexpr int BOX = 15360;
constexpr int OFF_G = SB;
constexpr int OFF_W = OFF_G + 3 * BOX;
constexpr int W_KT = 26624;
constexpr int W_L3 = W_KT + 4416;
constexpr int W_CW = W_L3 + 4096;
constexpr int W_MISC = W_CW + 640;
constexpr int W_BYTES = 35840;
constexpr int TILE = 10240;
constexpr int OFF_T = OFF_W + 4 * W_BYTES;
constexpr int ALT = TILE - W_KT;
static_assert(W_MISC + 32 <= W_BYTES && OFF_W % 1024 == 0 && W_BYTES % 1024 == 0 && W_BYTES + ALT <= 20480, "wg block");
constexpr int YT_PITCH = 1184;
constexpr int OFF_YT = OFF_T + 2 * TILE;
constexpr int OFF_WR = OFF_YT + 16 * YT_PITCH + 64;
constexpr int OFF_MISC = OFF_WR + 2304;
constexpr int SMEM_BYTES = OFF_MISC + 1024 - SB;
static_assert(OFF_YT % 16 == 0 && OFF_MISC % 16 == 0, "align");
static_assert(SMEM_BYTES <= 232448, "smem");
constexpr int MB_GU = OFF_MISC;
constexpr int MB_D = OFF_MISC + 8;
constexpr int MB_KF = OFF_MISC + 16;
constexpr int MB_GF = OFF_MISC + 48;
constexpr int MB_SC = OFF_MISC + 56;
constexpr int MB_UL = OFF_MISC + 64;
constexpr int MB_REL = OFF_MISC + 104;
constexpr int MB_GO = OFF_MISC + 112;
constexpr int MB_H = MB_KF + 128;
constexpr int MISC_EPOCH = OFF_MISC + 152;
constexpr int MISC_SW = OFF_MISC + 156;
constexpr int MISC_RT = OFF_MISC + 160;
constexpr int MISC_T0 = OFF_MISC + 296;
constexpr int MISC_EM = OFF_MISC + 288;
constexpr int OFF_PART = OFF_W + 20480;
constexpr int OFF_RK = OFF_PART + 3840;
constexpr int MISC_LN1 = OFF_MISC + 192;
constexpr int OFF_XS = OFF_T;
constexpr int OFF_RED = OFF_T + TILE;
constexpr int OFF_FIN = OFF_W + 3 * W_BYTES + W_KT;
constexpr int OFF_ACT = OFF_FIN + 4096;
constexpr int MISC_CNT = OFF_ACT + 1024;

__device__ __forceinline__ uint32_t smem_u32(const void* p) { return (uint32_t)__cvta_generic_to_shared(p); }
__device__ __forceinline__ uint32_t lds32(uint32_t a) { uint32_t v; asm volatile("ld.shared.b32 %0, [%1];" : "=r"(v) : "r"(a) : "memory"); return v; }
__device__ __forceinline__ uint32_t lds16(uint32_t a) { uint16_t v; asm volatile("ld.shared.u16 %0, [%1];" : "=h"(v) : "r"(a) : "memory"); return v; }
__device__ __forceinline__ uint2 lds64(uint32_t a) { uint2 v; asm volatile("ld.shared.v2.b32 {%0,%1}, [%2];" : "=r"(v.x), "=r"(v.y) : "r"(a) : "memory"); return v; }
__device__ __forceinline__ uint4 lds128(uint32_t a) { uint4 v; asm volatile("ld.shared.v4.b32 {%0,%1,%2,%3}, [%4];" : "=r"(v.x), "=r"(v.y), "=r"(v.z), "=r"(v.w) : "r"(a) : "memory"); return v; }
__device__ __forceinline__ void sts16(uint32_t a, uint32_t v) { asm volatile("st.shared.u16 [%0], %1;" :: "r"(a), "h"((uint16_t)v) : "memory"); }
__device__ __forceinline__ void sts32(uint32_t a, uint32_t v) { asm volatile("st.shared.b32 [%0], %1;" :: "r"(a), "r"(v) : "memory"); }
__device__ __forceinline__ void sts64(uint32_t a, uint32_t x, uint32_t y) { asm volatile("st.shared.v2.b32 [%0], {%1,%2};" :: "r"(a), "r"(x), "r"(y) : "memory"); }
__device__ __forceinline__ void sts128(uint32_t a, uint32_t x, uint32_t y, uint32_t z, uint32_t w) { asm volatile("st.shared.v4.b32 [%0], {%1,%2,%3,%4};" :: "r"(a), "r"(x), "r"(y), "r"(z), "r"(w) : "memory"); }
__device__ __forceinline__ void ldsm4(uint32_t a, uint32_t& r0, uint32_t& r1, uint32_t& r2, uint32_t& r3) {
  asm volatile("ldmatrix.sync.aligned.m8n8.x4.shared.b16 {%0,%1,%2,%3}, [%4];" : "=r"(r0), "=r"(r1), "=r"(r2), "=r"(r3) : "r"(a) : "memory");
}
__device__ __forceinline__ void ldsm2(uint32_t a, uint32_t& r0, uint32_t& r1) {
  asm volatile("ldmatrix.sync.aligned.m8n8.x2.shared.b16 {%0,%1}, [%2];" : "=r"(r0), "=r"(r1) : "r"(a) : "memory");
}
__device__ __forceinline__ void ldsm4t(uint32_t a, uint32_t& r0, uint32_t& r1, uint32_t& r2, uint32_t& r3) {
  asm volatile("ldmatrix.sync.aligned.m8n8.x4.trans.shared.b16 {%0,%1,%2,%3}, [%4];" : "=r"(r0), "=r"(r1), "=r"(r2), "=r"(r3) : "r"(a) : "memory");
}
__device__ __forceinline__ void stsm4t(uint32_t a, uint32_t r0, uint32_t r1, uint32_t r2, uint32_t r3) {
  asm volatile("stmatrix.sync.aligned.m8n8.x4.trans.shared.b16 [%0], {%1,%2,%3,%4};" :: "r"(a), "r"(r0), "r"(r1), "r"(r2), "r"(r3) : "memory");
}
__device__ __forceinline__ uint4 ldr128(const void* p) {
  unsigned long long lo, hi;
  asm volatile("{ .reg .b128 t; ld.relaxed.gpu.global.b128 t, [%2]; mov.b128 {%0, %1}, t; }" : "=l"(lo), "=l"(hi) : "l"(p) : "memory");
  return make_uint4((uint32_t)lo, (uint32_t)(lo >> 32), (uint32_t)hi, (uint32_t)(hi >> 32));
}
__device__ __forceinline__ void str128(void* p, uint32_t x, uint32_t y, uint32_t z, uint32_t w) {
  asm volatile("{ .reg .b128 t; .reg .b64 lo, hi; mov.b64 lo, {%1,%2}; mov.b64 hi, {%3,%4}; mov.b128 t, {lo, hi}; st.relaxed.gpu.global.b128 [%0], t; }"
               :: "l"(p), "r"(x), "r"(y), "r"(z), "r"(w) : "memory");
}
__device__ __forceinline__ void str64(void* p, uint32_t x, uint32_t y) {
  asm volatile("{ .reg .b64 t; mov.b64 t, {%1,%2}; st.relaxed.gpu.global.b64 [%0], t; }" :: "l"(p), "r"(x), "r"(y) : "memory");
}
__device__ __forceinline__ uint32_t ldr32(const void* p) { uint32_t v; asm volatile("ld.relaxed.gpu.global.b32 %0, [%1];" : "=r"(v) : "l"(p) : "memory"); return v; }
__device__ __forceinline__ void str32(void* p, uint32_t v) { asm volatile("st.relaxed.gpu.global.b32 [%0], %1;" :: "l"(p), "r"(v) : "memory"); }
__device__ __forceinline__ void str16(void* p, uint32_t v) { asm volatile("st.relaxed.gpu.global.u16 [%0], %1;" :: "l"(p), "h"((uint16_t)v) : "memory"); }
__device__ __forceinline__ void fence_gpu() { asm volatile("fence.acq_rel.gpu;" ::: "memory"); }
__device__ __forceinline__ void bar_sync(int id, int n) { asm volatile("bar.sync %0, %1;" :: "r"(id), "r"(n) : "memory"); }
__device__ __forceinline__ void bar_arrive(int id, int n) { asm volatile("bar.arrive %0, %1;" :: "r"(id), "r"(n) : "memory"); }

__device__ __forceinline__ float bf_lo(uint32_t w) { return __uint_as_float(w << 16); }
__device__ __forceinline__ float bf_hi(uint32_t w) { return __uint_as_float(w & 0xFFFF0000u); }
__device__ __forceinline__ uint32_t pack_bf(float lo, float hi) { uint32_t r; asm("cvt.rn.bf16x2.f32 %0, %1, %2;" : "=r"(r) : "f"(hi), "f"(lo)); return r; }
__device__ __forceinline__ uint32_t pack_h(float lo, float hi) { uint32_t r; asm("cvt.rn.f16x2.f32 %0, %1, %2;" : "=r"(r) : "f"(hi), "f"(lo)); return r; }
__device__ __forceinline__ uint32_t pack_hv(float lo, float hi) { uint32_t r; asm volatile("cvt.rn.f16x2.f32 %0, %1, %2;" : "=r"(r) : "f"(hi), "f"(lo) : "memory"); return r; }
__device__ __forceinline__ float bfr(float x) { return bf_lo(pack_bf(x, 0.f)); }
__device__ __forceinline__ uint32_t bf_sub2(uint32_t a, uint32_t b) { __nv_bfloat162 r = __hsub2(*(__nv_bfloat162*)&a, *(__nv_bfloat162*)&b); return *(uint32_t*)&r; }
__device__ __forceinline__ uint32_t bf_add2(uint32_t a, uint32_t b) { __nv_bfloat162 r = __hadd2(*(__nv_bfloat162*)&a, *(__nv_bfloat162*)&b); return *(uint32_t*)&r; }
__device__ __forceinline__ uint32_t bf_mul2(uint32_t a, uint32_t b) { __nv_bfloat162 r = __hmul2(*(__nv_bfloat162*)&a, *(__nv_bfloat162*)&b); return *(uint32_t*)&r; }
__device__ __forceinline__ float2 h2f(uint32_t w) { return __half22float2(*(__half2*)&w); }
__device__ __forceinline__ float ex2(float x) { float r; asm("ex2.approx.ftz.f32 %0, %1;" : "=f"(r) : "f"(x)); return r; }
__device__ __forceinline__ float warp_sum(float v) {
#pragma unroll
  for (int o = 16; o > 0; o >>= 1) v += __shfl_xor_sync(0xffffffffu, v, o);
  return v;
}
__device__ __forceinline__ void mma_f16_f32(float* d, uint32_t a0, uint32_t a1, uint32_t a2, uint32_t a3, uint32_t b0, uint32_t b1) {
  asm volatile("mma.sync.aligned.m16n8k16.row.col.f32.f16.f16.f32 {%0,%1,%2,%3}, {%4,%5,%6,%7}, {%8,%9}, {%0,%1,%2,%3};"
               : "+f"(d[0]), "+f"(d[1]), "+f"(d[2]), "+f"(d[3]) : "r"(a0), "r"(a1), "r"(a2), "r"(a3), "r"(b0), "r"(b1));
}
__device__ __forceinline__ void mma_f16_f16(uint32_t& d0, uint32_t& d1, uint32_t a0, uint32_t a1, uint32_t a2, uint32_t a3, uint32_t b0, uint32_t b1) {
  asm volatile("mma.sync.aligned.m16n8k16.row.col.f16.f16.f16.f16 {%0,%1}, {%2,%3,%4,%5}, {%6,%7}, {%0,%1};"
               : "+r"(d0), "+r"(d1) : "r"(a0), "r"(a1), "r"(a2), "r"(a3), "r"(b0), "r"(b1));
}
__device__ __forceinline__ void mma_bf16(float* d, uint32_t a0, uint32_t a1, uint32_t a2, uint32_t a3, uint32_t b0, uint32_t b1) {
  asm volatile("mma.sync.aligned.m16n8k16.row.col.f32.bf16.bf16.f32 {%0,%1,%2,%3}, {%4,%5,%6,%7}, {%8,%9}, {%0,%1,%2,%3};"
               : "+f"(d[0]), "+f"(d[1]), "+f"(d[2]), "+f"(d[3]) : "r"(a0), "r"(a1), "r"(a2), "r"(a3), "r"(b0), "r"(b1));
}
__device__ __forceinline__ void mma_bf16_k8(float* d, uint32_t a0, uint32_t a1, uint32_t b0) {
  asm volatile("mma.sync.aligned.m16n8k8.row.col.f32.bf16.bf16.f32 {%0,%1,%2,%3}, {%4,%5}, {%6}, {%0,%1,%2,%3};"
               : "+f"(d[0]), "+f"(d[1]), "+f"(d[2]), "+f"(d[3]) : "r"(a0), "r"(a1), "r"(b0));
}

__device__ __forceinline__ void wg_fence() { asm volatile("wgmma.fence.sync.aligned;" ::: "memory"); }
__device__ __forceinline__ void wg_commit() { asm volatile("wgmma.commit_group.sync.aligned;" ::: "memory"); }
template <int N> __device__ __forceinline__ void wg_wait() { asm volatile("wgmma.wait_group.sync.aligned %0;" :: "n"(N) : "memory"); }
template <int TB> __device__ __forceinline__ void wgmma32(float* d, const uint32_t* a, uint32_t dlo, uint32_t dhi) {
  asm volatile("{ .reg .b64 dd; mov.b64 dd, {%20, %21}; wgmma.mma_async.sync.aligned.m64n32k16.f32.f16.f16 "
               "{%0,%1,%2,%3,%4,%5,%6,%7,%8,%9,%10,%11,%12,%13,%14,%15}, {%16,%17,%18,%19}, dd, 1, 1, 1, %22; }"
               : "+f"(d[0]), "+f"(d[1]), "+f"(d[2]), "+f"(d[3]), "+f"(d[4]), "+f"(d[5]), "+f"(d[6]), "+f"(d[7]), "+f"(d[8]), "+f"(d[9]), "+f"(d[10]), "+f"(d[11]), "+f"(d[12]), "+f"(d[13]), "+f"(d[14]), "+f"(d[15])
               : "r"(a[0]), "r"(a[1]), "r"(a[2]), "r"(a[3]), "r"(dlo), "r"(dhi), "n"(TB));
}
template <int TB> __device__ __forceinline__ void wgmma64(float* d, const uint32_t* a, uint32_t dlo, uint32_t dhi) {
  asm volatile("{ .reg .b64 dd; mov.b64 dd, {%36, %37}; wgmma.mma_async.sync.aligned.m64n64k16.f32.f16.f16 "
               "{%0,%1,%2,%3,%4,%5,%6,%7,%8,%9,%10,%11,%12,%13,%14,%15,%16,%17,%18,%19,%20,%21,%22,%23,%24,%25,%26,%27,%28,%29,%30,%31}, {%32,%33,%34,%35}, dd, 1, 1, 1, %38; }"
               : "+f"(d[0]), "+f"(d[1]), "+f"(d[2]), "+f"(d[3]), "+f"(d[4]), "+f"(d[5]), "+f"(d[6]), "+f"(d[7]), "+f"(d[8]), "+f"(d[9]), "+f"(d[10]), "+f"(d[11]), "+f"(d[12]), "+f"(d[13]), "+f"(d[14]), "+f"(d[15]), "+f"(d[16]), "+f"(d[17]), "+f"(d[18]), "+f"(d[19]), "+f"(d[20]), "+f"(d[21]), "+f"(d[22]), "+f"(d[23]), "+f"(d[24]), "+f"(d[25]), "+f"(d[26]), "+f"(d[27]), "+f"(d[28]), "+f"(d[29]), "+f"(d[30]), "+f"(d[31])
               : "r"(a[0]), "r"(a[1]), "r"(a[2]), "r"(a[3]), "r"(dlo), "r"(dhi), "n"(TB));
}
template <int TB> __device__ __forceinline__ void wgmma64_init(float* d, const uint32_t* a, uint32_t dlo, uint32_t dhi) {
  asm volatile("{ .reg .b64 dd; mov.b64 dd, {%36, %37}; wgmma.mma_async.sync.aligned.m64n64k16.f32.f16.f16 "
               "{%0,%1,%2,%3,%4,%5,%6,%7,%8,%9,%10,%11,%12,%13,%14,%15,%16,%17,%18,%19,%20,%21,%22,%23,%24,%25,%26,%27,%28,%29,%30,%31}, {%32,%33,%34,%35}, dd, 0, 1, 1, %38; }"
               : "=f"(d[0]), "=f"(d[1]), "=f"(d[2]), "=f"(d[3]), "=f"(d[4]), "=f"(d[5]), "=f"(d[6]), "=f"(d[7]), "=f"(d[8]), "=f"(d[9]), "=f"(d[10]), "=f"(d[11]), "=f"(d[12]), "=f"(d[13]), "=f"(d[14]), "=f"(d[15]), "=f"(d[16]), "=f"(d[17]), "=f"(d[18]), "=f"(d[19]), "=f"(d[20]), "=f"(d[21]), "=f"(d[22]), "=f"(d[23]), "=f"(d[24]), "=f"(d[25]), "=f"(d[26]), "=f"(d[27]), "=f"(d[28]), "=f"(d[29]), "=f"(d[30]), "=f"(d[31])
               : "r"(a[0]), "r"(a[1]), "r"(a[2]), "r"(a[3]), "r"(dlo), "r"(dhi), "n"(TB));
}
template <int TB> __device__ __forceinline__ void wgmma32_init(float* d, const uint32_t* a, uint32_t dlo, uint32_t dhi) {
  asm volatile("{ .reg .b64 dd; mov.b64 dd, {%20, %21}; wgmma.mma_async.sync.aligned.m64n32k16.f32.f16.f16 "
               "{%0,%1,%2,%3,%4,%5,%6,%7,%8,%9,%10,%11,%12,%13,%14,%15}, {%16,%17,%18,%19}, dd, 0, 1, 1, %22; }"
               : "=f"(d[0]), "=f"(d[1]), "=f"(d[2]), "=f"(d[3]), "=f"(d[4]), "=f"(d[5]), "=f"(d[6]), "=f"(d[7]), "=f"(d[8]), "=f"(d[9]), "=f"(d[10]), "=f"(d[11]), "=f"(d[12]), "=f"(d[13]), "=f"(d[14]), "=f"(d[15])
               : "r"(a[0]), "r"(a[1]), "r"(a[2]), "r"(a[3]), "r"(dlo), "r"(dhi), "n"(TB));
}
__device__ __forceinline__ void wgmma64h(uint32_t* d, uint32_t a0, uint32_t a1, uint32_t a2, uint32_t a3, uint32_t dlo, uint32_t dhi) {
  asm volatile("{ .reg .b64 dd; mov.b64 dd, {%20, %21}; wgmma.mma_async.sync.aligned.m64n64k16.f16.f16.f16 "
               "{%0,%1,%2,%3,%4,%5,%6,%7,%8,%9,%10,%11,%12,%13,%14,%15}, {%16,%17,%18,%19}, dd, 1, 1, 1, 0; }"
               : "+r"(d[0]), "+r"(d[1]), "+r"(d[2]), "+r"(d[3]), "+r"(d[4]), "+r"(d[5]), "+r"(d[6]), "+r"(d[7]), "+r"(d[8]), "+r"(d[9]), "+r"(d[10]), "+r"(d[11]), "+r"(d[12]), "+r"(d[13]), "+r"(d[14]), "+r"(d[15])
               : "r"(a0), "r"(a1), "r"(a2), "r"(a3), "r"(dlo), "r"(dhi));
}
__device__ __forceinline__ void wgmma64h_init(uint32_t* d, uint32_t a0, uint32_t a1, uint32_t a2, uint32_t a3, uint32_t dlo, uint32_t dhi) {
  asm volatile("{ .reg .b64 dd; mov.b64 dd, {%20, %21}; wgmma.mma_async.sync.aligned.m64n64k16.f16.f16.f16 "
               "{%0,%1,%2,%3,%4,%5,%6,%7,%8,%9,%10,%11,%12,%13,%14,%15}, {%16,%17,%18,%19}, dd, 0, 1, 1, 0; }"
               : "=r"(d[0]), "=r"(d[1]), "=r"(d[2]), "=r"(d[3]), "=r"(d[4]), "=r"(d[5]), "=r"(d[6]), "=r"(d[7]), "=r"(d[8]), "=r"(d[9]), "=r"(d[10]), "=r"(d[11]), "=r"(d[12]), "=r"(d[13]), "=r"(d[14]), "=r"(d[15])
               : "r"(a0), "r"(a1), "r"(a2), "r"(a3), "r"(dlo), "r"(dhi));
}
__device__ __forceinline__ void wgmma40_ss(float* d, uint32_t alo, uint32_t blo, uint32_t hi) {
  asm volatile("{ .reg .b64 da, db; mov.b64 da, {%20, %22}; mov.b64 db, {%21, %22}; "
               "wgmma.mma_async.sync.aligned.m64n40k16.f32.f16.f16 {%0,%1,%2,%3,%4,%5,%6,%7,%8,%9,%10,%11,%12,%13,%14,%15,%16,%17,%18,%19}, da, db, 1, 1, 1, 1, 1; }"
               : "+f"(d[0]), "+f"(d[1]), "+f"(d[2]), "+f"(d[3]), "+f"(d[4]), "+f"(d[5]), "+f"(d[6]), "+f"(d[7]), "+f"(d[8]), "+f"(d[9]), "+f"(d[10]), "+f"(d[11]), "+f"(d[12]), "+f"(d[13]), "+f"(d[14]), "+f"(d[15]), "+f"(d[16]), "+f"(d[17]), "+f"(d[18]), "+f"(d[19])
               : "r"(alo), "r"(blo), "r"(hi));
}
__device__ __forceinline__ void wgmma40_ss_init(float* d, uint32_t alo, uint32_t blo, uint32_t hi) {
  asm volatile("{ .reg .b64 da, db; mov.b64 da, {%20, %22}; mov.b64 db, {%21, %22}; "
               "wgmma.mma_async.sync.aligned.m64n40k16.f32.f16.f16 {%0,%1,%2,%3,%4,%5,%6,%7,%8,%9,%10,%11,%12,%13,%14,%15,%16,%17,%18,%19}, da, db, 0, 1, 1, 1, 1; }"
               : "=f"(d[0]), "=f"(d[1]), "=f"(d[2]), "=f"(d[3]), "=f"(d[4]), "=f"(d[5]), "=f"(d[6]), "=f"(d[7]), "=f"(d[8]), "=f"(d[9]), "=f"(d[10]), "=f"(d[11]), "=f"(d[12]), "=f"(d[13]), "=f"(d[14]), "=f"(d[15]), "=f"(d[16]), "=f"(d[17]), "=f"(d[18]), "=f"(d[19])
               : "r"(alo), "r"(blo), "r"(hi));
}
__device__ __forceinline__ float vzero() { float v; asm volatile("mov.b32 %0, 0;" : "=f"(v)); return v; }
__device__ __forceinline__ void tma_box(uint32_t dst, const CUtensorMap* tm, uint32_t mb, int x, int y) {
  asm volatile("cp.async.bulk.tensor.2d.shared::cluster.global.mbarrier::complete_tx::bytes [%0], [%1, {%3, %4}], [%2];"
               :: "r"(dst), "l"(tm), "r"(mb), "r"(x), "r"(y) : "memory");
}
__device__ __forceinline__ void l2_prefetch(const void* src, uint32_t bytes) {
  asm volatile("cp.async.bulk.prefetch.L2.global [%0], %1;" :: "l"(src), "r"(bytes) : "memory");
}
__device__ __forceinline__ uint32_t uni(uint32_t v) {
  uint32_t r; asm volatile("shfl.sync.idx.b32 %0, %1, 0, 0x1f, 0xffffffff;" : "=r"(r) : "r"(v)); return r;
}
__device__ __forceinline__ int fresh_tid() { int v; asm volatile("mov.u32 %0, %tid.x;" : "=r"(v)); return v; }

struct Params {
  const unsigned char* x;
  Scratch* s;
  int off[7];
  uint32_t zero;
  uint32_t* out;
  const uint16_t* dskip;
  const uint32_t* w_r;
  long long* ts;
  const unsigned char* far[7];
  uint32_t sched[2][17];
};
__device__ __forceinline__ uint32_t ldnc32(const void* p) { uint32_t v; asm volatile("ld.global.nc.b32 %0, [%1];" : "=r"(v) : "l"(p)); return v; }
__device__ __forceinline__ uint32_t ldnc16(const void* p) { uint16_t v; asm volatile("ld.global.nc.u16 %0, [%1];" : "=h"(v) : "l"(p)); return v; }
__device__ __forceinline__ uint4 ldnc128(const void* p) { uint4 v; asm volatile("ld.global.nc.v4.b32 {%0,%1,%2,%3}, [%4];" : "=r"(v.x), "=r"(v.y), "=r"(v.z), "=r"(v.w) : "l"(p)); return v; }
__device__ __forceinline__ void mbar_wait(uint32_t mb, uint32_t ph = 0) {
#pragma unroll 1
  for (int it = 0; it < SPIN_MAX; it++) {
    uint32_t ok;
    asm volatile("{ .reg .pred q; mbarrier.try_wait.parity.shared::cta.b64 q, [%1], %2; selp.u32 %0, 1, 0, q; }" : "=r"(ok) : "r"(mb), "r"(ph) : "memory");
    if (ok) break;
  }
}
__device__ __forceinline__ uint32_t mbar_test(uint32_t mb) {
  uint32_t ok;
  asm volatile("{ .reg .pred q; mbarrier.test_wait.parity.shared::cta.b64 q, [%1], 0; selp.u32 %0, 1, 0, q; }" : "=r"(ok) : "r"(mb) : "memory");
  return ok;
}
__device__ __forceinline__ void mbar_arrive(uint32_t mb) { asm volatile("mbarrier.arrive.shared::cta.b64 _, [%0];" :: "r"(mb) : "memory"); }
__device__ __forceinline__ uint32_t ldg16(const void* p) { uint16_t v; asm volatile("ld.global.u16 %0, [%1];" : "=h"(v) : "l"(p) : "memory"); return v; }
__device__ __forceinline__ uint32_t ldr16(const void* p) { uint16_t v; asm volatile("ld.relaxed.gpu.global.u16 %0, [%1];" : "=h"(v) : "l"(p) : "memory"); return v; }
__device__ __forceinline__ void fence_async() { asm volatile("fence.proxy.async.shared::cta;" ::: "memory"); }
#define SPIN_WHILE(cond, body) _Pragma("unroll 1") for (int _it = 0; _it < SPIN_MAX && __any_sync(0xffffffffu, (cond)); _it++) { body; }

struct LnC { uint32_t m2, rh2, rl2; };
__device__ __forceinline__ float diag_sum(float d0, float d1, int t) {
  float q = __shfl_sync(0xffffffffu, d0, 9 * t) + __shfl_sync(0xffffffffu, d1, 9 * t + 4);
  q += __shfl_xor_sync(0xffffffffu, q, 1);
  return q + __shfl_xor_sync(0xffffffffu, q, 2);
}
__device__ __forceinline__ LnC ln_consts(float s, float q, float& r) {
  const float mean = s * (1.f / DM);
  const float var = fmaxf(fmaf(-mean, mean, q * (1.f / DM)), 0.f);
  float sd;
  asm("sqrt.approx.ftz.f32 %0, %1;" : "=f"(sd) : "f"(bfr(bfr(var) + 1e-5f)));
  asm("rcp.approx.ftz.f32 %0, %1;" : "=f"(r) : "f"(bfr(sd)));
  LnC c;
  c.m2 = pack_bf(mean, mean);
  c.rh2 = pack_bf(r, r);
  const float rl = r - bf_lo(c.rh2);
  c.rl2 = pack_bf(rl, rl);
  return c;
}
__device__ __forceinline__ float quad_sum(float s) { s += __shfl_xor_sync(0xffffffffu, s, 1); return s + __shfl_xor_sync(0xffffffffu, s, 2); }
__device__ __forceinline__ uint32_t bf_fma2(uint32_t a, uint32_t b, uint32_t c) {
  __nv_bfloat162 r = __hfma2(*(const __nv_bfloat162*)&a, *(const __nv_bfloat162*)&b, *(const __nv_bfloat162*)&c);
  return *(uint32_t*)&r;
}
__device__ __forceinline__ uint32_t ln_apply(uint32_t w, uint32_t m2, uint32_t rh2, uint32_t rl2) {
  const uint32_t d = bf_sub2(w, m2);
  return bf_fma2(d, rh2, bf_mul2(d, rl2));
}

__device__ __forceinline__ float2 cis(float mag_log2, float rev) {
  const float m = ex2(mag_log2), ang = rev * 6.283185307179586f;
  return make_float2(m * __cosf(ang), m * __sinf(ang));
}
__device__ __forceinline__ float2 csq(float2 a) { return make_float2(fmaf(a.x, a.x, -a.y * a.y), (a.x + a.x) * a.y); }
__device__ __forceinline__ float2 cmul(float2 a, float2 b) { return make_float2(fmaf(a.x, b.x, -a.y * b.y), fmaf(a.x, b.y, a.y * b.x)); }
__device__ __forceinline__ void pmul(uint32_t xr, uint32_t xi, uint32_t w, uint32_t& yr, uint32_t& yi) {
  const __half2 XR = *(__half2*)&xr, XI = *(__half2*)&xi, W = *(__half2*)&w;
  const __half2 a = __hfma2(__hneg2(XI), __high2half2(W), __hmul2(XR, __low2half2(W)));
  const __half2 b = __hfma2(XI, __low2half2(W), __hmul2(XR, __high2half2(W)));
  yr = *(const uint32_t*)&a; yi = *(const uint32_t*)&b;
}
__device__ __forceinline__ uint32_t pk(float2 a) { return pack_h(a.x, a.y); }

struct KgState { float2 c0, z8; float kl; uint32_t w64, w128, w192; };
__device__ __forceinline__ void kgen_tables_n(const uint32_t (&raw)[7], uint32_t scr, int wt, KgState& k) {
  const uint32_t dst = scr + 16384 + wt * 16;
  const float dt = bfr(ex2(bf_lo(raw[6]) * 1.4426950408889634f));
  const float th = dt * bf_lo(raw[1]);
  const float br = dt * bf_lo(raw[2]), bi = dt * bf_lo(raw[3]);
  const float Cr = bf_lo(raw[4]), Ci = bf_lo(raw[5]);
  k.c0 = make_float2(fmaf(Cr, br, -Ci * bi), fmaf(Cr, bi, Ci * br));
  const uint32_t mx = __reduce_max_sync(0xffffffffu, __float_as_uint(fmaxf(fabsf(k.c0.x), fabsf(k.c0.y))));
  const float a2 = dt * bf_lo(raw[0]) * 1.4426950408889634f;
  const float rh = th * 0.15915494309189535f;
  const float rl = fmaf(th, (float)(0.15915494309189535 - (double)0.15915494309189535f), fmaf(th, 0.15915494309189535f, -rh));
  const float rf = rh - rintf(rh);
  const float2 z1 = cis(a2, rf + rl);
  const float p64 = rf * 64.f;
  const float2 z64 = cis(a2 * 64.f, fmaf(64.f, rl, p64 - rintf(p64)));
  const float2 z2 = csq(z1), z128 = csq(z64), z3 = cmul(z2, z1), z4 = csq(z2), z256 = csq(z128), z6 = csq(z3), z512 = csq(z256);
  k.z8 = csq(z4);
  k.w64 = pk(z64); k.w128 = pk(z128); k.w192 = pk(cmul(z128, z64));
  sts128(dst, 0x00003C00u, pk(z2), pk(z4), pk(z6));
  const float2 z1024 = csq(z512), z768 = cmul(z512, z256);
  sts128(dst + 2048, pk(z1), pk(z3), pk(cmul(z4, z1)), pk(cmul(z4, z3)));
  const float2 z2048 = csq(z1024);
  k.kl = fmaf(k.c0.x, z2048.x, -k.c0.y * z2048.y);
  sts128(dst + 4096, pk(z256), pk(cmul(z256, z2)), pk(cmul(z256, z4)), pk(cmul(z256, z6)));
  sts128(dst + 6144, pk(z512), pk(cmul(z512, z4)), pk(z768), pk(cmul(z768, z4)));
  sts128(dst + 8192, pk(z1024), pk(cmul(z1024, z256)), pk(cmul(z1024, z512)), pk(cmul(z1024, z768)));
  sts32(scr + W_MISC + (wt >> 5) * 4, mx);
}
__device__ __forceinline__ int kgen_tables_m(uint32_t scr, int wt, const KgState& k) {
  const uint32_t dst = scr + wt * 16;
  const uint4 e4 = lds128(scr + W_MISC);
  const float2 z16 = csq(k.z8), z32 = csq(z16);
  const int em = max(min((int)(max(max(e4.x, e4.y), max(e4.z, e4.w)) >> 23), 238), 16);
  const float sc = __uint_as_float((uint32_t)(127 + 4 + 127 - em) << 23);
  sts32(scr + W_MISC + 16 + (wt >> 5) * 4, __reduce_add_sync(0xffffffffu, __float2int_rn(k.kl * sc * 262144.f)));
  const float2 c0 = make_float2(k.c0.x * sc, k.c0.y * sc);
  const float2 c1 = cmul(c0, k.z8), c2 = cmul(c0, z16), c4 = cmul(c0, z32), c3 = cmul(c1, z16), c5 = cmul(c1, z32), c6 = cmul(c2, z32), c7 = cmul(c3, z32);
  uint32_t pr[4], pi[4], yr[4], yi[4];
  pr[0] = pack_h(c0.x, c1.x); pi[0] = pack_h(c0.y, c1.y);
  pr[1] = pack_h(c2.x, c3.x); pi[1] = pack_h(c2.y, c3.y);
  pr[2] = pack_h(c4.x, c5.x); pi[2] = pack_h(c4.y, c5.y);
  pr[3] = pack_h(c6.x, c7.x); pi[3] = pack_h(c6.y, c7.y);
  sts128(dst, pr[0], pr[1], pr[2], pr[3]); sts128(dst + 2048, pi[0], pi[1], pi[2], pi[3]);
#pragma unroll
  for (int q = 1; q < 4; q++) {
    const uint32_t w = q == 1 ? k.w64 : q == 2 ? k.w128 : k.w192;
#pragma unroll
    for (int i = 0; i < 4; i++) pmul(pr[i], pi[i], w, yr[i], yi[i]);
    sts128(dst + q * 4096, yr[0], yr[1], yr[2], yr[3]); sts128(dst + q * 4096 + 2048, yi[0], yi[1], yi[2], yi[3]);
  }
  return em;
}
__device__ __forceinline__ void kgen_build(uint32_t tb, int wg, int wt, uint32_t k0, uint32_t k1, uint32_t k2) {
  const uint32_t kt = tb + W_KT, sc = tb + W_L3 + 3072;
  const int ix = ((wt >> 2) + (wt & 3) * 32 - 1) & 127;
  const uint32_t a3 = tb + W_CW + 32 + ((ix & 1) ? 0 : 304) + (ix >> 1) * 4;
  const uint32_t v3 = wt ? k2 : k2 >> 16;
  sts32(sc + 4 + wt * 4, __byte_perm(k0, k1, 0x5432));
  sts16(sc + 544 + (wt & ~3) + (wt & 1) * 2 + (wt & 2) * 64, k1 >> 16);
  sts16(a3, v3); sts16(a3 + 6, v3);
  if ((unsigned)(wt - 32) < 18u) sts128(kt + (wt < 36 ? -512 : 64 + 4128 - 576) + wt * 16, 0, 0, 0, 0);
  if (wt == 127) sts32(sc, k0 & 0xFFFF0000u);
  if (wt == 0) { sts32(sc + 516, k1); sts16(sc + 800, k2); }
  bar_sync(1 + wg, 128);
  const uint32_t cw = tb + W_CW + 32 + (wt >> 6) * 48 + wt * 4;
  const uint32_t pv = lds32(sc + wt * 4), nx = lds32(sc + 8 + wt * 4), c2 = lds16(sc + 544 + wt * 2), n2 = lds16(sc + 546 + wt * 2);
  sts128(tb + W_L3 + 512 + (wt >> 6) * 512 + wt * 16, lds32(cw), lds32(cw - 8), lds32(cw - 16), lds32(cw - 24));
  const bool odd = wt & 1;
  sts64(kt + 64 + wt * 8, __byte_perm(k0, pv, 0x5410), __byte_perm(k0, 0, 0x1032));
  sts64(kt + 64 + 1024 + wt * 8, __byte_perm(k1, pv, (odd || wt == 0) ? 0x7610 : 0x1010), __byte_perm(k1, nx, odd ? 0x1076 : 0x1010));
  const uint32_t cc = c2 * 0x10001u, nc = __byte_perm(n2, c2, 0x5410), nn = n2 * 0x10001u;
  sts128(kt + 64 + 2048 + wt * 16, cc, cc, odd ? nc : cc, odd ? nn : nc);
  if (wt == 127) { sts128(kt + 64 + 4096, nn, nn, nn, nn); sts128(kt + 64 + 4112, nn, nn << 16, 0, 0); }
}

__device__ __forceinline__ void load_a(uint32_t (&a)[4], uint32_t kp, int j) {
  a[0] = lds32(kp + 64 * j); a[1] = lds32(kp + 64 * j + 512); a[2] = lds32(kp + 64 * j - 32); a[3] = lds32(kp + 64 * j + 480);
}
__device__ __forceinline__ uint32_t band(int d, int lo, int hi) {
  return ((unsigned)(d - lo) <= (unsigned)(hi - lo) ? 1u : 0u) | ((unsigned)(d - 1 - lo) <= (unsigned)(hi - lo) ? 0x10000u : 0u);
}
__device__ __forceinline__ uint32_t hadd2u(uint32_t a, uint32_t b) { __half2 r = __hadd2(*(__half2*)&a, *(__half2*)&b); return *(uint32_t*)&r; }

__device__ __forceinline__ void zero_pads(uint32_t tb, int wt) {
  if (!(wt & 32)) sts128(tb + W_L3 + (wt >> 6) * 512 + wt * 16, 0, 0, 0, 0);
  if ((wt & 63) < 3) sts128(tb + W_CW + (wt >> 6) * 304 + (wt & 63) * 16, 0, 0, 0, 0);
}
__device__ __forceinline__ uint32_t tr_base(int lane) {
  return OFF_YT + (2 * (lane >> 3) + (lane & 1)) * YT_PITCH + ((lane >> 1) & 1) * (8 * YT_PITCH + 64) + ((lane >> 2) & 1) * 16;
}

__device__ __forceinline__ uint32_t sc_addr(int tp) { return OFF_YT + (tp < 16 ? tp * YT_PITCH + (tp >> 3) * 64 + 1152 : 8 * YT_PITCH - 512 + tp * 32); }
#define X_PS 1
#define X_PW 15
#define X_HU 16
#define X_HB 0
#define X_REL 1
#define X_PAD0 0
#define X_PAD1 0
#define PAD(n) _Pragma("unroll") for (int _i = 0; _i < (n); _i++) asm volatile("pmevent 0;");
#ifndef M_
#define M_ 12
#endif
#define X_NE 2
#define X_SCT 10000
#define X_DELTA 400
#define X_DSTEP 2000
#define X_PF0 2500
#define X_PFD 600
#define X_TD 450
#define X_WS 6
#define X_OR 8
#define X_ABS 5100
#define X_XD 0
#define X_RD 600
#define X_HD 400
#define X_PD 1080
#define X_PROMO 2
#define X_YD2 1000
#define X_GO 2
#define X_GW 2
#define X_NS 4700
#define X_XS 13600
#define X_LAG 1800
#define X_YD 1550
struct TMaps { CUtensorMap m[10]; };
__device__ __forceinline__ uint32_t h2bf(uint32_t w) { const float2 f = h2f(w); return pack_bf(f.x, f.y); }
__device__ __forceinline__ uint32_t keep(uint32_t v) { asm volatile("" : "+r"(v)); return v; }
__device__ __forceinline__ uint2 ldr64(const void* p) { uint2 v; asm volatile("{ .reg .b64 t; ld.relaxed.gpu.global.b64 t, [%2]; mov.b64 {%0, %1}, t; }" : "=r"(v.x), "=r"(v.y) : "l"(p) : "memory"); return v; }
__host__ __device__ __forceinline__ uint32_t down_box(int s, bool five) {
  return five ? OFF_W + W_BYTES + 12288 + (s / 3) * (W_BYTES - 12288) + s * 4096 : s < 6 ? OFF_W + W_BYTES + BOX + (s >> 1) * (W_BYTES - 10240) + s * 5120 : OFF_W + (s - 6) * 5120;
}
__device__ __forceinline__ void load_tile(const CUtensorMap* tmx, int i, int c, int again = 0) {
  asm volatile("mbarrier.arrive.expect_tx.shared::cta.b64 _, [%0], 8704;" :: "r"(MB_UL + i * 16 + again) : "memory");
  asm volatile("cp.async.bulk.tensor.3d.shared::cluster.global.mbarrier::complete_tx::bytes [%0], [%1, {%3, %4, %5}], [%2];"
               :: "r"(i < 2 ? OFF_T + i * TILE : OFF_W), "l"(tmx), "r"(MB_UL + i * 16 + again), "r"(0), "r"(c), "r"(-8) : "memory");
}
template <bool FAR> __device__ __forceinline__ void load_params(const Params& p, uint32_t ch, int wt, uint32_t dst, bool on) {
  const int o01 = (wt & 16) ? p.off[1] : p.off[0], o23 = (wt & 16) ? p.off[3] : p.off[2], o45 = (wt & 16) ? p.off[5] : p.off[4];
  const int o = (wt & 64) ? ((wt & 32) ? p.off[6] : o45) : ((wt & 32) ? o23 : o01);
  const unsigned char* b = FAR ? p.far[min(wt >> 4, 6)] : p.x + (long long)o * 16;
  asm volatile("{ .reg .pred q; setp.ne.u32 q, %2, 0; @q cp.async.cg.shared.global [%0], [%1], 16; }"
               :: "r"(dst + wt * 16), "l"(b + (wt < 96 ? ch * 256 + (wt & 15) * 16 : (ch >> 3) * 16)), "r"((uint32_t)(on && wt < 97)) : "memory");
}

struct ConvC { uint32_t ca, cb, bands; };
__device__ __forceinline__ ConvC conv_consts(int w, int lane) {
  const int h = w & 1, P = (w >> 1) & 1, d0 = 8 * h + (lane >> 2) - 2 * (lane & 3);
  ConvC k;
  k.ca = keep((W_KT + (16 + 256 * P + d0) * 4) | (((8 + 64 * P + lane) * 64 + (((h + ((w >> 1) & 2)) ^ (lane >> 1)) & 3) * 16) << 16));
  k.cb = keep(lane < 8 ? 0xFFFEFFFEu : ~0u);
  k.bands = keep(band(d0, 12, 20) + 2 * band(d0 + 8, 12, 20) + 4 * band(d0 + 16, 12, 20) + 8 * band(d0 + 24, 12, 20)
                 + 16 * band(d0 - 8, 5, 11) + 32 * band(d0, 5, 11) + 64 * band(d0 + 8, 5, 11) + 128 * band(d0 + 16, 5, 11));
  return k;
}
struct ConvPre { uint32_t e0, e2, f2, a[3][4]; };
__device__ __forceinline__ uint32_t lds32_if(uint32_t a, bool on) {
  uint32_t v; asm volatile("{ .reg .pred q; setp.ne.u32 q, %2, 0; mov.b32 %0, 0; @q ld.shared.b32 %0, [%1]; }" : "=r"(v) : "r"(a), "r"((uint32_t)on) : "memory"); return v;
}
__device__ __forceinline__ void conv_pre(ConvPre& r, uint32_t kp, int part, bool on, bool P) {
  if (part & 1) { r.e0 = lds32_if(kp + 4096, on && !P); r.e2 = lds32_if(kp + 4064, on && !P); r.f2 = lds32_if(kp + 4128, on && !P); }
#pragma unroll
  for (int j = 0; j < 3; j++) if (part & (j < X_PS ? 1 : 2)) {
    r.a[j][0] = lds32_if(kp + 2048 + 64 * j, on); r.a[j][1] = lds32_if(kp + 2560 + 64 * j, on); r.a[j][2] = lds32_if(kp + 2016 + 64 * j, on); r.a[j][3] = lds32_if(kp + 2528 + 64 * j, on);
  }
}
__device__ __forceinline__ void conv_item(uint32_t tb, uint32_t tl, int bid, int bn, ConvPre& pre, const ConvC& cv, uint32_t zero, const CUtensorMap* tmx, int ch, int warp, int lane, bool hold, bool more) {
  const bool go = more && warp == 0 && lane == 0;
  const uint32_t kp = tb + (cv.ca & 0xFFFFu);
  const uint32_t dlo = (tl >> 4) + 32 + ((warp >> 1) & 2) + (1u << 16), dhi = 32u | (2u << 30);
  const bool P = warp & 2;
  float a32[16], b32[16], a64[32];
  uint32_t A[40][4];
#define STEP(J) { wgmma64<0>(a64, A[J], dlo + 256 - 4 * (J), dhi); \
    if ((J) == 32) wgmma32_init<0>(b32, A[J], dlo, dhi); else wgmma32<0>(b32, A[J], ((J) < 8 ? dlo ^ zero : dlo) + 128 - 4 * (J), dhi); \
    if ((J) == 0) wgmma32_init<0>(a32, A[J], dlo, dhi); else if ((J) < 8) wgmma32<0>(a32, A[J], (dlo ^ zero) - 4 * (J), dhi); }
#define LD(J) load_a(A[J], kp, J);
#define FIRST(J) wg_fence(); STEP(J) wg_commit(); wg_wait<1>(); wg_fence();
  {
    uint32_t win[16], x9[4], x7[4], e[4], f[4];
    const uint32_t bz = keep(cv.bands);
#define BAND(i) keep((bz & (0x10001u << (i))) * (0x3C00u >> (i)))
    e[0] = pre.e0; e[2] = pre.e2; e[1] = keep(bz & 0x100u); e[3] = keep(bz & 0x200u);
    f[2] = pre.f2; f[0] = keep(bz & 0x4000u); f[1] = keep(bz & 0x8000u); f[3] = keep(bz & 0x300u);
#pragma unroll
    for (int j = 0; j < 12; j++) A[32 + j / 4][j & 3] = pre.a[j / 4][j & 3];
    const uint32_t q[12] = {BAND(0), BAND(5), keep(bz & 0x400u), BAND(4), BAND(2), BAND(7), BAND(1), BAND(6), keep(bz & 0x800u), keep(bz & 0x1000u), BAND(3), keep(bz & 0x2000u)};
#undef BAND
    const uint32_t ta = keep(tl + 512 + (warp & 3) * 2048 + lane * 64 + (lane & 6) * 8);
    if (X_GO && hold) mbar_wait(MB_GO);
    uint32_t mbl = MB_UL + (warp & 8) * 2, ph = 0;
#pragma unroll 1
    for (int it = 0; it < SPIN_MAX; it++) {
      if (ch < 512) mbar_wait(mbl, ph);
      if (it == 1) TS(13);
      TS(3);
      wg_fence();
      wgmma64h_init(win, q[0], q[1], q[2], q[3], dlo, dhi);
      wgmma64h(win, q[4], q[5], q[6], q[7], dlo - 4, dhi);
      wgmma64h(win, q[8], q[9], q[10], q[11], dlo - 8, dhi);
      wg_commit();
      wgmma64_init<0>(a64, e, dlo, dhi);
      wgmma64<0>(a64, f, dlo - 4, dhi);
      wg_commit();
      if (ch >= 512) break;
      uint32_t r0, r1, r2, r3, ok;
      if (warp & 4) {
        mbar_wait(mbl + 8);
        if (__all_sync(0xffffffffu, it || lds32(MISC_RT + (warp & 8)) == 0)) break;
        wg_wait<0>();
        continue;
      }
      ldsm4(ta, r0, r1, r2, r3);
      ok = r0 & r1 & r2 & r3;
      ldsm4(ta ^ 32, r0, r1, r2, r3);
      asm volatile("{ .reg .pred q; setp.ne.u32 q, %1, 0; barrier.red.and.pred q, %2, 128, q; selp.u32 %0, 1, 0, q; }" : "=r"(ok) : "r"((ok & r0 & r1 & r2 & r3 & 1u) | (lane & 3)), "r"(1 + (warp >> 2)) : "memory");
      if (ok) { if ((warp & 3) == 0 && lane == 0) { sts32(MISC_RT + warp, it); mbar_arrive(MB_UL + 8 + warp * 2); } break; }
      wg_wait<0>();
      if ((warp & 3) == 0 && lane == 0) load_tile(tmx - 1, warp >> 3, ch, 56);
      mbl = MB_UL + 56 + (warp & 8) * 2; ph = it & 1;
    }
    wg_wait<1>();
#pragma unroll
    for (int i = 0; i < 4; i++) {
      const int tl = 2 * ((i & 1) + ((i & 2) ? 0 : 4));
      x9[i] = P ? win[tl + 4] : win[tl]; x7[i] = P ? win[tl + 5] : win[tl + 1];
    }
    const uint32_t l3lo = ((tb + W_L3) >> 4) + (32u << 16);
    wg_fence();
    wgmma64<0>(a64, x9, l3lo, 8);
    wgmma64<0>(a64, x7, l3lo + 96, 8);
    wg_commit();
  }
  STEP(32) STEP(33) STEP(34) wg_commit(); wg_wait<1>();
  LD(35) LD(36) LD(37) LD(38)
  FIRST(35) STEP(36) STEP(37) STEP(38) wg_commit();
  LD(39) LD(0)
  TS(17);
  if (X_GO == 1 && go) mbar_arrive(MB_GO);
  FIRST(39) STEP(0) wg_commit();
  LD(1) LD(2) LD(3)
  FIRST(1) STEP(2) STEP(3) wg_commit();
  LD(4) LD(5)
  if (X_GO == 2 && go) mbar_arrive(MB_GO);
  FIRST(4) STEP(5) wg_commit();
  LD(6) LD(7)
  wg_fence(); STEP(6) STEP(7) wg_commit();
#undef STEP
#undef LD
#undef FIRST
  TS(18);
  if (X_GO == 3 && go) mbar_arrive(MB_GO);
  const uint32_t xc = tb + W_KT + (warp & 3) * 1024 + lane * 16;
  if (more) bar_sync(7, 288);
  wg_wait<1>();
  conv_pre(pre, kp + ALT, 1, more, P);
  wg_wait<0>();
  conv_pre(pre, kp + ALT, 2, more, P);
  uint32_t E[16], o[8];
#define ACC(i) ((i) < 16 ? a32[i] : (i) < 32 ? b32[(i) - 16] : a64[(i) - 32])
  E[0] = pack_h(a32[0], a32[1]);
#pragma unroll
  for (int i = 1; i < 16; i++) E[i] = pack_h(ACC(4 * i) + ACC(4 * i - 2), ACC(4 * i + 1) + ACC(4 * i - 1));
#undef ACC
#pragma unroll
  for (int j = 0; j < 8; j++) o[j] = P ? (j < 2 ? 0u : E[j - 2]) : E[8 + j];
  sts128(xc, o[0], o[1], o[2], o[3]); sts128(xc + 512, o[4], o[5], o[6], o[7]);
#pragma unroll
  for (int j = 0; j < 8; j++) o[j] = P ? E[6 + j] : E[j];
  TS(25);
  if (more) {
    sts128(xc + 4096, o[0], o[1], o[2], o[3]); sts128(xc + 4608, o[4], o[5], o[6], o[7]);
    bar_arrive(12, 192);
    return;
  }
  bar_sync(1 + (warp >> 2), 128);
  const uint4 vv[2] = {lds128(xc + (P ? -2048 : 2048)), lds128(xc + (P ? -1536 : 2560))};
#pragma unroll
  for (int q = 0; q < 2; q++) {
    const uint4 v = vv[q];
    stsm4t(tl + (cv.ca >> 16) + q * 2048, hadd2u(o[4 * q], v.x) & cv.cb, hadd2u(o[4 * q + 1], v.y) & cv.cb, hadd2u(o[4 * q + 2], v.z) & cv.cb, hadd2u(o[4 * q + 3], v.w) & cv.cb);
  }
  fence_async();
  bar_sync(bid, bn);
  if (warp == 0 && lane == 0) mbar_arrive(MB_REL);
  if ((warp & 7) == (ch < 512 ? 7 : 3) && lane == 0) {
    asm volatile("cp.async.bulk.tensor.3d.global.shared::cta.bulk_group [%0, {%3, %2, %3}], [%1];" :: "l"(tmx), "r"(tl + 512), "r"(ch), "r"(0) : "memory");
    asm volatile("cp.async.bulk.commit_group;" ::: "memory");
  }
}

template <bool FAR> __global__ void __launch_bounds__(NT, 1)
fused_kernel(const __grid_constant__ Params p, const __grid_constant__ TMaps tm) {
  extern __shared__ __align__(1024) unsigned char smem[];
  const int c = blockIdx.x;
  const bool five = (c & 1) == 0;
  const uint32_t pitch = five ? 64 : 80;
  const uint32_t ones = 0x3F803F80u;
  const int tid = threadIdx.x, lane = tid & 31;
  {
    const int w4 = tid >> 7, k5 = !five && w4 == 3;
    load_params<FAR>(p, k5 ? 512 + (c >> 1) : (w4 & 2) * 128 + 2 * c + (w4 & 1), tid & 127, OFF_W + w4 * W_BYTES + W_KT + k5 * 2048, w4 != 2 && w4 != 4);
  }
  const int warp = (int)uni(tid >> 5), wg = warp >> 2;
  TS(0);
  if (__builtin_expect(wg == 4, 0)) {
    asm volatile("setmaxnreg.dec.sync.aligned.u32 32;");
    const int role = warp;
    const int u0 = (c >> 1) * 9 + (five ? ((c & 2) ? 5 : 0) : ((c & 2) ? 0 : 4));
    const uint32_t t0 = clock() + c * 4;
    if (role == 16) {
      if (lane < 19) asm volatile("mbarrier.init.shared::cta.b64 [%0], %1;" :: "r"(OFF_MISC + lane * 8), "r"((unsigned)(lane - 2) < 4u ? 4 : 1) : "memory");
      if (lane < 2) asm volatile("mbarrier.arrive.expect_tx.shared::cta.b64 _, [%0], %1;" :: "r"(OFF_MISC + lane * 8), "r"(lane ? (five ? 36864 : 51200) : pitch * 1152) : "memory");
      fence_async();
      bar_arrive(5, 608);
      const CUtensorMap* tmb = &tm.m[five ? 3 : 0];
#pragma unroll 1
      for (int u = 0; u < 17; u++) {
        const uint32_t e = p.sched[five][u], kind = e & 3, s = (e >> 2) & 15, dst = e >> 14;
        if (kind == 3) continue;
        while ((int)(clock() - t0) < X_PF0 + (u < X_NE ? u * X_PFD : X_LAG + u * X_TD)) __nanosleep(20);
        if (e & 0x3FC0) mbar_wait(OFF_MISC + ((e >> 6) & 255));
        if (lane == 0) {
          if (kind == 2) asm volatile("cp.async.bulk.tensor.3d.shared::cluster.global.mbarrier::complete_tx::bytes [%0], [%1, {%3, %4, %5}], [%2];"
                                      :: "r"(dst), "l"(tmb + 2), "r"(MB_D), "r"(0), "r"(u0 * 8), "r"(s) : "memory");
          else tma_box(dst, tmb + kind, MB_GU, u0 * 8, s * 96);
        }
        if (u == 5) TS(2);
        if (u == 10) TS(3);
      }
      TS(4);
      TS_DUMP();
#define FINISH0 bar_sync(12, 192);        \
        _Pragma("unroll 1") for (int w = role & 2; w < (role & 2) + 2; w++) { \
          const uint32_t xa = OFF_W + W_KT + lane * 16, mk = lane < 8 ? 0xFFFEFFFEu : ~0u, ya = OFF_T + (8 + lane) * 64 + (((w & 1) ^ (lane >> 1)) & 3) * 16 + (w & 2) * 2048; \
          const uint4 a = lds128(xa + 4096 + w * 1024), b = lds128(xa + (w ^ 2) * 1024), d = lds128(xa + 4608 + w * 1024), e = lds128(xa + 512 + (w ^ 2) * 1024); \
          stsm4t(ya, hadd2u(a.x, b.x) & mk, hadd2u(a.y, b.y) & mk, hadd2u(a.z, b.z) & mk, hadd2u(a.w, b.w) & mk); \
          stsm4t(ya + 2048, hadd2u(d.x, e.x) & mk, hadd2u(d.y, e.y) & mk, hadd2u(d.z, e.z) & mk, hadd2u(d.w, e.w) & mk); \
        } \
        fence_async();
    } else if (role == 17) {
      if (smem_u32(smem) != SB) __trap();
      bar_sync(10, 576);
      if (lane == 0) {
        fence_async();
        while ((int)(clock() - t0) < X_NS - c * 4) {}
        asm volatile("cp.async.bulk.global.shared::cta.bulk_group [%0], [%1], 10240;" :: "l"(&p.s->X[c * DM * 2 + 512]), "r"(OFF_G) : "memory");
        asm volatile("cp.async.bulk.commit_group;" ::: "memory");
        asm volatile("cp.async.bulk.wait_group 0;" ::: "memory");
      }
      if (lane == 0) mbar_arrive(MB_GF);
      bar_arrive(11, 96);
      if (five) { FINISH0 bar_arrive(13, 192); }
    } else if (role == 18) {
      sts32(MISC_EPOCH, 0);
      sts32(MISC_T0, t0 - c * 4);
      bar_arrive(5, 608);
      uint4* q = lane < 2 ? &p.s->R[c * 2 + lane] : lane < 11 ? &p.s->HS[c * 9 + lane - 2] : lane == 11 ? &p.s->HS[1152 + (c & 7)] : (uint4*)&p.s->FLAG[c * 8];
      if (lane < (c < 8 ? 12 : 11)) str128(q, ~0u, ~0u, ~0u, ~0u);
      const uint32_t ep = __shfl_sync(0xffffffffu, ldr32(q), 31) + 1u;
      sts32(MISC_EPOCH, ep | 0x80000000u);
      TSX(21);
      if (lane == 31) str32(q, ep);
      bar_sync(11, 96);
      TSX(14);
      mbar_wait(MB_KF + (lane & 3) * 8);
      __syncwarp();
      { const uint2 e = lds64(MISC_EM); if (lane < 2) str128(&p.s->SC[c * 2 + lane], e.x, __byte_perm(e.y, ep, 0x6540), 0, 0); }
      TSX(17);
      while ((int)(clock() - t0) < X_SCT) __nanosleep(100);
      TSX(18);
      {
        uint2 v[4];
#pragma unroll 1
        for (int it = 0; it < SPIN_MAX; it++) {
          uint32_t bad = 0;
#pragma unroll
          for (int q = 0; q < 4; q++) v[q] = ldr64(&p.s->SC[lane * 2 + q * 64]);
#pragma unroll
          for (int q = 0; q < 4; q++) bad |= (v[q].y >> 8) ^ (ep & 0xFFFFFFu);
          if (!__any_sync(0xffffffffu, bad)) break;
        }
        TSX(25);
#pragma unroll
        for (int q = 0; q < 4; q++) {
          const uint32_t sa = (lane >> 4) * YT_PITCH + (lane & 15) * 2;
          sts16(sc_addr(2 * q) + sa, v[q].x); sts16(sc_addr(8 + 2 * q) + sa, v[q].x >> 16);
          if (lane & 1) asm volatile("st.shared.u8 [%0], %1;" :: "r"(sc_addr(16) + q * 16 + (lane >> 1)), "r"(v[q].y) : "memory");
        }
      }
      __syncwarp();
      if (lane == 0) mbar_arrive(MB_SC);
      TSX(27);
    } else {
      uint32_t w[9];
      const uint32_t dk = ldnc16(p.dskip + ((lane & 4) ? 512 + (c >> 1) : (lane & 2) * 128 + 2 * c + (lane & 1)));
      float s = 0.f;
#pragma unroll
      for (int i = 0; i < 9; i++) w[i] = ldnc32(p.w_r + lane + 32 * i);
      sts16(OFF_WR + 1152 + lane * 2, dk);
      bar_arrive(5, 608);
#pragma unroll
      for (int i = 0; i < 9; i++) { sts32(OFF_WR + lane * 4 + i * 128, w[i]); s += bf_lo(w[i]) + bf_hi(w[i]); }
      sts32(MISC_SW, __float_as_uint(warp_sum(s)));
      TSX(23);
      bar_sync(10, 576);
      if (lane == 0) {
        const uint32_t tp = clock();
        TSX(1);
        while ((int)(clock() - tp) < X_DELTA || (int)(clock() - t0) < X_ABS - c * 4) {}
        TSX(24);
        load_tile(&tm.m[6], 0, c);
        TSX(15);
        while ((int)(clock() - t0) < X_ABS + X_DSTEP - c * 4) {}
      }
      bar_sync(11, 96);
      if (lane == 0) {
        load_tile(&tm.m[6], 1, 128 + c);
      }
      if (five) {
        mbar_wait(MB_KF);
#pragma unroll 1
        for (int it = 0; it < SPIN_MAX; it++) {
          if (lane == 0) load_tile(&tm.m[8], 2, 512 + (c >> 1));
          mbar_wait(MB_UL + 32, it & 1);
          uint32_t m = 1;
#pragma unroll
          for (int q = 0; q < 4; q++) { uint32_t r0, r1, r2, r3; ldsm4(OFF_W + 512 + lane * 64 + (lane & 6) * 8 + q * 2048, r0, r1, r2, r3); m &= r0 & r1 & r2 & r3; }
          if (__all_sync(0xffffffffu, m || (lane & 3))) break;
        }
        bar_arrive(7, 288);
        FINISH0
        bar_arrive(13, 192);
      }
      bar_sync(0, 544);
      if (lane == 0) mbar_arrive(MB_H);
    }
    return;
  }
  const int wt = tid & 127, g = lane >> 2, t = lane & 3;
  const uint32_t wb = OFF_W + wg * W_BYTES;
  const uint32_t xrow = OFF_YT + (wt >> 3) * YT_PITCH + (wt & 64) + (lane & 7) * 16;
  if (wg == 2) {
    const unsigned char* xp = p.x + (uint32_t)((c * 16 + (wt >> 3)) * 1152 + (lane & 7) * 16);
    { const uint32_t tq = clock(); while ((int)(clock() - tq) < X_XD) {} }
#pragma unroll
    for (int k = 0; k < 9; k++) asm volatile("cp.async.cg.shared.global [%0], [%1], 16;" :: "r"(xrow + k * 128), "l"(xp + k * 128) : "memory");
  }
  asm volatile("cp.async.commit_group;" ::: "memory");
  const ConvC cv = conv_consts(warp, lane);
  zero_pads(wb, wt);
  load_params<FAR>(p, 254 + 2 * c + wg, wt, wb + W_KT, wg == 2 || (wg == 3 && !five));
  asm volatile("cp.async.commit_group;" ::: "memory");
  asm volatile("setmaxnreg.inc.sync.aligned.u32 112;");
  PAD(X_PAD0)
  {
    uint4 kw;
    uint4* kx = &p.s->KX[(c >> 1) * 128 + wt];
    bool two = wg == 3;
    uint32_t ep;
    int em = 0;
    int phase = wg == 2 ? 3 : 2;
#pragma unroll 1
    for (;;) {
      const bool first = two && !five;
      if (phase) asm volatile("cp.async.wait_group 1;" ::: "memory"); else asm volatile("cp.async.wait_group 0;" ::: "memory");
      if (phase == 3) {
        TS(21);
        float d[3][4], r;
        uint4 a[9];
#pragma unroll
        for (int k = 0; k < 9; k++) a[k] = lds128(xrow + k * 128);
#pragma unroll
        for (int i = 0; i < 4; i++) d[0][i] = d[1][i] = d[2][i] = 0.f;
#pragma unroll
        for (int k = 0; k < 9; k++) { mma_bf16(d[(2 * k) % 3], a[k].x, ones, a[k].y, ones, a[k].x, a[k].y); mma_bf16(d[(2 * k + 1) % 3], a[k].z, ones, a[k].w, ones, a[k].z, a[k].w); }
#pragma unroll
        for (int i = 0; i < 4; i++) d[0][i] += d[1][i] + d[2][i];
        const LnC lc = ln_consts(d[0][2] + d[0][3], __shfl_sync(0xffffffffu, d[0][0], 9 * t) + __shfl_sync(0xffffffffu, d[0][1], 9 * t + 4), r);
        if (lane < 12) sts16(MISC_LN1 + g * 32 + (warp & 3) * 8 + t * 2, lane < 4 ? lc.m2 : lane < 8 ? lc.rh2 : lc.rl2);
      } else {
        KgState ks;
        uint32_t raw[7];
        bar_sync(1 + wg, 128);
        TS(22);
#pragma unroll
        for (int i = 0; i < 7; i++) raw[i] = lds16(wb + W_KT + first * 2048 + i * 256 + (i < 6 ? wt : (first ? c >> 1 : 2 * c + (wg & 1)) & 7) * 2);
        kgen_tables_n(raw, wb, wt, ks);
        TS(20);
        bar_sync(1 + wg, 128);
        em = kgen_tables_m(wb, wt, ks);
        fence_async();
      }
      if (phase & 2) {
        const uint32_t tr_addr = tr_base(lane) + warp * 32;
        uint4* dst = &p.s->X[c * DM * 2 + warp * 32 + (8 * (t >> 1) + g) * 2 + (t & 1)];
        TS(23);
        bar_sync(5, 608);
        uint32_t x[3][4];
        ldsm4t(tr_addr, x[0][0], x[0][1], x[0][2], x[0][3]);
        const uint4 m = lds128(MISC_LN1 + (t & 1) * 16), rl = lds128(MISC_LN1 + 64 + (t & 1) * 16), rh = lds128(MISC_LN1 + 32 + (t & 1) * 16);
        ldsm4t(tr_addr + 512, x[1][0], x[1][1], x[1][2], x[1][3]);
        if (wg == 3) ldsm4t(tr_addr + 640, x[2][0], x[2][1], x[2][2], x[2][3]);
#pragma unroll
        for (int q = 0; q < 3; q++) {
          if (q < 2 || wg == 3) {
            const uint32_t r0 = ln_apply(x[q][0], m.x, rh.x, rl.x), r1 = ln_apply(x[q][1], m.y, rh.y, rl.y), r2 = ln_apply(x[q][2], m.z, rh.z, rl.z), r3 = ln_apply(x[q][3], m.w, rh.w, rl.w);
            const uint32_t w0 = (pack_h(bf_lo(r0), bf_hi(r0)) & 0xFFFEFFFEu) | 1u, w1 = pack_h(bf_lo(r1), bf_hi(r1)), w2 = pack_h(bf_lo(r2), bf_hi(r2)), w3 = pack_h(bf_lo(r3), bf_hi(r3));
            if (q == 0) str128(dst, w0, w1, w2, w3);
            else sts128(OFF_G + warp * 512 + (8 * (t >> 1) + g) * 32 + (t & 1) * 16 + (q == 2 ? 2048 : 0), w0, w1, w2, w3);
          }
          if (q == 0) TS(30);
        }
        bar_arrive(10, 576);
        TS(1);
      } else bar_sync(1 + wg, 128);
      phase &= 1;
      if (phase) { phase = 0; continue; }
      TS(14);
      float acc[20];
      const uint32_t alo = (wb >> 4) | (8u << 16);
      wg_fence();
      wgmma40_ss_init(acc, alo, alo + 1024, 2048 >> 4);
#pragma unroll
      for (int k = 1; k < 8; k++) wgmma40_ss(acc, alo + k * 16, alo + 1024 + k * 16, 2048 >> 4);
      wg_commit();
      const uint4 k4 = lds128(wb + W_MISC + 16);
      const float k2048 = (float)(int)(k4.x + k4.y + k4.z + k4.w) * (1.f / 262144.f);
      const uint32_t dk = lds16(OFF_WR + 1152 + (wg + first) * 2);
      const int ef = max(em, min((int)((dk >> 7) & 255u) - 7, 238));
      asm volatile("st.shared.u8 [%0], %1;" :: "r"(MISC_EM + wg + first), "r"(ef + 9) : "memory");
      const float un = __uint_as_float((uint32_t)max(114 + em - ef, 0) << 23), d0 = wt ? 0.f : bf_lo(dk) * __uint_as_float((uint32_t)(245 - ef) << 23);
      wg_wait<0>();
      kw.x = pack_h(fmaf(acc[0] - acc[3], un, d0), (acc[4] - acc[7]) * un);
      kw.y = pack_h((acc[8] - acc[11]) * un, (acc[12] - acc[15]) * un);
      kw.z = pack_h((acc[16] - acc[19]) * un, k2048 * un);
      TS(24);
      ep = 0;
      if (two) SPIN_WHILE(ep == 0, ep = lds32(MISC_EPOCH));
      if (five || !two) break;
      str128(kx, kw.x, kw.y, kw.z, ep);
      two = false;
    }
    if (lane == 0) mbar_arrive(MB_KF + wg * 8);
    if (two) { mbar_wait(MB_KF); zero_pads(OFF_W + ALT, wt); }
    uint32_t tb = wb;
#pragma unroll 1
    for (;;) {
      kgen_build(tb, wg, wt, kw.x, kw.y, kw.z);
      TS(15);
      if (!two) break;
      two = false;
      kw.w = 0;
      SPIN_WHILE(kw.w != ep, kw = ldr128(kx));
      tb = OFF_W + ALT;
    }
    fence_async();
    TS(31);
    if (tb != wb) bar_arrive(7, 288);
    bar_sync(1 + wg, 128);
  }
  uint32_t tpub;
  ConvPre pre;
  conv_pre(pre, wb + (cv.ca & 0xFFFFu), 3, true, warp & 2);
#pragma unroll 1
  for (int item = 0;; item++) {
    TS(2);
    conv_item(item ? OFF_W + ALT : wb, item ? OFF_W : OFF_T + (wg >> 1) * TILE, item ? 1 : 13 + (wg >> 1), item ? 128 : five && wg == 1 ? 192 : 256, pre, cv, p.zero,
              &tm.m[item ? 9 : 7], item ? 512 + (c >> 1) : (wg >> 1) * 128 + c, warp, lane, five && wg >= X_GW, five && !wg && !item);
    tpub = clock() - (item ? X_YD : wg >= 2 ? X_YD2 : 0);
    if (wg || !five || item) break;
    TS(27);
  }
  TS(4);
  PAD(X_PAD1)

  const int ln = lane ^ p.zero, td = warp * 32 + ln, gg = ln >> 2, tt = ln & 3;
  const int tok = c * 16 + warp;
  const int fu = warp / 3, fk = warp - fu * 3;
  uint32_t wa[12][4];
  uint4 ha[3];
  const uint4* hsrc = &p.s->HS[td + (td / 24) * 48];
  {
    uint32_t hw[9], wr[9];
    const uint32_t row = keep(OFF_YT + warp * YT_PITCH + (warp >> 3) * 64 + ln * 16);
    const uint32_t wabase = keep(((ln & 8) ? OFF_W + (fk + 1) * W_BYTES : OFF_G + fk * 192 * pitch) + ((ln >> 4) * 8 + (ln & 7)) * pitch
                                 + (five ? ((fu ^ (ln >> 1)) & 3) : min(fu, 4)) * 16);
    float sw;
    {
      const bool three = wg == 1;
      const int ch = 8 * (tt >> 1) + gg;
      const uint32_t tr_addr = tr_base(ln);
      const uint4* ysrc = &p.s->X[c * DM * 2 + ch * 2 + (tt & 1)];
      uint32_t x[3][4], s[3];
      uint4 v[3];
#define TL(q) ((q) < 2 ? 2 * warp + (q) : 28 + warp)
      asm volatile("cp.async.bulk.wait_group.read 0;" ::: "memory");
      if (wg >= 2) { const uint32_t ts = lds32(MISC_T0); while ((int)(clock() - ts) < X_XS) {} }
      while ((int)(clock() - tpub) < X_YD) {}
      TS(5);
      v[0] = ldr128(ysrc + TL(0) * 32); v[1] = ldr128(ysrc + TL(1) * 32); v[2] = make_uint4(three, 0, 0, 0);
      if (X_REL == 1 || (X_REL == 2 && wg != 1)) mbar_wait(MB_REL);
#pragma unroll
      for (int i = 0; i < 6; i++) if (i < 4 || three) wr[i] = (gg & 2) ? ones : lds32(OFF_WR + TL(i >> 1) * 32 + (i & 1) * 16 + tt * 4);
      const uint32_t ha = keep(OFF_YT + (ln & 7) * YT_PITCH + (ln >> 4) * (8 * YT_PITCH + 64) + (ln & 8) * 2);
      const uint32_t pa = keep(OFF_PART + warp * 4 + ((gg & 2) * 8 + (gg & 4) * 2 + 2 * tt + (gg & 1)) * 80), pb = keep(OFF_PART + 2560 + warp * 4 + gg * 80);
      float dl[4] = {0.f, 0.f, 0.f, 0.f}, dh[4] = {0.f, 0.f, 0.f, 0.f};
      sw = __uint_as_float(lds32(MISC_SW));
#pragma unroll
      for (int q = 0; q < 3; q++) {
        if (q < 2 || three) {
          ldsm4t(tr_addr + TL(q) * 32, x[q][0], x[q][1], x[q][2], x[q][3]);
        }
      }
      mbar_wait(MB_SC);
#pragma unroll
      for (int q = 0; q < 3; q++) {
        asm volatile("ld.shared.u8 %0, [%1];" : "=r"(s[q]) : "r"((q < 2 ? sc_addr(warp) + q * 16 : sc_addr(16) + (warp & 3) * 16) + ch) : "memory");
        s[q] = keep(s[q] * 0x800080u);
      }
#define FIN(q) stsm4t(tr_addr + TL(q) * 32, bf_fma2(h2bf(v[q].x), s[q], x[q][0]), bf_fma2(h2bf(v[q].y), s[q], x[q][1]), bf_fma2(h2bf(v[q].z), s[q], x[q][2]), bf_fma2(h2bf(v[q].w), s[q], x[q][3]));
      SPIN_WHILE((v[0].x | v[1].x) & 1u, _Pragma("unroll") for (int q = 0; q < 3; q++) if (v[q].x & 1u) v[q] = ldr128(ysrc + TL(q) * 32));
      if (v[2].x & 1u) v[2] = ldr128(ysrc + TL(2) * 32);
#define STAT(q) { uint32_t r0, r1, r2, r3; ldsm4(ha + TL(q) * 32, r0, r1, r2, r3); \
        mma_bf16(dl, r0, wr[2 * q], r1, wr[2 * q + 1], r0, r1); mma_bf16(dh, r2, wr[2 * q], r3, wr[2 * q + 1], r2, r3); }
      FIN(0) FIN(1)
      __syncwarp();
      STAT(0) STAT(1)
      if (three) {
        SPIN_WHILE(v[2].x & 1u, if (v[2].x & 1u) v[2] = ldr128(ysrc + TL(2) * 32));
        FIN(2)
        __syncwarp();
        STAT(2)
      }
      if (gg & 1) { dl[0] = dl[1]; dl[2] = dl[3]; dh[0] = dh[1]; dh[2] = dh[3]; }
      sts32(pa, __float_as_uint((gg & 4) ? dh[2] : dl[2]));
      if (tt == (gg >> 1)) { sts32(pb, __float_as_uint(dl[0])); sts32(pb + 640, __float_as_uint(dh[0])); }
#undef STAT
#undef FIN
#undef TL
    }
    uint32_t ra = keep(OFF_PART + (ln & 15) * 80 + (ln & 16) * 2);
    uint16_t* rp = (uint16_t*)p.s->R + c * 16 + (ln & 15);
    const uint2* rsrc = (const uint2*)p.s->R + td;
    asm volatile("" : "+l"(rp), "+l"(rsrc), "+l"(hsrc));
    uint2 rv = make_uint2(0u, 0u);
    TS(28);
    if (warp != X_PW) bar_sync(0, 544);
    else {
      float z[3], rd;
      asm volatile("bar.sync 0, 544;" : "+r"(ra) :: "memory");
#pragma unroll
      for (int k = 2; k >= 0; k--) {
        const uint4 a = lds128(ra + k * 1280), b = lds128(ra + k * 1280 + 16);
        z[k] = ((__uint_as_float(a.x) + __uint_as_float(a.y)) + (__uint_as_float(a.z) + __uint_as_float(a.w))) + ((__uint_as_float(b.x) + __uint_as_float(b.y)) + (__uint_as_float(b.z) + __uint_as_float(b.w)));
      }
#pragma unroll
      for (int k = 2; k >= 0; k--) z[k] += __shfl_xor_sync(0xffffffffu, z[k], 16);
      const LnC l = ln_consts(z[1], z[2], rd);
      const uint32_t b = pack_bf(0.f, fmaf(-bf_lo(l.m2), sw, z[0]) * rd);
      const uint32_t k16 = max(min((b ^ (((int)b >> 31) | 0x80000000u)) >> 16, 0xFFFEu), 1u);
      if (ln < 16) str16(rp, k16);
      sts64(OFF_RK + (ln & 15) * 8, __byte_perm(l.m2, l.rh2, 0x5410), __byte_perm(l.rl2, k16, 0x5410));
      sts128(MISC_CNT + ln * 16, 0, 0, 0, 0);
    }
    mbar_wait(MB_GU);
#define LD_HW { const uint4 a = lds128(row), b = lds128(row + 512); hw[8] = lds32(row + 1024 - ln * 12); \
      hw[0] = a.x; hw[1] = a.y; hw[2] = a.z; hw[3] = a.w; hw[4] = b.x; hw[5] = b.y; hw[6] = b.z; hw[7] = b.w; }
    LD_HW
    const uint32_t tr0 = clock();
    bar_sync(5, 512);
    TS(7);
    const uint2 lk = lds64(OFF_RK + warp * 8);
    LnC l2;
    l2.m2 = __byte_perm(lk.x, 0, 0x1010); l2.rh2 = __byte_perm(lk.x, 0, 0x3232); l2.rl2 = __byte_perm(lk.y, 0, 0x1010);
    const uint32_t key = (lk.y & 0xFFFF0000u) | (2047 - tok);
    uint32_t loc = ln < 16 ? (lds32(OFF_RK + 4 + ln * 8) & 0xFFFF0000u) | (2047 - c * 16 - ln) : 0u;
    int rank = __popc(__ballot_sync(0xffffffffu, loc > key));
#pragma unroll
    for (int i = 0; i < 9; i++) wr[i] = keep(ln_apply(hw[i], l2.m2, l2.rh2, l2.rl2));
#define OUT_ROW { uint32_t* o = p.out + tok * 288 + ln * 4; \
      *(uint4*)o = make_uint4(bf_add2(hw[0], wr[0]), bf_add2(hw[1], wr[1]), bf_add2(hw[2], wr[2]), bf_add2(hw[3], wr[3])); \
      *(uint4*)(o + 128) = make_uint4(bf_add2(hw[4], wr[4]), bf_add2(hw[5], wr[5]), bf_add2(hw[6], wr[6]), bf_add2(hw[7], wr[7])); \
      o[256 - ln * 3] = bf_add2(hw[8], wr[8]); }
    uint4* hs = p.s->HS + ln;
    asm volatile("" : "+l"(hs));
#pragma unroll 1
    for (int base = 0; base < 8; base += 2) {
      uint32_t T[2];
#pragma unroll
      for (int j = 0; j < 2; j++) {
        const uint32_t mx = __reduce_max_sync(0xffffffffu, loc);
        if (loc == mx) loc = 0;
        T[j] = (td >> 2) < c ? (mx & 0xFFFF0000u) - 1u : mx | 0xFFFFu;
      }
      const uint32_t sh = keep(rank == base ? 0x4410u : rank == base + 1 ? 0x4432u : 0x4445u), ca = keep(MISC_CNT + base * 64 + ln * 4);
      TS(29);
      if (base == 0) {
        while ((int)(clock() - tr0) < X_RD) {}
        if ((td >> 2) != c) rv = ldr64(rsrc);
        if (rank >= X_OR) OUT_ROW
        if (warp < (five ? 12 : 15)) {
#pragma unroll
          for (int k = 0; k < X_WS; k++) ldsm4t(wabase + k * 16 * pitch, wa[k][0], wa[k][1], wa[k][2], wa[k][3]);
        }
      }
      uint32_t cnt;
#pragma unroll 1
      for (int it = 0; it < SPIN_MAX; it++) {
        const uint32_t xs = rv.x << 16, ys = rv.y << 16;
        const bool bad = max(max(rv.x, xs), max(rv.y, ys)) >= 0xFFFF0000u;
        uint32_t cn2 = 0;
        cnt = bad ? 256u : 0u;
#pragma unroll
        for (int j = 0; j < 2; j++)
          asm("{ .reg .pred a, b, c, d; setp.gt.u32 a, %2, %6; setp.gt.u32 b, %3, %6; setp.gt.u32 c, %4, %6; setp.gt.u32 d, %5, %6; "
              "@a add.u32 %1, %1, %7; @b add.u32 %1, %1, %7; @c add.u32 %0, %0, %7; @d add.u32 %0, %0, %7; }"
              : "+r"(cnt), "+r"(cn2) : "r"(rv.x), "r"(rv.y), "r"(xs), "r"(ys), "r"(T[j]), "r"(1u << (16 * j)));
        cnt = __reduce_add_sync(0xffffffffu, cnt + cn2);
        asm volatile("{ .reg .pred q; setp.eq.u32 q, %2, 0; @q red.shared.add.u32 [%0], %1; }" :: "r"(ca), "r"(cnt), "r"(cnt & 0x3F00u) : "memory");
        if (!(cnt & 0x3F00u)) break;
        if (bad) rv = ldr64(rsrc);
      }
      TS(16);
      bar_sync(0, 512);
      cnt = lds32(ca);
      if (base == 0) tpub = clock();
      const int gr = rank + __byte_perm(cnt, 0x800u, sh);
      if (gr < 8) {
        uint4* ks = hs + 1152 + gr;
        hs = (uint4*)((char*)hs + gr * 1152);
        asm volatile("{ .reg .b128 t, u; .reg .b64 a, b, c, d; mov.b64 a, {%1,%2}; mov.b64 b, {%3,%4}; mov.b64 c, {%5,%6}; mov.b64 d, {%7,%8}; mov.b128 t, {a, b}; mov.b128 u, {c, d}; "
                     "st.relaxed.gpu.global.b128 [%0], t; st.relaxed.gpu.global.b128 [%0 + 512], u; }"
                     :: "l"(hs), "r"(wr[0]), "r"(wr[1]), "r"(wr[2]), "r"(wr[3]), "r"(wr[4]), "r"(wr[5]), "r"(wr[6]), "r"(wr[7]) : "memory");
        str32((uint32_t*)(hs + 64) - ln * 3, wr[8]);
        str128(hs + 576, hw[0], hw[1], hw[2], hw[3]); str128(hs + 608, hw[4], hw[5], hw[6], hw[7]); str32((uint32_t*)(hs + 640) - ln * 3, hw[8]);
        if (ln == 0) str32(ks, key);
        rank = 16;
      }
      if (__all_sync(0xffffffffu, (int)(cnt >> 16) + base + 2 >= 8)) break;
    }
    TS(8);
    if (warp < (five ? 12 : 15)) {
#pragma unroll
      for (int k = X_WS; k < 12; k++) ldsm4t(wabase + k * 16 * pitch, wa[k][0], wa[k][1], wa[k][2], wa[k][3]);
    }
    if (warp < 6) while ((int)(clock() - tpub) < X_HD) {}
    TS(19);
    if (warp < 6) { ha[0] = ldr128(hsrc); ha[1] = ldr128(hsrc + 24); ha[2] = ldr128(hsrc + 48); }
    if (rank < X_OR) OUT_ROW
  }
  uint32_t wd[10][4];
  const uint32_t xb = keep(OFF_XS + (ln & 7) * 1168 + (fk * 24 + (ln >> 3)) * 16);
  if (warp >= 7) {
    const uint32_t db = down_box(warp - 7, five) + (ln & 7) * 128;
    mbar_wait(MB_D);
#pragma unroll
    for (int j = 0; j < 4; j++) {
      const uint32_t a = db + (ln >> 4) * 1024 + (((2 * j + ((ln >> 3) & 1)) ^ (ln & 7)) << 4);
      ldsm4t(a, wd[j][0], wd[j][1], wd[j][2], wd[j][3]);
      ldsm4t(a + 2048, wd[4 + j][0], wd[4 + j][1], wd[4 + j][2], wd[4 + j][3]);
    }
#pragma unroll
    for (int j = 0; j < 2; j++) ldsm4t(db + 4096 + (((4 * j + (ln >> 3)) ^ (ln & 7)) << 4), wd[8 + j][0], wd[8 + j][1], wd[8 + j][2], wd[8 + j][3]);
  } else if (warp < 6) {
    const uint32_t xs = keep(OFF_XS + (td + (td / 24) * 49) * 16);
#pragma unroll 1
    for (int it = 0; it < SPIN_MAX; it++) {
      const bool bad = max(max(max(ha[0].x, ha[1].x), max(ha[2].x, ha[2].y)), max(ha[2].z, ha[2].w)) == ~0u;
      if (!__any_sync(0xffffffffu, bad)) break;
      if (bad) { ha[0] = ldr128(hsrc); ha[1] = ldr128(hsrc + 24); ha[2] = ldr128(hsrc + 48); }
    }
#pragma unroll
    for (int q = 0; q < 3; q++) sts128(xs + q * 384, ha[q].x, ha[q].y, ha[q].z, ha[q].w);
  }
  TS(9);

  if (!(M_ & 2)) bar_sync(0, 512);
  if (warp >= (five ? 12 : 15)) { if (M_ & 2) bar_sync(0, 512); }
  else {
    if (M_ & 2) bar_sync(0, 512);
    float d0[4] = {0.f, 0.f, 0.f, 0.f}, d1[4] = {0.f, 0.f, 0.f, 0.f};
#pragma unroll
    for (int k = 0; k < 12; k += 2) {
      uint32_t b0, b1, b2, b3;
      ldsm4(xb + k * 32, b0, b1, b2, b3);
      mma_bf16(d0, wa[k][0], wa[k][1], wa[k][2], wa[k][3], b0, b1);
      mma_bf16(d1, wa[k + 1][0], wa[k + 1][1], wa[k + 1][2], wa[k + 1][3], b2, b3);
    }
    sts128(OFF_RED + td * 16, __float_as_uint(d0[0] + d1[0]), __float_as_uint(d0[1] + d1[1]), __float_as_uint(d0[2] + d1[2]), __float_as_uint(d0[3] + d1[3]));
  }
  TS(26);
  if (warp < 5) {
    const uint32_t rb = OFF_RED + warp * 1536 + ln * 16;
    bar_sync(9, 512);
    const uint4 pa = lds128(rb), pb = lds128(rb + 512), pc = lds128(rb + 1024);
    const float ga = bfr(__uint_as_float(pa.x) + __uint_as_float(pb.x) + __uint_as_float(pc.x));
    const float gb = bfr(__uint_as_float(pa.y) + __uint_as_float(pb.y) + __uint_as_float(pc.y));
    const uint32_t uu = pack_bf(__uint_as_float(pa.z) + __uint_as_float(pb.z) + __uint_as_float(pc.z), __uint_as_float(pa.w) + __uint_as_float(pb.w) + __uint_as_float(pc.w));
    float ra, rb2;
    asm("rcp.approx.ftz.f32 %0, %1;" : "=f"(ra) : "f"(1.f + ex2(ga * -1.4426950408889634f)));
    asm("rcp.approx.ftz.f32 %0, %1;" : "=f"(rb2) : "f"(1.f + ex2(gb * -1.4426950408889634f)));
    const uint32_t act = bf_mul2(pack_bf(ga * ra, gb * rb2), uu);
    sts32(OFF_ACT + td * 4, act);
  } else bar_arrive(9, 512);
  uint4* dst = &p.s->X[c * DM * 2 + (warp - 7) * 64 + tt * 8 + gg];
  asm volatile("" : "+l"(dst));
  if (!(M_ & 1)) { bar_sync(8, 512); tpub = clock(); }
  if (warp < 7) { if (M_ & 1) { bar_sync(8, 512); tpub = clock(); } }
  else {
    uint32_t b0, b1, b2, b3, b4;
    if (M_ & 1) bar_sync(8, 512);
    ldsm4t(OFF_ACT + ln * 16, b0, b1, b2, b3);
    asm volatile("ldmatrix.sync.aligned.m8n8.x1.trans.shared.b16 {%0}, [%1];" : "=r"(b4) : "r"(OFF_ACT + 512 + ln * 16) : "memory");
    if (M_ & 1) tpub = clock();
    float y[4][4];
#pragma unroll
    for (int j = 0; j < 4; j++) {
      y[j][0] = y[j][1] = y[j][2] = y[j][3] = 0.f;
      mma_bf16(y[j], wd[j][0], wd[j][1], wd[j][2], wd[j][3], b0, b1);
    }
#pragma unroll
    for (int j = 0; j < 4; j++) mma_bf16(y[j], wd[4 + j][0], wd[4 + j][1], wd[4 + j][2], wd[4 + j][3], b2, b3);
    if (!five) {
#pragma unroll
      for (int j = 0; j < 4; j++) mma_bf16_k8(y[j], wd[8 + (j >> 1)][2 * (j & 1)], wd[8 + (j >> 1)][2 * (j & 1) + 1], b4);
    }
    str128(dst, (pack_bf(y[0][0], y[0][1]) & ~1u) | 0x10000u, pack_bf(y[0][2], y[0][3]), pack_bf(y[1][0], y[1][1]), pack_bf(y[1][2], y[1][3]));
    str128(dst + 32, (pack_bf(y[2][0], y[2][1]) & ~1u) | 0x10000u, pack_bf(y[2][2], y[2][3]), pack_bf(y[3][0], y[3][1]), pack_bf(y[3][2], y[3][3]));
  }
  TS(10);

  if (c < 72) {
    const uint4* src = &p.s->X[(warp * 4 + tt) * (DM * 2) + c * 8 + gg];
    const int slot = (c & 3) * 2 + (ln >> 4), dw = (c >> 2) * 16 + (ln & 15);
    uint32_t hv = 0, kv = 0, res = 0, rs2 = 0;
    uint32_t* o = p.out;
    if (warp == 0) {
      hv = ~0u;
      SPIN_WHILE(max(hv, kv) == ~0u, hv = ldr32((const uint32_t*)p.s->HS + 2304 + slot * 288 + dw); kv = ldr32(&p.s->HS[1152 + slot]));
      const float r = bf_hi(kv ^ (((int)~kv >> 31) | 0x80000000u));
      float rs;
      asm("rcp.approx.ftz.f32 %0, %1;" : "=f"(rs) : "f"(1.f + ex2(r * -1.4426950408889634f)));
      rs2 = keep(pack_bf(rs, rs));
      res = lds32(OFF_XS + slot * 1168 + dw * 4);
      o += (2047 - (int)(kv & 2047u)) * 288 + dw;
      asm volatile("" : "+l"(o));
    }
    const uint32_t sel = (gg & 1) ? 0x3F800000u : 0x00003F80u;
    const uint32_t q0 = keep((gg >> 1) == 0 ? sel : 0u), q1 = keep((gg >> 1) == 1 ? sel : 0u), q2 = keep((gg >> 1) == 2 ? sel : 0u), q3 = keep((gg >> 1) == 3 ? sel : 0u);
#if M_ & 4
    const uint32_t fa = keep(OFF_RED + warp * 8 + ((gg & 1) * 16 + (gg >> 1) * 4 + tt) * 144), fb = keep(OFF_RED + ln * 144);
#else
    const uint32_t fa = keep(OFF_FIN + warp * 256 + (gg & 1) * 128 + (gg >> 1) * 32 + tt * 8), fb = keep(OFF_FIN + ln * 8);
#endif
    uint4 a0 = make_uint4(0, 0, 0, 0), a1 = a0;
    while ((int)(clock() - tpub) < X_PD) {}
    SPIN_WHILE(!(a0.x & a1.x & 0x10000u), if (!(a0.x & 0x10000u)) a0 = ldr128(src); if (!(a1.x & 0x10000u)) a1 = ldr128(src + 64 * DM * 2));
    float d[4] = {0.f, 0.f, 0.f, 0.f}, e[4] = {0.f, 0.f, 0.f, 0.f}, d2[4] = {0.f, 0.f, 0.f, 0.f}, e2[4] = {0.f, 0.f, 0.f, 0.f};
    mma_bf16(d, q0, q2, q1, q3, a0.x, a0.y); mma_bf16(e, q0, q2, q1, q3, a0.z, a0.w);
#if M_ & 8
    mma_bf16(d2, q0, q2, q1, q3, a1.x, a1.y); mma_bf16(e2, q0, q2, q1, q3, a1.z, a1.w);
    sts64(fa, __float_as_uint(d[0] + e[2] + d2[0] + e2[2]), __float_as_uint(d[1] + e[3] + d2[1] + e2[3]));
#else
    mma_bf16(d, q0, q2, q1, q3, a1.x, a1.y); mma_bf16(e, q0, q2, q1, q3, a1.z, a1.w);
    sts64(fa, __float_as_uint(d[0] + e[2]), __float_as_uint(d[1] + e[3]));
#endif
    TS(11);
    if (warp == 0) {
      bar_sync(0, 512);
      float2 s[16];
#if !(M_ & 4)
#pragma unroll
      for (int i = 0; i < 16; i++) { const uint2 q = lds64(fb + i * 256); s[i] = make_float2(__uint_as_float(q.x), __uint_as_float(q.y)); }
#else
#pragma unroll
      for (int i = 0; i < 16; i += 2) { const uint4 q = lds128(fb + i * 8); s[i] = make_float2(__uint_as_float(q.x), __uint_as_float(q.y)); s[i + 1] = make_float2(__uint_as_float(q.z), __uint_as_float(q.w)); }
#endif
#pragma unroll
      for (int k = 1; k < 16; k *= 2)
#pragma unroll
        for (int i = 0; i < 16; i += 2 * k) { s[i].x += s[i + k].x; s[i].y += s[i + k].y; }
      *o = bf_add2(hv, bf_add2(res, bf_mul2(pack_bf(s[0].x, s[0].y), rs2)));
    } else bar_arrive(0, 512);
  }
  TS(12);
  TS_DUMP();
}

typedef CUresult (*EncodeFn)(CUtensorMap*, CUtensorMapDataType, cuuint32_t, void*, const cuuint64_t*, const cuuint64_t*, const cuuint32_t*,
                             const cuuint32_t*, CUtensorMapInterleave, CUtensorMapSwizzle, CUtensorMapL2promotion, CUtensorMapFloatOOBfill);

}

extern "C" void kernel_launch(void* const* d_in, const int* in_sizes, int n_in, void* d_out, int out_size) {
  (void)in_sizes; (void)n_in; (void)out_size;
  static EncodeFn enc = nullptr;
  static Scratch* scratch = nullptr;
  if (!enc) {
    void* fn = nullptr;
    cudaDriverEntryPointQueryResult qr;
    cudaGetDriverEntryPoint("cuTensorMapEncodeTiled", &fn, cudaEnableDefault, &qr);
    enc = (EncodeFn)fn;
    cudaGetSymbolAddress((void**)&scratch, g_S);
    cudaFuncSetAttribute(fused_kernel<false>, cudaFuncAttributeMaxDynamicSharedMemorySize, SMEM_BYTES);
    cudaFuncSetAttribute(fused_kernel<true>, cudaFuncAttributeMaxDynamicSharedMemorySize, SMEM_BYTES);
  }
  TMaps tm;
  for (int i = 0; i < 6; i++) {
    const bool dn = i % 3 == 2;
    const cuuint32_t w = i < 3 ? 40 : 32;
    cuuint64_t gd[3] = {(cuuint64_t)(dn ? 64 : FF), (cuuint64_t)(dn ? FF : DM), 9};
    cuuint64_t gs[2] = {(cuuint64_t)(dn ? DM * 2 : FF * 2), 128};
    cuuint32_t bx[3] = {dn ? 64 : w, dn ? w : 96, i < 3 ? 2u : 3u};
    cuuint32_t es[3] = {1, 1, 1};
    enc(&tm.m[i], CU_TENSOR_MAP_DATA_TYPE_BFLOAT16, dn ? 3 : 2, d_in[11 + i % 3], gd, gs, bx, es, CU_TENSOR_MAP_INTERLEAVE_NONE,
        dn ? CU_TENSOR_MAP_SWIZZLE_128B : i < 3 ? CU_TENSOR_MAP_SWIZZLE_NONE : CU_TENSOR_MAP_SWIZZLE_64B,
        (CUtensorMapL2promotion)X_PROMO, CU_TENSOR_MAP_FLOAT_OOB_FILL_NONE);
  }
  for (int i = 6; i < 10; i++) {
    cuuint64_t gd[3] = {i < 8 ? 32u : 16u, i < 8 ? DM / 2u : DM, NCTA};
    cuuint64_t gs[2] = {i < 8 ? 64u : 32u, DM * 32};
    cuuint32_t bx[3] = {32, 1, (i & 1) ? 128u : 136u};
    cuuint32_t es[3] = {1, 1, 1};
    enc(&tm.m[i], CU_TENSOR_MAP_DATA_TYPE_FLOAT16, 3, scratch->X, gd, gs, bx, es, CU_TENSOR_MAP_INTERLEAVE_NONE, CU_TENSOR_MAP_SWIZZLE_64B,
        CU_TENSOR_MAP_L2_PROMOTION_NONE, CU_TENSOR_MAP_FLOAT_OOB_FILL_NONE);
  }
  Params p;
  p.x = (const unsigned char*)d_in[0];
  bool far = false;
  for (int i = 0; i < 7; i++) {
    p.far[i] = (const unsigned char*)d_in[1 + i];
    const long long d = (long long)((intptr_t)d_in[1 + i] - (intptr_t)d_in[0]);
    p.off[i] = (int)(d / 16);
    if ((long long)p.off[i] * 16 != d) far = true;
  }
  p.dskip = (const uint16_t*)d_in[8];
  p.w_r = (const uint32_t*)d_in[10];
  for (int f = 0; f < 2; f++) {
    static const int kind[17] = {0, 0, 0, 0, 2, 2, 0, 0, 1, 1, 1, 1, 1, 1, 2, 2, 2};
    static const int idx[2][17] = {{2, 3, 4, 5, 6, 8, 0, 1, 0, 1, 2, 3, 4, 5, 0, 2, 4}, {2, 3, 4, 5, 0, -1, 0, 1, 0, 1, 2, 3, 4, 5, 3, -1, 6}};
    static const int blk[2][17] = {{-1, -1, -1, -1, 0, -1, 4, -1, 1, -1, 2, -1, 3, -1, 16, -1, -1}, {-1, -1, -1, -1, 1, -1, 4, -1, -1, -1, 2, -1, 3, -1, 16, -1, -1}};
    const int pitch = f ? 64 : 80;
    for (int u = 0; u < 17; u++) {
      const int s = idx[f][u];
      const uint32_t dst = kind[u] == 0 ? OFF_G + s * 96 * pitch : kind[u] == 2 ? down_box(s, f) : OFF_W + W_BYTES + (s >> 1) * W_BYTES + (s & 1) * 96 * pitch;
      const uint32_t mb = u >= 14 ? (u >= X_HU ? MB_H - OFF_MISC : X_HB) : blk[f][u] >= 0 ? MB_KF - OFF_MISC + blk[f][u] * 8 : 0;
      p.sched[f][u] = s < 0 ? 3u : kind[u] | s << 2 | mb << 6 | dst << 14;
    }
  }
  p.out = (uint32_t*)d_out;
  p.zero = 0;
  p.ts = nullptr;
  p.s = scratch;
  if (far) { fused_kernel<true><<<NCTA, NT, SMEM_BYTES, cudaStreamPerThread>>>(p, tm); return; }
  fused_kernel<false><<<NCTA, NT, SMEM_BYTES, cudaStreamPerThread>>>(p, tm);
}
```

```cpp
#include <cuda_runtime.h>
#include <cuda.h>
#include <cuda_bf16.h>
#include <cuda_fp16.h>
#include <stdint.h>
#include <stddef.h>

namespace {

constexpr int NCTA = 128;
constexpr int NT = 640;
constexpr int DM = 576;
constexpr int FF = 4608;
constexpr int SPIN_MAX = 1 << 20;

struct Scratch {
  uint4 X[NCTA * DM * 2];
  uint4 KX[64 * 128];
  uint4 HS[1152 + 8];
  uint4 R[256];
  uint4 SC[256];
  uint32_t FLAG[NCTA * 8];
};
__device__ Scratch g_S;

#define CLKS(i)
#define TS(i)
#define TSX(i)
#define TS_DUMP()

constexpr int SB = 1024;
constexpr int BOX = 15360;
constexpr int OFF_G = SB;
constexpr int OFF_W = OFF_G + 3 * BOX;
constexpr int W_KT = 26624;
constexpr int W_L3 = W_KT + 4416;
constexpr int W_CW = W_L3 + 4096;
constexpr int W_MISC = W_CW + 640;
constexpr int W_BYTES = 35840;
constexpr int TILE = 10240;
constexpr int OFF_T = OFF_W + 4 * W_BYTES;
constexpr int ALT = TILE - W_KT;
static_assert(W_MISC + 32 <= W_BYTES && OFF_W % 1024 == 0 && W_BYTES % 1024 == 0 && W_BYTES + ALT <= 20480, "wg block");
constexpr int YT_PITCH = 1184;
constexpr int OFF_YT = OFF_T + 2 * TILE;
constexpr int OFF_WR = OFF_YT + 16 * YT_PITCH + 64;
constexpr int OFF_MISC = OFF_WR + 2304;
constexpr int SMEM_BYTES = OFF_MISC + 1024 - SB;
static_assert(OFF_YT % 16 == 0 && OFF_MISC % 16 == 0, "align");
static_assert(SMEM_BYTES <= 232448, "smem");
constexpr int MB_GU = OFF_MISC;
constexpr int MB_D = OFF_MISC + 8;
constexpr int MB_KF = OFF_MISC + 16;
constexpr int MB_GF = OFF_MISC + 48;
constexpr int MB_SC = OFF_MISC + 56;
constexpr int MB_UL = OFF_MISC + 64;
constexpr int MB_REL = OFF_MISC + 104;
constexpr int MB_GO = OFF_MISC + 112;
constexpr int MB_H = MB_KF + 128;
constexpr int MISC_EPOCH = OFF_MISC + 152;
constexpr int MISC_SW = OFF_MISC + 156;
constexpr int MISC_RT = OFF_MISC + 160;
constexpr int MISC_T0 = OFF_MISC + 296;
constexpr int MISC_EM = OFF_MISC + 288;
constexpr int OFF_PART = OFF_W + 20480;
constexpr int OFF_RK = OFF_PART + 3840;
constexpr int MISC_LN1 = OFF_MISC + 192;
constexpr int OFF_XS = OFF_T;
constexpr int OFF_RED = OFF_T + TILE;
constexpr int OFF_FIN = OFF_W + 3 * W_BYTES + W_KT;
constexpr int OFF_ACT = OFF_FIN + 4096;
constexpr int MISC_CNT = OFF_ACT + 1024;

__device__ __forceinline__ uint32_t smem_u32(const void* p) { return (uint32_t)__cvta_generic_to_shared(p); }
__device__ __forceinline__ uint32_t lds32(uint32_t a) { uint32_t v; asm volatile("ld.shared.b32 %0, [%1];" : "=r"(v) : "r"(a) : "memory"); return v; }
__device__ __forceinline__ uint32_t lds16(uint32_t a) { uint16_t v; asm volatile("ld.shared.u16 %0, [%1];" : "=h"(v) : "r"(a) : "memory"); return v; }
__device__ __forceinline__ uint2 lds64(uint32_t a) { uint2 v; asm volatile("ld.shared.v2.b32 {%0,%1}, [%2];" : "=r"(v.x), "=r"(v.y) : "r"(a) : "memory"); return v; }
__device__ __forceinline__ uint4 lds128(uint32_t a) { uint4 v; asm volatile("ld.shared.v4.b32 {%0,%1,%2,%3}, [%4];" : "=r"(v.x), "=r"(v.y), "=r"(v.z), "=r"(v.w) : "r"(a) : "memory"); return v; }
__device__ __forceinline__ void sts16(uint32_t a, uint32_t v) { asm volatile("st.shared.u16 [%0], %1;" :: "r"(a), "h"((uint16_t)v) : "memory"); }
__device__ __forceinline__ void sts32(uint32_t a, uint32_t v) { asm volatile("st.shared.b32 [%0], %1;" :: "r"(a), "r"(v) : "memory"); }
__device__ __forceinline__ void sts64(uint32_t a, uint32_t x, uint32_t y) { asm volatile("st.shared.v2.b32 [%0], {%1,%2};" :: "r"(a), "r"(x), "r"(y) : "memory"); }
__device__ __forceinline__ void sts128(uint32_t a, uint32_t x, uint32_t y, uint32_t z, uint32_t w) { asm volatile("st.shared.v4.b32 [%0], {%1,%2,%3,%4};" :: "r"(a), "r"(x), "r"(y), "r"(z), "r"(w) : "memory"); }
__device__ __forceinline__ void ldsm4(uint32_t a, uint32_t& r0, uint32_t& r1, uint32_t& r2, uint32_t& r3) {
  asm volatile("ldmatrix.sync.aligned.m8n8.x4.shared.b16 {%0,%1,%2,%3}, [%4];" : "=r"(r0), "=r"(r1), "=r"(r2), "=r"(r3) : "r"(a) : "memory");
}
__device__ __forceinline__ void ldsm2(uint32_t a, uint32_t& r0, uint32_t& r1) {
  asm volatile("ldmatrix.sync.aligned.m8n8.x2.shared.b16 {%0,%1}, [%2];" : "=r"(r0), "=r"(r1) : "r"(a) : "memory");
}
__device__ __forceinline__ void ldsm4t(uint32_t a, uint32_t& r0, uint32_t& r1, uint32_t& r2, uint32_t& r3) {
  asm volatile("ldmatrix.sync.aligned.m8n8.x4.trans.shared.b16 {%0,%1,%2,%3}, [%4];" : "=r"(r0), "=r"(r1), "=r"(r2), "=r"(r3) : "r"(a) : "memory");
}
__device__ __forceinline__ void stsm4t(uint32_t a, uint32_t r0, uint32_t r1, uint32_t r2, uint32_t r3) {
  asm volatile("stmatrix.sync.aligned.m8n8.x4.trans.shared.b16 [%0], {%1,%2,%3,%4};" :: "r"(a), "r"(r0), "r"(r1), "r"(r2), "r"(r3) : "memory");
}
__device__ __forceinline__ uint4 ldr128(const void* p) {
  unsigned long long lo, hi;
  asm volatile("{ .reg .b128 t; ld.relaxed.gpu.global.b128 t, [%2]; mov.b128 {%0, %1}, t; }" : "=l"(lo), "=l"(hi) : "l"(p) : "memory");
  return make_uint4((uint32_t)lo, (uint32_t)(lo >> 32), (uint32_t)hi, (uint32_t)(hi >> 32));
}
__device__ __forceinline__ void str128(void* p, uint32_t x, uint32_t y, uint32_t z, uint32_t w) {
  asm volatile("{ .reg .b128 t; .reg .b64 lo, hi; mov.b64 lo, {%1,%2}; mov.b64 hi, {%3,%4}; mov.b128 t, {lo, hi}; st.relaxed.gpu.global.b128 [%0], t; }"
               :: "l"(p), "r"(x), "r"(y), "r"(z), "r"(w) : "memory");
}
__device__ __forceinline__ void str64(void* p, uint32_t x, uint32_t y) {
  asm volatile("{ .reg .b64 t; mov.b64 t, {%1,%2}; st.relaxed.gpu.global.b64 [%0], t; }" :: "l"(p), "r"(x), "r"(y) : "memory");
}
__device__ __forceinline__ uint32_t ldr32(const void* p) { uint32_t v; asm volatile("ld.relaxed.gpu.global.b32 %0, [%1];" : "=r"(v) : "l"(p) : "memory"); return v; }
__device__ __forceinline__ void str32(void* p, uint32_t v) { asm volatile("st.relaxed.gpu.global.b32 [%0], %1;" :: "l"(p), "r"(v) : "memory"); }
__device__ __forceinline__ void str16(void* p, uint32_t v) { asm volatile("st.relaxed.gpu.global.u16 [%0], %1;" :: "l"(p), "h"((uint16_t)v) : "memory"); }
__device__ __forceinline__ void fence_gpu() { asm volatile("fence.acq_rel.gpu;" ::: "memory"); }
__device__ __forceinline__ void bar_sync(int id, int n) { asm volatile("bar.sync %0, %1;" :: "r"(id), "r"(n) : "memory"); }
__device__ __forceinline__ void bar_arrive(int id, int n) { asm volatile("bar.arrive %0, %1;" :: "r"(id), "r"(n) : "memory"); }

__device__ __forceinline__ float bf_lo(uint32_t w) { return __uint_as_float(w << 16); }
__device__ __forceinline__ float bf_hi(uint32_t w) { return __uint_as_float(w & 0xFFFF0000u); }
__device__ __forceinline__ uint32_t pack_bf(float lo, float hi) { uint32_t r; asm("cvt.rn.bf16x2.f32 %0, %1, %2;" : "=r"(r) : "f"(hi), "f"(lo)); return r; }
__device__ __forceinline__ uint32_t pack_h(float lo, float hi) { uint32_t r; asm("cvt.rn.f16x2.f32 %0, %1, %2;" : "=r"(r) : "f"(hi), "f"(lo)); return r; }
__device__ __forceinline__ uint32_t pack_hv(float lo, float hi) { uint32_t r; asm volatile("cvt.rn.f16x2.f32 %0, %1, %2;" : "=r"(r) : "f"(hi), "f"(lo) : "memory"); return r; }
__device__ __forceinline__ float bfr(float x) { return bf_lo(pack_bf(x, 0.f)); }
__device__ __forceinline__ uint32_t bf_sub2(uint32_t a, uint32_t b) { __nv_bfloat162 r = __hsub2(*(__nv_bfloat162*)&a, *(__nv_bfloat162*)&b); return *(uint32_t*)&r; }
__device__ __forceinline__ uint32_t bf_add2(uint32_t a, uint32_t b) { __nv_bfloat162 r = __hadd2(*(__nv_bfloat162*)&a, *(__nv_bfloat162*)&b); return *(uint32_t*)&r; }
__device__ __forceinline__ uint32_t bf_mul2(uint32_t a, uint32_t b) { __nv_bfloat162 r = __hmul2(*(__nv_bfloat162*)&a, *(__nv_bfloat162*)&b); return *(uint32_t*)&r; }
__device__ __forceinline__ float2 h2f(uint32_t w) { return __half22float2(*(__half2*)&w); }
__device__ __forceinline__ float ex2(float x) { float r; asm("ex2.approx.ftz.f32 %0, %1;" : "=f"(r) : "f"(x)); return r; }
__device__ __forceinline__ float warp_sum(float v) {
#pragma unroll
  for (int o = 16; o > 0; o >>= 1) v += __shfl_xor_sync(0xffffffffu, v, o);
  return v;
}
__device__ __forceinline__ void mma_f16_f32(float* d, uint32_t a0, uint32_t a1, uint32_t a2, uint32_t a3, uint32_t b0, uint32_t b1) {
  asm volatile("mma.sync.aligned.m16n8k16.row.col.f32.f16.f16.f32 {%0,%1,%2,%3}, {%4,%5,%6,%7}, {%8,%9}, {%0,%1,%2,%3};"
               : "+f"(d[0]), "+f"(d[1]), "+f"(d[2]), "+f"(d[3]) : "r"(a0), "r"(a1), "r"(a2), "r"(a3), "r"(b0), "r"(b1));
}
__device__ __forceinline__ void mma_f16_f16(uint32_t& d0, uint32_t& d1, uint32_t a0, uint32_t a1, uint32_t a2, uint32_t a3, uint32_t b0, uint32_t b1) {
  asm volatile("mma.sync.aligned.m16n8k16.row.col.f16.f16.f16.f16 {%0,%1}, {%2,%3,%4,%5}, {%6,%7}, {%0,%1};"
               : "+r"(d0), "+r"(d1) : "r"(a0), "r"(a1), "r"(a2), "r"(a3), "r"(b0), "r"(b1));
}
__device__ __forceinline__ void mma_bf16(float* d, uint32_t a0, uint32_t a1, uint32_t a2, uint32_t a3, uint32_t b0, uint32_t b1) {
  asm volatile("mma.sync.aligned.m16n8k16.row.col.f32.bf16.bf16.f32 {%0,%1,%2,%3}, {%4,%5,%6,%7}, {%8,%9}, {%0,%1,%2,%3};"
               : "+f"(d[0]), "+f"(d[1]), "+f"(d[2]), "+f"(d[3]) : "r"(a0), "r"(a1), "r"(a2), "r"(a3), "r"(b0), "r"(b1));
}
__device__ __forceinline__ void mma_bf16_k8(float* d, uint32_t a0, uint32_t a1, uint32_t b0) {
  asm volatile("mma.sync.aligned.m16n8k8.row.col.f32.bf16.bf16.f32 {%0,%1,%2,%3}, {%4,%5}, {%6}, {%0,%1,%2,%3};"
               : "+f"(d[0]), "+f"(d[1]), "+f"(d[2]), "+f"(d[3]) : "r"(a0), "r"(a1), "r"(b0));
}

__device__ __forceinline__ void wg_fence() { asm volatile("wgmma.fence.sync.aligned;" ::: "memory"); }
__device__ __forceinline__ void wg_commit() { asm volatile("wgmma.commit_group.sync.aligned;" ::: "memory"); }
template <int N> __device__ __forceinline__ void wg_wait() { asm volatile("wgmma.wait_group.sync.aligned %0;" :: "n"(N) : "memory"); }
template <int TB> __device__ __forceinline__ void wgmma32(float* d, const uint32_t* a, uint32_t dlo, uint32_t dhi) {
  asm volatile("{ .reg .b64 dd; mov.b64 dd, {%20, %21}; wgmma.mma_async.sync.aligned.m64n32k16.f32.f16.f16 "
               "{%0,%1,%2,%3,%4,%5,%6,%7,%8,%9,%10,%11,%12,%13,%14,%15}, {%16,%17,%18,%19}, dd, 1, 1, 1, %22; }"
               : "+f"(d[0]), "+f"(d[1]), "+f"(d[2]), "+f"(d[3]), "+f"(d[4]), "+f"(d[5]), "+f"(d[6]), "+f"(d[7]), "+f"(d[8]), "+f"(d[9]), "+f"(d[10]), "+f"(d[11]), "+f"(d[12]), "+f"(d[13]), "+f"(d[14]), "+f"(d[15])
               : "r"(a[0]), "r"(a[1]), "r"(a[2]), "r"(a[3]), "r"(dlo), "r"(dhi), "n"(TB));
}
template <int TB> __device__ __forceinline__ void wgmma64(float* d, const uint32_t* a, uint32_t dlo, uint32_t dhi) {
  asm volatile("{ .reg .b64 dd; mov.b64 dd, {%36, %37}; wgmma.mma_async.sync.aligned.m64n64k16.f32.f16.f16 "
               "{%0,%1,%2,%3,%4,%5,%6,%7,%8,%9,%10,%11,%12,%13,%14,%15,%16,%17,%18,%19,%20,%21,%22,%23,%24,%25,%26,%27,%28,%29,%30,%31}, {%32,%33,%34,%35}, dd, 1, 1, 1, %38; }"
               : "+f"(d[0]), "+f"(d[1]), "+f"(d[2]), "+f"(d[3]), "+f"(d[4]), "+f"(d[5]), "+f"(d[6]), "+f"(d[7]), "+f"(d[8]), "+f"(d[9]), "+f"(d[10]), "+f"(d[11]), "+f"(d[12]), "+f"(d[13]), "+f"(d[14]), "+f"(d[15]), "+f"(d[16]), "+f"(d[17]), "+f"(d[18]), "+f"(d[19]), "+f"(d[20]), "+f"(d[21]), "+f"(d[22]), "+f"(d[23]), "+f"(d[24]), "+f"(d[25]), "+f"(d[26]), "+f"(d[27]), "+f"(d[28]), "+f"(d[29]), "+f"(d[30]), "+f"(d[31])
               : "r"(a[0]), "r"(a[1]), "r"(a[2]), "r"(a[3]), "r"(dlo), "r"(dhi), "n"(TB));
}
template <int TB> __device__ __forceinline__ void wgmma64_init(float* d, const uint32_t* a, uint32_t dlo, uint32_t dhi) {
  asm volatile("{ .reg .b64 dd; mov.b64 dd, {%36, %37}; wgmma.mma_async.sync.aligned.m64n64k16.f32.f16.f16 "
               "{%0,%1,%2,%3,%4,%5,%6,%7,%8,%9,%10,%11,%12,%13,%14,%15,%16,%17,%18,%19,%20,%21,%22,%23,%24,%25,%26,%27,%28,%29,%30,%31}, {%32,%33,%34,%35}, dd, 0, 1, 1, %38; }"
               : "=f"(d[0]), "=f"(d[1]), "=f"(d[2]), "=f"(d[3]), "=f"(d[4]), "=f"(d[5]), "=f"(d[6]), "=f"(d[7]), "=f"(d[8]), "=f"(d[9]), "=f"(d[10]), "=f"(d[11]), "=f"(d[12]), "=f"(d[13]), "=f"(d[14]), "=f"(d[15]), "=f"(d[16]), "=f"(d[17]), "=f"(d[18]), "=f"(d[19]), "=f"(d[20]), "=f"(d[21]), "=f"(d[22]), "=f"(d[23]), "=f"(d[24]), "=f"(d[25]), "=f"(d[26]), "=f"(d[27]), "=f"(d[28]), "=f"(d[29]), "=f"(d[30]), "=f"(d[31])
               : "r"(a[0]), "r"(a[1]), "r"(a[2]), "r"(a[3]), "r"(dlo), "r"(dhi), "n"(TB));
}
template <int TB> __device__ __forceinline__ void wgmma32_init(float* d, const uint32_t* a, uint32_t dlo, uint32_t dhi) {
  asm volatile("{ .reg .b64 dd; mov.b64 dd, {%20, %21}; wgmma.mma_async.sync.aligned.m64n32k16.f32.f16.f16 "
               "{%0,%1,%2,%3,%4,%5,%6,%7,%8,%9,%10,%11,%12,%13,%14,%15}, {%16,%17,%18,%19}, dd, 0, 1, 1, %22; }"
               : "=f"(d[0]), "=f"(d[1]), "=f"(d[2]), "=f"(d[3]), "=f"(d[4]), "=f"(d[5]), "=f"(d[6]), "=f"(d[7]), "=f"(d[8]), "=f"(d[9]), "=f"(d[10]), "=f"(d[11]), "=f"(d[12]), "=f"(d[13]), "=f"(d[14]), "=f"(d[15])
               : "r"(a[0]), "r"(a[1]), "r"(a[2]), "r"(a[3]), "r"(dlo), "r"(dhi), "n"(TB));
}
__device__ __forceinline__ void wgmma64h(uint32_t* d, uint32_t a0, uint32_t a1, uint32_t a2, uint32_t a3, uint32_t dlo, uint32_t dhi) {
  asm volatile("{ .reg .b64 dd; mov.b64 dd, {%20, %21}; wgmma.mma_async.sync.aligned.m64n64k16.f16.f16.f16 "
               "{%0,%1,%2,%3,%4,%5,%6,%7,%8,%9,%10,%11,%12,%13,%14,%15}, {%16,%17,%18,%19}, dd, 1, 1, 1, 0; }"
               : "+r"(d[0]), "+r"(d[1]), "+r"(d[2]), "+r"(d[3]), "+r"(d[4]), "+r"(d[5]), "+r"(d[6]), "+r"(d[7]), "+r"(d[8]), "+r"(d[9]), "+r"(d[10]), "+r"(d[11]), "+r"(d[12]), "+r"(d[13]), "+r"(d[14]), "+r"(d[15])
               : "r"(a0), "r"(a1), "r"(a2), "r"(a3), "r"(dlo), "r"(dhi));
}
__device__ __forceinline__ void wgmma64h_init(uint32_t* d, uint32_t a0, uint32_t a1, uint32_t a2, uint32_t a3, uint32_t dlo, uint32_t dhi) {
  asm volatile("{ .reg .b64 dd; mov.b64 dd, {%20, %21}; wgmma.mma_async.sync.aligned.m64n64k16.f16.f16.f16 "
               "{%0,%1,%2,%3,%4,%5,%6,%7,%8,%9,%10,%11,%12,%13,%14,%15}, {%16,%17,%18,%19}, dd, 0, 1, 1, 0; }"
               : "=r"(d[0]), "=r"(d[1]), "=r"(d[2]), "=r"(d[3]), "=r"(d[4]), "=r"(d[5]), "=r"(d[6]), "=r"(d[7]), "=r"(d[8]), "=r"(d[9]), "=r"(d[10]), "=r"(d[11]), "=r"(d[12]), "=r"(d[13]), "=r"(d[14]), "=r"(d[15])
               : "r"(a0), "r"(a1), "r"(a2), "r"(a3), "r"(dlo), "r"(dhi));
}
__device__ __forceinline__ void wgmma40_ss(float* d, uint32_t alo, uint32_t blo, uint32_t hi) {
  asm volatile("{ .reg .b64 da, db; mov.b64 da, {%20, %22}; mov.b64 db, {%21, %22}; "
               "wgmma.mma_async.sync.aligned.m64n40k16.f32.f16.f16 {%0,%1,%2,%3,%4,%5,%6,%7,%8,%9,%10,%11,%12,%13,%14,%15,%16,%17,%18,%19}, da, db, 1, 1, 1, 1, 1; }"
               : "+f"(d[0]), "+f"(d[1]), "+f"(d[2]), "+f"(d[3]), "+f"(d[4]), "+f"(d[5]), "+f"(d[6]), "+f"(d[7]), "+f"(d[8]), "+f"(d[9]), "+f"(d[10]), "+f"(d[11]), "+f"(d[12]), "+f"(d[13]), "+f"(d[14]), "+f"(d[15]), "+f"(d[16]), "+f"(d[17]), "+f"(d[18]), "+f"(d[19])
               : "r"(alo), "r"(blo), "r"(hi));
}
__device__ __forceinline__ void wgmma40_ss_init(float* d, uint32_t alo, uint32_t blo, uint32_t hi) {
  asm volatile("{ .reg .b64 da, db; mov.b64 da, {%20, %22}; mov.b64 db, {%21, %22}; "
               "wgmma.mma_async.sync.aligned.m64n40k16.f32.f16.f16 {%0,%1,%2,%3,%4,%5,%6,%7,%8,%9,%10,%11,%12,%13,%14,%15,%16,%17,%18,%19}, da, db, 0, 1, 1, 1, 1; }"
               : "=f"(d[0]), "=f"(d[1]), "=f"(d[2]), "=f"(d[3]), "=f"(d[4]), "=f"(d[5]), "=f"(d[6]), "=f"(d[7]), "=f"(d[8]), "=f"(d[9]), "=f"(d[10]), "=f"(d[11]), "=f"(d[12]), "=f"(d[13]), "=f"(d[14]), "=f"(d[15]), "=f"(d[16]), "=f"(d[17]), "=f"(d[18]), "=f"(d[19])
               : "r"(alo), "r"(blo), "r"(hi));
}
__device__ __forceinline__ float vzero() { float v; asm volatile("mov.b32 %0, 0;" : "=f"(v)); return v; }
__device__ __forceinline__ void tma_box(uint32_t dst, const CUtensorMap* tm, uint32_t mb, int x, int y) {
  asm volatile("cp.async.bulk.tensor.2d.shared::cluster.global.mbarrier::complete_tx::bytes [%0], [%1, {%3, %4}], [%2];"
               :: "r"(dst), "l"(tm), "r"(mb), "r"(x), "r"(y) : "memory");
}
__device__ __forceinline__ void l2_prefetch(const void* src, uint32_t bytes) {
  asm volatile("cp.async.bulk.prefetch.L2.global [%0], %1;" :: "l"(src), "r"(bytes) : "memory");
}
__device__ __forceinline__ uint32_t uni(uint32_t v) {
  uint32_t r; asm volatile("shfl.sync.idx.b32 %0, %1, 0, 0x1f, 0xffffffff;" : "=r"(r) : "r"(v)); return r;
}
__device__ __forceinline__ int fresh_tid() { int v; asm volatile("mov.u32 %0, %tid.x;" : "=r"(v)); return v; }

struct Params {
  const unsigned char* x;
  Scratch* s;
  int off[8];
  uint32_t* out;
  const uint16_t* dskip;
  const uint32_t* w_r;
  long long* ts;
  const unsigned char* far[7];
  uint32_t sched[2][17];
};
__device__ __forceinline__ uint32_t ldnc32(const void* p) { uint32_t v; asm volatile("ld.global.nc.b32 %0, [%1];" : "=r"(v) : "l"(p)); return v; }
__device__ __forceinline__ uint32_t ldnc16(const void* p) { uint16_t v; asm volatile("ld.global.nc.u16 %0, [%1];" : "=h"(v) : "l"(p)); return v; }
__device__ __forceinline__ uint4 ldnc128(const void* p) { uint4 v; asm volatile("ld.global.nc.v4.b32 {%0,%1,%2,%3}, [%4];" : "=r"(v.x), "=r"(v.y), "=r"(v.z), "=r"(v.w) : "l"(p)); return v; }
__device__ __forceinline__ void mbar_wait(uint32_t mb, uint32_t ph = 0) {
#pragma unroll 1
  for (int it = 0; it < SPIN_MAX; it++) {
    uint32_t ok;
    asm volatile("{ .reg .pred q; mbarrier.try_wait.parity.shared::cta.b64 q, [%1], %2; selp.u32 %0, 1, 0, q; }" : "=r"(ok) : "r"(mb), "r"(ph) : "memory");
    if (ok) break;
  }
}
__device__ __forceinline__ uint32_t mbar_test(uint32_t mb) {
  uint32_t ok;
  asm volatile("{ .reg .pred q; mbarrier.test_wait.parity.shared::cta.b64 q, [%1], 0; selp.u32 %0, 1, 0, q; }" : "=r"(ok) : "r"(mb) : "memory");
  return ok;
}
__device__ __forceinline__ void mbar_arrive(uint32_t mb) { asm volatile("mbarrier.arrive.shared::cta.b64 _, [%0];" :: "r"(mb) : "memory"); }
__device__ __forceinline__ uint32_t ldg16(const void* p) { uint16_t v; asm volatile("ld.global.u16 %0, [%1];" : "=h"(v) : "l"(p) : "memory"); return v; }
__device__ __forceinline__ uint32_t ldr16(const void* p) { uint16_t v; asm volatile("ld.relaxed.gpu.global.u16 %0, [%1];" : "=h"(v) : "l"(p) : "memory"); return v; }
__device__ __forceinline__ void fence_async() { asm volatile("fence.proxy.async.shared::cta;" ::: "memory"); }
#define SPIN_WHILE(cond, body) _Pragma("unroll 1") for (int _it = 0; _it < SPIN_MAX && __any_sync(0xffffffffu, (cond)); _it++) { body; }

struct LnC { uint32_t m2, rh2, rl2; };
__device__ __forceinline__ float diag_sum(float d0, float d1, int t) {
  float q = __shfl_sync(0xffffffffu, d0, 9 * t) + __shfl_sync(0xffffffffu, d1, 9 * t + 4);
  q += __shfl_xor_sync(0xffffffffu, q, 1);
  return q + __shfl_xor_sync(0xffffffffu, q, 2);
}
__device__ __forceinline__ LnC ln_consts(float s, float q, float& r) {
  const float mean = s * (1.f / DM);
  const float var = fmaxf(fmaf(-mean, mean, q * (1.f / DM)), 0.f);
  float sd;
  asm("sqrt.approx.ftz.f32 %0, %1;" : "=f"(sd) : "f"(bfr(bfr(var) + 1e-5f)));
  asm("rcp.approx.ftz.f32 %0, %1;" : "=f"(r) : "f"(bfr(sd)));
  LnC c;
  c.m2 = pack_bf(mean, mean);
  c.rh2 = pack_bf(r, r);
  const float rl = r - bf_lo(c.rh2);
  c.rl2 = pack_bf(rl, rl);
  return c;
}
__device__ __forceinline__ float quad_sum(float s) { s += __shfl_xor_sync(0xffffffffu, s, 1); return s + __shfl_xor_sync(0xffffffffu, s, 2); }
__device__ __forceinline__ uint32_t bf_fma2(uint32_t a, uint32_t b, uint32_t c) {
  __nv_bfloat162 r = __hfma2(*(const __nv_bfloat162*)&a, *(const __nv_bfloat162*)&b, *(const __nv_bfloat162*)&c);
  return *(uint32_t*)&r;
}
__device__ __forceinline__ uint32_t ln_apply(uint32_t w, uint32_t m2, uint32_t rh2, uint32_t rl2) {
  const uint32_t d = bf_sub2(w, m2);
  return bf_fma2(d, rh2, bf_mul2(d, rl2));
}

__device__ __forceinline__ float2 cis(float mag_log2, float rev) {
  const float m = ex2(mag_log2), ang = rev * 6.283185307179586f;
  return make_float2(m * __cosf(ang), m * __sinf(ang));
}
__device__ __forceinline__ float2 csq(float2 a) { return make_float2(fmaf(a.x, a.x, -a.y * a.y), (a.x + a.x) * a.y); }
__device__ __forceinline__ float2 cmul(float2 a, float2 b) { return make_float2(fmaf(a.x, b.x, -a.y * b.y), fmaf(a.x, b.y, a.y * b.x)); }
__device__ __forceinline__ void pmul(uint32_t xr, uint32_t xi, uint32_t w, uint32_t& yr, uint32_t& yi) {
  const __half2 XR = *(__half2*)&xr, XI = *(__half2*)&xi, W = *(__half2*)&w;
  const __half2 a = __hfma2(__hneg2(XI), __high2half2(W), __hmul2(XR, __low2half2(W)));
  const __half2 b = __hfma2(XI, __low2half2(W), __hmul2(XR, __high2half2(W)));
  yr = *(const uint32_t*)&a; yi = *(const uint32_t*)&b;
}
__device__ __forceinline__ uint32_t pk(float2 a) { return pack_h(a.x, a.y); }

struct KgState { float2 c0, z8; float kl; uint32_t w64, w128, w192; };
__device__ __forceinline__ void kgen_tables_n(const uint32_t (&raw)[7], uint32_t scr, int wt, KgState& k) {
  const uint32_t dst = scr + 16384 + wt * 16;
  const float dt = bfr(ex2(bf_lo(raw[6]) * 1.4426950408889634f));
  const float th = dt * bf_lo(raw[1]);
  const float br = dt * bf_lo(raw[2]), bi = dt * bf_lo(raw[3]);
  const float Cr = bf_lo(raw[4]), Ci = bf_lo(raw[5]);
  k.c0 = make_float2(fmaf(Cr, br, -Ci * bi), fmaf(Cr, bi, Ci * br));
  const uint32_t mx = __reduce_max_sync(0xffffffffu, __float_as_uint(fmaxf(fabsf(k.c0.x), fabsf(k.c0.y))));
  const float a2 = dt * bf_lo(raw[0]) * 1.4426950408889634f;
  const float rh = th * 0.15915494309189535f;
  const float rl = fmaf(th, (float)(0.15915494309189535 - (double)0.15915494309189535f), fmaf(th, 0.15915494309189535f, -rh));
  const float rf = rh - rintf(rh);
  const float2 z1 = cis(a2, rf + rl);
  const float p64 = rf * 64.f;
  const float2 z64 = cis(a2 * 64.f, fmaf(64.f, rl, p64 - rintf(p64)));
  const float2 z2 = csq(z1), z128 = csq(z64), z3 = cmul(z2, z1), z4 = csq(z2), z256 = csq(z128), z6 = csq(z3), z512 = csq(z256);
  k.z8 = csq(z4);
  k.w64 = pk(z64); k.w128 = pk(z128); k.w192 = pk(cmul(z128, z64));
  sts128(dst, 0x00003C00u, pk(z2), pk(z4), pk(z6));
  const float2 z1024 = csq(z512), z768 = cmul(z512, z256);
  sts128(dst + 2048, pk(z1), pk(z3), pk(cmul(z4, z1)), pk(cmul(z4, z3)));
  const float2 z2048 = csq(z1024);
  k.kl = fmaf(k.c0.x, z2048.x, -k.c0.y * z2048.y);
  sts128(dst + 4096, pk(z256), pk(cmul(z256, z2)), pk(cmul(z256, z4)), pk(cmul(z256, z6)));
  sts128(dst + 6144, pk(z512), pk(cmul(z512, z4)), pk(z768), pk(cmul(z768, z4)));
  sts128(dst + 8192, pk(z1024), pk(cmul(z1024, z256)), pk(cmul(z1024, z512)), pk(cmul(z1024, z768)));
  sts32(scr + W_MISC + (wt >> 5) * 4, mx);
}
__device__ __forceinline__ int kgen_tables_m(uint32_t scr, int wt, const KgState& k) {
  const uint32_t dst = scr + wt * 16;
  const uint4 e4 = lds128(scr + W_MISC);
  const float2 z16 = csq(k.z8), z32 = csq(z16);
  const int em = max(min((int)(max(max(e4.x, e4.y), max(e4.z, e4.w)) >> 23), 238), 16);
  const float sc = __uint_as_float((uint32_t)(127 + 4 + 127 - em) << 23);
  sts32(scr + W_MISC + 16 + (wt >> 5) * 4, __reduce_add_sync(0xffffffffu, __float2int_rn(k.kl * sc * 262144.f)));
  const float2 c0 = make_float2(k.c0.x * sc, k.c0.y * sc);
  const float2 c1 = cmul(c0, k.z8), c2 = cmul(c0, z16), c4 = cmul(c0, z32), c3 = cmul(c1, z16), c5 = cmul(c1, z32), c6 = cmul(c2, z32), c7 = cmul(c3, z32);
  uint32_t pr[4], pi[4], yr[4], yi[4];
  pr[0] = pack_h(c0.x, c1.x); pi[0] = pack_h(c0.y, c1.y);
  pr[1] = pack_h(c2.x, c3.x); pi[1] = pack_h(c2.y, c3.y);
  pr[2] = pack_h(c4.x, c5.x); pi[2] = pack_h(c4.y, c5.y);
  pr[3] = pack_h(c6.x, c7.x); pi[3] = pack_h(c6.y, c7.y);
  sts128(dst, pr[0], pr[1], pr[2], pr[3]); sts128(dst + 2048, pi[0], pi[1], pi[2], pi[3]);
#pragma unroll
  for (int q = 1; q < 4; q++) {
    const uint32_t w = q == 1 ? k.w64 : q == 2 ? k.w128 : k.w192;
#pragma unroll
    for (int i = 0; i < 4; i++) pmul(pr[i], pi[i], w, yr[i], yi[i]);
    sts128(dst + q * 4096, yr[0], yr[1], yr[2], yr[3]); sts128(dst + q * 4096 + 2048, yi[0], yi[1], yi[2], yi[3]);
  }
  return em;
}
__device__ __forceinline__ void kgen_build(uint32_t tb, int wg, int wt, uint32_t k0, uint32_t k1, uint32_t k2) {
  const uint32_t kt = tb + W_KT, sc = tb + W_L3 + 3072;
  const int ix = ((wt >> 2) + (wt & 3) * 32 - 1) & 127;
  const uint32_t a3 = tb + W_CW + 32 + ((ix & 1) ? 0 : 304) + (ix >> 1) * 4;
  const uint32_t v3 = wt ? k2 : k2 >> 16;
  sts32(sc + 4 + wt * 4, __byte_perm(k0, k1, 0x5432));
  sts16(sc + 544 + (wt & ~3) + (wt & 1) * 2 + (wt & 2) * 64, k1 >> 16);
  sts16(a3, v3); sts16(a3 + 6, v3);
  if ((unsigned)(wt - 32) < 18u) sts128(kt + (wt < 36 ? -512 : 64 + 4128 - 576) + wt * 16, 0, 0, 0, 0);
  if (wt == 127) sts32(sc, k0 & 0xFFFF0000u);
  if (wt == 0) { sts32(sc + 516, k1); sts16(sc + 800, k2); }
  bar_sync(1 + wg, 128);
  const uint32_t cw = tb + W_CW + 32 + (wt >> 6) * 48 + wt * 4;
  const uint32_t pv = lds32(sc + wt * 4), nx = lds32(sc + 8 + wt * 4), c2 = lds16(sc + 544 + wt * 2), n2 = lds16(sc + 546 + wt * 2);
  sts128(tb + W_L3 + 512 + (wt >> 6) * 512 + wt * 16, lds32(cw), lds32(cw - 8), lds32(cw - 16), lds32(cw - 24));
  const bool odd = wt & 1;
  sts64(kt + 64 + wt * 8, __byte_perm(k0, pv, 0x5410), __byte_perm(k0, 0, 0x1032));
  sts64(kt + 64 + 1024 + wt * 8, __byte_perm(k1, pv, (odd || wt == 0) ? 0x7610 : 0x1010), __byte_perm(k1, nx, odd ? 0x1076 : 0x1010));
  const uint32_t cc = c2 * 0x10001u, nc = __byte_perm(n2, c2, 0x5410), nn = n2 * 0x10001u;
  sts128(kt + 64 + 2048 + wt * 16, cc, cc, odd ? nc : cc, odd ? nn : nc);
  if (wt == 127) { sts128(kt + 64 + 4096, nn, nn, nn, nn); sts128(kt + 64 + 4112, nn, nn << 16, 0, 0); }
}

__device__ __forceinline__ void load_a(uint32_t (&a)[4], uint32_t kp, int j) {
  a[0] = lds32(kp + 64 * j); a[1] = lds32(kp + 64 * j + 512); a[2] = lds32(kp + 64 * j - 32); a[3] = lds32(kp + 64 * j + 480);
}
__device__ __forceinline__ uint32_t band(int d, int lo, int hi) {
  return ((unsigned)(d - lo) <= (unsigned)(hi - lo) ? 1u : 0u) | ((unsigned)(d - 1 - lo) <= (unsigned)(hi - lo) ? 0x10000u : 0u);
}
__device__ __forceinline__ uint32_t hadd2u(uint32_t a, uint32_t b) { __half2 r = __hadd2(*(__half2*)&a, *(__half2*)&b); return *(uint32_t*)&r; }

__device__ __forceinline__ void zero_pads(uint32_t tb, int wt) {
  if (!(wt & 32)) sts128(tb + W_L3 + (wt >> 6) * 512 + wt * 16, 0, 0, 0, 0);
  if ((wt & 63) < 3) sts128(tb + W_CW + (wt >> 6) * 304 + (wt & 63) * 16, 0, 0, 0, 0);
}
__device__ __forceinline__ uint32_t tr_base(int lane) {
  return OFF_YT + (2 * (lane >> 3) + (lane & 1)) * YT_PITCH + ((lane >> 1) & 1) * (8 * YT_PITCH + 64) + ((lane >> 2) & 1) * 16;
}

__device__ __forceinline__ uint32_t sc_addr(int tp) { return OFF_YT + (tp < 16 ? tp * YT_PITCH + (tp >> 3) * 64 + 1152 : 8 * YT_PITCH - 512 + tp * 32); }
#define X_PS 1
#define X_PW 15
#define X_HU 16
#define X_HB 0
#define X_REL 1
#define X_PAD0 0
#define X_PAD1 0
#define PAD(n) _Pragma("unroll") for (int _i = 0; _i < (n); _i++) asm volatile("pmevent 0;");
#ifndef M_
#define M_ 12
#endif
#define X_NE 2
#define X_SCT 10000
#define X_DELTA 400
#define X_DSTEP 2000
#define X_PF0 2500
#define X_PFD 600
#define X_TD 450
#define X_WS 6
#define X_OR 8
#define X_ABS 5100
#define X_XD 200
#define X_RD 600
#define X_HD 400
#define X_PD 1080
#define X_PROMO 2
#define X_YD2 1000
#define X_GO 2
#define X_GW 2
#define X_NS 4700
#define X_XS 13600
#define X_LAG 1800
#define X_YD 1550
struct TMaps { CUtensorMap m[10]; };
__device__ __forceinline__ uint32_t h2bf(uint32_t w) { const float2 f = h2f(w); return pack_bf(f.x, f.y); }
__device__ __forceinline__ uint32_t keep(uint32_t v) { asm volatile("" : "+r"(v)); return v; }
__device__ __forceinline__ uint2 ldr64(const void* p) { uint2 v; asm volatile("{ .reg .b64 t; ld.relaxed.gpu.global.b64 t, [%2]; mov.b64 {%0, %1}, t; }" : "=r"(v.x), "=r"(v.y) : "l"(p) : "memory"); return v; }
__host__ __device__ __forceinline__ uint32_t down_box(int s, bool five) {
  return five ? OFF_W + W_BYTES + 12288 + (s / 3) * (W_BYTES - 12288) + s * 4096 : s < 6 ? OFF_W + W_BYTES + BOX + (s >> 1) * (W_BYTES - 10240) + s * 5120 : OFF_W + (s - 6) * 5120;
}
__device__ __forceinline__ void load_tile(const CUtensorMap* tmx, int i, int c, int again = 0) {
  asm volatile("mbarrier.arrive.expect_tx.shared::cta.b64 _, [%0], 8704;" :: "r"(MB_UL + i * 16 + again) : "memory");
  asm volatile("cp.async.bulk.tensor.3d.shared::cluster.global.mbarrier::complete_tx::bytes [%0], [%1, {%3, %4, %5}], [%2];"
               :: "r"(i < 2 ? OFF_T + i * TILE : OFF_W), "l"(tmx), "r"(MB_UL + i * 16 + again), "r"(0), "r"(c), "r"(-8) : "memory");
}
template <bool FAR> __device__ __forceinline__ void load_params(const Params& p, uint32_t ch, int wt, uint32_t dst, bool on) {
  const int rel = wt < 96 ? ch * 16 + (wt & 15) : ch >> 3;
  const unsigned char* b = FAR ? p.far[min(wt >> 4, 6)] + rel * 16 : p.x + (long long)(p.off[wt >> 4] + rel) * 16;
  asm volatile("{ .reg .pred q; setp.ne.u32 q, %2, 0; @q cp.async.cg.shared.global [%0], [%1], 16; }"
               :: "r"(dst + wt * 16), "l"(b), "r"((uint32_t)(on && wt < 97)) : "memory");
}

struct ConvC { uint32_t ca, cb, bands; };
__device__ __forceinline__ ConvC conv_consts(int w, int lane) {
  const int h = w & 1, P = (w >> 1) & 1, d0 = 8 * h + (lane >> 2) - 2 * (lane & 3);
  ConvC k;
  k.ca = keep((W_KT + (16 + 256 * P + d0) * 4) | (((8 + 64 * P + lane) * 64 + (((h + ((w >> 1) & 2)) ^ (lane >> 1)) & 3) * 16) << 16));
  k.cb = keep(lane < 8 ? 0xFFFEFFFEu : ~0u);
  k.bands = keep(band(d0, 12, 20) + 2 * band(d0 + 8, 12, 20) + 4 * band(d0 + 16, 12, 20) + 8 * band(d0 + 24, 12, 20)
                 + 16 * band(d0 - 8, 5, 11) + 32 * band(d0, 5, 11) + 64 * band(d0 + 8, 5, 11) + 128 * band(d0 + 16, 5, 11));
  return k;
}
struct ConvPre { uint32_t e0, e2, f2, a[3][4]; };
__device__ __forceinline__ uint32_t lds32_if(uint32_t a, bool on) {
  uint32_t v; asm volatile("{ .reg .pred q; setp.ne.u32 q, %2, 0; mov.b32 %0, 0; @q ld.shared.b32 %0, [%1]; }" : "=r"(v) : "r"(a), "r"((uint32_t)on) : "memory"); return v;
}
__device__ __forceinline__ void conv_pre(ConvPre& r, uint32_t kp, int part, bool on, bool P) {
  if (part & 1) { r.e0 = lds32_if(kp + 4096, on && !P); r.e2 = lds32_if(kp + 4064, on && !P); r.f2 = lds32_if(kp + 4128, on && !P); }
#pragma unroll
  for (int j = 0; j < 3; j++) if (part & (j < X_PS ? 1 : 2)) {
    r.a[j][0] = lds32_if(kp + 2048 + 64 * j, on); r.a[j][1] = lds32_if(kp + 2560 + 64 * j, on); r.a[j][2] = lds32_if(kp + 2016 + 64 * j, on); r.a[j][3] = lds32_if(kp + 2528 + 64 * j, on);
  }
}
__device__ __forceinline__ void conv_item(uint32_t tb, uint32_t tl, int bid, int bn, ConvPre& pre, const ConvC& cv, uint32_t zero, const CUtensorMap* tmx, int ch, int warp, int lane, bool hold, bool more) {
  const bool go = more && warp == 0 && lane == 0;
  const uint32_t kp = tb + (cv.ca & 0xFFFFu);
  const uint32_t dlo = (tl >> 4) + 32 + ((warp >> 1) & 2) + (1u << 16), dhi = 32u | (2u << 30);
  const bool P = warp & 2;
  float a32[16], b32[16], a64[32];
  uint32_t A[40][4];
#define STEP(J) { wgmma64<0>(a64, A[J], dlo + 256 - 4 * (J), dhi); \
    if ((J) == 32) wgmma32_init<0>(b32, A[J], dlo, dhi); else wgmma32<0>(b32, A[J], ((J) < 8 ? dlo ^ zero : dlo) + 128 - 4 * (J), dhi); \
    if ((J) == 0) wgmma32_init<0>(a32, A[J], dlo, dhi); else if ((J) < 8) wgmma32<0>(a32, A[J], (dlo ^ zero) - 4 * (J), dhi); }
#define LD(J) load_a(A[J], kp, J);
#define FIRST(J) wg_fence(); STEP(J) wg_commit(); wg_wait<1>(); wg_fence();
  {
    uint32_t win[16], x9[4], x7[4], e[4], f[4];
    const uint32_t bz = keep(cv.bands);
#define BAND(i) keep((bz & (0x10001u << (i))) * (0x3C00u >> (i)))
    e[0] = pre.e0; e[2] = pre.e2; e[1] = keep(bz & 0x100u); e[3] = keep(bz & 0x200u);
    f[2] = pre.f2; f[0] = keep(bz & 0x4000u); f[1] = keep(bz & 0x8000u); f[3] = keep(bz & 0x300u);
#pragma unroll
    for (int j = 0; j < 12; j++) A[32 + j / 4][j & 3] = pre.a[j / 4][j & 3];
    const uint32_t q[12] = {BAND(0), BAND(5), keep(bz & 0x400u), BAND(4), BAND(2), BAND(7), BAND(1), BAND(6), keep(bz & 0x800u), keep(bz & 0x1000u), BAND(3), keep(bz & 0x2000u)};
#undef BAND
    const uint32_t ta = keep(tl + 512 + (warp & 3) * 2048 + lane * 64 + (lane & 6) * 8);
    if (X_GO && hold) mbar_wait(MB_GO);
    uint32_t mbl = MB_UL + (warp & 8) * 2, ph = 0;
#pragma unroll 1
    for (int it = 0; it < SPIN_MAX; it++) {
      if (ch < 512) mbar_wait(mbl, ph);
      if (it == 1) TS(13);
      TS(3);
      wg_fence();
      wgmma64h_init(win, q[0], q[1], q[2], q[3], dlo, dhi);
      wgmma64h(win, q[4], q[5], q[6], q[7], dlo - 4, dhi);
      wgmma64h(win, q[8], q[9], q[10], q[11], dlo - 8, dhi);
      wg_commit();
      wgmma64_init<0>(a64, e, dlo, dhi);
      wgmma64<0>(a64, f, dlo - 4, dhi);
      wg_commit();
      if (ch >= 512) break;
      uint32_t r0, r1, r2, r3, ok;
      if (warp & 4) {
        mbar_wait(mbl + 8);
        if (__all_sync(0xffffffffu, it || lds32(MISC_RT + (warp & 8)) == 0)) break;
        wg_wait<0>();
        continue;
      }
      ldsm4(ta, r0, r1, r2, r3);
      ok = r0 & r1 & r2 & r3;
      ldsm4(ta ^ 32, r0, r1, r2, r3);
      asm volatile("{ .reg .pred q; setp.ne.u32 q, %1, 0; barrier.red.and.pred q, %2, 128, q; selp.u32 %0, 1, 0, q; }" : "=r"(ok) : "r"((ok & r0 & r1 & r2 & r3 & 1u) | (lane & 3)), "r"(1 + (warp >> 2)) : "memory");
      if (ok) { if ((warp & 3) == 0 && lane == 0) { sts32(MISC_RT + warp, it); mbar_arrive(MB_UL + 8 + warp * 2); } break; }
      wg_wait<0>();
      if ((warp & 3) == 0 && lane == 0) load_tile(tmx - 1, warp >> 3, ch, 56);
      mbl = MB_UL + 56 + (warp & 8) * 2; ph = it & 1;
    }
    wg_wait<1>();
#pragma unroll
    for (int i = 0; i < 4; i++) {
      const int tl = 2 * ((i & 1) + ((i & 2) ? 0 : 4));
      x9[i] = P ? win[tl + 4] : win[tl]; x7[i] = P ? win[tl + 5] : win[tl + 1];
    }
    const uint32_t l3lo = ((tb + W_L3) >> 4) + (32u << 16);
    wg_fence();
    wgmma64<0>(a64, x9, l3lo, 8);
    wgmma64<0>(a64, x7, l3lo + 96, 8);
    wg_commit();
  }
  STEP(32) STEP(33) STEP(34) wg_commit(); wg_wait<1>();
  LD(35) LD(36) LD(37) LD(38)
  FIRST(35) STEP(36) STEP(37) STEP(38) wg_commit();
  LD(39) LD(0)
  TS(17);
  if (X_GO == 1 && go) mbar_arrive(MB_GO);
  FIRST(39) STEP(0) wg_commit();
  LD(1) LD(2) LD(3)
  FIRST(1) STEP(2) STEP(3) wg_commit();
  LD(4) LD(5)
  if (X_GO == 2 && go) mbar_arrive(MB_GO);
  FIRST(4) STEP(5) wg_commit();
  LD(6) LD(7)
  wg_fence(); STEP(6) STEP(7) wg_commit();
#undef STEP
#undef LD
#undef FIRST
  TS(18);
  if (X_GO == 3 && go) mbar_arrive(MB_GO);
  const uint32_t xc = tb + W_KT + (warp & 3) * 1024 + lane * 16;
  if (more) bar_sync(7, 288);
  wg_wait<1>();
  conv_pre(pre, kp + ALT, 1, more, P);
  wg_wait<0>();
  conv_pre(pre, kp + ALT, 2, more, P);
  uint32_t E[16], o[8];
#define ACC(i) ((i) < 16 ? a32[i] : (i) < 32 ? b32[(i) - 16] : a64[(i) - 32])
  E[0] = pack_h(a32[0], a32[1]);
#pragma unroll
  for (int i = 1; i < 16; i++) E[i] = pack_h(ACC(4 * i) + ACC(4 * i - 2), ACC(4 * i + 1) + ACC(4 * i - 1));
#undef ACC
#pragma unroll
  for (int j = 0; j < 8; j++) o[j] = P ? (j < 2 ? 0u : E[j - 2]) : E[8 + j];
  sts128(xc, o[0], o[1], o[2], o[3]); sts128(xc + 512, o[4], o[5], o[6], o[7]);
#pragma unroll
  for (int j = 0; j < 8; j++) o[j] = P ? E[6 + j] : E[j];
  TS(25);
  if (more) {
    sts128(xc + 4096, o[0], o[1], o[2], o[3]); sts128(xc + 4608, o[4], o[5], o[6], o[7]);
    bar_arrive(12, 192);
    return;
  }
  bar_sync(1 + (warp >> 2), 128);
  const uint4 vv[2] = {lds128(xc + (P ? -2048 : 2048)), lds128(xc + (P ? -1536 : 2560))};
#pragma unroll
  for (int q = 0; q < 2; q++) {
    const uint4 v = vv[q];
    stsm4t(tl + (cv.ca >> 16) + q * 2048, hadd2u(o[4 * q], v.x) & cv.cb, hadd2u(o[4 * q + 1], v.y) & cv.cb, hadd2u(o[4 * q + 2], v.z) & cv.cb, hadd2u(o[4 * q + 3], v.w) & cv.cb);
  }
  fence_async();
  bar_sync(bid, bn);
  if (warp == 0 && lane == 0) mbar_arrive(MB_REL);
  if ((warp & 7) == (ch < 512 ? 7 : 3) && lane == 0) {
    asm volatile("cp.async.bulk.tensor.3d.global.shared::cta.bulk_group [%0, {%3, %2, %3}], [%1];" :: "l"(tmx), "r"(tl + 512), "r"(ch), "r"(0) : "memory");
    asm volatile("cp.async.bulk.commit_group;" ::: "memory");
  }
}

template <bool FAR> __global__ void __launch_bounds__(NT, 1)
fused_kernel(const __grid_constant__ Params p, const __grid_constant__ TMaps tm) {
  extern __shared__ __align__(1024) unsigned char smem[];
  const int c = blockIdx.x;
  const bool five = (c & 1) == 0;
  const uint32_t pitch = five ? 64 : 80;
  const uint32_t ones = 0x3F803F80u;
  const int tid = threadIdx.x, lane = tid & 31;
  const uint32_t xrow = OFF_YT + ((tid & 127) >> 3) * YT_PITCH + (tid & 64) + (tid & 7) * 16;
  {
    const int w4 = tid >> 7;
    load_params<FAR>(p, w4 < 2 ? 2 * c + w4 : five ? 257 + 2 * c : 512 + (c >> 1), tid & 127, OFF_W + W_KT + (w4 < 2 ? w4 * W_BYTES : five ? 3 * W_BYTES : 3 * W_BYTES + 2048), (0xB >> w4) & 1);
  }
  if ((tid >> 7) == 2) {
    const unsigned char* xp = p.x + (uint32_t)((c * 16 - 32 + (tid >> 3)) * 1152 + (tid & 7) * 16);
    asm volatile("" : "+l"(xp));
    { const uint32_t tq = clock(); while ((int)(clock() - tq) < X_XD) {} }
#pragma unroll
    for (int k = 0; k < 9; k++) asm volatile("cp.async.cg.shared.global [%0], [%1], 16;" :: "r"(xrow + k * 128), "l"(xp + k * 128) : "memory");
  }
  const int warp = (int)uni(tid >> 5), wg = warp >> 2;
  TS(0);
  if (__builtin_expect(wg == 4, 0)) {
    asm volatile("setmaxnreg.dec.sync.aligned.u32 32;");
    const int role = warp;
    const int u0 = (c >> 1) * 9 + (five ? ((c & 2) ? 5 : 0) : ((c & 2) ? 0 : 4));
    const uint32_t t0 = clock() + c * 4;
    if (role == 16) {
      if (lane < 19) asm volatile("mbarrier.init.shared::cta.b64 [%0], %1;" :: "r"(OFF_MISC + lane * 8), "r"((unsigned)(lane - 2) < 4u ? 4 : 1) : "memory");
      if (lane < 2) asm volatile("mbarrier.arrive.expect_tx.shared::cta.b64 _, [%0], %1;" :: "r"(OFF_MISC + lane * 8), "r"(lane ? (five ? 36864 : 51200) : pitch * 1152) : "memory");
      fence_async();
      bar_arrive(5, 608);
      const CUtensorMap* tmb = &tm.m[five ? 3 : 0];
#pragma unroll 1
      for (int u = 0; u < 17; u++) {
        const uint32_t e = p.sched[five][u], kind = e & 3, s = (e >> 2) & 15, dst = e >> 14;
        if (kind == 3) continue;
        while ((int)(clock() - t0) < X_PF0 + (u < X_NE ? u * X_PFD : X_LAG + u * X_TD)) __nanosleep(20);
        if (e & 0x3FC0) mbar_wait(OFF_MISC + ((e >> 6) & 255));
        if (lane == 0) {
          if (kind == 2) asm volatile("cp.async.bulk.tensor.3d.shared::cluster.global.mbarrier::complete_tx::bytes [%0], [%1, {%3, %4, %5}], [%2];"
                                      :: "r"(dst), "l"(tmb + 2), "r"(MB_D), "r"(0), "r"(u0 * 8), "r"(s) : "memory");
          else tma_box(dst, tmb + kind, MB_GU, u0 * 8, s * 96);
        }
        if (u == 5) TS(2);
        if (u == 10) TS(3);
      }
      TS(4);
      TS_DUMP();
#define FINISH0 bar_sync(12, 192);        \
        _Pragma("unroll 1") for (int w = role & 2; w < (role & 2) + 2; w++) { \
          const uint32_t xa = OFF_W + W_KT + lane * 16, mk = lane < 8 ? 0xFFFEFFFEu : ~0u, ya = OFF_T + (8 + lane) * 64 + (((w & 1) ^ (lane >> 1)) & 3) * 16 + (w & 2) * 2048; \
          const uint4 a = lds128(xa + 4096 + w * 1024), b = lds128(xa + (w ^ 2) * 1024), d = lds128(xa + 4608 + w * 1024), e = lds128(xa + 512 + (w ^ 2) * 1024); \
          stsm4t(ya, hadd2u(a.x, b.x) & mk, hadd2u(a.y, b.y) & mk, hadd2u(a.z, b.z) & mk, hadd2u(a.w, b.w) & mk); \
          stsm4t(ya + 2048, hadd2u(d.x, e.x) & mk, hadd2u(d.y, e.y) & mk, hadd2u(d.z, e.z) & mk, hadd2u(d.w, e.w) & mk); \
        } \
        fence_async();
    } else if (role == 17) {
      if (smem_u32(smem) != SB) __trap();
      bar_sync(10, 576);
      if (lane == 0) {
        fence_async();
        while ((int)(clock() - t0) < X_NS - c * 4) {}
        asm volatile("cp.async.bulk.global.shared::cta.bulk_group [%0], [%1], 10240;" :: "l"(&p.s->X[c * DM * 2 + 512]), "r"(OFF_G) : "memory");
        asm volatile("cp.async.bulk.commit_group;" ::: "memory");
        asm volatile("cp.async.bulk.wait_group 0;" ::: "memory");
      }
      if (lane == 0) mbar_arrive(MB_GF);
      bar_arrive(11, 96);
      if (five) { FINISH0 bar_arrive(13, 192); }
    } else if (role == 18) {
      sts32(MISC_EPOCH, 0);
      sts32(MISC_T0, t0 - c * 4);
      bar_arrive(5, 608);
      uint4* q = lane < 2 ? &p.s->R[c * 2 + lane] : lane < 11 ? &p.s->HS[c * 9 + lane - 2] : lane == 11 ? &p.s->HS[1152 + (c & 7)] : (uint4*)&p.s->FLAG[c * 8];
      if (lane < (c < 8 ? 12 : 11)) str128(q, ~0u, ~0u, ~0u, ~0u);
      const uint32_t ep = __shfl_sync(0xffffffffu, ldr32(q), 31) + 1u;
      sts32(MISC_EPOCH, ep | 0x80000000u);
      TSX(21);
      if (lane == 31) str32(q, ep);
      bar_sync(11, 96);
      TSX(14);
      mbar_wait(MB_KF + (lane & 3) * 8);
      __syncwarp();
      { const uint2 e = lds64(MISC_EM); if (lane < 2) str128(&p.s->SC[c * 2 + lane], e.x, __byte_perm(e.y, ep, 0x6540), 0, 0); }
      TSX(17);
      while ((int)(clock() - t0) < X_SCT) __nanosleep(100);
      TSX(18);
      {
        uint2 v[4];
#pragma unroll 1
        for (int it = 0; it < SPIN_MAX; it++) {
          uint32_t bad = 0;
#pragma unroll
          for (int q = 0; q < 4; q++) v[q] = ldr64(&p.s->SC[lane * 2 + q * 64]);
#pragma unroll
          for (int q = 0; q < 4; q++) bad |= (v[q].y >> 8) ^ (ep & 0xFFFFFFu);
          if (!__any_sync(0xffffffffu, bad)) break;
        }
        TSX(25);
#pragma unroll
        for (int q = 0; q < 4; q++) {
          const uint32_t sa = (lane >> 4) * YT_PITCH + (lane & 15) * 2;
          sts16(sc_addr(2 * q) + sa, v[q].x); sts16(sc_addr(8 + 2 * q) + sa, v[q].x >> 16);
          if (lane & 1) asm volatile("st.shared.u8 [%0], %1;" :: "r"(sc_addr(16) + q * 16 + (lane >> 1)), "r"(v[q].y) : "memory");
        }
      }
      __syncwarp();
      if (lane == 0) mbar_arrive(MB_SC);
      TSX(27);
    } else {
      uint32_t w[9];
      const uint32_t dk = ldnc16(p.dskip + ((lane & 4) ? 512 + (c >> 1) : (lane & 2) * 128 + 2 * c + (lane & 1)));
      float s = 0.f;
#pragma unroll
      for (int i = 0; i < 9; i++) w[i] = ldnc32(p.w_r + lane + 32 * i);
      sts16(OFF_WR + 1152 + lane * 2, dk);
      bar_arrive(5, 608);
#pragma unroll
      for (int i = 0; i < 9; i++) { sts32(OFF_WR + lane * 4 + i * 128, w[i]); s += bf_lo(w[i]) + bf_hi(w[i]); }
      sts32(MISC_SW, __float_as_uint(warp_sum(s)));
      TSX(23);
      bar_sync(10, 576);
      if (lane == 0) {
        const uint32_t tp = clock();
        TSX(1);
        while ((int)(clock() - tp) < X_DELTA || (int)(clock() - t0) < X_ABS - c * 4) {}
        TSX(24);
        load_tile(&tm.m[6], 0, c);
        TSX(15);
        while ((int)(clock() - t0) < X_ABS + X_DSTEP - c * 4) {}
      }
      bar_sync(11, 96);
      if (lane == 0) {
        load_tile(&tm.m[6], 1, 128 + c);
      }
      if (five) {
        mbar_wait(MB_KF);
#pragma unroll 1
        for (int it = 0; it < SPIN_MAX; it++) {
          if (lane == 0) load_tile(&tm.m[8], 2, 512 + (c >> 1));
          mbar_wait(MB_UL + 32, it & 1);
          uint32_t m = 1;
#pragma unroll
          for (int q = 0; q < 4; q++) { uint32_t r0, r1, r2, r3; ldsm4(OFF_W + 512 + lane * 64 + (lane & 6) * 8 + q * 2048, r0, r1, r2, r3); m &= r0 & r1 & r2 & r3; }
          if (__all_sync(0xffffffffu, m || (lane & 3))) break;
        }
        bar_arrive(7, 288);
        FINISH0
        bar_arrive(13, 192);
      }
      bar_sync(0, 544);
      if (lane == 0) mbar_arrive(MB_H);
    }
    return;
  }
  const int wt = tid & 127, g = lane >> 2, t = lane & 3;
  const uint32_t wb = OFF_W + wg * W_BYTES;
  asm volatile("cp.async.commit_group;" ::: "memory");
  const ConvC cv = conv_consts(warp, lane);
  zero_pads(wb, wt);
  load_params<FAR>(p, 254 + 2 * c + wg, wt, wb + W_KT, wg == 2 || (wg == 3 && !five));
  asm volatile("cp.async.commit_group;" ::: "memory");
  asm volatile("setmaxnreg.inc.sync.aligned.u32 112;");
  PAD(X_PAD0)
  {
    uint4 kw;
    uint4* kx = &p.s->KX[(c >> 1) * 128 + wt];
    bool two = wg == 3;
    uint32_t ep;
    int em = 0;
    int phase = wg == 2 ? 3 : 2;
#pragma unroll 1
    for (;;) {
      const bool first = two && !five;
      if (phase) asm volatile("cp.async.wait_group 1;" ::: "memory"); else asm volatile("cp.async.wait_group 0;" ::: "memory");
      if (phase == 3) {
        TS(21);
        float d[3][4], r;
        uint4 a[9];
#pragma unroll
        for (int k = 0; k < 9; k++) a[k] = lds128(xrow + k * 128);
#pragma unroll
        for (int i = 0; i < 4; i++) d[0][i] = d[1][i] = d[2][i] = 0.f;
#pragma unroll
        for (int k = 0; k < 9; k++) { mma_bf16(d[(2 * k) % 3], a[k].x, ones, a[k].y, ones, a[k].x, a[k].y); mma_bf16(d[(2 * k + 1) % 3], a[k].z, ones, a[k].w, ones, a[k].z, a[k].w); }
#pragma unroll
        for (int i = 0; i < 4; i++) d[0][i] += d[1][i] + d[2][i];
        const LnC lc = ln_consts(d[0][2] + d[0][3], __shfl_sync(0xffffffffu, d[0][0], 9 * t) + __shfl_sync(0xffffffffu, d[0][1], 9 * t + 4), r);
        if (lane < 12) sts16(MISC_LN1 + g * 32 + (warp & 3) * 8 + t * 2, lane < 4 ? lc.m2 : lane < 8 ? lc.rh2 : lc.rl2);
      } else {
        KgState ks;
        uint32_t raw[7];
        bar_sync(1 + wg, 128);
        TS(22);
#pragma unroll
        for (int i = 0; i < 7; i++) raw[i] = lds16(wb + W_KT + first * 2048 + i * 256 + (i < 6 ? wt : (first ? c >> 1 : 2 * c + (wg & 1)) & 7) * 2);
        kgen_tables_n(raw, wb, wt, ks);
        TS(20);
        bar_sync(1 + wg, 128);
        em = kgen_tables_m(wb, wt, ks);
        fence_async();
      }
      if (phase & 2) {
        const uint32_t tr_addr = tr_base(lane) + warp * 32;
        uint4* dst = &p.s->X[c * DM * 2 + warp * 32 + (8 * (t >> 1) + g) * 2 + (t & 1)];
        TS(23);
        bar_sync(5, 608);
        uint32_t x[3][4];
        ldsm4t(tr_addr, x[0][0], x[0][1], x[0][2], x[0][3]);
        const uint4 m = lds128(MISC_LN1 + (t & 1) * 16), rl = lds128(MISC_LN1 + 64 + (t & 1) * 16), rh = lds128(MISC_LN1 + 32 + (t & 1) * 16);
        ldsm4t(tr_addr + 512, x[1][0], x[1][1], x[1][2], x[1][3]);
        if (wg == 3) ldsm4t(tr_addr + 640, x[2][0], x[2][1], x[2][2], x[2][3]);
#pragma unroll
        for (int q = 0; q < 3; q++) {
          if (q < 2 || wg == 3) {
            const uint32_t r0 = ln_apply(x[q][0], m.x, rh.x, rl.x), r1 = ln_apply(x[q][1], m.y, rh.y, rl.y), r2 = ln_apply(x[q][2], m.z, rh.z, rl.z), r3 = ln_apply(x[q][3], m.w, rh.w, rl.w);
            const uint32_t w0 = (pack_h(bf_lo(r0), bf_hi(r0)) & 0xFFFEFFFEu) | 1u, w1 = pack_h(bf_lo(r1), bf_hi(r1)), w2 = pack_h(bf_lo(r2), bf_hi(r2)), w3 = pack_h(bf_lo(r3), bf_hi(r3));
            if (q == 0) str128(dst, w0, w1, w2, w3);
            else sts128(OFF_G + warp * 512 + (8 * (t >> 1) + g) * 32 + (t & 1) * 16 + (q == 2 ? 2048 : 0), w0, w1, w2, w3);
          }
          if (q == 0) TS(30);
        }
        bar_arrive(10, 576);
        TS(1);
      } else bar_sync(1 + wg, 128);
      phase &= 1;
      if (phase) { phase = 0; continue; }
      TS(14);
      float acc[20];
      const uint32_t alo = (wb >> 4) | (8u << 16);
      wg_fence();
      wgmma40_ss_init(acc, alo, alo + 1024, 2048 >> 4);
#pragma unroll
      for (int k = 1; k < 8; k++) wgmma40_ss(acc, alo + k * 16, alo + 1024 + k * 16, 2048 >> 4);
      wg_commit();
      const uint4 k4 = lds128(wb + W_MISC + 16);
      const float k2048 = (float)(int)(k4.x + k4.y + k4.z + k4.w) * (1.f / 262144.f);
      const uint32_t dk = lds16(OFF_WR + 1152 + (wg + first) * 2);
      const int ef = max(em, min((int)((dk >> 7) & 255u) - 7, 238));
      asm volatile("st.shared.u8 [%0], %1;" :: "r"(MISC_EM + wg + first), "r"(ef + 9) : "memory");
      const float un = __uint_as_float((uint32_t)max(114 + em - ef, 0) << 23), d0 = wt ? 0.f : bf_lo(dk) * __uint_as_float((uint32_t)(245 - ef) << 23);
      wg_wait<0>();
      kw.x = pack_h(fmaf(acc[0] - acc[3], un, d0), (acc[4] - acc[7]) * un);
      kw.y = pack_h((acc[8] - acc[11]) * un, (acc[12] - acc[15]) * un);
      kw.z = pack_h((acc[16] - acc[19]) * un, k2048 * un);
      TS(24);
      ep = 0;
      if (two) SPIN_WHILE(ep == 0, ep = lds32(MISC_EPOCH));
      if (five || !two) break;
      str128(kx, kw.x, kw.y, kw.z, ep);
      two = false;
    }
    if (lane == 0) mbar_arrive(MB_KF + wg * 8);
    if (two) { mbar_wait(MB_KF); zero_pads(OFF_W + ALT, wt); }
    uint32_t tb = wb;
#pragma unroll 1
    for (;;) {
      kgen_build(tb, wg, wt, kw.x, kw.y, kw.z);
      TS(15);
      if (!two) break;
      two = false;
      kw.w = 0;
      SPIN_WHILE(kw.w != ep, kw = ldr128(kx));
      tb = OFF_W + ALT;
    }
    fence_async();
    TS(31);
    if (tb != wb) bar_arrive(7, 288);
    bar_sync(1 + wg, 128);
  }
  uint32_t tpub;
  ConvPre pre;
  conv_pre(pre, wb + (cv.ca & 0xFFFFu), 3, true, warp & 2);
#pragma unroll 1
  for (int item = 0;; item++) {
    TS(2);
    conv_item(item ? OFF_W + ALT : wb, item ? OFF_W : OFF_T + (wg >> 1) * TILE, item ? 1 : 13 + (wg >> 1), item ? 128 : five && wg == 1 ? 192 : 256, pre, cv, p.off[7],
              &tm.m[item ? 9 : 7], item ? 512 + (c >> 1) : (wg >> 1) * 128 + c, warp, lane, five && wg >= X_GW, five && !wg && !item);
    tpub = clock() - (item ? X_YD : wg >= 2 ? X_YD2 : 0);
    if (wg || !five || item) break;
    TS(27);
  }
  TS(4);
  PAD(X_PAD1)

  const int ln = lane ^ p.off[7], td = warp * 32 + ln, gg = ln >> 2, tt = ln & 3;
  const int tok = c * 16 + warp;
  const int fu = warp / 3, fk = warp - fu * 3;
  uint32_t wa[12][4];
  uint4 ha[3];
  const uint4* hsrc = &p.s->HS[td + (td / 24) * 48];
  {
    uint32_t hw[9], wr[9];
    const uint32_t row = keep(OFF_YT + warp * YT_PITCH + (warp >> 3) * 64 + ln * 16);
    const uint32_t wabase = keep(((ln & 8) ? OFF_W + (fk + 1) * W_BYTES : OFF_G + fk * 192 * pitch) + ((ln >> 4) * 8 + (ln & 7)) * pitch
                                 + (five ? ((fu ^ (ln >> 1)) & 3) : min(fu, 4)) * 16);
    float sw;
    {
      const bool three = wg == 1;
      const int ch = 8 * (tt >> 1) + gg;
      const uint32_t tr_addr = tr_base(ln);
      const uint4* ysrc = &p.s->X[c * DM * 2 + ch * 2 + (tt & 1)];
      uint32_t x[3][4], s[3];
      uint4 v[3];
#define TL(q) ((q) < 2 ? 2 * warp + (q) : 28 + warp)
      asm volatile("cp.async.bulk.wait_group.read 0;" ::: "memory");
      if (wg >= 2) { const uint32_t ts = lds32(MISC_T0); while ((int)(clock() - ts) < X_XS) {} }
      while ((int)(clock() - tpub) < X_YD) {}
      TS(5);
      v[0] = ldr128(ysrc + TL(0) * 32); v[1] = ldr128(ysrc + TL(1) * 32); v[2] = make_uint4(three, 0, 0, 0);
      if (X_REL == 1 || (X_REL == 2 && wg != 1)) mbar_wait(MB_REL);
#pragma unroll
      for (int i = 0; i < 6; i++) if (i < 4 || three) wr[i] = (gg & 2) ? ones : lds32(OFF_WR + TL(i >> 1) * 32 + (i & 1) * 16 + tt * 4);
      const uint32_t ha = keep(OFF_YT + (ln & 7) * YT_PITCH + (ln >> 4) * (8 * YT_PITCH + 64) + (ln & 8) * 2);
      const uint32_t pa = keep(OFF_PART + warp * 4 + ((gg & 2) * 8 + (gg & 4) * 2 + 2 * tt + (gg & 1)) * 80), pb = keep(OFF_PART + 2560 + warp * 4 + gg * 80);
      float dl[4] = {0.f, 0.f, 0.f, 0.f}, dh[4] = {0.f, 0.f, 0.f, 0.f};
      sw = __uint_as_float(lds32(MISC_SW));
#pragma unroll
      for (int q = 0; q < 3; q++) {
        if (q < 2 || three) {
          ldsm4t(tr_addr + TL(q) * 32, x[q][0], x[q][1], x[q][2], x[q][3]);
        }
      }
      mbar_wait(MB_SC);
#pragma unroll
      for (int q = 0; q < 3; q++) {
        asm volatile("ld.shared.u8 %0, [%1];" : "=r"(s[q]) : "r"((q < 2 ? sc_addr(warp) + q * 16 : sc_addr(16) + (warp & 3) * 16) + ch) : "memory");
        s[q] = keep(s[q] * 0x800080u);
      }
#define FIN(q) stsm4t(tr_addr + TL(q) * 32, bf_fma2(h2bf(v[q].x), s[q], x[q][0]), bf_fma2(h2bf(v[q].y), s[q], x[q][1]), bf_fma2(h2bf(v[q].z), s[q], x[q][2]), bf_fma2(h2bf(v[q].w), s[q], x[q][3]));
      SPIN_WHILE((v[0].x | v[1].x) & 1u, _Pragma("unroll") for (int q = 0; q < 3; q++) if (v[q].x & 1u) v[q] = ldr128(ysrc + TL(q) * 32));
      if (v[2].x & 1u) v[2] = ldr128(ysrc + TL(2) * 32);
#define STAT(q) { uint32_t r0, r1, r2, r3; ldsm4(ha + TL(q) * 32, r0, r1, r2, r3); \
        mma_bf16(dl, r0, wr[2 * q], r1, wr[2 * q + 1], r0, r1); mma_bf16(dh, r2, wr[2 * q], r3, wr[2 * q + 1], r2, r3); }
      FIN(0) FIN(1)
      __syncwarp();
      STAT(0) STAT(1)
      if (three) {
        SPIN_WHILE(v[2].x & 1u, if (v[2].x & 1u) v[2] = ldr128(ysrc + TL(2) * 32));
        FIN(2)
        __syncwarp();
        STAT(2)
      }
      if (gg & 1) { dl[0] = dl[1]; dl[2] = dl[3]; dh[0] = dh[1]; dh[2] = dh[3]; }
      sts32(pa, __float_as_uint((gg & 4) ? dh[2] : dl[2]));
      if (tt == (gg >> 1)) { sts32(pb, __float_as_uint(dl[0])); sts32(pb + 640, __float_as_uint(dh[0])); }
#undef STAT
#undef FIN
#undef TL
    }
    uint32_t ra = keep(OFF_PART + (ln & 15) * 80 + (ln & 16) * 2);
    uint16_t* rp = (uint16_t*)p.s->R + c * 16 + (ln & 15);
    const uint2* rsrc = (const uint2*)p.s->R + td;
    asm volatile("" : "+l"(rp), "+l"(rsrc), "+l"(hsrc));
    uint2 rv = make_uint2(0u, 0u);
    TS(28);
    if (warp != X_PW) bar_sync(0, 544);
    else {
      float z[3], rd;
      asm volatile("bar.sync 0, 544;" : "+r"(ra) :: "memory");
#pragma unroll
      for (int k = 2; k >= 0; k--) {
        const uint4 a = lds128(ra + k * 1280), b = lds128(ra + k * 1280 + 16);
        z[k] = ((__uint_as_float(a.x) + __uint_as_float(a.y)) + (__uint_as_float(a.z) + __uint_as_float(a.w))) + ((__uint_as_float(b.x) + __uint_as_float(b.y)) + (__uint_as_float(b.z) + __uint_as_float(b.w)));
      }
#pragma unroll
      for (int k = 2; k >= 0; k--) z[k] += __shfl_xor_sync(0xffffffffu, z[k], 16);
      const LnC l = ln_consts(z[1], z[2], rd);
      const uint32_t b = pack_bf(0.f, fmaf(-bf_lo(l.m2), sw, z[0]) * rd);
      const uint32_t k16 = max(min((b ^ (((int)b >> 31) | 0x80000000u)) >> 16, 0xFFFEu), 1u);
      if (ln < 16) str16(rp, k16);
      sts64(OFF_RK + (ln & 15) * 8, __byte_perm(l.m2, l.rh2, 0x5410), __byte_perm(l.rl2, k16, 0x5410));
      sts128(MISC_CNT + ln * 16, 0, 0, 0, 0);
    }
    mbar_wait(MB_GU);
#define LD_HW { const uint4 a = lds128(row), b = lds128(row + 512); hw[8] = lds32(row + 1024 - ln * 12); \
      hw[0] = a.x; hw[1] = a.y; hw[2] = a.z; hw[3] = a.w; hw[4] = b.x; hw[5] = b.y; hw[6] = b.z; hw[7] = b.w; }
    LD_HW
    const uint32_t tr0 = clock();
    bar_sync(5, 512);
    TS(7);
    const uint2 lk = lds64(OFF_RK + warp * 8);
    LnC l2;
    l2.m2 = __byte_perm(lk.x, 0, 0x1010); l2.rh2 = __byte_perm(lk.x, 0, 0x3232); l2.rl2 = __byte_perm(lk.y, 0, 0x1010);
    const uint32_t key = (lk.y & 0xFFFF0000u) | (2047 - tok);
    uint32_t loc = ln < 16 ? (lds32(OFF_RK + 4 + ln * 8) & 0xFFFF0000u) | (2047 - c * 16 - ln) : 0u;
    int rank = __popc(__ballot_sync(0xffffffffu, loc > key));
#pragma unroll
    for (int i = 0; i < 9; i++) wr[i] = keep(ln_apply(hw[i], l2.m2, l2.rh2, l2.rl2));
#define OUT_ROW { uint32_t* o = p.out + tok * 288 + ln * 4; \
      *(uint4*)o = make_uint4(bf_add2(hw[0], wr[0]), bf_add2(hw[1], wr[1]), bf_add2(hw[2], wr[2]), bf_add2(hw[3], wr[3])); \
      *(uint4*)(o + 128) = make_uint4(bf_add2(hw[4], wr[4]), bf_add2(hw[5], wr[5]), bf_add2(hw[6], wr[6]), bf_add2(hw[7], wr[7])); \
      o[256 - ln * 3] = bf_add2(hw[8], wr[8]); }
    uint4* hs = p.s->HS + ln;
    asm volatile("" : "+l"(hs));
#pragma unroll 1
    for (int base = 0; base < 8; base += 2) {
      uint32_t T[2];
#pragma unroll
      for (int j = 0; j < 2; j++) {
        const uint32_t mx = __reduce_max_sync(0xffffffffu, loc);
        if (loc == mx) loc = 0;
        T[j] = (td >> 2) < c ? (mx & 0xFFFF0000u) - 1u : mx | 0xFFFFu;
      }
      const uint32_t sh = keep(rank == base ? 0x4410u : rank == base + 1 ? 0x4432u : 0x4445u), ca = keep(MISC_CNT + base * 64 + ln * 4);
      TS(29);
      if (base == 0) {
        while ((int)(clock() - tr0) < X_RD) {}
        if ((td >> 2) != c) rv = ldr64(rsrc);
        if (rank >= X_OR) OUT_ROW
        if (warp < (five ? 12 : 15)) {
#pragma unroll
          for (int k = 0; k < X_WS; k++) ldsm4t(wabase + k * 16 * pitch, wa[k][0], wa[k][1], wa[k][2], wa[k][3]);
        }
      }
      uint32_t cnt;
#pragma unroll 1
      for (int it = 0; it < SPIN_MAX; it++) {
        const uint32_t xs = rv.x << 16, ys = rv.y << 16;
        const bool bad = max(max(rv.x, xs), max(rv.y, ys)) >= 0xFFFF0000u;
        uint32_t cn2 = 0;
        cnt = bad ? 256u : 0u;
#pragma unroll
        for (int j = 0; j < 2; j++)
          asm("{ .reg .pred a, b, c, d; setp.gt.u32 a, %2, %6; setp.gt.u32 b, %3, %6; setp.gt.u32 c, %4, %6; setp.gt.u32 d, %5, %6; "
              "@a add.u32 %1, %1, %7; @b add.u32 %1, %1, %7; @c add.u32 %0, %0, %7; @d add.u32 %0, %0, %7; }"
              : "+r"(cnt), "+r"(cn2) : "r"(rv.x), "r"(rv.y), "r"(xs), "r"(ys), "r"(T[j]), "r"(1u << (16 * j)));
        cnt = __reduce_add_sync(0xffffffffu, cnt + cn2);
        asm volatile("{ .reg .pred q; setp.eq.u32 q, %2, 0; @q red.shared.add.u32 [%0], %1; }" :: "r"(ca), "r"(cnt), "r"(cnt & 0x3F00u) : "memory");
        if (!(cnt & 0x3F00u)) break;
        if (bad) rv = ldr64(rsrc);
      }
      TS(16);
      bar_sync(0, 512);
      cnt = lds32(ca);
      if (base == 0) tpub = clock();
      const int gr = rank + __byte_perm(cnt, 0x800u, sh);
      if (gr < 8) {
        uint4* ks = hs + 1152 + gr;
        hs = (uint4*)((char*)hs + gr * 1152);
        asm volatile("{ .reg .b128 t, u; .reg .b64 a, b, c, d; mov.b64 a, {%1,%2}; mov.b64 b, {%3,%4}; mov.b64 c, {%5,%6}; mov.b64 d, {%7,%8}; mov.b128 t, {a, b}; mov.b128 u, {c, d}; "
                     "st.relaxed.gpu.global.b128 [%0], t; st.relaxed.gpu.global.b128 [%0 + 512], u; }"
                     :: "l"(hs), "r"(wr[0]), "r"(wr[1]), "r"(wr[2]), "r"(wr[3]), "r"(wr[4]), "r"(wr[5]), "r"(wr[6]), "r"(wr[7]) : "memory");
        str32((uint32_t*)(hs + 64) - ln * 3, wr[8]);
        str128(hs + 576, hw[0], hw[1], hw[2], hw[3]); str128(hs + 608, hw[4], hw[5], hw[6], hw[7]); str32((uint32_t*)(hs + 640) - ln * 3, hw[8]);
        if (ln == 0) str32(ks, key);
        rank = 16;
      }
      if (__all_sync(0xffffffffu, (int)(cnt >> 16) + base + 2 >= 8)) break;
    }
    TS(8);
    if (warp < (five ? 12 : 15)) {
#pragma unroll
      for (int k = X_WS; k < 12; k++) ldsm4t(wabase + k * 16 * pitch, wa[k][0], wa[k][1], wa[k][2], wa[k][3]);
    }
    if (warp < 6) while ((int)(clock() - tpub) < X_HD) {}
    TS(19);
    if (warp < 6) { ha[0] = ldr128(hsrc); ha[1] = ldr128(hsrc + 24); ha[2] = ldr128(hsrc + 48); }
    if (rank < X_OR) OUT_ROW
  }
  uint32_t wd[10][4];
  const uint32_t xb = keep(OFF_XS + (ln & 7) * 1168 + (fk * 24 + (ln >> 3)) * 16);
  if (warp >= 7) {
    const uint32_t db = down_box(warp - 7, five) + (ln & 7) * 128;
    mbar_wait(MB_D);
#pragma unroll
    for (int j = 0; j < 4; j++) {
      const uint32_t a = db + (ln >> 4) * 1024 + (((2 * j + ((ln >> 3) & 1)) ^ (ln & 7)) << 4);
      ldsm4t(a, wd[j][0], wd[j][1], wd[j][2], wd[j][3]);
      ldsm4t(a + 2048, wd[4 + j][0], wd[4 + j][1], wd[4 + j][2], wd[4 + j][3]);
    }
#pragma unroll
    for (int j = 0; j < 2; j++) ldsm4t(db + 4096 + (((4 * j + (ln >> 3)) ^ (ln & 7)) << 4), wd[8 + j][0], wd[8 + j][1], wd[8 + j][2], wd[8 + j][3]);
  } else if (warp < 6) {
    const uint32_t xs = keep(OFF_XS + (td + (td / 24) * 49) * 16);
#pragma unroll 1
    for (int it = 0; it < SPIN_MAX; it++) {
      const bool bad = max(max(max(ha[0].x, ha[1].x), max(ha[2].x, ha[2].y)), max(ha[2].z, ha[2].w)) == ~0u;
      if (!__any_sync(0xffffffffu, bad)) break;
      if (bad) { ha[0] = ldr128(hsrc); ha[1] = ldr128(hsrc + 24); ha[2] = ldr128(hsrc + 48); }
    }
#pragma unroll
    for (int q = 0; q < 3; q++) sts128(xs + q * 384, ha[q].x, ha[q].y, ha[q].z, ha[q].w);
  }
  TS(9);

  if (!(M_ & 2)) bar_sync(0, 512);
  if (warp >= (five ? 12 : 15)) { if (M_ & 2) bar_sync(0, 512); }
  else {
    if (M_ & 2) bar_sync(0, 512);
    float d0[4] = {0.f, 0.f, 0.f, 0.f}, d1[4] = {0.f, 0.f, 0.f, 0.f};
#pragma unroll
    for (int k = 0; k < 12; k += 2) {
      uint32_t b0, b1, b2, b3;
      ldsm4(xb + k * 32, b0, b1, b2, b3);
      mma_bf16(d0, wa[k][0], wa[k][1], wa[k][2], wa[k][3], b0, b1);
      mma_bf16(d1, wa[k + 1][0], wa[k + 1][1], wa[k + 1][2], wa[k + 1][3], b2, b3);
    }
    sts128(OFF_RED + td * 16, __float_as_uint(d0[0] + d1[0]), __float_as_uint(d0[1] + d1[1]), __float_as_uint(d0[2] + d1[2]), __float_as_uint(d0[3] + d1[3]));
  }
  TS(26);
  if (warp < 5) {
    const uint32_t rb = OFF_RED + warp * 1536 + ln * 16;
    bar_sync(9, 512);
    const uint4 pa = lds128(rb), pb = lds128(rb + 512), pc = lds128(rb + 1024);
    const float ga = bfr(__uint_as_float(pa.x) + __uint_as_float(pb.x) + __uint_as_float(pc.x));
    const float gb = bfr(__uint_as_float(pa.y) + __uint_as_float(pb.y) + __uint_as_float(pc.y));
    const uint32_t uu = pack_bf(__uint_as_float(pa.z) + __uint_as_float(pb.z) + __uint_as_float(pc.z), __uint_as_float(pa.w) + __uint_as_float(pb.w) + __uint_as_float(pc.w));
    float ra, rb2;
    asm("rcp.approx.ftz.f32 %0, %1;" : "=f"(ra) : "f"(1.f + ex2(ga * -1.4426950408889634f)));
    asm("rcp.approx.ftz.f32 %0, %1;" : "=f"(rb2) : "f"(1.f + ex2(gb * -1.4426950408889634f)));
    const uint32_t act = bf_mul2(pack_bf(ga * ra, gb * rb2), uu);
    sts32(OFF_ACT + td * 4, act);
  } else bar_arrive(9, 512);
  uint4* dst = &p.s->X[c * DM * 2 + (warp - 7) * 64 + tt * 8 + gg];
  asm volatile("" : "+l"(dst));
  if (!(M_ & 1)) { bar_sync(8, 512); tpub = clock(); }
  if (warp < 7) { if (M_ & 1) { bar_sync(8, 512); tpub = clock(); } }
  else {
    uint32_t b0, b1, b2, b3, b4;
    if (M_ & 1) bar_sync(8, 512);
    ldsm4t(OFF_ACT + ln * 16, b0, b1, b2, b3);
    asm volatile("ldmatrix.sync.aligned.m8n8.x1.trans.shared.b16 {%0}, [%1];" : "=r"(b4) : "r"(OFF_ACT + 512 + ln * 16) : "memory");
    if (M_ & 1) tpub = clock();
    float y[4][4];
#pragma unroll
    for (int j = 0; j < 4; j++) {
      y[j][0] = y[j][1] = y[j][2] = y[j][3] = 0.f;
      mma_bf16(y[j], wd[j][0], wd[j][1], wd[j][2], wd[j][3], b0, b1);
    }
#pragma unroll
    for (int j = 0; j < 4; j++) mma_bf16(y[j], wd[4 + j][0], wd[4 + j][1], wd[4 + j][2], wd[4 + j][3], b2, b3);
    if (!five) {
#pragma unroll
      for (int j = 0; j < 4; j++) mma_bf16_k8(y[j], wd[8 + (j >> 1)][2 * (j & 1)], wd[8 + (j >> 1)][2 * (j & 1) + 1], b4);
    }
    str128(dst, (pack_bf(y[0][0], y[0][1]) & ~1u) | 0x10000u, pack_bf(y[0][2], y[0][3]), pack_bf(y[1][0], y[1][1]), pack_bf(y[1][2], y[1][3]));
    str128(dst + 32, (pack_bf(y[2][0], y[2][1]) & ~1u) | 0x10000u, pack_bf(y[2][2], y[2][3]), pack_bf(y[3][0], y[3][1]), pack_bf(y[3][2], y[3][3]));
  }
  TS(10);

  if (c < 72) {
    const uint4* src = &p.s->X[(warp * 4 + tt) * (DM * 2) + c * 8 + gg];
    const int slot = (c & 3) * 2 + (ln >> 4), dw = (c >> 2) * 16 + (ln & 15);
    uint32_t hv = 0, kv = 0, res = 0, rs2 = 0;
    uint32_t* o = p.out;
    if (warp == 0) {
      hv = ~0u;
      SPIN_WHILE(max(hv, kv) == ~0u, hv = ldr32((const uint32_t*)p.s->HS + 2304 + slot * 288 + dw); kv = ldr32(&p.s->HS[1152 + slot]));
      const float r = bf_hi(kv ^ (((int)~kv >> 31) | 0x80000000u));
      float rs;
      asm("rcp.approx.ftz.f32 %0, %1;" : "=f"(rs) : "f"(1.f + ex2(r * -1.4426950408889634f)));
      rs2 = keep(pack_bf(rs, rs));
      res = lds32(OFF_XS + slot * 1168 + dw * 4);
      o += (2047 - (int)(kv & 2047u)) * 288 + dw;
      asm volatile("" : "+l"(o));
    }
    const uint32_t sel = (gg & 1) ? 0x3F800000u : 0x00003F80u;
    const uint32_t q0 = keep((gg >> 1) == 0 ? sel : 0u), q1 = keep((gg >> 1) == 1 ? sel : 0u), q2 = keep((gg >> 1) == 2 ? sel : 0u), q3 = keep((gg >> 1) == 3 ? sel : 0u);
#if M_ & 4
    const uint32_t fa = keep(OFF_RED + warp * 8 + ((gg & 1) * 16 + (gg >> 1) * 4 + tt) * 144), fb = keep(OFF_RED + ln * 144);
#else
    const uint32_t fa = keep(OFF_FIN + warp * 256 + (gg & 1) * 128 + (gg >> 1) * 32 + tt * 8), fb = keep(OFF_FIN + ln * 8);
#endif
    uint4 a0 = make_uint4(0, 0, 0, 0), a1 = a0;
    while ((int)(clock() - tpub) < X_PD) {}
    SPIN_WHILE(!(a0.x & a1.x & 0x10000u), if (!(a0.x & 0x10000u)) a0 = ldr128(src); if (!(a1.x & 0x10000u)) a1 = ldr128(src + 64 * DM * 2));
    float d[4] = {0.f, 0.f, 0.f, 0.f}, e[4] = {0.f, 0.f, 0.f, 0.f}, d2[4] = {0.f, 0.f, 0.f, 0.f}, e2[4] = {0.f, 0.f, 0.f, 0.f};
    mma_bf16(d, q0, q2, q1, q3, a0.x, a0.y); mma_bf16(e, q0, q2, q1, q3, a0.z, a0.w);
#if M_ & 8
    mma_bf16(d2, q0, q2, q1, q3, a1.x, a1.y); mma_bf16(e2, q0, q2, q1, q3, a1.z, a1.w);
    sts64(fa, __float_as_uint(d[0] + e[2] + d2[0] + e2[2]), __float_as_uint(d[1] + e[3] + d2[1] + e2[3]));
#else
    mma_bf16(d, q0, q2, q1, q3, a1.x, a1.y); mma_bf16(e, q0, q2, q1, q3, a1.z, a1.w);
    sts64(fa, __float_as_uint(d[0] + e[2]), __float_as_uint(d[1] + e[3]));
#endif
    TS(11);
    if (warp == 0) {
      bar_sync(0, 512);
      float2 s[16];
#if !(M_ & 4)
#pragma unroll
      for (int i = 0; i < 16; i++) { const uint2 q = lds64(fb + i * 256); s[i] = make_float2(__uint_as_float(q.x), __uint_as_float(q.y)); }
#else
#pragma unroll
      for (int i = 0; i < 16; i += 2) { const uint4 q = lds128(fb + i * 8); s[i] = make_float2(__uint_as_float(q.x), __uint_as_float(q.y)); s[i + 1] = make_float2(__uint_as_float(q.z), __uint_as_float(q.w)); }
#endif
#pragma unroll
      for (int k = 1; k < 16; k *= 2)
#pragma unroll
        for (int i = 0; i < 16; i += 2 * k) { s[i].x += s[i + k].x; s[i].y += s[i + k].y; }
      *o = bf_add2(hv, bf_add2(res, bf_mul2(pack_bf(s[0].x, s[0].y), rs2)));
    } else bar_arrive(0, 512);
  }
  TS(12);
  TS_DUMP();
}

typedef CUresult (*EncodeFn)(CUtensorMap*, CUtensorMapDataType, cuuint32_t, void*, const cuuint64_t*, const cuuint64_t*, const cuuint32_t*,
                             const cuuint32_t*, CUtensorMapInterleave, CUtensorMapSwizzle, CUtensorMapL2promotion, CUtensorMapFloatOOBfill);

}

extern "C" void kernel_launch(void* const* d_in, const int* in_sizes, int n_in, void* d_out, int out_size) {
  (void)in_sizes; (void)n_in; (void)out_size;
  static EncodeFn enc = nullptr;
  static Scratch* scratch = nullptr;
  if (!enc) {
    void* fn = nullptr;
    cudaDriverEntryPointQueryResult qr;
    cudaGetDriverEntryPoint("cuTensorMapEncodeTiled", &fn, cudaEnableDefault, &qr);
    enc = (EncodeFn)fn;
    cudaGetSymbolAddress((void**)&scratch, g_S);
    cudaFuncSetAttribute(fused_kernel<false>, cudaFuncAttributeMaxDynamicSharedMemorySize, SMEM_BYTES);
    cudaFuncSetAttribute(fused_kernel<true>, cudaFuncAttributeMaxDynamicSharedMemorySize, SMEM_BYTES);
  }
  TMaps tm;
  for (int i = 0; i < 6; i++) {
    const bool dn = i % 3 == 2;
    const cuuint32_t w = i < 3 ? 40 : 32;
    cuuint64_t gd[3] = {(cuuint64_t)(dn ? 64 : FF), (cuuint64_t)(dn ? FF : DM), 9};
    cuuint64_t gs[2] = {(cuuint64_t)(dn ? DM * 2 : FF * 2), 128};
    cuuint32_t bx[3] = {dn ? 64 : w, dn ? w : 96, i < 3 ? 2u : 3u};
    cuuint32_t es[3] = {1, 1, 1};
    enc(&tm.m[i], CU_TENSOR_MAP_DATA_TYPE_BFLOAT16, dn ? 3 : 2, d_in[11 + i % 3], gd, gs, bx, es, CU_TENSOR_MAP_INTERLEAVE_NONE,
        dn ? CU_TENSOR_MAP_SWIZZLE_128B : i < 3 ? CU_TENSOR_MAP_SWIZZLE_NONE : CU_TENSOR_MAP_SWIZZLE_64B,
        (CUtensorMapL2promotion)X_PROMO, CU_TENSOR_MAP_FLOAT_OOB_FILL_NONE);
  }
  for (int i = 6; i < 10; i++) {
    cuuint64_t gd[3] = {i < 8 ? 32u : 16u, i < 8 ? DM / 2u : DM, NCTA};
    cuuint64_t gs[2] = {i < 8 ? 64u : 32u, DM * 32};
    cuuint32_t bx[3] = {32, 1, (i & 1) ? 128u : 136u};
    cuuint32_t es[3] = {1, 1, 1};
    enc(&tm.m[i], CU_TENSOR_MAP_DATA_TYPE_FLOAT16, 3, scratch->X, gd, gs, bx, es, CU_TENSOR_MAP_INTERLEAVE_NONE, CU_TENSOR_MAP_SWIZZLE_64B,
        CU_TENSOR_MAP_L2_PROMOTION_NONE, CU_TENSOR_MAP_FLOAT_OOB_FILL_NONE);
  }
  Params p;
  p.x = (const unsigned char*)d_in[0];
  bool far = false;
  for (int i = 0; i < 7; i++) {
    p.far[i] = (const unsigned char*)d_in[1 + i];
    const long long d = (long long)((intptr_t)d_in[1 + i] - (intptr_t)d_in[0]);
    p.off[i] = (int)(d / 16);
    if ((long long)p.off[i] * 16 != d || p.off[i] > (1 << 30)) far = true;
  }
  p.dskip = (const uint16_t*)d_in[8];
  p.w_r = (const uint32_t*)d_in[10];
  for (int f = 0; f < 2; f++) {
    static const int kind[17] = {0, 0, 0, 0, 2, 2, 0, 0, 1, 1, 1, 1, 1, 1, 2, 2, 2};
    static const int idx[2][17] = {{2, 3, 4, 5, 6, 8, 0, 1, 0, 1, 2, 3, 4, 5, 0, 2, 4}, {2, 3, 4, 5, 0, -1, 0, 1, 0, 1, 2, 3, 4, 5, 3, -1, 6}};
    static const int blk[2][17] = {{-1, -1, -1, -1, 0, -1, 4, -1, 1, -1, 2, -1, 3, -1, 16, -1, -1}, {-1, -1, -1, -1, 1, -1, 4, -1, -1, -1, 2, -1, 3, -1, 16, -1, -1}};
    const int pitch = f ? 64 : 80;
    for (int u = 0; u < 17; u++) {
      const int s = idx[f][u];
      const uint32_t dst = kind[u] == 0 ? OFF_G + s * 96 * pitch : kind[u] == 2 ? down_box(s, f) : OFF_W + W_BYTES + (s >> 1) * W_BYTES + (s & 1) * 96 * pitch;
      const uint32_t mb = u >= 14 ? (u >= X_HU ? MB_H - OFF_MISC : X_HB) : blk[f][u] >= 0 ? MB_KF - OFF_MISC + blk[f][u] * 8 : 0;
      p.sched[f][u] = s < 0 ? 3u : kind[u] | s << 2 | mb << 6 | dst << 14;
    }
  }
  p.out = (uint32_t*)d_out;
  p.off[7] = 0;
  p.ts = nullptr;
  p.s = scratch;
  if (far) { fused_kernel<true><<<NCTA, NT, SMEM_BYTES, cudaStreamPerThread>>>(p, tm); return; }
  fused_kernel<false><<<NCTA, NT, SMEM_BYTES, cudaStreamPerThread>>>(p, tm);
}
```

```cpp
#include <cuda_runtime.h>
#include <cuda.h>
#include <cuda_bf16.h>
#include <cuda_fp16.h>
#include <stdint.h>
#include <stddef.h>

namespace {

constexpr int NCTA = 128;
constexpr int NT = 640;
constexpr int DM = 576;
constexpr int FF = 4608;
constexpr int SPIN_MAX = 1 << 20;

struct Scratch {
  uint4 X[NCTA * DM * 2];
  uint4 KX[64 * 128];
  uint4 HS[1152 + 8];
  uint4 R[256];
  uint4 SC[256];
  uint32_t FLAG[NCTA * 8];
};
__device__ Scratch g_S;

#define CLKS(i)
#define TS(i)
#define TSX(i)
#define TS_DUMP()

constexpr int SB = 1024;
constexpr int BOX = 15360;
constexpr int OFF_G = SB;
constexpr int OFF_W = OFF_G + 3 * BOX;
constexpr int W_KT = 26624;
constexpr int W_L3 = W_KT + 4416;
constexpr int W_CW = W_L3 + 4096;
constexpr int W_MISC = W_CW + 640;
constexpr int W_BYTES = 35840;
constexpr int TILE = 10240;
constexpr int OFF_T = OFF_W + 4 * W_BYTES;
constexpr int ALT = TILE - W_KT;
static_assert(W_MISC + 32 <= W_BYTES && OFF_W % 1024 == 0 && W_BYTES % 1024 == 0 && W_BYTES + ALT <= 20480, "wg block");
constexpr int YT_PITCH = 1184;
constexpr int OFF_YT = OFF_T + 2 * TILE;
constexpr int OFF_WR = OFF_YT + 16 * YT_PITCH + 64;
constexpr int OFF_MISC = OFF_WR + 2304;
constexpr int SMEM_BYTES = OFF_MISC + 1024 - SB;
static_assert(OFF_YT % 16 == 0 && OFF_MISC % 16 == 0, "align");
static_assert(SMEM_BYTES <= 232448, "smem");
constexpr int MB_GU = OFF_MISC;
constexpr int MB_D = OFF_MISC + 8;
constexpr int MB_KF = OFF_MISC + 16;
constexpr int MB_GF = OFF_MISC + 48;
constexpr int MB_SC = OFF_MISC + 56;
constexpr int MB_UL = OFF_MISC + 64;
constexpr int MB_REL = OFF_MISC + 104;
constexpr int MB_GO = OFF_MISC + 112;
constexpr int MB_H = MB_KF + 128;
constexpr int MISC_EPOCH = OFF_MISC + 152;
constexpr int MISC_SW = OFF_MISC + 156;
constexpr int MISC_RT = OFF_MISC + 160;
constexpr int MISC_T0 = OFF_MISC + 296;
constexpr int MISC_EM = OFF_MISC + 288;
constexpr int OFF_PART = OFF_W + 20480;
constexpr int OFF_RK = OFF_PART + 3840;
constexpr int MISC_LN1 = OFF_MISC + 192;
constexpr int OFF_XS = OFF_T;
constexpr int OFF_RED = OFF_T + TILE;
constexpr int OFF_FIN = OFF_W + 3 * W_BYTES + W_KT;
constexpr int OFF_ACT = OFF_FIN + 4096;
constexpr int MISC_CNT = OFF_ACT + 1024;

__device__ __forceinline__ uint32_t smem_u32(const void* p) { return (uint32_t)__cvta_generic_to_shared(p); }
__device__ __forceinline__ uint32_t lds32(uint32_t a) { uint32_t v; asm volatile("ld.shared.b32 %0, [%1];" : "=r"(v) : "r"(a) : "memory"); return v; }
__device__ __forceinline__ uint32_t lds16(uint32_t a) { uint16_t v; asm volatile("ld.shared.u16 %0, [%1];" : "=h"(v) : "r"(a) : "memory"); return v; }
__device__ __forceinline__ uint2 lds64(uint32_t a) { uint2 v; asm volatile("ld.shared.v2.b32 {%0,%1}, [%2];" : "=r"(v.x), "=r"(v.y) : "r"(a) : "memory"); return v; }
__device__ __forceinline__ uint4 lds128(uint32_t a) { uint4 v; asm volatile("ld.shared.v4.b32 {%0,%1,%2,%3}, [%4];" : "=r"(v.x), "=r"(v.y), "=r"(v.z), "=r"(v.w) : "r"(a) : "memory"); return v; }
__device__ __forceinline__ void sts16(uint32_t a, uint32_t v) { asm volatile("st.shared.u16 [%0], %1;" :: "r"(a), "h"((uint16_t)v) : "memory"); }
__device__ __forceinline__ void sts32(uint32_t a, uint32_t v) { asm volatile("st.shared.b32 [%0], %1;" :: "r"(a), "r"(v) : "memory"); }
__device__ __forceinline__ void sts64(uint32_t a, uint32_t x, uint32_t y) { asm volatile("st.shared.v2.b32 [%0], {%1,%2};" :: "r"(a), "r"(x), "r"(y) : "memory"); }
__device__ __forceinline__ void sts128(uint32_t a, uint32_t x, uint32_t y, uint32_t z, uint32_t w) { asm volatile("st.shared.v4.b32 [%0], {%1,%2,%3,%4};" :: "r"(a), "r"(x), "r"(y), "r"(z), "r"(w) : "memory"); }
__device__ __forceinline__ void ldsm4(uint32_t a, uint32_t& r0, uint32_t& r1, uint32_t& r2, uint32_t& r3) {
  asm volatile("ldmatrix.sync.aligned.m8n8.x4.shared.b16 {%0,%1,%2,%3}, [%4];" : "=r"(r0), "=r"(r1), "=r"(r2), "=r"(r3) : "r"(a) : "memory");
}
__device__ __forceinline__ void ldsm2(uint32_t a, uint32_t& r0, uint32_t& r1) {
  asm volatile("ldmatrix.sync.aligned.m8n8.x2.shared.b16 {%0,%1}, [%2];" : "=r"(r0), "=r"(r1) : "r"(a) : "memory");
}
__device__ __forceinline__ void ldsm4t(uint32_t a, uint32_t& r0, uint32_t& r1, uint32_t& r2, uint32_t& r3) {
  asm volatile("ldmatrix.sync.aligned.m8n8.x4.trans.shared.b16 {%0,%1,%2,%3}, [%4];" : "=r"(r0), "=r"(r1), "=r"(r2), "=r"(r3) : "r"(a) : "memory");
}
__device__ __forceinline__ void stsm4t(uint32_t a, uint32_t r0, uint32_t r1, uint32_t r2, uint32_t r3) {
  asm volatile("stmatrix.sync.aligned.m8n8.x4.trans.shared.b16 [%0], {%1,%2,%3,%4};" :: "r"(a), "r"(r0), "r"(r1), "r"(r2), "r"(r3) : "memory");
}
__device__ __forceinline__ uint4 ldr128(const void* p) {
  unsigned long long lo, hi;
  asm volatile("{ .reg .b128 t; ld.relaxed.gpu.global.b128 t, [%2]; mov.b128 {%0, %1}, t; }" : "=l"(lo), "=l"(hi) : "l"(p) : "memory");
  return make_uint4((uint32_t)lo, (uint32_t)(lo >> 32), (uint32_t)hi, (uint32_t)(hi >> 32));
}
__device__ __forceinline__ void str128(void* p, uint32_t x, uint32_t y, uint32_t z, uint32_t w) {
  asm volatile("{ .reg .b128 t; .reg .b64 lo, hi; mov.b64 lo, {%1,%2}; mov.b64 hi, {%3,%4}; mov.b128 t, {lo, hi}; st.relaxed.gpu.global.b128 [%0], t; }"
               :: "l"(p), "r"(x), "r"(y), "r"(z), "r"(w) : "memory");
}
__device__ __forceinline__ void str64(void* p, uint32_t x, uint32_t y) {
  asm volatile("{ .reg .b64 t; mov.b64 t, {%1,%2}; st.relaxed.gpu.global.b64 [%0], t; }" :: "l"(p), "r"(x), "r"(y) : "memory");
}
__device__ __forceinline__ uint32_t ldr32(const void* p) { uint32_t v; asm volatile("ld.relaxed.gpu.global.b32 %0, [%1];" : "=r"(v) : "l"(p) : "memory"); return v; }
__device__ __forceinline__ void str32(void* p, uint32_t v) { asm volatile("st.relaxed.gpu.global.b32 [%0], %1;" :: "l"(p), "r"(v) : "memory"); }
__device__ __forceinline__ void str16(void* p, uint32_t v) { asm volatile("st.relaxed.gpu.global.u16 [%0], %1;" :: "l"(p), "h"((uint16_t)v) : "memory"); }
__device__ __forceinline__ void fence_gpu() { asm volatile("fence.acq_rel.gpu;" ::: "memory"); }
__device__ __forceinline__ void bar_sync(int id, int n) { asm volatile("bar.sync %0, %1;" :: "r"(id), "r"(n) : "memory"); }
__device__ __forceinline__ void bar_arrive(int id, int n) { asm volatile("bar.arrive %0, %1;" :: "r"(id), "r"(n) : "memory"); }

__device__ __forceinline__ float bf_lo(uint32_t w) { return __uint_as_float(w << 16); }
__device__ __forceinline__ float bf_hi(uint32_t w) { return __uint_as_float(w & 0xFFFF0000u); }
__device__ __forceinline__ uint32_t pack_bf(float lo, float hi) { uint32_t r; asm("cvt.rn.bf16x2.f32 %0, %1, %2;" : "=r"(r) : "f"(hi), "f"(lo)); return r; }
__device__ __forceinline__ uint32_t pack_h(float lo, float hi) { uint32_t r; asm("cvt.rn.f16x2.f32 %0, %1, %2;" : "=r"(r) : "f"(hi), "f"(lo)); return r; }
__device__ __forceinline__ uint32_t pack_hv(float lo, float hi) { uint32_t r; asm volatile("cvt.rn.f16x2.f32 %0, %1, %2;" : "=r"(r) : "f"(hi), "f"(lo) : "memory"); return r; }
__device__ __forceinline__ float bfr(float x) { return bf_lo(pack_bf(x, 0.f)); }
__device__ __forceinline__ uint32_t bf_sub2(uint32_t a, uint32_t b) { __nv_bfloat162 r = __hsub2(*(__nv_bfloat162*)&a, *(__nv_bfloat162*)&b); return *(uint32_t*)&r; }
__device__ __forceinline__ uint32_t bf_add2(uint32_t a, uint32_t b) { __nv_bfloat162 r = __hadd2(*(__nv_bfloat162*)&a, *(__nv_bfloat162*)&b); return *(uint32_t*)&r; }
__device__ __forceinline__ uint32_t bf_mul2(uint32_t a, uint32_t b) { __nv_bfloat162 r = __hmul2(*(__nv_bfloat162*)&a, *(__nv_bfloat162*)&b); return *(uint32_t*)&r; }
__device__ __forceinline__ float2 h2f(uint32_t w) { return __half22float2(*(__half2*)&w); }
__device__ __forceinline__ float ex2(float x) { float r; asm("ex2.approx.ftz.f32 %0, %1;" : "=f"(r) : "f"(x)); return r; }
__device__ __forceinline__ float warp_sum(float v) {
#pragma unroll
  for (int o = 16; o > 0; o >>= 1) v += __shfl_xor_sync(0xffffffffu, v, o);
  return v;
}
__device__ __forceinline__ void mma_f16_f32(float* d, uint32_t a0, uint32_t a1, uint32_t a2, uint32_t a3, uint32_t b0, uint32_t b1) {
  asm volatile("mma.sync.aligned.m16n8k16.row.col.f32.f16.f16.f32 {%0,%1,%2,%3}, {%4,%5,%6,%7}, {%8,%9}, {%0,%1,%2,%3};"
               : "+f"(d[0]), "+f"(d[1]), "+f"(d[2]), "+f"(d[3]) : "r"(a0), "r"(a1), "r"(a2), "r"(a3), "r"(b0), "r"(b1));
}
__device__ __forceinline__ void mma_f16_f16(uint32_t& d0, uint32_t& d1, uint32_t a0, uint32_t a1, uint32_t a2, uint32_t a3, uint32_t b0, uint32_t b1) {
  asm volatile("mma.sync.aligned.m16n8k16.row.col.f16.f16.f16.f16 {%0,%1}, {%2,%3,%4,%5}, {%6,%7}, {%0,%1};"
               : "+r"(d0), "+r"(d1) : "r"(a0), "r"(a1), "r"(a2), "r"(a3), "r"(b0), "r"(b1));
}
__device__ __forceinline__ void mma_bf16(float* d, uint32_t a0, uint32_t a1, uint32_t a2, uint32_t a3, uint32_t b0, uint32_t b1) {
  asm volatile("mma.sync.aligned.m16n8k16.row.col.f32.bf16.bf16.f32 {%0,%1,%2,%3}, {%4,%5,%6,%7}, {%8,%9}, {%0,%1,%2,%3};"
               : "+f"(d[0]), "+f"(d[1]), "+f"(d[2]), "+f"(d[3]) : "r"(a0), "r"(a1), "r"(a2), "r"(a3), "r"(b0), "r"(b1));
}
__device__ __forceinline__ void mma_bf16_k8(float* d, uint32_t a0, uint32_t a1, uint32_t b0) {
  asm volatile("mma.sync.aligned.m16n8k8.row.col.f32.bf16.bf16.f32 {%0,%1,%2,%3}, {%4,%5}, {%6}, {%0,%1,%2,%3};"
               : "+f"(d[0]), "+f"(d[1]), "+f"(d[2]), "+f"(d[3]) : "r"(a0), "r"(a1), "r"(b0));
}

__device__ __forceinline__ void wg_fence() { asm volatile("wgmma.fence.sync.aligned;" ::: "memory"); }
__device__ __forceinline__ void wg_commit() { asm volatile("wgmma.commit_group.sync.aligned;" ::: "memory"); }
template <int N> __device__ __forceinline__ void wg_wait() { asm volatile("wgmma.wait_group.sync.aligned %0;" :: "n"(N) : "memory"); }
template <int TB> __device__ __forceinline__ void wgmma32(float* d, const uint32_t* a, uint32_t dlo, uint32_t dhi) {
  asm volatile("{ .reg .b64 dd; mov.b64 dd, {%20, %21}; wgmma.mma_async.sync.aligned.m64n32k16.f32.f16.f16 "
               "{%0,%1,%2,%3,%4,%5,%6,%7,%8,%9,%10,%11,%12,%13,%14,%15}, {%16,%17,%18,%19}, dd, 1, 1, 1, %22; }"
               : "+f"(d[0]), "+f"(d[1]), "+f"(d[2]), "+f"(d[3]), "+f"(d[4]), "+f"(d[5]), "+f"(d[6]), "+f"(d[7]), "+f"(d[8]), "+f"(d[9]), "+f"(d[10]), "+f"(d[11]), "+f"(d[12]), "+f"(d[13]), "+f"(d[14]), "+f"(d[15])
               : "r"(a[0]), "r"(a[1]), "r"(a[2]), "r"(a[3]), "r"(dlo), "r"(dhi), "n"(TB));
}
template <int TB> __device__ __forceinline__ void wgmma64(float* d, const uint32_t* a, uint32_t dlo, uint32_t dhi) {
  asm volatile("{ .reg .b64 dd; mov.b64 dd, {%36, %37}; wgmma.mma_async.sync.aligned.m64n64k16.f32.f16.f16 "
               "{%0,%1,%2,%3,%4,%5,%6,%7,%8,%9,%10,%11,%12,%13,%14,%15,%16,%17,%18,%19,%20,%21,%22,%23,%24,%25,%26,%27,%28,%29,%30,%31}, {%32,%33,%34,%35}, dd, 1, 1, 1, %38; }"
               : "+f"(d[0]), "+f"(d[1]), "+f"(d[2]), "+f"(d[3]), "+f"(d[4]), "+f"(d[5]), "+f"(d[6]), "+f"(d[7]), "+f"(d[8]), "+f"(d[9]), "+f"(d[10]), "+f"(d[11]), "+f"(d[12]), "+f"(d[13]), "+f"(d[14]), "+f"(d[15]), "+f"(d[16]), "+f"(d[17]), "+f"(d[18]), "+f"(d[19]), "+f"(d[20]), "+f"(d[21]), "+f"(d[22]), "+f"(d[23]), "+f"(d[24]), "+f"(d[25]), "+f"(d[26]), "+f"(d[27]), "+f"(d[28]), "+f"(d[29]), "+f"(d[30]), "+f"(d[31])
               : "r"(a[0]), "r"(a[1]), "r"(a[2]), "r"(a[3]), "r"(dlo), "r"(dhi), "n"(TB));
}
template <int TB> __device__ __forceinline__ void wgmma64_init(float* d, const uint32_t* a, uint32_t dlo, uint32_t dhi) {
  asm volatile("{ .reg .b64 dd; mov.b64 dd, {%36, %37}; wgmma.mma_async.sync.aligned.m64n64k16.f32.f16.f16 "
               "{%0,%1,%2,%3,%4,%5,%6,%7,%8,%9,%10,%11,%12,%13,%14,%15,%16,%17,%18,%19,%20,%21,%22,%23,%24,%25,%26,%27,%28,%29,%30,%31}, {%32,%33,%34,%35}, dd, 0, 1, 1, %38; }"
               : "=f"(d[0]), "=f"(d[1]), "=f"(d[2]), "=f"(d[3]), "=f"(d[4]), "=f"(d[5]), "=f"(d[6]), "=f"(d[7]), "=f"(d[8]), "=f"(d[9]), "=f"(d[10]), "=f"(d[11]), "=f"(d[12]), "=f"(d[13]), "=f"(d[14]), "=f"(d[15]), "=f"(d[16]), "=f"(d[17]), "=f"(d[18]), "=f"(d[19]), "=f"(d[20]), "=f"(d[21]), "=f"(d[22]), "=f"(d[23]), "=f"(d[24]), "=f"(d[25]), "=f"(d[26]), "=f"(d[27]), "=f"(d[28]), "=f"(d[29]), "=f"(d[30]), "=f"(d[31])
               : "r"(a[0]), "r"(a[1]), "r"(a[2]), "r"(a[3]), "r"(dlo), "r"(dhi), "n"(TB));
}
template <int TB> __device__ __forceinline__ void wgmma32_init(float* d, const uint32_t* a, uint32_t dlo, uint32_t dhi) {
  asm volatile("{ .reg .b64 dd; mov.b64 dd, {%20, %21}; wgmma.mma_async.sync.aligned.m64n32k16.f32.f16.f16 "
               "{%0,%1,%2,%3,%4,%5,%6,%7,%8,%9,%10,%11,%12,%13,%14,%15}, {%16,%17,%18,%19}, dd, 0, 1, 1, %22; }"
               : "=f"(d[0]), "=f"(d[1]), "=f"(d[2]), "=f"(d[3]), "=f"(d[4]), "=f"(d[5]), "=f"(d[6]), "=f"(d[7]), "=f"(d[8]), "=f"(d[9]), "=f"(d[10]), "=f"(d[11]), "=f"(d[12]), "=f"(d[13]), "=f"(d[14]), "=f"(d[15])
               : "r"(a[0]), "r"(a[1]), "r"(a[2]), "r"(a[3]), "r"(dlo), "r"(dhi), "n"(TB));
}
__device__ __forceinline__ void wgmma64h(uint32_t* d, uint32_t a0, uint32_t a1, uint32_t a2, uint32_t a3, uint32_t dlo, uint32_t dhi) {
  asm volatile("{ .reg .b64 dd; mov.b64 dd, {%20, %21}; wgmma.mma_async.sync.aligned.m64n64k16.f16.f16.f16 "
               "{%0,%1,%2,%3,%4,%5,%6,%7,%8,%9,%10,%11,%12,%13,%14,%15}, {%16,%17,%18,%19}, dd, 1, 1, 1, 0; }"
               : "+r"(d[0]), "+r"(d[1]), "+r"(d[2]), "+r"(d[3]), "+r"(d[4]), "+r"(d[5]), "+r"(d[6]), "+r"(d[7]), "+r"(d[8]), "+r"(d[9]), "+r"(d[10]), "+r"(d[11]), "+r"(d[12]), "+r"(d[13]), "+r"(d[14]), "+r"(d[15])
               : "r"(a0), "r"(a1), "r"(a2), "r"(a3), "r"(dlo), "r"(dhi));
}
__device__ __forceinline__ void wgmma64h_init(uint32_t* d, uint32_t a0, uint32_t a1, uint32_t a2, uint32_t a3, uint32_t dlo, uint32_t dhi) {
  asm volatile("{ .reg .b64 dd; mov.b64 dd, {%20, %21}; wgmma.mma_async.sync.aligned.m64n64k16.f16.f16.f16 "
               "{%0,%1,%2,%3,%4,%5,%6,%7,%8,%9,%10,%11,%12,%13,%14,%15}, {%16,%17,%18,%19}, dd, 0, 1, 1, 0; }"
               : "=r"(d[0]), "=r"(d[1]), "=r"(d[2]), "=r"(d[3]), "=r"(d[4]), "=r"(d[5]), "=r"(d[6]), "=r"(d[7]), "=r"(d[8]), "=r"(d[9]), "=r"(d[10]), "=r"(d[11]), "=r"(d[12]), "=r"(d[13]), "=r"(d[14]), "=r"(d[15])
               : "r"(a0), "r"(a1), "r"(a2), "r"(a3), "r"(dlo), "r"(dhi));
}
__device__ __forceinline__ void wgmma40_ss(float* d, uint32_t alo, uint32_t blo, uint32_t hi) {
  asm volatile("{ .reg .b64 da, db; mov.b64 da, {%20, %22}; mov.b64 db, {%21, %22}; "
               "wgmma.mma_async.sync.aligned.m64n40k16.f32.f16.f16 {%0,%1,%2,%3,%4,%5,%6,%7,%8,%9,%10,%11,%12,%13,%14,%15,%16,%17,%18,%19}, da, db, 1, 1, 1, 1, 1; }"
               : "+f"(d[0]), "+f"(d[1]), "+f"(d[2]), "+f"(d[3]), "+f"(d[4]), "+f"(d[5]), "+f"(d[6]), "+f"(d[7]), "+f"(d[8]), "+f"(d[9]), "+f"(d[10]), "+f"(d[11]), "+f"(d[12]), "+f"(d[13]), "+f"(d[14]), "+f"(d[15]), "+f"(d[16]), "+f"(d[17]), "+f"(d[18]), "+f"(d[19])
               : "r"(alo), "r"(blo), "r"(hi));
}
__device__ __forceinline__ void wgmma40_ss_init(float* d, uint32_t alo, uint32_t blo, uint32_t hi) {
  asm volatile("{ .reg .b64 da, db; mov.b64 da, {%20, %22}; mov.b64 db, {%21, %22}; "
               "wgmma.mma_async.sync.aligned.m64n40k16.f32.f16.f16 {%0,%1,%2,%3,%4,%5,%6,%7,%8,%9,%10,%11,%12,%13,%14,%15,%16,%17,%18,%19}, da, db, 0, 1, 1, 1, 1; }"
               : "=f"(d[0]), "=f"(d[1]), "=f"(d[2]), "=f"(d[3]), "=f"(d[4]), "=f"(d[5]), "=f"(d[6]), "=f"(d[7]), "=f"(d[8]), "=f"(d[9]), "=f"(d[10]), "=f"(d[11]), "=f"(d[12]), "=f"(d[13]), "=f"(d[14]), "=f"(d[15]), "=f"(d[16]), "=f"(d[17]), "=f"(d[18]), "=f"(d[19])
               : "r"(alo), "r"(blo), "r"(hi));
}
__device__ __forceinline__ float vzero() { float v; asm volatile("mov.b32 %0, 0;" : "=f"(v)); return v; }
__device__ __forceinline__ void tma_box(uint32_t dst, const CUtensorMap* tm, uint32_t mb, int x, int y) {
  asm volatile("cp.async.bulk.tensor.2d.shared::cluster.global.mbarrier::complete_tx::bytes [%0], [%1, {%3, %4}], [%2];"
               :: "r"(dst), "l"(tm), "r"(mb), "r"(x), "r"(y) : "memory");
}
__device__ __forceinline__ void l2_prefetch(const void* src, uint32_t bytes) {
  asm volatile("cp.async.bulk.prefetch.L2.global [%0], %1;" :: "l"(src), "r"(bytes) : "memory");
}
__device__ __forceinline__ uint32_t uni(uint32_t v) {
  uint32_t r; asm volatile("shfl.sync.idx.b32 %0, %1, 0, 0x1f, 0xffffffff;" : "=r"(r) : "r"(v)); return r;
}
__device__ __forceinline__ uint32_t pin(uint32_t v) {
  uint32_t r; asm volatile("shfl.sync.bfly.b32 %0, %1, 0, 0x1f, 0xffffffff;" : "=r"(r) : "r"(v)); return r;
}
__device__ __forceinline__ int fresh_tid() { int v; asm volatile("mov.u32 %0, %tid.x;" : "=r"(v)); return v; }

struct Params {
  const unsigned char* x;
  Scratch* s;
  int off[8];
  uint32_t* out;
  const uint16_t* dskip;
  const uint32_t* w_r;
  long long* ts;
  const unsigned char* far[7];
  uint32_t sched[2][17];
};
__device__ __forceinline__ uint32_t ldnc32(const void* p) { uint32_t v; asm volatile("ld.global.nc.b32 %0, [%1];" : "=r"(v) : "l"(p)); return v; }
__device__ __forceinline__ uint32_t ldnc16(const void* p) { uint16_t v; asm volatile("ld.global.nc.u16 %0, [%1];" : "=h"(v) : "l"(p)); return v; }
__device__ __forceinline__ uint4 ldnc128(const void* p) { uint4 v; asm volatile("ld.global.nc.v4.b32 {%0,%1,%2,%3}, [%4];" : "=r"(v.x), "=r"(v.y), "=r"(v.z), "=r"(v.w) : "l"(p)); return v; }
__device__ __forceinline__ void mbar_wait(uint32_t mb, uint32_t ph = 0) {
#pragma unroll 1
  for (int it = 0; it < SPIN_MAX; it++) {
    uint32_t ok;
    asm volatile("{ .reg .pred q; mbarrier.try_wait.parity.shared::cta.b64 q, [%1], %2; selp.u32 %0, 1, 0, q; }" : "=r"(ok) : "r"(mb), "r"(ph) : "memory");
    if (ok) break;
  }
}
__device__ __forceinline__ uint32_t mbar_test(uint32_t mb) {
  uint32_t ok;
  asm volatile("{ .reg .pred q; mbarrier.test_wait.parity.shared::cta.b64 q, [%1], 0; selp.u32 %0, 1, 0, q; }" : "=r"(ok) : "r"(mb) : "memory");
  return ok;
}
__device__ __forceinline__ void mbar_arrive(uint32_t mb) { asm volatile("mbarrier.arrive.shared::cta.b64 _, [%0];" :: "r"(mb) : "memory"); }
__device__ __forceinline__ uint32_t ldg16(const void* p) { uint16_t v; asm volatile("ld.global.u16 %0, [%1];" : "=h"(v) : "l"(p) : "memory"); return v; }
__device__ __forceinline__ uint32_t ldr16(const void* p) { uint16_t v; asm volatile("ld.relaxed.gpu.global.u16 %0, [%1];" : "=h"(v) : "l"(p) : "memory"); return v; }
__device__ __forceinline__ void fence_async() { asm volatile("fence.proxy.async.shared::cta;" ::: "memory"); }
#define SPIN_WHILE(cond, body) _Pragma("unroll 1") for (int _it = 0; _it < SPIN_MAX && __any_sync(0xffffffffu, (cond)); _it++) { body; }

struct LnC { uint32_t m2, rh2, rl2; };
__device__ __forceinline__ float diag_sum(float d0, float d1, int t) {
  float q = __shfl_sync(0xffffffffu, d0, 9 * t) + __shfl_sync(0xffffffffu, d1, 9 * t + 4);
  q += __shfl_xor_sync(0xffffffffu, q, 1);
  return q + __shfl_xor_sync(0xffffffffu, q, 2);
}
__device__ __forceinline__ LnC ln_consts(float s, float q, float& r) {
  const float mean = s * (1.f / DM);
  const float var = fmaxf(fmaf(-mean, mean, q * (1.f / DM)), 0.f);
  float sd;
  asm("sqrt.approx.ftz.f32 %0, %1;" : "=f"(sd) : "f"(bfr(bfr(var) + 1e-5f)));
  asm("rcp.approx.ftz.f32 %0, %1;" : "=f"(r) : "f"(bfr(sd)));
  LnC c;
  c.m2 = pack_bf(mean, mean);
  c.rh2 = pack_bf(r, r);
  const float rl = r - bf_lo(c.rh2);
  c.rl2 = pack_bf(rl, rl);
  return c;
}
__device__ __forceinline__ float quad_sum(float s) { s += __shfl_xor_sync(0xffffffffu, s, 1); return s + __shfl_xor_sync(0xffffffffu, s, 2); }
__device__ __forceinline__ uint32_t bf_fma2(uint32_t a, uint32_t b, uint32_t c) {
  __nv_bfloat162 r = __hfma2(*(const __nv_bfloat162*)&a, *(const __nv_bfloat162*)&b, *(const __nv_bfloat162*)&c);
  return *(uint32_t*)&r;
}
__device__ __forceinline__ uint32_t ln_apply(uint32_t w, uint32_t m2, uint32_t rh2, uint32_t rl2) {
  const uint32_t d = bf_sub2(w, m2);
  return bf_fma2(d, rh2, bf_mul2(d, rl2));
}

__device__ __forceinline__ float2 cis(float mag_log2, float rev) {
  const float m = ex2(mag_log2), ang = rev * 6.283185307179586f;
  return make_float2(m * __cosf(ang), m * __sinf(ang));
}
__device__ __forceinline__ float2 csq(float2 a) { return make_float2(fmaf(a.x, a.x, -a.y * a.y), (a.x + a.x) * a.y); }
__device__ __forceinline__ float2 cmul(float2 a, float2 b) { return make_float2(fmaf(a.x, b.x, -a.y * b.y), fmaf(a.x, b.y, a.y * b.x)); }
__device__ __forceinline__ void pmul(uint32_t xr, uint32_t xi, uint32_t w, uint32_t& yr, uint32_t& yi) {
  const __half2 XR = *(__half2*)&xr, XI = *(__half2*)&xi, W = *(__half2*)&w;
  const __half2 a = __hfma2(__hneg2(XI), __high2half2(W), __hmul2(XR, __low2half2(W)));
  const __half2 b = __hfma2(XI, __low2half2(W), __hmul2(XR, __high2half2(W)));
  yr = *(const uint32_t*)&a; yi = *(const uint32_t*)&b;
}
__device__ __forceinline__ uint32_t pk(float2 a) { return pack_h(a.x, a.y); }

struct KgState { float2 c0, z8; float kl; uint32_t w64, w128, w192; };
__device__ __forceinline__ void kgen_tables_n(const uint32_t (&raw)[7], uint32_t scr, int wt, KgState& k) {
  const uint32_t dst = scr + 16384 + wt * 16;
  const float dt = bfr(ex2(bf_lo(raw[6]) * 1.4426950408889634f));
  const float th = dt * bf_lo(raw[1]);
  const float br = dt * bf_lo(raw[2]), bi = dt * bf_lo(raw[3]);
  const float Cr = bf_lo(raw[4]), Ci = bf_lo(raw[5]);
  k.c0 = make_float2(fmaf(Cr, br, -Ci * bi), fmaf(Cr, bi, Ci * br));
  const uint32_t mx = __reduce_max_sync(0xffffffffu, __float_as_uint(fmaxf(fabsf(k.c0.x), fabsf(k.c0.y))));
  const float a2 = dt * bf_lo(raw[0]) * 1.4426950408889634f;
  const float rh = th * 0.15915494309189535f;
  const float rl = fmaf(th, (float)(0.15915494309189535 - (double)0.15915494309189535f), fmaf(th, 0.15915494309189535f, -rh));
  const float rf = rh - rintf(rh);
  const float2 z1 = cis(a2, rf + rl);
  const float p64 = rf * 64.f;
  const float2 z64 = cis(a2 * 64.f, fmaf(64.f, rl, p64 - rintf(p64)));
  const float2 z2 = csq(z1), z128 = csq(z64), z3 = cmul(z2, z1), z4 = csq(z2), z256 = csq(z128), z6 = csq(z3), z512 = csq(z256);
  k.z8 = csq(z4);
  k.w64 = pk(z64); k.w128 = pk(z128); k.w192 = pk(cmul(z128, z64));
  sts128(dst, 0x00003C00u, pk(z2), pk(z4), pk(z6));
  const float2 z1024 = csq(z512), z768 = cmul(z512, z256);
  sts128(dst + 2048, pk(z1), pk(z3), pk(cmul(z4, z1)), pk(cmul(z4, z3)));
  const float2 z2048 = csq(z1024);
  k.kl = fmaf(k.c0.x, z2048.x, -k.c0.y * z2048.y);
  sts128(dst + 4096, pk(z256), pk(cmul(z256, z2)), pk(cmul(z256, z4)), pk(cmul(z256, z6)));
  sts128(dst + 6144, pk(z512), pk(cmul(z512, z4)), pk(z768), pk(cmul(z768, z4)));
  sts128(dst + 8192, pk(z1024), pk(cmul(z1024, z256)), pk(cmul(z1024, z512)), pk(cmul(z1024, z768)));
  sts32(scr + W_MISC + (wt >> 5) * 4, mx);
}
__device__ __forceinline__ int kgen_tables_m(uint32_t scr, int wt, const KgState& k) {
  const uint32_t dst = scr + wt * 16;
  const uint4 e4 = lds128(scr + W_MISC);
  const float2 z16 = csq(k.z8), z32 = csq(z16);
  const int em = max(min((int)(max(max(e4.x, e4.y), max(e4.z, e4.w)) >> 23), 238), 16);
  const float sc = __uint_as_float((uint32_t)(127 + 4 + 127 - em) << 23);
  sts32(scr + W_MISC + 16 + (wt >> 5) * 4, __reduce_add_sync(0xffffffffu, __float2int_rn(k.kl * sc * 262144.f)));
  const float2 c0 = make_float2(k.c0.x * sc, k.c0.y * sc);
  const float2 c1 = cmul(c0, k.z8), c2 = cmul(c0, z16), c4 = cmul(c0, z32), c3 = cmul(c1, z16), c5 = cmul(c1, z32), c6 = cmul(c2, z32), c7 = cmul(c3, z32);
  uint32_t pr[4], pi[4], yr[4], yi[4];
  pr[0] = pack_h(c0.x, c1.x); pi[0] = pack_h(c0.y, c1.y);
  pr[1] = pack_h(c2.x, c3.x); pi[1] = pack_h(c2.y, c3.y);
  pr[2] = pack_h(c4.x, c5.x); pi[2] = pack_h(c4.y, c5.y);
  pr[3] = pack_h(c6.x, c7.x); pi[3] = pack_h(c6.y, c7.y);
  sts128(dst, pr[0], pr[1], pr[2], pr[3]); sts128(dst + 2048, pi[0], pi[1], pi[2], pi[3]);
#pragma unroll
  for (int q = 1; q < 4; q++) {
    const uint32_t w = q == 1 ? k.w64 : q == 2 ? k.w128 : k.w192;
#pragma unroll
    for (int i = 0; i < 4; i++) pmul(pr[i], pi[i], w, yr[i], yi[i]);
    sts128(dst + q * 4096, yr[0], yr[1], yr[2], yr[3]); sts128(dst + q * 4096 + 2048, yi[0], yi[1], yi[2], yi[3]);
  }
  return em;
}
__device__ __forceinline__ void kgen_build(uint32_t tb, int wg, int wt, uint32_t k0, uint32_t k1, uint32_t k2) {
  const uint32_t kt = tb + W_KT, sc = tb + W_L3 + 3072;
  const int ix = ((wt >> 2) + (wt & 3) * 32 - 1) & 127;
  const uint32_t a3 = tb + W_CW + 32 + ((ix & 1) ? 0 : 304) + (ix >> 1) * 4;
  const uint32_t v3 = wt ? k2 : k2 >> 16;
  sts32(sc + 4 + wt * 4, __byte_perm(k0, k1, 0x5432));
  sts16(sc + 544 + (wt & ~3) + (wt & 1) * 2 + (wt & 2) * 64, k1 >> 16);
  sts16(a3, v3); sts16(a3 + 6, v3);
  if ((unsigned)(wt - 32) < 18u) sts128(kt + (wt < 36 ? -512 : 64 + 4128 - 576) + wt * 16, 0, 0, 0, 0);
  if (wt == 127) sts32(sc, k0 & 0xFFFF0000u);
  if (wt == 0) { sts32(sc + 516, k1); sts16(sc + 800, k2); }
  bar_sync(1 + wg, 128);
  const uint32_t cw = tb + W_CW + 32 + (wt >> 6) * 48 + wt * 4;
  const uint32_t pv = lds32(sc + wt * 4), nx = lds32(sc + 8 + wt * 4), c2 = lds16(sc + 544 + wt * 2), n2 = lds16(sc + 546 + wt * 2);
  sts128(tb + W_L3 + 512 + (wt >> 6) * 512 + wt * 16, lds32(cw), lds32(cw - 8), lds32(cw - 16), lds32(cw - 24));
  const bool odd = wt & 1;
  sts64(kt + 64 + wt * 8, __byte_perm(k0, pv, 0x5410), __byte_perm(k0, 0, 0x1032));
  sts64(kt + 64 + 1024 + wt * 8, __byte_perm(k1, pv, (odd || wt == 0) ? 0x7610 : 0x1010), __byte_perm(k1, nx, odd ? 0x1076 : 0x1010));
  const uint32_t cc = c2 * 0x10001u, nc = __byte_perm(n2, c2, 0x5410), nn = n2 * 0x10001u;
  sts128(kt + 64 + 2048 + wt * 16, cc, cc, odd ? nc : cc, odd ? nn : nc);
  if (wt == 127) { sts128(kt + 64 + 4096, nn, nn, nn, nn); sts128(kt + 64 + 4112, nn, nn << 16, 0, 0); }
}

__device__ __forceinline__ void load_a(uint32_t (&a)[4], uint32_t kp, int j) {
  a[0] = lds32(kp + 64 * j); a[1] = lds32(kp + 64 * j + 512); a[2] = lds32(kp + 64 * j - 32); a[3] = lds32(kp + 64 * j + 480);
}
__device__ __forceinline__ uint32_t band(int d, int lo, int hi) {
  return ((unsigned)(d - lo) <= (unsigned)(hi - lo) ? 1u : 0u) | ((unsigned)(d - 1 - lo) <= (unsigned)(hi - lo) ? 0x10000u : 0u);
}
__device__ __forceinline__ uint32_t hadd2u(uint32_t a, uint32_t b) { __half2 r = __hadd2(*(__half2*)&a, *(__half2*)&b); return *(uint32_t*)&r; }

__device__ __forceinline__ void zero_pads(uint32_t tb, int wt) {
  if (!(wt & 32)) sts128(tb + W_L3 + (wt >> 6) * 512 + wt * 16, 0, 0, 0, 0);
  if ((wt & 63) < 3) sts128(tb + W_CW + (wt >> 6) * 304 + (wt & 63) * 16, 0, 0, 0, 0);
}
__device__ __forceinline__ uint32_t tr_base(int lane) {
  return OFF_YT + (2 * (lane >> 3) + (lane & 1)) * YT_PITCH + ((lane >> 1) & 1) * (8 * YT_PITCH + 64) + ((lane >> 2) & 1) * 16;
}

__device__ __forceinline__ uint32_t sc_addr(int tp) { return OFF_YT + (tp < 16 ? tp * YT_PITCH + (tp >> 3) * 64 + 1152 : 8 * YT_PITCH - 512 + tp * 32); }
#define X_PS 1
#define X_PW 15
#define X_HU 16
#define X_HB 0
#define X_REL 1
#define X_PAD0 0
#define X_PAD1 0
#define PAD(n) _Pragma("unroll") for (int _i = 0; _i < (n); _i++) asm volatile("pmevent 0;");
#ifndef M_
#define M_ 12
#endif
#define X_ES 1
#define X_NE 2
#define X_SCT 10000
#define X_DELTA 0
#define X_DSTEP 2000
#define X_PF0 2500
#define X_PFD 600
#define X_TD 450
#define X_WS 6
#define X_OR 8
#define X_ABS 4800
#define X_XD 200
#define X_RD 600
#define X_HD 400
#define X_PD 1080
#define X_PROMO 2
#define X_YD2 1000
#define X_GO 2
#define X_GW 2
#define X_NS 4400
#define X_XS 13600
#define X_LAG 1500
#define X_YD 1550
struct TMaps { CUtensorMap m[10]; };
__device__ __forceinline__ uint32_t h2bf(uint32_t w) { const float2 f = h2f(w); return pack_bf(f.x, f.y); }
__device__ __forceinline__ uint32_t keep(uint32_t v) { asm volatile("" : "+r"(v)); return v; }
__device__ __forceinline__ uint2 ldr64(const void* p) { uint2 v; asm volatile("{ .reg .b64 t; ld.relaxed.gpu.global.b64 t, [%2]; mov.b64 {%0, %1}, t; }" : "=r"(v.x), "=r"(v.y) : "l"(p) : "memory"); return v; }
__host__ __device__ __forceinline__ uint32_t down_box(int s, bool five) {
  return five ? OFF_W + W_BYTES + 12288 + (s / 3) * (W_BYTES - 12288) + s * 4096 : s < 6 ? OFF_W + W_BYTES + BOX + (s >> 1) * (W_BYTES - 10240) + s * 5120 : OFF_W + (s - 6) * 5120;
}
__device__ __forceinline__ void load_tile(const CUtensorMap* tmx, int i, int c, int again = 0) {
  asm volatile("mbarrier.arrive.expect_tx.shared::cta.b64 _, [%0], 8704;" :: "r"(MB_UL + i * 16 + again) : "memory");
  asm volatile("cp.async.bulk.tensor.3d.shared::cluster.global.mbarrier::complete_tx::bytes [%0], [%1, {%3, %4, %5}], [%2];"
               :: "r"(i < 2 ? OFF_T + i * TILE : OFF_W), "l"(tmx), "r"(MB_UL + i * 16 + again), "r"(0), "r"(c), "r"(-8) : "memory");
}
template <bool FAR> __device__ __forceinline__ void load_params(const Params& p, uint32_t ch, int wt, uint32_t dst, bool on) {
  const int rel = wt < 96 ? ch * 16 + (wt & 15) : ch >> 3;
  const unsigned char* b = FAR ? p.far[min(wt >> 4, 6)] + rel * 16 : p.x + (long long)(p.off[wt >> 4] + rel) * 16;
  asm volatile("{ .reg .pred q; setp.ne.u32 q, %2, 0; @q cp.async.cg.shared.global [%0], [%1], 16; }"
               :: "r"(dst + wt * 16), "l"(b), "r"((uint32_t)(on && wt < 97)) : "memory");
}

struct ConvC { uint32_t ca, cb, bands; };
__device__ __forceinline__ ConvC conv_consts(int w, int lane) {
  const int h = w & 1, P = (w >> 1) & 1, d0 = 8 * h + (lane >> 2) - 2 * (lane & 3);
  ConvC k;
  k.ca = keep((W_KT + (16 + 256 * P + d0) * 4) | (((8 + 64 * P + lane) * 64 + (((h + ((w >> 1) & 2)) ^ (lane >> 1)) & 3) * 16) << 16));
  k.cb = keep(lane < 8 ? 0xFFFEFFFEu : ~0u);
  k.bands = keep(band(d0, 12, 20) + 2 * band(d0 + 8, 12, 20) + 4 * band(d0 + 16, 12, 20) + 8 * band(d0 + 24, 12, 20)
                 + 16 * band(d0 - 8, 5, 11) + 32 * band(d0, 5, 11) + 64 * band(d0 + 8, 5, 11) + 128 * band(d0 + 16, 5, 11));
  return k;
}
struct ConvPre { uint32_t e0, e2, f2, a[3][4]; };
__device__ __forceinline__ uint32_t lds32_if(uint32_t a, bool on) {
  uint32_t v; asm volatile("{ .reg .pred q; setp.ne.u32 q, %2, 0; mov.b32 %0, 0; @q ld.shared.b32 %0, [%1]; }" : "=r"(v) : "r"(a), "r"((uint32_t)on) : "memory"); return v;
}
__device__ __forceinline__ void conv_pre(ConvPre& r, uint32_t kp, int part, bool on, bool P) {
  if (part & 1) { r.e0 = lds32_if(kp + 4096, on && !P); r.e2 = lds32_if(kp + 4064, on && !P); r.f2 = lds32_if(kp + 4128, on && !P); }
#pragma unroll
  for (int j = 0; j < 3; j++) if (part & (j < X_PS ? 1 : 2)) {
    r.a[j][0] = lds32_if(kp + 2048 + 64 * j, on); r.a[j][1] = lds32_if(kp + 2560 + 64 * j, on); r.a[j][2] = lds32_if(kp + 2016 + 64 * j, on); r.a[j][3] = lds32_if(kp + 2528 + 64 * j, on);
  }
}
__device__ __forceinline__ void conv_item(uint32_t tb, uint32_t tl, int bid, int bn, ConvPre& pre, const ConvC& cv, uint32_t zero, const CUtensorMap* tmx, int ch, int warp, int lane, bool hold, bool more) {
  const bool go = more && warp == 0 && lane == 0;
  const uint32_t kp = tb + (cv.ca & 0xFFFFu);
  const uint32_t dlo = (tl >> 4) + 32 + ((warp >> 1) & 2) + (1u << 16), dhi = 32u | (2u << 30);
  const bool P = warp & 2;
  float a32[16], b32[16], a64[32];
  uint32_t A[40][4];
#define STEP(J) { wgmma64<0>(a64, A[J], dlo + 256 - 4 * (J), dhi); \
    if ((J) == 32) wgmma32_init<0>(b32, A[J], dlo, dhi); else wgmma32<0>(b32, A[J], ((J) < 8 ? dlo ^ zero : dlo) + 128 - 4 * (J), dhi); \
    if ((J) == 0) wgmma32_init<0>(a32, A[J], dlo, dhi); else if ((J) < 8) wgmma32<0>(a32, A[J], (dlo ^ zero) - 4 * (J), dhi); }
#define LD(J) load_a(A[J], kp, J);
#define FIRST(J) wg_fence(); STEP(J) wg_commit(); wg_wait<1>(); wg_fence();
  {
    uint32_t win[16], x9[4], x7[4], e[4], f[4];
    const uint32_t bz = keep(cv.bands);
#define BAND(i) keep((bz & (0x10001u << (i))) * (0x3C00u >> (i)))
    e[0] = pre.e0; e[2] = pre.e2; e[1] = keep(bz & 0x100u); e[3] = keep(bz & 0x200u);
    f[2] = pre.f2; f[0] = keep(bz & 0x4000u); f[1] = keep(bz & 0x8000u); f[3] = keep(bz & 0x300u);
#pragma unroll
    for (int j = 0; j < 12; j++) A[32 + j / 4][j & 3] = pre.a[j / 4][j & 3];
    const uint32_t q[12] = {BAND(0), BAND(5), keep(bz & 0x400u), BAND(4), BAND(2), BAND(7), BAND(1), BAND(6), keep(bz & 0x800u), keep(bz & 0x1000u), BAND(3), keep(bz & 0x2000u)};
#undef BAND
    const uint32_t ta = keep(tl + 512 + (warp & 3) * 2048 + lane * 64 + (lane & 6) * 8);
    if (X_GO && hold) mbar_wait(MB_GO);
    uint32_t mbl = MB_UL + (warp & 8) * 2, ph = 0;
#pragma unroll 1
    for (int it = 0; it < SPIN_MAX; it++) {
      if (ch < 512) mbar_wait(mbl, ph);
      if (it == 1) TS(13);
      TS(3);
      wg_fence();
      wgmma64h_init(win, q[0], q[1], q[2], q[3], dlo, dhi);
      wgmma64h(win, q[4], q[5], q[6], q[7], dlo - 4, dhi);
      wgmma64h(win, q[8], q[9], q[10], q[11], dlo - 8, dhi);
      wg_commit();
      wgmma64_init<0>(a64, e, dlo, dhi);
      wgmma64<0>(a64, f, dlo - 4, dhi);
      wg_commit();
      if (ch >= 512) break;
      uint32_t r0, r1, r2, r3, ok;
      if (warp & 4) {
        mbar_wait(mbl + 8);
        if (__all_sync(0xffffffffu, it || lds32(MISC_RT + (warp & 8)) == 0)) break;
        wg_wait<0>();
        continue;
      }
      ldsm4(ta, r0, r1, r2, r3);
      ok = r0 & r1 & r2 & r3;
      ldsm4(ta ^ 32, r0, r1, r2, r3);
      asm volatile("{ .reg .pred q; setp.ne.u32 q, %1, 0; barrier.red.and.pred q, %2, 128, q; selp.u32 %0, 1, 0, q; }" : "=r"(ok) : "r"((ok & r0 & r1 & r2 & r3 & 1u) | (lane & 3)), "r"(1 + (warp >> 2)) : "memory");
      if (ok) { if ((warp & 3) == 0 && lane == 0) { sts32(MISC_RT + warp, it); mbar_arrive(MB_UL + 8 + warp * 2); } break; }
      wg_wait<0>();
      if ((warp & 3) == 0 && lane == 0) load_tile(tmx - 1, warp >> 3, ch, 56);
      mbl = MB_UL + 56 + (warp & 8) * 2; ph = it & 1;
    }
    wg_wait<1>();
#pragma unroll
    for (int i = 0; i < 4; i++) {
      const int tl = 2 * ((i & 1) + ((i & 2) ? 0 : 4));
      x9[i] = P ? win[tl + 4] : win[tl]; x7[i] = P ? win[tl + 5] : win[tl + 1];
    }
    const uint32_t l3lo = ((tb + W_L3) >> 4) + (32u << 16);
    wg_fence();
    wgmma64<0>(a64, x9, l3lo, 8);
    wgmma64<0>(a64, x7, l3lo + 96, 8);
    wg_commit();
  }
  STEP(32) STEP(33) STEP(34) wg_commit(); wg_wait<1>();
  LD(35) LD(36) LD(37) LD(38)
  FIRST(35) STEP(36) STEP(37) STEP(38) wg_commit();
  LD(39) LD(0)
  TS(17);
  if (X_GO == 1 && go) mbar_arrive(MB_GO);
  FIRST(39) STEP(0) wg_commit();
  LD(1) LD(2) LD(3)
  FIRST(1) STEP(2) STEP(3) wg_commit();
  LD(4) LD(5)
  if (X_GO == 2 && go) mbar_arrive(MB_GO);
  FIRST(4) STEP(5) wg_commit();
  LD(6) LD(7)
  wg_fence(); STEP(6) STEP(7) wg_commit();
#undef STEP
#undef LD
#undef FIRST
  TS(18);
  if (X_GO == 3 && go) mbar_arrive(MB_GO);
  const uint32_t xc = tb + W_KT + (warp & 3) * 1024 + lane * 16;
  if (more) bar_sync(7, 288);
  wg_wait<1>();
  conv_pre(pre, kp + ALT, 1, more, P);
  wg_wait<0>();
  conv_pre(pre, kp + ALT, 2, more, P);
  uint32_t E[16], o[8];
#define ACC(i) ((i) < 16 ? a32[i] : (i) < 32 ? b32[(i) - 16] : a64[(i) - 32])
  E[0] = pack_h(a32[0], a32[1]);
#pragma unroll
  for (int i = 1; i < 16; i++) E[i] = pack_h(ACC(4 * i) + ACC(4 * i - 2), ACC(4 * i + 1) + ACC(4 * i - 1));
#undef ACC
#pragma unroll
  for (int j = 0; j < 8; j++) o[j] = P ? (j < 2 ? 0u : E[j - 2]) : E[8 + j];
  sts128(xc, o[0], o[1], o[2], o[3]); sts128(xc + 512, o[4], o[5], o[6], o[7]);
#pragma unroll
  for (int j = 0; j < 8; j++) o[j] = P ? E[6 + j] : E[j];
  TS(25);
  if (more) {
    sts128(xc + 4096, o[0], o[1], o[2], o[3]); sts128(xc + 4608, o[4], o[5], o[6], o[7]);
    bar_arrive(12, 192);
    return;
  }
  bar_sync(1 + (warp >> 2), 128);
  const uint4 vv[2] = {lds128(xc + (P ? -2048 : 2048)), lds128(xc + (P ? -1536 : 2560))};
#pragma unroll
  for (int q = 0; q < 2; q++) {
    const uint4 v = vv[q];
    stsm4t(tl + (cv.ca >> 16) + q * 2048, hadd2u(o[4 * q], v.x) & cv.cb, hadd2u(o[4 * q + 1], v.y) & cv.cb, hadd2u(o[4 * q + 2], v.z) & cv.cb, hadd2u(o[4 * q + 3], v.w) & cv.cb);
  }
  fence_async();
  bar_sync(bid, bn);
  if (warp == 0 && lane == 0) mbar_arrive(MB_REL);
  if ((warp & 7) == (ch < 512 ? 7 : 3) && lane == 0) {
    asm volatile("cp.async.bulk.tensor.3d.global.shared::cta.bulk_group [%0, {%3, %2, %3}], [%1];" :: "l"(tmx), "r"(tl + 512), "r"(ch), "r"(0) : "memory");
    asm volatile("cp.async.bulk.commit_group;" ::: "memory");
  }
}

template <bool FAR> __global__ void __launch_bounds__(NT, 1)
fused_kernel(const __grid_constant__ Params p, const __grid_constant__ TMaps tm) {
  extern __shared__ __align__(1024) unsigned char smem[];
  const int c = blockIdx.x;
  const bool five = (c & 1) == 0;
  const uint32_t pitch = five ? 64 : 80;
  const uint32_t ones = 0x3F803F80u;
  const int tid = threadIdx.x, lane = tid & 31;
  const uint32_t xrow = OFF_YT + ((tid & 127) >> 3) * YT_PITCH + (tid & 64) + (tid & 7) * 16;
  {
    const int w4 = tid >> 7;
    load_params<FAR>(p, w4 < 2 ? 2 * c + w4 : five ? 257 + 2 * c : 512 + (c >> 1), tid & 127, OFF_W + W_KT + (w4 < 2 ? w4 * W_BYTES : five ? 3 * W_BYTES : 3 * W_BYTES + 2048), (0xB >> w4) & 1);
  }
  if ((tid >> 7) == 2) {
    const unsigned char* xp = p.x + (uint32_t)((c * 16 - 32 + (tid >> 3)) * 1152 + (tid & 7) * 16);
    asm volatile("" : "+l"(xp));
    { const uint32_t tq = clock(); while ((int)(clock() - tq) < X_XD) {} }
#pragma unroll
    for (int k = 0; k < 9; k++) asm volatile("cp.async.cg.shared.global [%0], [%1], 16;" :: "r"(xrow + k * 128), "l"(xp + k * 128) : "memory");
  }
  const int warp = (int)uni(tid >> 5), wg = warp >> 2;
  TS(0);
  if (__builtin_expect(wg == 4, 0)) {
    asm volatile("setmaxnreg.dec.sync.aligned.u32 32;");
    const int role = warp;
    const int u0 = (c >> 1) * 9 + (five ? ((c & 2) ? 5 : 0) : ((c & 2) ? 0 : 4));
    const uint32_t t0 = clock() + c * 4;
    if (role == 16) {
      if (lane < 19) asm volatile("mbarrier.init.shared::cta.b64 [%0], %1;" :: "r"(OFF_MISC + lane * 8), "r"((unsigned)(lane - 2) < 4u ? 4 : 1) : "memory");
      if (lane < 2) asm volatile("mbarrier.arrive.expect_tx.shared::cta.b64 _, [%0], %1;" :: "r"(OFF_MISC + lane * 8), "r"(lane ? (five ? 36864 : 51200) : pitch * 1152) : "memory");
      fence_async();
      bar_arrive(5, 608);
      const CUtensorMap* tmb = &tm.m[five ? 3 : 0];
#pragma unroll 1
      for (int u = 0; u < 17; u++) {
        const uint32_t e = p.sched[five][u], kind = e & 3, s = (e >> 2) & 15, dst = e >> 14;
        if (kind == 3) continue;
        while ((int)(clock() - t0) < X_PF0 + (u < X_NE ? u * X_PFD : X_LAG + u * X_TD)) __nanosleep(20);
        if (e & 0x3FC0) mbar_wait(OFF_MISC + ((e >> 6) & 255));
        if (lane == 0) {
          if (kind == 2) asm volatile("cp.async.bulk.tensor.3d.shared::cluster.global.mbarrier::complete_tx::bytes [%0], [%1, {%3, %4, %5}], [%2];"
                                      :: "r"(dst), "l"(tmb + 2), "r"(MB_D), "r"(0), "r"(u0 * 8), "r"(s) : "memory");
          else tma_box(dst, tmb + kind, MB_GU, u0 * 8, s * 96);
        }
        if (u == 5) TS(2);
        if (u == 10) TS(3);
      }
      TS(4);
      TS_DUMP();
#define FINISH0 bar_sync(12, 192);        \
        _Pragma("unroll 1") for (int w = role & 2; w < (role & 2) + 2; w++) { \
          const uint32_t xa = OFF_W + W_KT + lane * 16, mk = lane < 8 ? 0xFFFEFFFEu : ~0u, ya = OFF_T + (8 + lane) * 64 + (((w & 1) ^ (lane >> 1)) & 3) * 16 + (w & 2) * 2048; \
          const uint4 a = lds128(xa + 4096 + w * 1024), b = lds128(xa + (w ^ 2) * 1024), d = lds128(xa + 4608 + w * 1024), e = lds128(xa + 512 + (w ^ 2) * 1024); \
          stsm4t(ya, hadd2u(a.x, b.x) & mk, hadd2u(a.y, b.y) & mk, hadd2u(a.z, b.z) & mk, hadd2u(a.w, b.w) & mk); \
          stsm4t(ya + 2048, hadd2u(d.x, e.x) & mk, hadd2u(d.y, e.y) & mk, hadd2u(d.z, e.z) & mk, hadd2u(d.w, e.w) & mk); \
        } \
        fence_async();
    } else if (role == 17) {
      if (smem_u32(smem) != SB) __trap();
      bar_sync(10, 576);
      if (lane == 0) {
        fence_async();
        while ((int)(clock() - t0) < X_NS - c * 4) {}
        asm volatile("cp.async.bulk.global.shared::cta.bulk_group [%0], [%1], 10240;" :: "l"(&p.s->X[c * DM * 2 + 512]), "r"(OFF_G) : "memory");
        asm volatile("cp.async.bulk.commit_group;" ::: "memory");
        asm volatile("cp.async.bulk.wait_group 0;" ::: "memory");
      }
      if (lane == 0) mbar_arrive(MB_GF);
      bar_arrive(11, 96);
      if (five) { FINISH0 bar_arrive(13, 192); }
    } else if (role == 18) {
      sts32(MISC_EPOCH, 0);
      sts32(MISC_T0, t0 - c * 4);
      bar_arrive(5, 608);
      uint4* q = lane < 2 ? &p.s->R[c * 2 + lane] : lane < 11 ? &p.s->HS[c * 9 + lane - 2] : lane == 11 ? &p.s->HS[1152 + (c & 7)] : (uint4*)&p.s->FLAG[c * 8];
      if (lane < (c < 8 ? 12 : 11)) str128(q, ~0u, ~0u, ~0u, ~0u);
      const uint32_t ep = __shfl_sync(0xffffffffu, ldr32(q), 31) + 1u;
      sts32(MISC_EPOCH, ep | 0x80000000u);
      TSX(21);
      if (lane == 31) str32(q, ep);
      bar_sync(11, 96);
      TSX(14);
      mbar_wait(MB_KF + (lane & 3) * 8);
      __syncwarp();
      { const uint2 e = lds64(MISC_EM); if (lane < 2) str128(&p.s->SC[c * 2 + lane], e.x, __byte_perm(e.y, ep, 0x6540), 0, 0); }
      TSX(17);
      while ((int)(clock() - t0) < X_SCT) __nanosleep(100);
      TSX(18);
      {
        uint2 v[4];
#pragma unroll 1
        for (int it = 0; it < SPIN_MAX; it++) {
          uint32_t bad = 0;
#pragma unroll
          for (int q = 0; q < 4; q++) v[q] = ldr64(&p.s->SC[lane * 2 + q * 64]);
#pragma unroll
          for (int q = 0; q < 4; q++) bad |= (v[q].y >> 8) ^ (ep & 0xFFFFFFu);
          if (!__any_sync(0xffffffffu, bad)) break;
        }
        TSX(25);
#pragma unroll
        for (int q = 0; q < 4; q++) {
          const uint32_t sa = (lane >> 4) * YT_PITCH + (lane & 15) * 2;
          sts16(sc_addr(2 * q) + sa, v[q].x); sts16(sc_addr(8 + 2 * q) + sa, v[q].x >> 16);
          if (lane & 1) asm volatile("st.shared.u8 [%0], %1;" :: "r"(sc_addr(16) + q * 16 + (lane >> 1)), "r"(v[q].y) : "memory");
        }
      }
      __syncwarp();
      if (lane == 0) mbar_arrive(MB_SC);
      TSX(27);
    } else {
      uint32_t w[9];
      const uint32_t dk = ldnc16(p.dskip + ((lane & 4) ? 512 + (c >> 1) : (lane & 2) * 128 + 2 * c + (lane & 1)));
      float s = 0.f;
#pragma unroll
      for (int i = 0; i < 9; i++) w[i] = ldnc32(p.w_r + lane + 32 * i);
      sts16(OFF_WR + 1152 + lane * 2, dk);
      bar_arrive(5, 608);
#pragma unroll
      for (int i = 0; i < 9; i++) { sts32(OFF_WR + lane * 4 + i * 128, w[i]); s += bf_lo(w[i]) + bf_hi(w[i]); }
      sts32(MISC_SW, __float_as_uint(warp_sum(s)));
      TSX(23);
      bar_sync(10, 576);
      if (lane == 0) {
        const uint32_t tp = clock();
        TSX(1);
        while ((int)(clock() - tp) < X_DELTA || (int)(clock() - t0) < X_ABS - c * 4) {}
        TSX(24);
        load_tile(&tm.m[6], 0, c);
        TSX(15);
        while ((int)(clock() - t0) < X_ABS + X_DSTEP - c * 4) {}
      }
      bar_sync(11, 96);
      if (lane == 0) {
        load_tile(&tm.m[6], 1, 128 + c);
      }
      if (five) {
        mbar_wait(MB_KF);
#pragma unroll 1
        for (int it = 0; it < SPIN_MAX; it++) {
          if (lane == 0) load_tile(&tm.m[8], 2, 512 + (c >> 1));
          mbar_wait(MB_UL + 32, it & 1);
          uint32_t m = 1;
#pragma unroll
          for (int q = 0; q < 4; q++) { uint32_t r0, r1, r2, r3; ldsm4(OFF_W + 512 + lane * 64 + (lane & 6) * 8 + q * 2048, r0, r1, r2, r3); m &= r0 & r1 & r2 & r3; }
          if (__all_sync(0xffffffffu, m || (lane & 3))) break;
        }
        bar_arrive(7, 288);
        FINISH0
        bar_arrive(13, 192);
      }
      bar_sync(0, 544);
      if (lane == 0) mbar_arrive(MB_H);
    }
    return;
  }
  const int wt = tid & 127, g = lane >> 2, t = lane & 3;
  const uint32_t wb = OFF_W + wg * W_BYTES;
  asm volatile("cp.async.commit_group;" ::: "memory");
  const ConvC cv = conv_consts(warp, lane);
  zero_pads(wb, wt);
  load_params<FAR>(p, 254 + 2 * c + wg, wt, wb + W_KT, wg == 2 || (wg == 3 && !five));
  asm volatile("cp.async.commit_group;" ::: "memory");
  asm volatile("setmaxnreg.inc.sync.aligned.u32 112;");
  PAD(X_PAD0)
  {
    uint4 kw;
    uint4* kx = &p.s->KX[(c >> 1) * 128 + wt];
    bool two = wg == 3;
    uint32_t ep;
    int em = 0;
    const uint32_t tr_addr = pin(tr_base(lane) + warp * 32), lca = pin(MISC_LN1 + (t & 1) * 16);
    uint4* dst;
    { const unsigned long long a = (unsigned long long)&p.s->X[c * DM * 2 + warp * 32 + (8 * (t >> 1) + g) * 2 + (t & 1)];
      dst = (uint4*)(((unsigned long long)pin(a >> 32) << 32) | pin((uint32_t)a)); }
    int phase = wg == 2 ? 3 : 2;
#pragma unroll 1
    for (;;) {
      const bool first = two && !five;
      if (phase) asm volatile("cp.async.wait_group 1;" ::: "memory"); else asm volatile("cp.async.wait_group 0;" ::: "memory");
      if (phase == 3) {
        TS(21);
        float d[3][4], r;
        uint4 a[9];
#pragma unroll
        for (int k = 0; k < 9; k++) a[k] = lds128(xrow + k * 128);
#pragma unroll
        for (int i = 0; i < 4; i++) d[0][i] = d[1][i] = d[2][i] = 0.f;
#pragma unroll
        for (int k = 0; k < 9; k++) { mma_bf16(d[(2 * k) % 3], a[k].x, ones, a[k].y, ones, a[k].x, a[k].y); mma_bf16(d[(2 * k + 1) % 3], a[k].z, ones, a[k].w, ones, a[k].z, a[k].w); }
#pragma unroll
        for (int i = 0; i < 4; i++) d[0][i] += d[1][i] + d[2][i];
        const LnC lc = ln_consts(d[0][2] + d[0][3], __shfl_sync(0xffffffffu, d[0][0], 9 * t) + __shfl_sync(0xffffffffu, d[0][1], 9 * t + 4), r);
        if (lane < 12) sts16(MISC_LN1 + g * 32 + (warp & 3) * 8 + t * 2, lane < 4 ? lc.m2 : lane < 8 ? lc.rh2 : lc.rl2);
      } else {
        KgState ks;
        uint32_t raw[7];
        bar_sync(1 + wg, 128);
        TS(22);
#pragma unroll
        for (int i = 0; i < 7; i++) raw[i] = lds16(wb + W_KT + first * 2048 + i * 256 + (i < 6 ? wt : (first ? c >> 1 : 2 * c + (wg & 1)) & 7) * 2);
        kgen_tables_n(raw, wb, wt, ks);
        TS(20);
        bar_sync(1 + wg, 128);
        em = kgen_tables_m(wb, wt, ks);
        fence_async();
      }
      if (phase & 2) {
        TS(23);
        bar_sync(5, 608);
        uint32_t x[3][4];
        ldsm4t(tr_addr, x[0][0], x[0][1], x[0][2], x[0][3]);
        uint4 m = lds128(lca);
        const uint4 rl = lds128(lca + 64), rh = lds128(lca + 32);
        ldsm4t(tr_addr + 512, x[1][0], x[1][1], x[1][2], x[1][3]);
        if (wg == 3) ldsm4t(tr_addr + 640, x[2][0], x[2][1], x[2][2], x[2][3]);
#pragma unroll
        for (int q = 0; q < 3; q++) {
          if (q < 2 || wg == 3) {
            const uint32_t r0 = ln_apply(x[q][0], m.x, rh.x, rl.x), r1 = ln_apply(x[q][1], m.y, rh.y, rl.y), r2 = ln_apply(x[q][2], m.z, rh.z, rl.z), r3 = ln_apply(x[q][3], m.w, rh.w, rl.w);
            const uint32_t w0 = (pack_h(bf_lo(r0), bf_hi(r0)) & 0xFFFEFFFEu) | 1u, w1 = pack_h(bf_lo(r1), bf_hi(r1)), w2 = pack_h(bf_lo(r2), bf_hi(r2)), w3 = pack_h(bf_lo(r3), bf_hi(r3));
            if (q == 0) str128(dst, w0, w1, w2, w3);
            else sts128(OFF_G + warp * 512 + (8 * (t >> 1) + g) * 32 + (t & 1) * 16 + (q == 2 ? 2048 : 0), w0, w1, w2, w3);
          }
          if (q == 0 && X_ES) {
            const uint32_t z = clock() & p.off[7];
            m.x ^= z; m.y ^= z; m.z ^= z; m.w ^= z;
          }
          if (q == 0) TS(30);
        }
        bar_arrive(10, 576);
        TS(1);
      } else bar_sync(1 + wg, 128);
      phase &= 1;
      if (phase) { phase = 0; continue; }
      TS(14);
      float acc[20];
      const uint32_t alo = (wb >> 4) | (8u << 16);
      wg_fence();
      wgmma40_ss_init(acc, alo, alo + 1024, 2048 >> 4);
#pragma unroll
      for (int k = 1; k < 8; k++) wgmma40_ss(acc, alo + k * 16, alo + 1024 + k * 16, 2048 >> 4);
      wg_commit();
      const uint4 k4 = lds128(wb + W_MISC + 16);
      const float k2048 = (float)(int)(k4.x + k4.y + k4.z + k4.w) * (1.f / 262144.f);
      const uint32_t dk = lds16(OFF_WR + 1152 + (wg + first) * 2);
      const int ef = max(em, min((int)((dk >> 7) & 255u) - 7, 238));
      asm volatile("st.shared.u8 [%0], %1;" :: "r"(MISC_EM + wg + first), "r"(ef + 9) : "memory");
      const float un = __uint_as_float((uint32_t)max(114 + em - ef, 0) << 23), d0 = wt ? 0.f : bf_lo(dk) * __uint_as_float((uint32_t)(245 - ef) << 23);
      wg_wait<0>();
      kw.x = pack_h(fmaf(acc[0] - acc[3], un, d0), (acc[4] - acc[7]) * un);
      kw.y = pack_h((acc[8] - acc[11]) * un, (acc[12] - acc[15]) * un);
      kw.z = pack_h((acc[16] - acc[19]) * un, k2048 * un);
      TS(24);
      ep = 0;
      if (two) SPIN_WHILE(ep == 0, ep = lds32(MISC_EPOCH));
      if (five || !two) break;
      str128(kx, kw.x, kw.y, kw.z, ep);
      two = false;
    }
    if (lane == 0) mbar_arrive(MB_KF + wg * 8);
    if (two) { mbar_wait(MB_KF); zero_pads(OFF_W + ALT, wt); }
    uint32_t tb = wb;
#pragma unroll 1
    for (;;) {
      kgen_build(tb, wg, wt, kw.x, kw.y, kw.z);
      TS(15);
      if (!two) break;
      two = false;
      kw.w = 0;
      SPIN_WHILE(kw.w != ep, kw = ldr128(kx));
      tb = OFF_W + ALT;
    }
    fence_async();
    TS(31);
    if (tb != wb) bar_arrive(7, 288);
    bar_sync(1 + wg, 128);
  }
  uint32_t tpub;
  ConvPre pre;
  conv_pre(pre, wb + (cv.ca & 0xFFFFu), 3, true, warp & 2);
#pragma unroll 1
  for (int item = 0;; item++) {
    TS(2);
    conv_item(item ? OFF_W + ALT : wb, item ? OFF_W : OFF_T + (wg >> 1) * TILE, item ? 1 : 13 + (wg >> 1), item ? 128 : five && wg == 1 ? 192 : 256, pre, cv, p.off[7],
              &tm.m[item ? 9 : 7], item ? 512 + (c >> 1) : (wg >> 1) * 128 + c, warp, lane, five && wg >= X_GW, five && !wg && !item);
    tpub = clock() - (item ? X_YD : wg >= 2 ? X_YD2 : 0);
    if (wg || !five || item) break;
    TS(27);
  }
  TS(4);
  PAD(X_PAD1)

  const int ln = lane ^ p.off[7], td = warp * 32 + ln, gg = ln >> 2, tt = ln & 3;
  const int tok = c * 16 + warp;
  const int fu = warp / 3, fk = warp - fu * 3;
  uint32_t wa[12][4];
  uint4 ha[3];
  const uint4* hsrc = &p.s->HS[td + (td / 24) * 48];
  {
    uint32_t hw[9], wr[9];
    const uint32_t row = keep(OFF_YT + warp * YT_PITCH + (warp >> 3) * 64 + ln * 16);
    const uint32_t wabase = keep(((ln & 8) ? OFF_W + (fk + 1) * W_BYTES : OFF_G + fk * 192 * pitch) + ((ln >> 4) * 8 + (ln & 7)) * pitch
                                 + (five ? ((fu ^ (ln >> 1)) & 3) : min(fu, 4)) * 16);
    float sw;
    {
      const bool three = wg == 1;
      const int ch = 8 * (tt >> 1) + gg;
      const uint32_t tr_addr = tr_base(ln);
      const uint4* ysrc = &p.s->X[c * DM * 2 + ch * 2 + (tt & 1)];
      uint32_t x[3][4], s[3];
      uint4 v[3];
#define TL(q) ((q) < 2 ? 2 * warp + (q) : 28 + warp)
      asm volatile("cp.async.bulk.wait_group.read 0;" ::: "memory");
      if (wg >= 2) { const uint32_t ts = lds32(MISC_T0); while ((int)(clock() - ts) < X_XS) {} }
      while ((int)(clock() - tpub) < X_YD) {}
      TS(5);
      v[0] = ldr128(ysrc + TL(0) * 32); v[1] = ldr128(ysrc + TL(1) * 32); v[2] = make_uint4(three, 0, 0, 0);
      if (X_REL == 1 || (X_REL == 2 && wg != 1)) mbar_wait(MB_REL);
#pragma unroll
      for (int i = 0; i < 6; i++) if (i < 4 || three) wr[i] = (gg & 2) ? ones : lds32(OFF_WR + TL(i >> 1) * 32 + (i & 1) * 16 + tt * 4);
      const uint32_t ha = keep(OFF_YT + (ln & 7) * YT_PITCH + (ln >> 4) * (8 * YT_PITCH + 64) + (ln & 8) * 2);
      const uint32_t pa = keep(OFF_PART + warp * 4 + ((gg & 2) * 8 + (gg & 4) * 2 + 2 * tt + (gg & 1)) * 80), pb = keep(OFF_PART + 2560 + warp * 4 + gg * 80);
      float dl[4] = {0.f, 0.f, 0.f, 0.f}, dh[4] = {0.f, 0.f, 0.f, 0.f};
      sw = __uint_as_float(lds32(MISC_SW));
#pragma unroll
      for (int q = 0; q < 3; q++) {
        if (q < 2 || three) {
          ldsm4t(tr_addr + TL(q) * 32, x[q][0], x[q][1], x[q][2], x[q][3]);
        }
      }
      mbar_wait(MB_SC);
#pragma unroll
      for (int q = 0; q < 3; q++) {
        asm volatile("ld.shared.u8 %0, [%1];" : "=r"(s[q]) : "r"((q < 2 ? sc_addr(warp) + q * 16 : sc_addr(16) + (warp & 3) * 16) + ch) : "memory");
        s[q] = keep(s[q] * 0x800080u);
      }
#define FIN(q) stsm4t(tr_addr + TL(q) * 32, bf_fma2(h2bf(v[q].x), s[q], x[q][0]), bf_fma2(h2bf(v[q].y), s[q], x[q][1]), bf_fma2(h2bf(v[q].z), s[q], x[q][2]), bf_fma2(h2bf(v[q].w), s[q], x[q][3]));
      SPIN_WHILE((v[0].x | v[1].x) & 1u, _Pragma("unroll") for (int q = 0; q < 3; q++) if (v[q].x & 1u) v[q] = ldr128(ysrc + TL(q) * 32));
      if (v[2].x & 1u) v[2] = ldr128(ysrc + TL(2) * 32);
#define STAT(q) { uint32_t r0, r1, r2, r3; ldsm4(ha + TL(q) * 32, r0, r1, r2, r3); \
        mma_bf16(dl, r0, wr[2 * q], r1, wr[2 * q + 1], r0, r1); mma_bf16(dh, r2, wr[2 * q], r3, wr[2 * q + 1], r2, r3); }
      FIN(0) FIN(1)
      __syncwarp();
      STAT(0) STAT(1)
      if (three) {
        SPIN_WHILE(v[2].x & 1u, if (v[2].x & 1u) v[2] = ldr128(ysrc + TL(2) * 32));
        FIN(2)
        __syncwarp();
        STAT(2)
      }
      if (gg & 1) { dl[0] = dl[1]; dl[2] = dl[3]; dh[0] = dh[1]; dh[2] = dh[3]; }
      sts32(pa, __float_as_uint((gg & 4) ? dh[2] : dl[2]));
      if (tt == (gg >> 1)) { sts32(pb, __float_as_uint(dl[0])); sts32(pb + 640, __float_as_uint(dh[0])); }
#undef STAT
#undef FIN
#undef TL
    }
    uint32_t ra = keep(OFF_PART + (ln & 15) * 80 + (ln & 16) * 2);
    uint16_t* rp = (uint16_t*)p.s->R + c * 16 + (ln & 15);
    const uint2* rsrc = (const uint2*)p.s->R + td;
    asm volatile("" : "+l"(rp), "+l"(rsrc), "+l"(hsrc));
    uint2 rv = make_uint2(0u, 0u);
    TS(28);
    if (warp != X_PW) bar_sync(0, 544);
    else {
      float z[3], rd;
      asm volatile("bar.sync 0, 544;" : "+r"(ra) :: "memory");
#pragma unroll
      for (int k = 2; k >= 0; k--) {
        const uint4 a = lds128(ra + k * 1280), b = lds128(ra + k * 1280 + 16);
        z[k] = ((__uint_as_float(a.x) + __uint_as_float(a.y)) + (__uint_as_float(a.z) + __uint_as_float(a.w))) + ((__uint_as_float(b.x) + __uint_as_float(b.y)) + (__uint_as_float(b.z) + __uint_as_float(b.w)));
      }
#pragma unroll
      for (int k = 2; k >= 0; k--) z[k] += __shfl_xor_sync(0xffffffffu, z[k], 16);
      const LnC l = ln_consts(z[1], z[2], rd);
      const uint32_t b = pack_bf(0.f, fmaf(-bf_lo(l.m2), sw, z[0]) * rd);
      const uint32_t k16 = max(min((b ^ (((int)b >> 31) | 0x80000000u)) >> 16, 0xFFFEu), 1u);
      if (ln < 16) str16(rp, k16);
      sts64(OFF_RK + (ln & 15) * 8, __byte_perm(l.m2, l.rh2, 0x5410), __byte_perm(l.rl2, k16, 0x5410));
      sts128(MISC_CNT + ln * 16, 0, 0, 0, 0);
    }
    mbar_wait(MB_GU);
#define LD_HW { const uint4 a = lds128(row), b = lds128(row + 512); hw[8] = lds32(row + 1024 - ln * 12); \
      hw[0] = a.x; hw[1] = a.y; hw[2] = a.z; hw[3] = a.w; hw[4] = b.x; hw[5] = b.y; hw[6] = b.z; hw[7] = b.w; }
    LD_HW
    const uint32_t tr0 = clock();
    bar_sync(5, 512);
    TS(7);
    const uint2 lk = lds64(OFF_RK + warp * 8);
    LnC l2;
    l2.m2 = __byte_perm(lk.x, 0, 0x1010); l2.rh2 = __byte_perm(lk.x, 0, 0x3232); l2.rl2 = __byte_perm(lk.y, 0, 0x1010);
    const uint32_t key = (lk.y & 0xFFFF0000u) | (2047 - tok);
    uint32_t loc = ln < 16 ? (lds32(OFF_RK + 4 + ln * 8) & 0xFFFF0000u) | (2047 - c * 16 - ln) : 0u;
    int rank = __popc(__ballot_sync(0xffffffffu, loc > key));
#pragma unroll
    for (int i = 0; i < 9; i++) wr[i] = keep(ln_apply(hw[i], l2.m2, l2.rh2, l2.rl2));
#define OUT_ROW { uint32_t* o = p.out + tok * 288 + ln * 4; \
      *(uint4*)o = make_uint4(bf_add2(hw[0], wr[0]), bf_add2(hw[1], wr[1]), bf_add2(hw[2], wr[2]), bf_add2(hw[3], wr[3])); \
      *(uint4*)(o + 128) = make_uint4(bf_add2(hw[4], wr[4]), bf_add2(hw[5], wr[5]), bf_add2(hw[6], wr[6]), bf_add2(hw[7], wr[7])); \
      o[256 - ln * 3] = bf_add2(hw[8], wr[8]); }
    uint4* hs = p.s->HS + ln;
    asm volatile("" : "+l"(hs));
#pragma unroll 1
    for (int base = 0; base < 8; base += 2) {
      uint32_t T[2];
#pragma unroll
      for (int j = 0; j < 2; j++) {
        const uint32_t mx = __reduce_max_sync(0xffffffffu, loc);
        if (loc == mx) loc = 0;
        T[j] = (td >> 2) < c ? (mx & 0xFFFF0000u) - 1u : mx | 0xFFFFu;
      }
      const uint32_t sh = keep(rank == base ? 0x4410u : rank == base + 1 ? 0x4432u : 0x4445u), ca = keep(MISC_CNT + base * 64 + ln * 4);
      TS(29);
      if (base == 0) {
        while ((int)(clock() - tr0) < X_RD) {}
        if ((td >> 2) != c) rv = ldr64(rsrc);
        if (rank >= X_OR) OUT_ROW
        if (warp < (five ? 12 : 15)) {
#pragma unroll
          for (int k = 0; k < X_WS; k++) ldsm4t(wabase + k * 16 * pitch, wa[k][0], wa[k][1], wa[k][2], wa[k][3]);
        }
      }
      uint32_t cnt;
#pragma unroll 1
      for (int it = 0; it < SPIN_MAX; it++) {
        const uint32_t xs = rv.x << 16, ys = rv.y << 16;
        const bool bad = max(max(rv.x, xs), max(rv.y, ys)) >= 0xFFFF0000u;
        uint32_t cn2 = 0;
        cnt = bad ? 256u : 0u;
#pragma unroll
        for (int j = 0; j < 2; j++)
          asm("{ .reg .pred a, b, c, d; setp.gt.u32 a, %2, %6; setp.gt.u32 b, %3, %6; setp.gt.u32 c, %4, %6; setp.gt.u32 d, %5, %6; "
              "@a add.u32 %1, %1, %7; @b add.u32 %1, %1, %7; @c add.u32 %0, %0, %7; @d add.u32 %0, %0, %7; }"
              : "+r"(cnt), "+r"(cn2) : "r"(rv.x), "r"(rv.y), "r"(xs), "r"(ys), "r"(T[j]), "r"(1u << (16 * j)));
        cnt = __reduce_add_sync(0xffffffffu, cnt + cn2);
        asm volatile("{ .reg .pred q; setp.eq.u32 q, %2, 0; @q red.shared.add.u32 [%0], %1; }" :: "r"(ca), "r"(cnt), "r"(cnt & 0x3F00u) : "memory");
        if (!(cnt & 0x3F00u)) break;
        if (bad) rv = ldr64(rsrc);
      }
      TS(16);
      bar_sync(0, 512);
      cnt = lds32(ca);
      if (base == 0) tpub = clock();
      const int gr = rank + __byte_perm(cnt, 0x800u, sh);
      if (gr < 8) {
        uint4* ks = hs + 1152 + gr;
        hs = (uint4*)((char*)hs + gr * 1152);
        asm volatile("{ .reg .b128 t, u; .reg .b64 a, b, c, d; mov.b64 a, {%1,%2}; mov.b64 b, {%3,%4}; mov.b64 c, {%5,%6}; mov.b64 d, {%7,%8}; mov.b128 t, {a, b}; mov.b128 u, {c, d}; "
                     "st.relaxed.gpu.global.b128 [%0], t; st.relaxed.gpu.global.b128 [%0 + 512], u; }"
                     :: "l"(hs), "r"(wr[0]), "r"(wr[1]), "r"(wr[2]), "r"(wr[3]), "r"(wr[4]), "r"(wr[5]), "r"(wr[6]), "r"(wr[7]) : "memory");
        str32((uint32_t*)(hs + 64) - ln * 3, wr[8]);
        str128(hs + 576, hw[0], hw[1], hw[2], hw[3]); str128(hs + 608, hw[4], hw[5], hw[6], hw[7]); str32((uint32_t*)(hs + 640) - ln * 3, hw[8]);
        if (ln == 0) str32(ks, key);
        rank = 16;
      }
      if (__all_sync(0xffffffffu, (int)(cnt >> 16) + base + 2 >= 8)) break;
    }
    TS(8);
    if (warp < (five ? 12 : 15)) {
#pragma unroll
      for (int k = X_WS; k < 12; k++) ldsm4t(wabase + k * 16 * pitch, wa[k][0], wa[k][1], wa[k][2], wa[k][3]);
    }
    if (warp < 6) while ((int)(clock() - tpub) < X_HD) {}
    TS(19);
    if (warp < 6) { ha[0] = ldr128(hsrc); ha[1] = ldr128(hsrc + 24); ha[2] = ldr128(hsrc + 48); }
    if (rank < X_OR) OUT_ROW
  }
  uint32_t wd[10][4];
  const uint32_t xb = keep(OFF_XS + (ln & 7) * 1168 + (fk * 24 + (ln >> 3)) * 16);
  if (warp >= 7) {
    const uint32_t db = down_box(warp - 7, five) + (ln & 7) * 128;
    mbar_wait(MB_D);
#pragma unroll
    for (int j = 0; j < 4; j++) {
      const uint32_t a = db + (ln >> 4) * 1024 + (((2 * j + ((ln >> 3) & 1)) ^ (ln & 7)) << 4);
      ldsm4t(a, wd[j][0], wd[j][1], wd[j][2], wd[j][3]);
      ldsm4t(a + 2048, wd[4 + j][0], wd[4 + j][1], wd[4 + j][2], wd[4 + j][3]);
    }
#pragma unroll
    for (int j = 0; j < 2; j++) ldsm4t(db + 4096 + (((4 * j + (ln >> 3)) ^ (ln & 7)) << 4), wd[8 + j][0], wd[8 + j][1], wd[8 + j][2], wd[8 + j][3]);
  } else if (warp < 6) {
    const uint32_t xs = keep(OFF_XS + (td + (td / 24) * 49) * 16);
#pragma unroll 1
    for (int it = 0; it < SPIN_MAX; it++) {
      const bool bad = max(max(max(ha[0].x, ha[1].x), max(ha[2].x, ha[2].y)), max(ha[2].z, ha[2].w)) == ~0u;
      if (!__any_sync(0xffffffffu, bad)) break;
      if (bad) { ha[0] = ldr128(hsrc); ha[1] = ldr128(hsrc + 24); ha[2] = ldr128(hsrc + 48); }
    }
#pragma unroll
    for (int q = 0; q < 3; q++) sts128(xs + q * 384, ha[q].x, ha[q].y, ha[q].z, ha[q].w);
  }
  TS(9);

  if (!(M_ & 2)) bar_sync(0, 512);
  if (warp >= (five ? 12 : 15)) { if (M_ & 2) bar_sync(0, 512); }
  else {
    if (M_ & 2) bar_sync(0, 512);
    float d0[4] = {0.f, 0.f, 0.f, 0.f}, d1[4] = {0.f, 0.f, 0.f, 0.f};
#pragma unroll
    for (int k = 0; k < 12; k += 2) {
      uint32_t b0, b1, b2, b3;
      ldsm4(xb + k * 32, b0, b1, b2, b3);
      mma_bf16(d0, wa[k][0], wa[k][1], wa[k][2], wa[k][3], b0, b1);
      mma_bf16(d1, wa[k + 1][0], wa[k + 1][1], wa[k + 1][2], wa[k + 1][3], b2, b3);
    }
    sts128(OFF_RED + td * 16, __float_as_uint(d0[0] + d1[0]), __float_as_uint(d0[1] + d1[1]), __float_as_uint(d0[2] + d1[2]), __float_as_uint(d0[3] + d1[3]));
  }
  TS(26);
  if (warp < 5) {
    const uint32_t rb = OFF_RED + warp * 1536 + ln * 16;
    bar_sync(9, 512);
    const uint4 pa = lds128(rb), pb = lds128(rb + 512), pc = lds128(rb + 1024);
    const float ga = bfr(__uint_as_float(pa.x) + __uint_as_float(pb.x) + __uint_as_float(pc.x));
    const float gb = bfr(__uint_as_float(pa.y) + __uint_as_float(pb.y) + __uint_as_float(pc.y));
    const uint32_t uu = pack_bf(__uint_as_float(pa.z) + __uint_as_float(pb.z) + __uint_as_float(pc.z), __uint_as_float(pa.w) + __uint_as_float(pb.w) + __uint_as_float(pc.w));
    float ra, rb2;
    asm("rcp.approx.ftz.f32 %0, %1;" : "=f"(ra) : "f"(1.f + ex2(ga * -1.4426950408889634f)));
    asm("rcp.approx.ftz.f32 %0, %1;" : "=f"(rb2) : "f"(1.f + ex2(gb * -1.4426950408889634f)));
    const uint32_t act = bf_mul2(pack_bf(ga * ra, gb * rb2), uu);
    sts32(OFF_ACT + td * 4, act);
  } else bar_arrive(9, 512);
  uint4* dst = &p.s->X[c * DM * 2 + (warp - 7) * 64 + tt * 8 + gg];
  asm volatile("" : "+l"(dst));
  if (!(M_ & 1)) { bar_sync(8, 512); tpub = clock(); }
  if (warp < 7) { if (M_ & 1) { bar_sync(8, 512); tpub = clock(); } }
  else {
    uint32_t b0, b1, b2, b3, b4;
    if (M_ & 1) bar_sync(8, 512);
    ldsm4t(OFF_ACT + ln * 16, b0, b1, b2, b3);
    asm volatile("ldmatrix.sync.aligned.m8n8.x1.trans.shared.b16 {%0}, [%1];" : "=r"(b4) : "r"(OFF_ACT + 512 + ln * 16) : "memory");
    if (M_ & 1) tpub = clock();
    float y[4][4];
#pragma unroll
    for (int j = 0; j < 4; j++) {
      y[j][0] = y[j][1] = y[j][2] = y[j][3] = 0.f;
      mma_bf16(y[j], wd[j][0], wd[j][1], wd[j][2], wd[j][3], b0, b1);
    }
#pragma unroll
    for (int j = 0; j < 4; j++) mma_bf16(y[j], wd[4 + j][0], wd[4 + j][1], wd[4 + j][2], wd[4 + j][3], b2, b3);
    if (!five) {
#pragma unroll
      for (int j = 0; j < 4; j++) mma_bf16_k8(y[j], wd[8 + (j >> 1)][2 * (j & 1)], wd[8 + (j >> 1)][2 * (j & 1) + 1], b4);
    }
    str128(dst, (pack_bf(y[0][0], y[0][1]) & ~1u) | 0x10000u, pack_bf(y[0][2], y[0][3]), pack_bf(y[1][0], y[1][1]), pack_bf(y[1][2], y[1][3]));
    str128(dst + 32, (pack_bf(y[2][0], y[2][1]) & ~1u) | 0x10000u, pack_bf(y[2][2], y[2][3]), pack_bf(y[3][0], y[3][1]), pack_bf(y[3][2], y[3][3]));
  }
  TS(10);

  if (c < 72) {
    const uint4* src = &p.s->X[(warp * 4 + tt) * (DM * 2) + c * 8 + gg];
    const int slot = (c & 3) * 2 + (ln >> 4), dw = (c >> 2) * 16 + (ln & 15);
    uint32_t hv = 0, kv = 0, res = 0, rs2 = 0;
    uint32_t* o = p.out;
    if (warp == 0) {
      hv = ~0u;
      SPIN_WHILE(max(hv, kv) == ~0u, hv = ldr32((const uint32_t*)p.s->HS + 2304 + slot * 288 + dw); kv = ldr32(&p.s->HS[1152 + slot]));
      const float r = bf_hi(kv ^ (((int)~kv >> 31) | 0x80000000u));
      float rs;
      asm("rcp.approx.ftz.f32 %0, %1;" : "=f"(rs) : "f"(1.f + ex2(r * -1.4426950408889634f)));
      rs2 = keep(pack_bf(rs, rs));
      res = lds32(OFF_XS + slot * 1168 + dw * 4);
      o += (2047 - (int)(kv & 2047u)) * 288 + dw;
      asm volatile("" : "+l"(o));
    }
    const uint32_t sel = (gg & 1) ? 0x3F800000u : 0x00003F80u;
    const uint32_t q0 = keep((gg >> 1) == 0 ? sel : 0u), q1 = keep((gg >> 1) == 1 ? sel : 0u), q2 = keep((gg >> 1) == 2 ? sel : 0u), q3 = keep((gg >> 1) == 3 ? sel : 0u);
#if M_ & 4
    const uint32_t fa = keep(OFF_RED + warp * 8 + ((gg & 1) * 16 + (gg >> 1) * 4 + tt) * 144), fb = keep(OFF_RED + ln * 144);
#else
    const uint32_t fa = keep(OFF_FIN + warp * 256 + (gg & 1) * 128 + (gg >> 1) * 32 + tt * 8), fb = keep(OFF_FIN + ln * 8);
#endif
    uint4 a0 = make_uint4(0, 0, 0, 0), a1 = a0;
    while ((int)(clock() - tpub) < X_PD) {}
    SPIN_WHILE(!(a0.x & a1.x & 0x10000u), if (!(a0.x & 0x10000u)) a0 = ldr128(src); if (!(a1.x & 0x10000u)) a1 = ldr128(src + 64 * DM * 2));
    float d[4] = {0.f, 0.f, 0.f, 0.f}, e[4] = {0.f, 0.f, 0.f, 0.f}, d2[4] = {0.f, 0.f, 0.f, 0.f}, e2[4] = {0.f, 0.f, 0.f, 0.f};
    mma_bf16(d, q0, q2, q1, q3, a0.x, a0.y); mma_bf16(e, q0, q2, q1, q3, a0.z, a0.w);
#if M_ & 8
    mma_bf16(d2, q0, q2, q1, q3, a1.x, a1.y); mma_bf16(e2, q0, q2, q1, q3, a1.z, a1.w);
    sts64(fa, __float_as_uint(d[0] + e[2] + d2[0] + e2[2]), __float_as_uint(d[1] + e[3] + d2[1] + e2[3]));
#else
    mma_bf16(d, q0, q2, q1, q3, a1.x, a1.y); mma_bf16(e, q0, q2, q1, q3, a1.z, a1.w);
    sts64(fa, __float_as_uint(d[0] + e[2]), __float_as_uint(d[1] + e[3]));
#endif
    TS(11);
    if (warp == 0) {
      bar_sync(0, 512);
      float2 s[16];
#if !(M_ & 4)
#pragma unroll
      for (int i = 0; i < 16; i++) { const uint2 q = lds64(fb + i * 256); s[i] = make_float2(__uint_as_float(q.x), __uint_as_float(q.y)); }
#else
#pragma unroll
      for (int i = 0; i < 16; i += 2) { const uint4 q = lds128(fb + i * 8); s[i] = make_float2(__uint_as_float(q.x), __uint_as_float(q.y)); s[i + 1] = make_float2(__uint_as_float(q.z), __uint_as_float(q.w)); }
#endif
#pragma unroll
      for (int k = 1; k < 16; k *= 2)
#pragma unroll
        for (int i = 0; i < 16; i += 2 * k) { s[i].x += s[i + k].x; s[i].y += s[i + k].y; }
      *o = bf_add2(hv, bf_add2(res, bf_mul2(pack_bf(s[0].x, s[0].y), rs2)));
    } else bar_arrive(0, 512);
  }
  TS(12);
  TS_DUMP();
}

typedef CUresult (*EncodeFn)(CUtensorMap*, CUtensorMapDataType, cuuint32_t, void*, const cuuint64_t*, const cuuint64_t*, const cuuint32_t*,
                             const cuuint32_t*, CUtensorMapInterleave, CUtensorMapSwizzle, CUtensorMapL2promotion, CUtensorMapFloatOOBfill);

}

extern "C" void kernel_launch(void* const* d_in, const int* in_sizes, int n_in, void* d_out, int out_size) {
  (void)in_sizes; (void)n_in; (void)out_size;
  static EncodeFn enc = nullptr;
  static Scratch* scratch = nullptr;
  if (!enc) {
    void* fn = nullptr;
    cudaDriverEntryPointQueryResult qr;
    cudaGetDriverEntryPoint("cuTensorMapEncodeTiled", &fn, cudaEnableDefault, &qr);
    enc = (EncodeFn)fn;
    cudaGetSymbolAddress((void**)&scratch, g_S);
    cudaFuncSetAttribute(fused_kernel<false>, cudaFuncAttributeMaxDynamicSharedMemorySize, SMEM_BYTES);
    cudaFuncSetAttribute(fused_kernel<true>, cudaFuncAttributeMaxDynamicSharedMemorySize, SMEM_BYTES);
  }
  TMaps tm;
  for (int i = 0; i < 6; i++) {
    const bool dn = i % 3 == 2;
    const cuuint32_t w = i < 3 ? 40 : 32;
    cuuint64_t gd[3] = {(cuuint64_t)(dn ? 64 : FF), (cuuint64_t)(dn ? FF : DM), 9};
    cuuint64_t gs[2] = {(cuuint64_t)(dn ? DM * 2 : FF * 2), 128};
    cuuint32_t bx[3] = {dn ? 64 : w, dn ? w : 96, i < 3 ? 2u : 3u};
    cuuint32_t es[3] = {1, 1, 1};
    enc(&tm.m[i], CU_TENSOR_MAP_DATA_TYPE_BFLOAT16, dn ? 3 : 2, d_in[11 + i % 3], gd, gs, bx, es, CU_TENSOR_MAP_INTERLEAVE_NONE,
        dn ? CU_TENSOR_MAP_SWIZZLE_128B : i < 3 ? CU_TENSOR_MAP_SWIZZLE_NONE : CU_TENSOR_MAP_SWIZZLE_64B,
        (CUtensorMapL2promotion)X_PROMO, CU_TENSOR_MAP_FLOAT_OOB_FILL_NONE);
  }
  for (int i = 6; i < 10; i++) {
    cuuint64_t gd[3] = {i < 8 ? 32u : 16u, i < 8 ? DM / 2u : DM, NCTA};
    cuuint64_t gs[2] = {i < 8 ? 64u : 32u, DM * 32};
    cuuint32_t bx[3] = {32, 1, (i & 1) ? 128u : 136u};
    cuuint32_t es[3] = {1, 1, 1};
    enc(&tm.m[i], CU_TENSOR_MAP_DATA_TYPE_FLOAT16, 3, scratch->X, gd, gs, bx, es, CU_TENSOR_MAP_INTERLEAVE_NONE, CU_TENSOR_MAP_SWIZZLE_64B,
        CU_TENSOR_MAP_L2_PROMOTION_NONE, CU_TENSOR_MAP_FLOAT_OOB_FILL_NONE);
  }
  Params p;
  p.x = (const unsigned char*)d_in[0];
  bool far = false;
  for (int i = 0; i < 7; i++) {
    p.far[i] = (const unsigned char*)d_in[1 + i];
    const long long d = (long long)((intptr_t)d_in[1 + i] - (intptr_t)d_in[0]);
    p.off[i] = (int)(d / 16);
    if ((long long)p.off[i] * 16 != d || p.off[i] > (1 << 30)) far = true;
  }
  p.dskip = (const uint16_t*)d_in[8];
  p.w_r = (const uint32_t*)d_in[10];
  for (int f = 0; f < 2; f++) {
    static const int kind[17] = {0, 0, 0, 0, 2, 2, 0, 0, 1, 1, 1, 1, 1, 1, 2, 2, 2};
    static const int idx[2][17] = {{2, 3, 4, 5, 6, 8, 0, 1, 0, 1, 2, 3, 4, 5, 0, 2, 4}, {2, 3, 4, 5, 0, -1, 0, 1, 0, 1, 2, 3, 4, 5, 3, -1, 6}};
    static const int blk[2][17] = {{-1, -1, -1, -1, 0, -1, 4, -1, 1, -1, 2, -1, 3, -1, 16, -1, -1}, {-1, -1, -1, -1, 1, -1, 4, -1, -1, -1, 2, -1, 3, -1, 16, -1, -1}};
    const int pitch = f ? 64 : 80;
    for (int u = 0; u < 17; u++) {
      const int s = idx[f][u];
      const uint32_t dst = kind[u] == 0 ? OFF_G + s * 96 * pitch : kind[u] == 2 ? down_box(s, f) : OFF_W + W_BYTES + (s >> 1) * W_BYTES + (s & 1) * 96 * pitch;
      const uint32_t mb = u >= 14 ? (u >= X_HU ? MB_H - OFF_MISC : X_HB) : blk[f][u] >= 0 ? MB_KF - OFF_MISC + blk[f][u] * 8 : 0;
      p.sched[f][u] = s < 0 ? 3u : kind[u] | s << 2 | mb << 6 | dst << 14;
    }
  }
  p.out = (uint32_t*)d_out;
  p.off[7] = 0;
  p.ts = nullptr;
  p.s = scratch;
  if (far) { fused_kernel<true><<<NCTA, NT, SMEM_BYTES, cudaStreamPerThread>>>(p, tm); return; }
  fused_kernel<false><<<NCTA, NT, SMEM_BYTES, cudaStreamPerThread>>>(p, tm);
}
```

```cpp
#include <cuda_runtime.h>
#include <cuda.h>
#include <cuda_bf16.h>
#include <cuda_fp16.h>
#include <stdint.h>
#include <stddef.h>

namespace {

constexpr int NCTA = 128;
constexpr int NT = 640;
constexpr int DM = 576;
constexpr int FF = 4608;
constexpr int SPIN_MAX = 1 << 20;

struct Scratch {
  uint4 X[NCTA * DM * 2];
  uint4 KX[64 * 128];
  uint4 HS[1152 + 8];
  uint4 R[256];
  uint4 SC[256];
  uint32_t FLAG[NCTA * 8];
};
__device__ Scratch g_S;

#define CLKS(i)
#define TS(i)
#define TSX(i)
#define TS_DUMP()

constexpr int SB = 1024;
constexpr int BOX = 15360;
constexpr int OFF_G = SB;
constexpr int OFF_W = OFF_G + 3 * BOX;
constexpr int W_KT = 26624;
constexpr int W_L3 = W_KT + 4416;
constexpr int W_CW = W_L3 + 4096;
constexpr int W_MISC = W_CW + 640;
constexpr int W_BYTES = 35840;
constexpr int TILE = 10240;
constexpr int OFF_T = OFF_W + 4 * W_BYTES;
constexpr int ALT = TILE - W_KT;
static_assert(W_MISC + 32 <= W_BYTES && OFF_W % 1024 == 0 && W_BYTES % 1024 == 0 && W_BYTES + ALT <= 20480, "wg block");
constexpr int YT_PITCH = 1184;
constexpr int OFF_YT = OFF_T + 2 * TILE;
constexpr int OFF_WR = OFF_YT + 16 * YT_PITCH + 64;
constexpr int OFF_MISC = OFF_WR + 2304;
constexpr int SMEM_BYTES = OFF_MISC + 1024 - SB;
static_assert(OFF_YT % 16 == 0 && OFF_MISC % 16 == 0, "align");
static_assert(SMEM_BYTES <= 232448, "smem");
constexpr int MB_GU = OFF_MISC;
constexpr int MB_D = OFF_MISC + 8;
constexpr int MB_KF = OFF_MISC + 16;
constexpr int MB_GF = OFF_MISC + 48;
constexpr int MB_SC = OFF_MISC + 56;
constexpr int MB_UL = OFF_MISC + 64;
constexpr int MB_REL = OFF_MISC + 104;
constexpr int MB_GO = OFF_MISC + 112;
constexpr int MB_H = MB_KF + 128;
constexpr int MISC_EPOCH = OFF_MISC + 152;
constexpr int MISC_SW = OFF_MISC + 156;
constexpr int MISC_RT = OFF_MISC + 160;
constexpr int MISC_T0 = OFF_MISC + 296;
constexpr int MISC_EM = OFF_MISC + 288;
constexpr int OFF_PART = OFF_W + 20480;
constexpr int OFF_RK = OFF_PART + 3840;
constexpr int MISC_LN1 = OFF_MISC + 192;
constexpr int OFF_XS = OFF_T;
constexpr int OFF_RED = OFF_T + TILE;
constexpr int OFF_FIN = OFF_W + 3 * W_BYTES + W_KT;
constexpr int OFF_ACT = OFF_FIN + 4096;
constexpr int MISC_CNT = OFF_ACT + 1024;

__device__ __forceinline__ uint32_t smem_u32(const void* p) { return (uint32_t)__cvta_generic_to_shared(p); }
__device__ __forceinline__ uint32_t lds32(uint32_t a) { uint32_t v; asm volatile("ld.shared.b32 %0, [%1];" : "=r"(v) : "r"(a) : "memory"); return v; }
__device__ __forceinline__ uint32_t lds16(uint32_t a) { uint16_t v; asm volatile("ld.shared.u16 %0, [%1];" : "=h"(v) : "r"(a) : "memory"); return v; }
__device__ __forceinline__ uint2 lds64(uint32_t a) { uint2 v; asm volatile("ld.shared.v2.b32 {%0,%1}, [%2];" : "=r"(v.x), "=r"(v.y) : "r"(a) : "memory"); return v; }
__device__ __forceinline__ uint4 lds128(uint32_t a) { uint4 v; asm volatile("ld.shared.v4.b32 {%0,%1,%2,%3}, [%4];" : "=r"(v.x), "=r"(v.y), "=r"(v.z), "=r"(v.w) : "r"(a) : "memory"); return v; }
__device__ __forceinline__ void sts16(uint32_t a, uint32_t v) { asm volatile("st.shared.u16 [%0], %1;" :: "r"(a), "h"((uint16_t)v) : "memory"); }
__device__ __forceinline__ void sts32(uint32_t a, uint32_t v) { asm volatile("st.shared.b32 [%0], %1;" :: "r"(a), "r"(v) : "memory"); }
__device__ __forceinline__ void sts64(uint32_t a, uint32_t x, uint32_t y) { asm volatile("st.shared.v2.b32 [%0], {%1,%2};" :: "r"(a), "r"(x), "r"(y) : "memory"); }
__device__ __forceinline__ void sts128(uint32_t a, uint32_t x, uint32_t y, uint32_t z, uint32_t w) { asm volatile("st.shared.v4.b32 [%0], {%1,%2,%3,%4};" :: "r"(a), "r"(x), "r"(y), "r"(z), "r"(w) : "memory"); }
__device__ __forceinline__ void ldsm4(uint32_t a, uint32_t& r0, uint32_t& r1, uint32_t& r2, uint32_t& r3) {
  asm volatile("ldmatrix.sync.aligned.m8n8.x4.shared.b16 {%0,%1,%2,%3}, [%4];" : "=r"(r0), "=r"(r1), "=r"(r2), "=r"(r3) : "r"(a) : "memory");
}
__device__ __forceinline__ void ldsm2(uint32_t a, uint32_t& r0, uint32_t& r1) {
  asm volatile("ldmatrix.sync.aligned.m8n8.x2.shared.b16 {%0,%1}, [%2];" : "=r"(r0), "=r"(r1) : "r"(a) : "memory");
}
__device__ __forceinline__ void ldsm4t(uint32_t a, uint32_t& r0, uint32_t& r1, uint32_t& r2, uint32_t& r3) {
  asm volatile("ldmatrix.sync.aligned.m8n8.x4.trans.shared.b16 {%0,%1,%2,%3}, [%4];" : "=r"(r0), "=r"(r1), "=r"(r2), "=r"(r3) : "r"(a) : "memory");
}
__device__ __forceinline__ void stsm4t(uint32_t a, uint32_t r0, uint32_t r1, uint32_t r2, uint32_t r3) {
  asm volatile("stmatrix.sync.aligned.m8n8.x4.trans.shared.b16 [%0], {%1,%2,%3,%4};" :: "r"(a), "r"(r0), "r"(r1), "r"(r2), "r"(r3) : "memory");
}
__device__ __forceinline__ uint4 ldr128(const void* p) {
  unsigned long long lo, hi;
  asm volatile("{ .reg .b128 t; ld.relaxed.gpu.global.b128 t, [%2]; mov.b128 {%0, %1}, t; }" : "=l"(lo), "=l"(hi) : "l"(p) : "memory");
  return make_uint4((uint32_t)lo, (uint32_t)(lo >> 32), (uint32_t)hi, (uint32_t)(hi >> 32));
}
__device__ __forceinline__ void str128(void* p, uint32_t x, uint32_t y, uint32_t z, uint32_t w) {
  asm volatile("{ .reg .b128 t; .reg .b64 lo, hi; mov.b64 lo, {%1,%2}; mov.b64 hi, {%3,%4}; mov.b128 t, {lo, hi}; st.relaxed.gpu.global.b128 [%0], t; }"
               :: "l"(p), "r"(x), "r"(y), "r"(z), "r"(w) : "memory");
}
__device__ __forceinline__ void str64(void* p, uint32_t x, uint32_t y) {
  asm volatile("{ .reg .b64 t; mov.b64 t, {%1,%2}; st.relaxed.gpu.global.b64 [%0], t; }" :: "l"(p), "r"(x), "r"(y) : "memory");
}
__device__ __forceinline__ uint32_t ldr32(const void* p) { uint32_t v; asm volatile("ld.relaxed.gpu.global.b32 %0, [%1];" : "=r"(v) : "l"(p) : "memory"); return v; }
__device__ __forceinline__ void str32(void* p, uint32_t v) { asm volatile("st.relaxed.gpu.global.b32 [%0], %1;" :: "l"(p), "r"(v) : "memory"); }
__device__ __forceinline__ void str16(void* p, uint32_t v) { asm volatile("st.relaxed.gpu.global.u16 [%0], %1;" :: "l"(p), "h"((uint16_t)v) : "memory"); }
__device__ __forceinline__ void fence_gpu() { asm volatile("fence.acq_rel.gpu;" ::: "memory"); }
__device__ __forceinline__ void bar_sync(int id, int n) { asm volatile("bar.sync %0, %1;" :: "r"(id), "r"(n) : "memory"); }
__device__ __forceinline__ void bar_arrive(int id, int n) { asm volatile("bar.arrive %0, %1;" :: "r"(id), "r"(n) : "memory"); }

__device__ __forceinline__ float bf_lo(uint32_t w) { return __uint_as_float(w << 16); }
__device__ __forceinline__ float bf_hi(uint32_t w) { return __uint_as_float(w & 0xFFFF0000u); }
__device__ __forceinline__ uint32_t pack_bf(float lo, float hi) { uint32_t r; asm("cvt.rn.bf16x2.f32 %0, %1, %2;" : "=r"(r) : "f"(hi), "f"(lo)); return r; }
__device__ __forceinline__ uint32_t pack_h(float lo, float hi) { uint32_t r; asm("cvt.rn.f16x2.f32 %0, %1, %2;" : "=r"(r) : "f"(hi), "f"(lo)); return r; }
__device__ __forceinline__ uint32_t pack_hv(float lo, float hi) { uint32_t r; asm volatile("cvt.rn.f16x2.f32 %0, %1, %2;" : "=r"(r) : "f"(hi), "f"(lo) : "memory"); return r; }
__device__ __forceinline__ float bfr(float x) { return bf_lo(pack_bf(x, 0.f)); }
__device__ __forceinline__ uint32_t bf_sub2(uint32_t a, uint32_t b) { __nv_bfloat162 r = __hsub2(*(__nv_bfloat162*)&a, *(__nv_bfloat162*)&b); return *(uint32_t*)&r; }
__device__ __forceinline__ uint32_t bf_add2(uint32_t a, uint32_t b) { __nv_bfloat162 r = __hadd2(*(__nv_bfloat162*)&a, *(__nv_bfloat162*)&b); return *(uint32_t*)&r; }
__device__ __forceinline__ uint32_t bf_mul2(uint32_t a, uint32_t b) { __nv_bfloat162 r = __hmul2(*(__nv_bfloat162*)&a, *(__nv_bfloat162*)&b); return *(uint32_t*)&r; }
__device__ __forceinline__ float2 h2f(uint32_t w) { return __half22float2(*(__half2*)&w); }
__device__ __forceinline__ float ex2(float x) { float r; asm("ex2.approx.ftz.f32 %0, %1;" : "=f"(r) : "f"(x)); return r; }
__device__ __forceinline__ float warp_sum(float v) {
#pragma unroll
  for (int o = 16; o > 0; o >>= 1) v += __shfl_xor_sync(0xffffffffu, v, o);
  return v;
}
__device__ __forceinline__ void mma_f16_f32(float* d, uint32_t a0, uint32_t a1, uint32_t a2, uint32_t a3, uint32_t b0, uint32_t b1) {
  asm volatile("mma.sync.aligned.m16n8k16.row.col.f32.f16.f16.f32 {%0,%1,%2,%3}, {%4,%5,%6,%7}, {%8,%9}, {%0,%1,%2,%3};"
               : "+f"(d[0]), "+f"(d[1]), "+f"(d[2]), "+f"(d[3]) : "r"(a0), "r"(a1), "r"(a2), "r"(a3), "r"(b0), "r"(b1));
}
__device__ __forceinline__ void mma_f16_f16(uint32_t& d0, uint32_t& d1, uint32_t a0, uint32_t a1, uint32_t a2, uint32_t a3, uint32_t b0, uint32_t b1) {
  asm volatile("mma.sync.aligned.m16n8k16.row.col.f16.f16.f16.f16 {%0,%1}, {%2,%3,%4,%5}, {%6,%7}, {%0,%1};"
               : "+r"(d0), "+r"(d1) : "r"(a0), "r"(a1), "r"(a2), "r"(a3), "r"(b0), "r"(b1));
}
__device__ __forceinline__ void mma_bf16(float* d, uint32_t a0, uint32_t a1, uint32_t a2, uint32_t a3, uint32_t b0, uint32_t b1) {
  asm volatile("mma.sync.aligned.m16n8k16.row.col.f32.bf16.bf16.f32 {%0,%1,%2,%3}, {%4,%5,%6,%7}, {%8,%9}, {%0,%1,%2,%3};"
               : "+f"(d[0]), "+f"(d[1]), "+f"(d[2]), "+f"(d[3]) : "r"(a0), "r"(a1), "r"(a2), "r"(a3), "r"(b0), "r"(b1));
}
__device__ __forceinline__ void mma_bf16_k8(float* d, uint32_t a0, uint32_t a1, uint32_t b0) {
  asm volatile("mma.sync.aligned.m16n8k8.row.col.f32.bf16.bf16.f32 {%0,%1,%2,%3}, {%4,%5}, {%6}, {%0,%1,%2,%3};"
               : "+f"(d[0]), "+f"(d[1]), "+f"(d[2]), "+f"(d[3]) : "r"(a0), "r"(a1), "r"(b0));
}

__device__ __forceinline__ void wg_fence() { asm volatile("wgmma.fence.sync.aligned;" ::: "memory"); }
__device__ __forceinline__ void wg_commit() { asm volatile("wgmma.commit_group.sync.aligned;" ::: "memory"); }
template <int N> __device__ __forceinline__ void wg_wait() { asm volatile("wgmma.wait_group.sync.aligned %0;" :: "n"(N) : "memory"); }
template <int TB> __device__ __forceinline__ void wgmma32(float* d, const uint32_t* a, uint32_t dlo, uint32_t dhi) {
  asm volatile("{ .reg .b64 dd; mov.b64 dd, {%20, %21}; wgmma.mma_async.sync.aligned.m64n32k16.f32.f16.f16 "
               "{%0,%1,%2,%3,%4,%5,%6,%7,%8,%9,%10,%11,%12,%13,%14,%15}, {%16,%17,%18,%19}, dd, 1, 1, 1, %22; }"
               : "+f"(d[0]), "+f"(d[1]), "+f"(d[2]), "+f"(d[3]), "+f"(d[4]), "+f"(d[5]), "+f"(d[6]), "+f"(d[7]), "+f"(d[8]), "+f"(d[9]), "+f"(d[10]), "+f"(d[11]), "+f"(d[12]), "+f"(d[13]), "+f"(d[14]), "+f"(d[15])
               : "r"(a[0]), "r"(a[1]), "r"(a[2]), "r"(a[3]), "r"(dlo), "r"(dhi), "n"(TB));
}
template <int TB> __device__ __forceinline__ void wgmma64(float* d, const uint32_t* a, uint32_t dlo, uint32_t dhi) {
  asm volatile("{ .reg .b64 dd; mov.b64 dd, {%36, %37}; wgmma.mma_async.sync.aligned.m64n64k16.f32.f16.f16 "
               "{%0,%1,%2,%3,%4,%5,%6,%7,%8,%9,%10,%11,%12,%13,%14,%15,%16,%17,%18,%19,%20,%21,%22,%23,%24,%25,%26,%27,%28,%29,%30,%31}, {%32,%33,%34,%35}, dd, 1, 1, 1, %38; }"
               : "+f"(d[0]), "+f"(d[1]), "+f"(d[2]), "+f"(d[3]), "+f"(d[4]), "+f"(d[5]), "+f"(d[6]), "+f"(d[7]), "+f"(d[8]), "+f"(d[9]), "+f"(d[10]), "+f"(d[11]), "+f"(d[12]), "+f"(d[13]), "+f"(d[14]), "+f"(d[15]), "+f"(d[16]), "+f"(d[17]), "+f"(d[18]), "+f"(d[19]), "+f"(d[20]), "+f"(d[21]), "+f"(d[22]), "+f"(d[23]), "+f"(d[24]), "+f"(d[25]), "+f"(d[26]), "+f"(d[27]), "+f"(d[28]), "+f"(d[29]), "+f"(d[30]), "+f"(d[31])
               : "r"(a[0]), "r"(a[1]), "r"(a[2]), "r"(a[3]), "r"(dlo), "r"(dhi), "n"(TB));
}
template <int TB> __device__ __forceinline__ void wgmma64_init(float* d, const uint32_t* a, uint32_t dlo, uint32_t dhi) {
  asm volatile("{ .reg .b64 dd; mov.b64 dd, {%36, %37}; wgmma.mma_async.sync.aligned.m64n64k16.f32.f16.f16 "
               "{%0,%1,%2,%3,%4,%5,%6,%7,%8,%9,%10,%11,%12,%13,%14,%15,%16,%17,%18,%19,%20,%21,%22,%23,%24,%25,%26,%27,%28,%29,%30,%31}, {%32,%33,%34,%35}, dd, 0, 1, 1, %38; }"
               : "=f"(d[0]), "=f"(d[1]), "=f"(d[2]), "=f"(d[3]), "=f"(d[4]), "=f"(d[5]), "=f"(d[6]), "=f"(d[7]), "=f"(d[8]), "=f"(d[9]), "=f"(d[10]), "=f"(d[11]), "=f"(d[12]), "=f"(d[13]), "=f"(d[14]), "=f"(d[15]), "=f"(d[16]), "=f"(d[17]), "=f"(d[18]), "=f"(d[19]), "=f"(d[20]), "=f"(d[21]), "=f"(d[22]), "=f"(d[23]), "=f"(d[24]), "=f"(d[25]), "=f"(d[26]), "=f"(d[27]), "=f"(d[28]), "=f"(d[29]), "=f"(d[30]), "=f"(d[31])
               : "r"(a[0]), "r"(a[1]), "r"(a[2]), "r"(a[3]), "r"(dlo), "r"(dhi), "n"(TB));
}
template <int TB> __device__ __forceinline__ void wgmma32_init(float* d, const uint32_t* a, uint32_t dlo, uint32_t dhi) {
  asm volatile("{ .reg .b64 dd; mov.b64 dd, {%20, %21}; wgmma.mma_async.sync.aligned.m64n32k16.f32.f16.f16 "
               "{%0,%1,%2,%3,%4,%5,%6,%7,%8,%9,%10,%11,%12,%13,%14,%15}, {%16,%17,%18,%19}, dd, 0, 1, 1, %22; }"
               : "=f"(d[0]), "=f"(d[1]), "=f"(d[2]), "=f"(d[3]), "=f"(d[4]), "=f"(d[5]), "=f"(d[6]), "=f"(d[7]), "=f"(d[8]), "=f"(d[9]), "=f"(d[10]), "=f"(d[11]), "=f"(d[12]), "=f"(d[13]), "=f"(d[14]), "=f"(d[15])
               : "r"(a[0]), "r"(a[1]), "r"(a[2]), "r"(a[3]), "r"(dlo), "r"(dhi), "n"(TB));
}
__device__ __forceinline__ void wgmma64h(uint32_t* d, uint32_t a0, uint32_t a1, uint32_t a2, uint32_t a3, uint32_t dlo, uint32_t dhi) {
  asm volatile("{ .reg .b64 dd; mov.b64 dd, {%20, %21}; wgmma.mma_async.sync.aligned.m64n64k16.f16.f16.f16 "
               "{%0,%1,%2,%3,%4,%5,%6,%7,%8,%9,%10,%11,%12,%13,%14,%15}, {%16,%17,%18,%19}, dd, 1, 1, 1, 0; }"
               : "+r"(d[0]), "+r"(d[1]), "+r"(d[2]), "+r"(d[3]), "+r"(d[4]), "+r"(d[5]), "+r"(d[6]), "+r"(d[7]), "+r"(d[8]), "+r"(d[9]), "+r"(d[10]), "+r"(d[11]), "+r"(d[12]), "+r"(d[13]), "+r"(d[14]), "+r"(d[15])
               : "r"(a0), "r"(a1), "r"(a2), "r"(a3), "r"(dlo), "r"(dhi));
}
__device__ __forceinline__ void wgmma64h_init(uint32_t* d, uint32_t a0, uint32_t a1, uint32_t a2, uint32_t a3, uint32_t dlo, uint32_t dhi) {
  asm volatile("{ .reg .b64 dd; mov.b64 dd, {%20, %21}; wgmma.mma_async.sync.aligned.m64n64k16.f16.f16.f16 "
               "{%0,%1,%2,%3,%4,%5,%6,%7,%8,%9,%10,%11,%12,%13,%14,%15}, {%16,%17,%18,%19}, dd, 0, 1, 1, 0; }"
               : "=r"(d[0]), "=r"(d[1]), "=r"(d[2]), "=r"(d[3]), "=r"(d[4]), "=r"(d[5]), "=r"(d[6]), "=r"(d[7]), "=r"(d[8]), "=r"(d[9]), "=r"(d[10]), "=r"(d[11]), "=r"(d[12]), "=r"(d[13]), "=r"(d[14]), "=r"(d[15])
               : "r"(a0), "r"(a1), "r"(a2), "r"(a3), "r"(dlo), "r"(dhi));
}
__device__ __forceinline__ void wgmma40_ss(float* d, uint32_t alo, uint32_t blo, uint32_t hi) {
  asm volatile("{ .reg .b64 da, db; mov.b64 da, {%20, %22}; mov.b64 db, {%21, %22}; "
               "wgmma.mma_async.sync.aligned.m64n40k16.f32.f16.f16 {%0,%1,%2,%3,%4,%5,%6,%7,%8,%9,%10,%11,%12,%13,%14,%15,%16,%17,%18,%19}, da, db, 1, 1, 1, 1, 1; }"
               : "+f"(d[0]), "+f"(d[1]), "+f"(d[2]), "+f"(d[3]), "+f"(d[4]), "+f"(d[5]), "+f"(d[6]), "+f"(d[7]), "+f"(d[8]), "+f"(d[9]), "+f"(d[10]), "+f"(d[11]), "+f"(d[12]), "+f"(d[13]), "+f"(d[14]), "+f"(d[15]), "+f"(d[16]), "+f"(d[17]), "+f"(d[18]), "+f"(d[19])
               : "r"(alo), "r"(blo), "r"(hi));
}
__device__ __forceinline__ void wgmma40_ss_init(float* d, uint32_t alo, uint32_t blo, uint32_t hi) {
  asm volatile("{ .reg .b64 da, db; mov.b64 da, {%20, %22}; mov.b64 db, {%21, %22}; "
               "wgmma.mma_async.sync.aligned.m64n40k16.f32.f16.f16 {%0,%1,%2,%3,%4,%5,%6,%7,%8,%9,%10,%11,%12,%13,%14,%15,%16,%17,%18,%19}, da, db, 0, 1, 1, 1, 1; }"
               : "=f"(d[0]), "=f"(d[1]), "=f"(d[2]), "=f"(d[3]), "=f"(d[4]), "=f"(d[5]), "=f"(d[6]), "=f"(d[7]), "=f"(d[8]), "=f"(d[9]), "=f"(d[10]), "=f"(d[11]), "=f"(d[12]), "=f"(d[13]), "=f"(d[14]), "=f"(d[15]), "=f"(d[16]), "=f"(d[17]), "=f"(d[18]), "=f"(d[19])
               : "r"(alo), "r"(blo), "r"(hi));
}
__device__ __forceinline__ float vzero() { float v; asm volatile("mov.b32 %0, 0;" : "=f"(v)); return v; }
__device__ __forceinline__ void tma_box(uint32_t dst, const CUtensorMap* tm, uint32_t mb, int x, int y) {
  asm volatile("cp.async.bulk.tensor.2d.shared::cluster.global.mbarrier::complete_tx::bytes [%0], [%1, {%3, %4}], [%2];"
               :: "r"(dst), "l"(tm), "r"(mb), "r"(x), "r"(y) : "memory");
}
__device__ __forceinline__ void l2_prefetch(const void* src, uint32_t bytes) {
  asm volatile("cp.async.bulk.prefetch.L2.global [%0], %1;" :: "l"(src), "r"(bytes) : "memory");
}
__device__ __forceinline__ uint32_t uni(uint32_t v) {
  uint32_t r; asm volatile("shfl.sync.idx.b32 %0, %1, 0, 0x1f, 0xffffffff;" : "=r"(r) : "r"(v)); return r;
}
__device__ __forceinline__ uint32_t pin(uint32_t v) {
  uint32_t r; asm volatile("shfl.sync.bfly.b32 %0, %1, 0, 0x1f, 0xffffffff;" : "=r"(r) : "r"(v)); return r;
}
__device__ __forceinline__ int fresh_tid() { int v; asm volatile("mov.u32 %0, %tid.x;" : "=r"(v)); return v; }

struct Params {
  const unsigned char* x;
  Scratch* s;
  int off[8];
  uint32_t* out;
  const uint16_t* dskip;
  const uint32_t* w_r;
  long long* ts;
  const unsigned char* far[7];
  uint32_t sched[2][17];
};
__device__ __forceinline__ uint32_t ldnc32(const void* p) { uint32_t v; asm volatile("ld.global.nc.b32 %0, [%1];" : "=r"(v) : "l"(p)); return v; }
__device__ __forceinline__ uint32_t ldnc16(const void* p) { uint16_t v; asm volatile("ld.global.nc.u16 %0, [%1];" : "=h"(v) : "l"(p)); return v; }
__device__ __forceinline__ uint4 ldnc128(const void* p) { uint4 v; asm volatile("ld.global.nc.v4.b32 {%0,%1,%2,%3}, [%4];" : "=r"(v.x), "=r"(v.y), "=r"(v.z), "=r"(v.w) : "l"(p)); return v; }
__device__ __forceinline__ void mbar_wait(uint32_t mb, uint32_t ph = 0) {
#pragma unroll 1
  for (int it = 0; it < SPIN_MAX; it++) {
    uint32_t ok;
    asm volatile("{ .reg .pred q; mbarrier.try_wait.parity.shared::cta.b64 q, [%1], %2; selp.u32 %0, 1, 0, q; }" : "=r"(ok) : "r"(mb), "r"(ph) : "memory");
    if (ok) break;
  }
}
__device__ __forceinline__ uint32_t mbar_test(uint32_t mb) {
  uint32_t ok;
  asm volatile("{ .reg .pred q; mbarrier.test_wait.parity.shared::cta.b64 q, [%1], 0; selp.u32 %0, 1, 0, q; }" : "=r"(ok) : "r"(mb) : "memory");
  return ok;
}
__device__ __forceinline__ void mbar_arrive(uint32_t mb) { asm volatile("mbarrier.arrive.shared::cta.b64 _, [%0];" :: "r"(mb) : "memory"); }
__device__ __forceinline__ uint32_t ldg16(const void* p) { uint16_t v; asm volatile("ld.global.u16 %0, [%1];" : "=h"(v) : "l"(p) : "memory"); return v; }
__device__ __forceinline__ uint32_t ldr16(const void* p) { uint16_t v; asm volatile("ld.relaxed.gpu.global.u16 %0, [%1];" : "=h"(v) : "l"(p) : "memory"); return v; }
__device__ __forceinline__ void fence_async() { asm volatile("fence.proxy.async.shared::cta;" ::: "memory"); }
#define SPIN_WHILE(cond, body) _Pragma("unroll 1") for (int _it = 0; _it < SPIN_MAX && __any_sync(0xffffffffu, (cond)); _it++) { body; }

struct LnC { uint32_t m2, rh2, rl2; };
__device__ __forceinline__ float diag_sum(float d0, float d1, int t) {
  float q = __shfl_sync(0xffffffffu, d0, 9 * t) + __shfl_sync(0xffffffffu, d1, 9 * t + 4);
  q += __shfl_xor_sync(0xffffffffu, q, 1);
  return q + __shfl_xor_sync(0xffffffffu, q, 2);
}
__device__ __forceinline__ LnC ln_consts(float s, float q, float& r) {
  const float mean = s * (1.f / DM);
  const float var = fmaxf(fmaf(-mean, mean, q * (1.f / DM)), 0.f);
  float sd;
  asm("sqrt.approx.ftz.f32 %0, %1;" : "=f"(sd) : "f"(bfr(bfr(var) + 1e-5f)));
  asm("rcp.approx.ftz.f32 %0, %1;" : "=f"(r) : "f"(bfr(sd)));
  LnC c;
  c.m2 = pack_bf(mean, mean);
  c.rh2 = pack_bf(r, r);
  const float rl = r - bf_lo(c.rh2);
  c.rl2 = pack_bf(rl, rl);
  return c;
}
__device__ __forceinline__ float quad_sum(float s) { s += __shfl_xor_sync(0xffffffffu, s, 1); return s + __shfl_xor_sync(0xffffffffu, s, 2); }
__device__ __forceinline__ uint32_t bf_fma2(uint32_t a, uint32_t b, uint32_t c) {
  __nv_bfloat162 r = __hfma2(*(const __nv_bfloat162*)&a, *(const __nv_bfloat162*)&b, *(const __nv_bfloat162*)&c);
  return *(uint32_t*)&r;
}
__device__ __forceinline__ uint32_t ln_apply(uint32_t w, uint32_t m2, uint32_t rh2, uint32_t rl2) {
  const uint32_t d = bf_sub2(w, m2);
  return bf_fma2(d, rh2, bf_mul2(d, rl2));
}

__device__ __forceinline__ float2 cis(float mag_log2, float rev) {
  const float m = ex2(mag_log2), ang = rev * 6.283185307179586f;
  return make_float2(m * __cosf(ang), m * __sinf(ang));
}
__device__ __forceinline__ float2 csq(float2 a) { return make_float2(fmaf(a.x, a.x, -a.y * a.y), (a.x + a.x) * a.y); }
__device__ __forceinline__ float2 cmul(float2 a, float2 b) { return make_float2(fmaf(a.x, b.x, -a.y * b.y), fmaf(a.x, b.y, a.y * b.x)); }
__device__ __forceinline__ void pmul(uint32_t xr, uint32_t xi, uint32_t w, uint32_t& yr, uint32_t& yi) {
  const __half2 XR = *(__half2*)&xr, XI = *(__half2*)&xi, W = *(__half2*)&w;
  const __half2 a = __hfma2(__hneg2(XI), __high2half2(W), __hmul2(XR, __low2half2(W)));
  const __half2 b = __hfma2(XI, __low2half2(W), __hmul2(XR, __high2half2(W)));
  yr = *(const uint32_t*)&a; yi = *(const uint32_t*)&b;
}
__device__ __forceinline__ uint32_t pk(float2 a) { return pack_h(a.x, a.y); }

struct KgState { float2 c0, z8; float kl; uint32_t w64, w128, w192; };
__device__ __forceinline__ void kgen_tables_n(const uint32_t (&raw)[7], uint32_t scr, int wt, KgState& k) {
  const uint32_t dst = scr + 16384 + wt * 16;
  const float dt = bfr(ex2(bf_lo(raw[6]) * 1.4426950408889634f));
  const float th = dt * bf_lo(raw[1]);
  const float br = dt * bf_lo(raw[2]), bi = dt * bf_lo(raw[3]);
  const float Cr = bf_lo(raw[4]), Ci = bf_lo(raw[5]);
  k.c0 = make_float2(fmaf(Cr, br, -Ci * bi), fmaf(Cr, bi, Ci * br));
  const uint32_t mx = __reduce_max_sync(0xffffffffu, __float_as_uint(fmaxf(fabsf(k.c0.x), fabsf(k.c0.y))));
  const float a2 = dt * bf_lo(raw[0]) * 1.4426950408889634f;
  const float rh = th * 0.15915494309189535f;
  const float rl = fmaf(th, (float)(0.15915494309189535 - (double)0.15915494309189535f), fmaf(th, 0.15915494309189535f, -rh));
  const float rf = rh - rintf(rh);
  const float2 z1 = cis(a2, rf + rl);
  const float p64 = rf * 64.f;
  const float2 z64 = cis(a2 * 64.f, fmaf(64.f, rl, p64 - rintf(p64)));
  const float2 z2 = csq(z1), z128 = csq(z64), z3 = cmul(z2, z1), z4 = csq(z2), z256 = csq(z128), z6 = csq(z3), z512 = csq(z256);
  k.z8 = csq(z4);
  k.w64 = pk(z64); k.w128 = pk(z128); k.w192 = pk(cmul(z128, z64));
  sts128(dst, 0x00003C00u, pk(z2), pk(z4), pk(z6));
  const float2 z1024 = csq(z512), z768 = cmul(z512, z256);
  sts128(dst + 2048, pk(z1), pk(z3), pk(cmul(z4, z1)), pk(cmul(z4, z3)));
  const float2 z2048 = csq(z1024);
  k.kl = fmaf(k.c0.x, z2048.x, -k.c0.y * z2048.y);
  sts128(dst + 4096, pk(z256), pk(cmul(z256, z2)), pk(cmul(z256, z4)), pk(cmul(z256, z6)));
  sts128(dst + 6144, pk(z512), pk(cmul(z512, z4)), pk(z768), pk(cmul(z768, z4)));
  sts128(dst + 8192, pk(z1024), pk(cmul(z1024, z256)), pk(cmul(z1024, z512)), pk(cmul(z1024, z768)));
  sts32(scr + W_MISC + (wt >> 5) * 4, mx);
}
__device__ __forceinline__ int kgen_tables_m(uint32_t scr, int wt, const KgState& k) {
  const uint32_t dst = scr + wt * 16;
  const uint4 e4 = lds128(scr + W_MISC);
  const float2 z16 = csq(k.z8), z32 = csq(z16);
  const int em = max(min((int)(max(max(e4.x, e4.y), max(e4.z, e4.w)) >> 23), 238), 16);
  const float sc = __uint_as_float((uint32_t)(127 + 4 + 127 - em) << 23);
  sts32(scr + W_MISC + 16 + (wt >> 5) * 4, __reduce_add_sync(0xffffffffu, __float2int_rn(k.kl * sc * 262144.f)));
  const float2 c0 = make_float2(k.c0.x * sc, k.c0.y * sc);
  const float2 c1 = cmul(c0, k.z8), c2 = cmul(c0, z16), c4 = cmul(c0, z32), c3 = cmul(c1, z16), c5 = cmul(c1, z32), c6 = cmul(c2, z32), c7 = cmul(c3, z32);
  uint32_t pr[4], pi[4], yr[4], yi[4];
  pr[0] = pack_h(c0.x, c1.x); pi[0] = pack_h(c0.y, c1.y);
  pr[1] = pack_h(c2.x, c3.x); pi[1] = pack_h(c2.y, c3.y);
  pr[2] = pack_h(c4.x, c5.x); pi[2] = pack_h(c4.y, c5.y);
  pr[3] = pack_h(c6.x, c7.x); pi[3] = pack_h(c6.y, c7.y);
  sts128(dst, pr[0], pr[1], pr[2], pr[3]); sts128(dst + 2048, pi[0], pi[1], pi[2], pi[3]);
#pragma unroll
  for (int q = 1; q < 4; q++) {
    const uint32_t w = q == 1 ? k.w64 : q == 2 ? k.w128 : k.w192;
#pragma unroll
    for (int i = 0; i < 4; i++) pmul(pr[i], pi[i], w, yr[i], yi[i]);
    sts128(dst + q * 4096, yr[0], yr[1], yr[2], yr[3]); sts128(dst + q * 4096 + 2048, yi[0], yi[1], yi[2], yi[3]);
  }
  return em;
}
#define X_BC 0
#define BPIN
struct BuildC { uint32_t a3, a2, az, cw, l3, sel; };
__device__ __forceinline__ BuildC build_consts(int wt) {
  const int ix = ((wt >> 2) + (wt & 3) * 32 - 1) & 127;
  BuildC b;
  b.a3 = BPIN(W_CW + 32 + ((ix & 1) ? 0 : 304) + (ix >> 1) * 4);
  b.a2 = BPIN(W_L3 + 3072 + 544 + (wt & ~3) + (wt & 1) * 2 + (wt & 2) * 64);
  b.az = BPIN(W_KT + (wt < 36 ? -512 : 64 + 4128 - 576) + wt * 16);
  b.cw = BPIN(W_CW + 32 + (wt >> 6) * 48 + wt * 4);
  b.l3 = BPIN(W_L3 + 512 + (wt >> 6) * 512 + wt * 16);
  b.sel = BPIN((((wt & 1) || wt == 0) ? 0x7610 : 0x1010) | ((wt & 1) ? 0x10760000 : 0x10100000));
  return b;
}
__device__ __forceinline__ uint32_t prmt(uint32_t a, uint32_t b, uint32_t s) { uint32_t r; asm("prmt.b32 %0, %1, %2, %3;" : "=r"(r) : "r"(a), "r"(b), "r"(s)); return r; }
__device__ __forceinline__ void kgen_build(uint32_t tb, const BuildC& bc, int wg, int wt, uint32_t k0, uint32_t k1, uint32_t k2) {
  const uint32_t kt = tb + W_KT, sc = tb + W_L3 + 3072;
  const uint32_t v3 = wt ? k2 : k2 >> 16;
  sts32(sc + 4 + wt * 4, __byte_perm(k0, k1, 0x5432));
  sts16(tb + bc.a2, k1 >> 16);
  sts16(tb + bc.a3, v3); sts16(tb + bc.a3 + 6, v3);
  if ((unsigned)(wt - 32) < 18u) sts128(tb + bc.az, 0, 0, 0, 0);
  if (wt == 127) sts32(sc, k0 & 0xFFFF0000u);
  if (wt == 0) { sts32(sc + 516, k1); sts16(sc + 800, k2); }
  bar_sync(1 + wg, 128);
  const uint32_t cw = tb + bc.cw;
  const uint32_t pv = lds32(sc + wt * 4), nx = lds32(sc + 8 + wt * 4), c2 = lds16(sc + 544 + wt * 2), n2 = lds16(sc + 546 + wt * 2);
  sts128(tb + bc.l3, lds32(cw), lds32(cw - 8), lds32(cw - 16), lds32(cw - 24));
  const bool odd = wt & 1;
  sts64(kt + 64 + wt * 8, __byte_perm(k0, pv, 0x5410), __byte_perm(k0, 0, 0x1032));
  sts64(kt + 64 + 1024 + wt * 8, prmt(k1, pv, bc.sel), prmt(k1, nx, bc.sel >> 16));
  const uint32_t cc = c2 * 0x10001u, nc = __byte_perm(n2, c2, 0x5410), nn = n2 * 0x10001u;
  sts128(kt + 64 + 2048 + wt * 16, cc, cc, odd ? nc : cc, odd ? nn : nc);
  if (wt == 127) { sts128(kt + 64 + 4096, nn, nn, nn, nn); sts128(kt + 64 + 4112, nn, nn << 16, 0, 0); }
}

__device__ __forceinline__ void load_a(uint32_t (&a)[4], uint32_t kp, int j) {
  a[0] = lds32(kp + 64 * j); a[1] = lds32(kp + 64 * j + 512); a[2] = lds32(kp + 64 * j - 32); a[3] = lds32(kp + 64 * j + 480);
}
__device__ __forceinline__ uint32_t band(int d, int lo, int hi) {
  return ((unsigned)(d - lo) <= (unsigned)(hi - lo) ? 1u : 0u) | ((unsigned)(d - 1 - lo) <= (unsigned)(hi - lo) ? 0x10000u : 0u);
}
__device__ __forceinline__ uint32_t hadd2u(uint32_t a, uint32_t b) { __half2 r = __hadd2(*(__half2*)&a, *(__half2*)&b); return *(uint32_t*)&r; }

__device__ __forceinline__ void zero_pads(uint32_t tb, int wt) {
  if (!(wt & 32)) sts128(tb + W_L3 + (wt >> 6) * 512 + wt * 16, 0, 0, 0, 0);
  if ((wt & 63) < 3) sts128(tb + W_CW + (wt >> 6) * 304 + (wt & 63) * 16, 0, 0, 0, 0);
}
__device__ __forceinline__ uint32_t tr_base(int lane) {
  return OFF_YT + (2 * (lane >> 3) + (lane & 1)) * YT_PITCH + ((lane >> 1) & 1) * (8 * YT_PITCH + 64) + ((lane >> 2) & 1) * 16;
}

__device__ __forceinline__ uint32_t sc_addr(int tp) { return OFF_YT + (tp < 16 ? tp * YT_PITCH + (tp >> 3) * 64 + 1152 : 8 * YT_PITCH - 512 + tp * 32); }
#define X_PS 1
#define X_PW 15
#define X_HU 16
#define X_HB 0
#define X_REL 1
#define X_PAD0 0
#define X_PAD1 0
#define PAD(n) _Pragma("unroll") for (int _i = 0; _i < (n); _i++) asm volatile("pmevent 0;");
#ifndef M_
#define M_ 12
#endif
#define X_ES 1
#define X_NE 2
#define X_SCT 10000
#define X_DELTA 0
#define X_DSTEP 2000
#define X_PF0 2500
#define X_PFD 600
#define X_TD 450
#define X_WS 6
#define X_OR 8
#define X_ABS 4800
#define X_XD 200
#define X_RD 600
#define X_HD 400
#define X_PD 1080
#define X_PROMO 2
#define X_YD2 1000
#define X_GO 2
#define X_GW 2
#define X_NS 4400
#define X_XS 13600
#define X_LAG 1500
#define X_YD 1550
struct TMaps { CUtensorMap m[10]; };
__device__ __forceinline__ uint32_t h2bf(uint32_t w) { const float2 f = h2f(w); return pack_bf(f.x, f.y); }
__device__ __forceinline__ uint32_t keep(uint32_t v) { asm volatile("" : "+r"(v)); return v; }
__device__ __forceinline__ uint2 ldr64(const void* p) { uint2 v; asm volatile("{ .reg .b64 t; ld.relaxed.gpu.global.b64 t, [%2]; mov.b64 {%0, %1}, t; }" : "=r"(v.x), "=r"(v.y) : "l"(p) : "memory"); return v; }
__host__ __device__ __forceinline__ uint32_t down_box(int s, bool five) {
  return five ? OFF_W + W_BYTES + 12288 + (s / 3) * (W_BYTES - 12288) + s * 4096 : s < 6 ? OFF_W + W_BYTES + BOX + (s >> 1) * (W_BYTES - 10240) + s * 5120 : OFF_W + (s - 6) * 5120;
}
__device__ __forceinline__ void load_tile(const CUtensorMap* tmx, int i, int c, int again = 0) {
  asm volatile("mbarrier.arrive.expect_tx.shared::cta.b64 _, [%0], 8704;" :: "r"(MB_UL + i * 16 + again) : "memory");
  asm volatile("cp.async.bulk.tensor.3d.shared::cluster.global.mbarrier::complete_tx::bytes [%0], [%1, {%3, %4, %5}], [%2];"
               :: "r"(i < 2 ? OFF_T + i * TILE : OFF_W), "l"(tmx), "r"(MB_UL + i * 16 + again), "r"(0), "r"(c), "r"(-8) : "memory");
}
template <bool FAR> __device__ __forceinline__ void load_params(const Params& p, uint32_t ch, int wt, uint32_t dst, bool on) {
  const int rel = wt < 96 ? ch * 16 + (wt & 15) : ch >> 3;
  const unsigned char* b = FAR ? p.far[min(wt >> 4, 6)] + rel * 16 : p.x + (long long)(p.off[wt >> 4] + rel) * 16;
  asm volatile("{ .reg .pred q; setp.ne.u32 q, %2, 0; @q cp.async.cg.shared.global [%0], [%1], 16; }"
               :: "r"(dst + wt * 16), "l"(b), "r"((uint32_t)(on && wt < 97)) : "memory");
}

struct ConvC { uint32_t ca, cb, bands; };
__device__ __forceinline__ ConvC conv_consts(int w, int lane) {
  const int h = w & 1, P = (w >> 1) & 1, d0 = 8 * h + (lane >> 2) - 2 * (lane & 3);
  ConvC k;
  k.ca = keep((W_KT + (16 + 256 * P + d0) * 4) | (((8 + 64 * P + lane) * 64 + (((h + ((w >> 1) & 2)) ^ (lane >> 1)) & 3) * 16) << 16));
  k.cb = keep(lane < 8 ? 0xFFFEFFFEu : ~0u);
  k.bands = keep(band(d0, 12, 20) + 2 * band(d0 + 8, 12, 20) + 4 * band(d0 + 16, 12, 20) + 8 * band(d0 + 24, 12, 20)
                 + 16 * band(d0 - 8, 5, 11) + 32 * band(d0, 5, 11) + 64 * band(d0 + 8, 5, 11) + 128 * band(d0 + 16, 5, 11));
  return k;
}
struct ConvPre { uint32_t e0, e2, f2, a[3][4]; };
__device__ __forceinline__ uint32_t lds32_if(uint32_t a, bool on) {
  uint32_t v; asm volatile("{ .reg .pred q; setp.ne.u32 q, %2, 0; mov.b32 %0, 0; @q ld.shared.b32 %0, [%1]; }" : "=r"(v) : "r"(a), "r"((uint32_t)on) : "memory"); return v;
}
__device__ __forceinline__ void conv_pre(ConvPre& r, uint32_t kp, int part, bool on, bool P) {
  if (part & 1) { r.e0 = lds32_if(kp + 4096, on && !P); r.e2 = lds32_if(kp + 4064, on && !P); r.f2 = lds32_if(kp + 4128, on && !P); }
#pragma unroll
  for (int j = 0; j < 3; j++) if (part & (j < X_PS ? 1 : 2)) {
    r.a[j][0] = lds32_if(kp + 2048 + 64 * j, on); r.a[j][1] = lds32_if(kp + 2560 + 64 * j, on); r.a[j][2] = lds32_if(kp + 2016 + 64 * j, on); r.a[j][3] = lds32_if(kp + 2528 + 64 * j, on);
  }
}
__device__ __forceinline__ void conv_item(uint32_t tb, uint32_t tl, int bid, int bn, ConvPre& pre, const ConvC& cv, uint32_t zero, const CUtensorMap* tmx, int ch, int warp, int lane, bool hold, bool more) {
  const bool go = more && warp == 0 && lane == 0;
  const uint32_t kp = tb + (cv.ca & 0xFFFFu);
  const uint32_t dlo = (tl >> 4) + 32 + ((warp >> 1) & 2) + (1u << 16), dhi = 32u | (2u << 30);
  const bool P = warp & 2;
  float a32[16], b32[16], a64[32];
  uint32_t A[40][4];
#define STEP(J) { wgmma64<0>(a64, A[J], dlo + 256 - 4 * (J), dhi); \
    if ((J) == 32) wgmma32_init<0>(b32, A[J], dlo, dhi); else wgmma32<0>(b32, A[J], ((J) < 8 ? dlo ^ zero : dlo) + 128 - 4 * (J), dhi); \
    if ((J) == 0) wgmma32_init<0>(a32, A[J], dlo, dhi); else if ((J) < 8) wgmma32<0>(a32, A[J], (dlo ^ zero) - 4 * (J), dhi); }
#define LD(J) load_a(A[J], kp, J);
#define FIRST(J) wg_fence(); STEP(J) wg_commit(); wg_wait<1>(); wg_fence();
  {
    uint32_t win[16], x9[4], x7[4], e[4], f[4];
    const uint32_t bz = keep(cv.bands);
#define BAND(i) keep((bz & (0x10001u << (i))) * (0x3C00u >> (i)))
    e[0] = pre.e0; e[2] = pre.e2; e[1] = keep(bz & 0x100u); e[3] = keep(bz & 0x200u);
    f[2] = pre.f2; f[0] = keep(bz & 0x4000u); f[1] = keep(bz & 0x8000u); f[3] = keep(bz & 0x300u);
#pragma unroll
    for (int j = 0; j < 12; j++) A[32 + j / 4][j & 3] = pre.a[j / 4][j & 3];
    const uint32_t q[12] = {BAND(0), BAND(5), keep(bz & 0x400u), BAND(4), BAND(2), BAND(7), BAND(1), BAND(6), keep(bz & 0x800u), keep(bz & 0x1000u), BAND(3), keep(bz & 0x2000u)};
#undef BAND
    const uint32_t ta = keep(tl + 512 + (warp & 3) * 2048 + lane * 64 + (lane & 6) * 8);
    if (X_GO && hold) mbar_wait(MB_GO);
    uint32_t mbl = MB_UL + (warp & 8) * 2, ph = 0;
#pragma unroll 1
    for (int it = 0; it < SPIN_MAX; it++) {
      if (ch < 512) mbar_wait(mbl, ph);
      if (it == 1) TS(13);
      TS(3);
      wg_fence();
      wgmma64h_init(win, q[0], q[1], q[2], q[3], dlo, dhi);
      wgmma64h(win, q[4], q[5], q[6], q[7], dlo - 4, dhi);
      wgmma64h(win, q[8], q[9], q[10], q[11], dlo - 8, dhi);
      wg_commit();
      wgmma64_init<0>(a64, e, dlo, dhi);
      wgmma64<0>(a64, f, dlo - 4, dhi);
      wg_commit();
      if (ch >= 512) break;
      uint32_t r0, r1, r2, r3, ok;
      if (warp & 4) {
        mbar_wait(mbl + 8);
        if (__all_sync(0xffffffffu, it || lds32(MISC_RT + (warp & 8)) == 0)) break;
        wg_wait<0>();
        continue;
      }
      ldsm4(ta, r0, r1, r2, r3);
      ok = r0 & r1 & r2 & r3;
      ldsm4(ta ^ 32, r0, r1, r2, r3);
      asm volatile("{ .reg .pred q; setp.ne.u32 q, %1, 0; barrier.red.and.pred q, %2, 128, q; selp.u32 %0, 1, 0, q; }" : "=r"(ok) : "r"((ok & r0 & r1 & r2 & r3 & 1u) | (lane & 3)), "r"(1 + (warp >> 2)) : "memory");
      if (ok) { if ((warp & 3) == 0 && lane == 0) { sts32(MISC_RT + warp, it); mbar_arrive(MB_UL + 8 + warp * 2); } break; }
      wg_wait<0>();
      if ((warp & 3) == 0 && lane == 0) load_tile(tmx - 1, warp >> 3, ch, 56);
      mbl = MB_UL + 56 + (warp & 8) * 2; ph = it & 1;
    }
    wg_wait<1>();
#pragma unroll
    for (int i = 0; i < 4; i++) {
      const int tl = 2 * ((i & 1) + ((i & 2) ? 0 : 4));
      x9[i] = P ? win[tl + 4] : win[tl]; x7[i] = P ? win[tl + 5] : win[tl + 1];
    }
    const uint32_t l3lo = ((tb + W_L3) >> 4) + (32u << 16);
    wg_fence();
    wgmma64<0>(a64, x9, l3lo, 8);
    wgmma64<0>(a64, x7, l3lo + 96, 8);
    wg_commit();
  }
  STEP(32) STEP(33) STEP(34) wg_commit(); wg_wait<1>();
  LD(35) LD(36) LD(37) LD(38)
  FIRST(35) STEP(36) STEP(37) STEP(38) wg_commit();
  LD(39) LD(0)
  TS(17);
  if (X_GO == 1 && go) mbar_arrive(MB_GO);
  FIRST(39) STEP(0) wg_commit();
  LD(1) LD(2) LD(3)
  FIRST(1) STEP(2) STEP(3) wg_commit();
  LD(4) LD(5)
  if (X_GO == 2 && go) mbar_arrive(MB_GO);
  FIRST(4) STEP(5) wg_commit();
  LD(6) LD(7)
  wg_fence(); STEP(6) STEP(7) wg_commit();
#undef STEP
#undef LD
#undef FIRST
  TS(18);
  if (X_GO == 3 && go) mbar_arrive(MB_GO);
  const uint32_t xc = tb + W_KT + (warp & 3) * 1024 + lane * 16;
  if (more) bar_sync(7, 288);
  wg_wait<1>();
  conv_pre(pre, kp + ALT, 1, more, P);
  wg_wait<0>();
  conv_pre(pre, kp + ALT, 2, more, P);
  uint32_t E[16], o[8];
#define ACC(i) ((i) < 16 ? a32[i] : (i) < 32 ? b32[(i) - 16] : a64[(i) - 32])
  E[0] = pack_h(a32[0], a32[1]);
#pragma unroll
  for (int i = 1; i < 16; i++) E[i] = pack_h(ACC(4 * i) + ACC(4 * i - 2), ACC(4 * i + 1) + ACC(4 * i - 1));
#undef ACC
#pragma unroll
  for (int j = 0; j < 8; j++) o[j] = P ? (j < 2 ? 0u : E[j - 2]) : E[8 + j];
  sts128(xc, o[0], o[1], o[2], o[3]); sts128(xc + 512, o[4], o[5], o[6], o[7]);
#pragma unroll
  for (int j = 0; j < 8; j++) o[j] = P ? E[6 + j] : E[j];
  TS(25);
  if (more) {
    sts128(xc + 4096, o[0], o[1], o[2], o[3]); sts128(xc + 4608, o[4], o[5], o[6], o[7]);
    bar_arrive(12, 192);
    return;
  }
  bar_sync(1 + (warp >> 2), 128);
  const uint4 vv[2] = {lds128(xc + (P ? -2048 : 2048)), lds128(xc + (P ? -1536 : 2560))};
#pragma unroll
  for (int q = 0; q < 2; q++) {
    const uint4 v = vv[q];
    stsm4t(tl + (cv.ca >> 16) + q * 2048, hadd2u(o[4 * q], v.x) & cv.cb, hadd2u(o[4 * q + 1], v.y) & cv.cb, hadd2u(o[4 * q + 2], v.z) & cv.cb, hadd2u(o[4 * q + 3], v.w) & cv.cb);
  }
  fence_async();
  bar_sync(bid, bn);
  if (warp == 0 && lane == 0) mbar_arrive(MB_REL);
  if ((warp & 7) == (ch < 512 ? 7 : 3) && lane == 0) {
    asm volatile("cp.async.bulk.tensor.3d.global.shared::cta.bulk_group [%0, {%3, %2, %3}], [%1];" :: "l"(tmx), "r"(tl + 512), "r"(ch), "r"(0) : "memory");
    asm volatile("cp.async.bulk.commit_group;" ::: "memory");
  }
}

template <bool FAR> __global__ void __launch_bounds__(NT, 1)
fused_kernel(const __grid_constant__ Params p, const __grid_constant__ TMaps tm) {
  extern __shared__ __align__(1024) unsigned char smem[];
  const int c = blockIdx.x;
  const bool five = (c & 1) == 0;
  const uint32_t pitch = five ? 64 : 80;
  const uint32_t ones = 0x3F803F80u;
  const int tid = threadIdx.x, lane = tid & 31;
  const uint32_t xrow = OFF_YT + ((tid & 127) >> 3) * YT_PITCH + (tid & 64) + (tid & 7) * 16;
  {
    const int w4 = tid >> 7;
    load_params<FAR>(p, w4 < 2 ? 2 * c + w4 : five ? 257 + 2 * c : 512 + (c >> 1), tid & 127, OFF_W + W_KT + (w4 < 2 ? w4 * W_BYTES : five ? 3 * W_BYTES : 3 * W_BYTES + 2048), (0xB >> w4) & 1);
  }
  if ((tid >> 7) == 2) {
    const unsigned char* xp = p.x + (uint32_t)((c * 16 - 32 + (tid >> 3)) * 1152 + (tid & 7) * 16);
    asm volatile("" : "+l"(xp));
    { const uint32_t tq = clock(); while ((int)(clock() - tq) < X_XD) {} }
#pragma unroll
    for (int k = 0; k < 9; k++) asm volatile("cp.async.cg.shared.global [%0], [%1], 16;" :: "r"(xrow + k * 128), "l"(xp + k * 128) : "memory");
  }
  const int warp = (int)uni(tid >> 5), wg = warp >> 2;
  TS(0);
  if (__builtin_expect(wg == 4, 0)) {
    asm volatile("setmaxnreg.dec.sync.aligned.u32 32;");
    const int role = warp;
    const int u0 = (c >> 1) * 9 + (five ? ((c & 2) ? 5 : 0) : ((c & 2) ? 0 : 4));
    const uint32_t t0 = clock() + c * 4;
    if (role == 16) {
      if (lane < 19) asm volatile("mbarrier.init.shared::cta.b64 [%0], %1;" :: "r"(OFF_MISC + lane * 8), "r"((unsigned)(lane - 2) < 4u ? 4 : 1) : "memory");
      if (lane < 2) asm volatile("mbarrier.arrive.expect_tx.shared::cta.b64 _, [%0], %1;" :: "r"(OFF_MISC + lane * 8), "r"(lane ? (five ? 36864 : 51200) : pitch * 1152) : "memory");
      fence_async();
      bar_arrive(5, 608);
      const CUtensorMap* tmb = &tm.m[five ? 3 : 0];
#pragma unroll 1
      for (int u = 0; u < 17; u++) {
        const uint32_t e = p.sched[five][u], kind = e & 3, s = (e >> 2) & 15, dst = e >> 14;
        if (kind == 3) continue;
        while ((int)(clock() - t0) < X_PF0 + (u < X_NE ? u * X_PFD : X_LAG + u * X_TD)) __nanosleep(20);
        if (e & 0x3FC0) mbar_wait(OFF_MISC + ((e >> 6) & 255));
        if (lane == 0) {
          if (kind == 2) asm volatile("cp.async.bulk.tensor.3d.shared::cluster.global.mbarrier::complete_tx::bytes [%0], [%1, {%3, %4, %5}], [%2];"
                                      :: "r"(dst), "l"(tmb + 2), "r"(MB_D), "r"(0), "r"(u0 * 8), "r"(s) : "memory");
          else tma_box(dst, tmb + kind, MB_GU, u0 * 8, s * 96);
        }
        if (u == 5) TS(2);
        if (u == 10) TS(3);
      }
      TS(4);
      TS_DUMP();
#define FINISH0 bar_sync(12, 192);        \
        _Pragma("unroll 1") for (int w = role & 2; w < (role & 2) + 2; w++) { \
          const uint32_t xa = OFF_W + W_KT + lane * 16, mk = lane < 8 ? 0xFFFEFFFEu : ~0u, ya = OFF_T + (8 + lane) * 64 + (((w & 1) ^ (lane >> 1)) & 3) * 16 + (w & 2) * 2048; \
          const uint4 a = lds128(xa + 4096 + w * 1024), b = lds128(xa + (w ^ 2) * 1024), d = lds128(xa + 4608 + w * 1024), e = lds128(xa + 512 + (w ^ 2) * 1024); \
          stsm4t(ya, hadd2u(a.x, b.x) & mk, hadd2u(a.y, b.y) & mk, hadd2u(a.z, b.z) & mk, hadd2u(a.w, b.w) & mk); \
          stsm4t(ya + 2048, hadd2u(d.x, e.x) & mk, hadd2u(d.y, e.y) & mk, hadd2u(d.z, e.z) & mk, hadd2u(d.w, e.w) & mk); \
        } \
        fence_async();
    } else if (role == 17) {
      if (smem_u32(smem) != SB) __trap();
      bar_sync(10, 576);
      if (lane == 0) {
        fence_async();
        while ((int)(clock() - t0) < X_NS - c * 4) {}
        asm volatile("cp.async.bulk.global.shared::cta.bulk_group [%0], [%1], 10240;" :: "l"(&p.s->X[c * DM * 2 + 512]), "r"(OFF_G) : "memory");
        asm volatile("cp.async.bulk.commit_group;" ::: "memory");
        asm volatile("cp.async.bulk.wait_group 0;" ::: "memory");
      }
      if (lane == 0) mbar_arrive(MB_GF);
      bar_arrive(11, 96);
      if (five) { FINISH0 bar_arrive(13, 192); }
    } else if (role == 18) {
      sts32(MISC_EPOCH, 0);
      sts32(MISC_T0, t0 - c * 4);
      bar_arrive(5, 608);
      uint4* q = lane < 2 ? &p.s->R[c * 2 + lane] : lane < 11 ? &p.s->HS[c * 9 + lane - 2] : lane == 11 ? &p.s->HS[1152 + (c & 7)] : (uint4*)&p.s->FLAG[c * 8];
      if (lane < (c < 8 ? 12 : 11)) str128(q, ~0u, ~0u, ~0u, ~0u);
      const uint32_t ep = __shfl_sync(0xffffffffu, ldr32(q), 31) + 1u;
      sts32(MISC_EPOCH, ep | 0x80000000u);
      TSX(21);
      if (lane == 31) str32(q, ep);
      bar_sync(11, 96);
      TSX(14);
      mbar_wait(MB_KF + (lane & 3) * 8);
      __syncwarp();
      { const uint2 e = lds64(MISC_EM); if (lane < 2) str128(&p.s->SC[c * 2 + lane], e.x, __byte_perm(e.y, ep, 0x6540), 0, 0); }
      TSX(17);
      while ((int)(clock() - t0) < X_SCT) __nanosleep(100);
      TSX(18);
      {
        uint2 v[4];
#pragma unroll 1
        for (int it = 0; it < SPIN_MAX; it++) {
          uint32_t bad = 0;
#pragma unroll
          for (int q = 0; q < 4; q++) v[q] = ldr64(&p.s->SC[lane * 2 + q * 64]);
#pragma unroll
          for (int q = 0; q < 4; q++) bad |= (v[q].y >> 8) ^ (ep & 0xFFFFFFu);
          if (!__any_sync(0xffffffffu, bad)) break;
        }
        TSX(25);
#pragma unroll
        for (int q = 0; q < 4; q++) {
          const uint32_t sa = (lane >> 4) * YT_PITCH + (lane & 15) * 2;
          sts16(sc_addr(2 * q) + sa, v[q].x); sts16(sc_addr(8 + 2 * q) + sa, v[q].x >> 16);
          if (lane & 1) asm volatile("st.shared.u8 [%0], %1;" :: "r"(sc_addr(16) + q * 16 + (lane >> 1)), "r"(v[q].y) : "memory");
        }
      }
      __syncwarp();
      if (lane == 0) mbar_arrive(MB_SC);
      TSX(27);
    } else {
      uint32_t w[9];
      const uint32_t dk = ldnc16(p.dskip + ((lane & 4) ? 512 + (c >> 1) : (lane & 2) * 128 + 2 * c + (lane & 1)));
      float s = 0.f;
#pragma unroll
      for (int i = 0; i < 9; i++) w[i] = ldnc32(p.w_r + lane + 32 * i);
      sts16(OFF_WR + 1152 + lane * 2, dk);
      bar_arrive(5, 608);
#pragma unroll
      for (int i = 0; i < 9; i++) { sts32(OFF_WR + lane * 4 + i * 128, w[i]); s += bf_lo(w[i]) + bf_hi(w[i]); }
      sts32(MISC_SW, __float_as_uint(warp_sum(s)));
      TSX(23);
      bar_sync(10, 576);
      if (lane == 0) {
        const uint32_t tp = clock();
        TSX(1);
        while ((int)(clock() - tp) < X_DELTA || (int)(clock() - t0) < X_ABS - c * 4) {}
        TSX(24);
        load_tile(&tm.m[6], 0, c);
        TSX(15);
        while ((int)(clock() - t0) < X_ABS + X_DSTEP - c * 4) {}
      }
      bar_sync(11, 96);
      if (lane == 0) {
        load_tile(&tm.m[6], 1, 128 + c);
      }
      if (five) {
        mbar_wait(MB_KF);
#pragma unroll 1
        for (int it = 0; it < SPIN_MAX; it++) {
          if (lane == 0) load_tile(&tm.m[8], 2, 512 + (c >> 1));
          mbar_wait(MB_UL + 32, it & 1);
          uint32_t m = 1;
#pragma unroll
          for (int q = 0; q < 4; q++) { uint32_t r0, r1, r2, r3; ldsm4(OFF_W + 512 + lane * 64 + (lane & 6) * 8 + q * 2048, r0, r1, r2, r3); m &= r0 & r1 & r2 & r3; }
          if (__all_sync(0xffffffffu, m || (lane & 3))) break;
        }
        bar_arrive(7, 288);
        FINISH0
        bar_arrive(13, 192);
      }
      bar_sync(0, 544);
      if (lane == 0) mbar_arrive(MB_H);
    }
    return;
  }
  const int wt = tid & 127, g = lane >> 2, t = lane & 3;
  const uint32_t wb = OFF_W + wg * W_BYTES;
  asm volatile("cp.async.commit_group;" ::: "memory");
  const ConvC cv = conv_consts(warp, lane);
  zero_pads(wb, wt);
  load_params<FAR>(p, 254 + 2 * c + wg, wt, wb + W_KT, wg == 2 || (wg == 3 && !five));
  asm volatile("cp.async.commit_group;" ::: "memory");
  asm volatile("setmaxnreg.inc.sync.aligned.u32 112;");
  PAD(X_PAD0)
  {
    uint4 kw;
    uint4* kx = &p.s->KX[(c >> 1) * 128 + wt];
    bool two = wg == 3;
    uint32_t ep;
    int em = 0;
    BuildC bc;
    uint32_t slot = wg + (two && !five);
    const uint32_t ra0 = wb + W_KT + (slot & 4) * 512 + wt * 2, ra6 = wb + W_KT + 1536 + (slot & 4) * 512 + (((slot & 4) ? c >> 1 : 2 * c + (wg & 1)) & 7) * 2;
    uint32_t raw[7];
    if (wg != 2) {
      asm volatile("cp.async.wait_group 1;" ::: "memory");
      bar_sync(1 + wg, 128);
#pragma unroll
      for (int i = 0; i < 7; i++) raw[i] = lds16(i < 6 ? ra0 + i * 256 : ra6);
    }
    int phase = wg == 2 ? 3 : 2;
#pragma unroll 1
    for (;;) {
      if (phase != 3) {
        KgState ks;
        TS(22);
        kgen_tables_n(raw, wb, wt, ks);
        TS(20);
        bar_sync(1 + wg, 128);
        em = kgen_tables_m(wb, wt, ks);
        fence_async();
      }
      if (phase & 2) {
        const int lz = lane ^ (clock() & p.off[7]), wz = (wt & 96) | lz;
        const uint32_t tr_addr = pin(tr_base(lz) + warp * 32), lca = pin(MISC_LN1 + (lz & 1) * 16);
        uint4* dst;
        { const unsigned long long a = (unsigned long long)&p.s->X[c * DM * 2 + warp * 32 + (8 * ((lz >> 1) & 1) + (lz >> 2)) * 2 + (lz & 1)];
          dst = (uint4*)(((unsigned long long)pin(a >> 32) << 32) | pin((uint32_t)a)); }
        if (X_BC) bc = build_consts(wz);
        if (phase == 3) {
        asm volatile("cp.async.wait_group 1;" ::: "memory");
        TS(21);
        float d[3][4], r;
        uint4 a[9];
#pragma unroll
        for (int k = 0; k < 9; k++) a[k] = lds128(xrow + k * 128);
#pragma unroll
        for (int i = 0; i < 4; i++) d[0][i] = d[1][i] = d[2][i] = 0.f;
#pragma unroll
        for (int k = 0; k < 9; k++) { mma_bf16(d[(2 * k) % 3], a[k].x, ones, a[k].y, ones, a[k].x, a[k].y); mma_bf16(d[(2 * k + 1) % 3], a[k].z, ones, a[k].w, ones, a[k].z, a[k].w); }
#pragma unroll
        for (int i = 0; i < 4; i++) d[0][i] += d[1][i] + d[2][i];
        const LnC lc = ln_consts(d[0][2] + d[0][3], __shfl_sync(0xffffffffu, d[0][0], 9 * t) + __shfl_sync(0xffffffffu, d[0][1], 9 * t + 4), r);
        if (lane < 12) sts16(MISC_LN1 + g * 32 + (warp & 3) * 8 + t * 2, lane < 4 ? lc.m2 : lane < 8 ? lc.rh2 : lc.rl2);
        }
        asm volatile("cp.async.wait_group 0;" ::: "memory");
        TS(23);
        bar_sync(5, 608);
        uint32_t x[3][4];
        ldsm4t(tr_addr, x[0][0], x[0][1], x[0][2], x[0][3]);
        uint4 m = lds128(lca);
        const uint4 rl = lds128(lca + 64), rh = lds128(lca + 32);
        ldsm4t(tr_addr + 512, x[1][0], x[1][1], x[1][2], x[1][3]);
        if (wg == 3) ldsm4t(tr_addr + 640, x[2][0], x[2][1], x[2][2], x[2][3]);
#pragma unroll
        for (int q = 0; q < 3; q++) {
          if (q < 2 || wg == 3) {
            const uint32_t r0 = ln_apply(x[q][0], m.x, rh.x, rl.x), r1 = ln_apply(x[q][1], m.y, rh.y, rl.y), r2 = ln_apply(x[q][2], m.z, rh.z, rl.z), r3 = ln_apply(x[q][3], m.w, rh.w, rl.w);
            const uint32_t w0 = (pack_h(bf_lo(r0), bf_hi(r0)) & 0xFFFEFFFEu) | 1u, w1 = pack_h(bf_lo(r1), bf_hi(r1)), w2 = pack_h(bf_lo(r2), bf_hi(r2)), w3 = pack_h(bf_lo(r3), bf_hi(r3));
            if (q == 0) str128(dst, w0, w1, w2, w3);
            else sts128(OFF_G + warp * 512 + (8 * (t >> 1) + g) * 32 + (t & 1) * 16 + (q == 2 ? 2048 : 0), w0, w1, w2, w3);
          }
          if (q == 0 && X_ES) {
            const uint32_t z = clock() & p.off[7];
            m.x ^= z; m.y ^= z; m.z ^= z; m.w ^= z;
          }
          if (q == 0) TS(30);
          if (q == 0 && wg >= 2) {
#pragma unroll
            for (int i = 0; i < 7; i++) raw[i] = lds16(wb + W_KT + i * 256 + (i < 6 ? wt : (2 * c + (wg & 1)) & 7) * 2);
          }
        }
        bar_arrive(10, 576);
        TS(1);
      } else bar_sync(1 + wg, 128);
      phase &= 1;
      if (phase) { phase = 0; continue; }
      TS(14);
      float acc[20];
      const uint32_t alo = (wb >> 4) | (8u << 16);
      uint4 k4 = lds128(wb + W_MISC + 16);
      uint32_t dk = lds16(OFF_WR + 1152 + slot * 2);
      wg_fence();
      wgmma40_ss_init(acc, alo, alo + 1024, 2048 >> 4);
#pragma unroll
      for (int k = 1; k < 8; k++) wgmma40_ss(acc, alo + k * 16, alo + 1024 + k * 16, 2048 >> 4);
      wg_commit();
      { const uint32_t z = clock() & p.off[7]; dk ^= z; k4.x ^= z; k4.z ^= z; }
      const float k2048 = (float)(int)((k4.x + k4.y) + (k4.z + k4.w)) * (1.f / 262144.f);
      const int ef = max(em, min((int)((dk >> 7) & 255u) - 7, 238));
      asm volatile("st.shared.u8 [%0], %1;" :: "r"(MISC_EM + slot), "r"(ef + 9) : "memory");
      const float un = __uint_as_float((uint32_t)max(114 + em - ef, 0) << 23), d0 = wt ? 0.f : bf_lo(dk) * __uint_as_float((uint32_t)(245 - ef) << 23);
      wg_wait<0>();
      kw.x = pack_h(fmaf(acc[0] - acc[3], un, d0), (acc[4] - acc[7]) * un);
      kw.y = pack_h((acc[8] - acc[11]) * un, (acc[12] - acc[15]) * un);
      kw.z = pack_h((acc[16] - acc[19]) * un, k2048 * un);
      TS(24);
      ep = 0;
      if (two) SPIN_WHILE(ep == 0, ep = lds32(MISC_EPOCH));
      if (five || !two) break;
      str128(kx, kw.x, kw.y, kw.z, ep);
      two = false;
      slot = 3;
      bar_sync(1 + wg, 128);
    }
    if (lane == 0) mbar_arrive(MB_KF + wg * 8);
    if (two) { mbar_wait(MB_KF); zero_pads(OFF_W + ALT, wt); }
    uint32_t tb = wb;
    if (!X_BC) bc = build_consts(wt);
#pragma unroll 1
    for (;;) {
      kgen_build(tb, bc, wg, wt, kw.x, kw.y, kw.z);
      TS(15);
      if (!two) break;
      two = false;
      kw.w = 0;
      SPIN_WHILE(kw.w != ep, kw = ldr128(kx));
      tb = OFF_W + ALT;
    }
    fence_async();
    TS(31);
    if (tb != wb) bar_arrive(7, 288);
    bar_sync(1 + wg, 128);
  }
  uint32_t tpub;
  ConvPre pre;
  conv_pre(pre, (wb ^ p.off[7]) + (cv.ca & 0xFFFFu), 3, true, warp & 2);
#pragma unroll 1
  for (int item = 0;; item++) {
    TS(2);
    conv_item(item ? OFF_W + ALT : wb, item ? OFF_W : OFF_T + (wg >> 1) * TILE, item ? 1 : 13 + (wg >> 1), item ? 128 : five && wg == 1 ? 192 : 256, pre, cv, p.off[7],
              &tm.m[item ? 9 : 7], item ? 512 + (c >> 1) : (wg >> 1) * 128 + c, warp, lane, five && wg >= X_GW, five && !wg && !item);
    tpub = clock() - (item ? X_YD : wg >= 2 ? X_YD2 : 0);
    if (wg || !five || item) break;
    TS(27);
  }
  TS(4);
  PAD(X_PAD1)

  const int ln = lane ^ p.off[7], td = warp * 32 + ln, gg = ln >> 2, tt = ln & 3;
  const int tok = c * 16 + warp;
  const int fu = warp / 3, fk = warp - fu * 3;
  uint32_t wa[12][4];
  uint4 ha[3];
  const uint4* hsrc = &p.s->HS[td + (td / 24) * 48];
  {
    uint32_t hw[9], wr[9];
    const uint32_t row = keep(OFF_YT + warp * YT_PITCH + (warp >> 3) * 64 + ln * 16);
    const uint32_t wabase = keep(((ln & 8) ? OFF_W + (fk + 1) * W_BYTES : OFF_G + fk * 192 * pitch) + ((ln >> 4) * 8 + (ln & 7)) * pitch
                                 + (five ? ((fu ^ (ln >> 1)) & 3) : min(fu, 4)) * 16);
    float sw;
    {
      const bool three = wg == 1;
      const int ch = 8 * (tt >> 1) + gg;
      const uint32_t tr_addr = tr_base(ln);
      const uint4* ysrc = &p.s->X[c * DM * 2 + ch * 2 + (tt & 1)];
      uint32_t x[3][4], s[3];
      uint4 v[3];
#define TL(q) ((q) < 2 ? 2 * warp + (q) : 28 + warp)
      asm volatile("cp.async.bulk.wait_group.read 0;" ::: "memory");
      if (wg >= 2) { const uint32_t ts = lds32(MISC_T0); while ((int)(clock() - ts) < X_XS) {} }
      while ((int)(clock() - tpub) < X_YD) {}
      TS(5);
      v[0] = ldr128(ysrc + TL(0) * 32); v[1] = ldr128(ysrc + TL(1) * 32); v[2] = make_uint4(three, 0, 0, 0);
      if (X_REL == 1 || (X_REL == 2 && wg != 1)) mbar_wait(MB_REL);
#pragma unroll
      for (int i = 0; i < 6; i++) if (i < 4 || three) wr[i] = (gg & 2) ? ones : lds32(OFF_WR + TL(i >> 1) * 32 + (i & 1) * 16 + tt * 4);
      const uint32_t ha = keep(OFF_YT + (ln & 7) * YT_PITCH + (ln >> 4) * (8 * YT_PITCH + 64) + (ln & 8) * 2);
      const uint32_t pa = keep(OFF_PART + warp * 4 + ((gg & 2) * 8 + (gg & 4) * 2 + 2 * tt + (gg & 1)) * 80), pb = keep(OFF_PART + 2560 + warp * 4 + gg * 80);
      float dl[4] = {0.f, 0.f, 0.f, 0.f}, dh[4] = {0.f, 0.f, 0.f, 0.f};
      sw = __uint_as_float(lds32(MISC_SW));
#pragma unroll
      for (int q = 0; q < 3; q++) {
        if (q < 2 || three) {
          ldsm4t(tr_addr + TL(q) * 32, x[q][0], x[q][1], x[q][2], x[q][3]);
        }
      }
      mbar_wait(MB_SC);
#pragma unroll
      for (int q = 0; q < 3; q++) {
        asm volatile("ld.shared.u8 %0, [%1];" : "=r"(s[q]) : "r"((q < 2 ? sc_addr(warp) + q * 16 : sc_addr(16) + (warp & 3) * 16) + ch) : "memory");
        s[q] = keep(s[q] * 0x800080u);
      }
#define FIN(q) stsm4t(tr_addr + TL(q) * 32, bf_fma2(h2bf(v[q].x), s[q], x[q][0]), bf_fma2(h2bf(v[q].y), s[q], x[q][1]), bf_fma2(h2bf(v[q].z), s[q], x[q][2]), bf_fma2(h2bf(v[q].w), s[q], x[q][3]));
      SPIN_WHILE((v[0].x | v[1].x) & 1u, _Pragma("unroll") for (int q = 0; q < 3; q++) if (v[q].x & 1u) v[q] = ldr128(ysrc + TL(q) * 32));
      if (v[2].x & 1u) v[2] = ldr128(ysrc + TL(2) * 32);
#define STAT(q) { uint32_t r0, r1, r2, r3; ldsm4(ha + TL(q) * 32, r0, r1, r2, r3); \
        mma_bf16(dl, r0, wr[2 * q], r1, wr[2 * q + 1], r0, r1); mma_bf16(dh, r2, wr[2 * q], r3, wr[2 * q + 1], r2, r3); }
      FIN(0) FIN(1)
      __syncwarp();
      STAT(0) STAT(1)
      if (three) {
        SPIN_WHILE(v[2].x & 1u, if (v[2].x & 1u) v[2] = ldr128(ysrc + TL(2) * 32));
        FIN(2)
        __syncwarp();
        STAT(2)
      }
      if (gg & 1) { dl[0] = dl[1]; dl[2] = dl[3]; dh[0] = dh[1]; dh[2] = dh[3]; }
      sts32(pa, __float_as_uint((gg & 4) ? dh[2] : dl[2]));
      if (tt == (gg >> 1)) { sts32(pb, __float_as_uint(dl[0])); sts32(pb + 640, __float_as_uint(dh[0])); }
#undef STAT
#undef FIN
#undef TL
    }
    uint32_t ra = keep(OFF_PART + (ln & 15) * 80 + (ln & 16) * 2);
    uint16_t* rp = (uint16_t*)p.s->R + c * 16 + (ln & 15);
    const uint2* rsrc = (const uint2*)p.s->R + td;
    asm volatile("" : "+l"(rp), "+l"(rsrc), "+l"(hsrc));
    uint2 rv = make_uint2(0u, 0u);
    TS(28);
    if (warp != X_PW) bar_sync(0, 544);
    else {
      float z[3], rd;
      asm volatile("bar.sync 0, 544;" : "+r"(ra) :: "memory");
#pragma unroll
      for (int k = 2; k >= 0; k--) {
        const uint4 a = lds128(ra + k * 1280), b = lds128(ra + k * 1280 + 16);
        z[k] = ((__uint_as_float(a.x) + __uint_as_float(a.y)) + (__uint_as_float(a.z) + __uint_as_float(a.w))) + ((__uint_as_float(b.x) + __uint_as_float(b.y)) + (__uint_as_float(b.z) + __uint_as_float(b.w)));
      }
#pragma unroll
      for (int k = 2; k >= 0; k--) z[k] += __shfl_xor_sync(0xffffffffu, z[k], 16);
      const LnC l = ln_consts(z[1], z[2], rd);
      const uint32_t b = pack_bf(0.f, fmaf(-bf_lo(l.m2), sw, z[0]) * rd);
      const uint32_t k16 = max(min((b ^ (((int)b >> 31) | 0x80000000u)) >> 16, 0xFFFEu), 1u);
      if (ln < 16) str16(rp, k16);
      sts64(OFF_RK + (ln & 15) * 8, __byte_perm(l.m2, l.rh2, 0x5410), __byte_perm(l.rl2, k16, 0x5410));
      sts128(MISC_CNT + ln * 16, 0, 0, 0, 0);
    }
    mbar_wait(MB_GU);
#define LD_HW { const uint4 a = lds128(row), b = lds128(row + 512); hw[8] = lds32(row + 1024 - ln * 12); \
      hw[0] = a.x; hw[1] = a.y; hw[2] = a.z; hw[3] = a.w; hw[4] = b.x; hw[5] = b.y; hw[6] = b.z; hw[7] = b.w; }
    LD_HW
    const uint32_t tr0 = clock();
    bar_sync(5, 512);
    TS(7);
    const uint2 lk = lds64(OFF_RK + warp * 8);
    LnC l2;
    l2.m2 = __byte_perm(lk.x, 0, 0x1010); l2.rh2 = __byte_perm(lk.x, 0, 0x3232); l2.rl2 = __byte_perm(lk.y, 0, 0x1010);
    const uint32_t key = (lk.y & 0xFFFF0000u) | (2047 - tok);
    uint32_t loc = ln < 16 ? (lds32(OFF_RK + 4 + ln * 8) & 0xFFFF0000u) | (2047 - c * 16 - ln) : 0u;
    int rank = __popc(__ballot_sync(0xffffffffu, loc > key));
#pragma unroll
    for (int i = 0; i < 9; i++) wr[i] = keep(ln_apply(hw[i], l2.m2, l2.rh2, l2.rl2));
#define OUT_ROW { uint32_t* o = p.out + tok * 288 + ln * 4; \
      *(uint4*)o = make_uint4(bf_add2(hw[0], wr[0]), bf_add2(hw[1], wr[1]), bf_add2(hw[2], wr[2]), bf_add2(hw[3], wr[3])); \
      *(uint4*)(o + 128) = make_uint4(bf_add2(hw[4], wr[4]), bf_add2(hw[5], wr[5]), bf_add2(hw[6], wr[6]), bf_add2(hw[7], wr[7])); \
      o[256 - ln * 3] = bf_add2(hw[8], wr[8]); }
    uint4* hs = p.s->HS + ln;
    asm volatile("" : "+l"(hs));
#pragma unroll 1
    for (int base = 0; base < 8; base += 2) {
      uint32_t T[2];
#pragma unroll
      for (int j = 0; j < 2; j++) {
        const uint32_t mx = __reduce_max_sync(0xffffffffu, loc);
        if (loc == mx) loc = 0;
        T[j] = (td >> 2) < c ? (mx & 0xFFFF0000u) - 1u : mx | 0xFFFFu;
      }
      const uint32_t sh = keep(rank == base ? 0x4410u : rank == base + 1 ? 0x4432u : 0x4445u), ca = keep(MISC_CNT + base * 64 + ln * 4);
      TS(29);
      if (base == 0) {
        while ((int)(clock() - tr0) < X_RD) {}
        if ((td >> 2) != c) rv = ldr64(rsrc);
        if (rank >= X_OR) OUT_ROW
        if (warp < (five ? 12 : 15)) {
#pragma unroll
          for (int k = 0; k < X_WS; k++) ldsm4t(wabase + k * 16 * pitch, wa[k][0], wa[k][1], wa[k][2], wa[k][3]);
        }
      }
      uint32_t cnt;
#pragma unroll 1
      for (int it = 0; it < SPIN_MAX; it++) {
        const uint32_t xs = rv.x << 16, ys = rv.y << 16;
        const bool bad = max(max(rv.x, xs), max(rv.y, ys)) >= 0xFFFF0000u;
        uint32_t cn2 = 0;
        cnt = bad ? 256u : 0u;
#pragma unroll
        for (int j = 0; j < 2; j++)
          asm("{ .reg .pred a, b, c, d; setp.gt.u32 a, %2, %6; setp.gt.u32 b, %3, %6; setp.gt.u32 c, %4, %6; setp.gt.u32 d, %5, %6; "
              "@a add.u32 %1, %1, %7; @b add.u32 %1, %1, %7; @c add.u32 %0, %0, %7; @d add.u32 %0, %0, %7; }"
              : "+r"(cnt), "+r"(cn2) : "r"(rv.x), "r"(rv.y), "r"(xs), "r"(ys), "r"(T[j]), "r"(1u << (16 * j)));
        cnt = __reduce_add_sync(0xffffffffu, cnt + cn2);
        asm volatile("{ .reg .pred q; setp.eq.u32 q, %2, 0; @q red.shared.add.u32 [%0], %1; }" :: "r"(ca), "r"(cnt), "r"(cnt & 0x3F00u) : "memory");
        if (!(cnt & 0x3F00u)) break;
        if (bad) rv = ldr64(rsrc);
      }
      TS(16);
      bar_sync(0, 512);
      cnt = lds32(ca);
      if (base == 0) tpub = clock();
      const int gr = rank + __byte_perm(cnt, 0x800u, sh);
      if (gr < 8) {
        uint4* ks = hs + 1152 + gr;
        hs = (uint4*)((char*)hs + gr * 1152);
        asm volatile("{ .reg .b128 t, u; .reg .b64 a, b, c, d; mov.b64 a, {%1,%2}; mov.b64 b, {%3,%4}; mov.b64 c, {%5,%6}; mov.b64 d, {%7,%8}; mov.b128 t, {a, b}; mov.b128 u, {c, d}; "
                     "st.relaxed.gpu.global.b128 [%0], t; st.relaxed.gpu.global.b128 [%0 + 512], u; }"
                     :: "l"(hs), "r"(wr[0]), "r"(wr[1]), "r"(wr[2]), "r"(wr[3]), "r"(wr[4]), "r"(wr[5]), "r"(wr[6]), "r"(wr[7]) : "memory");
        str32((uint32_t*)(hs + 64) - ln * 3, wr[8]);
        str128(hs + 576, hw[0], hw[1], hw[2], hw[3]); str128(hs + 608, hw[4], hw[5], hw[6], hw[7]); str32((uint32_t*)(hs + 640) - ln * 3, hw[8]);
        if (ln == 0) str32(ks, key);
        rank = 16;
      }
      if (__all_sync(0xffffffffu, (int)(cnt >> 16) + base + 2 >= 8)) break;
    }
    TS(8);
    if (warp < (five ? 12 : 15)) {
#pragma unroll
      for (int k = X_WS; k < 12; k++) ldsm4t(wabase + k * 16 * pitch, wa[k][0], wa[k][1], wa[k][2], wa[k][3]);
    }
    if (warp < 6) while ((int)(clock() - tpub) < X_HD) {}
    TS(19);
    if (warp < 6) { ha[0] = ldr128(hsrc); ha[1] = ldr128(hsrc + 24); ha[2] = ldr128(hsrc + 48); }
    if (rank < X_OR) OUT_ROW
  }
  uint32_t wd[10][4];
  const uint32_t xb = keep(OFF_XS + (ln & 7) * 1168 + (fk * 24 + (ln >> 3)) * 16);
  if (warp >= 7) {
    const uint32_t db = down_box(warp - 7, five) + (ln & 7) * 128;
    mbar_wait(MB_D);
#pragma unroll
    for (int j = 0; j < 4; j++) {
      const uint32_t a = db + (ln >> 4) * 1024 + (((2 * j + ((ln >> 3) & 1)) ^ (ln & 7)) << 4);
      ldsm4t(a, wd[j][0], wd[j][1], wd[j][2], wd[j][3]);
      ldsm4t(a + 2048, wd[4 + j][0], wd[4 + j][1], wd[4 + j][2], wd[4 + j][3]);
    }
#pragma unroll
    for (int j = 0; j < 2; j++) ldsm4t(db + 4096 + (((4 * j + (ln >> 3)) ^ (ln & 7)) << 4), wd[8 + j][0], wd[8 + j][1], wd[8 + j][2], wd[8 + j][3]);
  } else if (warp < 6) {
    const uint32_t xs = keep(OFF_XS + (td + (td / 24) * 49) * 16);
#pragma unroll 1
    for (int it = 0; it < SPIN_MAX; it++) {
      const bool bad = max(max(max(ha[0].x, ha[1].x), max(ha[2].x, ha[2].y)), max(ha[2].z, ha[2].w)) == ~0u;
      if (!__any_sync(0xffffffffu, bad)) break;
      if (bad) { ha[0] = ldr128(hsrc); ha[1] = ldr128(hsrc + 24); ha[2] = ldr128(hsrc + 48); }
    }
#pragma unroll
    for (int q = 0; q < 3; q++) sts128(xs + q * 384, ha[q].x, ha[q].y, ha[q].z, ha[q].w);
  }
  TS(9);

  if (!(M_ & 2)) bar_sync(0, 512);
  if (warp >= (five ? 12 : 15)) { if (M_ & 2) bar_sync(0, 512); }
  else {
    if (M_ & 2) bar_sync(0, 512);
    float d0[4] = {0.f, 0.f, 0.f, 0.f}, d1[4] = {0.f, 0.f, 0.f, 0.f};
#pragma unroll
    for (int k = 0; k < 12; k += 2) {
      uint32_t b0, b1, b2, b3;
      ldsm4(xb + k * 32, b0, b1, b2, b3);
      mma_bf16(d0, wa[k][0], wa[k][1], wa[k][2], wa[k][3], b0, b1);
      mma_bf16(d1, wa[k + 1][0], wa[k + 1][1], wa[k + 1][2], wa[k + 1][3], b2, b3);
    }
    sts128(OFF_RED + td * 16, __float_as_uint(d0[0] + d1[0]), __float_as_uint(d0[1] + d1[1]), __float_as_uint(d0[2] + d1[2]), __float_as_uint(d0[3] + d1[3]));
  }
  TS(26);
  if (warp < 5) {
    const uint32_t rb = OFF_RED + warp * 1536 + ln * 16;
    bar_sync(9, 512);
    const uint4 pa = lds128(rb), pb = lds128(rb + 512), pc = lds128(rb + 1024);
    const float ga = bfr(__uint_as_float(pa.x) + __uint_as_float(pb.x) + __uint_as_float(pc.x));
    const float gb = bfr(__uint_as_float(pa.y) + __uint_as_float(pb.y) + __uint_as_float(pc.y));
    const uint32_t uu = pack_bf(__uint_as_float(pa.z) + __uint_as_float(pb.z) + __uint_as_float(pc.z), __uint_as_float(pa.w) + __uint_as_float(pb.w) + __uint_as_float(pc.w));
    float ra, rb2;
    asm("rcp.approx.ftz.f32 %0, %1;" : "=f"(ra) : "f"(1.f + ex2(ga * -1.4426950408889634f)));
    asm("rcp.approx.ftz.f32 %0, %1;" : "=f"(rb2) : "f"(1.f + ex2(gb * -1.4426950408889634f)));
    const uint32_t act = bf_mul2(pack_bf(ga * ra, gb * rb2), uu);
    sts32(OFF_ACT + td * 4, act);
  } else bar_arrive(9, 512);
  uint4* dst = &p.s->X[c * DM * 2 + (warp - 7) * 64 + tt * 8 + gg];
  asm volatile("" : "+l"(dst));
  if (!(M_ & 1)) { bar_sync(8, 512); tpub = clock(); }
  if (warp < 7) { if (M_ & 1) { bar_sync(8, 512); tpub = clock(); } }
  else {
    uint32_t b0, b1, b2, b3, b4;
    if (M_ & 1) bar_sync(8, 512);
    ldsm4t(OFF_ACT + ln * 16, b0, b1, b2, b3);
    asm volatile("ldmatrix.sync.aligned.m8n8.x1.trans.shared.b16 {%0}, [%1];" : "=r"(b4) : "r"(OFF_ACT + 512 + ln * 16) : "memory");
    if (M_ & 1) tpub = clock();
    float y[4][4];
#pragma unroll
    for (int j = 0; j < 4; j++) {
      y[j][0] = y[j][1] = y[j][2] = y[j][3] = 0.f;
      mma_bf16(y[j], wd[j][0], wd[j][1], wd[j][2], wd[j][3], b0, b1);
    }
#pragma unroll
    for (int j = 0; j < 4; j++) mma_bf16(y[j], wd[4 + j][0], wd[4 + j][1], wd[4 + j][2], wd[4 + j][3], b2, b3);
    if (!five) {
#pragma unroll
      for (int j = 0; j < 4; j++) mma_bf16_k8(y[j], wd[8 + (j >> 1)][2 * (j & 1)], wd[8 + (j >> 1)][2 * (j & 1) + 1], b4);
    }
    str128(dst, (pack_bf(y[0][0], y[0][1]) & ~1u) | 0x10000u, pack_bf(y[0][2], y[0][3]), pack_bf(y[1][0], y[1][1]), pack_bf(y[1][2], y[1][3]));
    str128(dst + 32, (pack_bf(y[2][0], y[2][1]) & ~1u) | 0x10000u, pack_bf(y[2][2], y[2][3]), pack_bf(y[3][0], y[3][1]), pack_bf(y[3][2], y[3][3]));
  }
  TS(10);

  if (c < 72) {
    const uint4* src = &p.s->X[(warp * 4 + tt) * (DM * 2) + c * 8 + gg];
    const int slot = (c & 3) * 2 + (ln >> 4), dw = (c >> 2) * 16 + (ln & 15);
    uint32_t hv = 0, kv = 0, res = 0, rs2 = 0;
    uint32_t* o = p.out;
    if (warp == 0) {
      hv = ~0u;
      SPIN_WHILE(max(hv, kv) == ~0u, hv = ldr32((const uint32_t*)p.s->HS + 2304 + slot * 288 + dw); kv = ldr32(&p.s->HS[1152 + slot]));
      const float r = bf_hi(kv ^ (((int)~kv >> 31) | 0x80000000u));
      float rs;
      asm("rcp.approx.ftz.f32 %0, %1;" : "=f"(rs) : "f"(1.f + ex2(r * -1.4426950408889634f)));
      rs2 = keep(pack_bf(rs, rs));
      res = lds32(OFF_XS + slot * 1168 + dw * 4);
      o += (2047 - (int)(kv & 2047u)) * 288 + dw;
      asm volatile("" : "+l"(o));
    }
    const uint32_t sel = (gg & 1) ? 0x3F800000u : 0x00003F80u;
    const uint32_t q0 = keep((gg >> 1) == 0 ? sel : 0u), q1 = keep((gg >> 1) == 1 ? sel : 0u), q2 = keep((gg >> 1) == 2 ? sel : 0u), q3 = keep((gg >> 1) == 3 ? sel : 0u);
#if M_ & 4
    const uint32_t fa = keep(OFF_RED + warp * 8 + ((gg & 1) * 16 + (gg >> 1) * 4 + tt) * 144), fb = keep(OFF_RED + ln * 144);
#else
    const uint32_t fa = keep(OFF_FIN + warp * 256 + (gg & 1) * 128 + (gg >> 1) * 32 + tt * 8), fb = keep(OFF_FIN + ln * 8);
#endif
    uint4 a0 = make_uint4(0, 0, 0, 0), a1 = a0;
    while ((int)(clock() - tpub) < X_PD) {}
    SPIN_WHILE(!(a0.x & a1.x & 0x10000u), if (!(a0.x & 0x10000u)) a0 = ldr128(src); if (!(a1.x & 0x10000u)) a1 = ldr128(src + 64 * DM * 2));
    float d[4] = {0.f, 0.f, 0.f, 0.f}, e[4] = {0.f, 0.f, 0.f, 0.f}, d2[4] = {0.f, 0.f, 0.f, 0.f}, e2[4] = {0.f, 0.f, 0.f, 0.f};
    mma_bf16(d, q0, q2, q1, q3, a0.x, a0.y); mma_bf16(e, q0, q2, q1, q3, a0.z, a0.w);
#if M_ & 8
    mma_bf16(d2, q0, q2, q1, q3, a1.x, a1.y); mma_bf16(e2, q0, q2, q1, q3, a1.z, a1.w);
    sts64(fa, __float_as_uint(d[0] + e[2] + d2[0] + e2[2]), __float_as_uint(d[1] + e[3] + d2[1] + e2[3]));
#else
    mma_bf16(d, q0, q2, q1, q3, a1.x, a1.y); mma_bf16(e, q0, q2, q1, q3, a1.z, a1.w);
    sts64(fa, __float_as_uint(d[0] + e[2]), __float_as_uint(d[1] + e[3]));
#endif
    TS(11);
    if (warp == 0) {
      bar_sync(0, 512);
      float2 s[16];
#if !(M_ & 4)
#pragma unroll
      for (int i = 0; i < 16; i++) { const uint2 q = lds64(fb + i * 256); s[i] = make_float2(__uint_as_float(q.x), __uint_as_float(q.y)); }
#else
#pragma unroll
      for (int i = 0; i < 16; i += 2) { const uint4 q = lds128(fb + i * 8); s[i] = make_float2(__uint_as_float(q.x), __uint_as_float(q.y)); s[i + 1] = make_float2(__uint_as_float(q.z), __uint_as_float(q.w)); }
#endif
#pragma unroll
      for (int k = 1; k < 16; k *= 2)
#pragma unroll
        for (int i = 0; i < 16; i += 2 * k) { s[i].x += s[i + k].x; s[i].y += s[i + k].y; }
      *o = bf_add2(hv, bf_add2(res, bf_mul2(pack_bf(s[0].x, s[0].y), rs2)));
    } else bar_arrive(0, 512);
  }
  TS(12);
  TS_DUMP();
}

typedef CUresult (*EncodeFn)(CUtensorMap*, CUtensorMapDataType, cuuint32_t, void*, const cuuint64_t*, const cuuint64_t*, const cuuint32_t*,
                             const cuuint32_t*, CUtensorMapInterleave, CUtensorMapSwizzle, CUtensorMapL2promotion, CUtensorMapFloatOOBfill);

}

extern "C" void kernel_launch(void* const* d_in, const int* in_sizes, int n_in, void* d_out, int out_size) {
  (void)in_sizes; (void)n_in; (void)out_size;
  static EncodeFn enc = nullptr;
  static Scratch* scratch = nullptr;
  if (!enc) {
    void* fn = nullptr;
    cudaDriverEntryPointQueryResult qr;
    cudaGetDriverEntryPoint("cuTensorMapEncodeTiled", &fn, cudaEnableDefault, &qr);
    enc = (EncodeFn)fn;
    cudaGetSymbolAddress((void**)&scratch, g_S);
    cudaFuncSetAttribute(fused_kernel<false>, cudaFuncAttributeMaxDynamicSharedMemorySize, SMEM_BYTES);
    cudaFuncSetAttribute(fused_kernel<true>, cudaFuncAttributeMaxDynamicSharedMemorySize, SMEM_BYTES);
  }
  TMaps tm;
  for (int i = 0; i < 6; i++) {
    const bool dn = i % 3 == 2;
    const cuuint32_t w = i < 3 ? 40 : 32;
    cuuint64_t gd[3] = {(cuuint64_t)(dn ? 64 : FF), (cuuint64_t)(dn ? FF : DM), 9};
    cuuint64_t gs[2] = {(cuuint64_t)(dn ? DM * 2 : FF * 2), 128};
    cuuint32_t bx[3] = {dn ? 64 : w, dn ? w : 96, i < 3 ? 2u : 3u};
    cuuint32_t es[3] = {1, 1, 1};
    enc(&tm.m[i], CU_TENSOR_MAP_DATA_TYPE_BFLOAT16, dn ? 3 : 2, d_in[11 + i % 3], gd, gs, bx, es, CU_TENSOR_MAP_INTERLEAVE_NONE,
        dn ? CU_TENSOR_MAP_SWIZZLE_128B : i < 3 ? CU_TENSOR_MAP_SWIZZLE_NONE : CU_TENSOR_MAP_SWIZZLE_64B,
        (CUtensorMapL2promotion)X_PROMO, CU_TENSOR_MAP_FLOAT_OOB_FILL_NONE);
  }
  for (int i = 6; i < 10; i++) {
    cuuint64_t gd[3] = {i < 8 ? 32u : 16u, i < 8 ? DM / 2u : DM, NCTA};
    cuuint64_t gs[2] = {i < 8 ? 64u : 32u, DM * 32};
    cuuint32_t bx[3] = {32, 1, (i & 1) ? 128u : 136u};
    cuuint32_t es[3] = {1, 1, 1};
    enc(&tm.m[i], CU_TENSOR_MAP_DATA_TYPE_FLOAT16, 3, scratch->X, gd, gs, bx, es, CU_TENSOR_MAP_INTERLEAVE_NONE, CU_TENSOR_MAP_SWIZZLE_64B,
        CU_TENSOR_MAP_L2_PROMOTION_NONE, CU_TENSOR_MAP_FLOAT_OOB_FILL_NONE);
  }
  Params p;
  p.x = (const unsigned char*)d_in[0];
  bool far = false;
  for (int i = 0; i < 7; i++) {
    p.far[i] = (const unsigned char*)d_in[1 + i];
    const long long d = (long long)((intptr_t)d_in[1 + i] - (intptr_t)d_in[0]);
    p.off[i] = (int)(d / 16);
    if ((long long)p.off[i] * 16 != d || p.off[i] > (1 << 30)) far = true;
  }
  p.dskip = (const uint16_t*)d_in[8];
  p.w_r = (const uint32_t*)d_in[10];
  for (int f = 0; f < 2; f++) {
    static const int kind[17] = {0, 0, 0, 0, 2, 2, 0, 0, 1, 1, 1, 1, 1, 1, 2, 2, 2};
    static const int idx[2][17] = {{2, 3, 4, 5, 6, 8, 0, 1, 0, 1, 2, 3, 4, 5, 0, 2, 4}, {2, 3, 4, 5, 0, -1, 0, 1, 0, 1, 2, 3, 4, 5, 3, -1, 6}};
    static const int blk[2][17] = {{-1, -1, -1, -1, 0, -1, 4, -1, 1, -1, 2, -1, 3, -1, 16, -1, -1}, {-1, -1, -1, -1, 1, -1, 4, -1, -1, -1, 2, -1, 3, -1, 16, -1, -1}};
    const int pitch = f ? 64 : 80;
    for (int u = 0; u < 17; u++) {
      const int s = idx[f][u];
      const uint32_t dst = kind[u] == 0 ? OFF_G + s * 96 * pitch : kind[u] == 2 ? down_box(s, f) : OFF_W + W_BYTES + (s >> 1) * W_BYTES + (s & 1) * 96 * pitch;
      const uint32_t mb = u >= 14 ? (u >= X_HU ? MB_H - OFF_MISC : X_HB) : blk[f][u] >= 0 ? MB_KF - OFF_MISC + blk[f][u] * 8 : 0;
      p.sched[f][u] = s < 0 ? 3u : kind[u] | s << 2 | mb << 6 | dst << 14;
    }
  }
  p.out = (uint32_t*)d_out;
  p.off[7] = 0;
  p.ts = nullptr;
  p.s = scratch;
  if (far) { fused_kernel<true><<<NCTA, NT, SMEM_BYTES, cudaStreamPerThread>>>(p, tm); return; }
  fused_kernel<false><<<NCTA, NT, SMEM_BYTES, cudaStreamPerThread>>>(p, tm);
}
```

```cpp
#include <cuda_runtime.h>
#include <cuda.h>
#include <cuda_bf16.h>
#include <cuda_fp16.h>
#include <stdint.h>
#include <stddef.h>

namespace {

constexpr int NCTA = 128;
constexpr int NT = 640;
constexpr int DM = 576;
constexpr int FF = 4608;
constexpr int SPIN_MAX = 1 << 20;

struct Scratch {
  uint4 X[NCTA * DM * 2];
  uint4 KX[64 * 128];
  uint4 HS[1152 + 8];
  uint4 R[256];
  uint4 SC[256];
  uint32_t FLAG[NCTA * 8];
};
__device__ Scratch g_S;

#define CLKS(i)
#define TS(i)
#define TSX(i)
#define TS_DUMP()

constexpr int SB = 1024;
constexpr int BOX = 15360;
constexpr int OFF_G = SB;
constexpr int OFF_W = OFF_G + 3 * BOX;
constexpr int W_KT = 26624;
constexpr int W_QT = W_KT + 64 + 2048 + 80;
constexpr int W_L3 = W_KT + 4352;
constexpr int W_CW = W_L3 + 4160;
constexpr int W_MISC = W_CW + 640;
constexpr int W_BYTES = 35840;
constexpr int TILE = 10240;
constexpr int OFF_T = OFF_W + 4 * W_BYTES;
constexpr int ALT = TILE - W_KT;
static_assert(W_MISC + 32 <= W_BYTES && OFF_W % 1024 == 0 && W_BYTES % 1024 == 0 && W_BYTES + ALT <= 20480, "wg block");
constexpr int YT_PITCH = 1184;
constexpr int OFF_YT = OFF_T + 2 * TILE;
constexpr int OFF_WR = OFF_YT + 16 * YT_PITCH + 64;
constexpr int OFF_MISC = OFF_WR + 2304;
constexpr int SMEM_BYTES = OFF_MISC + 1024 - SB;
static_assert(OFF_YT % 16 == 0 && OFF_MISC % 16 == 0, "align");
static_assert(SMEM_BYTES <= 232448, "smem");
constexpr int MB_GU = OFF_MISC;
constexpr int MB_D = OFF_MISC + 8;
constexpr int MB_KF = OFF_MISC + 16;
constexpr int MB_GF = OFF_MISC + 48;
constexpr int MB_SC = OFF_MISC + 56;
constexpr int MB_UL = OFF_MISC + 64;
constexpr int MB_REL = OFF_MISC + 104;
constexpr int MB_GO = OFF_MISC + 112;
constexpr int MB_H = MB_KF + 128;
constexpr int MISC_EPOCH = OFF_MISC + 152;
constexpr int MISC_SW = OFF_MISC + 156;
constexpr int MISC_RT = OFF_MISC + 160;
constexpr int MISC_T0 = OFF_MISC + 296;
constexpr int MISC_EM = OFF_MISC + 288;
constexpr int OFF_PART = OFF_W + 20480;
constexpr int OFF_RK = OFF_PART + 3840;
constexpr int MISC_LN1 = OFF_MISC + 192;
constexpr int OFF_XS = OFF_T;
constexpr int OFF_RED = OFF_T + TILE;
constexpr int OFF_FIN = OFF_W + 3 * W_BYTES + W_KT;
constexpr int OFF_ACT = OFF_FIN + 4096;
constexpr int MISC_CNT = OFF_ACT + 1024;

__device__ __forceinline__ uint32_t smem_u32(const void* p) { return (uint32_t)__cvta_generic_to_shared(p); }
__device__ __forceinline__ uint32_t lds32(uint32_t a) { uint32_t v; asm volatile("ld.shared.b32 %0, [%1];" : "=r"(v) : "r"(a) : "memory"); return v; }
__device__ __forceinline__ uint32_t lds16(uint32_t a) { uint16_t v; asm volatile("ld.shared.u16 %0, [%1];" : "=h"(v) : "r"(a) : "memory"); return v; }
__device__ __forceinline__ uint2 lds64(uint32_t a) { uint2 v; asm volatile("ld.shared.v2.b32 {%0,%1}, [%2];" : "=r"(v.x), "=r"(v.y) : "r"(a) : "memory"); return v; }
__device__ __forceinline__ uint4 lds128(uint32_t a) { uint4 v; asm volatile("ld.shared.v4.b32 {%0,%1,%2,%3}, [%4];" : "=r"(v.x), "=r"(v.y), "=r"(v.z), "=r"(v.w) : "r"(a) : "memory"); return v; }
__device__ __forceinline__ void sts16(uint32_t a, uint32_t v) { asm volatile("st.shared.u16 [%0], %1;" :: "r"(a), "h"((uint16_t)v) : "memory"); }
__device__ __forceinline__ void sts32(uint32_t a, uint32_t v) { asm volatile("st.shared.b32 [%0], %1;" :: "r"(a), "r"(v) : "memory"); }
__device__ __forceinline__ void sts64(uint32_t a, uint32_t x, uint32_t y) { asm volatile("st.shared.v2.b32 [%0], {%1,%2};" :: "r"(a), "r"(x), "r"(y) : "memory"); }
__device__ __forceinline__ void sts128(uint32_t a, uint32_t x, uint32_t y, uint32_t z, uint32_t w) { asm volatile("st.shared.v4.b32 [%0], {%1,%2,%3,%4};" :: "r"(a), "r"(x), "r"(y), "r"(z), "r"(w) : "memory"); }
__device__ __forceinline__ void ldsm4(uint32_t a, uint32_t& r0, uint32_t& r1, uint32_t& r2, uint32_t& r3) {
  asm volatile("ldmatrix.sync.aligned.m8n8.x4.shared.b16 {%0,%1,%2,%3}, [%4];" : "=r"(r0), "=r"(r1), "=r"(r2), "=r"(r3) : "r"(a) : "memory");
}
__device__ __forceinline__ void ldsm2(uint32_t a, uint32_t& r0, uint32_t& r1) {
  asm volatile("ldmatrix.sync.aligned.m8n8.x2.shared.b16 {%0,%1}, [%2];" : "=r"(r0), "=r"(r1) : "r"(a) : "memory");
}
__device__ __forceinline__ void ldsm4t(uint32_t a, uint32_t& r0, uint32_t& r1, uint32_t& r2, uint32_t& r3) {
  asm volatile("ldmatrix.sync.aligned.m8n8.x4.trans.shared.b16 {%0,%1,%2,%3}, [%4];" : "=r"(r0), "=r"(r1), "=r"(r2), "=r"(r3) : "r"(a) : "memory");
}
__device__ __forceinline__ void stsm4t(uint32_t a, uint32_t r0, uint32_t r1, uint32_t r2, uint32_t r3) {
  asm volatile("stmatrix.sync.aligned.m8n8.x4.trans.shared.b16 [%0], {%1,%2,%3,%4};" :: "r"(a), "r"(r0), "r"(r1), "r"(r2), "r"(r3) : "memory");
}
__device__ __forceinline__ uint4 ldr128(const void* p) {
  unsigned long long lo, hi;
  asm volatile("{ .reg .b128 t; ld.relaxed.gpu.global.b128 t, [%2]; mov.b128 {%0, %1}, t; }" : "=l"(lo), "=l"(hi) : "l"(p) : "memory");
  return make_uint4((uint32_t)lo, (uint32_t)(lo >> 32), (uint32_t)hi, (uint32_t)(hi >> 32));
}
__device__ __forceinline__ void str128(void* p, uint32_t x, uint32_t y, uint32_t z, uint32_t w) {
  asm volatile("{ .reg .b128 t; .reg .b64 lo, hi; mov.b64 lo, {%1,%2}; mov.b64 hi, {%3,%4}; mov.b128 t, {lo, hi}; st.relaxed.gpu.global.b128 [%0], t; }"
               :: "l"(p), "r"(x), "r"(y), "r"(z), "r"(w) : "memory");
}
__device__ __forceinline__ void str64(void* p, uint32_t x, uint32_t y) {
  asm volatile("{ .reg .b64 t; mov.b64 t, {%1,%2}; st.relaxed.gpu.global.b64 [%0], t; }" :: "l"(p), "r"(x), "r"(y) : "memory");
}
__device__ __forceinline__ uint32_t ldr32(const void* p) { uint32_t v; asm volatile("ld.relaxed.gpu.global.b32 %0, [%1];" : "=r"(v) : "l"(p) : "memory"); return v; }
__device__ __forceinline__ void str32(void* p, uint32_t v) { asm volatile("st.relaxed.gpu.global.b32 [%0], %1;" :: "l"(p), "r"(v) : "memory"); }
__device__ __forceinline__ void str16(void* p, uint32_t v) { asm volatile("st.relaxed.gpu.global.u16 [%0], %1;" :: "l"(p), "h"((uint16_t)v) : "memory"); }
__device__ __forceinline__ void fence_gpu() { asm volatile("fence.acq_rel.gpu;" ::: "memory"); }
__device__ __forceinline__ void bar_sync(int id, int n) { asm volatile("bar.sync %0, %1;" :: "r"(id), "r"(n) : "memory"); }
__device__ __forceinline__ void bar_arrive(int id, int n) { asm volatile("bar.arrive %0, %1;" :: "r"(id), "r"(n) : "memory"); }

__device__ __forceinline__ float bf_lo(uint32_t w) { return __uint_as_float(w << 16); }
__device__ __forceinline__ float bf_hi(uint32_t w) { return __uint_as_float(w & 0xFFFF0000u); }
__device__ __forceinline__ uint32_t pack_bf(float lo, float hi) { uint32_t r; asm("cvt.rn.bf16x2.f32 %0, %1, %2;" : "=r"(r) : "f"(hi), "f"(lo)); return r; }
__device__ __forceinline__ uint32_t pack_h(float lo, float hi) { uint32_t r; asm("cvt.rn.f16x2.f32 %0, %1, %2;" : "=r"(r) : "f"(hi), "f"(lo)); return r; }
__device__ __forceinline__ uint32_t pack_hv(float lo, float hi) { uint32_t r; asm volatile("cvt.rn.f16x2.f32 %0, %1, %2;" : "=r"(r) : "f"(hi), "f"(lo) : "memory"); return r; }
__device__ __forceinline__ float bfr(float x) { return bf_lo(pack_bf(x, 0.f)); }
__device__ __forceinline__ uint32_t bf_sub2(uint32_t a, uint32_t b) { __nv_bfloat162 r = __hsub2(*(__nv_bfloat162*)&a, *(__nv_bfloat162*)&b); return *(uint32_t*)&r; }
__device__ __forceinline__ uint32_t bf_add2(uint32_t a, uint32_t b) { __nv_bfloat162 r = __hadd2(*(__nv_bfloat162*)&a, *(__nv_bfloat162*)&b); return *(uint32_t*)&r; }
__device__ __forceinline__ uint32_t bf_mul2(uint32_t a, uint32_t b) { __nv_bfloat162 r = __hmul2(*(__nv_bfloat162*)&a, *(__nv_bfloat162*)&b); return *(uint32_t*)&r; }
__device__ __forceinline__ float2 h2f(uint32_t w) { return __half22float2(*(__half2*)&w); }
__device__ __forceinline__ float ex2(float x) { float r; asm("ex2.approx.ftz.f32 %0, %1;" : "=f"(r) : "f"(x)); return r; }
__device__ __forceinline__ float warp_sum(float v) {
#pragma unroll
  for (int o = 16; o > 0; o >>= 1) v += __shfl_xor_sync(0xffffffffu, v, o);
  return v;
}
__device__ __forceinline__ void mma_f16_f32(float* d, uint32_t a0, uint32_t a1, uint32_t a2, uint32_t a3, uint32_t b0, uint32_t b1) {
  asm volatile("mma.sync.aligned.m16n8k16.row.col.f32.f16.f16.f32 {%0,%1,%2,%3}, {%4,%5,%6,%7}, {%8,%9}, {%0,%1,%2,%3};"
               : "+f"(d[0]), "+f"(d[1]), "+f"(d[2]), "+f"(d[3]) : "r"(a0), "r"(a1), "r"(a2), "r"(a3), "r"(b0), "r"(b1));
}
__device__ __forceinline__ void mma_f16_f16(uint32_t& d0, uint32_t& d1, uint32_t a0, uint32_t a1, uint32_t a2, uint32_t a3, uint32_t b0, uint32_t b1) {
  asm volatile("mma.sync.aligned.m16n8k16.row.col.f16.f16.f16.f16 {%0,%1}, {%2,%3,%4,%5}, {%6,%7}, {%0,%1};"
               : "+r"(d0), "+r"(d1) : "r"(a0), "r"(a1), "r"(a2), "r"(a3), "r"(b0), "r"(b1));
}
__device__ __forceinline__ void mma_bf16(float* d, uint32_t a0, uint32_t a1, uint32_t a2, uint32_t a3, uint32_t b0, uint32_t b1) {
  asm volatile("mma.sync.aligned.m16n8k16.row.col.f32.bf16.bf16.f32 {%0,%1,%2,%3}, {%4,%5,%6,%7}, {%8,%9}, {%0,%1,%2,%3};"
               : "+f"(d[0]), "+f"(d[1]), "+f"(d[2]), "+f"(d[3]) : "r"(a0), "r"(a1), "r"(a2), "r"(a3), "r"(b0), "r"(b1));
}
__device__ __forceinline__ void mma_bf16_k8(float* d, uint32_t a0, uint32_t a1, uint32_t b0) {
  asm volatile("mma.sync.aligned.m16n8k8.row.col.f32.bf16.bf16.f32 {%0,%1,%2,%3}, {%4,%5}, {%6}, {%0,%1,%2,%3};"
               : "+f"(d[0]), "+f"(d[1]), "+f"(d[2]), "+f"(d[3]) : "r"(a0), "r"(a1), "r"(b0));
}

__device__ __forceinline__ void wg_fence() { asm volatile("wgmma.fence.sync.aligned;" ::: "memory"); }
__device__ __forceinline__ void wg_commit() { asm volatile("wgmma.commit_group.sync.aligned;" ::: "memory"); }
template <int N> __device__ __forceinline__ void wg_wait() { asm volatile("wgmma.wait_group.sync.aligned %0;" :: "n"(N) : "memory"); }
template <int TB> __device__ __forceinline__ void wgmma32(float* d, const uint32_t* a, uint32_t dlo, uint32_t dhi) {
  asm volatile("{ .reg .b64 dd; mov.b64 dd, {%20, %21}; wgmma.mma_async.sync.aligned.m64n32k16.f32.f16.f16 "
               "{%0,%1,%2,%3,%4,%5,%6,%7,%8,%9,%10,%11,%12,%13,%14,%15}, {%16,%17,%18,%19}, dd, 1, 1, 1, %22; }"
               : "+f"(d[0]), "+f"(d[1]), "+f"(d[2]), "+f"(d[3]), "+f"(d[4]), "+f"(d[5]), "+f"(d[6]), "+f"(d[7]), "+f"(d[8]), "+f"(d[9]), "+f"(d[10]), "+f"(d[11]), "+f"(d[12]), "+f"(d[13]), "+f"(d[14]), "+f"(d[15])
               : "r"(a[0]), "r"(a[1]), "r"(a[2]), "r"(a[3]), "r"(dlo), "r"(dhi), "n"(TB));
}
template <int TB> __device__ __forceinline__ void wgmma64(float* d, const uint32_t* a, uint32_t dlo, uint32_t dhi) {
  asm volatile("{ .reg .b64 dd; mov.b64 dd, {%36, %37}; wgmma.mma_async.sync.aligned.m64n64k16.f32.f16.f16 "
               "{%0,%1,%2,%3,%4,%5,%6,%7,%8,%9,%10,%11,%12,%13,%14,%15,%16,%17,%18,%19,%20,%21,%22,%23,%24,%25,%26,%27,%28,%29,%30,%31}, {%32,%33,%34,%35}, dd, 1, 1, 1, %38; }"
               : "+f"(d[0]), "+f"(d[1]), "+f"(d[2]), "+f"(d[3]), "+f"(d[4]), "+f"(d[5]), "+f"(d[6]), "+f"(d[7]), "+f"(d[8]), "+f"(d[9]), "+f"(d[10]), "+f"(d[11]), "+f"(d[12]), "+f"(d[13]), "+f"(d[14]), "+f"(d[15]), "+f"(d[16]), "+f"(d[17]), "+f"(d[18]), "+f"(d[19]), "+f"(d[20]), "+f"(d[21]), "+f"(d[22]), "+f"(d[23]), "+f"(d[24]), "+f"(d[25]), "+f"(d[26]), "+f"(d[27]), "+f"(d[28]), "+f"(d[29]), "+f"(d[30]), "+f"(d[31])
               : "r"(a[0]), "r"(a[1]), "r"(a[2]), "r"(a[3]), "r"(dlo), "r"(dhi), "n"(TB));
}
template <int TB> __device__ __forceinline__ void wgmma64_init(float* d, const uint32_t* a, uint32_t dlo, uint32_t dhi) {
  asm volatile("{ .reg .b64 dd; mov.b64 dd, {%36, %37}; wgmma.mma_async.sync.aligned.m64n64k16.f32.f16.f16 "
               "{%0,%1,%2,%3,%4,%5,%6,%7,%8,%9,%10,%11,%12,%13,%14,%15,%16,%17,%18,%19,%20,%21,%22,%23,%24,%25,%26,%27,%28,%29,%30,%31}, {%32,%33,%34,%35}, dd, 0, 1, 1, %38; }"
               : "=f"(d[0]), "=f"(d[1]), "=f"(d[2]), "=f"(d[3]), "=f"(d[4]), "=f"(d[5]), "=f"(d[6]), "=f"(d[7]), "=f"(d[8]), "=f"(d[9]), "=f"(d[10]), "=f"(d[11]), "=f"(d[12]), "=f"(d[13]), "=f"(d[14]), "=f"(d[15]), "=f"(d[16]), "=f"(d[17]), "=f"(d[18]), "=f"(d[19]), "=f"(d[20]), "=f"(d[21]), "=f"(d[22]), "=f"(d[23]), "=f"(d[24]), "=f"(d[25]), "=f"(d[26]), "=f"(d[27]), "=f"(d[28]), "=f"(d[29]), "=f"(d[30]), "=f"(d[31])
               : "r"(a[0]), "r"(a[1]), "r"(a[2]), "r"(a[3]), "r"(dlo), "r"(dhi), "n"(TB));
}
template <int TB> __device__ __forceinline__ void wgmma32_init(float* d, const uint32_t* a, uint32_t dlo, uint32_t dhi) {
  asm volatile("{ .reg .b64 dd; mov.b64 dd, {%20, %21}; wgmma.mma_async.sync.aligned.m64n32k16.f32.f16.f16 "
               "{%0,%1,%2,%3,%4,%5,%6,%7,%8,%9,%10,%11,%12,%13,%14,%15}, {%16,%17,%18,%19}, dd, 0, 1, 1, %22; }"
               : "=f"(d[0]), "=f"(d[1]), "=f"(d[2]), "=f"(d[3]), "=f"(d[4]), "=f"(d[5]), "=f"(d[6]), "=f"(d[7]), "=f"(d[8]), "=f"(d[9]), "=f"(d[10]), "=f"(d[11]), "=f"(d[12]), "=f"(d[13]), "=f"(d[14]), "=f"(d[15])
               : "r"(a[0]), "r"(a[1]), "r"(a[2]), "r"(a[3]), "r"(dlo), "r"(dhi), "n"(TB));
}
__device__ __forceinline__ void wgmma64h(uint32_t* d, uint32_t a0, uint32_t a1, uint32_t a2, uint32_t a3, uint32_t dlo, uint32_t dhi) {
  asm volatile("{ .reg .b64 dd; mov.b64 dd, {%20, %21}; wgmma.mma_async.sync.aligned.m64n64k16.f16.f16.f16 "
               "{%0,%1,%2,%3,%4,%5,%6,%7,%8,%9,%10,%11,%12,%13,%14,%15}, {%16,%17,%18,%19}, dd, 1, 1, 1, 0; }"
               : "+r"(d[0]), "+r"(d[1]), "+r"(d[2]), "+r"(d[3]), "+r"(d[4]), "+r"(d[5]), "+r"(d[6]), "+r"(d[7]), "+r"(d[8]), "+r"(d[9]), "+r"(d[10]), "+r"(d[11]), "+r"(d[12]), "+r"(d[13]), "+r"(d[14]), "+r"(d[15])
               : "r"(a0), "r"(a1), "r"(a2), "r"(a3), "r"(dlo), "r"(dhi));
}
__device__ __forceinline__ void wgmma64h_init(uint32_t* d, uint32_t a0, uint32_t a1, uint32_t a2, uint32_t a3, uint32_t dlo, uint32_t dhi) {
  asm volatile("{ .reg .b64 dd; mov.b64 dd, {%20, %21}; wgmma.mma_async.sync.aligned.m64n64k16.f16.f16.f16 "
               "{%0,%1,%2,%3,%4,%5,%6,%7,%8,%9,%10,%11,%12,%13,%14,%15}, {%16,%17,%18,%19}, dd, 0, 1, 1, 0; }"
               : "=r"(d[0]), "=r"(d[1]), "=r"(d[2]), "=r"(d[3]), "=r"(d[4]), "=r"(d[5]), "=r"(d[6]), "=r"(d[7]), "=r"(d[8]), "=r"(d[9]), "=r"(d[10]), "=r"(d[11]), "=r"(d[12]), "=r"(d[13]), "=r"(d[14]), "=r"(d[15])
               : "r"(a0), "r"(a1), "r"(a2), "r"(a3), "r"(dlo), "r"(dhi));
}
__device__ __forceinline__ void wgmma40_ss(float* d, uint32_t alo, uint32_t blo, uint32_t hi) {
  asm volatile("{ .reg .b64 da, db; mov.b64 da, {%20, %22}; mov.b64 db, {%21, %22}; "
               "wgmma.mma_async.sync.aligned.m64n40k16.f32.f16.f16 {%0,%1,%2,%3,%4,%5,%6,%7,%8,%9,%10,%11,%12,%13,%14,%15,%16,%17,%18,%19}, da, db, 1, 1, 1, 1, 1; }"
               : "+f"(d[0]), "+f"(d[1]), "+f"(d[2]), "+f"(d[3]), "+f"(d[4]), "+f"(d[5]), "+f"(d[6]), "+f"(d[7]), "+f"(d[8]), "+f"(d[9]), "+f"(d[10]), "+f"(d[11]), "+f"(d[12]), "+f"(d[13]), "+f"(d[14]), "+f"(d[15]), "+f"(d[16]), "+f"(d[17]), "+f"(d[18]), "+f"(d[19])
               : "r"(alo), "r"(blo), "r"(hi));
}
__device__ __forceinline__ void wgmma40_ss_init(float* d, uint32_t alo, uint32_t blo, uint32_t hi) {
  asm volatile("{ .reg .b64 da, db; mov.b64 da, {%20, %22}; mov.b64 db, {%21, %22}; "
               "wgmma.mma_async.sync.aligned.m64n40k16.f32.f16.f16 {%0,%1,%2,%3,%4,%5,%6,%7,%8,%9,%10,%11,%12,%13,%14,%15,%16,%17,%18,%19}, da, db, 0, 1, 1, 1, 1; }"
               : "=f"(d[0]), "=f"(d[1]), "=f"(d[2]), "=f"(d[3]), "=f"(d[4]), "=f"(d[5]), "=f"(d[6]), "=f"(d[7]), "=f"(d[8]), "=f"(d[9]), "=f"(d[10]), "=f"(d[11]), "=f"(d[12]), "=f"(d[13]), "=f"(d[14]), "=f"(d[15]), "=f"(d[16]), "=f"(d[17]), "=f"(d[18]), "=f"(d[19])
               : "r"(alo), "r"(blo), "r"(hi));
}
__device__ __forceinline__ float vzero() { float v; asm volatile("mov.b32 %0, 0;" : "=f"(v)); return v; }
__device__ __forceinline__ void tma_box(uint32_t dst, const CUtensorMap* tm, uint32_t mb, int x, int y) {
  asm volatile("cp.async.bulk.tensor.2d.shared::cluster.global.mbarrier::complete_tx::bytes [%0], [%1, {%3, %4}], [%2];"
               :: "r"(dst), "l"(tm), "r"(mb), "r"(x), "r"(y) : "memory");
}
__device__ __forceinline__ void l2_prefetch(const void* src, uint32_t bytes) {
  asm volatile("cp.async.bulk.prefetch.L2.global [%0], %1;" :: "l"(src), "r"(bytes) : "memory");
}
__device__ __forceinline__ uint32_t uni(uint32_t v) {
  uint32_t r; asm volatile("shfl.sync.idx.b32 %0, %1, 0, 0x1f, 0xffffffff;" : "=r"(r) : "r"(v)); return r;
}
__device__ __forceinline__ uint32_t pin(uint32_t v) {
  uint32_t r; asm volatile("shfl.sync.bfly.b32 %0, %1, 0, 0x1f, 0xffffffff;" : "=r"(r) : "r"(v)); return r;
}
__device__ __forceinline__ int fresh_tid() { int v; asm volatile("mov.u32 %0, %tid.x;" : "=r"(v)); return v; }

struct Params {
  const unsigned char* x;
  Scratch* s;
  int off[8];
  uint32_t* out;
  const uint16_t* dskip;
  const uint32_t* w_r;
  long long* ts;
  const unsigned char* far[7];
  uint32_t sched[2][17];
};
__device__ __forceinline__ uint32_t ldnc32(const void* p) { uint32_t v; asm volatile("ld.global.nc.b32 %0, [%1];" : "=r"(v) : "l"(p)); return v; }
__device__ __forceinline__ uint32_t ldnc16(const void* p) { uint16_t v; asm volatile("ld.global.nc.u16 %0, [%1];" : "=h"(v) : "l"(p)); return v; }
__device__ __forceinline__ uint4 ldnc128(const void* p) { uint4 v; asm volatile("ld.global.nc.v4.b32 {%0,%1,%2,%3}, [%4];" : "=r"(v.x), "=r"(v.y), "=r"(v.z), "=r"(v.w) : "l"(p)); return v; }
__device__ __forceinline__ void mbar_wait(uint32_t mb, uint32_t ph = 0) {
#pragma unroll 1
  for (int it = 0; it < SPIN_MAX; it++) {
    uint32_t ok;
    asm volatile("{ .reg .pred q; mbarrier.try_wait.parity.shared::cta.b64 q, [%1], %2; selp.u32 %0, 1, 0, q; }" : "=r"(ok) : "r"(mb), "r"(ph) : "memory");
    if (ok) break;
  }
}
__device__ __forceinline__ uint32_t mbar_test(uint32_t mb) {
  uint32_t ok;
  asm volatile("{ .reg .pred q; mbarrier.test_wait.parity.shared::cta.b64 q, [%1], 0; selp.u32 %0, 1, 0, q; }" : "=r"(ok) : "r"(mb) : "memory");
  return ok;
}
__device__ __forceinline__ void mbar_arrive(uint32_t mb) { asm volatile("mbarrier.arrive.shared::cta.b64 _, [%0];" :: "r"(mb) : "memory"); }
__device__ __forceinline__ uint32_t ldg16(const void* p) { uint16_t v; asm volatile("ld.global.u16 %0, [%1];" : "=h"(v) : "l"(p) : "memory"); return v; }
__device__ __forceinline__ uint32_t ldr16(const void* p) { uint16_t v; asm volatile("ld.relaxed.gpu.global.u16 %0, [%1];" : "=h"(v) : "l"(p) : "memory"); return v; }
__device__ __forceinline__ void fence_async() { asm volatile("fence.proxy.async.shared::cta;" ::: "memory"); }
#define SPIN_WHILE(cond, body) _Pragma("unroll 1") for (int _it = 0; _it < SPIN_MAX && __any_sync(0xffffffffu, (cond)); _it++) { body; }

struct LnC { uint32_t m2, rh2, rl2; };
__device__ __forceinline__ float diag_sum(float d0, float d1, int t) {
  float q = __shfl_sync(0xffffffffu, d0, 9 * t) + __shfl_sync(0xffffffffu, d1, 9 * t + 4);
  q += __shfl_xor_sync(0xffffffffu, q, 1);
  return q + __shfl_xor_sync(0xffffffffu, q, 2);
}
__device__ __forceinline__ LnC ln_consts(float s, float q, float& r) {
  const float mean = s * (1.f / DM);
  const float var = fmaxf(fmaf(-mean, mean, q * (1.f / DM)), 0.f);
  float sd;
  asm("sqrt.approx.ftz.f32 %0, %1;" : "=f"(sd) : "f"(bfr(bfr(var) + 1e-5f)));
  asm("rcp.approx.ftz.f32 %0, %1;" : "=f"(r) : "f"(bfr(sd)));
  LnC c;
  c.m2 = pack_bf(mean, mean);
  c.rh2 = pack_bf(r, r);
  const float rl = r - bf_lo(c.rh2);
  c.rl2 = pack_bf(rl, rl);
  return c;
}
__device__ __forceinline__ float quad_sum(float s) { s += __shfl_xor_sync(0xffffffffu, s, 1); return s + __shfl_xor_sync(0xffffffffu, s, 2); }
__device__ __forceinline__ uint32_t bf_fma2(uint32_t a, uint32_t b, uint32_t c) {
  __nv_bfloat162 r = __hfma2(*(const __nv_bfloat162*)&a, *(const __nv_bfloat162*)&b, *(const __nv_bfloat162*)&c);
  return *(uint32_t*)&r;
}
__device__ __forceinline__ uint32_t ln_apply(uint32_t w, uint32_t m2, uint32_t rh2, uint32_t rl2) {
  const uint32_t d = bf_sub2(w, m2);
  return bf_fma2(d, rh2, bf_mul2(d, rl2));
}

__device__ __forceinline__ float2 cis(float mag_log2, float rev) {
  const float m = ex2(mag_log2), ang = rev * 6.283185307179586f;
  return make_float2(m * __cosf(ang), m * __sinf(ang));
}
__device__ __forceinline__ float2 csq(float2 a) { return make_float2(fmaf(a.x, a.x, -a.y * a.y), (a.x + a.x) * a.y); }
__device__ __forceinline__ float2 cmul(float2 a, float2 b) { return make_float2(fmaf(a.x, b.x, -a.y * b.y), fmaf(a.x, b.y, a.y * b.x)); }
__device__ __forceinline__ void pmul(uint32_t xr, uint32_t xi, uint32_t w, uint32_t& yr, uint32_t& yi) {
  const __half2 XR = *(__half2*)&xr, XI = *(__half2*)&xi, W = *(__half2*)&w;
  const __half2 a = __hfma2(__hneg2(XI), __high2half2(W), __hmul2(XR, __low2half2(W)));
  const __half2 b = __hfma2(XI, __low2half2(W), __hmul2(XR, __high2half2(W)));
  yr = *(const uint32_t*)&a; yi = *(const uint32_t*)&b;
}
__device__ __forceinline__ uint32_t pk(float2 a) { return pack_h(a.x, a.y); }

struct KgState { float2 c0, z8; float kl; uint32_t w64, w128, w192; };
__device__ __forceinline__ void kgen_tables_n(const uint32_t (&raw)[7], uint32_t scr, int wt, KgState& k) {
  const uint32_t dst = scr + 16384 + wt * 16;
  const float dt = bfr(ex2(bf_lo(raw[6]) * 1.4426950408889634f));
  const float th = dt * bf_lo(raw[1]);
  const float br = dt * bf_lo(raw[2]), bi = dt * bf_lo(raw[3]);
  const float Cr = bf_lo(raw[4]), Ci = bf_lo(raw[5]);
  k.c0 = make_float2(fmaf(Cr, br, -Ci * bi), fmaf(Cr, bi, Ci * br));
  const uint32_t mx = __reduce_max_sync(0xffffffffu, __float_as_uint(fmaxf(fabsf(k.c0.x), fabsf(k.c0.y))));
  const float a2 = dt * bf_lo(raw[0]) * 1.4426950408889634f;
  const float rh = th * 0.15915494309189535f;
  const float rl = fmaf(th, (float)(0.15915494309189535 - (double)0.15915494309189535f), fmaf(th, 0.15915494309189535f, -rh));
  const float rf = rh - rintf(rh);
  const float2 z1 = cis(a2, rf + rl);
  const float p64 = rf * 64.f;
  const float2 z64 = cis(a2 * 64.f, fmaf(64.f, rl, p64 - rintf(p64)));
  const float2 z2 = csq(z1), z128 = csq(z64), z3 = cmul(z2, z1), z4 = csq(z2), z256 = csq(z128), z6 = csq(z3), z512 = csq(z256);
  k.z8 = csq(z4);
  k.w64 = pk(z64); k.w128 = pk(z128); k.w192 = pk(cmul(z128, z64));
  sts128(dst, 0x00003C00u, pk(z2), pk(z4), pk(z6));
  const float2 z1024 = csq(z512), z768 = cmul(z512, z256);
  sts128(dst + 2048, pk(z1), pk(z3), pk(cmul(z4, z1)), pk(cmul(z4, z3)));
  const float2 z2048 = csq(z1024);
  k.kl = fmaf(k.c0.x, z2048.x, -k.c0.y * z2048.y);
  sts128(dst + 4096, pk(z256), pk(cmul(z256, z2)), pk(cmul(z256, z4)), pk(cmul(z256, z6)));
  sts128(dst + 6144, pk(z512), pk(cmul(z512, z4)), pk(z768), pk(cmul(z768, z4)));
  sts128(dst + 8192, pk(z1024), pk(cmul(z1024, z256)), pk(cmul(z1024, z512)), pk(cmul(z1024, z768)));
  sts32(scr + W_MISC + (wt >> 5) * 4, mx);
}
__device__ __forceinline__ int kgen_tables_m(uint32_t scr, int wt, const KgState& k) {
  const uint32_t dst = scr + wt * 16;
  const uint4 e4 = lds128(scr + W_MISC);
  const float2 z16 = csq(k.z8), z32 = csq(z16);
  const int em = max(min((int)(max(max(e4.x, e4.y), max(e4.z, e4.w)) >> 23), 238), 16);
  const float sc = __uint_as_float((uint32_t)(127 + 4 + 127 - em) << 23);
  sts32(scr + W_MISC + 16 + (wt >> 5) * 4, __reduce_add_sync(0xffffffffu, __float2int_rn(k.kl * sc * 262144.f)));
  const float2 c0 = make_float2(k.c0.x * sc, k.c0.y * sc);
  const float2 c1 = cmul(c0, k.z8), c2 = cmul(c0, z16), c4 = cmul(c0, z32), c3 = cmul(c1, z16), c5 = cmul(c1, z32), c6 = cmul(c2, z32), c7 = cmul(c3, z32);
  uint32_t pr[4], pi[4], yr[4], yi[4];
  pr[0] = pack_h(c0.x, c1.x); pi[0] = pack_h(c0.y, c1.y);
  pr[1] = pack_h(c2.x, c3.x); pi[1] = pack_h(c2.y, c3.y);
  pr[2] = pack_h(c4.x, c5.x); pi[2] = pack_h(c4.y, c5.y);
  pr[3] = pack_h(c6.x, c7.x); pi[3] = pack_h(c6.y, c7.y);
  sts128(dst, pr[0], pr[1], pr[2], pr[3]); sts128(dst + 2048, pi[0], pi[1], pi[2], pi[3]);
#pragma unroll
  for (int q = 1; q < 4; q++) {
    const uint32_t w = q == 1 ? k.w64 : q == 2 ? k.w128 : k.w192;
#pragma unroll
    for (int i = 0; i < 4; i++) pmul(pr[i], pi[i], w, yr[i], yi[i]);
    sts128(dst + q * 4096, yr[0], yr[1], yr[2], yr[3]); sts128(dst + q * 4096 + 2048, yi[0], yi[1], yi[2], yi[3]);
  }
  return em;
}
__device__ __forceinline__ uint32_t lds32_if(uint32_t a, bool on) {
  uint32_t v; asm volatile("{ .reg .pred q; setp.ne.u32 q, %2, 0; mov.b32 %0, 0; @q ld.shared.b32 %0, [%1]; }" : "=r"(v) : "r"(a), "r"((uint32_t)on) : "memory"); return v;
}
__device__ __forceinline__ uint32_t prmt(uint32_t a, uint32_t b, uint32_t s) { uint32_t r; asm("prmt.b32 %0, %1, %2, %3;" : "=r"(r) : "r"(a), "r"(b), "r"(s)); return r; }
__device__ __forceinline__ void kgen_build(uint32_t tb, int wg, int wt, uint32_t k0, uint32_t k1, uint32_t k2) {
  const uint32_t kt = tb + W_KT, sc = tb + W_L3 + 3072;
  const int ix = ((wt >> 2) + (wt & 3) * 32 - 1) & 127;
  const uint32_t a3 = tb + W_CW + 32 + ((ix & 1) ? 0 : 304) + (ix >> 1) * 4, a2 = sc + 544 + (wt & ~3) * 2 + (wt & 1) * 4 + (wt & 2) * 128;
  const uint32_t v3 = wt ? k2 : k2 >> 16;
  sts32(sc + 4 + wt * 4, __byte_perm(k0, k1, 0x5432));
  sts16(a2, k1 >> 16); sts16(a2 + 6, k1 >> 16);
  sts16(a3, v3); sts16(a3 + 6, v3);
  if ((unsigned)(wt - 32) < 14u) sts128(kt + (wt < 36 ? -512 : 64 + 4128 - 576) + wt * 16, 0, 0, 0, 0);
  if (wt == 127) sts32(sc, k0 & 0xFFFF0000u);
  if (wt == 0) { sts32(sc + 516, k1); sts16(sc + 1056, k2); }
  bar_sync(1 + wg, 128);
  const uint32_t cw = tb + W_CW + 32 + (wt >> 6) * 48 + wt * 4, g2 = sc + 540 + wt * 4;
  const bool odd = wt & 1, ends = (unsigned)(wt - 4) >= 120u;
  const uint32_t pv = lds32(sc + wt * 4), nx = lds32(sc + 8 + wt * 4), nc = lds32_if(g2 + 8, ends);
  const uint32_t l0 = lds32(cw), l1 = lds32(cw - 8), l2 = lds32(cw - 16), l3 = lds32(cw - 24), q0 = lds32(g2), q1 = lds32(g2 + 128), q2 = lds32(g2 - 8), q3 = lds32(g2 + 120);
  sts64(kt + 64 + wt * 8, __byte_perm(k0, pv, 0x5410), __byte_perm(k0, 0, 0x1032));
  sts64(kt + 64 + 1024 + wt * 8, __byte_perm(k1, pv, (odd || wt == 0) ? 0x7610 : 0x1010), __byte_perm(k1, nx, odd ? 0x1076 : 0x1010));
  const uint32_t cc = __byte_perm(nc, 0, 0x3232), nn = __byte_perm(nc, 0, 0x1010);
  if (ends) sts128(kt + 64 + 2048 + wt * 16, cc, cc, odd ? nc : cc, odd ? nn : nc);
  if (wt == 127) { sts128(kt + 64 + 4096, nn, nn, nn, nn); sts128(kt + 64 + 4112, nn, nn << 16, 0, 0); }
  sts128(tb + W_L3 + 512 + (wt >> 6) * 512 + wt * 16, l0, l1, l2, l3);
  if ((wt & 63) < 34) sts128(tb + W_QT - 16 + wt * 16, q0, q1, q2, q3);
}

__device__ __forceinline__ void load_a(uint32_t (&a)[4], uint32_t kp, int j) {
  a[0] = lds32(kp + 64 * j); a[1] = lds32(kp + 64 * j + 512); a[2] = lds32(kp + 64 * j - 32); a[3] = lds32(kp + 64 * j + 480);
}
__device__ __forceinline__ uint32_t band(int d, int lo, int hi) {
  return ((unsigned)(d - lo) <= (unsigned)(hi - lo) ? 1u : 0u) | ((unsigned)(d - 1 - lo) <= (unsigned)(hi - lo) ? 0x10000u : 0u);
}
__device__ __forceinline__ uint32_t hadd2u(uint32_t a, uint32_t b) { __half2 r = __hadd2(*(__half2*)&a, *(__half2*)&b); return *(uint32_t*)&r; }

__device__ __forceinline__ void zero_pads(uint32_t tb, int wt) {
  if (!(wt & 32)) sts128(tb + W_L3 + (wt >> 6) * 512 + wt * 16, 0, 0, 0, 0);
  if ((wt & 63) < 3) sts128(tb + W_CW + (wt >> 6) * 304 + (wt & 63) * 16, 0, 0, 0, 0);
}
__device__ __forceinline__ uint32_t tr_base(int lane) {
  return OFF_YT + (2 * (lane >> 3) + (lane & 1)) * YT_PITCH + ((lane >> 1) & 1) * (8 * YT_PITCH + 64) + ((lane >> 2) & 1) * 16;
}

__device__ __forceinline__ uint32_t sc_addr(int tp) { return OFF_YT + (tp < 16 ? tp * YT_PITCH + (tp >> 3) * 64 + 1152 : 8 * YT_PITCH - 512 + tp * 32); }
#define X_PS 1
#define X_PW 15
#define X_HU 16
#define X_HB 0
#define X_REL 1
#define X_PAD0 0
#define X_PAD1 0
#define PAD(n) _Pragma("unroll") for (int _i = 0; _i < (n); _i++) asm volatile("pmevent 0;");
#ifndef M_
#define M_ 12
#endif
#define X_ES 1
#define X_NE 2
#define X_SCT 10000
#define X_DELTA 0
#define X_DSTEP 2000
#define X_PF0 2500
#define X_PFD 600
#define X_TD 450
#define X_WS 6
#define X_OR 8
#define X_ABS 4950
#define X_XD 200
#define X_RD 600
#define X_HD 400
#define X_PD 1080
#define X_PROMO 2
#define X_YD2 1000
#define X_GO 1
#define X_GW 2
#define X_NS 4400
#define X_XS 13400
#define X_LAG 1500
#define X_YD 1550
struct TMaps { CUtensorMap m[10]; };
__device__ __forceinline__ uint32_t h2bf(uint32_t w) { const float2 f = h2f(w); return pack_bf(f.x, f.y); }
__device__ __forceinline__ uint32_t keep(uint32_t v) { asm volatile("" : "+r"(v)); return v; }
__device__ __forceinline__ uint2 ldr64(const void* p) { uint2 v; asm volatile("{ .reg .b64 t; ld.relaxed.gpu.global.b64 t, [%2]; mov.b64 {%0, %1}, t; }" : "=r"(v.x), "=r"(v.y) : "l"(p) : "memory"); return v; }
__host__ __device__ __forceinline__ uint32_t down_box(int s, bool five) {
  return five ? OFF_W + W_BYTES + 12288 + (s / 3) * (W_BYTES - 12288) + s * 4096 : s < 6 ? OFF_W + W_BYTES + BOX + (s >> 1) * (W_BYTES - 10240) + s * 5120 : OFF_W + (s - 6) * 5120;
}
__device__ __forceinline__ void load_tile(const CUtensorMap* tmx, int i, int c, int again = 0) {
  asm volatile("mbarrier.arrive.expect_tx.shared::cta.b64 _, [%0], 8704;" :: "r"(MB_UL + i * 16 + again) : "memory");
  asm volatile("cp.async.bulk.tensor.3d.shared::cluster.global.mbarrier::complete_tx::bytes [%0], [%1, {%3, %4, %5}], [%2];"
               :: "r"(i < 2 ? OFF_T + i * TILE : OFF_W), "l"(tmx), "r"(MB_UL + i * 16 + again), "r"(0), "r"(c), "r"(-8) : "memory");
}
template <bool FAR> __device__ __forceinline__ void load_params(const Params& p, uint32_t ch, int wt, uint32_t dst, bool on) {
  const int rel = wt < 96 ? ch * 16 + (wt & 15) : ch >> 3;
  const unsigned char* b = FAR ? p.far[min(wt >> 4, 6)] + rel * 16 : p.x + (long long)(p.off[wt >> 4] + rel) * 16;
  asm volatile("{ .reg .pred q; setp.ne.u32 q, %2, 0; @q cp.async.cg.shared.global [%0], [%1], 16; }"
               :: "r"(dst + wt * 16), "l"(b), "r"((uint32_t)(on && wt < 97)) : "memory");
}

struct ConvC { uint32_t ca, cb, bands, qa; };
__device__ __forceinline__ ConvC conv_consts(int w, int lane) {
  const int h = w & 1, P = (w >> 1) & 1, d0 = 8 * h + (lane >> 2) - 2 * (lane & 3);
  ConvC k;
  k.ca = keep((W_KT + (16 + 256 * P + d0) * 4) | (((8 + 64 * P + lane) * 64 + (((h + ((w >> 1) & 2)) ^ (lane >> 1)) & 3) * 16) << 16));
  const int u = d0 + 2 * (lane & 1) + 2, in = (u & 7) - ((u & 7) >= 5 ? 5 : 0) - 2 * (lane & 1);
  k.cb = keep(in > 0 ? 0x1010 : in == 0 ? 0x3210 : 0x3232);
  k.qa = keep(W_QT + (2 * (u >> 3) + ((u & 7) >= 5) + 64 * P) * 16);
  k.bands = keep(band(d0, 12, 20) + 2 * band(d0 + 8, 12, 20) + 4 * band(d0 + 16, 12, 20) + 8 * band(d0 + 24, 12, 20)
                 + 16 * band(d0 - 8, 5, 11) + 32 * band(d0, 5, 11) + 64 * band(d0 + 8, 5, 11) + 128 * band(d0 + 16, 5, 11));
  return k;
}
struct ConvPre { uint32_t e0, e2, f2, b0, b2, a[3][4]; };
__device__ __forceinline__ void conv_pre(ConvPre& r, uint32_t kp, uint32_t qp, int part, bool on, bool P) {
  if (part & 1) {
    r.e0 = lds32_if(kp + 4096, on && !P); r.e2 = lds32_if(kp + 4064, on && !P); r.f2 = lds32_if(kp + 4128, on && !P);
    r.b0 = lds32_if(kp + 2048, on && !P); r.b2 = lds32_if(kp + 2016, on && !P);
  }
#pragma unroll
  for (int j = 0; j < 3; j++) if (part & (j < X_PS ? 1 : 2))
    asm volatile("{ .reg .pred q; setp.ne.u32 q, %5, 0; mov.b32 %0, 0; mov.b32 %1, 0; mov.b32 %2, 0; mov.b32 %3, 0; @q ld.shared.v4.b32 {%0,%1,%2,%3}, [%4]; }"
                 : "=r"(r.a[j][0]), "=r"(r.a[j][1]), "=r"(r.a[j][2]), "=r"(r.a[j][3]) : "r"(qp + 64 * j), "r"((uint32_t)on) : "memory");
}
__device__ __forceinline__ void conv_item(uint32_t tb, uint32_t tl, int bid, int bn, ConvPre& pre, const ConvC& cv, uint32_t zero, const CUtensorMap* tmx, int ch, int warp, int lane, bool hold, bool more) {
  const bool go = more && warp == 0 && lane == 0;
  const uint32_t kp = tb + (cv.ca & 0xFFFFu), qp = tb + cv.qa;
  const uint32_t dlo = (tl >> 4) + 32 + ((warp >> 1) & 2) + (1u << 16), dhi = 32u | (2u << 30);
  const bool P = warp & 2;
  float a32[16], b32[16], a64[32];
  uint32_t A[40][4];
#define STEP(J) { wgmma64<0>(a64, A[J], dlo + 256 - 4 * (J), dhi); \
    if ((J) == 32) wgmma32_init<0>(b32, A[J], dlo, dhi); else wgmma32<0>(b32, A[J], ((J) < 8 ? dlo ^ zero : dlo) + 128 - 4 * (J), dhi); \
    if ((J) == 0) wgmma32_init<0>(a32, A[J], dlo, dhi); else if ((J) < 8) wgmma32<0>(a32, A[J], (dlo ^ zero) - 4 * (J), dhi); }
#define LD(J) load_a(A[J], kp, J);
#define LQ(J) { const uint4 v = lds128(qp + 64 * ((J) - 32)); A[J][0] = v.x; A[J][1] = v.y; A[J][2] = v.z; A[J][3] = v.w; }
#define PQ(J) { A[J][0] = prmt(A[J][0], 0, cv.cb); A[J][1] = prmt(A[J][1], 0, cv.cb); A[J][2] = prmt(A[J][2], 0, cv.cb); A[J][3] = prmt(A[J][3], 0, cv.cb); }
#define FIRST(J) wg_fence(); STEP(J) wg_commit(); wg_wait<1>(); wg_fence();
  {
    uint32_t win[16], x9[4], x7[4], e[4], f[4];
    const uint32_t bz = keep(cv.bands);
#define BAND(i) keep((bz & (0x10001u << (i))) * (0x3C00u >> (i)))
    e[0] = pre.e0; e[2] = pre.e2; e[1] = keep(bz & 0x100u); e[3] = keep(bz & 0x200u);
    f[2] = pre.f2; f[0] = keep(bz & 0x4000u); f[1] = keep(bz & 0x8000u); f[3] = keep(bz & 0x300u);
#pragma unroll
    for (int j = 0; j < 12; j++) A[32 + j / 4][j & 3] = pre.a[j / 4][j & 3];
    PQ(32) PQ(33) PQ(34)
    if (!P) { A[32][0] = pre.b0; A[32][2] = pre.b2; }
    const uint32_t q[12] = {BAND(0), BAND(5), keep(bz & 0x400u), BAND(4), BAND(2), BAND(7), BAND(1), BAND(6), keep(bz & 0x800u), keep(bz & 0x1000u), BAND(3), keep(bz & 0x2000u)};
#undef BAND
    const uint32_t ta = keep(tl + 512 + (warp & 3) * 2048 + lane * 64 + (lane & 6) * 8);
    if (X_GO && hold) mbar_wait(MB_GO);
    uint32_t mbl = MB_UL + (warp & 8) * 2, ph = 0;
#pragma unroll 1
    for (int it = 0; it < SPIN_MAX; it++) {
      if (ch < 512) mbar_wait(mbl, ph);
      if (it == 1) TS(13);
      TS(3);
      wg_fence();
      wgmma64h_init(win, q[0], q[1], q[2], q[3], dlo, dhi);
      wgmma64h(win, q[4], q[5], q[6], q[7], dlo - 4, dhi);
      wgmma64h(win, q[8], q[9], q[10], q[11], dlo - 8, dhi);
      wg_commit();
      wgmma64_init<0>(a64, e, dlo, dhi);
      wgmma64<0>(a64, f, dlo - 4, dhi);
      wg_commit();
      if (ch >= 512) break;
      uint32_t r0, r1, r2, r3, ok;
      if (warp & 4) {
        mbar_wait(mbl + 8);
        if (__all_sync(0xffffffffu, it || lds32(MISC_RT + (warp & 8)) == 0)) break;
        wg_wait<0>();
        continue;
      }
      ldsm4(ta, r0, r1, r2, r3);
      ok = r0 & r1 & r2 & r3;
      ldsm4(ta ^ 32, r0, r1, r2, r3);
      asm volatile("{ .reg .pred q; setp.ne.u32 q, %1, 0; barrier.red.and.pred q, %2, 128, q; selp.u32 %0, 1, 0, q; }" : "=r"(ok) : "r"((ok & r0 & r1 & r2 & r3 & 1u) | (lane & 3)), "r"(1 + (warp >> 2)) : "memory");
      if (ok) { if ((warp & 3) == 0 && lane == 0) { sts32(MISC_RT + warp, it); mbar_arrive(MB_UL + 8 + warp * 2); } break; }
      wg_wait<0>();
      if ((warp & 3) == 0 && lane == 0) load_tile(tmx - 1, warp >> 3, ch, 56);
      mbl = MB_UL + 56 + (warp & 8) * 2; ph = it & 1;
    }
    wg_wait<1>();
#pragma unroll
    for (int i = 0; i < 4; i++) {
      const int tl = 2 * ((i & 1) + ((i & 2) ? 0 : 4));
      x9[i] = P ? win[tl + 4] : win[tl]; x7[i] = P ? win[tl + 5] : win[tl + 1];
    }
    const uint32_t l3lo = ((tb + W_L3) >> 4) + (32u << 16);
    wg_fence();
    wgmma64<0>(a64, x9, l3lo, 8);
    wgmma64<0>(a64, x7, l3lo + 96, 8);
    wg_commit();
  }
  STEP(32) STEP(33) STEP(34) wg_commit(); wg_wait<1>();
  LQ(35) LQ(36) LQ(37) LQ(38) PQ(35) PQ(36) PQ(37) PQ(38)
  FIRST(35) STEP(36) STEP(37) STEP(38) wg_commit();
  LQ(39) LD(0) PQ(39)
  TS(17);
  if (X_GO == 1 && go) mbar_arrive(MB_GO);
  FIRST(39) STEP(0) wg_commit();
  LD(1) LD(2) LD(3)
  FIRST(1) STEP(2) STEP(3) wg_commit();
  LD(4) LD(5)
  if (X_GO == 2 && go) mbar_arrive(MB_GO);
  FIRST(4) STEP(5) wg_commit();
  LD(6) LD(7)
  wg_fence(); STEP(6) STEP(7) wg_commit();
#undef STEP
#undef LD
#undef LQ
#undef PQ
#undef FIRST
  TS(18);
  if (X_GO == 3 && go) mbar_arrive(MB_GO);
  const uint32_t xc = tb + W_KT + (warp & 3) * 1024 + lane * 16;
  if (more) bar_sync(7, 288);
  wg_wait<1>();
  conv_pre(pre, kp + ALT, qp + ALT, 1, more, P);
  wg_wait<0>();
  conv_pre(pre, kp + ALT, qp + ALT, 2, more, P);
  uint32_t E[16], o[8];
#define ACC(i) ((i) < 16 ? a32[i] : (i) < 32 ? b32[(i) - 16] : a64[(i) - 32])
  E[0] = pack_h(a32[0], a32[1]);
#pragma unroll
  for (int i = 1; i < 16; i++) E[i] = pack_h(ACC(4 * i) + ACC(4 * i - 2), ACC(4 * i + 1) + ACC(4 * i - 1));
#undef ACC
#pragma unroll
  for (int j = 0; j < 8; j++) o[j] = P ? (j < 2 ? 0u : E[j - 2]) : E[8 + j];
  sts128(xc, o[0], o[1], o[2], o[3]); sts128(xc + 512, o[4], o[5], o[6], o[7]);
#pragma unroll
  for (int j = 0; j < 8; j++) o[j] = P ? E[6 + j] : E[j];
  TS(25);
  if (more) {
    sts128(xc + 4096, o[0], o[1], o[2], o[3]); sts128(xc + 4608, o[4], o[5], o[6], o[7]);
    bar_arrive(12, 192);
    return;
  }
  bar_sync(1 + (warp >> 2), 128);
  const uint4 vv[2] = {lds128(xc + (P ? -2048 : 2048)), lds128(xc + (P ? -1536 : 2560))};
  const uint32_t mk = lane < 8 ? 0xFFFEFFFEu : ~0u;
#pragma unroll
  for (int q = 0; q < 2; q++) {
    const uint4 v = vv[q];
    stsm4t(tl + (cv.ca >> 16) + q * 2048, hadd2u(o[4 * q], v.x) & mk, hadd2u(o[4 * q + 1], v.y) & mk, hadd2u(o[4 * q + 2], v.z) & mk, hadd2u(o[4 * q + 3], v.w) & mk);
  }
  fence_async();
  bar_sync(bid, bn);
  if (warp == 0 && lane == 0) mbar_arrive(MB_REL);
  if ((warp & 7) == (ch < 512 ? 7 : 3) && lane == 0) {
    asm volatile("cp.async.bulk.tensor.3d.global.shared::cta.bulk_group [%0, {%3, %2, %3}], [%1];" :: "l"(tmx), "r"(tl + 512), "r"(ch), "r"(0) : "memory");
    asm volatile("cp.async.bulk.commit_group;" ::: "memory");
  }
}

template <bool FAR> __global__ void __launch_bounds__(NT, 1)
fused_kernel(const __grid_constant__ Params p, const __grid_constant__ TMaps tm) {
  extern __shared__ __align__(1024) unsigned char smem[];
  const int c = blockIdx.x;
  const bool five = (c & 1) == 0;
  const uint32_t pitch = five ? 64 : 80;
  const uint32_t ones = 0x3F803F80u;
  const int tid = threadIdx.x, lane = tid & 31;
  const uint32_t xrow = OFF_YT + ((tid & 127) >> 3) * YT_PITCH + (tid & 64) + (tid & 7) * 16;
  {
    const int w4 = tid >> 7;
    load_params<FAR>(p, w4 < 2 ? 2 * c + w4 : five ? 257 + 2 * c : 512 + (c >> 1), tid & 127, OFF_W + W_KT + (w4 < 2 ? w4 * W_BYTES : five ? 3 * W_BYTES : 3 * W_BYTES + 2048), (0xB >> w4) & 1);
  }
  if ((tid >> 7) == 2) {
    const unsigned char* xp = p.x + (uint32_t)((c * 16 - 32 + (tid >> 3)) * 1152 + (tid & 7) * 16);
    asm volatile("" : "+l"(xp));
    { const uint32_t tq = clock(); while ((int)(clock() - tq) < X_XD) {} }
#pragma unroll
    for (int k = 0; k < 9; k++) asm volatile("cp.async.cg.shared.global [%0], [%1], 16;" :: "r"(xrow + k * 128), "l"(xp + k * 128) : "memory");
  }
  const int warp = (int)uni(tid >> 5), wg = warp >> 2;
  TS(0);
  if (__builtin_expect(wg == 4, 0)) {
    asm volatile("setmaxnreg.dec.sync.aligned.u32 32;");
    const int role = warp;
    const int u0 = (c >> 1) * 9 + (five ? ((c & 2) ? 5 : 0) : ((c & 2) ? 0 : 4));
    const uint32_t t0 = clock() + c * 4;
    if (role == 16) {
      if (lane < 19) asm volatile("mbarrier.init.shared::cta.b64 [%0], %1;" :: "r"(OFF_MISC + lane * 8), "r"((unsigned)(lane - 2) < 4u ? 4 : 1) : "memory");
      if (lane < 2) asm volatile("mbarrier.arrive.expect_tx.shared::cta.b64 _, [%0], %1;" :: "r"(OFF_MISC + lane * 8), "r"(lane ? (five ? 36864 : 51200) : pitch * 1152) : "memory");
      fence_async();
      bar_arrive(5, 608);
      const CUtensorMap* tmb = &tm.m[five ? 3 : 0];
#pragma unroll 1
      for (int u = 0; u < 17; u++) {
        const uint32_t e = p.sched[five][u], kind = e & 3, s = (e >> 2) & 15, dst = e >> 14;
        if (kind == 3) continue;
        while ((int)(clock() - t0) < X_PF0 + (u < X_NE ? u * X_PFD : X_LAG + u * X_TD)) __nanosleep(20);
        if (e & 0x3FC0) mbar_wait(OFF_MISC + ((e >> 6) & 255));
        if (lane == 0) {
          if (kind == 2) asm volatile("cp.async.bulk.tensor.3d.shared::cluster.global.mbarrier::complete_tx::bytes [%0], [%1, {%3, %4, %5}], [%2];"
                                      :: "r"(dst), "l"(tmb + 2), "r"(MB_D), "r"(0), "r"(u0 * 8), "r"(s) : "memory");
          else tma_box(dst, tmb + kind, MB_GU, u0 * 8, s * 96);
        }
        if (u == 5) TS(2);
        if (u == 10) TS(3);
      }
      TS(4);
      TS_DUMP();
#define FINISH0 bar_sync(12, 192);        \
        _Pragma("unroll 1") for (int w = role & 2; w < (role & 2) + 2; w++) { \
          const uint32_t xa = OFF_W + W_KT + lane * 16, mk = lane < 8 ? 0xFFFEFFFEu : ~0u, ya = OFF_T + (8 + lane) * 64 + (((w & 1) ^ (lane >> 1)) & 3) * 16 + (w & 2) * 2048; \
          const uint4 a = lds128(xa + 4096 + w * 1024), b = lds128(xa + (w ^ 2) * 1024), d = lds128(xa + 4608 + w * 1024), e = lds128(xa + 512 + (w ^ 2) * 1024); \
          stsm4t(ya, hadd2u(a.x, b.x) & mk, hadd2u(a.y, b.y) & mk, hadd2u(a.z, b.z) & mk, hadd2u(a.w, b.w) & mk); \
          stsm4t(ya + 2048, hadd2u(d.x, e.x) & mk, hadd2u(d.y, e.y) & mk, hadd2u(d.z, e.z) & mk, hadd2u(d.w, e.w) & mk); \
        } \
        fence_async();
    } else if (role == 17) {
      if (smem_u32(smem) != SB) __trap();
      bar_sync(10, 576);
      if (lane == 0) {
        fence_async();
        while ((int)(clock() - t0) < X_NS - c * 4) {}
        asm volatile("cp.async.bulk.global.shared::cta.bulk_group [%0], [%1], 10240;" :: "l"(&p.s->X[c * DM * 2 + 512]), "r"(OFF_G) : "memory");
        asm volatile("cp.async.bulk.commit_group;" ::: "memory");
        asm volatile("cp.async.bulk.wait_group 0;" ::: "memory");
      }
      if (lane == 0) mbar_arrive(MB_GF);
      bar_arrive(11, 96);
      if (five) { FINISH0 bar_arrive(13, 192); }
    } else if (role == 18) {
      sts32(MISC_EPOCH, 0);
      sts32(MISC_T0, t0 - c * 4);
      bar_arrive(5, 608);
      uint4* q = lane < 2 ? &p.s->R[c * 2 + lane] : lane < 11 ? &p.s->HS[c * 9 + lane - 2] : lane == 11 ? &p.s->HS[1152 + (c & 7)] : (uint4*)&p.s->FLAG[c * 8];
      if (lane < (c < 8 ? 12 : 11)) str128(q, ~0u, ~0u, ~0u, ~0u);
      const uint32_t ep = __shfl_sync(0xffffffffu, ldr32(q), 31) + 1u;
      sts32(MISC_EPOCH, ep | 0x80000000u);
      TSX(21);
      if (lane == 31) str32(q, ep);
      bar_sync(11, 96);
      TSX(14);
      mbar_wait(MB_KF + (lane & 3) * 8);
      __syncwarp();
      { const uint2 e = lds64(MISC_EM); if (lane < 2) str128(&p.s->SC[c * 2 + lane], e.x, __byte_perm(e.y, ep, 0x6540), 0, 0); }
      TSX(17);
      while ((int)(clock() - t0) < X_SCT) __nanosleep(100);
      TSX(18);
      {
        uint2 v[4];
#pragma unroll 1
        for (int it = 0; it < SPIN_MAX; it++) {
          uint32_t bad = 0;
#pragma unroll
          for (int q = 0; q < 4; q++) v[q] = ldr64(&p.s->SC[lane * 2 + q * 64]);
#pragma unroll
          for (int q = 0; q < 4; q++) bad |= (v[q].y >> 8) ^ (ep & 0xFFFFFFu);
          if (!__any_sync(0xffffffffu, bad)) break;
        }
        TSX(25);
#pragma unroll
        for (int q = 0; q < 4; q++) {
          const uint32_t sa = (lane >> 4) * YT_PITCH + (lane & 15) * 2;
          sts16(sc_addr(2 * q) + sa, v[q].x); sts16(sc_addr(8 + 2 * q) + sa, v[q].x >> 16);
          if (lane & 1) asm volatile("st.shared.u8 [%0], %1;" :: "r"(sc_addr(16) + q * 16 + (lane >> 1)), "r"(v[q].y) : "memory");
        }
      }
      __syncwarp();
      if (lane == 0) mbar_arrive(MB_SC);
      TSX(27);
    } else {
      uint32_t w[9];
      const uint32_t dk = ldnc16(p.dskip + ((lane & 4) ? 512 + (c >> 1) : (lane & 2) * 128 + 2 * c + (lane & 1)));
      float s = 0.f;
#pragma unroll
      for (int i = 0; i < 9; i++) w[i] = ldnc32(p.w_r + lane + 32 * i);
      sts16(OFF_WR + 1152 + lane * 2, dk);
      bar_arrive(5, 608);
#pragma unroll
      for (int i = 0; i < 9; i++) { sts32(OFF_WR + lane * 4 + i * 128, w[i]); s += bf_lo(w[i]) + bf_hi(w[i]); }
      sts32(MISC_SW, __float_as_uint(warp_sum(s)));
      TSX(23);
      bar_sync(10, 576);
      if (lane == 0) {
        const uint32_t tp = clock();
        TSX(1);
        while ((int)(clock() - tp) < X_DELTA || (int)(clock() - t0) < X_ABS - c * 4) {}
        TSX(24);
        load_tile(&tm.m[6], 0, c);
        TSX(15);
        while ((int)(clock() - t0) < X_ABS + X_DSTEP - c * 4) {}
      }
      bar_sync(11, 96);
      if (lane == 0) {
        load_tile(&tm.m[6], 1, 128 + c);
      }
      if (five) {
        mbar_wait(MB_KF);
#pragma unroll 1
        for (int it = 0; it < SPIN_MAX; it++) {
          if (lane == 0) load_tile(&tm.m[8], 2, 512 + (c >> 1));
          mbar_wait(MB_UL + 32, it & 1);
          uint32_t m = 1;
#pragma unroll
          for (int q = 0; q < 4; q++) { uint32_t r0, r1, r2, r3; ldsm4(OFF_W + 512 + lane * 64 + (lane & 6) * 8 + q * 2048, r0, r1, r2, r3); m &= r0 & r1 & r2 & r3; }
          if (__all_sync(0xffffffffu, m || (lane & 3))) break;
        }
        bar_arrive(7, 288);
        FINISH0
        bar_arrive(13, 192);
      }
      bar_sync(0, 544);
      if (lane == 0) mbar_arrive(MB_H);
    }
    return;
  }
  const int wt = tid & 127, g = lane >> 2, t = lane & 3;
  const uint32_t wb = OFF_W + wg * W_BYTES;
  asm volatile("cp.async.commit_group;" ::: "memory");
  const ConvC cv = conv_consts(warp, lane);
  zero_pads(wb, wt);
  load_params<FAR>(p, 254 + 2 * c + wg, wt, wb + W_KT, wg == 2 || (wg == 3 && !five));
  asm volatile("cp.async.commit_group;" ::: "memory");
  asm volatile("setmaxnreg.inc.sync.aligned.u32 112;");
  PAD(X_PAD0)
  {
    uint4 kw;
    uint4* kx = &p.s->KX[(c >> 1) * 128 + wt];
    bool two = wg == 3;
    uint32_t ep;
    int em = 0;
    uint32_t slot = wg + (two && !five);
    const uint32_t ra0 = wb + W_KT + (slot & 4) * 512 + wt * 2, ra6 = wb + W_KT + 1536 + (slot & 4) * 512 + (((slot & 4) ? c >> 1 : 2 * c + (wg & 1)) & 7) * 2;
    uint32_t raw[7];
    if (wg != 2) {
      asm volatile("cp.async.wait_group 1;" ::: "memory");
      bar_sync(1 + wg, 128);
#pragma unroll
      for (int i = 0; i < 7; i++) raw[i] = lds16(i < 6 ? ra0 + i * 256 : ra6);
    }
    int phase = wg == 2 ? 3 : 2;
#pragma unroll 1
    for (;;) {
      if (phase != 3) {
        KgState ks;
        TS(22);
        kgen_tables_n(raw, wb, wt, ks);
        TS(20);
        bar_sync(1 + wg, 128);
        em = kgen_tables_m(wb, wt, ks);
        fence_async();
      }
      if (phase & 2) {
        const int lz = lane ^ (clock() & p.off[7]);
        const uint32_t tr_addr = pin(tr_base(lz) + warp * 32), lca = pin(MISC_LN1 + (lz & 1) * 16);
        uint4* dst;
        { const unsigned long long a = (unsigned long long)&p.s->X[c * DM * 2 + warp * 32 + (8 * ((lz >> 1) & 1) + (lz >> 2)) * 2 + (lz & 1)];
          dst = (uint4*)(((unsigned long long)pin(a >> 32) << 32) | pin((uint32_t)a)); }
        if (phase == 3) {
        asm volatile("cp.async.wait_group 1;" ::: "memory");
        TS(21);
        float d[3][4], r;
        uint4 a[9];
#pragma unroll
        for (int k = 0; k < 9; k++) a[k] = lds128(xrow + k * 128);
#pragma unroll
        for (int i = 0; i < 4; i++) d[0][i] = d[1][i] = d[2][i] = 0.f;
#pragma unroll
        for (int k = 0; k < 9; k++) { mma_bf16(d[(2 * k) % 3], a[k].x, ones, a[k].y, ones, a[k].x, a[k].y); mma_bf16(d[(2 * k + 1) % 3], a[k].z, ones, a[k].w, ones, a[k].z, a[k].w); }
#pragma unroll
        for (int i = 0; i < 4; i++) d[0][i] += d[1][i] + d[2][i];
        const LnC lc = ln_consts(d[0][2] + d[0][3], __shfl_sync(0xffffffffu, d[0][0], 9 * t) + __shfl_sync(0xffffffffu, d[0][1], 9 * t + 4), r);
        if (lane < 12) sts16(MISC_LN1 + g * 32 + (warp & 3) * 8 + t * 2, lane < 4 ? lc.m2 : lane < 8 ? lc.rh2 : lc.rl2);
        }
        asm volatile("cp.async.wait_group 0;" ::: "memory");
        TS(23);
        bar_sync(5, 608);
        uint32_t x[3][4];
        ldsm4t(tr_addr, x[0][0], x[0][1], x[0][2], x[0][3]);
        uint4 m = lds128(lca);
        const uint4 rl = lds128(lca + 64), rh = lds128(lca + 32);
        ldsm4t(tr_addr + 512, x[1][0], x[1][1], x[1][2], x[1][3]);
        if (wg == 3) ldsm4t(tr_addr + 640, x[2][0], x[2][1], x[2][2], x[2][3]);
#pragma unroll
        for (int q = 0; q < 3; q++) {
          if (q < 2 || wg == 3) {
            const uint32_t r0 = ln_apply(x[q][0], m.x, rh.x, rl.x), r1 = ln_apply(x[q][1], m.y, rh.y, rl.y), r2 = ln_apply(x[q][2], m.z, rh.z, rl.z), r3 = ln_apply(x[q][3], m.w, rh.w, rl.w);
            const uint32_t w0 = (pack_h(bf_lo(r0), bf_hi(r0)) & 0xFFFEFFFEu) | 1u, w1 = pack_h(bf_lo(r1), bf_hi(r1)), w2 = pack_h(bf_lo(r2), bf_hi(r2)), w3 = pack_h(bf_lo(r3), bf_hi(r3));
            if (q == 0) str128(dst, w0, w1, w2, w3);
            else sts128(OFF_G + warp * 512 + (8 * (t >> 1) + g) * 32 + (t & 1) * 16 + (q == 2 ? 2048 : 0), w0, w1, w2, w3);
          }
          if (q == 0 && X_ES) {
            const uint32_t z = clock() & p.off[7];
            m.x ^= z; m.y ^= z; m.z ^= z; m.w ^= z;
          }
          if (q == 0) TS(30);
          if (q == 0 && wg >= 2) {
#pragma unroll
            for (int i = 0; i < 7; i++) raw[i] = lds16(wb + W_KT + i * 256 + (i < 6 ? wt : (2 * c + (wg & 1)) & 7) * 2);
          }
        }
        bar_arrive(10, 576);
        TS(1);
      } else bar_sync(1 + wg, 128);
      phase &= 1;
      if (phase) { phase = 0; continue; }
      TS(14);
      float acc[20];
      const uint32_t alo = (wb >> 4) | (8u << 16);
      uint4 k4 = lds128(wb + W_MISC + 16);
      uint32_t dk = lds16(OFF_WR + 1152 + slot * 2);
      wg_fence();
      wgmma40_ss_init(acc, alo, alo + 1024, 2048 >> 4);
#pragma unroll
      for (int k = 1; k < 8; k++) wgmma40_ss(acc, alo + k * 16, alo + 1024 + k * 16, 2048 >> 4);
      wg_commit();
      { const uint32_t z = clock() & p.off[7]; dk ^= z; k4.x ^= z; k4.z ^= z; }
      const float k2048 = (float)(int)((k4.x + k4.y) + (k4.z + k4.w)) * (1.f / 262144.f);
      const int ef = max(em, min((int)((dk >> 7) & 255u) - 7, 238));
      asm volatile("st.shared.u8 [%0], %1;" :: "r"(MISC_EM + slot), "r"(ef + 9) : "memory");
      const float un = __uint_as_float((uint32_t)max(114 + em - ef, 0) << 23), d0 = wt ? 0.f : bf_lo(dk) * __uint_as_float((uint32_t)(245 - ef) << 23);
      wg_wait<0>();
      kw.x = pack_h(fmaf(acc[0] - acc[3], un, d0), (acc[4] - acc[7]) * un);
      kw.y = pack_h((acc[8] - acc[11]) * un, (acc[12] - acc[15]) * un);
      kw.z = pack_h((acc[16] - acc[19]) * un, k2048 * un);
      TS(24);
      ep = 0;
      if (two) SPIN_WHILE(ep == 0, ep = lds32(MISC_EPOCH));
      if (five || !two) break;
      str128(kx, kw.x, kw.y, kw.z, ep);
      two = false;
      slot = 3;
      bar_sync(1 + wg, 128);
    }
    if (lane == 0) mbar_arrive(MB_KF + wg * 8);
    if (two) { mbar_wait(MB_KF); zero_pads(OFF_W + ALT, wt); }
    uint32_t tb = wb;
#pragma unroll 1
    for (;;) {
      kgen_build(tb, wg, wt, kw.x, kw.y, kw.z);
      TS(15);
      if (!two) break;
      two = false;
      kw.w = 0;
      SPIN_WHILE(kw.w != ep, kw = ldr128(kx));
      tb = OFF_W + ALT;
    }
    fence_async();
    TS(31);
    if (tb != wb) bar_arrive(7, 288);
    bar_sync(1 + wg, 128);
  }
  uint32_t tpub;
  ConvPre pre;
  conv_pre(pre, (wb ^ p.off[7]) + (cv.ca & 0xFFFFu), (wb ^ p.off[7]) + cv.qa, 3, true, warp & 2);
#pragma unroll 1
  for (int item = 0;; item++) {
    TS(2);
    conv_item(item ? OFF_W + ALT : wb, item ? OFF_W : OFF_T + (wg >> 1) * TILE, item ? 1 : 13 + (wg >> 1), item ? 128 : five && wg == 1 ? 192 : 256, pre, cv, p.off[7],
              &tm.m[item ? 9 : 7], item ? 512 + (c >> 1) : (wg >> 1) * 128 + c, warp, lane, five && wg >= X_GW, five && !wg && !item);
    tpub = clock() - (item ? X_YD : wg >= 2 ? X_YD2 : 0);
    if (wg || !five || item) break;
    TS(27);
  }
  TS(4);
  PAD(X_PAD1)

  const int ln = lane ^ p.off[7], td = warp * 32 + ln, gg = ln >> 2, tt = ln & 3;
  const int tok = c * 16 + warp;
  const int fu = warp / 3, fk = warp - fu * 3;
  uint32_t wa[12][4];
  uint4 ha[3];
  const uint4* hsrc = &p.s->HS[td + (td / 24) * 48];
  {
    uint32_t hw[9], wr[9];
    const uint32_t row = keep(OFF_YT + warp * YT_PITCH + (warp >> 3) * 64 + ln * 16);
    const uint32_t wabase = keep(((ln & 8) ? OFF_W + (fk + 1) * W_BYTES : OFF_G + fk * 192 * pitch) + ((ln >> 4) * 8 + (ln & 7)) * pitch
                                 + (five ? ((fu ^ (ln >> 1)) & 3) : min(fu, 4)) * 16);
    float sw;
    {
      const bool three = wg == 1;
      const int ch = 8 * (tt >> 1) + gg;
      const uint32_t tr_addr = tr_base(ln);
      const uint4* ysrc = &p.s->X[c * DM * 2 + ch * 2 + (tt & 1)];
      uint32_t x[3][4], s[3];
      uint4 v[3];
#define TL(q) ((q) < 2 ? 2 * warp + (q) : 28 + warp)
      asm volatile("cp.async.bulk.wait_group.read 0;" ::: "memory");
      if (wg >= 2) { const uint32_t ts = lds32(MISC_T0); while ((int)(clock() - ts) < X_XS) {} }
      while ((int)(clock() - tpub) < X_YD) {}
      TS(5);
      v[0] = ldr128(ysrc + TL(0) * 32); v[1] = ldr128(ysrc + TL(1) * 32); v[2] = make_uint4(three, 0, 0, 0);
      if (X_REL == 1 || (X_REL == 2 && wg != 1)) mbar_wait(MB_REL);
#pragma unroll
      for (int i = 0; i < 6; i++) if (i < 4 || three) wr[i] = (gg & 2) ? ones : lds32(OFF_WR + TL(i >> 1) * 32 + (i & 1) * 16 + tt * 4);
      const uint32_t ha = keep(OFF_YT + (ln & 7) * YT_PITCH + (ln >> 4) * (8 * YT_PITCH + 64) + (ln & 8) * 2);
      const uint32_t pa = keep(OFF_PART + warp * 4 + ((gg & 2) * 8 + (gg & 4) * 2 + 2 * tt + (gg & 1)) * 80), pb = keep(OFF_PART + 2560 + warp * 4 + gg * 80);
      float dl[4] = {0.f, 0.f, 0.f, 0.f}, dh[4] = {0.f, 0.f, 0.f, 0.f};
      sw = __uint_as_float(lds32(MISC_SW));
#pragma unroll
      for (int q = 0; q < 3; q++) {
        if (q < 2 || three) {
          ldsm4t(tr_addr + TL(q) * 32, x[q][0], x[q][1], x[q][2], x[q][3]);
        }
      }
      mbar_wait(MB_SC);
#pragma unroll
      for (int q = 0; q < 3; q++) {
        asm volatile("ld.shared.u8 %0, [%1];" : "=r"(s[q]) : "r"((q < 2 ? sc_addr(warp) + q * 16 : sc_addr(16) + (warp & 3) * 16) + ch) : "memory");
        s[q] = keep(s[q] * 0x800080u);
      }
#define FIN(q) stsm4t(tr_addr + TL(q) * 32, bf_fma2(h2bf(v[q].x), s[q], x[q][0]), bf_fma2(h2bf(v[q].y), s[q], x[q][1]), bf_fma2(h2bf(v[q].z), s[q], x[q][2]), bf_fma2(h2bf(v[q].w), s[q], x[q][3]));
      SPIN_WHILE((v[0].x | v[1].x) & 1u, _Pragma("unroll") for (int q = 0; q < 3; q++) if (v[q].x & 1u) v[q] = ldr128(ysrc + TL(q) * 32));
      if (v[2].x & 1u) v[2] = ldr128(ysrc + TL(2) * 32);
#define STAT(q) { uint32_t r0, r1, r2, r3; ldsm4(ha + TL(q) * 32, r0, r1, r2, r3); \
        mma_bf16(dl, r0, wr[2 * q], r1, wr[2 * q + 1], r0, r1); mma_bf16(dh, r2, wr[2 * q], r3, wr[2 * q + 1], r2, r3); }
      FIN(0) FIN(1)
      __syncwarp();
      STAT(0) STAT(1)
      if (three) {
        SPIN_WHILE(v[2].x & 1u, if (v[2].x & 1u) v[2] = ldr128(ysrc + TL(2) * 32));
        FIN(2)
        __syncwarp();
        STAT(2)
      }
      if (gg & 1) { dl[0] = dl[1]; dl[2] = dl[3]; dh[0] = dh[1]; dh[2] = dh[3]; }
      sts32(pa, __float_as_uint((gg & 4) ? dh[2] : dl[2]));
      if (tt == (gg >> 1)) { sts32(pb, __float_as_uint(dl[0])); sts32(pb + 640, __float_as_uint(dh[0])); }
#undef STAT
#undef FIN
#undef TL
    }
    uint32_t ra = keep(OFF_PART + (ln & 15) * 80 + (ln & 16) * 2);
    uint16_t* rp = (uint16_t*)p.s->R + c * 16 + (ln & 15);
    const uint2* rsrc = (const uint2*)p.s->R + td;
    asm volatile("" : "+l"(rp), "+l"(rsrc), "+l"(hsrc));
    uint2 rv = make_uint2(0u, 0u);
    TS(28);
    if (warp != X_PW) bar_sync(0, 544);
    else {
      float z[3], rd;
      asm volatile("bar.sync 0, 544;" : "+r"(ra) :: "memory");
#pragma unroll
      for (int k = 2; k >= 0; k--) {
        const uint4 a = lds128(ra + k * 1280), b = lds128(ra + k * 1280 + 16);
        z[k] = ((__uint_as_float(a.x) + __uint_as_float(a.y)) + (__uint_as_float(a.z) + __uint_as_float(a.w))) + ((__uint_as_float(b.x) + __uint_as_float(b.y)) + (__uint_as_float(b.z) + __uint_as_float(b.w)));
      }
#pragma unroll
      for (int k = 2; k >= 0; k--) z[k] += __shfl_xor_sync(0xffffffffu, z[k], 16);
      const LnC l = ln_consts(z[1], z[2], rd);
      const uint32_t b = pack_bf(0.f, fmaf(-bf_lo(l.m2), sw, z[0]) * rd);
      const uint32_t k16 = max(min((b ^ (((int)b >> 31) | 0x80000000u)) >> 16, 0xFFFEu), 1u);
      if (ln < 16) str16(rp, k16);
      sts64(OFF_RK + (ln & 15) * 8, __byte_perm(l.m2, l.rh2, 0x5410), __byte_perm(l.rl2, k16, 0x5410));
      sts128(MISC_CNT + ln * 16, 0, 0, 0, 0);
    }
    mbar_wait(MB_GU);
#define LD_HW { const uint4 a = lds128(row), b = lds128(row + 512); hw[8] = lds32(row + 1024 - ln * 12); \
      hw[0] = a.x; hw[1] = a.y; hw[2] = a.z; hw[3] = a.w; hw[4] = b.x; hw[5] = b.y; hw[6] = b.z; hw[7] = b.w; }
    LD_HW
    const uint32_t tr0 = clock();
    bar_sync(5, 512);
    TS(7);
    const uint2 lk = lds64(OFF_RK + warp * 8);
    LnC l2;
    l2.m2 = __byte_perm(lk.x, 0, 0x1010); l2.rh2 = __byte_perm(lk.x, 0, 0x3232); l2.rl2 = __byte_perm(lk.y, 0, 0x1010);
    const uint32_t key = (lk.y & 0xFFFF0000u) | (2047 - tok);
    uint32_t loc = ln < 16 ? (lds32(OFF_RK + 4 + ln * 8) & 0xFFFF0000u) | (2047 - c * 16 - ln) : 0u;
    int rank = __popc(__ballot_sync(0xffffffffu, loc > key));
#pragma unroll
    for (int i = 0; i < 9; i++) wr[i] = keep(ln_apply(hw[i], l2.m2, l2.rh2, l2.rl2));
#define OUT_ROW { uint32_t* o = p.out + tok * 288 + ln * 4; \
      *(uint4*)o = make_uint4(bf_add2(hw[0], wr[0]), bf_add2(hw[1], wr[1]), bf_add2(hw[2], wr[2]), bf_add2(hw[3], wr[3])); \
      *(uint4*)(o + 128) = make_uint4(bf_add2(hw[4], wr[4]), bf_add2(hw[5], wr[5]), bf_add2(hw[6], wr[6]), bf_add2(hw[7], wr[7])); \
      o[256 - ln * 3] = bf_add2(hw[8], wr[8]); }
    uint4* hs = p.s->HS + ln;
    asm volatile("" : "+l"(hs));
#pragma unroll 1
    for (int base = 0; base < 8; base += 2) {
      uint32_t T[2];
#pragma unroll
      for (int j = 0; j < 2; j++) {
        const uint32_t mx = __reduce_max_sync(0xffffffffu, loc);
        if (loc == mx) loc = 0;
        T[j] = (td >> 2) < c ? (mx & 0xFFFF0000u) - 1u : mx | 0xFFFFu;
      }
      const uint32_t sh = keep(rank == base ? 0x4410u : rank == base + 1 ? 0x4432u : 0x4445u), ca = keep(MISC_CNT + base * 64 + ln * 4);
      TS(29);
      if (base == 0) {
        while ((int)(clock() - tr0) < X_RD) {}
        if ((td >> 2) != c) rv = ldr64(rsrc);
        if (rank >= X_OR) OUT_ROW
        if (warp < (five ? 12 : 15)) {
#pragma unroll
          for (int k = 0; k < X_WS; k++) ldsm4t(wabase + k * 16 * pitch, wa[k][0], wa[k][1], wa[k][2], wa[k][3]);
        }
      }
      uint32_t cnt;
#pragma unroll 1
      for (int it = 0; it < SPIN_MAX; it++) {
        const uint32_t xs = rv.x << 16, ys = rv.y << 16;
        const bool bad = max(max(rv.x, xs), max(rv.y, ys)) >= 0xFFFF0000u;
        uint32_t cn2 = 0;
        cnt = bad ? 256u : 0u;
#pragma unroll
        for (int j = 0; j < 2; j++)
          asm("{ .reg .pred a, b, c, d; setp.gt.u32 a, %2, %6; setp.gt.u32 b, %3, %6; setp.gt.u32 c, %4, %6; setp.gt.u32 d, %5, %6; "
              "@a add.u32 %1, %1, %7; @b add.u32 %1, %1, %7; @c add.u32 %0, %0, %7; @d add.u32 %0, %0, %7; }"
              : "+r"(cnt), "+r"(cn2) : "r"(rv.x), "r"(rv.y), "r"(xs), "r"(ys), "r"(T[j]), "r"(1u << (16 * j)));
        cnt = __reduce_add_sync(0xffffffffu, cnt + cn2);
        asm volatile("{ .reg .pred q; setp.eq.u32 q, %2, 0; @q red.shared.add.u32 [%0], %1; }" :: "r"(ca), "r"(cnt), "r"(cnt & 0x3F00u) : "memory");
        if (!(cnt & 0x3F00u)) break;
        if (bad) rv = ldr64(rsrc);
      }
      TS(16);
      bar_sync(0, 512);
      cnt = lds32(ca);
      if (base == 0) tpub = clock();
      const int gr = rank + __byte_perm(cnt, 0x800u, sh);
      if (gr < 8) {
        uint4* ks = hs + 1152 + gr;
        hs = (uint4*)((char*)hs + gr * 1152);
        asm volatile("{ .reg .b128 t, u; .reg .b64 a, b, c, d; mov.b64 a, {%1,%2}; mov.b64 b, {%3,%4}; mov.b64 c, {%5,%6}; mov.b64 d, {%7,%8}; mov.b128 t, {a, b}; mov.b128 u, {c, d}; "
                     "st.relaxed.gpu.global.b128 [%0], t; st.relaxed.gpu.global.b128 [%0 + 512], u; }"
                     :: "l"(hs), "r"(wr[0]), "r"(wr[1]), "r"(wr[2]), "r"(wr[3]), "r"(wr[4]), "r"(wr[5]), "r"(wr[6]), "r"(wr[7]) : "memory");
        str32((uint32_t*)(hs + 64) - ln * 3, wr[8]);
        str128(hs + 576, hw[0], hw[1], hw[2], hw[3]); str128(hs + 608, hw[4], hw[5], hw[6], hw[7]); str32((uint32_t*)(hs + 640) - ln * 3, hw[8]);
        if (ln == 0) str32(ks, key);
        rank = 16;
      }
      if (__all_sync(0xffffffffu, (int)(cnt >> 16) + base + 2 >= 8)) break;
    }
    TS(8);
    if (warp < (five ? 12 : 15)) {
#pragma unroll
      for (int k = X_WS; k < 12; k++) ldsm4t(wabase + k * 16 * pitch, wa[k][0], wa[k][1], wa[k][2], wa[k][3]);
    }
    if (warp < 6) while ((int)(clock() - tpub) < X_HD) {}
    TS(19);
    if (warp < 6) { ha[0] = ldr128(hsrc); ha[1] = ldr128(hsrc + 24); ha[2] = ldr128(hsrc + 48); }
    if (rank < X_OR) OUT_ROW
  }
  uint32_t wd[10][4];
  const uint32_t xb = keep(OFF_XS + (ln & 7) * 1168 + (fk * 24 + (ln >> 3)) * 16);
  if (warp >= 7) {
    const uint32_t db = down_box(warp - 7, five) + (ln & 7) * 128;
    mbar_wait(MB_D);
#pragma unroll
    for (int j = 0; j < 4; j++) {
      const uint32_t a = db + (ln >> 4) * 1024 + (((2 * j + ((ln >> 3) & 1)) ^ (ln & 7)) << 4);
      ldsm4t(a, wd[j][0], wd[j][1], wd[j][2], wd[j][3]);
      ldsm4t(a + 2048, wd[4 + j][0], wd[4 + j][1], wd[4 + j][2], wd[4 + j][3]);
    }
#pragma unroll
    for (int j = 0; j < 2; j++) ldsm4t(db + 4096 + (((4 * j + (ln >> 3)) ^ (ln & 7)) << 4), wd[8 + j][0], wd[8 + j][1], wd[8 + j][2], wd[8 + j][3]);
  } else if (warp < 6) {
    const uint32_t xs = keep(OFF_XS + (td + (td / 24) * 49) * 16);
#pragma unroll 1
    for (int it = 0; it < SPIN_MAX; it++) {
      const bool bad = max(max(max(ha[0].x, ha[1].x), max(ha[2].x, ha[2].y)), max(ha[2].z, ha[2].w)) == ~0u;
      if (!__any_sync(0xffffffffu, bad)) break;
      if (bad) { ha[0] = ldr128(hsrc); ha[1] = ldr128(hsrc + 24); ha[2] = ldr128(hsrc + 48); }
    }
#pragma unroll
    for (int q = 0; q < 3; q++) sts128(xs + q * 384, ha[q].x, ha[q].y, ha[q].z, ha[q].w);
  }
  TS(9);

  if (!(M_ & 2)) bar_sync(0, 512);
  if (warp >= (five ? 12 : 15)) { if (M_ & 2) bar_sync(0, 512); }
  else {
    if (M_ & 2) bar_sync(0, 512);
    float d0[4] = {0.f, 0.f, 0.f, 0.f}, d1[4] = {0.f, 0.f, 0.f, 0.f};
#pragma unroll
    for (int k = 0; k < 12; k += 2) {
      uint32_t b0, b1, b2, b3;
      ldsm4(xb + k * 32, b0, b1, b2, b3);
      mma_bf16(d0, wa[k][0], wa[k][1], wa[k][2], wa[k][3], b0, b1);
      mma_bf16(d1, wa[k + 1][0], wa[k + 1][1], wa[k + 1][2], wa[k + 1][3], b2, b3);
    }
    sts128(OFF_RED + td * 16, __float_as_uint(d0[0] + d1[0]), __float_as_uint(d0[1] + d1[1]), __float_as_uint(d0[2] + d1[2]), __float_as_uint(d0[3] + d1[3]));
  }
  TS(26);
  if (warp < 5) {
    const uint32_t rb = OFF_RED + warp * 1536 + ln * 16;
    bar_sync(9, 512);
    const uint4 pa = lds128(rb), pb = lds128(rb + 512), pc = lds128(rb + 1024);
    const float ga = bfr(__uint_as_float(pa.x) + __uint_as_float(pb.x) + __uint_as_float(pc.x));
    const float gb = bfr(__uint_as_float(pa.y) + __uint_as_float(pb.y) + __uint_as_float(pc.y));
    const uint32_t uu = pack_bf(__uint_as_float(pa.z) + __uint_as_float(pb.z) + __uint_as_float(pc.z), __uint_as_float(pa.w) + __uint_as_float(pb.w) + __uint_as_float(pc.w));
    float ra, rb2;
    asm("rcp.approx.ftz.f32 %0, %1;" : "=f"(ra) : "f"(1.f + ex2(ga * -1.4426950408889634f)));
    asm("rcp.approx.ftz.f32 %0, %1;" : "=f"(rb2) : "f"(1.f + ex2(gb * -1.4426950408889634f)));
    const uint32_t act = bf_mul2(pack_bf(ga * ra, gb * rb2), uu);
    sts32(OFF_ACT + td * 4, act);
  } else bar_arrive(9, 512);
  uint4* dst = &p.s->X[c * DM * 2 + (warp - 7) * 64 + tt * 8 + gg];
  asm volatile("" : "+l"(dst));
  if (!(M_ & 1)) { bar_sync(8, 512); tpub = clock(); }
  if (warp < 7) { if (M_ & 1) { bar_sync(8, 512); tpub = clock(); } }
  else {
    uint32_t b0, b1, b2, b3, b4;
    if (M_ & 1) bar_sync(8, 512);
    ldsm4t(OFF_ACT + ln * 16, b0, b1, b2, b3);
    asm volatile("ldmatrix.sync.aligned.m8n8.x1.trans.shared.b16 {%0}, [%1];" : "=r"(b4) : "r"(OFF_ACT + 512 + ln * 16) : "memory");
    if (M_ & 1) tpub = clock();
    float y[4][4];
#pragma unroll
    for (int j = 0; j < 4; j++) {
      y[j][0] = y[j][1] = y[j][2] = y[j][3] = 0.f;
      mma_bf16(y[j], wd[j][0], wd[j][1], wd[j][2], wd[j][3], b0, b1);
    }
#pragma unroll
    for (int j = 0; j < 4; j++) mma_bf16(y[j], wd[4 + j][0], wd[4 + j][1], wd[4 + j][2], wd[4 + j][3], b2, b3);
    if (!five) {
#pragma unroll
      for (int j = 0; j < 4; j++) mma_bf16_k8(y[j], wd[8 + (j >> 1)][2 * (j & 1)], wd[8 + (j >> 1)][2 * (j & 1) + 1], b4);
    }
    str128(dst, (pack_bf(y[0][0], y[0][1]) & ~1u) | 0x10000u, pack_bf(y[0][2], y[0][3]), pack_bf(y[1][0], y[1][1]), pack_bf(y[1][2], y[1][3]));
    str128(dst + 32, (pack_bf(y[2][0], y[2][1]) & ~1u) | 0x10000u, pack_bf(y[2][2], y[2][3]), pack_bf(y[3][0], y[3][1]), pack_bf(y[3][2], y[3][3]));
  }
  TS(10);

  if (c < 72) {
    const uint4* src = &p.s->X[(warp * 4 + tt) * (DM * 2) + c * 8 + gg];
    const int slot = (c & 3) * 2 + (ln >> 4), dw = (c >> 2) * 16 + (ln & 15);
    uint32_t hv = 0, kv = 0, res = 0, rs2 = 0;
    uint32_t* o = p.out;
    if (warp == 0) {
      hv = ~0u;
      SPIN_WHILE(max(hv, kv) == ~0u, hv = ldr32((const uint32_t*)p.s->HS + 2304 + slot * 288 + dw); kv = ldr32(&p.s->HS[1152 + slot]));
      const float r = bf_hi(kv ^ (((int)~kv >> 31) | 0x80000000u));
      float rs;
      asm("rcp.approx.ftz.f32 %0, %1;" : "=f"(rs) : "f"(1.f + ex2(r * -1.4426950408889634f)));
      rs2 = keep(pack_bf(rs, rs));
      res = lds32(OFF_XS + slot * 1168 + dw * 4);
      o += (2047 - (int)(kv & 2047u)) * 288 + dw;
      asm volatile("" : "+l"(o));
    }
    const uint32_t sel = (gg & 1) ? 0x3F800000u : 0x00003F80u;
    const uint32_t q0 = keep((gg >> 1) == 0 ? sel : 0u), q1 = keep((gg >> 1) == 1 ? sel : 0u), q2 = keep((gg >> 1) == 2 ? sel : 0u), q3 = keep((gg >> 1) == 3 ? sel : 0u);
#if M_ & 4
    const uint32_t fa = keep(OFF_RED + warp * 8 + ((gg & 1) * 16 + (gg >> 1) * 4 + tt) * 144), fb = keep(OFF_RED + ln * 144);
#else
    const uint32_t fa = keep(OFF_FIN + warp * 256 + (gg & 1) * 128 + (gg >> 1) * 32 + tt * 8), fb = keep(OFF_FIN + ln * 8);
#endif
    uint4 a0 = make_uint4(0, 0, 0, 0), a1 = a0;
    while ((int)(clock() - tpub) < X_PD) {}
    SPIN_WHILE(!(a0.x & a1.x & 0x10000u), if (!(a0.x & 0x10000u)) a0 = ldr128(src); if (!(a1.x & 0x10000u)) a1 = ldr128(src + 64 * DM * 2));
    float d[4] = {0.f, 0.f, 0.f, 0.f}, e[4] = {0.f, 0.f, 0.f, 0.f}, d2[4] = {0.f, 0.f, 0.f, 0.f}, e2[4] = {0.f, 0.f, 0.f, 0.f};
    mma_bf16(d, q0, q2, q1, q3, a0.x, a0.y); mma_bf16(e, q0, q2, q1, q3, a0.z, a0.w);
#if M_ & 8
    mma_bf16(d2, q0, q2, q1, q3, a1.x, a1.y); mma_bf16(e2, q0, q2, q1, q3, a1.z, a1.w);
    sts64(fa, __float_as_uint(d[0] + e[2] + d2[0] + e2[2]), __float_as_uint(d[1] + e[3] + d2[1] + e2[3]));
#else
    mma_bf16(d, q0, q2, q1, q3, a1.x, a1.y); mma_bf16(e, q0, q2, q1, q3, a1.z, a1.w);
    sts64(fa, __float_as_uint(d[0] + e[2]), __float_as_uint(d[1] + e[3]));
#endif
    TS(11);
    if (warp == 0) {
      bar_sync(0, 512);
      float2 s[16];
#if !(M_ & 4)
#pragma unroll
      for (int i = 0; i < 16; i++) { const uint2 q = lds64(fb + i * 256); s[i] = make_float2(__uint_as_float(q.x), __uint_as_float(q.y)); }
#else
#pragma unroll
      for (int i = 0; i < 16; i += 2) { const uint4 q = lds128(fb + i * 8); s[i] = make_float2(__uint_as_float(q.x), __uint_as_float(q.y)); s[i + 1] = make_float2(__uint_as_float(q.z), __uint_as_float(q.w)); }
#endif
#pragma unroll
      for (int k = 1; k < 16; k *= 2)
#pragma unroll
        for (int i = 0; i < 16; i += 2 * k) { s[i].x += s[i + k].x; s[i].y += s[i + k].y; }
      *o = bf_add2(hv, bf_add2(res, bf_mul2(pack_bf(s[0].x, s[0].y), rs2)));
    } else bar_arrive(0, 512);
  }
  TS(12);
  TS_DUMP();
}

typedef CUresult (*EncodeFn)(CUtensorMap*, CUtensorMapDataType, cuuint32_t, void*, const cuuint64_t*, const cuuint64_t*, const cuuint32_t*,
                             const cuuint32_t*, CUtensorMapInterleave, CUtensorMapSwizzle, CUtensorMapL2promotion, CUtensorMapFloatOOBfill);

}

extern "C" void kernel_launch(void* const* d_in, const int* in_sizes, int n_in, void* d_out, int out_size) {
  (void)in_sizes; (void)n_in; (void)out_size;
  static EncodeFn enc = nullptr;
  static Scratch* scratch = nullptr;
  if (!enc) {
    void* fn = nullptr;
    cudaDriverEntryPointQueryResult qr;
    cudaGetDriverEntryPoint("cuTensorMapEncodeTiled", &fn, cudaEnableDefault, &qr);
    enc = (EncodeFn)fn;
    cudaGetSymbolAddress((void**)&scratch, g_S);
    cudaFuncSetAttribute(fused_kernel<false>, cudaFuncAttributeMaxDynamicSharedMemorySize, SMEM_BYTES);
    cudaFuncSetAttribute(fused_kernel<true>, cudaFuncAttributeMaxDynamicSharedMemorySize, SMEM_BYTES);
  }
  TMaps tm;
  for (int i = 0; i < 6; i++) {
    const bool dn = i % 3 == 2;
    const cuuint32_t w = i < 3 ? 40 : 32;
    cuuint64_t gd[3] = {(cuuint64_t)(dn ? 64 : FF), (cuuint64_t)(dn ? FF : DM), 9};
    cuuint64_t gs[2] = {(cuuint64_t)(dn ? DM * 2 : FF * 2), 128};
    cuuint32_t bx[3] = {dn ? 64 : w, dn ? w : 96, i < 3 ? 2u : 3u};
    cuuint32_t es[3] = {1, 1, 1};
    enc(&tm.m[i], CU_TENSOR_MAP_DATA_TYPE_BFLOAT16, dn ? 3 : 2, d_in[11 + i % 3], gd, gs, bx, es, CU_TENSOR_MAP_INTERLEAVE_NONE,
        dn ? CU_TENSOR_MAP_SWIZZLE_128B : i < 3 ? CU_TENSOR_MAP_SWIZZLE_NONE : CU_TENSOR_MAP_SWIZZLE_64B,
        (CUtensorMapL2promotion)X_PROMO, CU_TENSOR_MAP_FLOAT_OOB_FILL_NONE);
  }
  for (int i = 6; i < 10; i++) {
    cuuint64_t gd[3] = {i < 8 ? 32u : 16u, i < 8 ? DM / 2u : DM, NCTA};
    cuuint64_t gs[2] = {i < 8 ? 64u : 32u, DM * 32};
    cuuint32_t bx[3] = {32, 1, (i & 1) ? 128u : 136u};
    cuuint32_t es[3] = {1, 1, 1};
    enc(&tm.m[i], CU_TENSOR_MAP_DATA_TYPE_FLOAT16, 3, scratch->X, gd, gs, bx, es, CU_TENSOR_MAP_INTERLEAVE_NONE, CU_TENSOR_MAP_SWIZZLE_64B,
        CU_TENSOR_MAP_L2_PROMOTION_NONE, CU_TENSOR_MAP_FLOAT_OOB_FILL_NONE);
  }
  Params p;
  p.x = (const unsigned char*)d_in[0];
  bool far = false;
  for (int i = 0; i < 7; i++) {
    p.far[i] = (const unsigned char*)d_in[1 + i];
    const long long d = (long long)((intptr_t)d_in[1 + i] - (intptr_t)d_in[0]);
    p.off[i] = (int)(d / 16);
    if ((long long)p.off[i] * 16 != d || p.off[i] > (1 << 30)) far = true;
  }
  p.dskip = (const uint16_t*)d_in[8];
  p.w_r = (const uint32_t*)d_in[10];
  for (int f = 0; f < 2; f++) {
    static const int kind[17] = {0, 0, 0, 0, 2, 2, 0, 0, 1, 1, 1, 1, 1, 1, 2, 2, 2};
    static const int idx[2][17] = {{2, 3, 4, 5, 6, 8, 0, 1, 0, 1, 2, 3, 4, 5, 0, 2, 4}, {2, 3, 4, 5, 0, -1, 0, 1, 0, 1, 2, 3, 4, 5, 3, -1, 6}};
    static const int blk[2][17] = {{-1, -1, -1, -1, 0, -1, 4, -1, 1, -1, 2, -1, 3, -1, 16, -1, -1}, {-1, -1, -1, -1, 1, -1, 4, -1, -1, -1, 2, -1, 3, -1, 16, -1, -1}};
    const int pitch = f ? 64 : 80;
    for (int u = 0; u < 17; u++) {
      const int s = idx[f][u];
      const uint32_t dst = kind[u] == 0 ? OFF_G + s * 96 * pitch : kind[u] == 2 ? down_box(s, f) : OFF_W + W_BYTES + (s >> 1) * W_BYTES + (s & 1) * 96 * pitch;
      const uint32_t mb = u >= 14 ? (u >= X_HU ? MB_H - OFF_MISC : X_HB) : blk[f][u] >= 0 ? MB_KF - OFF_MISC + blk[f][u] * 8 : 0;
      p.sched[f][u] = s < 0 ? 3u : kind[u] | s << 2 | mb << 6 | dst << 14;
    }
  }
  p.out = (uint32_t*)d_out;
  p.off[7] = 0;
  p.ts = nullptr;
  p.s = scratch;
  if (far) { fused_kernel<true><<<NCTA, NT, SMEM_BYTES, cudaStreamPerThread>>>(p, tm); return; }
  fused_kernel<false><<<NCTA, NT, SMEM_BYTES, cudaStreamPerThread>>>(p, tm);
}
```

```cpp
#include <cuda_runtime.h>
#include <cuda.h>
#include <cuda_bf16.h>
#include <cuda_fp16.h>
#include <stdint.h>
#include <stddef.h>

namespace {

constexpr int NCTA = 128;
constexpr int NT = 640;
constexpr int DM = 576;
constexpr int FF = 4608;
constexpr int SPIN_MAX = 1 << 20;

struct Scratch {
  uint4 X[NCTA * DM * 2];
  uint4 KX[64 * 128];
  uint4 HS[1152 + 8];
  uint4 R[256];
  uint4 SC[256];
  uint32_t FLAG[NCTA * 8];
};
__device__ Scratch g_S;

#define CLKS(i)
#define TS(i)
#define TSX(i)
#define TS_DUMP()

constexpr int SB = 1024;
constexpr int BOX = 15360;
constexpr int OFF_G = SB;
constexpr int OFF_W = OFF_G + 3 * BOX;
constexpr int W_KT = 26624;
constexpr int W_QT = W_KT + 64 + 2048 + 80;
constexpr int W_L3 = W_KT + 4352;
constexpr int W_CW = W_L3 + 4160;
constexpr int W_MISC = W_CW + 640;
constexpr int W_BYTES = 35840;
constexpr int TILE = 10240;
constexpr int OFF_T = OFF_W + 4 * W_BYTES;
constexpr int ALT = TILE - W_KT;
static_assert(W_MISC + 32 <= W_BYTES && OFF_W % 1024 == 0 && W_BYTES % 1024 == 0 && W_BYTES + ALT <= 20480, "wg block");
constexpr int YT_PITCH = 1184;
constexpr int OFF_YT = OFF_T + 2 * TILE;
constexpr int OFF_WR = OFF_YT + 16 * YT_PITCH + 64;
constexpr int OFF_MISC = OFF_WR + 2304;
constexpr int SMEM_BYTES = OFF_MISC + 1024 - SB;
static_assert(OFF_YT % 16 == 0 && OFF_MISC % 16 == 0, "align");
static_assert(SMEM_BYTES <= 232448, "smem");
constexpr int MB_GU = OFF_MISC;
constexpr int MB_D = OFF_MISC + 8;
constexpr int MB_KF = OFF_MISC + 16;
constexpr int MB_GF = OFF_MISC + 48;
constexpr int MB_SC = OFF_MISC + 56;
constexpr int MB_UL = OFF_MISC + 64;
constexpr int MB_REL = OFF_MISC + 104;
constexpr int MB_GO = OFF_MISC + 112;
constexpr int MB_H = MB_KF + 128;
constexpr int MISC_EPOCH = OFF_MISC + 152;
constexpr int MISC_SW = OFF_MISC + 156;
constexpr int MISC_RT = OFF_MISC + 160;
constexpr int MISC_T0 = OFF_MISC + 296;
constexpr int MISC_EM = OFF_MISC + 288;
constexpr int OFF_PART = OFF_W + 20480;
constexpr int OFF_RK = OFF_PART + 3840;
constexpr int MISC_LN1 = OFF_MISC + 192;
constexpr int OFF_XS = OFF_T;
constexpr int OFF_RED = OFF_T + TILE;
constexpr int OFF_FIN = OFF_W + 3 * W_BYTES + W_KT;
constexpr int OFF_ACT = OFF_FIN + 4096;
constexpr int MISC_CNT = OFF_ACT + 1024;

__device__ __forceinline__ uint32_t smem_u32(const void* p) { return (uint32_t)__cvta_generic_to_shared(p); }
__device__ __forceinline__ uint32_t lds32(uint32_t a) { uint32_t v; asm volatile("ld.shared.b32 %0, [%1];" : "=r"(v) : "r"(a) : "memory"); return v; }
__device__ __forceinline__ uint32_t lds16(uint32_t a) { uint16_t v; asm volatile("ld.shared.u16 %0, [%1];" : "=h"(v) : "r"(a) : "memory"); return v; }
__device__ __forceinline__ uint2 lds64(uint32_t a) { uint2 v; asm volatile("ld.shared.v2.b32 {%0,%1}, [%2];" : "=r"(v.x), "=r"(v.y) : "r"(a) : "memory"); return v; }
__device__ __forceinline__ uint4 lds128(uint32_t a) { uint4 v; asm volatile("ld.shared.v4.b32 {%0,%1,%2,%3}, [%4];" : "=r"(v.x), "=r"(v.y), "=r"(v.z), "=r"(v.w) : "r"(a) : "memory"); return v; }
__device__ __forceinline__ void sts16(uint32_t a, uint32_t v) { asm volatile("st.shared.u16 [%0], %1;" :: "r"(a), "h"((uint16_t)v) : "memory"); }
__device__ __forceinline__ void sts32(uint32_t a, uint32_t v) { asm volatile("st.shared.b32 [%0], %1;" :: "r"(a), "r"(v) : "memory"); }
__device__ __forceinline__ void sts64(uint32_t a, uint32_t x, uint32_t y) { asm volatile("st.shared.v2.b32 [%0], {%1,%2};" :: "r"(a), "r"(x), "r"(y) : "memory"); }
__device__ __forceinline__ void sts128(uint32_t a, uint32_t x, uint32_t y, uint32_t z, uint32_t w) { asm volatile("st.shared.v4.b32 [%0], {%1,%2,%3,%4};" :: "r"(a), "r"(x), "r"(y), "r"(z), "r"(w) : "memory"); }
__device__ __forceinline__ void ldsm4(uint32_t a, uint32_t& r0, uint32_t& r1, uint32_t& r2, uint32_t& r3) {
  asm volatile("ldmatrix.sync.aligned.m8n8.x4.shared.b16 {%0,%1,%2,%3}, [%4];" : "=r"(r0), "=r"(r1), "=r"(r2), "=r"(r3) : "r"(a) : "memory");
}
__device__ __forceinline__ void ldsm4t(uint32_t a, uint32_t& r0, uint32_t& r1, uint32_t& r2, uint32_t& r3) {
  asm volatile("ldmatrix.sync.aligned.m8n8.x4.trans.shared.b16 {%0,%1,%2,%3}, [%4];" : "=r"(r0), "=r"(r1), "=r"(r2), "=r"(r3) : "r"(a) : "memory");
}
__device__ __forceinline__ void stsm4t(uint32_t a, uint32_t r0, uint32_t r1, uint32_t r2, uint32_t r3) {
  asm volatile("stmatrix.sync.aligned.m8n8.x4.trans.shared.b16 [%0], {%1,%2,%3,%4};" :: "r"(a), "r"(r0), "r"(r1), "r"(r2), "r"(r3) : "memory");
}
__device__ __forceinline__ uint4 ldr128(const void* p) {
  unsigned long long lo, hi;
  asm volatile("{ .reg .b128 t; ld.relaxed.gpu.global.b128 t, [%2]; mov.b128 {%0, %1}, t; }" : "=l"(lo), "=l"(hi) : "l"(p) : "memory");
  return make_uint4((uint32_t)lo, (uint32_t)(lo >> 32), (uint32_t)hi, (uint32_t)(hi >> 32));
}
__device__ __forceinline__ void str128(void* p, uint32_t x, uint32_t y, uint32_t z, uint32_t w) {
  asm volatile("{ .reg .b128 t; .reg .b64 lo, hi; mov.b64 lo, {%1,%2}; mov.b64 hi, {%3,%4}; mov.b128 t, {lo, hi}; st.relaxed.gpu.global.b128 [%0], t; }"
               :: "l"(p), "r"(x), "r"(y), "r"(z), "r"(w) : "memory");
}
__device__ __forceinline__ uint32_t ldr32(const void* p) { uint32_t v; asm volatile("ld.relaxed.gpu.global.b32 %0, [%1];" : "=r"(v) : "l"(p) : "memory"); return v; }
__device__ __forceinline__ void str32(void* p, uint32_t v) { asm volatile("st.relaxed.gpu.global.b32 [%0], %1;" :: "l"(p), "r"(v) : "memory"); }
__device__ __forceinline__ void str16(void* p, uint32_t v) { asm volatile("st.relaxed.gpu.global.u16 [%0], %1;" :: "l"(p), "h"((uint16_t)v) : "memory"); }
__device__ __forceinline__ void bar_sync(int id, int n) { asm volatile("bar.sync %0, %1;" :: "r"(id), "r"(n) : "memory"); }
__device__ __forceinline__ void bar_arrive(int id, int n) { asm volatile("bar.arrive %0, %1;" :: "r"(id), "r"(n) : "memory"); }

__device__ __forceinline__ float bf_lo(uint32_t w) { return __uint_as_float(w << 16); }
__device__ __forceinline__ float bf_hi(uint32_t w) { return __uint_as_float(w & 0xFFFF0000u); }
__device__ __forceinline__ uint32_t pack_bf(float lo, float hi) { uint32_t r; asm("cvt.rn.bf16x2.f32 %0, %1, %2;" : "=r"(r) : "f"(hi), "f"(lo)); return r; }
__device__ __forceinline__ uint32_t pack_h(float lo, float hi) { uint32_t r; asm("cvt.rn.f16x2.f32 %0, %1, %2;" : "=r"(r) : "f"(hi), "f"(lo)); return r; }
__device__ __forceinline__ float bfr(float x) { return bf_lo(pack_bf(x, 0.f)); }
__device__ __forceinline__ uint32_t bf_sub2(uint32_t a, uint32_t b) { __nv_bfloat162 r = __hsub2(*(__nv_bfloat162*)&a, *(__nv_bfloat162*)&b); return *(uint32_t*)&r; }
__device__ __forceinline__ uint32_t bf_add2(uint32_t a, uint32_t b) { __nv_bfloat162 r = __hadd2(*(__nv_bfloat162*)&a, *(__nv_bfloat162*)&b); return *(uint32_t*)&r; }
__device__ __forceinline__ uint32_t bf_mul2(uint32_t a, uint32_t b) { __nv_bfloat162 r = __hmul2(*(__nv_bfloat162*)&a, *(__nv_bfloat162*)&b); return *(uint32_t*)&r; }
__device__ __forceinline__ float2 h2f(uint32_t w) { return __half22float2(*(__half2*)&w); }
__device__ __forceinline__ float ex2(float x) { float r; asm("ex2.approx.ftz.f32 %0, %1;" : "=f"(r) : "f"(x)); return r; }
__device__ __forceinline__ float warp_sum(float v) {
#pragma unroll
  for (int o = 16; o > 0; o >>= 1) v += __shfl_xor_sync(0xffffffffu, v, o);
  return v;
}
__device__ __forceinline__ void mma_bf16(float* d, uint32_t a0, uint32_t a1, uint32_t a2, uint32_t a3, uint32_t b0, uint32_t b1) {
  asm volatile("mma.sync.aligned.m16n8k16.row.col.f32.bf16.bf16.f32 {%0,%1,%2,%3}, {%4,%5,%6,%7}, {%8,%9}, {%0,%1,%2,%3};"
               : "+f"(d[0]), "+f"(d[1]), "+f"(d[2]), "+f"(d[3]) : "r"(a0), "r"(a1), "r"(a2), "r"(a3), "r"(b0), "r"(b1));
}
__device__ __forceinline__ void mma_bf16_k8(float* d, uint32_t a0, uint32_t a1, uint32_t b0) {
  asm volatile("mma.sync.aligned.m16n8k8.row.col.f32.bf16.bf16.f32 {%0,%1,%2,%3}, {%4,%5}, {%6}, {%0,%1,%2,%3};"
               : "+f"(d[0]), "+f"(d[1]), "+f"(d[2]), "+f"(d[3]) : "r"(a0), "r"(a1), "r"(b0));
}

__device__ __forceinline__ void wg_fence() { asm volatile("wgmma.fence.sync.aligned;" ::: "memory"); }
__device__ __forceinline__ void wg_commit() { asm volatile("wgmma.commit_group.sync.aligned;" ::: "memory"); }
template <int N> __device__ __forceinline__ void wg_wait() { asm volatile("wgmma.wait_group.sync.aligned %0;" :: "n"(N) : "memory"); }
template <int TB> __device__ __forceinline__ void wgmma32(float* d, const uint32_t* a, uint32_t dlo, uint32_t dhi) {
  asm volatile("{ .reg .b64 dd; mov.b64 dd, {%20, %21}; wgmma.mma_async.sync.aligned.m64n32k16.f32.f16.f16 "
               "{%0,%1,%2,%3,%4,%5,%6,%7,%8,%9,%10,%11,%12,%13,%14,%15}, {%16,%17,%18,%19}, dd, 1, 1, 1, %22; }"
               : "+f"(d[0]), "+f"(d[1]), "+f"(d[2]), "+f"(d[3]), "+f"(d[4]), "+f"(d[5]), "+f"(d[6]), "+f"(d[7]), "+f"(d[8]), "+f"(d[9]), "+f"(d[10]), "+f"(d[11]), "+f"(d[12]), "+f"(d[13]), "+f"(d[14]), "+f"(d[15])
               : "r"(a[0]), "r"(a[1]), "r"(a[2]), "r"(a[3]), "r"(dlo), "r"(dhi), "n"(TB));
}
template <int TB> __device__ __forceinline__ void wgmma64(float* d, const uint32_t* a, uint32_t dlo, uint32_t dhi) {
  asm volatile("{ .reg .b64 dd; mov.b64 dd, {%36, %37}; wgmma.mma_async.sync.aligned.m64n64k16.f32.f16.f16 "
               "{%0,%1,%2,%3,%4,%5,%6,%7,%8,%9,%10,%11,%12,%13,%14,%15,%16,%17,%18,%19,%20,%21,%22,%23,%24,%25,%26,%27,%28,%29,%30,%31}, {%32,%33,%34,%35}, dd, 1, 1, 1, %38; }"
               : "+f"(d[0]), "+f"(d[1]), "+f"(d[2]), "+f"(d[3]), "+f"(d[4]), "+f"(d[5]), "+f"(d[6]), "+f"(d[7]), "+f"(d[8]), "+f"(d[9]), "+f"(d[10]), "+f"(d[11]), "+f"(d[12]), "+f"(d[13]), "+f"(d[14]), "+f"(d[15]), "+f"(d[16]), "+f"(d[17]), "+f"(d[18]), "+f"(d[19]), "+f"(d[20]), "+f"(d[21]), "+f"(d[22]), "+f"(d[23]), "+f"(d[24]), "+f"(d[25]), "+f"(d[26]), "+f"(d[27]), "+f"(d[28]), "+f"(d[29]), "+f"(d[30]), "+f"(d[31])
               : "r"(a[0]), "r"(a[1]), "r"(a[2]), "r"(a[3]), "r"(dlo), "r"(dhi), "n"(TB));
}
template <int TB> __device__ __forceinline__ void wgmma64_init(float* d, const uint32_t* a, uint32_t dlo, uint32_t dhi) {
  asm volatile("{ .reg .b64 dd; mov.b64 dd, {%36, %37}; wgmma.mma_async.sync.aligned.m64n64k16.f32.f16.f16 "
               "{%0,%1,%2,%3,%4,%5,%6,%7,%8,%9,%10,%11,%12,%13,%14,%15,%16,%17,%18,%19,%20,%21,%22,%23,%24,%25,%26,%27,%28,%29,%30,%31}, {%32,%33,%34,%35}, dd, 0, 1, 1, %38; }"
               : "=f"(d[0]), "=f"(d[1]), "=f"(d[2]), "=f"(d[3]), "=f"(d[4]), "=f"(d[5]), "=f"(d[6]), "=f"(d[7]), "=f"(d[8]), "=f"(d[9]), "=f"(d[10]), "=f"(d[11]), "=f"(d[12]), "=f"(d[13]), "=f"(d[14]), "=f"(d[15]), "=f"(d[16]), "=f"(d[17]), "=f"(d[18]), "=f"(d[19]), "=f"(d[20]), "=f"(d[21]), "=f"(d[22]), "=f"(d[23]), "=f"(d[24]), "=f"(d[25]), "=f"(d[26]), "=f"(d[27]), "=f"(d[28]), "=f"(d[29]), "=f"(d[30]), "=f"(d[31])
               : "r"(a[0]), "r"(a[1]), "r"(a[2]), "r"(a[3]), "r"(dlo), "r"(dhi), "n"(TB));
}
template <int TB> __device__ __forceinline__ void wgmma32_init(float* d, const uint32_t* a, uint32_t dlo, uint32_t dhi) {
  asm volatile("{ .reg .b64 dd; mov.b64 dd, {%20, %21}; wgmma.mma_async.sync.aligned.m64n32k16.f32.f16.f16 "
               "{%0,%1,%2,%3,%4,%5,%6,%7,%8,%9,%10,%11,%12,%13,%14,%15}, {%16,%17,%18,%19}, dd, 0, 1, 1, %22; }"
               : "=f"(d[0]), "=f"(d[1]), "=f"(d[2]), "=f"(d[3]), "=f"(d[4]), "=f"(d[5]), "=f"(d[6]), "=f"(d[7]), "=f"(d[8]), "=f"(d[9]), "=f"(d[10]), "=f"(d[11]), "=f"(d[12]), "=f"(d[13]), "=f"(d[14]), "=f"(d[15])
               : "r"(a[0]), "r"(a[1]), "r"(a[2]), "r"(a[3]), "r"(dlo), "r"(dhi), "n"(TB));
}
__device__ __forceinline__ void wgmma64h(uint32_t* d, uint32_t a0, uint32_t a1, uint32_t a2, uint32_t a3, uint32_t dlo, uint32_t dhi) {
  asm volatile("{ .reg .b64 dd; mov.b64 dd, {%20, %21}; wgmma.mma_async.sync.aligned.m64n64k16.f16.f16.f16 "
               "{%0,%1,%2,%3,%4,%5,%6,%7,%8,%9,%10,%11,%12,%13,%14,%15}, {%16,%17,%18,%19}, dd, 1, 1, 1, 0; }"
               : "+r"(d[0]), "+r"(d[1]), "+r"(d[2]), "+r"(d[3]), "+r"(d[4]), "+r"(d[5]), "+r"(d[6]), "+r"(d[7]), "+r"(d[8]), "+r"(d[9]), "+r"(d[10]), "+r"(d[11]), "+r"(d[12]), "+r"(d[13]), "+r"(d[14]), "+r"(d[15])
               : "r"(a0), "r"(a1), "r"(a2), "r"(a3), "r"(dlo), "r"(dhi));
}
__device__ __forceinline__ void wgmma64h_init(uint32_t* d, uint32_t a0, uint32_t a1, uint32_t a2, uint32_t a3, uint32_t dlo, uint32_t dhi) {
  asm volatile("{ .reg .b64 dd; mov.b64 dd, {%20, %21}; wgmma.mma_async.sync.aligned.m64n64k16.f16.f16.f16 "
               "{%0,%1,%2,%3,%4,%5,%6,%7,%8,%9,%10,%11,%12,%13,%14,%15}, {%16,%17,%18,%19}, dd, 0, 1, 1, 0; }"
               : "=r"(d[0]), "=r"(d[1]), "=r"(d[2]), "=r"(d[3]), "=r"(d[4]), "=r"(d[5]), "=r"(d[6]), "=r"(d[7]), "=r"(d[8]), "=r"(d[9]), "=r"(d[10]), "=r"(d[11]), "=r"(d[12]), "=r"(d[13]), "=r"(d[14]), "=r"(d[15])
               : "r"(a0), "r"(a1), "r"(a2), "r"(a3), "r"(dlo), "r"(dhi));
}
__device__ __forceinline__ void wgmma40_ss(float* d, uint32_t alo, uint32_t blo, uint32_t hi) {
  asm volatile("{ .reg .b64 da, db; mov.b64 da, {%20, %22}; mov.b64 db, {%21, %22}; "
               "wgmma.mma_async.sync.aligned.m64n40k16.f32.f16.f16 {%0,%1,%2,%3,%4,%5,%6,%7,%8,%9,%10,%11,%12,%13,%14,%15,%16,%17,%18,%19}, da, db, 1, 1, 1, 1, 1; }"
               : "+f"(d[0]), "+f"(d[1]), "+f"(d[2]), "+f"(d[3]), "+f"(d[4]), "+f"(d[5]), "+f"(d[6]), "+f"(d[7]), "+f"(d[8]), "+f"(d[9]), "+f"(d[10]), "+f"(d[11]), "+f"(d[12]), "+f"(d[13]), "+f"(d[14]), "+f"(d[15]), "+f"(d[16]), "+f"(d[17]), "+f"(d[18]), "+f"(d[19])
               : "r"(alo), "r"(blo), "r"(hi));
}
__device__ __forceinline__ void wgmma40_ss_init(float* d, uint32_t alo, uint32_t blo, uint32_t hi) {
  asm volatile("{ .reg .b64 da, db; mov.b64 da, {%20, %22}; mov.b64 db, {%21, %22}; "
               "wgmma.mma_async.sync.aligned.m64n40k16.f32.f16.f16 {%0,%1,%2,%3,%4,%5,%6,%7,%8,%9,%10,%11,%12,%13,%14,%15,%16,%17,%18,%19}, da, db, 0, 1, 1, 1, 1; }"
               : "=f"(d[0]), "=f"(d[1]), "=f"(d[2]), "=f"(d[3]), "=f"(d[4]), "=f"(d[5]), "=f"(d[6]), "=f"(d[7]), "=f"(d[8]), "=f"(d[9]), "=f"(d[10]), "=f"(d[11]), "=f"(d[12]), "=f"(d[13]), "=f"(d[14]), "=f"(d[15]), "=f"(d[16]), "=f"(d[17]), "=f"(d[18]), "=f"(d[19])
               : "r"(alo), "r"(blo), "r"(hi));
}
__device__ __forceinline__ void tma_box(uint32_t dst, const CUtensorMap* tm, uint32_t mb, int x, int y) {
  asm volatile("cp.async.bulk.tensor.2d.shared::cluster.global.mbarrier::complete_tx::bytes [%0], [%1, {%3, %4}], [%2];"
               :: "r"(dst), "l"(tm), "r"(mb), "r"(x), "r"(y) : "memory");
}
__device__ __forceinline__ uint32_t uni(uint32_t v) {
  uint32_t r; asm volatile("shfl.sync.idx.b32 %0, %1, 0, 0x1f, 0xffffffff;" : "=r"(r) : "r"(v)); return r;
}
__device__ __forceinline__ uint32_t pin(uint32_t v) {
  uint32_t r; asm volatile("shfl.sync.bfly.b32 %0, %1, 0, 0x1f, 0xffffffff;" : "=r"(r) : "r"(v)); return r;
}

struct Params {
  const unsigned char* x;
  Scratch* s;
  int off[8];
  uint32_t* out;
  const uint16_t* dskip;
  const uint32_t* w_r;
  long long* ts;
  const unsigned char* far[7];
  uint32_t sched[2][17];
};
__device__ __forceinline__ uint32_t ldnc32(const void* p) { uint32_t v; asm volatile("ld.global.nc.b32 %0, [%1];" : "=r"(v) : "l"(p)); return v; }
__device__ __forceinline__ uint32_t ldnc16(const void* p) { uint16_t v; asm volatile("ld.global.nc.u16 %0, [%1];" : "=h"(v) : "l"(p)); return v; }
__device__ __forceinline__ void mbar_wait(uint32_t mb, uint32_t ph = 0) {
#pragma unroll 1
  for (int it = 0; it < SPIN_MAX; it++) {
    uint32_t ok;
    asm volatile("{ .reg .pred q; mbarrier.try_wait.parity.shared::cta.b64 q, [%1], %2; selp.u32 %0, 1, 0, q; }" : "=r"(ok) : "r"(mb), "r"(ph) : "memory");
    if (ok) break;
  }
}
__device__ __forceinline__ void mbar_arrive(uint32_t mb) { asm volatile("mbarrier.arrive.shared::cta.b64 _, [%0];" :: "r"(mb) : "memory"); }
__device__ __forceinline__ void fence_async() { asm volatile("fence.proxy.async.shared::cta;" ::: "memory"); }
#define SPIN_WHILE(cond, body) _Pragma("unroll 1") for (int _it = 0; _it < SPIN_MAX && __any_sync(0xffffffffu, (cond)); _it++) { body; }

struct LnC { uint32_t m2, rh2, rl2; };
__device__ __forceinline__ LnC ln_consts(float s, float q, float& r) {
  const float mean = s * (1.f / DM);
  const float var = fmaxf(fmaf(-mean, mean, q * (1.f / DM)), 0.f);
  float sd;
  asm("sqrt.approx.ftz.f32 %0, %1;" : "=f"(sd) : "f"(bfr(bfr(var) + 1e-5f)));
  asm("rcp.approx.ftz.f32 %0, %1;" : "=f"(r) : "f"(bfr(sd)));
  LnC c;
  c.m2 = pack_bf(mean, mean);
  c.rh2 = pack_bf(r, r);
  const float rl = r - bf_lo(c.rh2);
  c.rl2 = pack_bf(rl, rl);
  return c;
}
__device__ __forceinline__ uint32_t bf_fma2(uint32_t a, uint32_t b, uint32_t c) {
  __nv_bfloat162 r = __hfma2(*(const __nv_bfloat162*)&a, *(const __nv_bfloat162*)&b, *(const __nv_bfloat162*)&c);
  return *(uint32_t*)&r;
}
__device__ __forceinline__ uint32_t ln_apply(uint32_t w, uint32_t m2, uint32_t rh2, uint32_t rl2) {
  const uint32_t d = bf_sub2(w, m2);
  return bf_fma2(d, rh2, bf_mul2(d, rl2));
}

__device__ __forceinline__ float2 cis(float mag_log2, float rev) {
  const float m = ex2(mag_log2), ang = rev * 6.283185307179586f;
  return make_float2(m * __cosf(ang), m * __sinf(ang));
}
__device__ __forceinline__ float2 csq(float2 a) { return make_float2(fmaf(a.x, a.x, -a.y * a.y), (a.x + a.x) * a.y); }
__device__ __forceinline__ float2 cmul(float2 a, float2 b) { return make_float2(fmaf(a.x, b.x, -a.y * b.y), fmaf(a.x, b.y, a.y * b.x)); }
__device__ __forceinline__ void pmul(uint32_t xr, uint32_t xi, uint32_t w, uint32_t& yr, uint32_t& yi) {
  const __half2 XR = *(__half2*)&xr, XI = *(__half2*)&xi, W = *(__half2*)&w;
  const __half2 a = __hfma2(__hneg2(XI), __high2half2(W), __hmul2(XR, __low2half2(W)));
  const __half2 b = __hfma2(XI, __low2half2(W), __hmul2(XR, __high2half2(W)));
  yr = *(const uint32_t*)&a; yi = *(const uint32_t*)&b;
}
__device__ __forceinline__ uint32_t pk(float2 a) { return pack_h(a.x, a.y); }

struct KgState { float2 c0, z8; float kl; uint32_t w64, w128, w192; };
__device__ __forceinline__ void kgen_tables_n(const uint32_t (&raw)[7], uint32_t scr, int wt, KgState& k) {
  const uint32_t dst = scr + 16384 + wt * 16;
  const float dt = bfr(ex2(bf_lo(raw[6]) * 1.4426950408889634f));
  const float th = dt * bf_lo(raw[1]);
  const float br = dt * bf_lo(raw[2]), bi = dt * bf_lo(raw[3]);
  const float Cr = bf_lo(raw[4]), Ci = bf_lo(raw[5]);
  k.c0 = make_float2(fmaf(Cr, br, -Ci * bi), fmaf(Cr, bi, Ci * br));
  const uint32_t mx = __reduce_max_sync(0xffffffffu, __float_as_uint(fmaxf(fabsf(k.c0.x), fabsf(k.c0.y))));
  const float a2 = dt * bf_lo(raw[0]) * 1.4426950408889634f;
  const float rh = th * 0.15915494309189535f;
  const float rl = fmaf(th, (float)(0.15915494309189535 - (double)0.15915494309189535f), fmaf(th, 0.15915494309189535f, -rh));
  const float rf = rh - rintf(rh);
  const float2 z1 = cis(a2, rf + rl);
  const float p64 = rf * 64.f;
  const float2 z64 = cis(a2 * 64.f, fmaf(64.f, rl, p64 - rintf(p64)));
  const float2 z2 = csq(z1), z128 = csq(z64), z3 = cmul(z2, z1), z4 = csq(z2), z256 = csq(z128), z6 = csq(z3), z512 = csq(z256);
  k.z8 = csq(z4);
  k.w64 = pk(z64); k.w128 = pk(z128); k.w192 = pk(cmul(z128, z64));
  sts128(dst, 0x00003C00u, pk(z2), pk(z4), pk(z6));
  const float2 z1024 = csq(z512), z768 = cmul(z512, z256);
  sts128(dst + 2048, pk(z1), pk(z3), pk(cmul(z4, z1)), pk(cmul(z4, z3)));
  const float2 z2048 = csq(z1024);
  k.kl = fmaf(k.c0.x, z2048.x, -k.c0.y * z2048.y);
  sts128(dst + 4096, pk(z256), pk(cmul(z256, z2)), pk(cmul(z256, z4)), pk(cmul(z256, z6)));
  sts128(dst + 6144, pk(z512), pk(cmul(z512, z4)), pk(z768), pk(cmul(z768, z4)));
  sts128(dst + 8192, pk(z1024), pk(cmul(z1024, z256)), pk(cmul(z1024, z512)), pk(cmul(z1024, z768)));
  sts32(scr + W_MISC + (wt >> 5) * 4, mx);
}
__device__ __forceinline__ int kgen_tables_m(uint32_t scr, int wt, const KgState& k) {
  const uint32_t dst = scr + wt * 16;
  const uint4 e4 = lds128(scr + W_MISC);
  const float2 z16 = csq(k.z8), z32 = csq(z16);
  const int em = max(min((int)(max(max(e4.x, e4.y), max(e4.z, e4.w)) >> 23), 238), 16);
  const float sc = __uint_as_float((uint32_t)(127 + 4 + 127 - em) << 23);
  sts32(scr + W_MISC + 16 + (wt >> 5) * 4, __reduce_add_sync(0xffffffffu, __float2int_rn(k.kl * sc * 262144.f)));
  const float2 c0 = make_float2(k.c0.x * sc, k.c0.y * sc);
  const float2 c1 = cmul(c0, k.z8), c2 = cmul(c0, z16), c4 = cmul(c0, z32), c3 = cmul(c1, z16), c5 = cmul(c1, z32), c6 = cmul(c2, z32), c7 = cmul(c3, z32);
  uint32_t pr[4], pi[4], yr[4], yi[4];
  pr[0] = pack_h(c0.x, c1.x); pi[0] = pack_h(c0.y, c1.y);
  pr[1] = pack_h(c2.x, c3.x); pi[1] = pack_h(c2.y, c3.y);
  pr[2] = pack_h(c4.x, c5.x); pi[2] = pack_h(c4.y, c5.y);
  pr[3] = pack_h(c6.x, c7.x); pi[3] = pack_h(c6.y, c7.y);
  sts128(dst, pr[0], pr[1], pr[2], pr[3]); sts128(dst + 2048, pi[0], pi[1], pi[2], pi[3]);
#pragma unroll
  for (int q = 1; q < 4; q++) {
    const uint32_t w = q == 1 ? k.w64 : q == 2 ? k.w128 : k.w192;
#pragma unroll
    for (int i = 0; i < 4; i++) pmul(pr[i], pi[i], w, yr[i], yi[i]);
    sts128(dst + q * 4096, yr[0], yr[1], yr[2], yr[3]); sts128(dst + q * 4096 + 2048, yi[0], yi[1], yi[2], yi[3]);
  }
  return em;
}
__device__ __forceinline__ uint32_t lds32_if(uint32_t a, bool on) {
  uint32_t v; asm volatile("{ .reg .pred q; setp.ne.u32 q, %2, 0; mov.b32 %0, 0; @q ld.shared.b32 %0, [%1]; }" : "=r"(v) : "r"(a), "r"((uint32_t)on) : "memory"); return v;
}
__device__ __forceinline__ uint32_t prmt(uint32_t a, uint32_t b, uint32_t s) { uint32_t r; asm("prmt.b32 %0, %1, %2, %3;" : "=r"(r) : "r"(a), "r"(b), "r"(s)); return r; }
__device__ __forceinline__ void kgen_build(uint32_t tb, int wg, int wt, uint32_t k0, uint32_t k1, uint32_t k2) {
  const uint32_t kt = tb + W_KT, sc = tb + W_L3 + 3072;
  const int ix = ((wt >> 2) + (wt & 3) * 32 - 1) & 127;
  const uint32_t a3 = tb + W_CW + 32 + ((ix & 1) ? 0 : 304) + (ix >> 1) * 4, a2 = sc + 544 + (wt & ~3) * 2 + (wt & 1) * 4 + (wt & 2) * 128;
  const uint32_t v3 = wt ? k2 : k2 >> 16;
  sts32(sc + 4 + wt * 4, __byte_perm(k0, k1, 0x5432));
  sts16(a2, k1 >> 16); sts16(a2 + 6, k1 >> 16);
  sts16(a3, v3); sts16(a3 + 6, v3);
  if ((unsigned)(wt - 32) < 14u) sts128(kt + (wt < 36 ? -512 : 64 + 4128 - 576) + wt * 16, 0, 0, 0, 0);
  if (wt == 127) sts32(sc, k0 & 0xFFFF0000u);
  if (wt == 0) { sts32(sc + 516, k1); sts16(sc + 1056, k2); }
  bar_sync(1 + wg, 128);
  const uint32_t cw = tb + W_CW + 32 + (wt >> 6) * 48 + wt * 4, g2 = sc + 540 + wt * 4;
  const bool odd = wt & 1, ends = (unsigned)(wt - 4) >= 120u;
  const uint32_t pv = lds32(sc + wt * 4), nx = lds32(sc + 8 + wt * 4), nc = lds32_if(g2 + 8, ends);
  const uint32_t l0 = lds32(cw), l1 = lds32(cw - 8), l2 = lds32(cw - 16), l3 = lds32(cw - 24), q0 = lds32(g2), q1 = lds32(g2 + 128), q2 = lds32(g2 - 8), q3 = lds32(g2 + 120);
  sts64(kt + 64 + wt * 8, __byte_perm(k0, pv, 0x5410), __byte_perm(k0, 0, 0x1032));
  sts64(kt + 64 + 1024 + wt * 8, __byte_perm(k1, pv, (odd || wt == 0) ? 0x7610 : 0x1010), __byte_perm(k1, nx, odd ? 0x1076 : 0x1010));
  const uint32_t cc = __byte_perm(nc, 0, 0x3232), nn = __byte_perm(nc, 0, 0x1010);
  if (ends) sts128(kt + 64 + 2048 + wt * 16, cc, cc, odd ? nc : cc, odd ? nn : nc);
  if (wt == 127) { sts128(kt + 64 + 4096, nn, nn, nn, nn); sts128(kt + 64 + 4112, nn, nn << 16, 0, 0); }
  sts128(tb + W_L3 + 512 + (wt >> 6) * 512 + wt * 16, l0, l1, l2, l3);
  if ((wt & 63) < 34) sts128(tb + W_QT - 16 + wt * 16, q0, q1, q2, q3);
}

__device__ __forceinline__ void load_a(uint32_t (&a)[4], uint32_t kp, int j) {
  a[0] = lds32(kp + 64 * j); a[1] = lds32(kp + 64 * j + 512); a[2] = lds32(kp + 64 * j - 32); a[3] = lds32(kp + 64 * j + 480);
}
__device__ __forceinline__ uint32_t band(int d, int lo, int hi) {
  return ((unsigned)(d - lo) <= (unsigned)(hi - lo) ? 1u : 0u) | ((unsigned)(d - 1 - lo) <= (unsigned)(hi - lo) ? 0x10000u : 0u);
}
__device__ __forceinline__ uint32_t hadd2u(uint32_t a, uint32_t b) { __half2 r = __hadd2(*(__half2*)&a, *(__half2*)&b); return *(uint32_t*)&r; }

__device__ __forceinline__ void zero_pads(uint32_t tb, int wt) {
  if (!(wt & 32)) sts128(tb + W_L3 + (wt >> 6) * 512 + wt * 16, 0, 0, 0, 0);
  if ((wt & 63) < 3) sts128(tb + W_CW + (wt >> 6) * 304 + (wt & 63) * 16, 0, 0, 0, 0);
}
__device__ __forceinline__ uint32_t tr_base(int lane) {
  return OFF_YT + (2 * (lane >> 3) + (lane & 1)) * YT_PITCH + ((lane >> 1) & 1) * (8 * YT_PITCH + 64) + ((lane >> 2) & 1) * 16;
}

__device__ __forceinline__ uint32_t sc_addr(int tp) { return OFF_YT + (tp < 16 ? tp * YT_PITCH + (tp >> 3) * 64 + 1152 : 8 * YT_PITCH - 512 + tp * 32); }
#define X_PW 15
#define X_HU 16
#define X_NE 2
#define X_SCT 10000
#define X_DELTA 0
#define X_DSTEP 2000
#define X_PF0 2500
#define X_PFD 600
#define X_TD 450
#define X_WS 6
#define X_OR 8
#define X_ABS 4950
#define X_XD 200
#define X_RD 600
#define X_HD 400
#define X_PD 1080
#define X_PROMO 2
#define X_YD2 1000
#define X_GO 1
#define X_GW 2
#define X_NS 4400
#define X_XS 13400
#define X_LAG 1500
#define X_YD 1550
struct TMaps { CUtensorMap m[10]; };
__device__ __forceinline__ uint32_t h2bf(uint32_t w) { const float2 f = h2f(w); return pack_bf(f.x, f.y); }
__device__ __forceinline__ uint32_t keep(uint32_t v) { asm volatile("" : "+r"(v)); return v; }
__device__ __forceinline__ uint2 ldr64(const void* p) { uint2 v; asm volatile("{ .reg .b64 t; ld.relaxed.gpu.global.b64 t, [%2]; mov.b64 {%0, %1}, t; }" : "=r"(v.x), "=r"(v.y) : "l"(p) : "memory"); return v; }
__host__ __device__ __forceinline__ uint32_t down_box(int s, bool five) {
  return five ? OFF_W + W_BYTES + 12288 + (s / 3) * (W_BYTES - 12288) + s * 4096 : s < 6 ? OFF_W + W_BYTES + BOX + (s >> 1) * (W_BYTES - 10240) + s * 5120 : OFF_W + (s - 6) * 5120;
}
__device__ __forceinline__ void load_tile(const CUtensorMap* tmx, int i, int c, int again = 0) {
  asm volatile("mbarrier.arrive.expect_tx.shared::cta.b64 _, [%0], 8704;" :: "r"(MB_UL + i * 16 + again) : "memory");
  asm volatile("cp.async.bulk.tensor.3d.shared::cluster.global.mbarrier::complete_tx::bytes [%0], [%1, {%3, %4, %5}], [%2];"
               :: "r"(i < 2 ? OFF_T + i * TILE : OFF_W), "l"(tmx), "r"(MB_UL + i * 16 + again), "r"(0), "r"(c), "r"(-8) : "memory");
}
template <bool FAR> __device__ __forceinline__ void load_params(const Params& p, uint32_t ch, int wt, uint32_t dst, bool on) {
  const int rel = wt < 96 ? ch * 16 + (wt & 15) : ch >> 3;
  const unsigned char* b = FAR ? p.far[min(wt >> 4, 6)] + rel * 16 : p.x + (long long)(p.off[wt >> 4] + rel) * 16;
  asm volatile("{ .reg .pred q; setp.ne.u32 q, %2, 0; @q cp.async.cg.shared.global [%0], [%1], 16; }"
               :: "r"(dst + wt * 16), "l"(b), "r"((uint32_t)(on && wt < 97)) : "memory");
}

struct ConvC { uint32_t ca, cb, bands, qa; };
__device__ __forceinline__ ConvC conv_consts(int w, int lane) {
  const int h = w & 1, P = (w >> 1) & 1, d0 = 8 * h + (lane >> 2) - 2 * (lane & 3);
  ConvC k;
  k.ca = keep((W_KT + (16 + 256 * P + d0) * 4) | (((8 + 64 * P + lane) * 64 + (((h + ((w >> 1) & 2)) ^ (lane >> 1)) & 3) * 16) << 16));
  const int u = d0 + 2 * (lane & 1) + 2, in = (u & 7) - ((u & 7) >= 5 ? 5 : 0) - 2 * (lane & 1);
  k.cb = keep(in > 0 ? 0x1010 : in == 0 ? 0x3210 : 0x3232);
  k.qa = keep(W_QT + (2 * (u >> 3) + ((u & 7) >= 5) + 64 * P) * 16);
  k.bands = keep(band(d0, 12, 20) + 2 * band(d0 + 8, 12, 20) + 4 * band(d0 + 16, 12, 20) + 8 * band(d0 + 24, 12, 20)
                 + 16 * band(d0 - 8, 5, 11) + 32 * band(d0, 5, 11) + 64 * band(d0 + 8, 5, 11) + 128 * band(d0 + 16, 5, 11));
  return k;
}
struct ConvPre { uint32_t e0, e2, f2, b0, b2, a[3][4]; };
__device__ __forceinline__ void conv_pre(ConvPre& r, uint32_t kp, uint32_t qp, int part, bool on, bool P) {
  if (part & 1) {
    r.e0 = lds32_if(kp + 4096, on && !P); r.e2 = lds32_if(kp + 4064, on && !P); r.f2 = lds32_if(kp + 4128, on && !P);
    r.b0 = lds32_if(kp + 2048, on && !P); r.b2 = lds32_if(kp + 2016, on && !P);
  }
#pragma unroll
  for (int j = 0; j < 3; j++) if (part & (j < 1 ? 1 : 2))
    asm volatile("{ .reg .pred q; setp.ne.u32 q, %5, 0; mov.b32 %0, 0; mov.b32 %1, 0; mov.b32 %2, 0; mov.b32 %3, 0; @q ld.shared.v4.b32 {%0,%1,%2,%3}, [%4]; }"
                 : "=r"(r.a[j][0]), "=r"(r.a[j][1]), "=r"(r.a[j][2]), "=r"(r.a[j][3]) : "r"(qp + 64 * j), "r"((uint32_t)on) : "memory");
}
__device__ __forceinline__ void conv_item(uint32_t tb, uint32_t tl, int bid, int bn, ConvPre& pre, const ConvC& cv, uint32_t zero, const CUtensorMap* tmx, int ch, int warp, int lane, bool hold, bool more) {
  const bool go = more && warp == 0 && lane == 0;
  const uint32_t kp = tb + (cv.ca & 0xFFFFu), qp = tb + cv.qa;
  const uint32_t dlo = (tl >> 4) + 32 + ((warp >> 1) & 2) + (1u << 16), dhi = 32u | (2u << 30);
  const bool P = warp & 2;
  float a32[16], b32[16], a64[32];
  uint32_t A[40][4];
#define STEP(J) { wgmma64<0>(a64, A[J], dlo + 256 - 4 * (J), dhi); \
    if ((J) == 32) wgmma32_init<0>(b32, A[J], dlo, dhi); else wgmma32<0>(b32, A[J], ((J) < 8 ? dlo ^ zero : dlo) + 128 - 4 * (J), dhi); \
    if ((J) == 0) wgmma32_init<0>(a32, A[J], dlo, dhi); else if ((J) < 8) wgmma32<0>(a32, A[J], (dlo ^ zero) - 4 * (J), dhi); }
#define LD(J) load_a(A[J], kp, J);
#define LQ(J) { const uint4 v = lds128(qp + 64 * ((J) - 32)); A[J][0] = v.x; A[J][1] = v.y; A[J][2] = v.z; A[J][3] = v.w; }
#define PQ(J) { A[J][0] = prmt(A[J][0], 0, cv.cb); A[J][1] = prmt(A[J][1], 0, cv.cb); A[J][2] = prmt(A[J][2], 0, cv.cb); A[J][3] = prmt(A[J][3], 0, cv.cb); }
#define FIRST(J) wg_fence(); STEP(J) wg_commit(); wg_wait<1>(); wg_fence();
  {
    uint32_t win[16], x9[4], x7[4], e[4], f[4];
    const uint32_t bz = keep(cv.bands);
#define BAND(i) keep((bz & (0x10001u << (i))) * (0x3C00u >> (i)))
    e[0] = pre.e0; e[2] = pre.e2; e[1] = keep(bz & 0x100u); e[3] = keep(bz & 0x200u);
    f[2] = pre.f2; f[0] = keep(bz & 0x4000u); f[1] = keep(bz & 0x8000u); f[3] = keep(bz & 0x300u);
#pragma unroll
    for (int j = 0; j < 12; j++) A[32 + j / 4][j & 3] = pre.a[j / 4][j & 3];
    PQ(32) PQ(33) PQ(34)
    if (!P) { A[32][0] = pre.b0; A[32][2] = pre.b2; }
    const uint32_t q[12] = {BAND(0), BAND(5), keep(bz & 0x400u), BAND(4), BAND(2), BAND(7), BAND(1), BAND(6), keep(bz & 0x800u), keep(bz & 0x1000u), BAND(3), keep(bz & 0x2000u)};
#undef BAND
    const uint32_t ta = keep(tl + 512 + (warp & 3) * 2048 + lane * 64 + (lane & 6) * 8);
    if (X_GO && hold) mbar_wait(MB_GO);
    uint32_t mbl = MB_UL + (warp & 8) * 2, ph = 0;
#pragma unroll 1
    for (int it = 0; it < SPIN_MAX; it++) {
      if (ch < 512) mbar_wait(mbl, ph);
      if (it == 1) TS(13);
      TS(3);
      wg_fence();
      wgmma64h_init(win, q[0], q[1], q[2], q[3], dlo, dhi);
      wgmma64h(win, q[4], q[5], q[6], q[7], dlo - 4, dhi);
      wgmma64h(win, q[8], q[9], q[10], q[11], dlo - 8, dhi);
      wg_commit();
      wgmma64_init<0>(a64, e, dlo, dhi);
      wgmma64<0>(a64, f, dlo - 4, dhi);
      wg_commit();
      if (ch >= 512) break;
      uint32_t r0, r1, r2, r3, ok;
      if (warp & 4) {
        mbar_wait(mbl + 8);
        if (__all_sync(0xffffffffu, it || lds32(MISC_RT + (warp & 8)) == 0)) break;
        wg_wait<0>();
        continue;
      }
      ldsm4(ta, r0, r1, r2, r3);
      ok = r0 & r1 & r2 & r3;
      ldsm4(ta ^ 32, r0, r1, r2, r3);
      asm volatile("{ .reg .pred q; setp.ne.u32 q, %1, 0; barrier.red.and.pred q, %2, 128, q; selp.u32 %0, 1, 0, q; }" : "=r"(ok) : "r"((ok & r0 & r1 & r2 & r3 & 1u) | (lane & 3)), "r"(1 + (warp >> 2)) : "memory");
      if (ok) { if ((warp & 3) == 0 && lane == 0) { sts32(MISC_RT + warp, it); mbar_arrive(MB_UL + 8 + warp * 2); } break; }
      wg_wait<0>();
      if ((warp & 3) == 0 && lane == 0) load_tile(tmx - 1, warp >> 3, ch, 56);
      mbl = MB_UL + 56 + (warp & 8) * 2; ph = it & 1;
    }
    wg_wait<1>();
#pragma unroll
    for (int i = 0; i < 4; i++) {
      const int tl = 2 * ((i & 1) + ((i & 2) ? 0 : 4));
      x9[i] = P ? win[tl + 4] : win[tl]; x7[i] = P ? win[tl + 5] : win[tl + 1];
    }
    const uint32_t l3lo = ((tb + W_L3) >> 4) + (32u << 16);
    wg_fence();
    wgmma64<0>(a64, x9, l3lo, 8);
    wgmma64<0>(a64, x7, l3lo + 96, 8);
    wg_commit();
  }
  STEP(32) STEP(33) STEP(34) wg_commit(); wg_wait<1>();
  LQ(35) LQ(36) LQ(37) LQ(38) PQ(35) PQ(36) PQ(37) PQ(38)
  FIRST(35) STEP(36) STEP(37) STEP(38) wg_commit();
  LQ(39) LD(0) PQ(39)
  TS(17);
  if (X_GO == 1 && go) mbar_arrive(MB_GO);
  FIRST(39) STEP(0) wg_commit();
  LD(1) LD(2) LD(3)
  FIRST(1) STEP(2) STEP(3) wg_commit();
  LD(4) LD(5)
  if (X_GO == 2 && go) mbar_arrive(MB_GO);
  FIRST(4) STEP(5) wg_commit();
  LD(6) LD(7)
  wg_fence(); STEP(6) STEP(7) wg_commit();
#undef STEP
#undef LD
#undef LQ
#undef PQ
#undef FIRST
  TS(18);
  if (X_GO == 3 && go) mbar_arrive(MB_GO);
  const uint32_t xc = tb + W_KT + (warp & 3) * 1024 + lane * 16;
  if (more) bar_sync(7, 288);
  wg_wait<1>();
  conv_pre(pre, kp + ALT, qp + ALT, 1, more, P);
  wg_wait<0>();
  conv_pre(pre, kp + ALT, qp + ALT, 2, more, P);
  uint32_t E[16], o[8];
#define ACC(i) ((i) < 16 ? a32[i] : (i) < 32 ? b32[(i) - 16] : a64[(i) - 32])
  E[0] = pack_h(a32[0], a32[1]);
#pragma unroll
  for (int i = 1; i < 16; i++) E[i] = pack_h(ACC(4 * i) + ACC(4 * i - 2), ACC(4 * i + 1) + ACC(4 * i - 1));
#undef ACC
#pragma unroll
  for (int j = 0; j < 8; j++) o[j] = P ? (j < 2 ? 0u : E[j - 2]) : E[8 + j];
  sts128(xc, o[0], o[1], o[2], o[3]); sts128(xc + 512, o[4], o[5], o[6], o[7]);
#pragma unroll
  for (int j = 0; j < 8; j++) o[j] = P ? E[6 + j] : E[j];
  TS(25);
  if (more) {
    sts128(xc + 4096, o[0], o[1], o[2], o[3]); sts128(xc + 4608, o[4], o[5], o[6], o[7]);
    bar_arrive(12, 192);
    return;
  }
  bar_sync(1 + (warp >> 2), 128);
  const uint4 vv[2] = {lds128(xc + (P ? -2048 : 2048)), lds128(xc + (P ? -1536 : 2560))};
  const uint32_t mk = lane < 8 ? 0xFFFEFFFEu : ~0u;
#pragma unroll
  for (int q = 0; q < 2; q++) {
    const uint4 v = vv[q];
    stsm4t(tl + (cv.ca >> 16) + q * 2048, hadd2u(o[4 * q], v.x) & mk, hadd2u(o[4 * q + 1], v.y) & mk, hadd2u(o[4 * q + 2], v.z) & mk, hadd2u(o[4 * q + 3], v.w) & mk);
  }
  fence_async();
  bar_sync(bid, bn);
  if (warp == 0 && lane == 0) mbar_arrive(MB_REL);
  if ((warp & 7) == (ch < 512 ? 7 : 3) && lane == 0) {
    asm volatile("cp.async.bulk.tensor.3d.global.shared::cta.bulk_group [%0, {%3, %2, %3}], [%1];" :: "l"(tmx), "r"(tl + 512), "r"(ch), "r"(0) : "memory");
    asm volatile("cp.async.bulk.commit_group;" ::: "memory");
  }
}

template <bool FAR> __global__ void __launch_bounds__(NT, 1)
fused_kernel(const __grid_constant__ Params p, const __grid_constant__ TMaps tm) {
  extern __shared__ __align__(1024) unsigned char smem[];
  const int c = blockIdx.x;
  const bool five = (c & 1) == 0;
  const uint32_t pitch = five ? 64 : 80;
  const uint32_t ones = 0x3F803F80u;
  const int tid = threadIdx.x, lane = tid & 31;
  const uint32_t xrow = OFF_YT + ((tid & 127) >> 3) * YT_PITCH + (tid & 64) + (tid & 7) * 16;
  {
    const int w4 = tid >> 7;
    load_params<FAR>(p, w4 < 2 ? 2 * c + w4 : five ? 257 + 2 * c : 512 + (c >> 1), tid & 127, OFF_W + W_KT + (w4 < 2 ? w4 * W_BYTES : five ? 3 * W_BYTES : 3 * W_BYTES + 2048), (0xB >> w4) & 1);
  }
  if ((tid >> 7) == 2) {
    const unsigned char* xp = p.x + (uint32_t)((c * 16 - 32 + (tid >> 3)) * 1152 + (tid & 7) * 16);
    asm volatile("" : "+l"(xp));
    { const uint32_t tq = clock(); while ((int)(clock() - tq) < X_XD) {} }
#pragma unroll
    for (int k = 0; k < 9; k++) asm volatile("cp.async.cg.shared.global [%0], [%1], 16;" :: "r"(xrow + k * 128), "l"(xp + k * 128) : "memory");
  }
  const int warp = (int)uni(tid >> 5), wg = warp >> 2;
  TS(0);
  if (__builtin_expect(wg == 4, 0)) {
    asm volatile("setmaxnreg.dec.sync.aligned.u32 32;");
    const int role = warp;
    const int u0 = (c >> 1) * 9 + (five ? ((c & 2) ? 5 : 0) : ((c & 2) ? 0 : 4));
    const uint32_t t0 = clock() + c * 4;
    if (role == 16) {
      if (lane < 19) asm volatile("mbarrier.init.shared::cta.b64 [%0], %1;" :: "r"(OFF_MISC + lane * 8), "r"((unsigned)(lane - 2) < 4u ? 4 : 1) : "memory");
      if (lane < 2) asm volatile("mbarrier.arrive.expect_tx.shared::cta.b64 _, [%0], %1;" :: "r"(OFF_MISC + lane * 8), "r"(lane ? (five ? 36864 : 51200) : pitch * 1152) : "memory");
      fence_async();
      bar_arrive(5, 608);
      const CUtensorMap* tmb = &tm.m[five ? 3 : 0];
#pragma unroll 1
      for (int u = 0; u < 17; u++) {
        const uint32_t e = p.sched[five][u], kind = e & 3, s = (e >> 2) & 15, dst = e >> 14;
        if (kind == 3) continue;
        while ((int)(clock() - t0) < X_PF0 + (u < X_NE ? u * X_PFD : X_LAG + u * X_TD)) __nanosleep(20);
        if (e & 0x3FC0) mbar_wait(OFF_MISC + ((e >> 6) & 255));
        if (lane == 0) {
          if (kind == 2) asm volatile("cp.async.bulk.tensor.3d.shared::cluster.global.mbarrier::complete_tx::bytes [%0], [%1, {%3, %4, %5}], [%2];"
                                      :: "r"(dst), "l"(tmb + 2), "r"(MB_D), "r"(0), "r"(u0 * 8), "r"(s) : "memory");
          else tma_box(dst, tmb + kind, MB_GU, u0 * 8, s * 96);
        }
        if (u == 5) TS(2);
        if (u == 10) TS(3);
      }
      TS(4);
      TS_DUMP();
#define FINISH0 bar_sync(12, 192);        \
        _Pragma("unroll 1") for (int w = role & 2; w < (role & 2) + 2; w++) { \
          const uint32_t xa = OFF_W + W_KT + lane * 16, mk = lane < 8 ? 0xFFFEFFFEu : ~0u, ya = OFF_T + (8 + lane) * 64 + (((w & 1) ^ (lane >> 1)) & 3) * 16 + (w & 2) * 2048; \
          const uint4 a = lds128(xa + 4096 + w * 1024), b = lds128(xa + (w ^ 2) * 1024), d = lds128(xa + 4608 + w * 1024), e = lds128(xa + 512 + (w ^ 2) * 1024); \
          stsm4t(ya, hadd2u(a.x, b.x) & mk, hadd2u(a.y, b.y) & mk, hadd2u(a.z, b.z) & mk, hadd2u(a.w, b.w) & mk); \
          stsm4t(ya + 2048, hadd2u(d.x, e.x) & mk, hadd2u(d.y, e.y) & mk, hadd2u(d.z, e.z) & mk, hadd2u(d.w, e.w) & mk); \
        } \
        fence_async();
    } else if (role == 17) {
      if (smem_u32(smem) != SB) __trap();
      bar_sync(10, 576);
      if (lane == 0) {
        fence_async();
        while ((int)(clock() - t0) < X_NS - c * 4) {}
        asm volatile("cp.async.bulk.global.shared::cta.bulk_group [%0], [%1], 10240;" :: "l"(&p.s->X[c * DM * 2 + 512]), "r"(OFF_G) : "memory");
        asm volatile("cp.async.bulk.commit_group;" ::: "memory");
        asm volatile("cp.async.bulk.wait_group 0;" ::: "memory");
      }
      if (lane == 0) mbar_arrive(MB_GF);
      bar_arrive(11, 96);
      if (five) { FINISH0 bar_arrive(13, 192); }
    } else if (role == 18) {
      sts32(MISC_EPOCH, 0);
      sts32(MISC_T0, t0 - c * 4);
      bar_arrive(5, 608);
      uint4* q = lane < 2 ? &p.s->R[c * 2 + lane] : lane < 11 ? &p.s->HS[c * 9 + lane - 2] : lane == 11 ? &p.s->HS[1152 + (c & 7)] : (uint4*)&p.s->FLAG[c * 8];
      if (lane < (c < 8 ? 12 : 11)) str128(q, ~0u, ~0u, ~0u, ~0u);
      const uint32_t ep = __shfl_sync(0xffffffffu, ldr32(q), 31) + 1u;
      sts32(MISC_EPOCH, ep | 0x80000000u);
      TSX(21);
      if (lane == 31) str32(q, ep);
      bar_sync(11, 96);
      TSX(14);
      mbar_wait(MB_KF + (lane & 3) * 8);
      __syncwarp();
      { const uint2 e = lds64(MISC_EM); if (lane < 2) str128(&p.s->SC[c * 2 + lane], e.x, __byte_perm(e.y, ep, 0x6540), 0, 0); }
      TSX(17);
      while ((int)(clock() - t0) < X_SCT) __nanosleep(100);
      TSX(18);
      {
        uint2 v[4];
#pragma unroll 1
        for (int it = 0; it < SPIN_MAX; it++) {
          uint32_t bad = 0;
#pragma unroll
          for (int q = 0; q < 4; q++) v[q] = ldr64(&p.s->SC[lane * 2 + q * 64]);
#pragma unroll
          for (int q = 0; q < 4; q++) bad |= (v[q].y >> 8) ^ (ep & 0xFFFFFFu);
          if (!__any_sync(0xffffffffu, bad)) break;
        }
        TSX(25);
#pragma unroll
        for (int q = 0; q < 4; q++) {
          const uint32_t sa = (lane >> 4) * YT_PITCH + (lane & 15) * 2;
          sts16(sc_addr(2 * q) + sa, v[q].x); sts16(sc_addr(8 + 2 * q) + sa, v[q].x >> 16);
          if (lane & 1) asm volatile("st.shared.u8 [%0], %1;" :: "r"(sc_addr(16) + q * 16 + (lane >> 1)), "r"(v[q].y) : "memory");
        }
      }
      __syncwarp();
      if (lane == 0) mbar_arrive(MB_SC);
      TSX(27);
    } else {
      uint32_t w[9];
      const uint32_t dk = ldnc16(p.dskip + ((lane & 4) ? 512 + (c >> 1) : (lane & 2) * 128 + 2 * c + (lane & 1)));
      float s = 0.f;
#pragma unroll
      for (int i = 0; i < 9; i++) w[i] = ldnc32(p.w_r + lane + 32 * i);
      sts16(OFF_WR + 1152 + lane * 2, dk);
      bar_arrive(5, 608);
#pragma unroll
      for (int i = 0; i < 9; i++) { sts32(OFF_WR + lane * 4 + i * 128, w[i]); s += bf_lo(w[i]) + bf_hi(w[i]); }
      sts32(MISC_SW, __float_as_uint(warp_sum(s)));
      TSX(23);
      bar_sync(10, 576);
      if (lane == 0) {
        const uint32_t tp = clock();
        TSX(1);
        while ((int)(clock() - tp) < X_DELTA || (int)(clock() - t0) < X_ABS - c * 4) {}
        TSX(24);
        load_tile(&tm.m[6], 0, c);
        TSX(15);
        while ((int)(clock() - t0) < X_ABS + X_DSTEP - c * 4) {}
      }
      bar_sync(11, 96);
      if (lane == 0) {
        load_tile(&tm.m[6], 1, 128 + c);
      }
      if (five) {
        mbar_wait(MB_KF);
#pragma unroll 1
        for (int it = 0; it < SPIN_MAX; it++) {
          if (lane == 0) load_tile(&tm.m[8], 2, 512 + (c >> 1));
          mbar_wait(MB_UL + 32, it & 1);
          uint32_t m = 1;
#pragma unroll
          for (int q = 0; q < 4; q++) { uint32_t r0, r1, r2, r3; ldsm4(OFF_W + 512 + lane * 64 + (lane & 6) * 8 + q * 2048, r0, r1, r2, r3); m &= r0 & r1 & r2 & r3; }
          if (__all_sync(0xffffffffu, m || (lane & 3))) break;
        }
        bar_arrive(7, 288);
        FINISH0
        bar_arrive(13, 192);
      }
      bar_sync(0, 544);
      if (lane == 0) mbar_arrive(MB_H);
    }
    return;
  }
  const int wt = tid & 127, g = lane >> 2, t = lane & 3;
  const uint32_t wb = OFF_W + wg * W_BYTES;
  asm volatile("cp.async.commit_group;" ::: "memory");
  const ConvC cv = conv_consts(warp, lane);
  zero_pads(wb, wt);
  load_params<FAR>(p, 254 + 2 * c + wg, wt, wb + W_KT, wg == 2 || (wg == 3 && !five));
  asm volatile("cp.async.commit_group;" ::: "memory");
  asm volatile("setmaxnreg.inc.sync.aligned.u32 112;");
  {
    uint4 kw;
    uint4* kx = &p.s->KX[(c >> 1) * 128 + wt];
    bool two = wg == 3;
    uint32_t ep;
    int em = 0;
    uint32_t slot = wg + (two && !five);
    const uint32_t ra0 = wb + W_KT + (slot & 4) * 512 + wt * 2, ra6 = wb + W_KT + 1536 + (slot & 4) * 512 + (((slot & 4) ? c >> 1 : 2 * c + (wg & 1)) & 7) * 2;
    uint32_t raw[7];
    if (wg != 2) {
      asm volatile("cp.async.wait_group 1;" ::: "memory");
      bar_sync(1 + wg, 128);
#pragma unroll
      for (int i = 0; i < 7; i++) raw[i] = lds16(i < 6 ? ra0 + i * 256 : ra6);
    }
    int phase = wg == 2 ? 3 : 2;
#pragma unroll 1
    for (;;) {
      if (phase != 3) {
        KgState ks;
        TS(22);
        kgen_tables_n(raw, wb, wt, ks);
        TS(20);
        bar_sync(1 + wg, 128);
        em = kgen_tables_m(wb, wt, ks);
        fence_async();
      }
      if (phase & 2) {
        const int lz = lane ^ (clock() & p.off[7]);
        const uint32_t tr_addr = pin(tr_base(lz) + warp * 32), lca = pin(MISC_LN1 + (lz & 1) * 16);
        uint4* dst;
        { const unsigned long long a = (unsigned long long)&p.s->X[c * DM * 2 + warp * 32 + (8 * ((lz >> 1) & 1) + (lz >> 2)) * 2 + (lz & 1)];
          dst = (uint4*)(((unsigned long long)pin(a >> 32) << 32) | pin((uint32_t)a)); }
        if (phase == 3) {
        asm volatile("cp.async.wait_group 1;" ::: "memory");
        TS(21);
        float d[3][4], r;
        uint4 a[9];
#pragma unroll
        for (int k = 0; k < 9; k++) a[k] = lds128(xrow + k * 128);
#pragma unroll
        for (int i = 0; i < 4; i++) d[0][i] = d[1][i] = d[2][i] = 0.f;
#pragma unroll
        for (int k = 0; k < 9; k++) { mma_bf16(d[(2 * k) % 3], a[k].x, ones, a[k].y, ones, a[k].x, a[k].y); mma_bf16(d[(2 * k + 1) % 3], a[k].z, ones, a[k].w, ones, a[k].z, a[k].w); }
#pragma unroll
        for (int i = 0; i < 4; i++) d[0][i] += d[1][i] + d[2][i];
        const LnC lc = ln_consts(d[0][2] + d[0][3], __shfl_sync(0xffffffffu, d[0][0], 9 * t) + __shfl_sync(0xffffffffu, d[0][1], 9 * t + 4), r);
        if (lane < 12) sts16(MISC_LN1 + g * 32 + (warp & 3) * 8 + t * 2, lane < 4 ? lc.m2 : lane < 8 ? lc.rh2 : lc.rl2);
        }
        asm volatile("cp.async.wait_group 0;" ::: "memory");
        TS(23);
        bar_sync(5, 608);
        uint32_t x[3][4];
        ldsm4t(tr_addr, x[0][0], x[0][1], x[0][2], x[0][3]);
        uint4 m = lds128(lca);
        const uint4 rl = lds128(lca + 64), rh = lds128(lca + 32);
        ldsm4t(tr_addr + 512, x[1][0], x[1][1], x[1][2], x[1][3]);
        if (wg == 3) ldsm4t(tr_addr + 640, x[2][0], x[2][1], x[2][2], x[2][3]);
#pragma unroll
        for (int q = 0; q < 3; q++) {
          if (q < 2 || wg == 3) {
            const uint32_t r0 = ln_apply(x[q][0], m.x, rh.x, rl.x), r1 = ln_apply(x[q][1], m.y, rh.y, rl.y), r2 = ln_apply(x[q][2], m.z, rh.z, rl.z), r3 = ln_apply(x[q][3], m.w, rh.w, rl.w);
            const uint32_t w0 = (pack_h(bf_lo(r0), bf_hi(r0)) & 0xFFFEFFFEu) | 1u, w1 = pack_h(bf_lo(r1), bf_hi(r1)), w2 = pack_h(bf_lo(r2), bf_hi(r2)), w3 = pack_h(bf_lo(r3), bf_hi(r3));
            if (q == 0) str128(dst, w0, w1, w2, w3);
            else sts128(OFF_G + warp * 512 + (8 * (t >> 1) + g) * 32 + (t & 1) * 16 + (q == 2 ? 2048 : 0), w0, w1, w2, w3);
          }
          if (q == 0) {
            const uint32_t z = clock() & p.off[7];
            m.x ^= z; m.y ^= z; m.z ^= z; m.w ^= z;
          }
          if (q == 0) TS(30);
          if (q == 0 && wg >= 2) {
#pragma unroll
            for (int i = 0; i < 7; i++) raw[i] = lds16(wb + W_KT + i * 256 + (i < 6 ? wt : (2 * c + (wg & 1)) & 7) * 2);
          }
        }
        bar_arrive(10, 576);
        TS(1);
      } else bar_sync(1 + wg, 128);
      phase &= 1;
      if (phase) { phase = 0; continue; }
      TS(14);
      float acc[20];
      const uint32_t alo = (wb >> 4) | (8u << 16);
      uint4 k4 = lds128(wb + W_MISC + 16);
      uint32_t dk = lds16(OFF_WR + 1152 + slot * 2);
      wg_fence();
      wgmma40_ss_init(acc, alo, alo + 1024, 2048 >> 4);
#pragma unroll
      for (int k = 1; k < 8; k++) wgmma40_ss(acc, alo + k * 16, alo + 1024 + k * 16, 2048 >> 4);
      wg_commit();
      { const uint32_t z = clock() & p.off[7]; dk ^= z; k4.x ^= z; k4.z ^= z; }
      const float k2048 = (float)(int)((k4.x + k4.y) + (k4.z + k4.w)) * (1.f / 262144.f);
      const int ef = max(em, min((int)((dk >> 7) & 255u) - 7, 238));
      asm volatile("st.shared.u8 [%0], %1;" :: "r"(MISC_EM + slot), "r"(ef + 9) : "memory");
      const float un = __uint_as_float((uint32_t)max(114 + em - ef, 0) << 23), d0 = wt ? 0.f : bf_lo(dk) * __uint_as_float((uint32_t)(245 - ef) << 23);
      wg_wait<0>();
      kw.x = pack_h(fmaf(acc[0] - acc[3], un, d0), (acc[4] - acc[7]) * un);
      kw.y = pack_h((acc[8] - acc[11]) * un, (acc[12] - acc[15]) * un);
      kw.z = pack_h((acc[16] - acc[19]) * un, k2048 * un);
      TS(24);
      ep = 0;
      if (two) SPIN_WHILE(ep == 0, ep = lds32(MISC_EPOCH));
      if (five || !two) break;
      str128(kx, kw.x, kw.y, kw.z, ep);
      two = false;
      slot = 3;
      bar_sync(1 + wg, 128);
    }
    if (lane == 0) mbar_arrive(MB_KF + wg * 8);
    if (two) { mbar_wait(MB_KF); zero_pads(OFF_W + ALT, wt); }
    uint32_t tb = wb;
#pragma unroll 1
    for (;;) {
      kgen_build(tb, wg, wt, kw.x, kw.y, kw.z);
      TS(15);
      if (!two) break;
      two = false;
      kw.w = 0;
      SPIN_WHILE(kw.w != ep, kw = ldr128(kx));
      tb = OFF_W + ALT;
    }
    fence_async();
    TS(31);
    if (tb != wb) bar_arrive(7, 288);
    bar_sync(1 + wg, 128);
  }
  uint32_t tpub;
  ConvPre pre;
  conv_pre(pre, (wb ^ p.off[7]) + (cv.ca & 0xFFFFu), (wb ^ p.off[7]) + cv.qa, 3, true, warp & 2);
#pragma unroll 1
  for (int item = 0;; item++) {
    TS(2);
    conv_item(item ? OFF_W + ALT : wb, item ? OFF_W : OFF_T + (wg >> 1) * TILE, item ? 1 : 13 + (wg >> 1), item ? 128 : five && wg == 1 ? 192 : 256, pre, cv, p.off[7],
              &tm.m[item ? 9 : 7], item ? 512 + (c >> 1) : (wg >> 1) * 128 + c, warp, lane, five && wg >= X_GW, five && !wg && !item);
    tpub = clock() - (item ? X_YD : wg >= 2 ? X_YD2 : 0);
    if (wg || !five || item) break;
    TS(27);
  }
  TS(4);

  const int ln = lane ^ p.off[7], td = warp * 32 + ln, gg = ln >> 2, tt = ln & 3;
  const int tok = c * 16 + warp;
  const int fu = warp / 3, fk = warp - fu * 3;
  uint32_t wa[12][4];
  uint4 ha[3];
  const uint4* hsrc = &p.s->HS[td + (td / 24) * 48];
  {
    uint32_t hw[9], wr[9];
    const uint32_t row = keep(OFF_YT + warp * YT_PITCH + (warp >> 3) * 64 + ln * 16);
    const uint32_t wabase = keep(((ln & 8) ? OFF_W + (fk + 1) * W_BYTES : OFF_G + fk * 192 * pitch) + ((ln >> 4) * 8 + (ln & 7)) * pitch
                                 + (five ? ((fu ^ (ln >> 1)) & 3) : min(fu, 4)) * 16);
    float sw;
    {
      const bool three = wg == 1;
      const int ch = 8 * (tt >> 1) + gg;
      const uint32_t tr_addr = tr_base(ln);
      const uint4* ysrc = &p.s->X[c * DM * 2 + ch * 2 + (tt & 1)];
      uint32_t x[3][4], s[3];
      uint4 v[3];
#define TL(q) ((q) < 2 ? 2 * warp + (q) : 28 + warp)
      asm volatile("cp.async.bulk.wait_group.read 0;" ::: "memory");
      if (wg >= 2) { const uint32_t ts = lds32(MISC_T0); while ((int)(clock() - ts) < X_XS) {} }
      while ((int)(clock() - tpub) < X_YD) {}
      TS(5);
      v[0] = ldr128(ysrc + TL(0) * 32); v[1] = ldr128(ysrc + TL(1) * 32); v[2] = make_uint4(three, 0, 0, 0);
      mbar_wait(MB_REL);
#pragma unroll
      for (int i = 0; i < 6; i++) if (i < 4 || three) wr[i] = (gg & 2) ? ones : lds32(OFF_WR + TL(i >> 1) * 32 + (i & 1) * 16 + tt * 4);
      const uint32_t ha = keep(OFF_YT + (ln & 7) * YT_PITCH + (ln >> 4) * (8 * YT_PITCH + 64) + (ln & 8) * 2);
      const uint32_t pa = keep(OFF_PART + warp * 4 + ((gg & 2) * 8 + (gg & 4) * 2 + 2 * tt + (gg & 1)) * 80), pb = keep(OFF_PART + 2560 + warp * 4 + gg * 80);
      float dl[4] = {0.f, 0.f, 0.f, 0.f}, dh[4] = {0.f, 0.f, 0.f, 0.f};
      sw = __uint_as_float(lds32(MISC_SW));
#pragma unroll
      for (int q = 0; q < 3; q++) {
        if (q < 2 || three) {
          ldsm4t(tr_addr + TL(q) * 32, x[q][0], x[q][1], x[q][2], x[q][3]);
        }
      }
      mbar_wait(MB_SC);
#pragma unroll
      for (int q = 0; q < 3; q++) {
        asm volatile("ld.shared.u8 %0, [%1];" : "=r"(s[q]) : "r"((q < 2 ? sc_addr(warp) + q * 16 : sc_addr(16) + (warp & 3) * 16) + ch) : "memory");
        s[q] = keep(s[q] * 0x800080u);
      }
#define FIN(q) stsm4t(tr_addr + TL(q) * 32, bf_fma2(h2bf(v[q].x), s[q], x[q][0]), bf_fma2(h2bf(v[q].y), s[q], x[q][1]), bf_fma2(h2bf(v[q].z), s[q], x[q][2]), bf_fma2(h2bf(v[q].w), s[q], x[q][3]));
      SPIN_WHILE((v[0].x | v[1].x) & 1u, _Pragma("unroll") for (int q = 0; q < 3; q++) if (v[q].x & 1u) v[q] = ldr128(ysrc + TL(q) * 32));
      if (v[2].x & 1u) v[2] = ldr128(ysrc + TL(2) * 32);
#define STAT(q) { uint32_t r0, r1, r2, r3; ldsm4(ha + TL(q) * 32, r0, r1, r2, r3); \
        mma_bf16(dl, r0, wr[2 * q], r1, wr[2 * q + 1], r0, r1); mma_bf16(dh, r2, wr[2 * q], r3, wr[2 * q + 1], r2, r3); }
      FIN(0) FIN(1)
      __syncwarp();
      STAT(0) STAT(1)
      if (three) {
        SPIN_WHILE(v[2].x & 1u, if (v[2].x & 1u) v[2] = ldr128(ysrc + TL(2) * 32));
        FIN(2)
        __syncwarp();
        STAT(2)
      }
      if (gg & 1) { dl[0] = dl[1]; dl[2] = dl[3]; dh[0] = dh[1]; dh[2] = dh[3]; }
      sts32(pa, __float_as_uint((gg & 4) ? dh[2] : dl[2]));
      if (tt == (gg >> 1)) { sts32(pb, __float_as_uint(dl[0])); sts32(pb + 640, __float_as_uint(dh[0])); }
#undef STAT
#undef FIN
#undef TL
    }
    uint32_t ra = keep(OFF_PART + (ln & 15) * 80 + (ln & 16) * 2);
    uint16_t* rp = (uint16_t*)p.s->R + c * 16 + (ln & 15);
    const uint2* rsrc = (const uint2*)p.s->R + td;
    asm volatile("" : "+l"(rp), "+l"(rsrc), "+l"(hsrc));
    uint2 rv = make_uint2(0u, 0u);
    TS(28);
    if (warp != X_PW) bar_sync(0, 544);
    else {
      float z[3], rd;
      asm volatile("bar.sync 0, 544;" : "+r"(ra) :: "memory");
#pragma unroll
      for (int k = 2; k >= 0; k--) {
        const uint4 a = lds128(ra + k * 1280), b = lds128(ra + k * 1280 + 16);
        z[k] = ((__uint_as_float(a.x) + __uint_as_float(a.y)) + (__uint_as_float(a.z) + __uint_as_float(a.w))) + ((__uint_as_float(b.x) + __uint_as_float(b.y)) + (__uint_as_float(b.z) + __uint_as_float(b.w)));
      }
#pragma unroll
      for (int k = 2; k >= 0; k--) z[k] += __shfl_xor_sync(0xffffffffu, z[k], 16);
      const LnC l = ln_consts(z[1], z[2], rd);
      const uint32_t b = pack_bf(0.f, fmaf(-bf_lo(l.m2), sw, z[0]) * rd);
      const uint32_t k16 = max(min((b ^ (((int)b >> 31) | 0x80000000u)) >> 16, 0xFFFEu), 1u);
      if (ln < 16) str16(rp, k16);
      sts64(OFF_RK + (ln & 15) * 8, __byte_perm(l.m2, l.rh2, 0x5410), __byte_perm(l.rl2, k16, 0x5410));
      sts128(MISC_CNT + ln * 16, 0, 0, 0, 0);
    }
    mbar_wait(MB_GU);
#define LD_HW { const uint4 a = lds128(row), b = lds128(row + 512); hw[8] = lds32(row + 1024 - ln * 12); \
      hw[0] = a.x; hw[1] = a.y; hw[2] = a.z; hw[3] = a.w; hw[4] = b.x; hw[5] = b.y; hw[6] = b.z; hw[7] = b.w; }
    LD_HW
    const uint32_t tr0 = clock();
    bar_sync(5, 512);
    TS(7);
    const uint2 lk = lds64(OFF_RK + warp * 8);
    LnC l2;
    l2.m2 = __byte_perm(lk.x, 0, 0x1010); l2.rh2 = __byte_perm(lk.x, 0, 0x3232); l2.rl2 = __byte_perm(lk.y, 0, 0x1010);
    const uint32_t key = (lk.y & 0xFFFF0000u) | (2047 - tok);
    uint32_t loc = ln < 16 ? (lds32(OFF_RK + 4 + ln * 8) & 0xFFFF0000u) | (2047 - c * 16 - ln) : 0u;
    int rank = __popc(__ballot_sync(0xffffffffu, loc > key));
#pragma unroll
    for (int i = 0; i < 9; i++) wr[i] = keep(ln_apply(hw[i], l2.m2, l2.rh2, l2.rl2));
#define OUT_ROW { uint32_t* o = p.out + tok * 288 + ln * 4; \
      *(uint4*)o = make_uint4(bf_add2(hw[0], wr[0]), bf_add2(hw[1], wr[1]), bf_add2(hw[2], wr[2]), bf_add2(hw[3], wr[3])); \
      *(uint4*)(o + 128) = make_uint4(bf_add2(hw[4], wr[4]), bf_add2(hw[5], wr[5]), bf_add2(hw[6], wr[6]), bf_add2(hw[7], wr[7])); \
      o[256 - ln * 3] = bf_add2(hw[8], wr[8]); }
    uint4* hs = p.s->HS + ln;
    asm volatile("" : "+l"(hs));
#pragma unroll 1
    for (int base = 0; base < 8; base += 2) {
      uint32_t T[2];
#pragma unroll
      for (int j = 0; j < 2; j++) {
        const uint32_t mx = __reduce_max_sync(0xffffffffu, loc);
        if (loc == mx) loc = 0;
        T[j] = (td >> 2) < c ? (mx & 0xFFFF0000u) - 1u : mx | 0xFFFFu;
      }
      const uint32_t sh = keep(rank == base ? 0x4410u : rank == base + 1 ? 0x4432u : 0x4445u), ca = keep(MISC_CNT + base * 64 + ln * 4);
      TS(29);
      if (base == 0) {
        while ((int)(clock() - tr0) < X_RD) {}
        if ((td >> 2) != c) rv = ldr64(rsrc);
        if (rank >= X_OR) OUT_ROW
        if (warp < (five ? 12 : 15)) {
#pragma unroll
          for (int k = 0; k < X_WS; k++) ldsm4t(wabase + k * 16 * pitch, wa[k][0], wa[k][1], wa[k][2], wa[k][3]);
        }
      }
      uint32_t cnt;
#pragma unroll 1
      for (int it = 0; it < SPIN_MAX; it++) {
        const uint32_t xs = rv.x << 16, ys = rv.y << 16;
        const bool bad = max(max(rv.x, xs), max(rv.y, ys)) >= 0xFFFF0000u;
        uint32_t cn2 = 0;
        cnt = bad ? 256u : 0u;
#pragma unroll
        for (int j = 0; j < 2; j++)
          asm("{ .reg .pred a, b, c, d; setp.gt.u32 a, %2, %6; setp.gt.u32 b, %3, %6; setp.gt.u32 c, %4, %6; setp.gt.u32 d, %5, %6; "
              "@a add.u32 %1, %1, %7; @b add.u32 %1, %1, %7; @c add.u32 %0, %0, %7; @d add.u32 %0, %0, %7; }"
              : "+r"(cnt), "+r"(cn2) : "r"(rv.x), "r"(rv.y), "r"(xs), "r"(ys), "r"(T[j]), "r"(1u << (16 * j)));
        cnt = __reduce_add_sync(0xffffffffu, cnt + cn2);
        asm volatile("{ .reg .pred q; setp.eq.u32 q, %2, 0; @q red.shared.add.u32 [%0], %1; }" :: "r"(ca), "r"(cnt), "r"(cnt & 0x3F00u) : "memory");
        if (!(cnt & 0x3F00u)) break;
        if (bad) rv = ldr64(rsrc);
      }
      TS(16);
      bar_sync(0, 512);
      cnt = lds32(ca);
      if (base == 0) tpub = clock();
      const int gr = rank + __byte_perm(cnt, 0x800u, sh);
      if (gr < 8) {
        uint4* ks = hs + 1152 + gr;
        hs = (uint4*)((char*)hs + gr * 1152);
        asm volatile("{ .reg .b128 t, u; .reg .b64 a, b, c, d; mov.b64 a, {%1,%2}; mov.b64 b, {%3,%4}; mov.b64 c, {%5,%6}; mov.b64 d, {%7,%8}; mov.b128 t, {a, b}; mov.b128 u, {c, d}; "
                     "st.relaxed.gpu.global.b128 [%0], t; st.relaxed.gpu.global.b128 [%0 + 512], u; }"
                     :: "l"(hs), "r"(wr[0]), "r"(wr[1]), "r"(wr[2]), "r"(wr[3]), "r"(wr[4]), "r"(wr[5]), "r"(wr[6]), "r"(wr[7]) : "memory");
        str32((uint32_t*)(hs + 64) - ln * 3, wr[8]);
        str128(hs + 576, hw[0], hw[1], hw[2], hw[3]); str128(hs + 608, hw[4], hw[5], hw[6], hw[7]); str32((uint32_t*)(hs + 640) - ln * 3, hw[8]);
        if (ln == 0) str32(ks, key);
        rank = 16;
      }
      if (__all_sync(0xffffffffu, (int)(cnt >> 16) + base + 2 >= 8)) break;
    }
    TS(8);
    if (warp < (five ? 12 : 15)) {
#pragma unroll
      for (int k = X_WS; k < 12; k++) ldsm4t(wabase + k * 16 * pitch, wa[k][0], wa[k][1], wa[k][2], wa[k][3]);
    }
    if (warp < 6) while ((int)(clock() - tpub) < X_HD) {}
    TS(19);
    if (warp < 6) { ha[0] = ldr128(hsrc); ha[1] = ldr128(hsrc + 24); ha[2] = ldr128(hsrc + 48); }
    if (rank < X_OR) OUT_ROW
  }
  uint32_t wd[10][4];
  const uint32_t xb = keep(OFF_XS + (ln & 7) * 1168 + (fk * 24 + (ln >> 3)) * 16);
  if (warp >= 7) {
    const uint32_t db = down_box(warp - 7, five) + (ln & 7) * 128;
    mbar_wait(MB_D);
#pragma unroll
    for (int j = 0; j < 4; j++) {
      const uint32_t a = db + (ln >> 4) * 1024 + (((2 * j + ((ln >> 3) & 1)) ^ (ln & 7)) << 4);
      ldsm4t(a, wd[j][0], wd[j][1], wd[j][2], wd[j][3]);
      ldsm4t(a + 2048, wd[4 + j][0], wd[4 + j][1], wd[4 + j][2], wd[4 + j][3]);
    }
#pragma unroll
    for (int j = 0; j < 2; j++) ldsm4t(db + 4096 + (((4 * j + (ln >> 3)) ^ (ln & 7)) << 4), wd[8 + j][0], wd[8 + j][1], wd[8 + j][2], wd[8 + j][3]);
  } else if (warp < 6) {
    const uint32_t xs = keep(OFF_XS + (td + (td / 24) * 49) * 16);
#pragma unroll 1
    for (int it = 0; it < SPIN_MAX; it++) {
      const bool bad = max(max(max(ha[0].x, ha[1].x), max(ha[2].x, ha[2].y)), max(ha[2].z, ha[2].w)) == ~0u;
      if (!__any_sync(0xffffffffu, bad)) break;
      if (bad) { ha[0] = ldr128(hsrc); ha[1] = ldr128(hsrc + 24); ha[2] = ldr128(hsrc + 48); }
    }
#pragma unroll
    for (int q = 0; q < 3; q++) sts128(xs + q * 384, ha[q].x, ha[q].y, ha[q].z, ha[q].w);
  }
  TS(9);

  bar_sync(0, 512);
  if (warp < (five ? 12 : 15)) {
    float d0[4] = {0.f, 0.f, 0.f, 0.f}, d1[4] = {0.f, 0.f, 0.f, 0.f};
#pragma unroll
    for (int k = 0; k < 12; k += 2) {
      uint32_t b0, b1, b2, b3;
      ldsm4(xb + k * 32, b0, b1, b2, b3);
      mma_bf16(d0, wa[k][0], wa[k][1], wa[k][2], wa[k][3], b0, b1);
      mma_bf16(d1, wa[k + 1][0], wa[k + 1][1], wa[k + 1][2], wa[k + 1][3], b2, b3);
    }
    sts128(OFF_RED + td * 16, __float_as_uint(d0[0] + d1[0]), __float_as_uint(d0[1] + d1[1]), __float_as_uint(d0[2] + d1[2]), __float_as_uint(d0[3] + d1[3]));
  }
  TS(26);
  if (warp < 5) {
    const uint32_t rb = OFF_RED + warp * 1536 + ln * 16;
    bar_sync(9, 512);
    const uint4 pa = lds128(rb), pb = lds128(rb + 512), pc = lds128(rb + 1024);
    const float ga = bfr(__uint_as_float(pa.x) + __uint_as_float(pb.x) + __uint_as_float(pc.x));
    const float gb = bfr(__uint_as_float(pa.y) + __uint_as_float(pb.y) + __uint_as_float(pc.y));
    const uint32_t uu = pack_bf(__uint_as_float(pa.z) + __uint_as_float(pb.z) + __uint_as_float(pc.z), __uint_as_float(pa.w) + __uint_as_float(pb.w) + __uint_as_float(pc.w));
    float ra, rb2;
    asm("rcp.approx.ftz.f32 %0, %1;" : "=f"(ra) : "f"(1.f + ex2(ga * -1.4426950408889634f)));
    asm("rcp.approx.ftz.f32 %0, %1;" : "=f"(rb2) : "f"(1.f + ex2(gb * -1.4426950408889634f)));
    const uint32_t act = bf_mul2(pack_bf(ga * ra, gb * rb2), uu);
    sts32(OFF_ACT + td * 4, act);
  } else bar_arrive(9, 512);
  uint4* dst = &p.s->X[c * DM * 2 + (warp - 7) * 64 + tt * 8 + gg];
  asm volatile("" : "+l"(dst));
  bar_sync(8, 512);
  tpub = clock();
  if (warp >= 7) {
    uint32_t b0, b1, b2, b3, b4;
    ldsm4t(OFF_ACT + ln * 16, b0, b1, b2, b3);
    asm volatile("ldmatrix.sync.aligned.m8n8.x1.trans.shared.b16 {%0}, [%1];" : "=r"(b4) : "r"(OFF_ACT + 512 + ln * 16) : "memory");
    float y[4][4];
#pragma unroll
    for (int j = 0; j < 4; j++) {
      y[j][0] = y[j][1] = y[j][2] = y[j][3] = 0.f;
      mma_bf16(y[j], wd[j][0], wd[j][1], wd[j][2], wd[j][3], b0, b1);
    }
#pragma unroll
    for (int j = 0; j < 4; j++) mma_bf16(y[j], wd[4 + j][0], wd[4 + j][1], wd[4 + j][2], wd[4 + j][3], b2, b3);
    if (!five) {
#pragma unroll
      for (int j = 0; j < 4; j++) mma_bf16_k8(y[j], wd[8 + (j >> 1)][2 * (j & 1)], wd[8 + (j >> 1)][2 * (j & 1) + 1], b4);
    }
    str128(dst, (pack_bf(y[0][0], y[0][1]) & ~1u) | 0x10000u, pack_bf(y[0][2], y[0][3]), pack_bf(y[1][0], y[1][1]), pack_bf(y[1][2], y[1][3]));
    str128(dst + 32, (pack_bf(y[2][0], y[2][1]) & ~1u) | 0x10000u, pack_bf(y[2][2], y[2][3]), pack_bf(y[3][0], y[3][1]), pack_bf(y[3][2], y[3][3]));
  }
  TS(10);

  if (c < 72) {
    const uint4* src = &p.s->X[(warp * 4 + tt) * (DM * 2) + c * 8 + gg];
    const int slot = (c & 3) * 2 + (ln >> 4), dw = (c >> 2) * 16 + (ln & 15);
    uint32_t hv = 0, kv = 0, res = 0, rs2 = 0;
    uint32_t* o = p.out;
    if (warp == 0) {
      hv = ~0u;
      SPIN_WHILE(max(hv, kv) == ~0u, hv = ldr32((const uint32_t*)p.s->HS + 2304 + slot * 288 + dw); kv = ldr32(&p.s->HS[1152 + slot]));
      const float r = bf_hi(kv ^ (((int)~kv >> 31) | 0x80000000u));
      float rs;
      asm("rcp.approx.ftz.f32 %0, %1;" : "=f"(rs) : "f"(1.f + ex2(r * -1.4426950408889634f)));
      rs2 = keep(pack_bf(rs, rs));
      res = lds32(OFF_XS + slot * 1168 + dw * 4);
      o += (2047 - (int)(kv & 2047u)) * 288 + dw;
      asm volatile("" : "+l"(o));
    }
    const uint32_t sel = (gg & 1) ? 0x3F800000u : 0x00003F80u;
    const uint32_t q0 = keep((gg >> 1) == 0 ? sel : 0u), q1 = keep((gg >> 1) == 1 ? sel : 0u), q2 = keep((gg >> 1) == 2 ? sel : 0u), q3 = keep((gg >> 1) == 3 ? sel : 0u);
    const uint32_t fa = keep(OFF_RED + warp * 8 + ((gg & 1) * 16 + (gg >> 1) * 4 + tt) * 144), fb = keep(OFF_RED + ln * 144);
    uint4 a0 = make_uint4(0, 0, 0, 0), a1 = a0;
    while ((int)(clock() - tpub) < X_PD) {}
    SPIN_WHILE(!(a0.x & a1.x & 0x10000u), if (!(a0.x & 0x10000u)) a0 = ldr128(src); if (!(a1.x & 0x10000u)) a1 = ldr128(src + 64 * DM * 2));
    float d[4] = {0.f, 0.f, 0.f, 0.f}, e[4] = {0.f, 0.f, 0.f, 0.f}, d2[4] = {0.f, 0.f, 0.f, 0.f}, e2[4] = {0.f, 0.f, 0.f, 0.f};
    mma_bf16(d, q0, q2, q1, q3, a0.x, a0.y); mma_bf16(e, q0, q2, q1, q3, a0.z, a0.w);
    mma_bf16(d2, q0, q2, q1, q3, a1.x, a1.y); mma_bf16(e2, q0, q2, q1, q3, a1.z, a1.w);
    sts64(fa, __float_as_uint(d[0] + e[2] + d2[0] + e2[2]), __float_as_uint(d[1] + e[3] + d2[1] + e2[3]));
    TS(11);
    if (warp == 0) {
      bar_sync(0, 512);
      float2 s[16];
#pragma unroll
      for (int i = 0; i < 16; i += 2) { const uint4 q = lds128(fb + i * 8); s[i] = make_float2(__uint_as_float(q.x), __uint_as_float(q.y)); s[i + 1] = make_float2(__uint_as_float(q.z), __uint_as_float(q.w)); }
#pragma unroll
      for (int k = 1; k < 16; k *= 2)
#pragma unroll
        for (int i = 0; i < 16; i += 2 * k) { s[i].x += s[i + k].x; s[i].y += s[i + k].y; }
      *o = bf_add2(hv, bf_add2(res, bf_mul2(pack_bf(s[0].x, s[0].y), rs2)));
    } else bar_arrive(0, 512);
  }
  TS(12);
  TS_DUMP();
}

typedef CUresult (*EncodeFn)(CUtensorMap*, CUtensorMapDataType, cuuint32_t, void*, const cuuint64_t*, const cuuint64_t*, const cuuint32_t*,
                             const cuuint32_t*, CUtensorMapInterleave, CUtensorMapSwizzle, CUtensorMapL2promotion, CUtensorMapFloatOOBfill);

}

extern "C" void kernel_launch(void* const* d_in, const int* in_sizes, int n_in, void* d_out, int out_size) {
  (void)in_sizes; (void)n_in; (void)out_size;
  static EncodeFn enc = nullptr;
  static Scratch* scratch = nullptr;
  if (!enc) {
    void* fn = nullptr;
    cudaDriverEntryPointQueryResult qr;
    cudaGetDriverEntryPoint("cuTensorMapEncodeTiled", &fn, cudaEnableDefault, &qr);
    enc = (EncodeFn)fn;
    cudaGetSymbolAddress((void**)&scratch, g_S);
    cudaFuncSetAttribute(fused_kernel<false>, cudaFuncAttributeMaxDynamicSharedMemorySize, SMEM_BYTES);
    cudaFuncSetAttribute(fused_kernel<true>, cudaFuncAttributeMaxDynamicSharedMemorySize, SMEM_BYTES);
  }
  TMaps tm;
  for (int i = 0; i < 6; i++) {
    const bool dn = i % 3 == 2;
    const cuuint32_t w = i < 3 ? 40 : 32;
    cuuint64_t gd[3] = {(cuuint64_t)(dn ? 64 : FF), (cuuint64_t)(dn ? FF : DM), 9};
    cuuint64_t gs[2] = {(cuuint64_t)(dn ? DM * 2 : FF * 2), 128};
    cuuint32_t bx[3] = {dn ? 64 : w, dn ? w : 96, i < 3 ? 2u : 3u};
    cuuint32_t es[3] = {1, 1, 1};
    enc(&tm.m[i], CU_TENSOR_MAP_DATA_TYPE_BFLOAT16, dn ? 3 : 2, d_in[11 + i % 3], gd, gs, bx, es, CU_TENSOR_MAP_INTERLEAVE_NONE,
        dn ? CU_TENSOR_MAP_SWIZZLE_128B : i < 3 ? CU_TENSOR_MAP_SWIZZLE_NONE : CU_TENSOR_MAP_SWIZZLE_64B,
        (CUtensorMapL2promotion)X_PROMO, CU_TENSOR_MAP_FLOAT_OOB_FILL_NONE);
  }
  for (int i = 6; i < 10; i++) {
    cuuint64_t gd[3] = {i < 8 ? 32u : 16u, i < 8 ? DM / 2u : DM, NCTA};
    cuuint64_t gs[2] = {i < 8 ? 64u : 32u, DM * 32};
    cuuint32_t bx[3] = {32, 1, (i & 1) ? 128u : 136u};
    cuuint32_t es[3] = {1, 1, 1};
    enc(&tm.m[i], CU_TENSOR_MAP_DATA_TYPE_FLOAT16, 3, scratch->X, gd, gs, bx, es, CU_TENSOR_MAP_INTERLEAVE_NONE, CU_TENSOR_MAP_SWIZZLE_64B,
        CU_TENSOR_MAP_L2_PROMOTION_NONE, CU_TENSOR_MAP_FLOAT_OOB_FILL_NONE);
  }
  Params p;
  p.x = (const unsigned char*)d_in[0];
  bool far = false;
  for (int i = 0; i < 7; i++) {
    p.far[i] = (const unsigned char*)d_in[1 + i];
    const long long d = (long long)((intptr_t)d_in[1 + i] - (intptr_t)d_in[0]);
    p.off[i] = (int)(d / 16);
    if ((long long)p.off[i] * 16 != d || p.off[i] > (1 << 30)) far = true;
  }
  p.dskip = (const uint16_t*)d_in[8];
  p.w_r = (const uint32_t*)d_in[10];
  for (int f = 0; f < 2; f++) {
    static const int kind[17] = {0, 0, 0, 0, 2, 2, 0, 0, 1, 1, 1, 1, 1, 1, 2, 2, 2};
    static const int idx[2][17] = {{2, 3, 4, 5, 6, 8, 0, 1, 0, 1, 2, 3, 4, 5, 0, 2, 4}, {2, 3, 4, 5, 0, -1, 0, 1, 0, 1, 2, 3, 4, 5, 3, -1, 6}};
    static const int blk[2][17] = {{-1, -1, -1, -1, 0, -1, 4, -1, 1, -1, 2, -1, 3, -1, 16, -1, -1}, {-1, -1, -1, -1, 1, -1, 4, -1, -1, -1, 2, -1, 3, -1, 16, -1, -1}};
    const int pitch = f ? 64 : 80;
    for (int u = 0; u < 17; u++) {
      const int s = idx[f][u];
      const uint32_t dst = kind[u] == 0 ? OFF_G + s * 96 * pitch : kind[u] == 2 ? down_box(s, f) : OFF_W + W_BYTES + (s >> 1) * W_BYTES + (s & 1) * 96 * pitch;
      const uint32_t mb = u >= 14 ? (u >= X_HU ? MB_H - OFF_MISC : 0) : blk[f][u] >= 0 ? MB_KF - OFF_MISC + blk[f][u] * 8 : 0;
      p.sched[f][u] = s < 0 ? 3u : kind[u] | s << 2 | mb << 6 | dst << 14;
    }
  }
  p.out = (uint32_t*)d_out;
  p.off[7] = 0;
  p.ts = nullptr;
  p.s = scratch;
  if (far) { fused_kernel<true><<<NCTA, NT, SMEM_BYTES, cudaStreamPerThread>>>(p, tm); return; }
  fused_kernel<false><<<NCTA, NT, SMEM_BYTES, cudaStreamPerThread>>>(p, tm);
}
```

```cpp
#include <cuda_runtime.h>
#include <cuda.h>
#include <cuda_bf16.h>
#include <cuda_fp16.h>
#include <stdint.h>
#include <stddef.h>

namespace {

constexpr int NCTA = 128;
constexpr int NT = 640;
constexpr int DM = 576;
constexpr int FF = 4608;
constexpr int SPIN_MAX = 1 << 20;

struct Scratch {
  uint4 X[NCTA * DM * 2];
  uint4 KX[64 * 128];
  uint4 HS[1152 + 8];
  uint4 R[256];
  uint4 SC[256];
  uint32_t FLAG[NCTA * 8];
};
__device__ Scratch g_S;

#define CLKS(i)
#define TS(i)
#define TSX(i)
#define TS_DUMP()

constexpr int SB = 1024;
constexpr int BOX = 15360;
constexpr int OFF_G = SB;
constexpr int OFF_W = OFF_G + 3 * BOX;
constexpr int W_KT = 26624;
constexpr int W_QT = W_KT + 64 + 2048 + 80;
constexpr int W_L3 = W_KT + 4352;
constexpr int W_CW = W_L3 + 4160;
constexpr int W_MISC = W_CW + 640;
constexpr int W_BYTES = 35840;
constexpr int TILE = 10240;
constexpr int OFF_T = OFF_W + 4 * W_BYTES;
constexpr int ALT = TILE - W_KT;
static_assert(W_MISC + 32 <= W_BYTES && OFF_W % 1024 == 0 && W_BYTES % 1024 == 0 && W_BYTES + ALT <= 20480, "wg block");
constexpr int YT_PITCH = 1184;
constexpr int OFF_YT = OFF_T + 2 * TILE;
constexpr int OFF_WR = OFF_YT + 16 * YT_PITCH + 64;
constexpr int OFF_MISC = OFF_WR + 2304;
constexpr int SMEM_BYTES = OFF_MISC + 1024 - SB;
static_assert(OFF_YT % 16 == 0 && OFF_MISC % 16 == 0, "align");
static_assert(SMEM_BYTES <= 232448, "smem");
constexpr int MB_GU = OFF_MISC;
constexpr int MB_D = OFF_MISC + 8;
constexpr int MB_KF = OFF_MISC + 16;
constexpr int MB_GF = OFF_MISC + 48;
constexpr int MB_SC = OFF_MISC + 56;
constexpr int MB_UL = OFF_MISC + 64;
constexpr int MB_REL = OFF_MISC + 104;
constexpr int MB_GO = OFF_MISC + 112;
constexpr int MB_H = MB_KF + 128;
constexpr int MISC_EPOCH = OFF_MISC + 152;
constexpr int MISC_SW = OFF_MISC + 156;
constexpr int MISC_RT = OFF_MISC + 160;
constexpr int MISC_T0 = OFF_MISC + 296;
constexpr int MISC_EM = OFF_MISC + 288;
constexpr int OFF_PART = OFF_W + 20480;
constexpr int OFF_RK = OFF_PART + 3840;
constexpr int MISC_LN1 = OFF_MISC + 192;
constexpr int OFF_XS = OFF_T;
constexpr int OFF_RED = OFF_T + TILE;
constexpr int OFF_FIN = OFF_W + 3 * W_BYTES + W_KT;
constexpr int OFF_ACT = OFF_FIN + 4096;
constexpr int MISC_CNT = OFF_ACT + 1024;

__device__ __forceinline__ uint32_t smem_u32(const void* p) { return (uint32_t)__cvta_generic_to_shared(p); }
__device__ __forceinline__ uint32_t lds32(uint32_t a) { uint32_t v; asm volatile("ld.shared.b32 %0, [%1];" : "=r"(v) : "r"(a) : "memory"); return v; }
__device__ __forceinline__ uint32_t lds16(uint32_t a) { uint16_t v; asm volatile("ld.shared.u16 %0, [%1];" : "=h"(v) : "r"(a) : "memory"); return v; }
__device__ __forceinline__ uint2 lds64(uint32_t a) { uint2 v; asm volatile("ld.shared.v2.b32 {%0,%1}, [%2];" : "=r"(v.x), "=r"(v.y) : "r"(a) : "memory"); return v; }
__device__ __forceinline__ uint4 lds128(uint32_t a) { uint4 v; asm volatile("ld.shared.v4.b32 {%0,%1,%2,%3}, [%4];" : "=r"(v.x), "=r"(v.y), "=r"(v.z), "=r"(v.w) : "r"(a) : "memory"); return v; }
__device__ __forceinline__ void sts16(uint32_t a, uint32_t v) { asm volatile("st.shared.u16 [%0], %1;" :: "r"(a), "h"((uint16_t)v) : "memory"); }
__device__ __forceinline__ void sts32(uint32_t a, uint32_t v) { asm volatile("st.shared.b32 [%0], %1;" :: "r"(a), "r"(v) : "memory"); }
__device__ __forceinline__ void sts64(uint32_t a, uint32_t x, uint32_t y) { asm volatile("st.shared.v2.b32 [%0], {%1,%2};" :: "r"(a), "r"(x), "r"(y) : "memory"); }
__device__ __forceinline__ void sts128(uint32_t a, uint32_t x, uint32_t y, uint32_t z, uint32_t w) { asm volatile("st.shared.v4.b32 [%0], {%1,%2,%3,%4};" :: "r"(a), "r"(x), "r"(y), "r"(z), "r"(w) : "memory"); }
__device__ __forceinline__ void ldsm4(uint32_t a, uint32_t& r0, uint32_t& r1, uint32_t& r2, uint32_t& r3) {
  asm volatile("ldmatrix.sync.aligned.m8n8.x4.shared.b16 {%0,%1,%2,%3}, [%4];" : "=r"(r0), "=r"(r1), "=r"(r2), "=r"(r3) : "r"(a) : "memory");
}
__device__ __forceinline__ void ldsm4t(uint32_t a, uint32_t& r0, uint32_t& r1, uint32_t& r2, uint32_t& r3) {
  asm volatile("ldmatrix.sync.aligned.m8n8.x4.trans.shared.b16 {%0,%1,%2,%3}, [%4];" : "=r"(r0), "=r"(r1), "=r"(r2), "=r"(r3) : "r"(a) : "memory");
}
__device__ __forceinline__ void stsm4t(uint32_t a, uint32_t r0, uint32_t r1, uint32_t r2, uint32_t r3) {
  asm volatile("stmatrix.sync.aligned.m8n8.x4.trans.shared.b16 [%0], {%1,%2,%3,%4};" :: "r"(a), "r"(r0), "r"(r1), "r"(r2), "r"(r3) : "memory");
}
__device__ __forceinline__ uint4 ldr128(const void* p) {
  unsigned long long lo, hi;
  asm volatile("{ .reg .b128 t; ld.relaxed.gpu.global.b128 t, [%2]; mov.b128 {%0, %1}, t; }" : "=l"(lo), "=l"(hi) : "l"(p) : "memory");
  return make_uint4((uint32_t)lo, (uint32_t)(lo >> 32), (uint32_t)hi, (uint32_t)(hi >> 32));
}
__device__ __forceinline__ void str128(void* p, uint32_t x, uint32_t y, uint32_t z, uint32_t w) {
  asm volatile("{ .reg .b128 t; .reg .b64 lo, hi; mov.b64 lo, {%1,%2}; mov.b64 hi, {%3,%4}; mov.b128 t, {lo, hi}; st.relaxed.gpu.global.b128 [%0], t; }"
               :: "l"(p), "r"(x), "r"(y), "r"(z), "r"(w) : "memory");
}
__device__ __forceinline__ uint32_t ldr32(const void* p) { uint32_t v; asm volatile("ld.relaxed.gpu.global.b32 %0, [%1];" : "=r"(v) : "l"(p) : "memory"); return v; }
__device__ __forceinline__ void str32(void* p, uint32_t v) { asm volatile("st.relaxed.gpu.global.b32 [%0], %1;" :: "l"(p), "r"(v) : "memory"); }
__device__ __forceinline__ void str16(void* p, uint32_t v) { asm volatile("st.relaxed.gpu.global.u16 [%0], %1;" :: "l"(p), "h"((uint16_t)v) : "memory"); }
__device__ __forceinline__ void bar_sync(int id, int n) { asm volatile("bar.sync %0, %1;" :: "r"(id), "r"(n) : "memory"); }
__device__ __forceinline__ void bar_arrive(int id, int n) { asm volatile("bar.arrive %0, %1;" :: "r"(id), "r"(n) : "memory"); }

__device__ __forceinline__ float bf_lo(uint32_t w) { return __uint_as_float(w << 16); }
__device__ __forceinline__ float bf_hi(uint32_t w) { return __uint_as_float(w & 0xFFFF0000u); }
__device__ __forceinline__ uint32_t pack_bf(float lo, float hi) { uint32_t r; asm("cvt.rn.bf16x2.f32 %0, %1, %2;" : "=r"(r) : "f"(hi), "f"(lo)); return r; }
__device__ __forceinline__ uint32_t pack_h(float lo, float hi) { uint32_t r; asm("cvt.rn.f16x2.f32 %0, %1, %2;" : "=r"(r) : "f"(hi), "f"(lo)); return r; }
__device__ __forceinline__ float bfr(float x) { return bf_lo(pack_bf(x, 0.f)); }
__device__ __forceinline__ uint32_t bf_sub2(uint32_t a, uint32_t b) { __nv_bfloat162 r = __hsub2(*(__nv_bfloat162*)&a, *(__nv_bfloat162*)&b); return *(uint32_t*)&r; }
__device__ __forceinline__ uint32_t bf_add2(uint32_t a, uint32_t b) { __nv_bfloat162 r = __hadd2(*(__nv_bfloat162*)&a, *(__nv_bfloat162*)&b); return *(uint32_t*)&r; }
__device__ __forceinline__ uint32_t bf_mul2(uint32_t a, uint32_t b) { __nv_bfloat162 r = __hmul2(*(__nv_bfloat162*)&a, *(__nv_bfloat162*)&b); return *(uint32_t*)&r; }
__device__ __forceinline__ float2 h2f(uint32_t w) { return __half22float2(*(__half2*)&w); }
__device__ __forceinline__ float ex2(float x) { float r; asm("ex2.approx.ftz.f32 %0, %1;" : "=f"(r) : "f"(x)); return r; }
__device__ __forceinline__ float warp_sum(float v) {
#pragma unroll
  for (int o = 16; o > 0; o >>= 1) v += __shfl_xor_sync(0xffffffffu, v, o);
  return v;
}
__device__ __forceinline__ void mma_bf16(float* d, uint32_t a0, uint32_t a1, uint32_t a2, uint32_t a3, uint32_t b0, uint32_t b1) {
  asm volatile("mma.sync.aligned.m16n8k16.row.col.f32.bf16.bf16.f32 {%0,%1,%2,%3}, {%4,%5,%6,%7}, {%8,%9}, {%0,%1,%2,%3};"
               : "+f"(d[0]), "+f"(d[1]), "+f"(d[2]), "+f"(d[3]) : "r"(a0), "r"(a1), "r"(a2), "r"(a3), "r"(b0), "r"(b1));
}
__device__ __forceinline__ void mma_bf16_k8(float* d, uint32_t a0, uint32_t a1, uint32_t b0) {
  asm volatile("mma.sync.aligned.m16n8k8.row.col.f32.bf16.bf16.f32 {%0,%1,%2,%3}, {%4,%5}, {%6}, {%0,%1,%2,%3};"
               : "+f"(d[0]), "+f"(d[1]), "+f"(d[2]), "+f"(d[3]) : "r"(a0), "r"(a1), "r"(b0));
}

__device__ __forceinline__ void wg_fence() { asm volatile("wgmma.fence.sync.aligned;" ::: "memory"); }
__device__ __forceinline__ void wg_commit() { asm volatile("wgmma.commit_group.sync.aligned;" ::: "memory"); }
template <int N> __device__ __forceinline__ void wg_wait() { asm volatile("wgmma.wait_group.sync.aligned %0;" :: "n"(N) : "memory"); }
template <int TB> __device__ __forceinline__ void wgmma32(float* d, const uint32_t* a, uint32_t dlo, uint32_t dhi) {
  asm volatile("{ .reg .b64 dd; mov.b64 dd, {%20, %21}; wgmma.mma_async.sync.aligned.m64n32k16.f32.f16.f16 "
               "{%0,%1,%2,%3,%4,%5,%6,%7,%8,%9,%10,%11,%12,%13,%14,%15}, {%16,%17,%18,%19}, dd, 1, 1, 1, %22; }"
               : "+f"(d[0]), "+f"(d[1]), "+f"(d[2]), "+f"(d[3]), "+f"(d[4]), "+f"(d[5]), "+f"(d[6]), "+f"(d[7]), "+f"(d[8]), "+f"(d[9]), "+f"(d[10]), "+f"(d[11]), "+f"(d[12]), "+f"(d[13]), "+f"(d[14]), "+f"(d[15])
               : "r"(a[0]), "r"(a[1]), "r"(a[2]), "r"(a[3]), "r"(dlo), "r"(dhi), "n"(TB));
}
template <int TB> __device__ __forceinline__ void wgmma64(float* d, const uint32_t* a, uint32_t dlo, uint32_t dhi) {
  asm volatile("{ .reg .b64 dd; mov.b64 dd, {%36, %37}; wgmma.mma_async.sync.aligned.m64n64k16.f32.f16.f16 "
               "{%0,%1,%2,%3,%4,%5,%6,%7,%8,%9,%10,%11,%12,%13,%14,%15,%16,%17,%18,%19,%20,%21,%22,%23,%24,%25,%26,%27,%28,%29,%30,%31}, {%32,%33,%34,%35}, dd, 1, 1, 1, %38; }"
               : "+f"(d[0]), "+f"(d[1]), "+f"(d[2]), "+f"(d[3]), "+f"(d[4]), "+f"(d[5]), "+f"(d[6]), "+f"(d[7]), "+f"(d[8]), "+f"(d[9]), "+f"(d[10]), "+f"(d[11]), "+f"(d[12]), "+f"(d[13]), "+f"(d[14]), "+f"(d[15]), "+f"(d[16]), "+f"(d[17]), "+f"(d[18]), "+f"(d[19]), "+f"(d[20]), "+f"(d[21]), "+f"(d[22]), "+f"(d[23]), "+f"(d[24]), "+f"(d[25]), "+f"(d[26]), "+f"(d[27]), "+f"(d[28]), "+f"(d[29]), "+f"(d[30]), "+f"(d[31])
               : "r"(a[0]), "r"(a[1]), "r"(a[2]), "r"(a[3]), "r"(dlo), "r"(dhi), "n"(TB));
}
template <int TB> __device__ __forceinline__ void wgmma64_init(float* d, const uint32_t* a, uint32_t dlo, uint32_t dhi) {
  asm volatile("{ .reg .b64 dd; mov.b64 dd, {%36, %37}; wgmma.mma_async.sync.aligned.m64n64k16.f32.f16.f16 "
               "{%0,%1,%2,%3,%4,%5,%6,%7,%8,%9,%10,%11,%12,%13,%14,%15,%16,%17,%18,%19,%20,%21,%22,%23,%24,%25,%26,%27,%28,%29,%30,%31}, {%32,%33,%34,%35}, dd, 0, 1, 1, %38; }"
               : "=f"(d[0]), "=f"(d[1]), "=f"(d[2]), "=f"(d[3]), "=f"(d[4]), "=f"(d[5]), "=f"(d[6]), "=f"(d[7]), "=f"(d[8]), "=f"(d[9]), "=f"(d[10]), "=f"(d[11]), "=f"(d[12]), "=f"(d[13]), "=f"(d[14]), "=f"(d[15]), "=f"(d[16]), "=f"(d[17]), "=f"(d[18]), "=f"(d[19]), "=f"(d[20]), "=f"(d[21]), "=f"(d[22]), "=f"(d[23]), "=f"(d[24]), "=f"(d[25]), "=f"(d[26]), "=f"(d[27]), "=f"(d[28]), "=f"(d[29]), "=f"(d[30]), "=f"(d[31])
               : "r"(a[0]), "r"(a[1]), "r"(a[2]), "r"(a[3]), "r"(dlo), "r"(dhi), "n"(TB));
}
template <int TB> __device__ __forceinline__ void wgmma32_init(float* d, const uint32_t* a, uint32_t dlo, uint32_t dhi) {
  asm volatile("{ .reg .b64 dd; mov.b64 dd, {%20, %21}; wgmma.mma_async.sync.aligned.m64n32k16.f32.f16.f16 "
               "{%0,%1,%2,%3,%4,%5,%6,%7,%8,%9,%10,%11,%12,%13,%14,%15}, {%16,%17,%18,%19}, dd, 0, 1, 1, %22; }"
               : "=f"(d[0]), "=f"(d[1]), "=f"(d[2]), "=f"(d[3]), "=f"(d[4]), "=f"(d[5]), "=f"(d[6]), "=f"(d[7]), "=f"(d[8]), "=f"(d[9]), "=f"(d[10]), "=f"(d[11]), "=f"(d[12]), "=f"(d[13]), "=f"(d[14]), "=f"(d[15])
               : "r"(a[0]), "r"(a[1]), "r"(a[2]), "r"(a[3]), "r"(dlo), "r"(dhi), "n"(TB));
}
__device__ __forceinline__ void wgmma64h(uint32_t* d, uint32_t a0, uint32_t a1, uint32_t a2, uint32_t a3, uint32_t dlo, uint32_t dhi) {
  asm volatile("{ .reg .b64 dd; mov.b64 dd, {%20, %21}; wgmma.mma_async.sync.aligned.m64n64k16.f16.f16.f16 "
               "{%0,%1,%2,%3,%4,%5,%6,%7,%8,%9,%10,%11,%12,%13,%14,%15}, {%16,%17,%18,%19}, dd, 1, 1, 1, 0; }"
               : "+r"(d[0]), "+r"(d[1]), "+r"(d[2]), "+r"(d[3]), "+r"(d[4]), "+r"(d[5]), "+r"(d[6]), "+r"(d[7]), "+r"(d[8]), "+r"(d[9]), "+r"(d[10]), "+r"(d[11]), "+r"(d[12]), "+r"(d[13]), "+r"(d[14]), "+r"(d[15])
               : "r"(a0), "r"(a1), "r"(a2), "r"(a3), "r"(dlo), "r"(dhi));
}
__device__ __forceinline__ void wgmma64h_init(uint32_t* d, uint32_t a0, uint32_t a1, uint32_t a2, uint32_t a3, uint32_t dlo, uint32_t dhi) {
  asm volatile("{ .reg .b64 dd; mov.b64 dd, {%20, %21}; wgmma.mma_async.sync.aligned.m64n64k16.f16.f16.f16 "
               "{%0,%1,%2,%3,%4,%5,%6,%7,%8,%9,%10,%11,%12,%13,%14,%15}, {%16,%17,%18,%19}, dd, 0, 1, 1, 0; }"
               : "=r"(d[0]), "=r"(d[1]), "=r"(d[2]), "=r"(d[3]), "=r"(d[4]), "=r"(d[5]), "=r"(d[6]), "=r"(d[7]), "=r"(d[8]), "=r"(d[9]), "=r"(d[10]), "=r"(d[11]), "=r"(d[12]), "=r"(d[13]), "=r"(d[14]), "=r"(d[15])
               : "r"(a0), "r"(a1), "r"(a2), "r"(a3), "r"(dlo), "r"(dhi));
}
__device__ __forceinline__ void wgmma40_ss(float* d, uint32_t alo, uint32_t blo, uint32_t hi) {
  asm volatile("{ .reg .b64 da, db; mov.b64 da, {%20, %22}; mov.b64 db, {%21, %22}; "
               "wgmma.mma_async.sync.aligned.m64n40k16.f32.f16.f16 {%0,%1,%2,%3,%4,%5,%6,%7,%8,%9,%10,%11,%12,%13,%14,%15,%16,%17,%18,%19}, da, db, 1, 1, 1, 1, 1; }"
               : "+f"(d[0]), "+f"(d[1]), "+f"(d[2]), "+f"(d[3]), "+f"(d[4]), "+f"(d[5]), "+f"(d[6]), "+f"(d[7]), "+f"(d[8]), "+f"(d[9]), "+f"(d[10]), "+f"(d[11]), "+f"(d[12]), "+f"(d[13]), "+f"(d[14]), "+f"(d[15]), "+f"(d[16]), "+f"(d[17]), "+f"(d[18]), "+f"(d[19])
               : "r"(alo), "r"(blo), "r"(hi));
}
__device__ __forceinline__ void wgmma40_ss_init(float* d, uint32_t alo, uint32_t blo, uint32_t hi) {
  asm volatile("{ .reg .b64 da, db; mov.b64 da, {%20, %22}; mov.b64 db, {%21, %22}; "
               "wgmma.mma_async.sync.aligned.m64n40k16.f32.f16.f16 {%0,%1,%2,%3,%4,%5,%6,%7,%8,%9,%10,%11,%12,%13,%14,%15,%16,%17,%18,%19}, da, db, 0, 1, 1, 1, 1; }"
               : "=f"(d[0]), "=f"(d[1]), "=f"(d[2]), "=f"(d[3]), "=f"(d[4]), "=f"(d[5]), "=f"(d[6]), "=f"(d[7]), "=f"(d[8]), "=f"(d[9]), "=f"(d[10]), "=f"(d[11]), "=f"(d[12]), "=f"(d[13]), "=f"(d[14]), "=f"(d[15]), "=f"(d[16]), "=f"(d[17]), "=f"(d[18]), "=f"(d[19])
               : "r"(alo), "r"(blo), "r"(hi));
}
__device__ __forceinline__ void tma_box(uint32_t dst, const CUtensorMap* tm, uint32_t mb, int x, int y) {
  asm volatile("cp.async.bulk.tensor.2d.shared::cluster.global.mbarrier::complete_tx::bytes [%0], [%1, {%3, %4}], [%2];"
               :: "r"(dst), "l"(tm), "r"(mb), "r"(x), "r"(y) : "memory");
}
__device__ __forceinline__ uint32_t uni(uint32_t v) {
  uint32_t r; asm volatile("shfl.sync.idx.b32 %0, %1, 0, 0x1f, 0xffffffff;" : "=r"(r) : "r"(v)); return r;
}
__device__ __forceinline__ uint32_t pin(uint32_t v) {
  uint32_t r; asm volatile("shfl.sync.bfly.b32 %0, %1, 0, 0x1f, 0xffffffff;" : "=r"(r) : "r"(v)); return r;
}

struct Params {
  const unsigned char* x;
  Scratch* s;
  int off[8];
  uint32_t* out;
  const uint16_t* dskip;
  const uint32_t* w_r;
  long long* ts;
  const unsigned char* far[7];
  uint32_t sched[2][17];
};
__device__ __forceinline__ uint32_t ldnc32(const void* p) { uint32_t v; asm volatile("ld.global.nc.b32 %0, [%1];" : "=r"(v) : "l"(p)); return v; }
__device__ __forceinline__ uint32_t ldnc16(const void* p) { uint16_t v; asm volatile("ld.global.nc.u16 %0, [%1];" : "=h"(v) : "l"(p)); return v; }
__device__ __forceinline__ void mbar_wait(uint32_t mb, uint32_t ph = 0) {
#pragma unroll 1
  for (int it = 0; it < SPIN_MAX; it++) {
    uint32_t ok;
    asm volatile("{ .reg .pred q; mbarrier.try_wait.parity.shared::cta.b64 q, [%1], %2; selp.u32 %0, 1, 0, q; }" : "=r"(ok) : "r"(mb), "r"(ph) : "memory");
    if (ok) break;
  }
}
__device__ __forceinline__ void mbar_arrive(uint32_t mb) { asm volatile("mbarrier.arrive.shared::cta.b64 _, [%0];" :: "r"(mb) : "memory"); }
__device__ __forceinline__ void fence_async() { asm volatile("fence.proxy.async.shared::cta;" ::: "memory"); }
#define SPIN_WHILE(cond, body) _Pragma("unroll 1") for (int _it = 0; _it < SPIN_MAX && __any_sync(0xffffffffu, (cond)); _it++) { body; }

struct LnC { uint32_t m2, rh2, rl2; };
__device__ __forceinline__ LnC ln_consts(float s, float q, float& r) {
  const float mean = s * (1.f / DM);
  const float var = fmaxf(fmaf(-mean, mean, q * (1.f / DM)), 0.f);
  float sd;
  asm("sqrt.approx.ftz.f32 %0, %1;" : "=f"(sd) : "f"(bfr(bfr(var) + 1e-5f)));
  asm("rcp.approx.ftz.f32 %0, %1;" : "=f"(r) : "f"(bfr(sd)));
  LnC c;
  c.m2 = pack_bf(mean, mean);
  c.rh2 = pack_bf(r, r);
  const float rl = r - bf_lo(c.rh2);
  c.rl2 = pack_bf(rl, rl);
  return c;
}
__device__ __forceinline__ uint32_t bf_fma2(uint32_t a, uint32_t b, uint32_t c) {
  __nv_bfloat162 r = __hfma2(*(const __nv_bfloat162*)&a, *(const __nv_bfloat162*)&b, *(const __nv_bfloat162*)&c);
  return *(uint32_t*)&r;
}
__device__ __forceinline__ uint32_t ln_apply(uint32_t w, uint32_t m2, uint32_t rh2, uint32_t rl2) {
  const uint32_t d = bf_sub2(w, m2);
  return bf_fma2(d, rh2, bf_mul2(d, rl2));
}

__device__ __forceinline__ float2 cis(float mag_log2, float rev) {
  const float m = ex2(mag_log2), ang = rev * 6.283185307179586f;
  return make_float2(m * __cosf(ang), m * __sinf(ang));
}
__device__ __forceinline__ float2 csq(float2 a) { return make_float2(fmaf(a.x, a.x, -a.y * a.y), (a.x + a.x) * a.y); }
__device__ __forceinline__ float2 cmul(float2 a, float2 b) { return make_float2(fmaf(a.x, b.x, -a.y * b.y), fmaf(a.x, b.y, a.y * b.x)); }
__device__ __forceinline__ void pmul(uint32_t xr, uint32_t xi, uint32_t w, uint32_t& yr, uint32_t& yi) {
  const __half2 XR = *(__half2*)&xr, XI = *(__half2*)&xi, W = *(__half2*)&w;
  const __half2 a = __hfma2(__hneg2(XI), __high2half2(W), __hmul2(XR, __low2half2(W)));
  const __half2 b = __hfma2(XI, __low2half2(W), __hmul2(XR, __high2half2(W)));
  yr = *(const uint32_t*)&a; yi = *(const uint32_t*)&b;
}
__device__ __forceinline__ uint32_t pk(float2 a) { return pack_h(a.x, a.y); }

struct KgState { float2 c0, z8; float kl; uint32_t w64, w128, w192; };
__device__ __forceinline__ void kgen_tables_n(const uint32_t (&raw)[7], uint32_t scr, int wt, KgState& k) {
  const uint32_t dst = scr + 16384 + wt * 16;
  const float dt = bfr(ex2(bf_lo(raw[6]) * 1.4426950408889634f));
  const float th = dt * bf_lo(raw[1]);
  const float br = dt * bf_lo(raw[2]), bi = dt * bf_lo(raw[3]);
  const float Cr = bf_lo(raw[4]), Ci = bf_lo(raw[5]);
  k.c0 = make_float2(fmaf(Cr, br, -Ci * bi), fmaf(Cr, bi, Ci * br));
  const uint32_t mx = __reduce_max_sync(0xffffffffu, __float_as_uint(fmaxf(fabsf(k.c0.x), fabsf(k.c0.y))));
  const float a2 = dt * bf_lo(raw[0]) * 1.4426950408889634f;
  const float rh = th * 0.15915494309189535f;
  const float rl = fmaf(th, (float)(0.15915494309189535 - (double)0.15915494309189535f), fmaf(th, 0.15915494309189535f, -rh));
  const float rf = rh - rintf(rh);
  const float2 z1 = cis(a2, rf + rl);
  const float p64 = rf * 64.f;
  const float2 z64 = cis(a2 * 64.f, fmaf(64.f, rl, p64 - rintf(p64)));
  const float2 z2 = csq(z1), z128 = csq(z64), z3 = cmul(z2, z1), z4 = csq(z2), z256 = csq(z128), z6 = csq(z3), z512 = csq(z256);
  k.z8 = csq(z4);
  k.w64 = pk(z64); k.w128 = pk(z128); k.w192 = pk(cmul(z128, z64));
  sts128(dst, 0x00003C00u, pk(z2), pk(z4), pk(z6));
  const float2 z1024 = csq(z512), z768 = cmul(z512, z256);
  sts128(dst + 2048, pk(z1), pk(z3), pk(cmul(z4, z1)), pk(cmul(z4, z3)));
  const float2 z2048 = csq(z1024);
  k.kl = fmaf(k.c0.x, z2048.x, -k.c0.y * z2048.y);
  sts128(dst + 4096, pk(z256), pk(cmul(z256, z2)), pk(cmul(z256, z4)), pk(cmul(z256, z6)));
  sts128(dst + 6144, pk(z512), pk(cmul(z512, z4)), pk(z768), pk(cmul(z768, z4)));
  sts128(dst + 8192, pk(z1024), pk(cmul(z1024, z256)), pk(cmul(z1024, z512)), pk(cmul(z1024, z768)));
  sts32(scr + W_MISC + (wt >> 5) * 4, mx);
}
__device__ __forceinline__ int kgen_tables_m(uint32_t scr, int wt, const KgState& k) {
  const uint32_t dst = scr + wt * 16;
  const uint4 e4 = lds128(scr + W_MISC);
  const float2 z16 = csq(k.z8), z32 = csq(z16);
  const int em = max(min((int)(max(max(e4.x, e4.y), max(e4.z, e4.w)) >> 23), 238), 16);
  const float sc = __uint_as_float((uint32_t)(127 + 4 + 127 - em) << 23);
  sts32(scr + W_MISC + 16 + (wt >> 5) * 4, __reduce_add_sync(0xffffffffu, __float2int_rn(k.kl * sc * 262144.f)));
  const float2 c0 = make_float2(k.c0.x * sc, k.c0.y * sc);
  const float2 c1 = cmul(c0, k.z8), c2 = cmul(c0, z16), c4 = cmul(c0, z32), c3 = cmul(c1, z16), c5 = cmul(c1, z32), c6 = cmul(c2, z32), c7 = cmul(c3, z32);
  uint32_t pr[4], pi[4], yr[4], yi[4];
  pr[0] = pack_h(c0.x, c1.x); pi[0] = pack_h(c0.y, c1.y);
  pr[1] = pack_h(c2.x, c3.x); pi[1] = pack_h(c2.y, c3.y);
  pr[2] = pack_h(c4.x, c5.x); pi[2] = pack_h(c4.y, c5.y);
  pr[3] = pack_h(c6.x, c7.x); pi[3] = pack_h(c6.y, c7.y);
  sts128(dst, pr[0], pr[1], pr[2], pr[3]); sts128(dst + 2048, pi[0], pi[1], pi[2], pi[3]);
#pragma unroll
  for (int q = 1; q < 4; q++) {
    const uint32_t w = q == 1 ? k.w64 : q == 2 ? k.w128 : k.w192;
#pragma unroll
    for (int i = 0; i < 4; i++) pmul(pr[i], pi[i], w, yr[i], yi[i]);
    sts128(dst + q * 4096, yr[0], yr[1], yr[2], yr[3]); sts128(dst + q * 4096 + 2048, yi[0], yi[1], yi[2], yi[3]);
  }
  return em;
}
__device__ __forceinline__ uint32_t lds32_if(uint32_t a, bool on) {
  uint32_t v; asm volatile("{ .reg .pred q; setp.ne.u32 q, %2, 0; mov.b32 %0, 0; @q ld.shared.b32 %0, [%1]; }" : "=r"(v) : "r"(a), "r"((uint32_t)on) : "memory"); return v;
}
__device__ __forceinline__ uint32_t prmt(uint32_t a, uint32_t b, uint32_t s) { uint32_t r; asm("prmt.b32 %0, %1, %2, %3;" : "=r"(r) : "r"(a), "r"(b), "r"(s)); return r; }
__device__ __forceinline__ void kgen_build(uint32_t tb, int wg, int wt, uint32_t k0, uint32_t k1, uint32_t k2) {
  const uint32_t kt = tb + W_KT, sc = tb + W_L3 + 3072;
  const int ix = ((wt >> 2) + (wt & 3) * 32 - 1) & 127;
  const uint32_t a3 = tb + W_CW + 32 + ((ix & 1) ? 0 : 304) + (ix >> 1) * 4, a2 = sc + 544 + (wt & ~3) * 2 + (wt & 1) * 4 + (wt & 2) * 128;
  const uint32_t v3 = wt ? k2 : k2 >> 16;
  sts32(sc + 4 + wt * 4, __byte_perm(k0, k1, 0x5432));
  sts16(a2, k1 >> 16); sts16(a2 + 6, k1 >> 16);
  sts16(a3, v3); sts16(a3 + 6, v3);
  if ((unsigned)(wt - 32) < 14u) sts128(kt + (wt < 36 ? -512 : 64 + 4128 - 576) + wt * 16, 0, 0, 0, 0);
  if (wt == 127) sts32(sc, k0 & 0xFFFF0000u);
  if (wt == 0) { sts32(sc + 516, k1); sts16(sc + 1056, k2); }
  bar_sync(1 + wg, 128);
  const uint32_t cw = tb + W_CW + 32 + (wt >> 6) * 48 + wt * 4, g2 = sc + 540 + wt * 4;
  const bool odd = wt & 1, ends = (unsigned)(wt - 4) >= 120u;
  const uint32_t pv = lds32(sc + wt * 4), nx = lds32(sc + 8 + wt * 4), nc = lds32_if(g2 + 8, ends);
  const uint32_t l0 = lds32(cw), l1 = lds32(cw - 8), l2 = lds32(cw - 16), l3 = lds32(cw - 24), q0 = lds32(g2), q1 = lds32(g2 + 128), q2 = lds32(g2 - 8), q3 = lds32(g2 + 120);
  sts64(kt + 64 + wt * 8, __byte_perm(k0, pv, 0x5410), __byte_perm(k0, 0, 0x1032));
  sts64(kt + 64 + 1024 + wt * 8, __byte_perm(k1, pv, (odd || wt == 0) ? 0x7610 : 0x1010), __byte_perm(k1, nx, odd ? 0x1076 : 0x1010));
  const uint32_t cc = __byte_perm(nc, 0, 0x3232), nn = __byte_perm(nc, 0, 0x1010);
  if (ends) sts128(kt + 64 + 2048 + wt * 16, cc, cc, odd ? nc : cc, odd ? nn : nc);
  if (wt == 127) { sts128(kt + 64 + 4096, nn, nn, nn, nn); sts128(kt + 64 + 4112, nn, nn << 16, 0, 0); }
  sts128(tb + W_L3 + 512 + (wt >> 6) * 512 + wt * 16, l0, l1, l2, l3);
  if ((wt & 63) < 34) sts128(tb + W_QT - 16 + wt * 16, q0, q1, q2, q3);
}

__device__ __forceinline__ void load_a(uint32_t (&a)[4], uint32_t kp, int j) {
  a[0] = lds32(kp + 64 * j); a[1] = lds32(kp + 64 * j + 512); a[2] = lds32(kp + 64 * j - 32); a[3] = lds32(kp + 64 * j + 480);
}
__device__ __forceinline__ uint32_t band(int d, int lo, int hi) {
  return ((unsigned)(d - lo) <= (unsigned)(hi - lo) ? 1u : 0u) | ((unsigned)(d - 1 - lo) <= (unsigned)(hi - lo) ? 0x10000u : 0u);
}
__device__ __forceinline__ uint32_t hadd2u(uint32_t a, uint32_t b) { __half2 r = __hadd2(*(__half2*)&a, *(__half2*)&b); return *(uint32_t*)&r; }

__device__ __forceinline__ void zero_pads(uint32_t tb, int wt) {
  if (!(wt & 32)) sts128(tb + W_L3 + (wt >> 6) * 512 + wt * 16, 0, 0, 0, 0);
  if ((wt & 63) < 3) sts128(tb + W_CW + (wt >> 6) * 304 + (wt & 63) * 16, 0, 0, 0, 0);
}
__device__ __forceinline__ uint32_t tr_base(int lane) {
  return OFF_YT + (2 * (lane >> 3) + (lane & 1)) * YT_PITCH + ((lane >> 1) & 1) * (8 * YT_PITCH + 64) + ((lane >> 2) & 1) * 16;
}

__device__ __forceinline__ uint32_t sc_addr(int tp) { return OFF_YT + (tp < 16 ? tp * YT_PITCH + (tp >> 3) * 64 + 1152 : 8 * YT_PITCH - 512 + tp * 32); }
#define X_PW 15
#define X_HU 16
#define X_NE 2
#define X_SCT 10000
#define X_DELTA 0
#define X_DSTEP 2000
#define X_PF0 2500
#define X_PFD 600
#define X_TD 450
#define X_WS 6
#define X_OR 8
#define X_ABS 4950
#define X_XD 200
#define X_RD 630
#define X_HD 450
#define X_PD 1170
#define X_PROMO 2
#define X_YD2 1000
#define X_GO 1
#define X_GW 2
#define X_NS 4300
#define X_XS 13450
#define X_LAG 1500
#define X_YD 1550
struct TMaps { CUtensorMap m[10]; };
__device__ __forceinline__ uint32_t h2bf(uint32_t w) { const float2 f = h2f(w); return pack_bf(f.x, f.y); }
__device__ __forceinline__ uint32_t keep(uint32_t v) { asm volatile("" : "+r"(v)); return v; }
__device__ __forceinline__ uint2 ldr64(const void* p) { uint2 v; asm volatile("{ .reg .b64 t; ld.relaxed.gpu.global.b64 t, [%2]; mov.b64 {%0, %1}, t; }" : "=r"(v.x), "=r"(v.y) : "l"(p) : "memory"); return v; }
__host__ __device__ __forceinline__ uint32_t down_box(int s, bool five) {
  return five ? OFF_W + W_BYTES + 12288 + (s / 3) * (W_BYTES - 12288) + s * 4096 : s < 6 ? OFF_W + W_BYTES + BOX + (s >> 1) * (W_BYTES - 10240) + s * 5120 : OFF_W + (s - 6) * 5120;
}
__device__ __forceinline__ void load_tile(const CUtensorMap* tmx, int i, int c, int again = 0) {
  asm volatile("mbarrier.arrive.expect_tx.shared::cta.b64 _, [%0], 8704;" :: "r"(MB_UL + i * 16 + again) : "memory");
  asm volatile("cp.async.bulk.tensor.3d.shared::cluster.global.mbarrier::complete_tx::bytes [%0], [%1, {%3, %4, %5}], [%2];"
               :: "r"(i < 2 ? OFF_T + i * TILE : OFF_W), "l"(tmx), "r"(MB_UL + i * 16 + again), "r"(0), "r"(c), "r"(-8) : "memory");
}
template <bool FAR> __device__ __forceinline__ void load_params(const Params& p, uint32_t ch, int wt, uint32_t dst, bool on) {
  const int rel = wt < 96 ? ch * 16 + (wt & 15) : ch >> 3;
  const unsigned char* b = FAR ? p.far[min(wt >> 4, 6)] + rel * 16 : p.x + (long long)(p.off[wt >> 4] + rel) * 16;
  asm volatile("{ .reg .pred q; setp.ne.u32 q, %2, 0; @q cp.async.cg.shared.global [%0], [%1], 16; }"
               :: "r"(dst + wt * 16), "l"(b), "r"((uint32_t)(on && wt < 97)) : "memory");
}

struct ConvC { uint32_t ca, cb, bands, qa; };
__device__ __forceinline__ ConvC conv_consts(int w, int lane) {
  const int h = w & 1, P = (w >> 1) & 1, d0 = 8 * h + (lane >> 2) - 2 * (lane & 3);
  ConvC k;
  k.ca = keep((W_KT + (16 + 256 * P + d0) * 4) | (((8 + 64 * P + lane) * 64 + (((h + ((w >> 1) & 2)) ^ (lane >> 1)) & 3) * 16) << 16));
  const int u = d0 + 2 * (lane & 1) + 2, in = (u & 7) - ((u & 7) >= 5 ? 5 : 0) - 2 * (lane & 1);
  k.cb = keep(in > 0 ? 0x1010 : in == 0 ? 0x3210 : 0x3232);
  k.qa = keep(W_QT + (2 * (u >> 3) + ((u & 7) >= 5) + 64 * P) * 16);
  k.bands = keep(band(d0, 12, 20) + 2 * band(d0 + 8, 12, 20) + 4 * band(d0 + 16, 12, 20) + 8 * band(d0 + 24, 12, 20)
                 + 16 * band(d0 - 8, 5, 11) + 32 * band(d0, 5, 11) + 64 * band(d0 + 8, 5, 11) + 128 * band(d0 + 16, 5, 11));
  return k;
}
struct ConvPre { uint32_t e0, e2, f2, b0, b2, a[3][4]; };
__device__ __forceinline__ void conv_pre(ConvPre& r, uint32_t kp, uint32_t qp, int part, bool on, bool P) {
  if (part & 1) {
    r.e0 = lds32_if(kp + 4096, on && !P); r.e2 = lds32_if(kp + 4064, on && !P); r.f2 = lds32_if(kp + 4128, on && !P);
    r.b0 = lds32_if(kp + 2048, on && !P); r.b2 = lds32_if(kp + 2016, on && !P);
  }
#pragma unroll
  for (int j = 0; j < 3; j++) if (part & (j < 1 ? 1 : 2))
    asm volatile("{ .reg .pred q; setp.ne.u32 q, %5, 0; mov.b32 %0, 0; mov.b32 %1, 0; mov.b32 %2, 0; mov.b32 %3, 0; @q ld.shared.v4.b32 {%0,%1,%2,%3}, [%4]; }"
                 : "=r"(r.a[j][0]), "=r"(r.a[j][1]), "=r"(r.a[j][2]), "=r"(r.a[j][3]) : "r"(qp + 64 * j), "r"((uint32_t)on) : "memory");
}
__device__ __forceinline__ void conv_item(uint32_t tb, uint32_t tl, int bid, int bn, ConvPre& pre, const ConvC& cv, uint32_t zero, const CUtensorMap* tmx, int ch, int warp, int lane, bool hold, bool more) {
  const bool go = more && warp == 0 && lane == 0;
  const uint32_t kp = tb + (cv.ca & 0xFFFFu), qp = tb + cv.qa;
  const uint32_t dlo = (tl >> 4) + 32 + ((warp >> 1) & 2) + (1u << 16), dhi = 32u | (2u << 30);
  const bool P = warp & 2;
  float a32[16], b32[16], a64[32];
  uint32_t A[40][4];
#define STEP(J) { wgmma64<0>(a64, A[J], dlo + 256 - 4 * (J), dhi); \
    if ((J) == 32) wgmma32_init<0>(b32, A[J], dlo, dhi); else wgmma32<0>(b32, A[J], ((J) < 8 ? dlo ^ zero : dlo) + 128 - 4 * (J), dhi); \
    if ((J) == 0) wgmma32_init<0>(a32, A[J], dlo, dhi); else if ((J) < 8) wgmma32<0>(a32, A[J], (dlo ^ zero) - 4 * (J), dhi); }
#define LD(J) load_a(A[J], kp, J);
#define LQ(J) { const uint4 v = lds128(qp + 64 * ((J) - 32)); A[J][0] = v.x; A[J][1] = v.y; A[J][2] = v.z; A[J][3] = v.w; }
#define PQ(J) { A[J][0] = prmt(A[J][0], 0, cv.cb); A[J][1] = prmt(A[J][1], 0, cv.cb); A[J][2] = prmt(A[J][2], 0, cv.cb); A[J][3] = prmt(A[J][3], 0, cv.cb); }
#define FIRST(J) wg_fence(); STEP(J) wg_commit(); wg_wait<1>(); wg_fence();
  {
    uint32_t win[16], x9[4], x7[4], e[4], f[4];
    const uint32_t bz = keep(cv.bands);
#define BAND(i) keep((bz & (0x10001u << (i))) * (0x3C00u >> (i)))
    e[0] = pre.e0; e[2] = pre.e2; e[1] = keep(bz & 0x100u); e[3] = keep(bz & 0x200u);
    f[2] = pre.f2; f[0] = keep(bz & 0x4000u); f[1] = keep(bz & 0x8000u); f[3] = keep(bz & 0x300u);
#pragma unroll
    for (int j = 0; j < 12; j++) A[32 + j / 4][j & 3] = pre.a[j / 4][j & 3];
    PQ(32) PQ(33) PQ(34)
    if (!P) { A[32][0] = pre.b0; A[32][2] = pre.b2; }
    const uint32_t q[12] = {BAND(0), BAND(5), keep(bz & 0x400u), BAND(4), BAND(2), BAND(7), BAND(1), BAND(6), keep(bz & 0x800u), keep(bz & 0x1000u), BAND(3), keep(bz & 0x2000u)};
#undef BAND
    const uint32_t ta = keep(tl + 512 + (warp & 3) * 2048 + lane * 64 + (lane & 6) * 8);
    if (X_GO && hold) mbar_wait(MB_GO);
    uint32_t mbl = MB_UL + (warp & 8) * 2, ph = 0;
#pragma unroll 1
    for (int it = 0; it < SPIN_MAX; it++) {
      if (ch < 512) mbar_wait(mbl, ph);
      if (it == 1) TS(13);
      TS(3);
      wg_fence();
      wgmma64h_init(win, q[0], q[1], q[2], q[3], dlo, dhi);
      wgmma64h(win, q[4], q[5], q[6], q[7], dlo - 4, dhi);
      wgmma64h(win, q[8], q[9], q[10], q[11], dlo - 8, dhi);
      wg_commit();
      wgmma64_init<0>(a64, e, dlo, dhi);
      wgmma64<0>(a64, f, dlo - 4, dhi);
      wg_commit();
      if (ch >= 512) break;
      uint32_t r0, r1, r2, r3, ok;
      if (warp & 4) {
        mbar_wait(mbl + 8);
        if (__all_sync(0xffffffffu, it || lds32(MISC_RT + (warp & 8)) == 0)) break;
        wg_wait<0>();
        continue;
      }
      ldsm4(ta, r0, r1, r2, r3);
      ok = r0 & r1 & r2 & r3;
      ldsm4(ta ^ 32, r0, r1, r2, r3);
      asm volatile("{ .reg .pred q; setp.ne.u32 q, %1, 0; barrier.red.and.pred q, %2, 128, q; selp.u32 %0, 1, 0, q; }" : "=r"(ok) : "r"((ok & r0 & r1 & r2 & r3 & 1u) | (lane & 3)), "r"(1 + (warp >> 2)) : "memory");
      if (ok) { if ((warp & 3) == 0 && lane == 0) { sts32(MISC_RT + warp, it); mbar_arrive(MB_UL + 8 + warp * 2); } break; }
      wg_wait<0>();
      if ((warp & 3) == 0 && lane == 0) load_tile(tmx - 1, warp >> 3, ch, 56);
      mbl = MB_UL + 56 + (warp & 8) * 2; ph = it & 1;
    }
    wg_wait<1>();
#pragma unroll
    for (int i = 0; i < 4; i++) {
      const int tl = 2 * ((i & 1) + ((i & 2) ? 0 : 4));
      x9[i] = P ? win[tl + 4] : win[tl]; x7[i] = P ? win[tl + 5] : win[tl + 1];
    }
    const uint32_t l3lo = ((tb + W_L3) >> 4) + (32u << 16);
    wg_fence();
    wgmma64<0>(a64, x9, l3lo, 8);
    wgmma64<0>(a64, x7, l3lo + 96, 8);
    wg_commit();
  }
  STEP(32) STEP(33) STEP(34) wg_commit(); wg_wait<1>();
  LQ(35) LQ(36) LQ(37) LQ(38) PQ(35) PQ(36) PQ(37) PQ(38)
  FIRST(35) STEP(36) STEP(37) STEP(38) wg_commit();
  LQ(39) LD(0) PQ(39)
  TS(17);
  if (X_GO == 1 && go) mbar_arrive(MB_GO);
  FIRST(39) STEP(0) wg_commit();
  LD(1) LD(2) LD(3)
  FIRST(1) STEP(2) STEP(3) wg_commit();
  LD(4) LD(5)
  if (X_GO == 2 && go) mbar_arrive(MB_GO);
  FIRST(4) STEP(5) wg_commit();
  LD(6) LD(7)
  wg_fence(); STEP(6) STEP(7) wg_commit();
#undef STEP
#undef LD
#undef LQ
#undef PQ
#undef FIRST
  TS(18);
  if (X_GO == 3 && go) mbar_arrive(MB_GO);
  const uint32_t xc = tb + W_KT + (warp & 3) * 1024 + lane * 16;
  if (more) bar_sync(7, 288);
  wg_wait<1>();
  conv_pre(pre, kp + ALT, qp + ALT, 1, more, P);
  wg_wait<0>();
  conv_pre(pre, kp + ALT, qp + ALT, 2, more, P);
  uint32_t E[16], o[8];
#define ACC(i) ((i) < 16 ? a32[i] : (i) < 32 ? b32[(i) - 16] : a64[(i) - 32])
  E[0] = pack_h(a32[0], a32[1]);
#pragma unroll
  for (int i = 1; i < 16; i++) E[i] = pack_h(ACC(4 * i) + ACC(4 * i - 2), ACC(4 * i + 1) + ACC(4 * i - 1));
#undef ACC
#pragma unroll
  for (int j = 0; j < 8; j++) o[j] = P ? (j < 2 ? 0u : E[j - 2]) : E[8 + j];
  sts128(xc, o[0], o[1], o[2], o[3]); sts128(xc + 512, o[4], o[5], o[6], o[7]);
#pragma unroll
  for (int j = 0; j < 8; j++) o[j] = P ? E[6 + j] : E[j];
  TS(25);
  if (more) {
    sts128(xc + 4096, o[0], o[1], o[2], o[3]); sts128(xc + 4608, o[4], o[5], o[6], o[7]);
    bar_arrive(12, 192);
    return;
  }
  bar_sync(1 + (warp >> 2), 128);
  const uint4 vv[2] = {lds128(xc + (P ? -2048 : 2048)), lds128(xc + (P ? -1536 : 2560))};
  const uint32_t mk = lane < 8 ? 0xFFFEFFFEu : ~0u;
#pragma unroll
  for (int q = 0; q < 2; q++) {
    const uint4 v = vv[q];
    stsm4t(tl + (cv.ca >> 16) + q * 2048, hadd2u(o[4 * q], v.x) & mk, hadd2u(o[4 * q + 1], v.y) & mk, hadd2u(o[4 * q + 2], v.z) & mk, hadd2u(o[4 * q + 3], v.w) & mk);
  }
  fence_async();
  bar_sync(bid, bn);
  if (warp == 0 && lane == 0) mbar_arrive(MB_REL);
  if ((warp & 7) == (ch < 512 ? 7 : 3) && lane == 0) {
    asm volatile("cp.async.bulk.tensor.3d.global.shared::cta.bulk_group [%0, {%3, %2, %3}], [%1];" :: "l"(tmx), "r"(tl + 512), "r"(ch), "r"(0) : "memory");
    asm volatile("cp.async.bulk.commit_group;" ::: "memory");
  }
}

template <bool FAR> __global__ void __launch_bounds__(NT, 1)
fused_kernel(const __grid_constant__ Params p, const __grid_constant__ TMaps tm) {
  extern __shared__ __align__(1024) unsigned char smem[];
  const int c = blockIdx.x;
  const bool five = (c & 1) == 0;
  const uint32_t pitch = five ? 64 : 80;
  const uint32_t ones = 0x3F803F80u;
  const int tid = threadIdx.x, lane = tid & 31;
  const uint32_t xrow = OFF_YT + ((tid & 127) >> 3) * YT_PITCH + (tid & 64) + (tid & 7) * 16;
  {
    const int w4 = tid >> 7;
    load_params<FAR>(p, w4 < 2 ? 2 * c + w4 : five ? 257 + 2 * c : 512 + (c >> 1), tid & 127, OFF_W + W_KT + (w4 < 2 ? w4 * W_BYTES : five ? 3 * W_BYTES : 3 * W_BYTES + 2048), (0xB >> w4) & 1);
  }
  if ((tid >> 7) == 2) {
    const unsigned char* xp = p.x + (uint32_t)((c * 16 - 32 + (tid >> 3)) * 1152 + (tid & 7) * 16);
    asm volatile("" : "+l"(xp));
    { const uint32_t tq = clock(); while ((int)(clock() - tq) < X_XD) {} }
#pragma unroll
    for (int k = 0; k < 9; k++) asm volatile("cp.async.cg.shared.global [%0], [%1], 16;" :: "r"(xrow + k * 128), "l"(xp + k * 128) : "memory");
  }
  const int warp = (int)uni(tid >> 5), wg = warp >> 2;
  TS(0);
  if (__builtin_expect(wg == 4, 0)) {
    asm volatile("setmaxnreg.dec.sync.aligned.u32 32;");
    const int role = warp;
    const int u0 = (c >> 1) * 9 + (five ? ((c & 2) ? 5 : 0) : ((c & 2) ? 0 : 4));
    const uint32_t t0 = clock() + c * 4;
    if (role == 16) {
      if (lane < 19) asm volatile("mbarrier.init.shared::cta.b64 [%0], %1;" :: "r"(OFF_MISC + lane * 8), "r"((unsigned)(lane - 2) < 4u ? 4 : 1) : "memory");
      if (lane < 2) asm volatile("mbarrier.arrive.expect_tx.shared::cta.b64 _, [%0], %1;" :: "r"(OFF_MISC + lane * 8), "r"(lane ? (five ? 36864 : 51200) : pitch * 1152) : "memory");
      fence_async();
      bar_arrive(5, 608);
      const CUtensorMap* tmb = &tm.m[five ? 3 : 0];
#pragma unroll 1
      for (int u = 0; u < 17; u++) {
        const uint32_t e = p.sched[five][u], kind = e & 3, s = (e >> 2) & 15, dst = e >> 14;
        if (kind == 3) continue;
        while ((int)(clock() - t0) < X_PF0 + (u < X_NE ? u * X_PFD : X_LAG + u * X_TD)) __nanosleep(20);
        if (e & 0x3FC0) mbar_wait(OFF_MISC + ((e >> 6) & 255));
        if (lane == 0) {
          if (kind == 2) asm volatile("cp.async.bulk.tensor.3d.shared::cluster.global.mbarrier::complete_tx::bytes [%0], [%1, {%3, %4, %5}], [%2];"
                                      :: "r"(dst), "l"(tmb + 2), "r"(MB_D), "r"(0), "r"(u0 * 8), "r"(s) : "memory");
          else tma_box(dst, tmb + kind, MB_GU, u0 * 8, s * 96);
        }
        if (u == 5) TS(2);
        if (u == 10) TS(3);
      }
      TS(4);
      TS_DUMP();
#define FINISH0 bar_sync(12, 192);        \
        _Pragma("unroll 1") for (int w = role & 2; w < (role & 2) + 2; w++) { \
          const uint32_t xa = OFF_W + W_KT + lane * 16, mk = lane < 8 ? 0xFFFEFFFEu : ~0u, ya = OFF_T + (8 + lane) * 64 + (((w & 1) ^ (lane >> 1)) & 3) * 16 + (w & 2) * 2048; \
          const uint4 a = lds128(xa + 4096 + w * 1024), b = lds128(xa + (w ^ 2) * 1024), d = lds128(xa + 4608 + w * 1024), e = lds128(xa + 512 + (w ^ 2) * 1024); \
          stsm4t(ya, hadd2u(a.x, b.x) & mk, hadd2u(a.y, b.y) & mk, hadd2u(a.z, b.z) & mk, hadd2u(a.w, b.w) & mk); \
          stsm4t(ya + 2048, hadd2u(d.x, e.x) & mk, hadd2u(d.y, e.y) & mk, hadd2u(d.z, e.z) & mk, hadd2u(d.w, e.w) & mk); \
        } \
        fence_async();
    } else if (role == 17) {
      if (smem_u32(smem) != SB) __trap();
      bar_sync(10, 576);
      if (lane == 0) {
        fence_async();
        while ((int)(clock() - t0) < X_NS - c * 4) {}
        asm volatile("cp.async.bulk.global.shared::cta.bulk_group [%0], [%1], 10240;" :: "l"(&p.s->X[c * DM * 2 + 512]), "r"(OFF_G) : "memory");
        asm volatile("cp.async.bulk.commit_group;" ::: "memory");
        asm volatile("cp.async.bulk.wait_group 0;" ::: "memory");
      }
      if (lane == 0) mbar_arrive(MB_GF);
      bar_arrive(11, 96);
      if (five) { FINISH0 bar_arrive(13, 192); }
    } else if (role == 18) {
      sts32(MISC_EPOCH, 0);
      sts32(MISC_T0, t0 - c * 4);
      bar_arrive(5, 608);
      uint4* q = lane < 2 ? &p.s->R[c * 2 + lane] : lane < 11 ? &p.s->HS[c * 9 + lane - 2] : lane == 11 ? &p.s->HS[1152 + (c & 7)] : (uint4*)&p.s->FLAG[c * 8];
      if (lane < (c < 8 ? 12 : 11)) str128(q, ~0u, ~0u, ~0u, ~0u);
      const uint32_t ep = __shfl_sync(0xffffffffu, ldr32(q), 31) + 1u;
      sts32(MISC_EPOCH, ep | 0x80000000u);
      TSX(21);
      if (lane == 31) str32(q, ep);
      bar_sync(11, 96);
      TSX(14);
      mbar_wait(MB_KF + (lane & 3) * 8);
      __syncwarp();
      { const uint2 e = lds64(MISC_EM); if (lane < 2) str128(&p.s->SC[c * 2 + lane], e.x, __byte_perm(e.y, ep, 0x6540), 0, 0); }
      TSX(17);
      while ((int)(clock() - t0) < X_SCT) __nanosleep(100);
      TSX(18);
      {
        uint2 v[4];
#pragma unroll 1
        for (int it = 0; it < SPIN_MAX; it++) {
          uint32_t bad = 0;
#pragma unroll
          for (int q = 0; q < 4; q++) v[q] = ldr64(&p.s->SC[lane * 2 + q * 64]);
#pragma unroll
          for (int q = 0; q < 4; q++) bad |= (v[q].y >> 8) ^ (ep & 0xFFFFFFu);
          if (!__any_sync(0xffffffffu, bad)) break;
        }
        TSX(25);
#pragma unroll
        for (int q = 0; q < 4; q++) {
          const uint32_t sa = (lane >> 4) * YT_PITCH + (lane & 15) * 2;
          sts16(sc_addr(2 * q) + sa, v[q].x); sts16(sc_addr(8 + 2 * q) + sa, v[q].x >> 16);
          if (lane & 1) asm volatile("st.shared.u8 [%0], %1;" :: "r"(sc_addr(16) + q * 16 + (lane >> 1)), "r"(v[q].y) : "memory");
        }
      }
      __syncwarp();
      if (lane == 0) mbar_arrive(MB_SC);
      TSX(27);
    } else {
      uint32_t w[9];
      const uint32_t dk = ldnc16(p.dskip + ((lane & 4) ? 512 + (c >> 1) : (lane & 2) * 128 + 2 * c + (lane & 1)));
      float s = 0.f;
#pragma unroll
      for (int i = 0; i < 9; i++) w[i] = ldnc32(p.w_r + lane + 32 * i);
      sts16(OFF_WR + 1152 + lane * 2, dk);
      bar_arrive(5, 608);
#pragma unroll
      for (int i = 0; i < 9; i++) { sts32(OFF_WR + lane * 4 + i * 128, w[i]); s += bf_lo(w[i]) + bf_hi(w[i]); }
      sts32(MISC_SW, __float_as_uint(warp_sum(s)));
      TSX(23);
      bar_sync(10, 576);
      if (lane == 0) {
        const uint32_t tp = clock();
        TSX(1);
        while ((int)(clock() - tp) < X_DELTA || (int)(clock() - t0) < X_ABS - c * 4) {}
        TSX(24);
        load_tile(&tm.m[6], 0, c);
        TSX(15);
        while ((int)(clock() - t0) < X_ABS + X_DSTEP - c * 4) {}
      }
      bar_sync(11, 96);
      if (lane == 0) {
        load_tile(&tm.m[6], 1, 128 + c);
      }
      if (five) {
        mbar_wait(MB_KF);
#pragma unroll 1
        for (int it = 0; it < SPIN_MAX; it++) {
          if (lane == 0) load_tile(&tm.m[8], 2, 512 + (c >> 1));
          mbar_wait(MB_UL + 32, it & 1);
          uint32_t m = 1;
#pragma unroll
          for (int q = 0; q < 4; q++) { uint32_t r0, r1, r2, r3; ldsm4(OFF_W + 512 + lane * 64 + (lane & 6) * 8 + q * 2048, r0, r1, r2, r3); m &= r0 & r1 & r2 & r3; }
          if (__all_sync(0xffffffffu, m || (lane & 3))) break;
        }
        bar_arrive(7, 288);
        FINISH0
        bar_arrive(13, 192);
      }
      bar_sync(0, 544);
      if (lane == 0) mbar_arrive(MB_H);
    }
    return;
  }
  const int wt = tid & 127, g = lane >> 2, t = lane & 3;
  const uint32_t wb = OFF_W + wg * W_BYTES;
  asm volatile("cp.async.commit_group;" ::: "memory");
  const ConvC cv = conv_consts(warp, lane);
  zero_pads(wb, wt);
  load_params<FAR>(p, 254 + 2 * c + wg, wt, wb + W_KT, wg == 2 || (wg == 3 && !five));
  asm volatile("cp.async.commit_group;" ::: "memory");
  asm volatile("setmaxnreg.inc.sync.aligned.u32 112;");
  {
    uint4 kw;
    uint4* kx = &p.s->KX[(c >> 1) * 128 + wt];
    bool two = wg == 3;
    uint32_t ep;
    int em = 0;
    uint32_t slot = wg + (two && !five);
    const uint32_t ra0 = wb + W_KT + (slot & 4) * 512 + wt * 2, ra6 = wb + W_KT + 1536 + (slot & 4) * 512 + (((slot & 4) ? c >> 1 : 2 * c + (wg & 1)) & 7) * 2;
    uint32_t raw[7];
    if (wg != 2) {
      asm volatile("cp.async.wait_group 1;" ::: "memory");
      bar_sync(1 + wg, 128);
#pragma unroll
      for (int i = 0; i < 7; i++) raw[i] = lds16(i < 6 ? ra0 + i * 256 : ra6);
    }
    int phase = wg == 2 ? 3 : 2;
#pragma unroll 1
    for (;;) {
      if (phase != 3) {
        KgState ks;
        TS(22);
        kgen_tables_n(raw, wb, wt, ks);
        TS(20);
        bar_sync(1 + wg, 128);
        em = kgen_tables_m(wb, wt, ks);
        fence_async();
      }
      if (phase & 2) {
        const int lz = lane ^ (clock() & p.off[7]);
        const uint32_t tr_addr = pin(tr_base(lz) + warp * 32), lca = pin(MISC_LN1 + (lz & 1) * 16);
        uint4* dst;
        { const unsigned long long a = (unsigned long long)&p.s->X[c * DM * 2 + warp * 32 + (8 * ((lz >> 1) & 1) + (lz >> 2)) * 2 + (lz & 1)];
          dst = (uint4*)(((unsigned long long)pin(a >> 32) << 32) | pin((uint32_t)a)); }
        if (phase == 3) {
        asm volatile("cp.async.wait_group 1;" ::: "memory");
        TS(21);
        float d[3][4], r;
        uint4 a[9];
#pragma unroll
        for (int k = 0; k < 9; k++) a[k] = lds128(xrow + k * 128);
#pragma unroll
        for (int i = 0; i < 4; i++) d[0][i] = d[1][i] = d[2][i] = 0.f;
#pragma unroll
        for (int k = 0; k < 9; k++) { mma_bf16(d[(2 * k) % 3], a[k].x, ones, a[k].y, ones, a[k].x, a[k].y); mma_bf16(d[(2 * k + 1) % 3], a[k].z, ones, a[k].w, ones, a[k].z, a[k].w); }
#pragma unroll
        for (int i = 0; i < 4; i++) d[0][i] += d[1][i] + d[2][i];
        const LnC lc = ln_consts(d[0][2] + d[0][3], __shfl_sync(0xffffffffu, d[0][0], 9 * t) + __shfl_sync(0xffffffffu, d[0][1], 9 * t + 4), r);
        if (lane < 12) sts16(MISC_LN1 + g * 32 + (warp & 3) * 8 + t * 2, lane < 4 ? lc.m2 : lane < 8 ? lc.rh2 : lc.rl2);
        }
        asm volatile("cp.async.wait_group 0;" ::: "memory");
        TS(23);
        bar_sync(5, 608);
        uint32_t x[3][4];
        ldsm4t(tr_addr, x[0][0], x[0][1], x[0][2], x[0][3]);
        uint4 m = lds128(lca);
        const uint4 rl = lds128(lca + 64), rh = lds128(lca + 32);
        ldsm4t(tr_addr + 512, x[1][0], x[1][1], x[1][2], x[1][3]);
        if (wg == 3) ldsm4t(tr_addr + 640, x[2][0], x[2][1], x[2][2], x[2][3]);
#pragma unroll
        for (int q = 0; q < 3; q++) {
          if (q < 2 || wg == 3) {
            const uint32_t r0 = ln_apply(x[q][0], m.x, rh.x, rl.x), r1 = ln_apply(x[q][1], m.y, rh.y, rl.y), r2 = ln_apply(x[q][2], m.z, rh.z, rl.z), r3 = ln_apply(x[q][3], m.w, rh.w, rl.w);
            const uint32_t w0 = (pack_h(bf_lo(r0), bf_hi(r0)) & 0xFFFEFFFEu) | 1u, w1 = pack_h(bf_lo(r1), bf_hi(r1)), w2 = pack_h(bf_lo(r2), bf_hi(r2)), w3 = pack_h(bf_lo(r3), bf_hi(r3));
            if (q == 0) str128(dst, w0, w1, w2, w3);
            else sts128(OFF_G + warp * 512 + (8 * (t >> 1) + g) * 32 + (t & 1) * 16 + (q == 2 ? 2048 : 0), w0, w1, w2, w3);
          }
          if (q == 0) {
            const uint32_t z = clock() & p.off[7];
            m.x ^= z; m.y ^= z; m.z ^= z; m.w ^= z;
          }
          if (q == 0) TS(30);
          if (q == 0 && wg >= 2) {
#pragma unroll
            for (int i = 0; i < 7; i++) raw[i] = lds16(wb + W_KT + i * 256 + (i < 6 ? wt : (2 * c + (wg & 1)) & 7) * 2);
          }
        }
        bar_arrive(10, 576);
        TS(1);
      } else bar_sync(1 + wg, 128);
      phase &= 1;
      if (phase) { phase = 0; continue; }
      TS(14);
      float acc[20];
      const uint32_t alo = (wb >> 4) | (8u << 16);
      uint4 k4 = lds128(wb + W_MISC + 16);
      uint32_t dk = lds16(OFF_WR + 1152 + slot * 2);
      wg_fence();
      wgmma40_ss_init(acc, alo, alo + 1024, 2048 >> 4);
#pragma unroll
      for (int k = 1; k < 8; k++) wgmma40_ss(acc, alo + k * 16, alo + 1024 + k * 16, 2048 >> 4);
      wg_commit();
      { const uint32_t z = clock() & p.off[7]; dk ^= z; k4.x ^= z; k4.z ^= z; }
      const float k2048 = (float)(int)((k4.x + k4.y) + (k4.z + k4.w)) * (1.f / 262144.f);
      const int ef = max(em, min((int)((dk >> 7) & 255u) - 7, 238));
      asm volatile("st.shared.u8 [%0], %1;" :: "r"(MISC_EM + slot), "r"(ef + 9) : "memory");
      const float un = __uint_as_float((uint32_t)max(114 + em - ef, 0) << 23), d0 = wt ? 0.f : bf_lo(dk) * __uint_as_float((uint32_t)(245 - ef) << 23);
      wg_wait<0>();
      kw.x = pack_h(fmaf(acc[0] - acc[3], un, d0), (acc[4] - acc[7]) * un);
      kw.y = pack_h((acc[8] - acc[11]) * un, (acc[12] - acc[15]) * un);
      kw.z = pack_h((acc[16] - acc[19]) * un, k2048 * un);
      TS(24);
      ep = 0;
      if (two) SPIN_WHILE(ep == 0, ep = lds32(MISC_EPOCH));
      if (five || !two) break;
      str128(kx, kw.x, kw.y, kw.z, ep);
      two = false;
      slot = 3;
      bar_sync(1 + wg, 128);
    }
    if (lane == 0) mbar_arrive(MB_KF + wg * 8);
    if (two) { mbar_wait(MB_KF); zero_pads(OFF_W + ALT, wt); }
    uint32_t tb = wb;
#pragma unroll 1
    for (;;) {
      kgen_build(tb, wg, wt, kw.x, kw.y, kw.z);
      TS(15);
      if (!two) break;
      two = false;
      kw.w = 0;
      SPIN_WHILE(kw.w != ep, kw = ldr128(kx));
      tb = OFF_W + ALT;
    }
    fence_async();
    TS(31);
    if (tb != wb) bar_arrive(7, 288);
    bar_sync(1 + wg, 128);
  }
  uint32_t tpub;
  ConvPre pre;
  conv_pre(pre, (wb ^ p.off[7]) + (cv.ca & 0xFFFFu), (wb ^ p.off[7]) + cv.qa, 3, true, warp & 2);
#pragma unroll 1
  for (int item = 0;; item++) {
    TS(2);
    conv_item(item ? OFF_W + ALT : wb, item ? OFF_W : OFF_T + (wg >> 1) * TILE, item ? 1 : 13 + (wg >> 1), item ? 128 : five && wg == 1 ? 192 : 256, pre, cv, p.off[7],
              &tm.m[item ? 9 : 7], item ? 512 + (c >> 1) : (wg >> 1) * 128 + c, warp, lane, five && wg >= X_GW, five && !wg && !item);
    tpub = clock() - (item ? X_YD : wg >= 2 ? X_YD2 : 0);
    if (wg || !five || item) break;
    TS(27);
  }
  TS(4);

  const int ln = lane ^ p.off[7], td = warp * 32 + ln, gg = ln >> 2, tt = ln & 3;
  const int tok = c * 16 + warp;
  const int fu = warp / 3, fk = warp - fu * 3;
  uint32_t wa[12][4];
  uint4 ha[3];
  const uint4* hsrc = &p.s->HS[td + (td / 24) * 48];
  {
    uint32_t hw[9], wr[9];
    const uint32_t row = keep(OFF_YT + warp * YT_PITCH + (warp >> 3) * 64 + ln * 16);
    const uint32_t wabase = keep(((ln & 8) ? OFF_W + (fk + 1) * W_BYTES : OFF_G + fk * 192 * pitch) + ((ln >> 4) * 8 + (ln & 7)) * pitch
                                 + (five ? ((fu ^ (ln >> 1)) & 3) : min(fu, 4)) * 16);
    float sw;
    {
      const bool three = wg == 1;
      const int ch = 8 * (tt >> 1) + gg;
      const uint32_t tr_addr = tr_base(ln);
      const uint4* ysrc = &p.s->X[c * DM * 2 + ch * 2 + (tt & 1)];
      uint32_t x[3][4], s[3];
      uint4 v[3];
#define TL(q) ((q) < 2 ? 2 * warp + (q) : 28 + warp)
      asm volatile("cp.async.bulk.wait_group.read 0;" ::: "memory");
      if (wg >= 2) { const uint32_t ts = lds32(MISC_T0); while ((int)(clock() - ts) < X_XS) {} }
      while ((int)(clock() - tpub) < X_YD) {}
      TS(5);
      v[0] = ldr128(ysrc + TL(0) * 32); v[1] = ldr128(ysrc + TL(1) * 32); v[2] = make_uint4(three, 0, 0, 0);
      mbar_wait(MB_REL);
#pragma unroll
      for (int i = 0; i < 6; i++) if (i < 4 || three) wr[i] = (gg & 2) ? ones : lds32(OFF_WR + TL(i >> 1) * 32 + (i & 1) * 16 + tt * 4);
      const uint32_t ha = keep(OFF_YT + (ln & 7) * YT_PITCH + (ln >> 4) * (8 * YT_PITCH + 64) + (ln & 8) * 2);
      const uint32_t pa = keep(OFF_PART + warp * 4 + ((gg & 2) * 8 + (gg & 4) * 2 + 2 * tt + (gg & 1)) * 80), pb = keep(OFF_PART + 2560 + warp * 4 + gg * 80);
      float dl[4] = {0.f, 0.f, 0.f, 0.f}, dh[4] = {0.f, 0.f, 0.f, 0.f};
      sw = __uint_as_float(lds32(MISC_SW));
#pragma unroll
      for (int q = 0; q < 3; q++) {
        if (q < 2 || three) {
          ldsm4t(tr_addr + TL(q) * 32, x[q][0], x[q][1], x[q][2], x[q][3]);
        }
      }
      mbar_wait(MB_SC);
#pragma unroll
      for (int q = 0; q < 3; q++) {
        asm volatile("ld.shared.u8 %0, [%1];" : "=r"(s[q]) : "r"((q < 2 ? sc_addr(warp) + q * 16 : sc_addr(16) + (warp & 3) * 16) + ch) : "memory");
        s[q] = keep(s[q] * 0x800080u);
      }
#define FIN(q) stsm4t(tr_addr + TL(q) * 32, bf_fma2(h2bf(v[q].x), s[q], x[q][0]), bf_fma2(h2bf(v[q].y), s[q], x[q][1]), bf_fma2(h2bf(v[q].z), s[q], x[q][2]), bf_fma2(h2bf(v[q].w), s[q], x[q][3]));
      SPIN_WHILE((v[0].x | v[1].x) & 1u, _Pragma("unroll") for (int q = 0; q < 3; q++) if (v[q].x & 1u) v[q] = ldr128(ysrc + TL(q) * 32));
      if (v[2].x & 1u) v[2] = ldr128(ysrc + TL(2) * 32);
#define STAT(q) { uint32_t r0, r1, r2, r3; ldsm4(ha + TL(q) * 32, r0, r1, r2, r3); \
        mma_bf16(dl, r0, wr[2 * q], r1, wr[2 * q + 1], r0, r1); mma_bf16(dh, r2, wr[2 * q], r3, wr[2 * q + 1], r2, r3); }
      FIN(0) FIN(1)
      __syncwarp();
      STAT(0) STAT(1)
      if (three) {
        SPIN_WHILE(v[2].x & 1u, if (v[2].x & 1u) v[2] = ldr128(ysrc + TL(2) * 32));
        FIN(2)
        __syncwarp();
        STAT(2)
      }
      if (gg & 1) { dl[0] = dl[1]; dl[2] = dl[3]; dh[0] = dh[1]; dh[2] = dh[3]; }
      sts32(pa, __float_as_uint((gg & 4) ? dh[2] : dl[2]));
      if (tt == (gg >> 1)) { sts32(pb, __float_as_uint(dl[0])); sts32(pb + 640, __float_as_uint(dh[0])); }
#undef STAT
#undef FIN
#undef TL
    }
    uint32_t ra = keep(OFF_PART + (ln & 15) * 80 + (ln & 16) * 2);
    uint16_t* rp = (uint16_t*)p.s->R + c * 16 + (ln & 15);
    const uint2* rsrc = (const uint2*)p.s->R + td;
    asm volatile("" : "+l"(rp), "+l"(rsrc), "+l"(hsrc));
    uint2 rv = make_uint2(0u, 0u);
    TS(28);
    if (warp != X_PW) bar_sync(0, 544);
    else {
      float z[3], rd;
      asm volatile("bar.sync 0, 544;" : "+r"(ra) :: "memory");
#pragma unroll
      for (int k = 2; k >= 0; k--) {
        const uint4 a = lds128(ra + k * 1280), b = lds128(ra + k * 1280 + 16);
        z[k] = ((__uint_as_float(a.x) + __uint_as_float(a.y)) + (__uint_as_float(a.z) + __uint_as_float(a.w))) + ((__uint_as_float(b.x) + __uint_as_float(b.y)) + (__uint_as_float(b.z) + __uint_as_float(b.w)));
      }
#pragma unroll
      for (int k = 2; k >= 0; k--) z[k] += __shfl_xor_sync(0xffffffffu, z[k], 16);
      const LnC l = ln_consts(z[1], z[2], rd);
      const uint32_t b = pack_bf(0.f, fmaf(-bf_lo(l.m2), sw, z[0]) * rd);
      const uint32_t k16 = max(min((b ^ (((int)b >> 31) | 0x80000000u)) >> 16, 0xFFFEu), 1u);
      if (ln < 16) str16(rp, k16);
      sts64(OFF_RK + (ln & 15) * 8, __byte_perm(l.m2, l.rh2, 0x5410), __byte_perm(l.rl2, k16, 0x5410));
      sts128(MISC_CNT + ln * 16, 0, 0, 0, 0);
    }
    mbar_wait(MB_GU);
#define LD_HW { const uint4 a = lds128(row), b = lds128(row + 512); hw[8] = lds32(row + 1024 - ln * 12); \
      hw[0] = a.x; hw[1] = a.y; hw[2] = a.z; hw[3] = a.w; hw[4] = b.x; hw[5] = b.y; hw[6] = b.z; hw[7] = b.w; }
    LD_HW
    const uint32_t tr0 = clock();
    bar_sync(5, 512);
    TS(7);
    const uint2 lk = lds64(OFF_RK + warp * 8);
    LnC l2;
    l2.m2 = __byte_perm(lk.x, 0, 0x1010); l2.rh2 = __byte_perm(lk.x, 0, 0x3232); l2.rl2 = __byte_perm(lk.y, 0, 0x1010);
    const uint32_t key = (lk.y & 0xFFFF0000u) | (2047 - tok);
    uint32_t loc = ln < 16 ? (lds32(OFF_RK + 4 + ln * 8) & 0xFFFF0000u) | (2047 - c * 16 - ln) : 0u;
    int rank = __popc(__ballot_sync(0xffffffffu, loc > key));
#pragma unroll
    for (int i = 0; i < 9; i++) wr[i] = keep(ln_apply(hw[i], l2.m2, l2.rh2, l2.rl2));
#define OUT_ROW { uint32_t* o = p.out + tok * 288 + ln * 4; \
      *(uint4*)o = make_uint4(bf_add2(hw[0], wr[0]), bf_add2(hw[1], wr[1]), bf_add2(hw[2], wr[2]), bf_add2(hw[3], wr[3])); \
      *(uint4*)(o + 128) = make_uint4(bf_add2(hw[4], wr[4]), bf_add2(hw[5], wr[5]), bf_add2(hw[6], wr[6]), bf_add2(hw[7], wr[7])); \
      o[256 - ln * 3] = bf_add2(hw[8], wr[8]); }
    uint4* hs = p.s->HS + ln;
    asm volatile("" : "+l"(hs));
#pragma unroll 1
    for (int base = 0; base < 8; base += 2) {
      uint32_t T[2];
#pragma unroll
      for (int j = 0; j < 2; j++) {
        const uint32_t mx = __reduce_max_sync(0xffffffffu, loc);
        if (loc == mx) loc = 0;
        T[j] = (td >> 2) < c ? (mx & 0xFFFF0000u) - 1u : mx | 0xFFFFu;
      }
      const uint32_t sh = keep(rank == base ? 0x4410u : rank == base + 1 ? 0x4432u : 0x4445u), ca = keep(MISC_CNT + base * 64 + ln * 4);
      TS(29);
      if (base == 0) {
        while ((int)(clock() - tr0) < X_RD) {}
        if ((td >> 2) != c) rv = ldr64(rsrc);
        if (rank >= X_OR) OUT_ROW
        if (warp < (five ? 12 : 15)) {
#pragma unroll
          for (int k = 0; k < X_WS; k++) ldsm4t(wabase + k * 16 * pitch, wa[k][0], wa[k][1], wa[k][2], wa[k][3]);
        }
      }
      uint32_t cnt;
#pragma unroll 1
      for (int it = 0; it < SPIN_MAX; it++) {
        const uint32_t xs = rv.x << 16, ys = rv.y << 16;
        const bool bad = max(max(rv.x, xs), max(rv.y, ys)) >= 0xFFFF0000u;
        uint32_t cn2 = 0;
        cnt = bad ? 256u : 0u;
#pragma unroll
        for (int j = 0; j < 2; j++)
          asm("{ .reg .pred a, b, c, d; setp.gt.u32 a, %2, %6; setp.gt.u32 b, %3, %6; setp.gt.u32 c, %4, %6; setp.gt.u32 d, %5, %6; "
              "@a add.u32 %1, %1, %7; @b add.u32 %1, %1, %7; @c add.u32 %0, %0, %7; @d add.u32 %0, %0, %7; }"
              : "+r"(cnt), "+r"(cn2) : "r"(rv.x), "r"(rv.y), "r"(xs), "r"(ys), "r"(T[j]), "r"(1u << (16 * j)));
        cnt = __reduce_add_sync(0xffffffffu, cnt + cn2);
        asm volatile("{ .reg .pred q; setp.eq.u32 q, %2, 0; @q red.shared.add.u32 [%0], %1; }" :: "r"(ca), "r"(cnt), "r"(cnt & 0x3F00u) : "memory");
        if (!(cnt & 0x3F00u)) break;
        if (bad) rv = ldr64(rsrc);
      }
      TS(16);
      bar_sync(0, 512);
      cnt = lds32(ca);
      if (base == 0) tpub = clock();
      const int gr = rank + __byte_perm(cnt, 0x800u, sh);
      if (gr < 8) {
        uint4* ks = hs + 1152 + gr;
        hs = (uint4*)((char*)hs + gr * 1152);
        asm volatile("{ .reg .b128 t, u; .reg .b64 a, b, c, d; mov.b64 a, {%1,%2}; mov.b64 b, {%3,%4}; mov.b64 c, {%5,%6}; mov.b64 d, {%7,%8}; mov.b128 t, {a, b}; mov.b128 u, {c, d}; "
                     "st.relaxed.gpu.global.b128 [%0], t; st.relaxed.gpu.global.b128 [%0 + 512], u; }"
                     :: "l"(hs), "r"(wr[0]), "r"(wr[1]), "r"(wr[2]), "r"(wr[3]), "r"(wr[4]), "r"(wr[5]), "r"(wr[6]), "r"(wr[7]) : "memory");
        str32((uint32_t*)(hs + 64) - ln * 3, wr[8]);
        str128(hs + 576, hw[0], hw[1], hw[2], hw[3]); str128(hs + 608, hw[4], hw[5], hw[6], hw[7]); str32((uint32_t*)(hs + 640) - ln * 3, hw[8]);
        if (ln == 0) str32(ks, key);
        rank = 16;
      }
      if (__all_sync(0xffffffffu, (int)(cnt >> 16) + base + 2 >= 8)) break;
    }
    TS(8);
    if (warp < (five ? 12 : 15)) {
#pragma unroll
      for (int k = X_WS; k < 12; k++) ldsm4t(wabase + k * 16 * pitch, wa[k][0], wa[k][1], wa[k][2], wa[k][3]);
    }
    if (warp < 6) while ((int)(clock() - tpub) < X_HD) {}
    TS(19);
    if (warp < 6) { ha[0] = ldr128(hsrc); ha[1] = ldr128(hsrc + 24); ha[2] = ldr128(hsrc + 48); }
    if (rank < X_OR) OUT_ROW
  }
  uint32_t wd[10][4];
  const uint32_t xb = keep(OFF_XS + (ln & 7) * 1168 + (fk * 24 + (ln >> 3)) * 16);
  if (warp >= 7) {
    const uint32_t db = down_box(warp - 7, five) + (ln & 7) * 128;
    mbar_wait(MB_D);
#pragma unroll
    for (int j = 0; j < 4; j++) {
      const uint32_t a = db + (ln >> 4) * 1024 + (((2 * j + ((ln >> 3) & 1)) ^ (ln & 7)) << 4);
      ldsm4t(a, wd[j][0], wd[j][1], wd[j][2], wd[j][3]);
      ldsm4t(a + 2048, wd[4 + j][0], wd[4 + j][1], wd[4 + j][2], wd[4 + j][3]);
    }
#pragma unroll
    for (int j = 0; j < 2; j++) ldsm4t(db + 4096 + (((4 * j + (ln >> 3)) ^ (ln & 7)) << 4), wd[8 + j][0], wd[8 + j][1], wd[8 + j][2], wd[8 + j][3]);
  } else if (warp < 6) {
    const uint32_t xs = keep(OFF_XS + (td + (td / 24) * 49) * 16);
#pragma unroll 1
    for (int it = 0; it < SPIN_MAX; it++) {
      const bool bad = max(max(max(ha[0].x, ha[1].x), max(ha[2].x, ha[2].y)), max(ha[2].z, ha[2].w)) == ~0u;
      if (!__any_sync(0xffffffffu, bad)) break;
      if (bad) { ha[0] = ldr128(hsrc); ha[1] = ldr128(hsrc + 24); ha[2] = ldr128(hsrc + 48); }
    }
#pragma unroll
    for (int q = 0; q < 3; q++) sts128(xs + q * 384, ha[q].x, ha[q].y, ha[q].z, ha[q].w);
  }
  TS(9);

  bar_sync(0, 512);
  if (warp < (five ? 12 : 15)) {
    float d0[4] = {0.f, 0.f, 0.f, 0.f}, d1[4] = {0.f, 0.f, 0.f, 0.f};
#pragma unroll
    for (int k = 0; k < 12; k += 2) {
      uint32_t b0, b1, b2, b3;
      ldsm4(xb + k * 32, b0, b1, b2, b3);
      mma_bf16(d0, wa[k][0], wa[k][1], wa[k][2], wa[k][3], b0, b1);
      mma_bf16(d1, wa[k + 1][0], wa[k + 1][1], wa[k + 1][2], wa[k + 1][3], b2, b3);
    }
    sts128(OFF_RED + td * 16, __float_as_uint(d0[0] + d1[0]), __float_as_uint(d0[1] + d1[1]), __float_as_uint(d0[2] + d1[2]), __float_as_uint(d0[3] + d1[3]));
  }
  TS(26);
  if (warp < 5) {
    const uint32_t rb = OFF_RED + warp * 1536 + ln * 16;
    bar_sync(9, 512);
    const uint4 pa = lds128(rb), pb = lds128(rb + 512), pc = lds128(rb + 1024);
    const float ga = bfr(__uint_as_float(pa.x) + __uint_as_float(pb.x) + __uint_as_float(pc.x));
    const float gb = bfr(__uint_as_float(pa.y) + __uint_as_float(pb.y) + __uint_as_float(pc.y));
    const uint32_t uu = pack_bf(__uint_as_float(pa.z) + __uint_as_float(pb.z) + __uint_as_float(pc.z), __uint_as_float(pa.w) + __uint_as_float(pb.w) + __uint_as_float(pc.w));
    float ra, rb2;
    asm("rcp.approx.ftz.f32 %0, %1;" : "=f"(ra) : "f"(1.f + ex2(ga * -1.4426950408889634f)));
    asm("rcp.approx.ftz.f32 %0, %1;" : "=f"(rb2) : "f"(1.f + ex2(gb * -1.4426950408889634f)));
    const uint32_t act = bf_mul2(pack_bf(ga * ra, gb * rb2), uu);
    sts32(OFF_ACT + td * 4, act);
  } else bar_arrive(9, 512);
  uint4* dst = &p.s->X[c * DM * 2 + (warp - 7) * 64 + tt * 8 + gg];
  asm volatile("" : "+l"(dst));
  bar_sync(8, 512);
  tpub = clock();
  if (warp >= 7) {
    uint32_t b0, b1, b2, b3, b4;
    ldsm4t(OFF_ACT + ln * 16, b0, b1, b2, b3);
    asm volatile("ldmatrix.sync.aligned.m8n8.x1.trans.shared.b16 {%0}, [%1];" : "=r"(b4) : "r"(OFF_ACT + 512 + ln * 16) : "memory");
    float y[4][4];
#pragma unroll
    for (int j = 0; j < 4; j++) {
      y[j][0] = y[j][1] = y[j][2] = y[j][3] = 0.f;
      mma_bf16(y[j], wd[j][0], wd[j][1], wd[j][2], wd[j][3], b0, b1);
    }
#pragma unroll
    for (int j = 0; j < 4; j++) mma_bf16(y[j], wd[4 + j][0], wd[4 + j][1], wd[4 + j][2], wd[4 + j][3], b2, b3);
    if (!five) {
#pragma unroll
      for (int j = 0; j < 4; j++) mma_bf16_k8(y[j], wd[8 + (j >> 1)][2 * (j & 1)], wd[8 + (j >> 1)][2 * (j & 1) + 1], b4);
    }
    str128(dst, (pack_bf(y[0][0], y[0][1]) & ~1u) | 0x10000u, pack_bf(y[0][2], y[0][3]), pack_bf(y[1][0], y[1][1]), pack_bf(y[1][2], y[1][3]));
    str128(dst + 32, (pack_bf(y[2][0], y[2][1]) & ~1u) | 0x10000u, pack_bf(y[2][2], y[2][3]), pack_bf(y[3][0], y[3][1]), pack_bf(y[3][2], y[3][3]));
  }
  TS(10);

  if (c < 72) {
    const uint4* src = &p.s->X[(warp * 4 + tt) * (DM * 2) + c * 8 + gg];
    const int slot = (c & 3) * 2 + (ln >> 4), dw = (c >> 2) * 16 + (ln & 15);
    uint32_t hv = 0, kv = 0, res = 0, rs2 = 0;
    uint32_t* o = p.out;
    if (warp == 0) {
      hv = ~0u;
      SPIN_WHILE(max(hv, kv) == ~0u, hv = ldr32((const uint32_t*)p.s->HS + 2304 + slot * 288 + dw); kv = ldr32(&p.s->HS[1152 + slot]));
      const float r = bf_hi(kv ^ (((int)~kv >> 31) | 0x80000000u));
      float rs;
      asm("rcp.approx.ftz.f32 %0, %1;" : "=f"(rs) : "f"(1.f + ex2(r * -1.4426950408889634f)));
      rs2 = keep(pack_bf(rs, rs));
      res = lds32(OFF_XS + slot * 1168 + dw * 4);
      o += (2047 - (int)(kv & 2047u)) * 288 + dw;
      asm volatile("" : "+l"(o));
    }
    const uint32_t sel = (gg & 1) ? 0x3F800000u : 0x00003F80u;
    const uint32_t q0 = keep((gg >> 1) == 0 ? sel : 0u), q1 = keep((gg >> 1) == 1 ? sel : 0u), q2 = keep((gg >> 1) == 2 ? sel : 0u), q3 = keep((gg >> 1) == 3 ? sel : 0u);
    const uint32_t fa = keep(OFF_RED + warp * 8 + ((gg & 1) * 16 + (gg >> 1) * 4 + tt) * 144), fb = keep(OFF_RED + ln * 144);
    uint4 a0 = make_uint4(0, 0, 0, 0), a1 = a0;
    while ((int)(clock() - tpub) < X_PD) {}
    SPIN_WHILE(!(a0.x & a1.x & 0x10000u), if (!(a0.x & 0x10000u)) a0 = ldr128(src); if (!(a1.x & 0x10000u)) a1 = ldr128(src + 64 * DM * 2));
    float d[4] = {0.f, 0.f, 0.f, 0.f}, e[4] = {0.f, 0.f, 0.f, 0.f}, d2[4] = {0.f, 0.f, 0.f, 0.f}, e2[4] = {0.f, 0.f, 0.f, 0.f};
    mma_bf16(d, q0, q2, q1, q3, a0.x, a0.y); mma_bf16(e, q0, q2, q1, q3, a0.z, a0.w);
    mma_bf16(d2, q0, q2, q1, q3, a1.x, a1.y); mma_bf16(e2, q0, q2, q1, q3, a1.z, a1.w);
    sts64(fa, __float_as_uint(d[0] + e[2] + d2[0] + e2[2]), __float_as_uint(d[1] + e[3] + d2[1] + e2[3]));
    TS(11);
    if (warp == 0) {
      bar_sync(0, 512);
      float2 s[16];
#pragma unroll
      for (int i = 0; i < 16; i += 2) { const uint4 q = lds128(fb + i * 8); s[i] = make_float2(__uint_as_float(q.x), __uint_as_float(q.y)); s[i + 1] = make_float2(__uint_as_float(q.z), __uint_as_float(q.w)); }
#pragma unroll
      for (int k = 1; k < 16; k *= 2)
#pragma unroll
        for (int i = 0; i < 16; i += 2 * k) { s[i].x += s[i + k].x; s[i].y += s[i + k].y; }
      *o = bf_add2(hv, bf_add2(res, bf_mul2(pack_bf(s[0].x, s[0].y), rs2)));
    } else bar_arrive(0, 512);
  }
  TS(12);
  TS_DUMP();
}

typedef CUresult (*EncodeFn)(CUtensorMap*, CUtensorMapDataType, cuuint32_t, void*, const cuuint64_t*, const cuuint64_t*, const cuuint32_t*,
                             const cuuint32_t*, CUtensorMapInterleave, CUtensorMapSwizzle, CUtensorMapL2promotion, CUtensorMapFloatOOBfill);

}

extern "C" void kernel_launch(void* const* d_in, const int* in_sizes, int n_in, void* d_out, int out_size) {
  (void)in_sizes; (void)n_in; (void)out_size;
  static EncodeFn enc = nullptr;
  static Scratch* scratch = nullptr;
  if (!enc) {
    void* fn = nullptr;
    cudaDriverEntryPointQueryResult qr;
    cudaGetDriverEntryPoint("cuTensorMapEncodeTiled", &fn, cudaEnableDefault, &qr);
    enc = (EncodeFn)fn;
    cudaGetSymbolAddress((void**)&scratch, g_S);
    cudaFuncSetAttribute(fused_kernel<false>, cudaFuncAttributeMaxDynamicSharedMemorySize, SMEM_BYTES);
    cudaFuncSetAttribute(fused_kernel<true>, cudaFuncAttributeMaxDynamicSharedMemorySize, SMEM_BYTES);
  }
  TMaps tm;
  for (int i = 0; i < 6; i++) {
    const bool dn = i % 3 == 2;
    const cuuint32_t w = i < 3 ? 40 : 32;
    cuuint64_t gd[3] = {(cuuint64_t)(dn ? 64 : FF), (cuuint64_t)(dn ? FF : DM), 9};
    cuuint64_t gs[2] = {(cuuint64_t)(dn ? DM * 2 : FF * 2), 128};
    cuuint32_t bx[3] = {dn ? 64 : w, dn ? w : 96, i < 3 ? 2u : 3u};
    cuuint32_t es[3] = {1, 1, 1};
    enc(&tm.m[i], CU_TENSOR_MAP_DATA_TYPE_BFLOAT16, dn ? 3 : 2, d_in[11 + i % 3], gd, gs, bx, es, CU_TENSOR_MAP_INTERLEAVE_NONE,
        dn ? CU_TENSOR_MAP_SWIZZLE_128B : i < 3 ? CU_TENSOR_MAP_SWIZZLE_NONE : CU_TENSOR_MAP_SWIZZLE_64B,
        (CUtensorMapL2promotion)X_PROMO, CU_TENSOR_MAP_FLOAT_OOB_FILL_NONE);
  }
  for (int i = 6; i < 10; i++) {
    cuuint64_t gd[3] = {i < 8 ? 32u : 16u, i < 8 ? DM / 2u : DM, NCTA};
    cuuint64_t gs[2] = {i < 8 ? 64u : 32u, DM * 32};
    cuuint32_t bx[3] = {32, 1, (i & 1) ? 128u : 136u};
    cuuint32_t es[3] = {1, 1, 1};
    enc(&tm.m[i], CU_TENSOR_MAP_DATA_TYPE_FLOAT16, 3, scratch->X, gd, gs, bx, es, CU_TENSOR_MAP_INTERLEAVE_NONE, CU_TENSOR_MAP_SWIZZLE_64B,
        CU_TENSOR_MAP_L2_PROMOTION_NONE, CU_TENSOR_MAP_FLOAT_OOB_FILL_NONE);
  }
  Params p;
  p.x = (const unsigned char*)d_in[0];
  bool far = false;
  for (int i = 0; i < 7; i++) {
    p.far[i] = (const unsigned char*)d_in[1 + i];
    const long long d = (long long)((intptr_t)d_in[1 + i] - (intptr_t)d_in[0]);
    p.off[i] = (int)(d / 16);
    if ((long long)p.off[i] * 16 != d || p.off[i] > (1 << 30)) far = true;
  }
  p.dskip = (const uint16_t*)d_in[8];
  p.w_r = (const uint32_t*)d_in[10];
  for (int f = 0; f < 2; f++) {
    static const int kind[17] = {0, 0, 0, 0, 2, 2, 0, 0, 1, 1, 1, 1, 1, 1, 2, 2, 2};
    static const int idx[2][17] = {{2, 3, 4, 5, 6, 8, 0, 1, 0, 1, 2, 3, 4, 5, 0, 2, 4}, {2, 3, 4, 5, 0, -1, 0, 1, 0, 1, 2, 3, 4, 5, 3, -1, 6}};
    static const int blk[2][17] = {{-1, -1, -1, -1, 0, -1, 4, -1, 1, -1, 2, -1, 3, -1, 16, -1, -1}, {-1, -1, -1, -1, 1, -1, 4, -1, -1, -1, 2, -1, 3, -1, 16, -1, -1}};
    const int pitch = f ? 64 : 80;
    for (int u = 0; u < 17; u++) {
      const int s = idx[f][u];
      const uint32_t dst = kind[u] == 0 ? OFF_G + s * 96 * pitch : kind[u] == 2 ? down_box(s, f) : OFF_W + W_BYTES + (s >> 1) * W_BYTES + (s & 1) * 96 * pitch;
      const uint32_t mb = u >= 14 ? (u >= X_HU ? MB_H - OFF_MISC : 0) : blk[f][u] >= 0 ? MB_KF - OFF_MISC + blk[f][u] * 8 : 0;
      p.sched[f][u] = s < 0 ? 3u : kind[u] | s << 2 | mb << 6 | dst << 14;
    }
  }
  p.out = (uint32_t*)d_out;
  p.off[7] = 0;
  p.ts = nullptr;
  p.s = scratch;
  if (far) { fused_kernel<true><<<NCTA, NT, SMEM_BYTES, cudaStreamPerThread>>>(p, tm); return; }
  fused_kernel<false><<<NCTA, NT, SMEM_BYTES, cudaStreamPerThread>>>(p, tm);
}
```

```cpp
#include <cuda_runtime.h>
#include <cuda.h>
#include <cuda_bf16.h>
#include <cuda_fp16.h>
#include <stdint.h>
#include <stddef.h>

namespace {

constexpr int NCTA = 128;
constexpr int NT = 640;
constexpr int DM = 576;
constexpr int FF = 4608;
constexpr int SPIN_MAX = 1 << 20;

struct Scratch {
  uint4 X[NCTA * DM * 2];
  uint4 KX[64 * 128];
  uint4 HS[1152 + 8];
  uint4 R[256];
  uint4 SC[256];
  uint32_t FLAG[NCTA * 8];
};
__device__ Scratch g_S;

#define CLKS(i)
#define TS(i)
#define TSX(i)
#define TS_DUMP()

constexpr int SB = 1024;
constexpr int BOX = 15360;
constexpr int OFF_G = SB;
constexpr int OFF_W = OFF_G + 3 * BOX;
constexpr int W_KT = 26624;
constexpr int W_QT = W_KT + 64 + 2048 + 80;
constexpr int W_L3 = W_KT + 4352;
constexpr int W_CW = W_L3 + 4160;
constexpr int W_MISC = W_CW + 640;
constexpr int W_BYTES = 35840;
constexpr int TILE = 10240;
constexpr int OFF_T = OFF_W + 4 * W_BYTES;
constexpr int ALT = TILE - W_KT;
static_assert(W_MISC + 32 <= W_BYTES && OFF_W % 1024 == 0 && W_BYTES % 1024 == 0 && W_BYTES + ALT <= 20480, "wg block");
constexpr int YT_PITCH = 1184;
constexpr int OFF_YT = OFF_T + 2 * TILE;
constexpr int OFF_WR = OFF_YT + 16 * YT_PITCH + 64;
constexpr int OFF_MISC = OFF_WR + 2304;
constexpr int SMEM_BYTES = OFF_MISC + 1024 - SB;
static_assert(OFF_YT % 16 == 0 && OFF_MISC % 16 == 0, "align");
static_assert(SMEM_BYTES <= 232448, "smem");
constexpr int MB_GU = OFF_MISC;
constexpr int MB_D = OFF_MISC + 8;
constexpr int MB_KF = OFF_MISC + 16;
constexpr int MB_GF = OFF_MISC + 48;
constexpr int MB_SC = OFF_MISC + 56;
constexpr int MB_UL = OFF_MISC + 64;
constexpr int MB_REL = OFF_MISC + 104;
constexpr int MB_GO = OFF_MISC + 112;
constexpr int MB_H = MB_KF + 128;
constexpr int MISC_EPOCH = OFF_MISC + 152;
constexpr int MISC_SW = OFF_MISC + 156;
constexpr int MISC_RT = OFF_MISC + 160;
constexpr int MISC_T0 = OFF_MISC + 296;
constexpr int MISC_EM = OFF_MISC + 288;
constexpr int OFF_PART = OFF_W + 20480;
constexpr int OFF_RK = OFF_PART + 3840;
constexpr int MISC_LN1 = OFF_MISC + 192;
constexpr int OFF_XS = OFF_T;
constexpr int OFF_RED = OFF_T + TILE;
constexpr int OFF_FIN = OFF_W + 3 * W_BYTES + W_KT;
constexpr int OFF_ACT = OFF_FIN + 4096;
constexpr int MISC_CNT = OFF_ACT + 1024;

__device__ __forceinline__ uint32_t smem_u32(const void* p) { return (uint32_t)__cvta_generic_to_shared(p); }
__device__ __forceinline__ uint32_t lds32(uint32_t a) { uint32_t v; asm volatile("ld.shared.b32 %0, [%1];" : "=r"(v) : "r"(a) : "memory"); return v; }
__device__ __forceinline__ uint32_t lds16(uint32_t a) { uint16_t v; asm volatile("ld.shared.u16 %0, [%1];" : "=h"(v) : "r"(a) : "memory"); return v; }
__device__ __forceinline__ uint2 lds64(uint32_t a) { uint2 v; asm volatile("ld.shared.v2.b32 {%0,%1}, [%2];" : "=r"(v.x), "=r"(v.y) : "r"(a) : "memory"); return v; }
__device__ __forceinline__ uint4 lds128(uint32_t a) { uint4 v; asm volatile("ld.shared.v4.b32 {%0,%1,%2,%3}, [%4];" : "=r"(v.x), "=r"(v.y), "=r"(v.z), "=r"(v.w) : "r"(a) : "memory"); return v; }
__device__ __forceinline__ void sts16(uint32_t a, uint32_t v) { asm volatile("st.shared.u16 [%0], %1;" :: "r"(a), "h"((uint16_t)v) : "memory"); }
__device__ __forceinline__ void sts32(uint32_t a, uint32_t v) { asm volatile("st.shared.b32 [%0], %1;" :: "r"(a), "r"(v) : "memory"); }
__device__ __forceinline__ void sts64(uint32_t a, uint32_t x, uint32_t y) { asm volatile("st.shared.v2.b32 [%0], {%1,%2};" :: "r"(a), "r"(x), "r"(y) : "memory"); }
__device__ __forceinline__ void sts128(uint32_t a, uint32_t x, uint32_t y, uint32_t z, uint32_t w) { asm volatile("st.shared.v4.b32 [%0], {%1,%2,%3,%4};" :: "r"(a), "r"(x), "r"(y), "r"(z), "r"(w) : "memory"); }
__device__ __forceinline__ void ldsm4(uint32_t a, uint32_t& r0, uint32_t& r1, uint32_t& r2, uint32_t& r3) {
  asm volatile("ldmatrix.sync.aligned.m8n8.x4.shared.b16 {%0,%1,%2,%3}, [%4];" : "=r"(r0), "=r"(r1), "=r"(r2), "=r"(r3) : "r"(a) : "memory");
}
__device__ __forceinline__ void ldsm4t(uint32_t a, uint32_t& r0, uint32_t& r1, uint32_t& r2, uint32_t& r3) {
  asm volatile("ldmatrix.sync.aligned.m8n8.x4.trans.shared.b16 {%0,%1,%2,%3}, [%4];" : "=r"(r0), "=r"(r1), "=r"(r2), "=r"(r3) : "r"(a) : "memory");
}
__device__ __forceinline__ void stsm4t(uint32_t a, uint32_t r0, uint32_t r1, uint32_t r2, uint32_t r3) {
  asm volatile("stmatrix.sync.aligned.m8n8.x4.trans.shared.b16 [%0], {%1,%2,%3,%4};" :: "r"(a), "r"(r0), "r"(r1), "r"(r2), "r"(r3) : "memory");
}
__device__ __forceinline__ uint4 ldr128(const void* p) {
  unsigned long long lo, hi;
  asm volatile("{ .reg .b128 t; ld.relaxed.gpu.global.b128 t, [%2]; mov.b128 {%0, %1}, t; }" : "=l"(lo), "=l"(hi) : "l"(p) : "memory");
  return make_uint4((uint32_t)lo, (uint32_t)(lo >> 32), (uint32_t)hi, (uint32_t)(hi >> 32));
}
__device__ __forceinline__ void str128(void* p, uint32_t x, uint32_t y, uint32_t z, uint32_t w) {
  asm volatile("{ .reg .b128 t; .reg .b64 lo, hi; mov.b64 lo, {%1,%2}; mov.b64 hi, {%3,%4}; mov.b128 t, {lo, hi}; st.relaxed.gpu.global.b128 [%0], t; }"
               :: "l"(p), "r"(x), "r"(y), "r"(z), "r"(w) : "memory");
}
__device__ __forceinline__ uint32_t ldr32(const void* p) { uint32_t v; asm volatile("ld.relaxed.gpu.global.b32 %0, [%1];" : "=r"(v) : "l"(p) : "memory"); return v; }
__device__ __forceinline__ void str32(void* p, uint32_t v) { asm volatile("st.relaxed.gpu.global.b32 [%0], %1;" :: "l"(p), "r"(v) : "memory"); }
__device__ __forceinline__ void str16(void* p, uint32_t v) { asm volatile("st.relaxed.gpu.global.u16 [%0], %1;" :: "l"(p), "h"((uint16_t)v) : "memory"); }
__device__ __forceinline__ void bar_sync(int id, int n) { asm volatile("bar.sync %0, %1;" :: "r"(id), "r"(n) : "memory"); }
__device__ __forceinline__ void bar_arrive(int id, int n) { asm volatile("bar.arrive %0, %1;" :: "r"(id), "r"(n) : "memory"); }

__device__ __forceinline__ float bf_lo(uint32_t w) { return __uint_as_float(w << 16); }
__device__ __forceinline__ float bf_hi(uint32_t w) { return __uint_as_float(w & 0xFFFF0000u); }
__device__ __forceinline__ uint32_t pack_bf(float lo, float hi) { uint32_t r; asm("cvt.rn.bf16x2.f32 %0, %1, %2;" : "=r"(r) : "f"(hi), "f"(lo)); return r; }
__device__ __forceinline__ uint32_t pack_h(float lo, float hi) { uint32_t r; asm("cvt.rn.f16x2.f32 %0, %1, %2;" : "=r"(r) : "f"(hi), "f"(lo)); return r; }
__device__ __forceinline__ float bfr(float x) { return bf_lo(pack_bf(x, 0.f)); }
__device__ __forceinline__ uint32_t bf_sub2(uint32_t a, uint32_t b) { __nv_bfloat162 r = __hsub2(*(__nv_bfloat162*)&a, *(__nv_bfloat162*)&b); return *(uint32_t*)&r; }
__device__ __forceinline__ uint32_t bf_add2(uint32_t a, uint32_t b) { __nv_bfloat162 r = __hadd2(*(__nv_bfloat162*)&a, *(__nv_bfloat162*)&b); return *(uint32_t*)&r; }
__device__ __forceinline__ uint32_t bf_mul2(uint32_t a, uint32_t b) { __nv_bfloat162 r = __hmul2(*(__nv_bfloat162*)&a, *(__nv_bfloat162*)&b); return *(uint32_t*)&r; }
__device__ __forceinline__ float2 h2f(uint32_t w) { return __half22float2(*(__half2*)&w); }
__device__ __forceinline__ float ex2(float x) { float r; asm("ex2.approx.ftz.f32 %0, %1;" : "=f"(r) : "f"(x)); return r; }
__device__ __forceinline__ float warp_sum(float v) {
#pragma unroll
  for (int o = 16; o > 0; o >>= 1) v += __shfl_xor_sync(0xffffffffu, v, o);
  return v;
}
__device__ __forceinline__ void mma_bf16(float* d, uint32_t a0, uint32_t a1, uint32_t a2, uint32_t a3, uint32_t b0, uint32_t b1) {
  asm volatile("mma.sync.aligned.m16n8k16.row.col.f32.bf16.bf16.f32 {%0,%1,%2,%3}, {%4,%5,%6,%7}, {%8,%9}, {%0,%1,%2,%3};"
               : "+f"(d[0]), "+f"(d[1]), "+f"(d[2]), "+f"(d[3]) : "r"(a0), "r"(a1), "r"(a2), "r"(a3), "r"(b0), "r"(b1));
}
__device__ __forceinline__ void mma_bf16_k8(float* d, uint32_t a0, uint32_t a1, uint32_t b0) {
  asm volatile("mma.sync.aligned.m16n8k8.row.col.f32.bf16.bf16.f32 {%0,%1,%2,%3}, {%4,%5}, {%6}, {%0,%1,%2,%3};"
               : "+f"(d[0]), "+f"(d[1]), "+f"(d[2]), "+f"(d[3]) : "r"(a0), "r"(a1), "r"(b0));
}

__device__ __forceinline__ void wg_fence() { asm volatile("wgmma.fence.sync.aligned;" ::: "memory"); }
__device__ __forceinline__ void wg_commit() { asm volatile("wgmma.commit_group.sync.aligned;" ::: "memory"); }
template <int N> __device__ __forceinline__ void wg_wait() { asm volatile("wgmma.wait_group.sync.aligned %0;" :: "n"(N) : "memory"); }
template <int TB> __device__ __forceinline__ void wgmma32(float* d, const uint32_t* a, uint32_t dlo, uint32_t dhi) {
  asm volatile("{ .reg .b64 dd; mov.b64 dd, {%20, %21}; wgmma.mma_async.sync.aligned.m64n32k16.f32.f16.f16 "
               "{%0,%1,%2,%3,%4,%5,%6,%7,%8,%9,%10,%11,%12,%13,%14,%15}, {%16,%17,%18,%19}, dd, 1, 1, 1, %22; }"
               : "+f"(d[0]), "+f"(d[1]), "+f"(d[2]), "+f"(d[3]), "+f"(d[4]), "+f"(d[5]), "+f"(d[6]), "+f"(d[7]), "+f"(d[8]), "+f"(d[9]), "+f"(d[10]), "+f"(d[11]), "+f"(d[12]), "+f"(d[13]), "+f"(d[14]), "+f"(d[15])
               : "r"(a[0]), "r"(a[1]), "r"(a[2]), "r"(a[3]), "r"(dlo), "r"(dhi), "n"(TB));
}
template <int TB> __device__ __forceinline__ void wgmma64(float* d, const uint32_t* a, uint32_t dlo, uint32_t dhi) {
  asm volatile("{ .reg .b64 dd; mov.b64 dd, {%36, %37}; wgmma.mma_async.sync.aligned.m64n64k16.f32.f16.f16 "
               "{%0,%1,%2,%3,%4,%5,%6,%7,%8,%9,%10,%11,%12,%13,%14,%15,%16,%17,%18,%19,%20,%21,%22,%23,%24,%25,%26,%27,%28,%29,%30,%31}, {%32,%33,%34,%35}, dd, 1, 1, 1, %38; }"
               : "+f"(d[0]), "+f"(d[1]), "+f"(d[2]), "+f"(d[3]), "+f"(d[4]), "+f"(d[5]), "+f"(d[6]), "+f"(d[7]), "+f"(d[8]), "+f"(d[9]), "+f"(d[10]), "+f"(d[11]), "+f"(d[12]), "+f"(d[13]), "+f"(d[14]), "+f"(d[15]), "+f"(d[16]), "+f"(d[17]), "+f"(d[18]), "+f"(d[19]), "+f"(d[20]), "+f"(d[21]), "+f"(d[22]), "+f"(d[23]), "+f"(d[24]), "+f"(d[25]), "+f"(d[26]), "+f"(d[27]), "+f"(d[28]), "+f"(d[29]), "+f"(d[30]), "+f"(d[31])
               : "r"(a[0]), "r"(a[1]), "r"(a[2]), "r"(a[3]), "r"(dlo), "r"(dhi), "n"(TB));
}
template <int TB> __device__ __forceinline__ void wgmma64_init(float* d, const uint32_t* a, uint32_t dlo, uint32_t dhi) {
  asm volatile("{ .reg .b64 dd; mov.b64 dd, {%36, %37}; wgmma.mma_async.sync.aligned.m64n64k16.f32.f16.f16 "
               "{%0,%1,%2,%3,%4,%5,%6,%7,%8,%9,%10,%11,%12,%13,%14,%15,%16,%17,%18,%19,%20,%21,%22,%23,%24,%25,%26,%27,%28,%29,%30,%31}, {%32,%33,%34,%35}, dd, 0, 1, 1, %38; }"
               : "=f"(d[0]), "=f"(d[1]), "=f"(d[2]), "=f"(d[3]), "=f"(d[4]), "=f"(d[5]), "=f"(d[6]), "=f"(d[7]), "=f"(d[8]), "=f"(d[9]), "=f"(d[10]), "=f"(d[11]), "=f"(d[12]), "=f"(d[13]), "=f"(d[14]), "=f"(d[15]), "=f"(d[16]), "=f"(d[17]), "=f"(d[18]), "=f"(d[19]), "=f"(d[20]), "=f"(d[21]), "=f"(d[22]), "=f"(d[23]), "=f"(d[24]), "=f"(d[25]), "=f"(d[26]), "=f"(d[27]), "=f"(d[28]), "=f"(d[29]), "=f"(d[30]), "=f"(d[31])
               : "r"(a[0]), "r"(a[1]), "r"(a[2]), "r"(a[3]), "r"(dlo), "r"(dhi), "n"(TB));
}
template <int TB> __device__ __forceinline__ void wgmma32_init(float* d, const uint32_t* a, uint32_t dlo, uint32_t dhi) {
  asm volatile("{ .reg .b64 dd; mov.b64 dd, {%20, %21}; wgmma.mma_async.sync.aligned.m64n32k16.f32.f16.f16 "
               "{%0,%1,%2,%3,%4,%5,%6,%7,%8,%9,%10,%11,%12,%13,%14,%15}, {%16,%17,%18,%19}, dd, 0, 1, 1, %22; }"
               : "=f"(d[0]), "=f"(d[1]), "=f"(d[2]), "=f"(d[3]), "=f"(d[4]), "=f"(d[5]), "=f"(d[6]), "=f"(d[7]), "=f"(d[8]), "=f"(d[9]), "=f"(d[10]), "=f"(d[11]), "=f"(d[12]), "=f"(d[13]), "=f"(d[14]), "=f"(d[15])
               : "r"(a[0]), "r"(a[1]), "r"(a[2]), "r"(a[3]), "r"(dlo), "r"(dhi), "n"(TB));
}
__device__ __forceinline__ void wgmma64h(uint32_t* d, uint32_t a0, uint32_t a1, uint32_t a2, uint32_t a3, uint32_t dlo, uint32_t dhi) {
  asm volatile("{ .reg .b64 dd; mov.b64 dd, {%20, %21}; wgmma.mma_async.sync.aligned.m64n64k16.f16.f16.f16 "
               "{%0,%1,%2,%3,%4,%5,%6,%7,%8,%9,%10,%11,%12,%13,%14,%15}, {%16,%17,%18,%19}, dd, 1, 1, 1, 0; }"
               : "+r"(d[0]), "+r"(d[1]), "+r"(d[2]), "+r"(d[3]), "+r"(d[4]), "+r"(d[5]), "+r"(d[6]), "+r"(d[7]), "+r"(d[8]), "+r"(d[9]), "+r"(d[10]), "+r"(d[11]), "+r"(d[12]), "+r"(d[13]), "+r"(d[14]), "+r"(d[15])
               : "r"(a0), "r"(a1), "r"(a2), "r"(a3), "r"(dlo), "r"(dhi));
}
__device__ __forceinline__ void wgmma64h_init(uint32_t* d, uint32_t a0, uint32_t a1, uint32_t a2, uint32_t a3, uint32_t dlo, uint32_t dhi) {
  asm volatile("{ .reg .b64 dd; mov.b64 dd, {%20, %21}; wgmma.mma_async.sync.aligned.m64n64k16.f16.f16.f16 "
               "{%0,%1,%2,%3,%4,%5,%6,%7,%8,%9,%10,%11,%12,%13,%14,%15}, {%16,%17,%18,%19}, dd, 0, 1, 1, 0; }"
               : "=r"(d[0]), "=r"(d[1]), "=r"(d[2]), "=r"(d[3]), "=r"(d[4]), "=r"(d[5]), "=r"(d[6]), "=r"(d[7]), "=r"(d[8]), "=r"(d[9]), "=r"(d[10]), "=r"(d[11]), "=r"(d[12]), "=r"(d[13]), "=r"(d[14]), "=r"(d[15])
               : "r"(a0), "r"(a1), "r"(a2), "r"(a3), "r"(dlo), "r"(dhi));
}
__device__ __forceinline__ void wgmma40_ss(float* d, uint32_t alo, uint32_t blo, uint32_t hi) {
  asm volatile("{ .reg .b64 da, db; mov.b64 da, {%20, %22}; mov.b64 db, {%21, %22}; "
               "wgmma.mma_async.sync.aligned.m64n40k16.f32.f16.f16 {%0,%1,%2,%3,%4,%5,%6,%7,%8,%9,%10,%11,%12,%13,%14,%15,%16,%17,%18,%19}, da, db, 1, 1, 1, 1, 1; }"
               : "+f"(d[0]), "+f"(d[1]), "+f"(d[2]), "+f"(d[3]), "+f"(d[4]), "+f"(d[5]), "+f"(d[6]), "+f"(d[7]), "+f"(d[8]), "+f"(d[9]), "+f"(d[10]), "+f"(d[11]), "+f"(d[12]), "+f"(d[13]), "+f"(d[14]), "+f"(d[15]), "+f"(d[16]), "+f"(d[17]), "+f"(d[18]), "+f"(d[19])
               : "r"(alo), "r"(blo), "r"(hi));
}
__device__ __forceinline__ void wgmma40_ss_init(float* d, uint32_t alo, uint32_t blo, uint32_t hi) {
  asm volatile("{ .reg .b64 da, db; mov.b64 da, {%20, %22}; mov.b64 db, {%21, %22}; "
               "wgmma.mma_async.sync.aligned.m64n40k16.f32.f16.f16 {%0,%1,%2,%3,%4,%5,%6,%7,%8,%9,%10,%11,%12,%13,%14,%15,%16,%17,%18,%19}, da, db, 0, 1, 1, 1, 1; }"
               : "=f"(d[0]), "=f"(d[1]), "=f"(d[2]), "=f"(d[3]), "=f"(d[4]), "=f"(d[5]), "=f"(d[6]), "=f"(d[7]), "=f"(d[8]), "=f"(d[9]), "=f"(d[10]), "=f"(d[11]), "=f"(d[12]), "=f"(d[13]), "=f"(d[14]), "=f"(d[15]), "=f"(d[16]), "=f"(d[17]), "=f"(d[18]), "=f"(d[19])
               : "r"(alo), "r"(blo), "r"(hi));
}
__device__ __forceinline__ void tma_box(uint32_t dst, const CUtensorMap* tm, uint32_t mb, int x, int y) {
  asm volatile("cp.async.bulk.tensor.2d.shared::cluster.global.mbarrier::complete_tx::bytes [%0], [%1, {%3, %4}], [%2];"
               :: "r"(dst), "l"(tm), "r"(mb), "r"(x), "r"(y) : "memory");
}
__device__ __forceinline__ uint32_t uni(uint32_t v) {
  uint32_t r; asm volatile("shfl.sync.idx.b32 %0, %1, 0, 0x1f, 0xffffffff;" : "=r"(r) : "r"(v)); return r;
}
__device__ __forceinline__ uint32_t pin(uint32_t v) {
  uint32_t r; asm volatile("shfl.sync.bfly.b32 %0, %1, 0, 0x1f, 0xffffffff;" : "=r"(r) : "r"(v)); return r;
}

struct Params {
  const unsigned char* x;
  Scratch* s;
  int off[8];
  uint32_t* out;
  const uint16_t* dskip;
  const uint32_t* w_r;
  long long* ts;
  const unsigned char* far[7];
  uint32_t sched[2][17];
};
__device__ __forceinline__ uint32_t ldnc32(const void* p) { uint32_t v; asm volatile("ld.global.nc.b32 %0, [%1];" : "=r"(v) : "l"(p)); return v; }
__device__ __forceinline__ uint32_t ldnc16(const void* p) { uint16_t v; asm volatile("ld.global.nc.u16 %0, [%1];" : "=h"(v) : "l"(p)); return v; }
__device__ __forceinline__ void mbar_wait(uint32_t mb, uint32_t ph = 0) {
#pragma unroll 1
  for (int it = 0; it < SPIN_MAX; it++) {
    uint32_t ok;
    asm volatile("{ .reg .pred q; mbarrier.try_wait.parity.shared::cta.b64 q, [%1], %2; selp.u32 %0, 1, 0, q; }" : "=r"(ok) : "r"(mb), "r"(ph) : "memory");
    if (ok) break;
  }
}
__device__ __forceinline__ void mbar_arrive(uint32_t mb) { asm volatile("mbarrier.arrive.shared::cta.b64 _, [%0];" :: "r"(mb) : "memory"); }
__device__ __forceinline__ void fence_async() { asm volatile("fence.proxy.async.shared::cta;" ::: "memory"); }
#define SPIN_WHILE(cond, body) _Pragma("unroll 1") for (int _it = 0; _it < SPIN_MAX && __any_sync(0xffffffffu, (cond)); _it++) { body; }

struct LnC { uint32_t m2, rh2, rl2; };
__device__ __forceinline__ LnC ln_consts(float s, float q, float& r) {
  const float mean = s * (1.f / DM);
  const float var = fmaxf(fmaf(-mean, mean, q * (1.f / DM)), 0.f);
  float sd;
  asm("sqrt.approx.ftz.f32 %0, %1;" : "=f"(sd) : "f"(bfr(bfr(var) + 1e-5f)));
  asm("rcp.approx.ftz.f32 %0, %1;" : "=f"(r) : "f"(bfr(sd)));
  LnC c;
  c.m2 = pack_bf(mean, mean);
  c.rh2 = pack_bf(r, r);
  const float rl = r - bf_lo(c.rh2);
  c.rl2 = pack_bf(rl, rl);
  return c;
}
__device__ __forceinline__ uint32_t bf_fma2(uint32_t a, uint32_t b, uint32_t c) {
  __nv_bfloat162 r = __hfma2(*(const __nv_bfloat162*)&a, *(const __nv_bfloat162*)&b, *(const __nv_bfloat162*)&c);
  return *(uint32_t*)&r;
}
__device__ __forceinline__ uint32_t ln_apply(uint32_t w, uint32_t m2, uint32_t rh2, uint32_t rl2) {
  const uint32_t d = bf_sub2(w, m2);
  return bf_fma2(d, rh2, bf_mul2(d, rl2));
}

__device__ __forceinline__ float2 cis(float mag_log2, float rev) {
  const float m = ex2(mag_log2), ang = rev * 6.283185307179586f;
  return make_float2(m * __cosf(ang), m * __sinf(ang));
}
__device__ __forceinline__ float2 csq(float2 a) { return make_float2(fmaf(a.x, a.x, -a.y * a.y), (a.x + a.x) * a.y); }
__device__ __forceinline__ float2 cmul(float2 a, float2 b) { return make_float2(fmaf(a.x, b.x, -a.y * b.y), fmaf(a.x, b.y, a.y * b.x)); }
__device__ __forceinline__ void pmul(uint32_t xr, uint32_t xi, uint32_t w, uint32_t& yr, uint32_t& yi) {
  const __half2 XR = *(__half2*)&xr, XI = *(__half2*)&xi, W = *(__half2*)&w;
  const __half2 a = __hfma2(__hneg2(XI), __high2half2(W), __hmul2(XR, __low2half2(W)));
  const __half2 b = __hfma2(XI, __low2half2(W), __hmul2(XR, __high2half2(W)));
  yr = *(const uint32_t*)&a; yi = *(const uint32_t*)&b;
}
__device__ __forceinline__ uint32_t pk(float2 a) { return pack_h(a.x, a.y); }

struct KgState { float2 c0, z8; float kl; uint32_t w64, w128, w192; };
__device__ __forceinline__ void kgen_tables_n(const uint32_t (&raw)[7], uint32_t scr, int wt, KgState& k) {
  const uint32_t dst = scr + 16384 + wt * 16;
  const float dt = bfr(ex2(bf_lo(raw[6]) * 1.4426950408889634f));
  const float th = dt * bf_lo(raw[1]);
  const float br = dt * bf_lo(raw[2]), bi = dt * bf_lo(raw[3]);
  const float Cr = bf_lo(raw[4]), Ci = bf_lo(raw[5]);
  k.c0 = make_float2(fmaf(Cr, br, -Ci * bi), fmaf(Cr, bi, Ci * br));
  const uint32_t mx = __reduce_max_sync(0xffffffffu, __float_as_uint(fmaxf(fabsf(k.c0.x), fabsf(k.c0.y))));
  const float a2 = dt * bf_lo(raw[0]) * 1.4426950408889634f;
  const float rh = th * 0.15915494309189535f;
  const float rl = fmaf(th, (float)(0.15915494309189535 - (double)0.15915494309189535f), fmaf(th, 0.15915494309189535f, -rh));
  const float rf = rh - rintf(rh);
  const float2 z1 = cis(a2, rf + rl);
  const float p64 = rf * 64.f;
  const float2 z64 = cis(a2 * 64.f, fmaf(64.f, rl, p64 - rintf(p64)));
  const float2 z2 = csq(z1), z128 = csq(z64), z3 = cmul(z2, z1), z4 = csq(z2), z256 = csq(z128), z6 = csq(z3), z512 = csq(z256);
  k.z8 = csq(z4);
  k.w64 = pk(z64); k.w128 = pk(z128); k.w192 = pk(cmul(z128, z64));
  sts128(dst, 0x00003C00u, pk(z2), pk(z4), pk(z6));
  const float2 z1024 = csq(z512), z768 = cmul(z512, z256);
  sts128(dst + 2048, pk(z1), pk(z3), pk(cmul(z4, z1)), pk(cmul(z4, z3)));
  const float2 z2048 = csq(z1024);
  k.kl = fmaf(k.c0.x, z2048.x, -k.c0.y * z2048.y);
  sts128(dst + 4096, pk(z256), pk(cmul(z256, z2)), pk(cmul(z256, z4)), pk(cmul(z256, z6)));
  sts128(dst + 6144, pk(z512), pk(cmul(z512, z4)), pk(z768), pk(cmul(z768, z4)));
  sts128(dst + 8192, pk(z1024), pk(cmul(z1024, z256)), pk(cmul(z1024, z512)), pk(cmul(z1024, z768)));
  sts32(scr + W_MISC + (wt >> 5) * 4, mx);
}
__device__ __forceinline__ int kgen_tables_m(uint32_t scr, int wt, const KgState& k) {
  const uint32_t dst = scr + wt * 16;
  const uint4 e4 = lds128(scr + W_MISC);
  const float2 z16 = csq(k.z8), z32 = csq(z16);
  const int em = max(min((int)(max(max(e4.x, e4.y), max(e4.z, e4.w)) >> 23), 238), 16);
  const float sc = __uint_as_float((uint32_t)(127 + 4 + 127 - em) << 23);
  sts32(scr + W_MISC + 16 + (wt >> 5) * 4, __reduce_add_sync(0xffffffffu, __float2int_rn(k.kl * sc * 262144.f)));
  const float2 c0 = make_float2(k.c0.x * sc, k.c0.y * sc);
  const float2 c1 = cmul(c0, k.z8), c2 = cmul(c0, z16), c4 = cmul(c0, z32), c3 = cmul(c1, z16), c5 = cmul(c1, z32), c6 = cmul(c2, z32), c7 = cmul(c3, z32);
  uint32_t pr[4], pi[4], yr[4], yi[4];
  pr[0] = pack_h(c0.x, c1.x); pi[0] = pack_h(c0.y, c1.y);
  pr[1] = pack_h(c2.x, c3.x); pi[1] = pack_h(c2.y, c3.y);
  pr[2] = pack_h(c4.x, c5.x); pi[2] = pack_h(c4.y, c5.y);
  pr[3] = pack_h(c6.x, c7.x); pi[3] = pack_h(c6.y, c7.y);
  sts128(dst, pr[0], pr[1], pr[2], pr[3]); sts128(dst + 2048, pi[0], pi[1], pi[2], pi[3]);
#pragma unroll
  for (int q = 1; q < 4; q++) {
    const uint32_t w = q == 1 ? k.w64 : q == 2 ? k.w128 : k.w192;
#pragma unroll
    for (int i = 0; i < 4; i++) pmul(pr[i], pi[i], w, yr[i], yi[i]);
    sts128(dst + q * 4096, yr[0], yr[1], yr[2], yr[3]); sts128(dst + q * 4096 + 2048, yi[0], yi[1], yi[2], yi[3]);
  }
  return em;
}
__device__ __forceinline__ uint32_t lds32_if(uint32_t a, bool on) {
  uint32_t v; asm volatile("{ .reg .pred q; setp.ne.u32 q, %2, 0; mov.b32 %0, 0; @q ld.shared.b32 %0, [%1]; }" : "=r"(v) : "r"(a), "r"((uint32_t)on) : "memory"); return v;
}
__device__ __forceinline__ uint32_t prmt(uint32_t a, uint32_t b, uint32_t s) { uint32_t r; asm("prmt.b32 %0, %1, %2, %3;" : "=r"(r) : "r"(a), "r"(b), "r"(s)); return r; }
__device__ __forceinline__ void kgen_build(uint32_t tb, int wg, int wt, uint32_t k0, uint32_t k1, uint32_t k2) {
  const uint32_t kt = tb + W_KT, sc = tb + W_L3 + 3072;
  const int ix = ((wt >> 2) + (wt & 3) * 32 - 1) & 127;
  const uint32_t a3 = tb + W_CW + 32 + ((ix & 1) ? 0 : 304) + (ix >> 1) * 4, a2 = sc + 544 + (wt & ~3) * 2 + (wt & 1) * 4 + (wt & 2) * 128;
  const uint32_t v3 = wt ? k2 : k2 >> 16;
  sts32(sc + 4 + wt * 4, __byte_perm(k0, k1, 0x5432));
  sts16(a2, k1 >> 16); sts16(a2 + 6, k1 >> 16);
  sts16(a3, v3); sts16(a3 + 6, v3);
  if ((unsigned)(wt - 32) < 14u) sts128(kt + (wt < 36 ? -512 : 64 + 4128 - 576) + wt * 16, 0, 0, 0, 0);
  if (wt == 127) sts32(sc, k0 & 0xFFFF0000u);
  if (wt == 0) { sts32(sc + 516, k1); sts16(sc + 1056, k2); }
  bar_sync(1 + wg, 128);
  const uint32_t cw = tb + W_CW + 32 + (wt >> 6) * 48 + wt * 4, g2 = sc + 540 + wt * 4;
  const bool odd = wt & 1, ends = (unsigned)(wt - 4) >= 120u;
  const uint32_t pv = lds32(sc + wt * 4), nx = lds32(sc + 8 + wt * 4), nc = lds32_if(g2 + 8, ends);
  const uint32_t l0 = lds32(cw), l1 = lds32(cw - 8), l2 = lds32(cw - 16), l3 = lds32(cw - 24), q0 = lds32(g2), q1 = lds32(g2 + 128), q2 = lds32(g2 - 8), q3 = lds32(g2 + 120);
  sts64(kt + 64 + wt * 8, __byte_perm(k0, pv, 0x5410), __byte_perm(k0, 0, 0x1032));
  sts64(kt + 64 + 1024 + wt * 8, __byte_perm(k1, pv, (odd || wt == 0) ? 0x7610 : 0x1010), __byte_perm(k1, nx, odd ? 0x1076 : 0x1010));
  const uint32_t cc = __byte_perm(nc, 0, 0x3232), nn = __byte_perm(nc, 0, 0x1010);
  if (ends) sts128(kt + 64 + 2048 + wt * 16, cc, cc, odd ? nc : cc, odd ? nn : nc);
  if (wt == 127) { sts128(kt + 64 + 4096, nn, nn, nn, nn); sts128(kt + 64 + 4112, nn, nn << 16, 0, 0); }
  sts128(tb + W_L3 + 512 + (wt >> 6) * 512 + wt * 16, l0, l1, l2, l3);
  if ((wt & 63) < 34) sts128(tb + W_QT - 16 + wt * 16, q0, q1, q2, q3);
}

__device__ __forceinline__ void load_a(uint32_t (&a)[4], uint32_t kp, int j) {
  a[0] = lds32(kp + 64 * j); a[1] = lds32(kp + 64 * j + 512); a[2] = lds32(kp + 64 * j - 32); a[3] = lds32(kp + 64 * j + 480);
}
__device__ __forceinline__ uint32_t band(int d, int lo, int hi) {
  return ((unsigned)(d - lo) <= (unsigned)(hi - lo) ? 1u : 0u) | ((unsigned)(d - 1 - lo) <= (unsigned)(hi - lo) ? 0x10000u : 0u);
}
__device__ __forceinline__ uint32_t hadd2u(uint32_t a, uint32_t b) { __half2 r = __hadd2(*(__half2*)&a, *(__half2*)&b); return *(uint32_t*)&r; }

__device__ __forceinline__ void zero_pads(uint32_t tb, int wt) {
  if (!(wt & 32)) sts128(tb + W_L3 + (wt >> 6) * 512 + wt * 16, 0, 0, 0, 0);
  if ((wt & 63) < 3) sts128(tb + W_CW + (wt >> 6) * 304 + (wt & 63) * 16, 0, 0, 0, 0);
}
__device__ __forceinline__ uint32_t tr_base(int lane) {
  return OFF_YT + (2 * (lane >> 3) + (lane & 1)) * YT_PITCH + ((lane >> 1) & 1) * (8 * YT_PITCH + 64) + ((lane >> 2) & 1) * 16;
}

__device__ __forceinline__ uint32_t sc_addr(int tp) { return OFF_YT + (tp < 16 ? tp * YT_PITCH + (tp >> 3) * 64 + 1152 : 8 * YT_PITCH - 512 + tp * 32); }
#define X_PW 15
#define X_HU 16
#define X_NE 2
#define X_SCT 10000
#define X_DELTA 0
#define X_DSTEP 2000
#define X_PF0 2700
#define X_PFD 600
#define X_TD 450
#define X_WS 6
#define X_OR 8
#define X_ABS 4950
#define X_XD 200
#define X_RD 630
#define X_HD 450
#define X_PD 1170
#define X_PROMO 2
#define X_YD2 1000
#define X_GO 1
#define X_GW 2
#define X_NS 4300
#define X_XS 13450
#define X_LAG 1300
#define X_YD 1550
struct TMaps { CUtensorMap m[10]; };
__device__ __forceinline__ uint32_t h2bf(uint32_t w) { const float2 f = h2f(w); return pack_bf(f.x, f.y); }
__device__ __forceinline__ uint32_t keep(uint32_t v) { asm volatile("" : "+r"(v)); return v; }
__device__ __forceinline__ uint2 ldr64(const void* p) { uint2 v; asm volatile("{ .reg .b64 t; ld.relaxed.gpu.global.b64 t, [%2]; mov.b64 {%0, %1}, t; }" : "=r"(v.x), "=r"(v.y) : "l"(p) : "memory"); return v; }
__host__ __device__ __forceinline__ uint32_t down_box(int s, bool five) {
  return five ? OFF_W + W_BYTES + 12288 + (s / 3) * (W_BYTES - 12288) + s * 4096 : s < 6 ? OFF_W + W_BYTES + BOX + (s >> 1) * (W_BYTES - 10240) + s * 5120 : OFF_W + (s - 6) * 5120;
}
__device__ __forceinline__ void load_tile(const CUtensorMap* tmx, int i, int c, int again = 0) {
  asm volatile("mbarrier.arrive.expect_tx.shared::cta.b64 _, [%0], 8704;" :: "r"(MB_UL + i * 16 + again) : "memory");
  asm volatile("cp.async.bulk.tensor.3d.shared::cluster.global.mbarrier::complete_tx::bytes [%0], [%1, {%3, %4, %5}], [%2];"
               :: "r"(i < 2 ? OFF_T + i * TILE : OFF_W), "l"(tmx), "r"(MB_UL + i * 16 + again), "r"(0), "r"(c), "r"(-8) : "memory");
}
template <bool FAR> __device__ __forceinline__ void load_params(const Params& p, uint32_t ch, int wt, uint32_t dst, bool on) {
  const int rel = wt < 96 ? ch * 16 + (wt & 15) : ch >> 3;
  const unsigned char* b = FAR ? p.far[min(wt >> 4, 6)] + rel * 16 : p.x + (long long)(p.off[wt >> 4] + rel) * 16;
  asm volatile("{ .reg .pred q; setp.ne.u32 q, %2, 0; @q cp.async.cg.shared.global [%0], [%1], 16; }"
               :: "r"(dst + wt * 16), "l"(b), "r"((uint32_t)(on && wt < 97)) : "memory");
}

struct ConvC { uint32_t ca, cb, bands, qa; };
__device__ __forceinline__ ConvC conv_consts(int w, int lane) {
  const int h = w & 1, P = (w >> 1) & 1, d0 = 8 * h + (lane >> 2) - 2 * (lane & 3);
  ConvC k;
  k.ca = keep((W_KT + (16 + 256 * P + d0) * 4) | (((8 + 64 * P + lane) * 64 + (((h + ((w >> 1) & 2)) ^ (lane >> 1)) & 3) * 16) << 16));
  const int u = d0 + 2 * (lane & 1) + 2, in = (u & 7) - ((u & 7) >= 5 ? 5 : 0) - 2 * (lane & 1);
  k.cb = keep(in > 0 ? 0x1010 : in == 0 ? 0x3210 : 0x3232);
  k.qa = keep(W_QT + (2 * (u >> 3) + ((u & 7) >= 5) + 64 * P) * 16);
  k.bands = keep(band(d0, 12, 20) + 2 * band(d0 + 8, 12, 20) + 4 * band(d0 + 16, 12, 20) + 8 * band(d0 + 24, 12, 20)
                 + 16 * band(d0 - 8, 5, 11) + 32 * band(d0, 5, 11) + 64 * band(d0 + 8, 5, 11) + 128 * band(d0 + 16, 5, 11));
  return k;
}
struct ConvPre { uint32_t e0, e2, f2, b0, b2, a[3][4]; };
__device__ __forceinline__ void conv_pre(ConvPre& r, uint32_t kp, uint32_t qp, int part, bool on, bool P) {
  if (part & 1) {
    r.e0 = lds32_if(kp + 4096, on && !P); r.e2 = lds32_if(kp + 4064, on && !P); r.f2 = lds32_if(kp + 4128, on && !P);
    r.b0 = lds32_if(kp + 2048, on && !P); r.b2 = lds32_if(kp + 2016, on && !P);
  }
#pragma unroll
  for (int j = 0; j < 3; j++) if (part & (j < 1 ? 1 : 2))
    asm volatile("{ .reg .pred q; setp.ne.u32 q, %5, 0; mov.b32 %0, 0; mov.b32 %1, 0; mov.b32 %2, 0; mov.b32 %3, 0; @q ld.shared.v4.b32 {%0,%1,%2,%3}, [%4]; }"
                 : "=r"(r.a[j][0]), "=r"(r.a[j][1]), "=r"(r.a[j][2]), "=r"(r.a[j][3]) : "r"(qp + 64 * j), "r"((uint32_t)on) : "memory");
}
__device__ __forceinline__ void conv_item(uint32_t tb, uint32_t tl, int bid, int bn, ConvPre& pre, const ConvC& cv, uint32_t zero, const CUtensorMap* tmx, int ch, int warp, int lane, bool hold, bool more) {
  const bool go = more && warp == 0 && lane == 0;
  const uint32_t kp = tb + (cv.ca & 0xFFFFu), qp = tb + cv.qa;
  const uint32_t dlo = (tl >> 4) + 32 + ((warp >> 1) & 2) + (1u << 16), dhi = 32u | (2u << 30);
  const bool P = warp & 2;
  float a32[16], b32[16], a64[32];
  uint32_t A[40][4];
#define STEP(J) { wgmma64<0>(a64, A[J], dlo + 256 - 4 * (J), dhi); \
    if ((J) == 32) wgmma32_init<0>(b32, A[J], dlo, dhi); else wgmma32<0>(b32, A[J], ((J) < 8 ? dlo ^ zero : dlo) + 128 - 4 * (J), dhi); \
    if ((J) == 0) wgmma32_init<0>(a32, A[J], dlo, dhi); else if ((J) < 8) wgmma32<0>(a32, A[J], (dlo ^ zero) - 4 * (J), dhi); }
#define LD(J) load_a(A[J], kp, J);
#define LQ(J) { const uint4 v = lds128(qp + 64 * ((J) - 32)); A[J][0] = v.x; A[J][1] = v.y; A[J][2] = v.z; A[J][3] = v.w; }
#define PQ(J) { A[J][0] = prmt(A[J][0], 0, cv.cb); A[J][1] = prmt(A[J][1], 0, cv.cb); A[J][2] = prmt(A[J][2], 0, cv.cb); A[J][3] = prmt(A[J][3], 0, cv.cb); }
#define FIRST(J) wg_fence(); STEP(J) wg_commit(); wg_wait<1>(); wg_fence();
  {
    uint32_t win[16], x9[4], x7[4], e[4], f[4];
    const uint32_t bz = keep(cv.bands);
#define BAND(i) keep((bz & (0x10001u << (i))) * (0x3C00u >> (i)))
    e[0] = pre.e0; e[2] = pre.e2; e[1] = keep(bz & 0x100u); e[3] = keep(bz & 0x200u);
    f[2] = pre.f2; f[0] = keep(bz & 0x4000u); f[1] = keep(bz & 0x8000u); f[3] = keep(bz & 0x300u);
#pragma unroll
    for (int j = 0; j < 12; j++) A[32 + j / 4][j & 3] = pre.a[j / 4][j & 3];
    PQ(32) PQ(33) PQ(34)
    if (!P) { A[32][0] = pre.b0; A[32][2] = pre.b2; }
    const uint32_t q[12] = {BAND(0), BAND(5), keep(bz & 0x400u), BAND(4), BAND(2), BAND(7), BAND(1), BAND(6), keep(bz & 0x800u), keep(bz & 0x1000u), BAND(3), keep(bz & 0x2000u)};
#undef BAND
    const uint32_t ta = keep(tl + 512 + (warp & 3) * 2048 + lane * 64 + (lane & 6) * 8);
    if (X_GO && hold) mbar_wait(MB_GO);
    uint32_t mbl = MB_UL + (warp & 8) * 2, ph = 0;
#pragma unroll 1
    for (int it = 0; it < SPIN_MAX; it++) {
      if (ch < 512) mbar_wait(mbl, ph);
      if (it == 1) TS(13);
      TS(3);
      wg_fence();
      wgmma64h_init(win, q[0], q[1], q[2], q[3], dlo, dhi);
      wgmma64h(win, q[4], q[5], q[6], q[7], dlo - 4, dhi);
      wgmma64h(win, q[8], q[9], q[10], q[11], dlo - 8, dhi);
      wg_commit();
      wgmma64_init<0>(a64, e, dlo, dhi);
      wgmma64<0>(a64, f, dlo - 4, dhi);
      wg_commit();
      if (ch >= 512) break;
      uint32_t r0, r1, r2, r3, ok;
      if (warp & 4) {
        mbar_wait(mbl + 8);
        if (__all_sync(0xffffffffu, it || lds32(MISC_RT + (warp & 8)) == 0)) break;
        wg_wait<0>();
        continue;
      }
      ldsm4(ta, r0, r1, r2, r3);
      ok = r0 & r1 & r2 & r3;
      ldsm4(ta ^ 32, r0, r1, r2, r3);
      asm volatile("{ .reg .pred q; setp.ne.u32 q, %1, 0; barrier.red.and.pred q, %2, 128, q; selp.u32 %0, 1, 0, q; }" : "=r"(ok) : "r"((ok & r0 & r1 & r2 & r3 & 1u) | (lane & 3)), "r"(1 + (warp >> 2)) : "memory");
      if (ok) { if ((warp & 3) == 0 && lane == 0) { sts32(MISC_RT + warp, it); mbar_arrive(MB_UL + 8 + warp * 2); } break; }
      wg_wait<0>();
      if ((warp & 3) == 0 && lane == 0) load_tile(tmx - 1, warp >> 3, ch, 56);
      mbl = MB_UL + 56 + (warp & 8) * 2; ph = it & 1;
    }
    wg_wait<1>();
#pragma unroll
    for (int i = 0; i < 4; i++) {
      const int tl = 2 * ((i & 1) + ((i & 2) ? 0 : 4));
      x9[i] = P ? win[tl + 4] : win[tl]; x7[i] = P ? win[tl + 5] : win[tl + 1];
    }
    const uint32_t l3lo = ((tb + W_L3) >> 4) + (32u << 16);
    wg_fence();
    wgmma64<0>(a64, x9, l3lo, 8);
    wgmma64<0>(a64, x7, l3lo + 96, 8);
    wg_commit();
  }
  STEP(32) STEP(33) STEP(34) wg_commit(); wg_wait<1>();
  LQ(35) LQ(36) LQ(37) LQ(38) PQ(35) PQ(36) PQ(37) PQ(38)
  FIRST(35) STEP(36) STEP(37) STEP(38) wg_commit();
  LQ(39) LD(0) PQ(39)
  TS(17);
  if (X_GO == 1 && go) mbar_arrive(MB_GO);
  FIRST(39) STEP(0) wg_commit();
  LD(1) LD(2) LD(3)
  FIRST(1) STEP(2) STEP(3) wg_commit();
  LD(4) LD(5)
  if (X_GO == 2 && go) mbar_arrive(MB_GO);
  FIRST(4) STEP(5) wg_commit();
  LD(6) LD(7)
  wg_fence(); STEP(6) STEP(7) wg_commit();
#undef STEP
#undef LD
#undef LQ
#undef PQ
#undef FIRST
  TS(18);
  if (X_GO == 3 && go) mbar_arrive(MB_GO);
  const uint32_t xc = tb + W_KT + (warp & 3) * 1024 + lane * 16;
  if (more) bar_sync(7, 288);
  wg_wait<1>();
  conv_pre(pre, kp + ALT, qp + ALT, 1, more, P);
  wg_wait<0>();
  conv_pre(pre, kp + ALT, qp + ALT, 2, more, P);
  uint32_t E[16], o[8];
#define ACC(i) ((i) < 16 ? a32[i] : (i) < 32 ? b32[(i) - 16] : a64[(i) - 32])
  E[0] = pack_h(a32[0], a32[1]);
#pragma unroll
  for (int i = 1; i < 16; i++) E[i] = pack_h(ACC(4 * i) + ACC(4 * i - 2), ACC(4 * i + 1) + ACC(4 * i - 1));
#undef ACC
#pragma unroll
  for (int j = 0; j < 8; j++) o[j] = P ? (j < 2 ? 0u : E[j - 2]) : E[8 + j];
  sts128(xc, o[0], o[1], o[2], o[3]); sts128(xc + 512, o[4], o[5], o[6], o[7]);
#pragma unroll
  for (int j = 0; j < 8; j++) o[j] = P ? E[6 + j] : E[j];
  TS(25);
  if (more) {
    sts128(xc + 4096, o[0], o[1], o[2], o[3]); sts128(xc + 4608, o[4], o[5], o[6], o[7]);
    bar_arrive(12, 192);
    return;
  }
  bar_sync(1 + (warp >> 2), 128);
  const uint4 vv[2] = {lds128(xc + (P ? -2048 : 2048)), lds128(xc + (P ? -1536 : 2560))};
  const uint32_t mk = lane < 8 ? 0xFFFEFFFEu : ~0u;
#pragma unroll
  for (int q = 0; q < 2; q++) {
    const uint4 v = vv[q];
    stsm4t(tl + (cv.ca >> 16) + q * 2048, hadd2u(o[4 * q], v.x) & mk, hadd2u(o[4 * q + 1], v.y) & mk, hadd2u(o[4 * q + 2], v.z) & mk, hadd2u(o[4 * q + 3], v.w) & mk);
  }
  fence_async();
  bar_sync(bid, bn);
  if (warp == 0 && lane == 0) mbar_arrive(MB_REL);
  if ((warp & 7) == (ch < 512 ? 7 : 3) && lane == 0) {
    asm volatile("cp.async.bulk.tensor.3d.global.shared::cta.bulk_group [%0, {%3, %2, %3}], [%1];" :: "l"(tmx), "r"(tl + 512), "r"(ch), "r"(0) : "memory");
    asm volatile("cp.async.bulk.commit_group;" ::: "memory");
  }
}

template <bool FAR> __global__ void __launch_bounds__(NT, 1)
fused_kernel(const __grid_constant__ Params p, const __grid_constant__ TMaps tm) {
  extern __shared__ __align__(1024) unsigned char smem[];
  const int c = blockIdx.x;
  const bool five = (c & 1) == 0;
  const uint32_t pitch = five ? 64 : 80;
  const uint32_t ones = 0x3F803F80u;
  const int tid = threadIdx.x, lane = tid & 31;
  const uint32_t xrow = OFF_YT + ((tid & 127) >> 3) * YT_PITCH + (tid & 64) + (tid & 7) * 16;
  {
    const int w4 = tid >> 7;
    load_params<FAR>(p, w4 < 2 ? 2 * c + w4 : five ? 257 + 2 * c : 512 + (c >> 1), tid & 127, OFF_W + W_KT + (w4 < 2 ? w4 * W_BYTES : five ? 3 * W_BYTES : 3 * W_BYTES + 2048), (0xB >> w4) & 1);
  }
  if ((tid >> 7) == 2) {
    const unsigned char* xp = p.x + (uint32_t)((c * 16 - 32 + (tid >> 3)) * 1152 + (tid & 7) * 16);
    asm volatile("" : "+l"(xp));
    { const uint32_t tq = clock(); while ((int)(clock() - tq) < X_XD) {} }
#pragma unroll
    for (int k = 0; k < 9; k++) asm volatile("cp.async.cg.shared.global [%0], [%1], 16;" :: "r"(xrow + k * 128), "l"(xp + k * 128) : "memory");
  }
  const int warp = (int)uni(tid >> 5), wg = warp >> 2;
  TS(0);
  if (__builtin_expect(wg == 4, 0)) {
    asm volatile("setmaxnreg.dec.sync.aligned.u32 32;");
    const int role = warp;
    const int u0 = (c >> 1) * 9 + (five ? ((c & 2) ? 5 : 0) : ((c & 2) ? 0 : 4));
    const uint32_t t0 = clock() + c * 4;
    if (role == 16) {
      if (lane == 0) {
#pragma unroll
        for (int i = 0; i < 19; i++) if (i != 16) asm volatile("mbarrier.init.shared::cta.b64 [%0], %1;" :: "r"(OFF_MISC + i * 8), "r"((unsigned)(i - 2) < 4u ? 4 : 1) : "memory");
      }
      __syncwarp();
      if (lane < 2) asm volatile("mbarrier.arrive.expect_tx.shared::cta.b64 _, [%0], %1;" :: "r"(OFF_MISC + lane * 8), "r"(lane ? (five ? 36864 : 51200) : pitch * 1152) : "memory");
      fence_async();
      bar_arrive(5, 608);
      const CUtensorMap* tmb = &tm.m[five ? 3 : 0];
#pragma unroll 1
      for (int u = 0; u < 17; u++) {
        const uint32_t e = p.sched[five][u], kind = e & 3, s = (e >> 2) & 15, dst = e >> 14;
        if (kind == 3) continue;
        while ((int)(clock() - t0) < X_PF0 + (u < X_NE ? u * X_PFD : X_LAG + u * X_TD)) __nanosleep(20);
        if (e & 0x3FC0) mbar_wait(OFF_MISC + ((e >> 6) & 255));
        if (lane == 0) {
          if (kind == 2) asm volatile("cp.async.bulk.tensor.3d.shared::cluster.global.mbarrier::complete_tx::bytes [%0], [%1, {%3, %4, %5}], [%2];"
                                      :: "r"(dst), "l"(tmb + 2), "r"(MB_D), "r"(0), "r"(u0 * 8), "r"(s) : "memory");
          else tma_box(dst, tmb + kind, MB_GU, u0 * 8, s * 96);
        }
        if (u == 5) TS(2);
        if (u == 10) TS(3);
      }
      TS(4);
      TS_DUMP();
#define FINISH0 bar_sync(12, 192);        \
        _Pragma("unroll 1") for (int w = role & 2; w < (role & 2) + 2; w++) { \
          const uint32_t xa = OFF_W + W_KT + lane * 16, mk = lane < 8 ? 0xFFFEFFFEu : ~0u, ya = OFF_T + (8 + lane) * 64 + (((w & 1) ^ (lane >> 1)) & 3) * 16 + (w & 2) * 2048; \
          const uint4 a = lds128(xa + 4096 + w * 1024), b = lds128(xa + (w ^ 2) * 1024), d = lds128(xa + 4608 + w * 1024), e = lds128(xa + 512 + (w ^ 2) * 1024); \
          stsm4t(ya, hadd2u(a.x, b.x) & mk, hadd2u(a.y, b.y) & mk, hadd2u(a.z, b.z) & mk, hadd2u(a.w, b.w) & mk); \
          stsm4t(ya + 2048, hadd2u(d.x, e.x) & mk, hadd2u(d.y, e.y) & mk, hadd2u(d.z, e.z) & mk, hadd2u(d.w, e.w) & mk); \
        } \
        fence_async();
    } else if (role == 17) {
      if (smem_u32(smem) != SB) __trap();
      bar_sync(10, 576);
      if (lane == 0) {
        fence_async();
        while ((int)(clock() - t0) < X_NS - c * 4) {}
        asm volatile("cp.async.bulk.global.shared::cta.bulk_group [%0], [%1], 10240;" :: "l"(&p.s->X[c * DM * 2 + 512]), "r"(OFF_G) : "memory");
        asm volatile("cp.async.bulk.commit_group;" ::: "memory");
        asm volatile("cp.async.bulk.wait_group 0;" ::: "memory");
      }
      if (lane == 0) mbar_arrive(MB_GF);
      bar_arrive(11, 96);
      if (five) { FINISH0 bar_arrive(13, 192); }
    } else if (role == 18) {
      sts32(MISC_EPOCH, 0);
      sts32(MISC_T0, t0 - c * 4);
      bar_arrive(5, 608);
      uint4* q = lane < 2 ? &p.s->R[c * 2 + lane] : lane < 11 ? &p.s->HS[c * 9 + lane - 2] : lane == 11 ? &p.s->HS[1152 + (c & 7)] : (uint4*)&p.s->FLAG[c * 8];
      if (lane < (c < 8 ? 12 : 11)) str128(q, ~0u, ~0u, ~0u, ~0u);
      const uint32_t ep = __shfl_sync(0xffffffffu, ldr32(q), 31) + 1u;
      sts32(MISC_EPOCH, ep | 0x80000000u);
      TSX(21);
      if (lane == 31) str32(q, ep);
      bar_sync(11, 96);
      TSX(14);
      mbar_wait(MB_KF + (lane & 3) * 8);
      __syncwarp();
      { const uint2 e = lds64(MISC_EM); if (lane < 2) str128(&p.s->SC[c * 2 + lane], e.x, __byte_perm(e.y, ep, 0x6540), 0, 0); }
      TSX(17);
      while ((int)(clock() - t0) < X_SCT) __nanosleep(100);
      TSX(18);
      {
        uint2 v[4];
#pragma unroll 1
        for (int it = 0; it < SPIN_MAX; it++) {
          uint32_t bad = 0;
#pragma unroll
          for (int q = 0; q < 4; q++) v[q] = ldr64(&p.s->SC[lane * 2 + q * 64]);
#pragma unroll
          for (int q = 0; q < 4; q++) bad |= (v[q].y >> 8) ^ (ep & 0xFFFFFFu);
          if (!__any_sync(0xffffffffu, bad)) break;
        }
        TSX(25);
#pragma unroll
        for (int q = 0; q < 4; q++) {
          const uint32_t sa = (lane >> 4) * YT_PITCH + (lane & 15) * 2;
          sts16(sc_addr(2 * q) + sa, v[q].x); sts16(sc_addr(8 + 2 * q) + sa, v[q].x >> 16);
          if (lane & 1) asm volatile("st.shared.u8 [%0], %1;" :: "r"(sc_addr(16) + q * 16 + (lane >> 1)), "r"(v[q].y) : "memory");
        }
      }
      __syncwarp();
      if (lane == 0) mbar_arrive(MB_SC);
      TSX(27);
    } else {
      uint32_t w[9];
      const uint32_t dk = ldnc16(p.dskip + ((lane & 4) ? 512 + (c >> 1) : (lane & 2) * 128 + 2 * c + (lane & 1)));
      float s = 0.f;
#pragma unroll
      for (int i = 0; i < 9; i++) w[i] = ldnc32(p.w_r + lane + 32 * i);
      sts16(OFF_WR + 1152 + lane * 2, dk);
      bar_arrive(5, 608);
#pragma unroll
      for (int i = 0; i < 9; i++) { sts32(OFF_WR + lane * 4 + i * 128, w[i]); s += bf_lo(w[i]) + bf_hi(w[i]); }
      sts32(MISC_SW, __float_as_uint(warp_sum(s)));
      TSX(23);
      bar_sync(10, 576);
      if (lane == 0) {
        const uint32_t tp = clock();
        TSX(1);
        while ((int)(clock() - tp) < X_DELTA || (int)(clock() - t0) < X_ABS - c * 4) {}
        TSX(24);
        load_tile(&tm.m[6], 0, c);
        TSX(15);
        while ((int)(clock() - t0) < X_ABS + X_DSTEP - c * 4) {}
      }
      bar_sync(11, 96);
      if (lane == 0) {
        load_tile(&tm.m[6], 1, 128 + c);
      }
      if (five) {
        mbar_wait(MB_KF);
#pragma unroll 1
        for (int it = 0; it < SPIN_MAX; it++) {
          if (lane == 0) load_tile(&tm.m[8], 2, 512 + (c >> 1));
          mbar_wait(MB_UL + 32, it & 1);
          uint32_t m = 1;
#pragma unroll
          for (int q = 0; q < 4; q++) { uint32_t r0, r1, r2, r3; ldsm4(OFF_W + 512 + lane * 64 + (lane & 6) * 8 + q * 2048, r0, r1, r2, r3); m &= r0 & r1 & r2 & r3; }
          if (__all_sync(0xffffffffu, m || (lane & 3))) break;
        }
        bar_arrive(7, 288);
        FINISH0
        bar_arrive(13, 192);
      }
      bar_sync(0, 544);
      if (lane == 0) mbar_arrive(MB_H);
    }
    return;
  }
  const int wt = tid & 127, g = lane >> 2, t = lane & 3;
  const uint32_t wb = OFF_W + wg * W_BYTES;
  asm volatile("cp.async.commit_group;" ::: "memory");
  const ConvC cv = conv_consts(warp, lane);
  zero_pads(wb, wt);
  load_params<FAR>(p, 254 + 2 * c + wg, wt, wb + W_KT, wg == 2 || (wg == 3 && !five));
  asm volatile("cp.async.commit_group;" ::: "memory");
  asm volatile("setmaxnreg.inc.sync.aligned.u32 112;");
  {
    uint4 kw;
    uint4* kx = &p.s->KX[(c >> 1) * 128 + wt];
    bool two = wg == 3;
    uint32_t ep;
    int em = 0;
    uint32_t slot = wg + (two && !five);
    const uint32_t ra0 = wb + W_KT + (slot & 4) * 512 + wt * 2, ra6 = wb + W_KT + 1536 + (slot & 4) * 512 + (((slot & 4) ? c >> 1 : 2 * c + (wg & 1)) & 7) * 2;
    uint32_t raw[7];
    if (wg != 2) {
      asm volatile("cp.async.wait_group 1;" ::: "memory");
      bar_sync(1 + wg, 128);
#pragma unroll
      for (int i = 0; i < 7; i++) raw[i] = lds16(i < 6 ? ra0 + i * 256 : ra6);
    }
    int phase = wg == 2 ? 3 : 2;
#pragma unroll 1
    for (;;) {
      if (phase != 3) {
        KgState ks;
        TS(22);
        kgen_tables_n(raw, wb, wt, ks);
        TS(20);
        bar_sync(1 + wg, 128);
        em = kgen_tables_m(wb, wt, ks);
        fence_async();
      }
      if (phase & 2) {
        const int lz = lane ^ (clock() & p.off[7]);
        const uint32_t tr_addr = pin(tr_base(lz) + warp * 32), lca = pin(MISC_LN1 + (lz & 1) * 16);
        uint4* dst;
        { const unsigned long long a = (unsigned long long)&p.s->X[c * DM * 2 + warp * 32 + (8 * ((lz >> 1) & 1) + (lz >> 2)) * 2 + (lz & 1)];
          dst = (uint4*)(((unsigned long long)pin(a >> 32) << 32) | pin((uint32_t)a)); }
        if (phase == 3) {
        asm volatile("cp.async.wait_group 1;" ::: "memory");
        TS(21);
        float d[3][4], r;
        uint4 a[9];
#pragma unroll
        for (int k = 0; k < 9; k++) a[k] = lds128(xrow + k * 128);
#pragma unroll
        for (int i = 0; i < 4; i++) d[0][i] = d[1][i] = d[2][i] = 0.f;
#pragma unroll
        for (int k = 0; k < 9; k++) { mma_bf16(d[(2 * k) % 3], a[k].x, ones, a[k].y, ones, a[k].x, a[k].y); mma_bf16(d[(2 * k + 1) % 3], a[k].z, ones, a[k].w, ones, a[k].z, a[k].w); }
#pragma unroll
        for (int i = 0; i < 4; i++) d[0][i] += d[1][i] + d[2][i];
        const LnC lc = ln_consts(d[0][2] + d[0][3], __shfl_sync(0xffffffffu, d[0][0], 9 * t) + __shfl_sync(0xffffffffu, d[0][1], 9 * t + 4), r);
        if (lane < 12) sts16(MISC_LN1 + g * 32 + (warp & 3) * 8 + t * 2, lane < 4 ? lc.m2 : lane < 8 ? lc.rh2 : lc.rl2);
        }
        asm volatile("cp.async.wait_group 0;" ::: "memory");
        TS(23);
        bar_sync(5, 608);
        uint32_t x[3][4];
        ldsm4t(tr_addr, x[0][0], x[0][1], x[0][2], x[0][3]);
        uint4 m = lds128(lca);
        const uint4 rl = lds128(lca + 64), rh = lds128(lca + 32);
        ldsm4t(tr_addr + 512, x[1][0], x[1][1], x[1][2], x[1][3]);
        if (wg == 3) ldsm4t(tr_addr + 640, x[2][0], x[2][1], x[2][2], x[2][3]);
#pragma unroll
        for (int q = 0; q < 3; q++) {
          if (q < 2 || wg == 3) {
            const uint32_t r0 = ln_apply(x[q][0], m.x, rh.x, rl.x), r1 = ln_apply(x[q][1], m.y, rh.y, rl.y), r2 = ln_apply(x[q][2], m.z, rh.z, rl.z), r3 = ln_apply(x[q][3], m.w, rh.w, rl.w);
            const uint32_t w0 = (pack_h(bf_lo(r0), bf_hi(r0)) & 0xFFFEFFFEu) | 1u, w1 = pack_h(bf_lo(r1), bf_hi(r1)), w2 = pack_h(bf_lo(r2), bf_hi(r2)), w3 = pack_h(bf_lo(r3), bf_hi(r3));
            if (q == 0) str128(dst, w0, w1, w2, w3);
            else sts128(OFF_G + warp * 512 + (8 * (t >> 1) + g) * 32 + (t & 1) * 16 + (q == 2 ? 2048 : 0), w0, w1, w2, w3);
          }
          if (q == 0) {
            const uint32_t z = clock() & p.off[7];
            m.x ^= z; m.y ^= z; m.z ^= z; m.w ^= z;
          }
          if (q == 0) TS(30);
          if (q == 0 && wg >= 2) {
#pragma unroll
            for (int i = 0; i < 7; i++) raw[i] = lds16(wb + W_KT + i * 256 + (i < 6 ? wt : (2 * c + (wg & 1)) & 7) * 2);
          }
        }
        bar_arrive(10, 576);
        TS(1);
      } else bar_sync(1 + wg, 128);
      phase &= 1;
      if (phase) { phase = 0; continue; }
      TS(14);
      float acc[20];
      const uint32_t alo = (wb >> 4) | (8u << 16);
      uint4 k4 = lds128(wb + W_MISC + 16);
      uint32_t dk = lds16(OFF_WR + 1152 + slot * 2);
      wg_fence();
      wgmma40_ss_init(acc, alo, alo + 1024, 2048 >> 4);
#pragma unroll
      for (int k = 1; k < 8; k++) wgmma40_ss(acc, alo + k * 16, alo + 1024 + k * 16, 2048 >> 4);
      wg_commit();
      { const uint32_t z = clock() & p.off[7]; dk ^= z; k4.x ^= z; k4.z ^= z; }
      const float k2048 = (float)(int)((k4.x + k4.y) + (k4.z + k4.w)) * (1.f / 262144.f);
      const int ef = max(em, min((int)((dk >> 7) & 255u) - 7, 238));
      asm volatile("st.shared.u8 [%0], %1;" :: "r"(MISC_EM + slot), "r"(ef + 9) : "memory");
      const float un = __uint_as_float((uint32_t)max(114 + em - ef, 0) << 23), d0 = wt ? 0.f : bf_lo(dk) * __uint_as_float((uint32_t)(245 - ef) << 23);
      wg_wait<0>();
      kw.x = pack_h(fmaf(acc[0] - acc[3], un, d0), (acc[4] - acc[7]) * un);
      kw.y = pack_h((acc[8] - acc[11]) * un, (acc[12] - acc[15]) * un);
      kw.z = pack_h((acc[16] - acc[19]) * un, k2048 * un);
      TS(24);
      ep = 0;
      if (two) SPIN_WHILE(ep == 0, ep = lds32(MISC_EPOCH));
      if (five || !two) break;
      str128(kx, kw.x, kw.y, kw.z, ep);
      two = false;
      slot = 3;
      bar_sync(1 + wg, 128);
    }
    if (lane == 0) mbar_arrive(MB_KF + wg * 8);
    if (two) { mbar_wait(MB_KF); zero_pads(OFF_W + ALT, wt); }
    uint32_t tb = wb;
#pragma unroll 1
    for (;;) {
      kgen_build(tb, wg, wt, kw.x, kw.y, kw.z);
      TS(15);
      if (!two) break;
      two = false;
      kw.w = 0;
      SPIN_WHILE(kw.w != ep, kw = ldr128(kx));
      tb = OFF_W + ALT;
    }
    fence_async();
    TS(31);
    if (tb != wb) bar_arrive(7, 288);
    bar_sync(1 + wg, 128);
  }
  uint32_t tpub;
  ConvPre pre;
  conv_pre(pre, (wb ^ p.off[7]) + (cv.ca & 0xFFFFu), (wb ^ p.off[7]) + cv.qa, 3, true, warp & 2);
#pragma unroll 1
  for (int item = 0;; item++) {
    TS(2);
    conv_item(item ? OFF_W + ALT : wb, item ? OFF_W : OFF_T + (wg >> 1) * TILE, item ? 1 : 13 + (wg >> 1), item ? 128 : five && wg == 1 ? 192 : 256, pre, cv, p.off[7],
              &tm.m[item ? 9 : 7], item ? 512 + (c >> 1) : (wg >> 1) * 128 + c, warp, lane, five && wg >= X_GW, five && !wg && !item);
    tpub = clock() - (item ? X_YD : wg >= 2 ? X_YD2 : 0);
    if (wg || !five || item) break;
    TS(27);
  }
  TS(4);

  const int ln = lane ^ p.off[7], td = warp * 32 + ln, gg = ln >> 2, tt = ln & 3;
  const int tok = c * 16 + warp;
  const int fu = warp / 3, fk = warp - fu * 3;
  uint32_t wa[12][4];
  uint4 ha[3];
  const uint4* hsrc = &p.s->HS[td + (td / 24) * 48];
  {
    uint32_t hw[9], wr[9];
    const uint32_t row = keep(OFF_YT + warp * YT_PITCH + (warp >> 3) * 64 + ln * 16);
    const uint32_t wabase = keep(((ln & 8) ? OFF_W + (fk + 1) * W_BYTES : OFF_G + fk * 192 * pitch) + ((ln >> 4) * 8 + (ln & 7)) * pitch
                                 + (five ? ((fu ^ (ln >> 1)) & 3) : min(fu, 4)) * 16);
    float sw;
    {
      const bool three = wg == 1;
      const int ch = 8 * (tt >> 1) + gg;
      const uint32_t tr_addr = tr_base(ln);
      const uint4* ysrc = &p.s->X[c * DM * 2 + ch * 2 + (tt & 1)];
      uint32_t x[3][4], s[3];
      uint4 v[3];
#define TL(q) ((q) < 2 ? 2 * warp + (q) : 28 + warp)
      asm volatile("cp.async.bulk.wait_group.read 0;" ::: "memory");
      if (wg >= 2) { const uint32_t ts = lds32(MISC_T0); while ((int)(clock() - ts) < X_XS) {} }
      while ((int)(clock() - tpub) < X_YD) {}
      TS(5);
      v[0] = ldr128(ysrc + TL(0) * 32); v[1] = ldr128(ysrc + TL(1) * 32); v[2] = make_uint4(three, 0, 0, 0);
      mbar_wait(MB_REL);
#pragma unroll
      for (int i = 0; i < 6; i++) if (i < 4 || three) wr[i] = (gg & 2) ? ones : lds32(OFF_WR + TL(i >> 1) * 32 + (i & 1) * 16 + tt * 4);
      const uint32_t ha = keep(OFF_YT + (ln & 7) * YT_PITCH + (ln >> 4) * (8 * YT_PITCH + 64) + (ln & 8) * 2);
      const uint32_t pa = keep(OFF_PART + warp * 4 + ((gg & 2) * 8 + (gg & 4) * 2 + 2 * tt + (gg & 1)) * 80), pb = keep(OFF_PART + 2560 + warp * 4 + gg * 80);
      float dl[4] = {0.f, 0.f, 0.f, 0.f}, dh[4] = {0.f, 0.f, 0.f, 0.f};
      sw = __uint_as_float(lds32(MISC_SW));
#pragma unroll
      for (int q = 0; q < 3; q++) {
        if (q < 2 || three) {
          ldsm4t(tr_addr + TL(q) * 32, x[q][0], x[q][1], x[q][2], x[q][3]);
        }
      }
      mbar_wait(MB_SC);
#pragma unroll
      for (int q = 0; q < 3; q++) {
        asm volatile("ld.shared.u8 %0, [%1];" : "=r"(s[q]) : "r"((q < 2 ? sc_addr(warp) + q * 16 : sc_addr(16) + (warp & 3) * 16) + ch) : "memory");
        s[q] = keep(s[q] * 0x800080u);
      }
#define FIN(q) stsm4t(tr_addr + TL(q) * 32, bf_fma2(h2bf(v[q].x), s[q], x[q][0]), bf_fma2(h2bf(v[q].y), s[q], x[q][1]), bf_fma2(h2bf(v[q].z), s[q], x[q][2]), bf_fma2(h2bf(v[q].w), s[q], x[q][3]));
      SPIN_WHILE((v[0].x | v[1].x) & 1u, _Pragma("unroll") for (int q = 0; q < 3; q++) if (v[q].x & 1u) v[q] = ldr128(ysrc + TL(q) * 32));
      if (v[2].x & 1u) v[2] = ldr128(ysrc + TL(2) * 32);
#define STAT(q) { uint32_t r0, r1, r2, r3; ldsm4(ha + TL(q) * 32, r0, r1, r2, r3); \
        mma_bf16(dl, r0, wr[2 * q], r1, wr[2 * q + 1], r0, r1); mma_bf16(dh, r2, wr[2 * q], r3, wr[2 * q + 1], r2, r3); }
      FIN(0) FIN(1)
      __syncwarp();
      STAT(0) STAT(1)
      if (three) {
        SPIN_WHILE(v[2].x & 1u, if (v[2].x & 1u) v[2] = ldr128(ysrc + TL(2) * 32));
        FIN(2)
        __syncwarp();
        STAT(2)
      }
      if (gg & 1) { dl[0] = dl[1]; dl[2] = dl[3]; dh[0] = dh[1]; dh[2] = dh[3]; }
      sts32(pa, __float_as_uint((gg & 4) ? dh[2] : dl[2]));
      if (tt == (gg >> 1)) { sts32(pb, __float_as_uint(dl[0])); sts32(pb + 640, __float_as_uint(dh[0])); }
#undef STAT
#undef FIN
#undef TL
    }
    uint32_t ra = keep(OFF_PART + (ln & 15) * 80 + (ln & 16) * 2);
    uint16_t* rp = (uint16_t*)p.s->R + c * 16 + (ln & 15);
    const uint2* rsrc = (const uint2*)p.s->R + td;
    asm volatile("" : "+l"(rp), "+l"(rsrc), "+l"(hsrc));
    uint2 rv = make_uint2(0u, 0u);
    TS(28);
    if (warp != X_PW) bar_sync(0, 544);
    else {
      float z[3], rd;
      asm volatile("bar.sync 0, 544;" : "+r"(ra) :: "memory");
#pragma unroll
      for (int k = 2; k >= 0; k--) {
        const uint4 a = lds128(ra + k * 1280), b = lds128(ra + k * 1280 + 16);
        z[k] = ((__uint_as_float(a.x) + __uint_as_float(a.y)) + (__uint_as_float(a.z) + __uint_as_float(a.w))) + ((__uint_as_float(b.x) + __uint_as_float(b.y)) + (__uint_as_float(b.z) + __uint_as_float(b.w)));
      }
#pragma unroll
      for (int k = 2; k >= 0; k--) z[k] += __shfl_xor_sync(0xffffffffu, z[k], 16);
      const LnC l = ln_consts(z[1], z[2], rd);
      const uint32_t b = pack_bf(0.f, fmaf(-bf_lo(l.m2), sw, z[0]) * rd);
      const uint32_t k16 = max(min((b ^ (((int)b >> 31) | 0x80000000u)) >> 16, 0xFFFEu), 1u);
      if (ln < 16) str16(rp, k16);
      sts64(OFF_RK + (ln & 15) * 8, __byte_perm(l.m2, l.rh2, 0x5410), __byte_perm(l.rl2, k16, 0x5410));
      sts128(MISC_CNT + ln * 16, 0, 0, 0, 0);
    }
    mbar_wait(MB_GU);
#define LD_HW { const uint4 a = lds128(row), b = lds128(row + 512); hw[8] = lds32(row + 1024 - ln * 12); \
      hw[0] = a.x; hw[1] = a.y; hw[2] = a.z; hw[3] = a.w; hw[4] = b.x; hw[5] = b.y; hw[6] = b.z; hw[7] = b.w; }
    LD_HW
    const uint32_t tr0 = clock();
    bar_sync(5, 512);
    TS(7);
    const uint2 lk = lds64(OFF_RK + warp * 8);
    LnC l2;
    l2.m2 = __byte_perm(lk.x, 0, 0x1010); l2.rh2 = __byte_perm(lk.x, 0, 0x3232); l2.rl2 = __byte_perm(lk.y, 0, 0x1010);
    const uint32_t key = (lk.y & 0xFFFF0000u) | (2047 - tok);
    uint32_t loc = ln < 16 ? (lds32(OFF_RK + 4 + ln * 8) & 0xFFFF0000u) | (2047 - c * 16 - ln) : 0u;
    int rank = __popc(__ballot_sync(0xffffffffu, loc > key));
#pragma unroll
    for (int i = 0; i < 9; i++) wr[i] = keep(ln_apply(hw[i], l2.m2, l2.rh2, l2.rl2));
#define OUT_ROW { uint32_t* o = p.out + tok * 288 + ln * 4; \
      *(uint4*)o = make_uint4(bf_add2(hw[0], wr[0]), bf_add2(hw[1], wr[1]), bf_add2(hw[2], wr[2]), bf_add2(hw[3], wr[3])); \
      *(uint4*)(o + 128) = make_uint4(bf_add2(hw[4], wr[4]), bf_add2(hw[5], wr[5]), bf_add2(hw[6], wr[6]), bf_add2(hw[7], wr[7])); \
      o[256 - ln * 3] = bf_add2(hw[8], wr[8]); }
    uint4* hs = p.s->HS + ln;
    asm volatile("" : "+l"(hs));
#pragma unroll 1
    for (int base = 0; base < 8; base += 2) {
      uint32_t T[2];
#pragma unroll
      for (int j = 0; j < 2; j++) {
        const uint32_t mx = __reduce_max_sync(0xffffffffu, loc);
        if (loc == mx) loc = 0;
        T[j] = (td >> 2) < c ? (mx & 0xFFFF0000u) - 1u : mx | 0xFFFFu;
      }
      const uint32_t sh = keep(rank == base ? 0x4410u : rank == base + 1 ? 0x4432u : 0x4445u), ca = keep(MISC_CNT + base * 64 + ln * 4);
      TS(29);
      if (base == 0) {
        while ((int)(clock() - tr0) < X_RD) {}
        if ((td >> 2) != c) rv = ldr64(rsrc);
        if (rank >= X_OR) OUT_ROW
        if (warp < (five ? 12 : 15)) {
#pragma unroll
          for (int k = 0; k < X_WS; k++) ldsm4t(wabase + k * 16 * pitch, wa[k][0], wa[k][1], wa[k][2], wa[k][3]);
        }
      }
      uint32_t cnt;
#pragma unroll 1
      for (int it = 0; it < SPIN_MAX; it++) {
        const uint32_t xs = rv.x << 16, ys = rv.y << 16;
        const bool bad = max(max(rv.x, xs), max(rv.y, ys)) >= 0xFFFF0000u;
        uint32_t cn2 = 0;
        cnt = bad ? 256u : 0u;
#pragma unroll
        for (int j = 0; j < 2; j++)
          asm("{ .reg .pred a, b, c, d; setp.gt.u32 a, %2, %6; setp.gt.u32 b, %3, %6; setp.gt.u32 c, %4, %6; setp.gt.u32 d, %5, %6; "
              "@a add.u32 %1, %1, %7; @b add.u32 %1, %1, %7; @c add.u32 %0, %0, %7; @d add.u32 %0, %0, %7; }"
              : "+r"(cnt), "+r"(cn2) : "r"(rv.x), "r"(rv.y), "r"(xs), "r"(ys), "r"(T[j]), "r"(1u << (16 * j)));
        cnt = __reduce_add_sync(0xffffffffu, cnt + cn2);
        asm volatile("{ .reg .pred q; setp.eq.u32 q, %2, 0; @q red.shared.add.u32 [%0], %1; }" :: "r"(ca), "r"(cnt), "r"(cnt & 0x3F00u) : "memory");
        if (!(cnt & 0x3F00u)) break;
        if (bad) rv = ldr64(rsrc);
      }
      TS(16);
      bar_sync(0, 512);
      cnt = lds32(ca);
      if (base == 0) tpub = clock();
      const int gr = rank + __byte_perm(cnt, 0x800u, sh);
      if (gr < 8) {
        uint4* ks = hs + 1152 + gr;
        hs = (uint4*)((char*)hs + gr * 1152);
        asm volatile("{ .reg .b128 t, u; .reg .b64 a, b, c, d; mov.b64 a, {%1,%2}; mov.b64 b, {%3,%4}; mov.b64 c, {%5,%6}; mov.b64 d, {%7,%8}; mov.b128 t, {a, b}; mov.b128 u, {c, d}; "
                     "st.relaxed.gpu.global.b128 [%0], t; st.relaxed.gpu.global.b128 [%0 + 512], u; }"
                     :: "l"(hs), "r"(wr[0]), "r"(wr[1]), "r"(wr[2]), "r"(wr[3]), "r"(wr[4]), "r"(wr[5]), "r"(wr[6]), "r"(wr[7]) : "memory");
        str32((uint32_t*)(hs + 64) - ln * 3, wr[8]);
        str128(hs + 576, hw[0], hw[1], hw[2], hw[3]); str128(hs + 608, hw[4], hw[5], hw[6], hw[7]); str32((uint32_t*)(hs + 640) - ln * 3, hw[8]);
        if (ln == 0) str32(ks, key);
        rank = 16;
      }
      if (__all_sync(0xffffffffu, (int)(cnt >> 16) + base + 2 >= 8)) break;
    }
    TS(8);
    if (warp < (five ? 12 : 15)) {
#pragma unroll
      for (int k = X_WS; k < 12; k++) ldsm4t(wabase + k * 16 * pitch, wa[k][0], wa[k][1], wa[k][2], wa[k][3]);
    }
    if (warp < 6) while ((int)(clock() - tpub) < X_HD) {}
    TS(19);
    if (warp < 6) { ha[0] = ldr128(hsrc); ha[1] = ldr128(hsrc + 24); ha[2] = ldr128(hsrc + 48); }
    if (rank < X_OR) OUT_ROW
  }
  uint32_t wd[10][4];
  const uint32_t xb = keep(OFF_XS + (ln & 7) * 1168 + (fk * 24 + (ln >> 3)) * 16);
  if (warp >= 7) {
    const uint32_t db = down_box(warp - 7, five) + (ln & 7) * 128;
    mbar_wait(MB_D);
#pragma unroll
    for (int j = 0; j < 4; j++) {
      const uint32_t a = db + (ln >> 4) * 1024 + (((2 * j + ((ln >> 3) & 1)) ^ (ln & 7)) << 4);
      ldsm4t(a, wd[j][0], wd[j][1], wd[j][2], wd[j][3]);
      ldsm4t(a + 2048, wd[4 + j][0], wd[4 + j][1], wd[4 + j][2], wd[4 + j][3]);
    }
#pragma unroll
    for (int j = 0; j < 2; j++) ldsm4t(db + 4096 + (((4 * j + (ln >> 3)) ^ (ln & 7)) << 4), wd[8 + j][0], wd[8 + j][1], wd[8 + j][2], wd[8 + j][3]);
  } else if (warp < 6) {
    const uint32_t xs = keep(OFF_XS + (td + (td / 24) * 49) * 16);
#pragma unroll 1
    for (int it = 0; it < SPIN_MAX; it++) {
      const bool bad = max(max(max(ha[0].x, ha[1].x), max(ha[2].x, ha[2].y)), max(ha[2].z, ha[2].w)) == ~0u;
      if (!__any_sync(0xffffffffu, bad)) break;
      if (bad) { ha[0] = ldr128(hsrc); ha[1] = ldr128(hsrc + 24); ha[2] = ldr128(hsrc + 48); }
    }
#pragma unroll
    for (int q = 0; q < 3; q++) sts128(xs + q * 384, ha[q].x, ha[q].y, ha[q].z, ha[q].w);
  }
  TS(9);

  bar_sync(0, 512);
  if (warp < (five ? 12 : 15)) {
    float d0[4] = {0.f, 0.f, 0.f, 0.f}, d1[4] = {0.f, 0.f, 0.f, 0.f};
#pragma unroll
    for (int k = 0; k < 12; k += 2) {
      uint32_t b0, b1, b2, b3;
      ldsm4(xb + k * 32, b0, b1, b2, b3);
      mma_bf16(d0, wa[k][0], wa[k][1], wa[k][2], wa[k][3], b0, b1);
      mma_bf16(d1, wa[k + 1][0], wa[k + 1][1], wa[k + 1][2], wa[k + 1][3], b2, b3);
    }
    sts128(OFF_RED + td * 16, __float_as_uint(d0[0] + d1[0]), __float_as_uint(d0[1] + d1[1]), __float_as_uint(d0[2] + d1[2]), __float_as_uint(d0[3] + d1[3]));
  }
  TS(26);
  if (warp < 5) {
    const uint32_t rb = OFF_RED + warp * 1536 + ln * 16;
    bar_sync(9, 512);
    const uint4 pa = lds128(rb), pb = lds128(rb + 512), pc = lds128(rb + 1024);
    const float ga = bfr(__uint_as_float(pa.x) + __uint_as_float(pb.x) + __uint_as_float(pc.x));
    const float gb = bfr(__uint_as_float(pa.y) + __uint_as_float(pb.y) + __uint_as_float(pc.y));
    const uint32_t uu = pack_bf(__uint_as_float(pa.z) + __uint_as_float(pb.z) + __uint_as_float(pc.z), __uint_as_float(pa.w) + __uint_as_float(pb.w) + __uint_as_float(pc.w));
    float ra, rb2;
    asm("rcp.approx.ftz.f32 %0, %1;" : "=f"(ra) : "f"(1.f + ex2(ga * -1.4426950408889634f)));
    asm("rcp.approx.ftz.f32 %0, %1;" : "=f"(rb2) : "f"(1.f + ex2(gb * -1.4426950408889634f)));
    const uint32_t act = bf_mul2(pack_bf(ga * ra, gb * rb2), uu);
    sts32(OFF_ACT + td * 4, act);
  } else bar_arrive(9, 512);
  uint4* dst = &p.s->X[c * DM * 2 + (warp - 7) * 64 + tt * 8 + gg];
  asm volatile("" : "+l"(dst));
  bar_sync(8, 512);
  tpub = clock();
  if (warp >= 7) {
    uint32_t b0, b1, b2, b3, b4;
    ldsm4t(OFF_ACT + ln * 16, b0, b1, b2, b3);
    asm volatile("ldmatrix.sync.aligned.m8n8.x1.trans.shared.b16 {%0}, [%1];" : "=r"(b4) : "r"(OFF_ACT + 512 + ln * 16) : "memory");
    float y[4][4];
#pragma unroll
    for (int j = 0; j < 4; j++) {
      y[j][0] = y[j][1] = y[j][2] = y[j][3] = 0.f;
      mma_bf16(y[j], wd[j][0], wd[j][1], wd[j][2], wd[j][3], b0, b1);
    }
#pragma unroll
    for (int j = 0; j < 4; j++) mma_bf16(y[j], wd[4 + j][0], wd[4 + j][1], wd[4 + j][2], wd[4 + j][3], b2, b3);
    if (!five) {
#pragma unroll
      for (int j = 0; j < 4; j++) mma_bf16_k8(y[j], wd[8 + (j >> 1)][2 * (j & 1)], wd[8 + (j >> 1)][2 * (j & 1) + 1], b4);
    }
    str128(dst, (pack_bf(y[0][0], y[0][1]) & ~1u) | 0x10000u, pack_bf(y[0][2], y[0][3]), pack_bf(y[1][0], y[1][1]), pack_bf(y[1][2], y[1][3]));
    str128(dst + 32, (pack_bf(y[2][0], y[2][1]) & ~1u) | 0x10000u, pack_bf(y[2][2], y[2][3]), pack_bf(y[3][0], y[3][1]), pack_bf(y[3][2], y[3][3]));
  }
  TS(10);

  if (c < 72) {
    const uint4* src = &p.s->X[(warp * 4 + tt) * (DM * 2) + c * 8 + gg];
    const int slot = (c & 3) * 2 + (ln >> 4), dw = (c >> 2) * 16 + (ln & 15);
    uint32_t hv = 0, kv = 0, res = 0, rs2 = 0;
    uint32_t* o = p.out;
    if (warp == 0) {
      hv = ~0u;
      SPIN_WHILE(max(hv, kv) == ~0u, hv = ldr32((const uint32_t*)p.s->HS + 2304 + slot * 288 + dw); kv = ldr32(&p.s->HS[1152 + slot]));
      const float r = bf_hi(kv ^ (((int)~kv >> 31) | 0x80000000u));
      float rs;
      asm("rcp.approx.ftz.f32 %0, %1;" : "=f"(rs) : "f"(1.f + ex2(r * -1.4426950408889634f)));
      rs2 = keep(pack_bf(rs, rs));
      res = lds32(OFF_XS + slot * 1168 + dw * 4);
      o += (2047 - (int)(kv & 2047u)) * 288 + dw;
      asm volatile("" : "+l"(o));
    }
    const uint32_t sel = (gg & 1) ? 0x3F800000u : 0x00003F80u;
    const uint32_t q0 = keep((gg >> 1) == 0 ? sel : 0u), q1 = keep((gg >> 1) == 1 ? sel : 0u), q2 = keep((gg >> 1) == 2 ? sel : 0u), q3 = keep((gg >> 1) == 3 ? sel : 0u);
    const uint32_t fa = keep(OFF_RED + warp * 8 + ((gg & 1) * 16 + (gg >> 1) * 4 + tt) * 144), fb = keep(OFF_RED + ln * 144);
    uint4 a0 = make_uint4(0, 0, 0, 0), a1 = a0;
    while ((int)(clock() - tpub) < X_PD) {}
    SPIN_WHILE(!(a0.x & a1.x & 0x10000u), if (!(a0.x & 0x10000u)) a0 = ldr128(src); if (!(a1.x & 0x10000u)) a1 = ldr128(src + 64 * DM * 2));
    float d[4] = {0.f, 0.f, 0.f, 0.f}, e[4] = {0.f, 0.f, 0.f, 0.f}, d2[4] = {0.f, 0.f, 0.f, 0.f}, e2[4] = {0.f, 0.f, 0.f, 0.f};
    mma_bf16(d, q0, q2, q1, q3, a0.x, a0.y); mma_bf16(e, q0, q2, q1, q3, a0.z, a0.w);
    mma_bf16(d2, q0, q2, q1, q3, a1.x, a1.y); mma_bf16(e2, q0, q2, q1, q3, a1.z, a1.w);
    sts64(fa, __float_as_uint(d[0] + e[2] + d2[0] + e2[2]), __float_as_uint(d[1] + e[3] + d2[1] + e2[3]));
    TS(11);
    if (warp == 0) {
      bar_sync(0, 512);
      float2 s[16];
#pragma unroll
      for (int i = 0; i < 16; i += 2) { const uint4 q = lds128(fb + i * 8); s[i] = make_float2(__uint_as_float(q.x), __uint_as_float(q.y)); s[i + 1] = make_float2(__uint_as_float(q.z), __uint_as_float(q.w)); }
#pragma unroll
      for (int k = 1; k < 16; k *= 2)
#pragma unroll
        for (int i = 0; i < 16; i += 2 * k) { s[i].x += s[i + k].x; s[i].y += s[i + k].y; }
      asm volatile("st.global.b32 [%0], %1;" :: "l"(o), "r"(bf_add2(hv, bf_add2(res, bf_mul2(pack_bf(s[0].x, s[0].y), rs2)))) : "memory");
    } else bar_arrive(0, 512);
  }
  TS(12);
  TS_DUMP();
}

typedef CUresult (*EncodeFn)(CUtensorMap*, CUtensorMapDataType, cuuint32_t, void*, const cuuint64_t*, const cuuint64_t*, const cuuint32_t*,
                             const cuuint32_t*, CUtensorMapInterleave, CUtensorMapSwizzle, CUtensorMapL2promotion, CUtensorMapFloatOOBfill);

}

extern "C" void kernel_launch(void* const* d_in, const int* in_sizes, int n_in, void* d_out, int out_size) {
  (void)in_sizes; (void)n_in; (void)out_size;
  static EncodeFn enc = nullptr;
  static Scratch* scratch = nullptr;
  if (!enc) {
    void* fn = nullptr;
    cudaDriverEntryPointQueryResult qr;
    cudaGetDriverEntryPoint("cuTensorMapEncodeTiled", &fn, cudaEnableDefault, &qr);
    enc = (EncodeFn)fn;
    cudaGetSymbolAddress((void**)&scratch, g_S);
    cudaFuncSetAttribute(fused_kernel<false>, cudaFuncAttributeMaxDynamicSharedMemorySize, SMEM_BYTES);
    cudaFuncSetAttribute(fused_kernel<true>, cudaFuncAttributeMaxDynamicSharedMemorySize, SMEM_BYTES);
  }
  TMaps tm;
  for (int i = 0; i < 6; i++) {
    const bool dn = i % 3 == 2;
    const cuuint32_t w = i < 3 ? 40 : 32;
    cuuint64_t gd[3] = {(cuuint64_t)(dn ? 64 : FF), (cuuint64_t)(dn ? FF : DM), 9};
    cuuint64_t gs[2] = {(cuuint64_t)(dn ? DM * 2 : FF * 2), 128};
    cuuint32_t bx[3] = {dn ? 64 : w, dn ? w : 96, i < 3 ? 2u : 3u};
    cuuint32_t es[3] = {1, 1, 1};
    enc(&tm.m[i], CU_TENSOR_MAP_DATA_TYPE_BFLOAT16, dn ? 3 : 2, d_in[11 + i % 3], gd, gs, bx, es, CU_TENSOR_MAP_INTERLEAVE_NONE,
        dn ? CU_TENSOR_MAP_SWIZZLE_128B : i < 3 ? CU_TENSOR_MAP_SWIZZLE_NONE : CU_TENSOR_MAP_SWIZZLE_64B,
        (CUtensorMapL2promotion)X_PROMO, CU_TENSOR_MAP_FLOAT_OOB_FILL_NONE);
  }
  for (int i = 6; i < 10; i++) {
    cuuint64_t gd[3] = {i < 8 ? 32u : 16u, i < 8 ? DM / 2u : DM, NCTA};
    cuuint64_t gs[2] = {i < 8 ? 64u : 32u, DM * 32};
    cuuint32_t bx[3] = {32, 1, (i & 1) ? 128u : 136u};
    cuuint32_t es[3] = {1, 1, 1};
    enc(&tm.m[i], CU_TENSOR_MAP_DATA_TYPE_FLOAT16, 3, scratch->X, gd, gs, bx, es, CU_TENSOR_MAP_INTERLEAVE_NONE, CU_TENSOR_MAP_SWIZZLE_64B,
        CU_TENSOR_MAP_L2_PROMOTION_NONE, CU_TENSOR_MAP_FLOAT_OOB_FILL_NONE);
  }
  Params p;
  p.x = (const unsigned char*)d_in[0];
  bool far = false;
  for (int i = 0; i < 7; i++) {
    p.far[i] = (const unsigned char*)d_in[1 + i];
    const long long d = (long long)((intptr_t)d_in[1 + i] - (intptr_t)d_in[0]);
    p.off[i] = (int)(d / 16);
    if ((long long)p.off[i] * 16 != d || p.off[i] > (1 << 30)) far = true;
  }
  p.dskip = (const uint16_t*)d_in[8];
  p.w_r = (const uint32_t*)d_in[10];
  for (int f = 0; f < 2; f++) {
    static const int kind[17] = {0, 0, 0, 0, 2, 2, 0, 0, 1, 1, 1, 1, 1, 1, 2, 2, 2};
    static const int idx[2][17] = {{2, 3, 4, 5, 6, 8, 0, 1, 0, 1, 2, 3, 4, 5, 0, 2, 4}, {2, 3, 4, 5, 0, -1, 0, 1, 0, 1, 2, 3, 4, 5, 3, -1, 6}};
    static const int blk[2][17] = {{-1, -1, -1, -1, 0, -1, 4, -1, 1, -1, 2, -1, 3, -1, 16, -1, -1}, {-1, -1, -1, -1, 1, -1, 4, -1, -1, -1, 2, -1, 3, -1, 16, -1, -1}};
    const int pitch = f ? 64 : 80;
    for (int u = 0; u < 17; u++) {
      const int s = idx[f][u];
      const uint32_t dst = kind[u] == 0 ? OFF_G + s * 96 * pitch : kind[u] == 2 ? down_box(s, f) : OFF_W + W_BYTES + (s >> 1) * W_BYTES + (s & 1) * 96 * pitch;
      const uint32_t mb = u >= 14 ? (u >= X_HU ? MB_H - OFF_MISC : 0) : blk[f][u] >= 0 ? MB_KF - OFF_MISC + blk[f][u] * 8 : 0;
      p.sched[f][u] = s < 0 ? 3u : kind[u] | s << 2 | mb << 6 | dst << 14;
    }
  }
  p.out = (uint32_t*)d_out;
  p.off[7] = 0;
  p.ts = nullptr;
  p.s = scratch;
  if (far) { fused_kernel<true><<<NCTA, NT, SMEM_BYTES, cudaStreamPerThread>>>(p, tm); return; }
  fused_kernel<false><<<NCTA, NT, SMEM_BYTES, cudaStreamPerThread>>>(p, tm);
}
```

```cpp
#include <cuda_runtime.h>
#include <cuda.h>
#include <cuda_bf16.h>
#include <cuda_fp16.h>
#include <stdint.h>
#include <stddef.h>

namespace {

constexpr int NCTA = 128;
constexpr int NT = 640;
constexpr int DM = 576;
constexpr int FF = 4608;
constexpr int SPIN_MAX = 1 << 20;

struct Scratch {
  uint4 X[NCTA * DM * 2];
  uint4 KX[64 * 128];
  uint4 HS[1152 + 8];
  uint4 R[256];
  uint4 SC[256];
  uint32_t FLAG[NCTA * 8];
};
__device__ Scratch g_S;

#define CLKS(i)
#define TS(i)
#define TSX(i)
#define TS_DUMP()

constexpr int SB = 1024;
constexpr int BOX = 15360;
constexpr int OFF_G = SB;
constexpr int OFF_W = OFF_G + 3 * BOX;
constexpr int W_KT = 26624;
constexpr int W_QT = W_KT + 64 + 2048 + 80;
constexpr int W_L3 = W_KT + 4352;
constexpr int W_CW = W_L3 + 4160;
constexpr int W_MISC = W_CW + 640;
constexpr int W_BYTES = 35840;
constexpr int TILE = 10240;
constexpr int OFF_T = OFF_W + 4 * W_BYTES;
constexpr int ALT = TILE - W_KT;
static_assert(W_MISC + 32 <= W_BYTES && OFF_W % 1024 == 0 && W_BYTES % 1024 == 0 && W_BYTES + ALT <= 20480, "wg block");
constexpr int YT_PITCH = 1184;
constexpr int OFF_YT = OFF_T + 2 * TILE;
constexpr int OFF_WR = OFF_YT + 16 * YT_PITCH + 64;
constexpr int OFF_MISC = OFF_WR + 2304;
constexpr int SMEM_BYTES = OFF_MISC + 1024 - SB;
static_assert(OFF_YT % 16 == 0 && OFF_MISC % 16 == 0, "align");
static_assert(SMEM_BYTES <= 232448, "smem");
constexpr int MB_GU = OFF_MISC;
constexpr int MB_D = OFF_MISC + 8;
constexpr int MB_KF = OFF_MISC + 16;
constexpr int MB_GF = OFF_MISC + 48;
constexpr int MB_SC = OFF_MISC + 56;
constexpr int MB_UL = OFF_MISC + 64;
constexpr int MB_REL = OFF_MISC + 104;
constexpr int MB_GO = OFF_MISC + 112;
constexpr int MB_H = MB_KF + 128;
constexpr int MISC_EPOCH = OFF_MISC + 152;
constexpr int MISC_SW = OFF_MISC + 156;
constexpr int MISC_RT = OFF_MISC + 160;
constexpr int MISC_T0 = OFF_MISC + 296;
constexpr int MISC_EM = OFF_MISC + 288;
constexpr int OFF_PART = OFF_W + 20480;
constexpr int OFF_RK = OFF_PART + 3840;
constexpr int MISC_LN1 = OFF_MISC + 192;
constexpr int OFF_XS = OFF_T;
constexpr int OFF_RED = OFF_T + TILE;
constexpr int OFF_FIN = OFF_W + 3 * W_BYTES + W_KT;
constexpr int OFF_ACT = OFF_FIN + 4096;
constexpr int MISC_CNT = OFF_ACT + 1024;

__device__ __forceinline__ uint32_t smem_u32(const void* p) { return (uint32_t)__cvta_generic_to_shared(p); }
__device__ __forceinline__ uint32_t lds32(uint32_t a) { uint32_t v; asm volatile("ld.shared.b32 %0, [%1];" : "=r"(v) : "r"(a) : "memory"); return v; }
__device__ __forceinline__ uint32_t lds16(uint32_t a) { uint16_t v; asm volatile("ld.shared.u16 %0, [%1];" : "=h"(v) : "r"(a) : "memory"); return v; }
__device__ __forceinline__ uint2 lds64(uint32_t a) { uint2 v; asm volatile("ld.shared.v2.b32 {%0,%1}, [%2];" : "=r"(v.x), "=r"(v.y) : "r"(a) : "memory"); return v; }
__device__ __forceinline__ uint4 lds128(uint32_t a) { uint4 v; asm volatile("ld.shared.v4.b32 {%0,%1,%2,%3}, [%4];" : "=r"(v.x), "=r"(v.y), "=r"(v.z), "=r"(v.w) : "r"(a) : "memory"); return v; }
__device__ __forceinline__ void sts16(uint32_t a, uint32_t v) { asm volatile("st.shared.u16 [%0], %1;" :: "r"(a), "h"((uint16_t)v) : "memory"); }
__device__ __forceinline__ void sts32(uint32_t a, uint32_t v) { asm volatile("st.shared.b32 [%0], %1;" :: "r"(a), "r"(v) : "memory"); }
__device__ __forceinline__ void sts64(uint32_t a, uint32_t x, uint32_t y) { asm volatile("st.shared.v2.b32 [%0], {%1,%2};" :: "r"(a), "r"(x), "r"(y) : "memory"); }
__device__ __forceinline__ void sts128(uint32_t a, uint32_t x, uint32_t y, uint32_t z, uint32_t w) { asm volatile("st.shared.v4.b32 [%0], {%1,%2,%3,%4};" :: "r"(a), "r"(x), "r"(y), "r"(z), "r"(w) : "memory"); }
__device__ __forceinline__ void ldsm4(uint32_t a, uint32_t& r0, uint32_t& r1, uint32_t& r2, uint32_t& r3) {
  asm volatile("ldmatrix.sync.aligned.m8n8.x4.shared.b16 {%0,%1,%2,%3}, [%4];" : "=r"(r0), "=r"(r1), "=r"(r2), "=r"(r3) : "r"(a) : "memory");
}
__device__ __forceinline__ void ldsm4t(uint32_t a, uint32_t& r0, uint32_t& r1, uint32_t& r2, uint32_t& r3) {
  asm volatile("ldmatrix.sync.aligned.m8n8.x4.trans.shared.b16 {%0,%1,%2,%3}, [%4];" : "=r"(r0), "=r"(r1), "=r"(r2), "=r"(r3) : "r"(a) : "memory");
}
__device__ __forceinline__ void stsm4t(uint32_t a, uint32_t r0, uint32_t r1, uint32_t r2, uint32_t r3) {
  asm volatile("stmatrix.sync.aligned.m8n8.x4.trans.shared.b16 [%0], {%1,%2,%3,%4};" :: "r"(a), "r"(r0), "r"(r1), "r"(r2), "r"(r3) : "memory");
}
__device__ __forceinline__ uint4 ldr128(const void* p) {
  unsigned long long lo, hi;
  asm volatile("{ .reg .b128 t; ld.relaxed.gpu.global.b128 t, [%2]; mov.b128 {%0, %1}, t; }" : "=l"(lo), "=l"(hi) : "l"(p) : "memory");
  return make_uint4((uint32_t)lo, (uint32_t)(lo >> 32), (uint32_t)hi, (uint32_t)(hi >> 32));
}
__device__ __forceinline__ void str128(void* p, uint32_t x, uint32_t y, uint32_t z, uint32_t w) {
  asm volatile("{ .reg .b128 t; .reg .b64 lo, hi; mov.b64 lo, {%1,%2}; mov.b64 hi, {%3,%4}; mov.b128 t, {lo, hi}; st.relaxed.gpu.global.b128 [%0], t; }"
               :: "l"(p), "r"(x), "r"(y), "r"(z), "r"(w) : "memory");
}
__device__ __forceinline__ uint32_t ldr32(const void* p) { uint32_t v; asm volatile("ld.relaxed.gpu.global.b32 %0, [%1];" : "=r"(v) : "l"(p) : "memory"); return v; }
__device__ __forceinline__ void str32(void* p, uint32_t v) { asm volatile("st.relaxed.gpu.global.b32 [%0], %1;" :: "l"(p), "r"(v) : "memory"); }
__device__ __forceinline__ void str16(void* p, uint32_t v) { asm volatile("st.relaxed.gpu.global.u16 [%0], %1;" :: "l"(p), "h"((uint16_t)v) : "memory"); }
__device__ __forceinline__ void bar_sync(int id, int n) { asm volatile("bar.sync %0, %1;" :: "r"(id), "r"(n) : "memory"); }
__device__ __forceinline__ void bar_arrive(int id, int n) { asm volatile("bar.arrive %0, %1;" :: "r"(id), "r"(n) : "memory"); }

__device__ __forceinline__ float bf_lo(uint32_t w) { return __uint_as_float(w << 16); }
__device__ __forceinline__ float bf_hi(uint32_t w) { return __uint_as_float(w & 0xFFFF0000u); }
__device__ __forceinline__ uint32_t pack_bf(float lo, float hi) { uint32_t r; asm("cvt.rn.bf16x2.f32 %0, %1, %2;" : "=r"(r) : "f"(hi), "f"(lo)); return r; }
__device__ __forceinline__ uint32_t pack_h(float lo, float hi) { uint32_t r; asm("cvt.rn.f16x2.f32 %0, %1, %2;" : "=r"(r) : "f"(hi), "f"(lo)); return r; }
__device__ __forceinline__ float bfr(float x) { return bf_lo(pack_bf(x, 0.f)); }
__device__ __forceinline__ uint32_t bf_sub2(uint32_t a, uint32_t b) { __nv_bfloat162 r = __hsub2(*(__nv_bfloat162*)&a, *(__nv_bfloat162*)&b); return *(uint32_t*)&r; }
__device__ __forceinline__ uint32_t bf_add2(uint32_t a, uint32_t b) { __nv_bfloat162 r = __hadd2(*(__nv_bfloat162*)&a, *(__nv_bfloat162*)&b); return *(uint32_t*)&r; }
__device__ __forceinline__ uint32_t bf_mul2(uint32_t a, uint32_t b) { __nv_bfloat162 r = __hmul2(*(__nv_bfloat162*)&a, *(__nv_bfloat162*)&b); return *(uint32_t*)&r; }
__device__ __forceinline__ float2 h2f(uint32_t w) { return __half22float2(*(__half2*)&w); }
__device__ __forceinline__ float ex2(float x) { float r; asm("ex2.approx.ftz.f32 %0, %1;" : "=f"(r) : "f"(x)); return r; }
__device__ __forceinline__ float warp_sum(float v) {
#pragma unroll
  for (int o = 16; o > 0; o >>= 1) v += __shfl_xor_sync(0xffffffffu, v, o);
  return v;
}
__device__ __forceinline__ void mma_bf16(float* d, uint32_t a0, uint32_t a1, uint32_t a2, uint32_t a3, uint32_t b0, uint32_t b1) {
  asm volatile("mma.sync.aligned.m16n8k16.row.col.f32.bf16.bf16.f32 {%0,%1,%2,%3}, {%4,%5,%6,%7}, {%8,%9}, {%0,%1,%2,%3};"
               : "+f"(d[0]), "+f"(d[1]), "+f"(d[2]), "+f"(d[3]) : "r"(a0), "r"(a1), "r"(a2), "r"(a3), "r"(b0), "r"(b1));
}
__device__ __forceinline__ void mma_bf16_k8(float* d, uint32_t a0, uint32_t a1, uint32_t b0) {
  asm volatile("mma.sync.aligned.m16n8k8.row.col.f32.bf16.bf16.f32 {%0,%1,%2,%3}, {%4,%5}, {%6}, {%0,%1,%2,%3};"
               : "+f"(d[0]), "+f"(d[1]), "+f"(d[2]), "+f"(d[3]) : "r"(a0), "r"(a1), "r"(b0));
}

__device__ __forceinline__ void wg_fence() { asm volatile("wgmma.fence.sync.aligned;" ::: "memory"); }
__device__ __forceinline__ void wg_commit() { asm volatile("wgmma.commit_group.sync.aligned;" ::: "memory"); }
template <int N> __device__ __forceinline__ void wg_wait() { asm volatile("wgmma.wait_group.sync.aligned %0;" :: "n"(N) : "memory"); }
template <int TB> __device__ __forceinline__ void wgmma32(float* d, const uint32_t* a, uint32_t dlo, uint32_t dhi) {
  asm volatile("{ .reg .b64 dd; mov.b64 dd, {%20, %21}; wgmma.mma_async.sync.aligned.m64n32k16.f32.f16.f16 "
               "{%0,%1,%2,%3,%4,%5,%6,%7,%8,%9,%10,%11,%12,%13,%14,%15}, {%16,%17,%18,%19}, dd, 1, 1, 1, %22; }"
               : "+f"(d[0]), "+f"(d[1]), "+f"(d[2]), "+f"(d[3]), "+f"(d[4]), "+f"(d[5]), "+f"(d[6]), "+f"(d[7]), "+f"(d[8]), "+f"(d[9]), "+f"(d[10]), "+f"(d[11]), "+f"(d[12]), "+f"(d[13]), "+f"(d[14]), "+f"(d[15])
               : "r"(a[0]), "r"(a[1]), "r"(a[2]), "r"(a[3]), "r"(dlo), "r"(dhi), "n"(TB));
}
template <int TB> __device__ __forceinline__ void wgmma64(float* d, const uint32_t* a, uint32_t dlo, uint32_t dhi) {
  asm volatile("{ .reg .b64 dd; mov.b64 dd, {%36, %37}; wgmma.mma_async.sync.aligned.m64n64k16.f32.f16.f16 "
               "{%0,%1,%2,%3,%4,%5,%6,%7,%8,%9,%10,%11,%12,%13,%14,%15,%16,%17,%18,%19,%20,%21,%22,%23,%24,%25,%26,%27,%28,%29,%30,%31}, {%32,%33,%34,%35}, dd, 1, 1, 1, %38; }"
               : "+f"(d[0]), "+f"(d[1]), "+f"(d[2]), "+f"(d[3]), "+f"(d[4]), "+f"(d[5]), "+f"(d[6]), "+f"(d[7]), "+f"(d[8]), "+f"(d[9]), "+f"(d[10]), "+f"(d[11]), "+f"(d[12]), "+f"(d[13]), "+f"(d[14]), "+f"(d[15]), "+f"(d[16]), "+f"(d[17]), "+f"(d[18]), "+f"(d[19]), "+f"(d[20]), "+f"(d[21]), "+f"(d[22]), "+f"(d[23]), "+f"(d[24]), "+f"(d[25]), "+f"(d[26]), "+f"(d[27]), "+f"(d[28]), "+f"(d[29]), "+f"(d[30]), "+f"(d[31])
               : "r"(a[0]), "r"(a[1]), "r"(a[2]), "r"(a[3]), "r"(dlo), "r"(dhi), "n"(TB));
}
template <int TB> __device__ __forceinline__ void wgmma64_init(float* d, const uint32_t* a, uint32_t dlo, uint32_t dhi) {
  asm volatile("{ .reg .b64 dd; mov.b64 dd, {%36, %37}; wgmma.mma_async.sync.aligned.m64n64k16.f32.f16.f16 "
               "{%0,%1,%2,%3,%4,%5,%6,%7,%8,%9,%10,%11,%12,%13,%14,%15,%16,%17,%18,%19,%20,%21,%22,%23,%24,%25,%26,%27,%28,%29,%30,%31}, {%32,%33,%34,%35}, dd, 0, 1, 1, %38; }"
               : "=f"(d[0]), "=f"(d[1]), "=f"(d[2]), "=f"(d[3]), "=f"(d[4]), "=f"(d[5]), "=f"(d[6]), "=f"(d[7]), "=f"(d[8]), "=f"(d[9]), "=f"(d[10]), "=f"(d[11]), "=f"(d[12]), "=f"(d[13]), "=f"(d[14]), "=f"(d[15]), "=f"(d[16]), "=f"(d[17]), "=f"(d[18]), "=f"(d[19]), "=f"(d[20]), "=f"(d[21]), "=f"(d[22]), "=f"(d[23]), "=f"(d[24]), "=f"(d[25]), "=f"(d[26]), "=f"(d[27]), "=f"(d[28]), "=f"(d[29]), "=f"(d[30]), "=f"(d[31])
               : "r"(a[0]), "r"(a[1]), "r"(a[2]), "r"(a[3]), "r"(dlo), "r"(dhi), "n"(TB));
}
template <int TB> __device__ __forceinline__ void wgmma32_init(float* d, const uint32_t* a, uint32_t dlo, uint32_t dhi) {
  asm volatile("{ .reg .b64 dd; mov.b64 dd, {%20, %21}; wgmma.mma_async.sync.aligned.m64n32k16.f32.f16.f16 "
               "{%0,%1,%2,%3,%4,%5,%6,%7,%8,%9,%10,%11,%12,%13,%14,%15}, {%16,%17,%18,%19}, dd, 0, 1, 1, %22; }"
               : "=f"(d[0]), "=f"(d[1]), "=f"(d[2]), "=f"(d[3]), "=f"(d[4]), "=f"(d[5]), "=f"(d[6]), "=f"(d[7]), "=f"(d[8]), "=f"(d[9]), "=f"(d[10]), "=f"(d[11]), "=f"(d[12]), "=f"(d[13]), "=f"(d[14]), "=f"(d[15])
               : "r"(a[0]), "r"(a[1]), "r"(a[2]), "r"(a[3]), "r"(dlo), "r"(dhi), "n"(TB));
}
__device__ __forceinline__ void wgmma64h(uint32_t* d, uint32_t a0, uint32_t a1, uint32_t a2, uint32_t a3, uint32_t dlo, uint32_t dhi) {
  asm volatile("{ .reg .b64 dd; mov.b64 dd, {%20, %21}; wgmma.mma_async.sync.aligned.m64n64k16.f16.f16.f16 "
               "{%0,%1,%2,%3,%4,%5,%6,%7,%8,%9,%10,%11,%12,%13,%14,%15}, {%16,%17,%18,%19}, dd, 1, 1, 1, 0; }"
               : "+r"(d[0]), "+r"(d[1]), "+r"(d[2]), "+r"(d[3]), "+r"(d[4]), "+r"(d[5]), "+r"(d[6]), "+r"(d[7]), "+r"(d[8]), "+r"(d[9]), "+r"(d[10]), "+r"(d[11]), "+r"(d[12]), "+r"(d[13]), "+r"(d[14]), "+r"(d[15])
               : "r"(a0), "r"(a1), "r"(a2), "r"(a3), "r"(dlo), "r"(dhi));
}
__device__ __forceinline__ void wgmma64h_init(uint32_t* d, uint32_t a0, uint32_t a1, uint32_t a2, uint32_t a3, uint32_t dlo, uint32_t dhi) {
  asm volatile("{ .reg .b64 dd; mov.b64 dd, {%20, %21}; wgmma.mma_async.sync.aligned.m64n64k16.f16.f16.f16 "
               "{%0,%1,%2,%3,%4,%5,%6,%7,%8,%9,%10,%11,%12,%13,%14,%15}, {%16,%17,%18,%19}, dd, 0, 1, 1, 0; }"
               : "=r"(d[0]), "=r"(d[1]), "=r"(d[2]), "=r"(d[3]), "=r"(d[4]), "=r"(d[5]), "=r"(d[6]), "=r"(d[7]), "=r"(d[8]), "=r"(d[9]), "=r"(d[10]), "=r"(d[11]), "=r"(d[12]), "=r"(d[13]), "=r"(d[14]), "=r"(d[15])
               : "r"(a0), "r"(a1), "r"(a2), "r"(a3), "r"(dlo), "r"(dhi));
}
__device__ __forceinline__ void wgmma40_ss(float* d, uint32_t alo, uint32_t blo, uint32_t hi) {
  asm volatile("{ .reg .b64 da, db; mov.b64 da, {%20, %22}; mov.b64 db, {%21, %22}; "
               "wgmma.mma_async.sync.aligned.m64n40k16.f32.f16.f16 {%0,%1,%2,%3,%4,%5,%6,%7,%8,%9,%10,%11,%12,%13,%14,%15,%16,%17,%18,%19}, da, db, 1, 1, 1, 1, 1; }"
               : "+f"(d[0]), "+f"(d[1]), "+f"(d[2]), "+f"(d[3]), "+f"(d[4]), "+f"(d[5]), "+f"(d[6]), "+f"(d[7]), "+f"(d[8]), "+f"(d[9]), "+f"(d[10]), "+f"(d[11]), "+f"(d[12]), "+f"(d[13]), "+f"(d[14]), "+f"(d[15]), "+f"(d[16]), "+f"(d[17]), "+f"(d[18]), "+f"(d[19])
               : "r"(alo), "r"(blo), "r"(hi));
}
__device__ __forceinline__ void wgmma40_ss_init(float* d, uint32_t alo, uint32_t blo, uint32_t hi) {
  asm volatile("{ .reg .b64 da, db; mov.b64 da, {%20, %22}; mov.b64 db, {%21, %22}; "
               "wgmma.mma_async.sync.aligned.m64n40k16.f32.f16.f16 {%0,%1,%2,%3,%4,%5,%6,%7,%8,%9,%10,%11,%12,%13,%14,%15,%16,%17,%18,%19}, da, db, 0, 1, 1, 1, 1; }"
               : "=f"(d[0]), "=f"(d[1]), "=f"(d[2]), "=f"(d[3]), "=f"(d[4]), "=f"(d[5]), "=f"(d[6]), "=f"(d[7]), "=f"(d[8]), "=f"(d[9]), "=f"(d[10]), "=f"(d[11]), "=f"(d[12]), "=f"(d[13]), "=f"(d[14]), "=f"(d[15]), "=f"(d[16]), "=f"(d[17]), "=f"(d[18]), "=f"(d[19])
               : "r"(alo), "r"(blo), "r"(hi));
}
__device__ __forceinline__ void tma_box(uint32_t dst, const CUtensorMap* tm, uint32_t mb, int x, int y) {
  asm volatile("cp.async.bulk.tensor.2d.shared::cluster.global.mbarrier::complete_tx::bytes [%0], [%1, {%3, %4}], [%2];"
               :: "r"(dst), "l"(tm), "r"(mb), "r"(x), "r"(y) : "memory");
}
__device__ __forceinline__ uint32_t uni(uint32_t v) {
  uint32_t r; asm volatile("shfl.sync.idx.b32 %0, %1, 0, 0x1f, 0xffffffff;" : "=r"(r) : "r"(v)); return r;
}
__device__ __forceinline__ uint32_t pin(uint32_t v) {
  uint32_t r; asm volatile("shfl.sync.bfly.b32 %0, %1, 0, 0x1f, 0xffffffff;" : "=r"(r) : "r"(v)); return r;
}

struct Params {
  const unsigned char* x;
  Scratch* s;
  int off[8];
  uint32_t* out;
  const uint16_t* dskip;
  const uint32_t* w_r;
  long long* ts;
  const unsigned char* far[7];
  uint32_t sched[2][17];
};
__device__ __forceinline__ uint32_t ldnc32(const void* p) { uint32_t v; asm volatile("ld.global.nc.b32 %0, [%1];" : "=r"(v) : "l"(p)); return v; }
__device__ __forceinline__ uint32_t ldnc16(const void* p) { uint16_t v; asm volatile("ld.global.nc.u16 %0, [%1];" : "=h"(v) : "l"(p)); return v; }
__device__ __forceinline__ void mbar_wait(uint32_t mb, uint32_t ph = 0) {
#pragma unroll 1
  for (int it = 0; it < SPIN_MAX; it++) {
    uint32_t ok;
    asm volatile("{ .reg .pred q; mbarrier.try_wait.parity.shared::cta.b64 q, [%1], %2; selp.u32 %0, 1, 0, q; }" : "=r"(ok) : "r"(mb), "r"(ph) : "memory");
    if (ok) break;
  }
}
__device__ __forceinline__ void mbar_arrive(uint32_t mb) { asm volatile("mbarrier.arrive.shared::cta.b64 _, [%0];" :: "r"(mb) : "memory"); }
__device__ __forceinline__ void fence_async() { asm volatile("fence.proxy.async.shared::cta;" ::: "memory"); }
#define SPIN_WHILE(cond, body) _Pragma("unroll 1") for (int _it = 0; _it < SPIN_MAX && __any_sync(0xffffffffu, (cond)); _it++) { body; }

struct LnC { uint32_t m2, rh2, rl2; };
__device__ __forceinline__ LnC ln_consts(float s, float q, float& r) {
  const float mean = s * (1.f / DM);
  const float var = fmaxf(fmaf(-mean, mean, q * (1.f / DM)), 0.f);
  float sd;
  asm("sqrt.approx.ftz.f32 %0, %1;" : "=f"(sd) : "f"(bfr(bfr(var) + 1e-5f)));
  asm("rcp.approx.ftz.f32 %0, %1;" : "=f"(r) : "f"(bfr(sd)));
  LnC c;
  c.m2 = pack_bf(mean, mean);
  c.rh2 = pack_bf(r, r);
  const float rl = r - bf_lo(c.rh2);
  c.rl2 = pack_bf(rl, rl);
  return c;
}
__device__ __forceinline__ uint32_t bf_fma2(uint32_t a, uint32_t b, uint32_t c) {
  __nv_bfloat162 r = __hfma2(*(const __nv_bfloat162*)&a, *(const __nv_bfloat162*)&b, *(const __nv_bfloat162*)&c);
  return *(uint32_t*)&r;
}
__device__ __forceinline__ uint32_t ln_apply(uint32_t w, uint32_t m2, uint32_t rh2, uint32_t rl2) {
  const uint32_t d = bf_sub2(w, m2);
  return bf_fma2(d, rh2, bf_mul2(d, rl2));
}

__device__ __forceinline__ float2 cis(float mag_log2, float rev) {
  const float m = ex2(mag_log2), ang = rev * 6.283185307179586f;
  return make_float2(m * __cosf(ang), m * __sinf(ang));
}
__device__ __forceinline__ float2 csq(float2 a) { return make_float2(fmaf(a.x, a.x, -a.y * a.y), (a.x + a.x) * a.y); }
__device__ __forceinline__ float2 cmul(float2 a, float2 b) { return make_float2(fmaf(a.x, b.x, -a.y * b.y), fmaf(a.x, b.y, a.y * b.x)); }
__device__ __forceinline__ void pmul(uint32_t xr, uint32_t xi, uint32_t w, uint32_t& yr, uint32_t& yi) {
  const __half2 XR = *(__half2*)&xr, XI = *(__half2*)&xi, W = *(__half2*)&w;
  const __half2 a = __hfma2(__hneg2(XI), __high2half2(W), __hmul2(XR, __low2half2(W)));
  const __half2 b = __hfma2(XI, __low2half2(W), __hmul2(XR, __high2half2(W)));
  yr = *(const uint32_t*)&a; yi = *(const uint32_t*)&b;
}
__device__ __forceinline__ uint32_t pk(float2 a) { return pack_h(a.x, a.y); }

struct KgState { float2 c0, z8; float kl; uint32_t w64, w128, w192; };
__device__ __forceinline__ void kgen_tables_n(const uint32_t (&raw)[7], uint32_t scr, int wt, KgState& k) {
  const uint32_t dst = scr + 16384 + wt * 16;
  const float dt = bfr(ex2(bf_lo(raw[6]) * 1.4426950408889634f));
  const float th = dt * bf_lo(raw[1]);
  const float br = dt * bf_lo(raw[2]), bi = dt * bf_lo(raw[3]);
  const float Cr = bf_lo(raw[4]), Ci = bf_lo(raw[5]);
  k.c0 = make_float2(fmaf(Cr, br, -Ci * bi), fmaf(Cr, bi, Ci * br));
  const uint32_t mx = __reduce_max_sync(0xffffffffu, __float_as_uint(fmaxf(fabsf(k.c0.x), fabsf(k.c0.y))));
  const float a2 = dt * bf_lo(raw[0]) * 1.4426950408889634f;
  const float rh = th * 0.15915494309189535f;
  const float rl = fmaf(th, (float)(0.15915494309189535 - (double)0.15915494309189535f), fmaf(th, 0.15915494309189535f, -rh));
  const float rf = rh - rintf(rh);
  const float2 z1 = cis(a2, rf + rl);
  const float p64 = rf * 64.f;
  const float2 z64 = cis(a2 * 64.f, fmaf(64.f, rl, p64 - rintf(p64)));
  const float2 z2 = csq(z1), z128 = csq(z64), z3 = cmul(z2, z1), z4 = csq(z2), z256 = csq(z128), z6 = csq(z3), z512 = csq(z256);
  k.z8 = csq(z4);
  k.w64 = pk(z64); k.w128 = pk(z128); k.w192 = pk(cmul(z128, z64));
  sts128(dst, 0x00003C00u, pk(z2), pk(z4), pk(z6));
  const float2 z1024 = csq(z512), z768 = cmul(z512, z256);
  sts128(dst + 2048, pk(z1), pk(z3), pk(cmul(z4, z1)), pk(cmul(z4, z3)));
  const float2 z2048 = csq(z1024);
  k.kl = fmaf(k.c0.x, z2048.x, -k.c0.y * z2048.y);
  sts128(dst + 4096, pk(z256), pk(cmul(z256, z2)), pk(cmul(z256, z4)), pk(cmul(z256, z6)));
  sts128(dst + 6144, pk(z512), pk(cmul(z512, z4)), pk(z768), pk(cmul(z768, z4)));
  sts128(dst + 8192, pk(z1024), pk(cmul(z1024, z256)), pk(cmul(z1024, z512)), pk(cmul(z1024, z768)));
  sts32(scr + W_MISC + (wt >> 5) * 4, mx);
}
__device__ __forceinline__ int kgen_tables_m(uint32_t scr, int wt, const KgState& k) {
  const uint32_t dst = scr + wt * 16;
  const uint4 e4 = lds128(scr + W_MISC);
  const float2 z16 = csq(k.z8), z32 = csq(z16);
  const int em = max(min((int)(max(max(e4.x, e4.y), max(e4.z, e4.w)) >> 23), 238), 16);
  const float sc = __uint_as_float((uint32_t)(127 + 4 + 127 - em) << 23);
  sts32(scr + W_MISC + 16 + (wt >> 5) * 4, __reduce_add_sync(0xffffffffu, __float2int_rn(k.kl * sc * 262144.f)));
  const float2 c0 = make_float2(k.c0.x * sc, k.c0.y * sc);
  const float2 c1 = cmul(c0, k.z8), c2 = cmul(c0, z16), c4 = cmul(c0, z32), c3 = cmul(c1, z16), c5 = cmul(c1, z32), c6 = cmul(c2, z32), c7 = cmul(c3, z32);
  uint32_t pr[4], pi[4], yr[4], yi[4];
  pr[0] = pack_h(c0.x, c1.x); pi[0] = pack_h(c0.y, c1.y);
  pr[1] = pack_h(c2.x, c3.x); pi[1] = pack_h(c2.y, c3.y);
  pr[2] = pack_h(c4.x, c5.x); pi[2] = pack_h(c4.y, c5.y);
  pr[3] = pack_h(c6.x, c7.x); pi[3] = pack_h(c6.y, c7.y);
  sts128(dst, pr[0], pr[1], pr[2], pr[3]); sts128(dst + 2048, pi[0], pi[1], pi[2], pi[3]);
#pragma unroll
  for (int q = 1; q < 4; q++) {
    const uint32_t w = q == 1 ? k.w64 : q == 2 ? k.w128 : k.w192;
#pragma unroll
    for (int i = 0; i < 4; i++) pmul(pr[i], pi[i], w, yr[i], yi[i]);
    sts128(dst + q * 4096, yr[0], yr[1], yr[2], yr[3]); sts128(dst + q * 4096 + 2048, yi[0], yi[1], yi[2], yi[3]);
  }
  return em;
}
__device__ __forceinline__ uint32_t lds32_if(uint32_t a, bool on) {
  uint32_t v; asm volatile("{ .reg .pred q; setp.ne.u32 q, %2, 0; mov.b32 %0, 0; @q ld.shared.b32 %0, [%1]; }" : "=r"(v) : "r"(a), "r"((uint32_t)on) : "memory"); return v;
}
__device__ __forceinline__ uint32_t prmt(uint32_t a, uint32_t b, uint32_t s) { uint32_t r; asm("prmt.b32 %0, %1, %2, %3;" : "=r"(r) : "r"(a), "r"(b), "r"(s)); return r; }
__device__ __forceinline__ void kgen_build(uint32_t tb, int wg, int wt, uint32_t k0, uint32_t k1, uint32_t k2) {
  const uint32_t kt = tb + W_KT, sc = tb + W_L3 + 3072;
  const int ix = ((wt >> 2) + (wt & 3) * 32 - 1) & 127;
  const uint32_t a3 = tb + W_CW + 32 + ((ix & 1) ? 0 : 304) + (ix >> 1) * 4, a2 = sc + 544 + (wt & ~3) * 2 + (wt & 1) * 4 + (wt & 2) * 128;
  const uint32_t v3 = wt ? k2 : k2 >> 16;
  sts32(sc + 4 + wt * 4, __byte_perm(k0, k1, 0x5432));
  sts16(a2, k1 >> 16); sts16(a2 + 6, k1 >> 16);
  sts16(a3, v3); sts16(a3 + 6, v3);
  if ((unsigned)(wt - 32) < 14u) sts128(kt + (wt < 36 ? -512 : 64 + 4128 - 576) + wt * 16, 0, 0, 0, 0);
  if (wt == 127) sts32(sc, k0 & 0xFFFF0000u);
  if (wt == 0) { sts32(sc + 516, k1); sts16(sc + 1056, k2); }
  bar_sync(1 + wg, 128);
  const uint32_t cw = tb + W_CW + 32 + (wt >> 6) * 48 + wt * 4, g2 = sc + 540 + wt * 4;
  const bool odd = wt & 1, ends = (unsigned)(wt - 4) >= 120u;
  const uint32_t pv = lds32(sc + wt * 4), nx = lds32(sc + 8 + wt * 4), nc = lds32_if(g2 + 8, ends);
  const uint32_t l0 = lds32(cw), l1 = lds32(cw - 8), l2 = lds32(cw - 16), l3 = lds32(cw - 24), q0 = lds32(g2), q1 = lds32(g2 + 128), q2 = lds32(g2 - 8), q3 = lds32(g2 + 120);
  sts64(kt + 64 + wt * 8, __byte_perm(k0, pv, 0x5410), __byte_perm(k0, 0, 0x1032));
  sts64(kt + 64 + 1024 + wt * 8, __byte_perm(k1, pv, (odd || wt == 0) ? 0x7610 : 0x1010), __byte_perm(k1, nx, odd ? 0x1076 : 0x1010));
  const uint32_t cc = __byte_perm(nc, 0, 0x3232), nn = __byte_perm(nc, 0, 0x1010);
  if (ends) sts128(kt + 64 + 2048 + wt * 16, cc, cc, odd ? nc : cc, odd ? nn : nc);
  if (wt == 127) { sts128(kt + 64 + 4096, nn, nn, nn, nn); sts128(kt + 64 + 4112, nn, nn << 16, 0, 0); }
  sts128(tb + W_L3 + 512 + (wt >> 6) * 512 + wt * 16, l0, l1, l2, l3);
  if ((wt & 63) < 34) sts128(tb + W_QT - 16 + wt * 16, q0, q1, q2, q3);
}

__device__ __forceinline__ void load_a(uint32_t (&a)[4], uint32_t kp, int j) {
  a[0] = lds32(kp + 64 * j); a[1] = lds32(kp + 64 * j + 512); a[2] = lds32(kp + 64 * j - 32); a[3] = lds32(kp + 64 * j + 480);
}
__device__ __forceinline__ uint32_t band(int d, int lo, int hi) {
  return ((unsigned)(d - lo) <= (unsigned)(hi - lo) ? 1u : 0u) | ((unsigned)(d - 1 - lo) <= (unsigned)(hi - lo) ? 0x10000u : 0u);
}
__device__ __forceinline__ uint32_t hadd2u(uint32_t a, uint32_t b) { __half2 r = __hadd2(*(__half2*)&a, *(__half2*)&b); return *(uint32_t*)&r; }

__device__ __forceinline__ void zero_pads(uint32_t tb, int wt) {
  if (!(wt & 32)) sts128(tb + W_L3 + (wt >> 6) * 512 + wt * 16, 0, 0, 0, 0);
  if ((wt & 63) < 3) sts128(tb + W_CW + (wt >> 6) * 304 + (wt & 63) * 16, 0, 0, 0, 0);
}
__device__ __forceinline__ uint32_t tr_base(int lane) {
  return OFF_YT + (2 * (lane >> 3) + (lane & 1)) * YT_PITCH + ((lane >> 1) & 1) * (8 * YT_PITCH + 64) + ((lane >> 2) & 1) * 16;
}

__device__ __forceinline__ uint32_t sc_addr(int tp) { return OFF_YT + (tp < 16 ? tp * YT_PITCH + (tp >> 3) * 64 + 1152 : 8 * YT_PITCH - 512 + tp * 32); }
#define X_PW 15
#define X_HU 16
#define X_NE 2
#define X_SCT 10000
#define X_DELTA 0
#define X_DSTEP 2000
#define X_PF0 2700
#define X_PFD 600
#define X_TD 450
#define X_WS 6
#define X_OR 8
#define X_ABS 4950
#define X_XD 200
#define X_RD 630
#define X_HD 450
#define X_PD 1170
#define X_PROMO 2
#define X_YD2 1000
#define X_GO 1
#define X_GW 2
#define X_NS 4300
#define X_XS 13450
#define X_LAG 1300
#define X_YD 1550
struct TMaps { CUtensorMap m[10]; };
__device__ __forceinline__ uint32_t h2bf(uint32_t w) { const float2 f = h2f(w); return pack_bf(f.x, f.y); }
__device__ __forceinline__ uint32_t keep(uint32_t v) { asm volatile("" : "+r"(v)); return v; }
__device__ __forceinline__ uint2 ldr64(const void* p) { uint2 v; asm volatile("{ .reg .b64 t; ld.relaxed.gpu.global.b64 t, [%2]; mov.b64 {%0, %1}, t; }" : "=r"(v.x), "=r"(v.y) : "l"(p) : "memory"); return v; }
__host__ __device__ __forceinline__ uint32_t down_box(int s, bool five) {
  return five ? OFF_W + W_BYTES + 12288 + (s / 3) * (W_BYTES - 12288) + s * 4096 : s < 6 ? OFF_W + W_BYTES + BOX + (s >> 1) * (W_BYTES - 10240) + s * 5120 : OFF_W + (s - 6) * 5120;
}
__device__ __forceinline__ void load_tile(const CUtensorMap* tmx, int i, int c, int again = 0) {
  asm volatile("mbarrier.arrive.expect_tx.shared::cta.b64 _, [%0], 8704;" :: "r"(MB_UL + i * 16 + again) : "memory");
  asm volatile("cp.async.bulk.tensor.3d.shared::cluster.global.mbarrier::complete_tx::bytes [%0], [%1, {%3, %4, %5}], [%2];"
               :: "r"(i < 2 ? OFF_T + i * TILE : OFF_W), "l"(tmx), "r"(MB_UL + i * 16 + again), "r"(0), "r"(c), "r"(-8) : "memory");
}
template <bool FAR> __device__ __forceinline__ void load_params(const Params& p, uint32_t ch, int wt, uint32_t dst, bool on) {
  const int rel = wt < 96 ? ch * 16 + (wt & 15) : ch >> 3;
  const unsigned char* b = FAR ? p.far[min(wt >> 4, 6)] + rel * 16 : p.x + (long long)(p.off[wt >> 4] + rel) * 16;
  asm volatile("{ .reg .pred q; setp.ne.u32 q, %2, 0; @q cp.async.cg.shared.global [%0], [%1], 16; }"
               :: "r"(dst + wt * 16), "l"(b), "r"((uint32_t)(on && wt < 97)) : "memory");
}

struct ConvC { uint32_t ca, cb, bands, qa; };
__device__ __forceinline__ ConvC conv_consts(int w, int lane) {
  const int h = w & 1, P = (w >> 1) & 1, d0 = 8 * h + (lane >> 2) - 2 * (lane & 3);
  ConvC k;
  k.ca = keep((W_KT + (16 + 256 * P + d0) * 4) | (((8 + 64 * P + lane) * 64 + (((h + ((w >> 1) & 2)) ^ (lane >> 1)) & 3) * 16) << 16));
  const int u = d0 + 2 * (lane & 1) + 2, in = (u & 7) - ((u & 7) >= 5 ? 5 : 0) - 2 * (lane & 1);
  k.cb = keep(in > 0 ? 0x1010 : in == 0 ? 0x3210 : 0x3232);
  k.qa = keep(W_QT + (2 * (u >> 3) + ((u & 7) >= 5) + 64 * P) * 16);
  k.bands = keep(band(d0, 12, 20) + 2 * band(d0 + 8, 12, 20) + 4 * band(d0 + 16, 12, 20) + 8 * band(d0 + 24, 12, 20)
                 + 16 * band(d0 - 8, 5, 11) + 32 * band(d0, 5, 11) + 64 * band(d0 + 8, 5, 11) + 128 * band(d0 + 16, 5, 11));
  return k;
}
struct ConvPre { uint32_t e0, e2, f2, b0, b2, a[3][4]; };
__device__ __forceinline__ void conv_pre(ConvPre& r, uint32_t kp, uint32_t qp, int part, bool on, bool P) {
  if (part & 1) {
    r.e0 = lds32_if(kp + 4096, on && !P); r.e2 = lds32_if(kp + 4064, on && !P); r.f2 = lds32_if(kp + 4128, on && !P);
    r.b0 = lds32_if(kp + 2048, on && !P); r.b2 = lds32_if(kp + 2016, on && !P);
  }
#pragma unroll
  for (int j = 0; j < 3; j++) if (part & (j < 1 ? 1 : 2))
    asm volatile("{ .reg .pred q; setp.ne.u32 q, %5, 0; mov.b32 %0, 0; mov.b32 %1, 0; mov.b32 %2, 0; mov.b32 %3, 0; @q ld.shared.v4.b32 {%0,%1,%2,%3}, [%4]; }"
                 : "=r"(r.a[j][0]), "=r"(r.a[j][1]), "=r"(r.a[j][2]), "=r"(r.a[j][3]) : "r"(qp + 64 * j), "r"((uint32_t)on) : "memory");
}
__device__ __forceinline__ void conv_item(uint32_t tb, uint32_t tl, int bid, int bn, ConvPre& pre, const ConvC& cv, uint32_t zero, const CUtensorMap* tmx, int ch, int warp, int lane, bool hold, bool more) {
  const bool go = more && warp == 0 && lane == 0;
  const uint32_t kp = tb + (cv.ca & 0xFFFFu), qp = tb + cv.qa;
  const uint32_t dlo = (tl >> 4) + 32 + ((warp >> 1) & 2) + (1u << 16), dhi = 32u | (2u << 30);
  const bool P = warp & 2;
  float a32[16], b32[16], a64[32];
  uint32_t A[40][4];
#define STEP(J) { wgmma64<0>(a64, A[J], dlo + 256 - 4 * (J), dhi); \
    if ((J) == 32) wgmma32_init<0>(b32, A[J], dlo, dhi); else wgmma32<0>(b32, A[J], ((J) < 8 ? dlo ^ zero : dlo) + 128 - 4 * (J), dhi); \
    if ((J) == 0) wgmma32_init<0>(a32, A[J], dlo, dhi); else if ((J) < 8) wgmma32<0>(a32, A[J], (dlo ^ zero) - 4 * (J), dhi); }
#define LD(J) load_a(A[J], kp, J);
#define LQ(J) { const uint4 v = lds128(qp + 64 * ((J) - 32)); A[J][0] = v.x; A[J][1] = v.y; A[J][2] = v.z; A[J][3] = v.w; }
#define PQ(J) { A[J][0] = prmt(A[J][0], 0, cv.cb); A[J][1] = prmt(A[J][1], 0, cv.cb); A[J][2] = prmt(A[J][2], 0, cv.cb); A[J][3] = prmt(A[J][3], 0, cv.cb); }
#define FIRST(J) wg_fence(); STEP(J) wg_commit(); wg_wait<1>(); wg_fence();
  {
    uint32_t win[16], x9[4], x7[4], e[4], f[4];
    const uint32_t bz = keep(cv.bands);
#define BAND(i) keep((bz & (0x10001u << (i))) * (0x3C00u >> (i)))
    e[0] = pre.e0; e[2] = pre.e2; e[1] = keep(bz & 0x100u); e[3] = keep(bz & 0x200u);
    f[2] = pre.f2; f[0] = keep(bz & 0x4000u); f[1] = keep(bz & 0x8000u); f[3] = keep(bz & 0x300u);
#pragma unroll
    for (int j = 0; j < 12; j++) A[32 + j / 4][j & 3] = pre.a[j / 4][j & 3];
    PQ(32) PQ(33) PQ(34)
    if (!P) { A[32][0] = pre.b0; A[32][2] = pre.b2; }
    const uint32_t q[12] = {BAND(0), BAND(5), keep(bz & 0x400u), BAND(4), BAND(2), BAND(7), BAND(1), BAND(6), keep(bz & 0x800u), keep(bz & 0x1000u), BAND(3), keep(bz & 0x2000u)};
#undef BAND
    const uint32_t ta = keep(tl + 512 + (warp & 3) * 2048 + lane * 64 + (lane & 6) * 8);
    if (X_GO && hold) mbar_wait(MB_GO);
    uint32_t mbl = MB_UL + (warp & 8) * 2, ph = 0;
#pragma unroll 1
    for (int it = 0; it < SPIN_MAX; it++) {
      if (ch < 512) mbar_wait(mbl, ph);
      if (it == 1) TS(13);
      TS(3);
      wg_fence();
      wgmma64h_init(win, q[0], q[1], q[2], q[3], dlo, dhi);
      wgmma64h(win, q[4], q[5], q[6], q[7], dlo - 4, dhi);
      wgmma64h(win, q[8], q[9], q[10], q[11], dlo - 8, dhi);
      wg_commit();
      wgmma64_init<0>(a64, e, dlo, dhi);
      wgmma64<0>(a64, f, dlo - 4, dhi);
      wg_commit();
      if (ch >= 512) break;
      uint32_t r0, r1, r2, r3, ok;
      if (warp & 4) {
        mbar_wait(mbl + 8);
        if (__all_sync(0xffffffffu, it || lds32(MISC_RT + (warp & 8)) == 0)) break;
        wg_wait<0>();
        continue;
      }
      ldsm4(ta, r0, r1, r2, r3);
      ok = r0 & r1 & r2 & r3;
      ldsm4(ta ^ 32, r0, r1, r2, r3);
      asm volatile("{ .reg .pred q; setp.ne.u32 q, %1, 0; barrier.red.and.pred q, %2, 128, q; selp.u32 %0, 1, 0, q; }" : "=r"(ok) : "r"((ok & r0 & r1 & r2 & r3 & 1u) | (lane & 3)), "r"(1 + (warp >> 2)) : "memory");
      if (ok) { if ((warp & 3) == 0 && lane == 0) { sts32(MISC_RT + warp, it); mbar_arrive(MB_UL + 8 + warp * 2); } break; }
      wg_wait<0>();
      if ((warp & 3) == 0 && lane == 0) load_tile(tmx - 1, warp >> 3, ch, 56);
      mbl = MB_UL + 56 + (warp & 8) * 2; ph = it & 1;
    }
    wg_wait<1>();
#pragma unroll
    for (int i = 0; i < 4; i++) {
      const int tl = 2 * ((i & 1) + ((i & 2) ? 0 : 4));
      x9[i] = P ? win[tl + 4] : win[tl]; x7[i] = P ? win[tl + 5] : win[tl + 1];
    }
    const uint32_t l3lo = ((tb + W_L3) >> 4) + (32u << 16);
    wg_fence();
    wgmma64<0>(a64, x9, l3lo, 8);
    wgmma64<0>(a64, x7, l3lo + 96, 8);
    wg_commit();
  }
  STEP(32) STEP(33) STEP(34) wg_commit(); wg_wait<1>();
  LQ(35) LQ(36) LQ(37) LQ(38) PQ(35) PQ(36) PQ(37) PQ(38)
  FIRST(35) STEP(36) STEP(37) STEP(38) wg_commit();
  LQ(39) LD(0) PQ(39)
  TS(17);
  if (X_GO == 1 && go) mbar_arrive(MB_GO);
  FIRST(39) STEP(0) wg_commit();
  LD(1) LD(2) LD(3)
  FIRST(1) STEP(2) STEP(3) wg_commit();
  LD(4) LD(5)
  if (X_GO == 2 && go) mbar_arrive(MB_GO);
  FIRST(4) STEP(5) wg_commit();
  LD(6) LD(7)
  wg_fence(); STEP(6) STEP(7) wg_commit();
#undef STEP
#undef LD
#undef LQ
#undef PQ
#undef FIRST
  TS(18);
  if (X_GO == 3 && go) mbar_arrive(MB_GO);
  const uint32_t xc = tb + W_KT + (warp & 3) * 1024 + lane * 16;
  if (more) bar_sync(7, 288);
  wg_wait<1>();
  conv_pre(pre, kp + ALT, qp + ALT, 1, more, P);
  wg_wait<0>();
  conv_pre(pre, kp + ALT, qp + ALT, 2, more, P);
  uint32_t E[16], o[8];
#define ACC(i) ((i) < 16 ? a32[i] : (i) < 32 ? b32[(i) - 16] : a64[(i) - 32])
  E[0] = pack_h(a32[0], a32[1]);
#pragma unroll
  for (int i = 1; i < 16; i++) E[i] = pack_h(ACC(4 * i) + ACC(4 * i - 2), ACC(4 * i + 1) + ACC(4 * i - 1));
#undef ACC
#pragma unroll
  for (int j = 0; j < 8; j++) o[j] = P ? (j < 2 ? 0u : E[j - 2]) : E[8 + j];
  sts128(xc, o[0], o[1], o[2], o[3]); sts128(xc + 512, o[4], o[5], o[6], o[7]);
#pragma unroll
  for (int j = 0; j < 8; j++) o[j] = P ? E[6 + j] : E[j];
  TS(25);
  if (more) {
    sts128(xc + 4096, o[0], o[1], o[2], o[3]); sts128(xc + 4608, o[4], o[5], o[6], o[7]);
    bar_arrive(12, 192);
    return;
  }
  bar_sync(1 + (warp >> 2), 128);
  const uint4 vv[2] = {lds128(xc + (P ? -2048 : 2048)), lds128(xc + (P ? -1536 : 2560))};
  const uint32_t mk = lane < 8 ? 0xFFFEFFFEu : ~0u;
#pragma unroll
  for (int q = 0; q < 2; q++) {
    const uint4 v = vv[q];
    stsm4t(tl + (cv.ca >> 16) + q * 2048, hadd2u(o[4 * q], v.x) & mk, hadd2u(o[4 * q + 1], v.y) & mk, hadd2u(o[4 * q + 2], v.z) & mk, hadd2u(o[4 * q + 3], v.w) & mk);
  }
  fence_async();
  bar_sync(bid, bn);
  if (warp == 0 && lane == 0) mbar_arrive(MB_REL);
  if ((warp & 7) == (ch < 512 ? 7 : 3) && lane == 0) {
    asm volatile("cp.async.bulk.tensor.3d.global.shared::cta.bulk_group [%0, {%3, %2, %3}], [%1];" :: "l"(tmx), "r"(tl + 512), "r"(ch), "r"(0) : "memory");
    asm volatile("cp.async.bulk.commit_group;" ::: "memory");
  }
}

template <bool FAR> __global__ void __launch_bounds__(NT, 1)
fused_kernel(const __grid_constant__ Params p, const __grid_constant__ TMaps tm) {
  extern __shared__ __align__(1024) unsigned char smem[];
  const int c = blockIdx.x;
  const bool five = (c & 1) == 0;
  const uint32_t pitch = five ? 64 : 80;
  const uint32_t ones = 0x3F803F80u;
  const int tid = threadIdx.x, lane = tid & 31;
  const uint32_t xrow = OFF_YT + ((tid & 127) >> 3) * YT_PITCH + (tid & 64) + (tid & 7) * 16;
  {
    const int w4 = tid >> 7;
    load_params<FAR>(p, w4 < 2 ? 2 * c + w4 : five ? 257 + 2 * c : 512 + (c >> 1), tid & 127, OFF_W + W_KT + (w4 < 2 ? w4 * W_BYTES : five ? 3 * W_BYTES : 3 * W_BYTES + 2048), (0xB >> w4) & 1);
  }
  if ((tid >> 7) == 2) {
    const unsigned char* xp = p.x + (uint32_t)((c * 16 - 32 + (tid >> 3)) * 1152 + (tid & 7) * 16);
    asm volatile("" : "+l"(xp));
    { const uint32_t tq = clock(); while ((int)(clock() - tq) < X_XD) {} }
#pragma unroll
    for (int k = 0; k < 9; k++) asm volatile("cp.async.cg.shared.global [%0], [%1], 16;" :: "r"(xrow + k * 128), "l"(xp + k * 128) : "memory");
  }
  const int warp = (int)uni(tid >> 5), wg = warp >> 2;
  TS(0);
  if (__builtin_expect(wg == 4, 0)) {
    asm volatile("setmaxnreg.dec.sync.aligned.u32 32;");
    const int role = warp;
    const int u0 = (c >> 1) * 9 + (five ? ((c & 2) ? 5 : 0) : ((c & 2) ? 0 : 4));
    const uint32_t t0 = clock() + c * 4;
    if (role == 16) {
      if (lane == 0) {
#pragma unroll
        for (int i = 0; i < 19; i++) if (i != 16) asm volatile("mbarrier.init.shared::cta.b64 [%0], %1;" :: "r"(OFF_MISC + i * 8), "r"((unsigned)(i - 2) < 4u ? 4 : 1) : "memory");
      }
      __syncwarp();
      if (lane < 2) asm volatile("mbarrier.arrive.expect_tx.shared::cta.b64 _, [%0], %1;" :: "r"(OFF_MISC + lane * 8), "r"(lane ? (five ? 36864 : 51200) : pitch * 1152) : "memory");
      fence_async();
      bar_arrive(5, 608);
      const CUtensorMap* tmb = &tm.m[five ? 3 : 0];
#pragma unroll 1
      for (int u = 0; u < 17; u++) {
        const uint32_t e = p.sched[five][u], kind = e & 3, s = (e >> 2) & 15, dst = e >> 14;
        if (kind == 3) continue;
        while ((int)(clock() - t0) < X_PF0 + (u < X_NE ? u * X_PFD : X_LAG + u * X_TD)) __nanosleep(20);
        if (e & 0x3FC0) mbar_wait(OFF_MISC + ((e >> 6) & 255));
        if (lane == 0) {
          if (kind == 2) asm volatile("cp.async.bulk.tensor.3d.shared::cluster.global.mbarrier::complete_tx::bytes [%0], [%1, {%3, %4, %5}], [%2];"
                                      :: "r"(dst), "l"(tmb + 2), "r"(MB_D), "r"(0), "r"(u0 * 8), "r"(s) : "memory");
          else tma_box(dst, tmb + kind, MB_GU, u0 * 8, s * 96);
        }
        if (u == 5) TS(2);
        if (u == 10) TS(3);
      }
      TS(4);
      TS_DUMP();
#define FINISH0 bar_sync(12, 192);        \
        _Pragma("unroll 1") for (int w = role & 2; w < (role & 2) + 2; w++) { \
          const uint32_t xa = OFF_W + W_KT + lane * 16, mk = lane < 8 ? 0xFFFEFFFEu : ~0u, ya = OFF_T + (8 + lane) * 64 + (((w & 1) ^ (lane >> 1)) & 3) * 16 + (w & 2) * 2048; \
          const uint4 a = lds128(xa + 4096 + w * 1024), b = lds128(xa + (w ^ 2) * 1024), d = lds128(xa + 4608 + w * 1024), e = lds128(xa + 512 + (w ^ 2) * 1024); \
          stsm4t(ya, hadd2u(a.x, b.x) & mk, hadd2u(a.y, b.y) & mk, hadd2u(a.z, b.z) & mk, hadd2u(a.w, b.w) & mk); \
          stsm4t(ya + 2048, hadd2u(d.x, e.x) & mk, hadd2u(d.y, e.y) & mk, hadd2u(d.z, e.z) & mk, hadd2u(d.w, e.w) & mk); \
        } \
        fence_async();
    } else if (role == 17) {
      if (smem_u32(smem) != SB) __trap();
      bar_sync(10, 576);
      if (lane == 0) {
        fence_async();
        while ((int)(clock() - t0) < X_NS - c * 4) {}
        asm volatile("cp.async.bulk.global.shared::cta.bulk_group [%0], [%1], 10240;" :: "l"(&p.s->X[c * DM * 2 + 512]), "r"(OFF_G) : "memory");
        asm volatile("cp.async.bulk.commit_group;" ::: "memory");
        asm volatile("cp.async.bulk.wait_group 0;" ::: "memory");
      }
      if (lane == 0) mbar_arrive(MB_GF);
      bar_arrive(11, 96);
      if (five) { FINISH0 bar_arrive(13, 192); }
    } else if (role == 18) {
      sts32(MISC_EPOCH, 0);
      sts32(MISC_T0, t0 - c * 4);
      bar_arrive(5, 608);
      uint4* q = lane < 2 ? &p.s->R[c * 2 + lane] : lane < 11 ? &p.s->HS[c * 9 + lane - 2] : lane == 11 ? &p.s->HS[1152 + (c & 7)] : (uint4*)&p.s->FLAG[c * 8];
      if (lane < (c < 8 ? 12 : 11)) str128(q, ~0u, ~0u, ~0u, ~0u);
      const uint32_t ep = __shfl_sync(0xffffffffu, ldr32(q), 31) + 1u;
      sts32(MISC_EPOCH, ep | 0x80000000u);
      TSX(21);
      if (lane == 31) str32(q, ep);
      bar_sync(11, 96);
      TSX(14);
      mbar_wait(MB_KF + (lane & 3) * 8);
      __syncwarp();
      { const uint2 e = lds64(MISC_EM); if (lane < 2) str128(&p.s->SC[c * 2 + lane], e.x, __byte_perm(e.y, ep, 0x6540), 0, 0); }
      TSX(17);
      while ((int)(clock() - t0) < X_SCT) __nanosleep(100);
      TSX(18);
      {
        uint2 v[4];
#pragma unroll 1
        for (int it = 0; it < SPIN_MAX; it++) {
          uint32_t bad = 0;
#pragma unroll
          for (int q = 0; q < 4; q++) v[q] = ldr64(&p.s->SC[lane * 2 + q * 64]);
#pragma unroll
          for (int q = 0; q < 4; q++) bad |= (v[q].y >> 8) ^ (ep & 0xFFFFFFu);
          if (!__any_sync(0xffffffffu, bad)) break;
        }
        TSX(25);
#pragma unroll
        for (int q = 0; q < 4; q++) {
          const uint32_t sa = (lane >> 4) * YT_PITCH + (lane & 15) * 2;
          sts16(sc_addr(2 * q) + sa, v[q].x); sts16(sc_addr(8 + 2 * q) + sa, v[q].x >> 16);
          if (lane & 1) asm volatile("st.shared.u8 [%0], %1;" :: "r"(sc_addr(16) + q * 16 + (lane >> 1)), "r"(v[q].y) : "memory");
        }
      }
      __syncwarp();
      if (lane == 0) mbar_arrive(MB_SC);
      TSX(27);
    } else {
      uint32_t w[9];
      const uint32_t dk = ldnc16(p.dskip + ((lane & 4) ? 512 + (c >> 1) : (lane & 2) * 128 + 2 * c + (lane & 1)));
      float s = 0.f;
#pragma unroll
      for (int i = 0; i < 9; i++) w[i] = ldnc32(p.w_r + lane + 32 * i);
      sts16(OFF_WR + 1152 + lane * 2, dk);
      bar_arrive(5, 608);
#pragma unroll
      for (int i = 0; i < 9; i++) { sts32(OFF_WR + lane * 4 + i * 128, w[i]); s += bf_lo(w[i]) + bf_hi(w[i]); }
      sts32(MISC_SW, __float_as_uint(warp_sum(s)));
      TSX(23);
      bar_sync(10, 576);
      if (lane == 0) {
        const uint32_t tp = clock();
        TSX(1);
        while ((int)(clock() - tp) < X_DELTA || (int)(clock() - t0) < X_ABS - c * 4) {}
        TSX(24);
        load_tile(&tm.m[6], 0, c);
        TSX(15);
        while ((int)(clock() - t0) < X_ABS + X_DSTEP - c * 4) {}
      }
      bar_sync(11, 96);
      if (lane == 0) {
        load_tile(&tm.m[6], 1, 128 + c);
      }
      if (five) {
        mbar_wait(MB_KF);
#pragma unroll 1
        for (int it = 0; it < SPIN_MAX; it++) {
          if (lane == 0) load_tile(&tm.m[8], 2, 512 + (c >> 1));
          mbar_wait(MB_UL + 32, it & 1);
          uint32_t m = 1;
#pragma unroll
          for (int q = 0; q < 4; q++) { uint32_t r0, r1, r2, r3; ldsm4(OFF_W + 512 + lane * 64 + (lane & 6) * 8 + q * 2048, r0, r1, r2, r3); m &= r0 & r1 & r2 & r3; }
          if (__all_sync(0xffffffffu, m || (lane & 3))) break;
        }
        bar_arrive(7, 288);
        FINISH0
        bar_arrive(13, 192);
      }
      bar_sync(0, 544);
      if (lane == 0) mbar_arrive(MB_H);
    }
    return;
  }
  const int wt = tid & 127, g = lane >> 2, t = lane & 3;
  const uint32_t wb = OFF_W + wg * W_BYTES;
  asm volatile("cp.async.commit_group;" ::: "memory");
  const ConvC cv = conv_consts(warp, lane);
  zero_pads(wb, wt);
  load_params<FAR>(p, 254 + 2 * c + wg, wt, wb + W_KT, wg == 2 || (wg == 3 && !five));
  asm volatile("cp.async.commit_group;" ::: "memory");
  asm volatile("setmaxnreg.inc.sync.aligned.u32 112;");
  {
    uint4 kw;
    uint4* kx = &p.s->KX[(c >> 1) * 128 + wt];
    bool two = wg == 3;
    uint32_t ep;
    int em = 0;
    uint32_t slot = wg + (two && !five);
    const uint32_t ra0 = wb + W_KT + (slot & 4) * 512 + wt * 2, ra6 = wb + W_KT + 1536 + (slot & 4) * 512 + (((slot & 4) ? c >> 1 : 2 * c + (wg & 1)) & 7) * 2;
    uint32_t raw[7];
    if (wg != 2) {
      asm volatile("cp.async.wait_group 1;" ::: "memory");
      bar_sync(1 + wg, 128);
#pragma unroll
      for (int i = 0; i < 7; i++) raw[i] = lds16(i < 6 ? ra0 + i * 256 : ra6);
    }
    int phase = wg == 2 ? 3 : 2;
#pragma unroll 1
    for (;;) {
      if (phase != 3) {
        KgState ks;
        TS(22);
        kgen_tables_n(raw, wb, wt, ks);
        TS(20);
        bar_sync(1 + wg, 128);
        em = kgen_tables_m(wb, wt, ks);
        fence_async();
      }
      if (phase & 2) {
        const int lz = lane ^ (clock() & p.off[7]);
        const uint32_t tr_addr = pin(tr_base(lz) + warp * 32), lca = pin(MISC_LN1 + (lz & 1) * 16);
        uint4* dst;
        { const unsigned long long a = (unsigned long long)&p.s->X[c * DM * 2 + warp * 32 + (8 * ((lz >> 1) & 1) + (lz >> 2)) * 2 + (lz & 1)];
          dst = (uint4*)(((unsigned long long)pin(a >> 32) << 32) | pin((uint32_t)a)); }
        if (phase == 3) {
        asm volatile("cp.async.wait_group 1;" ::: "memory");
        TS(21);
        float d[3][4], r;
        uint4 a[9];
#pragma unroll
        for (int k = 0; k < 9; k++) a[k] = lds128(xrow + k * 128);
#pragma unroll
        for (int i = 0; i < 4; i++) d[0][i] = d[1][i] = d[2][i] = 0.f;
#pragma unroll
        for (int k = 0; k < 9; k++) { mma_bf16(d[(2 * k) % 3], a[k].x, ones, a[k].y, ones, a[k].x, a[k].y); mma_bf16(d[(2 * k + 1) % 3], a[k].z, ones, a[k].w, ones, a[k].z, a[k].w); }
#pragma unroll
        for (int i = 0; i < 4; i++) d[0][i] += d[1][i] + d[2][i];
        const LnC lc = ln_consts(d[0][2] + d[0][3], __shfl_sync(0xffffffffu, d[0][0], 9 * t) + __shfl_sync(0xffffffffu, d[0][1], 9 * t + 4), r);
        if (lane < 12) sts16(MISC_LN1 + g * 32 + (warp & 3) * 8 + t * 2, lane < 4 ? lc.m2 : lane < 8 ? lc.rh2 : lc.rl2);
        }
        asm volatile("cp.async.wait_group 0;" ::: "memory");
        TS(23);
        bar_sync(5, 608);
        uint32_t x[3][4];
        ldsm4t(tr_addr, x[0][0], x[0][1], x[0][2], x[0][3]);
        uint4 m = lds128(lca);
        const uint4 rl = lds128(lca + 64), rh = lds128(lca + 32);
        ldsm4t(tr_addr + 512, x[1][0], x[1][1], x[1][2], x[1][3]);
        if (wg == 3) ldsm4t(tr_addr + 640, x[2][0], x[2][1], x[2][2], x[2][3]);
#pragma unroll
        for (int q = 0; q < 3; q++) {
          if (q < 2 || wg == 3) {
            const uint32_t r0 = ln_apply(x[q][0], m.x, rh.x, rl.x), r1 = ln_apply(x[q][1], m.y, rh.y, rl.y), r2 = ln_apply(x[q][2], m.z, rh.z, rl.z), r3 = ln_apply(x[q][3], m.w, rh.w, rl.w);
            const uint32_t w0 = (pack_h(bf_lo(r0), bf_hi(r0)) & 0xFFFEFFFEu) | 1u, w1 = pack_h(bf_lo(r1), bf_hi(r1)), w2 = pack_h(bf_lo(r2), bf_hi(r2)), w3 = pack_h(bf_lo(r3), bf_hi(r3));
            if (q == 0) str128(dst, w0, w1, w2, w3);
            else sts128(OFF_G + warp * 512 + (8 * (t >> 1) + g) * 32 + (t & 1) * 16 + (q == 2 ? 2048 : 0), w0, w1, w2, w3);
          }
          if (q == 0) {
            const uint32_t z = clock() & p.off[7];
            m.x ^= z; m.y ^= z; m.z ^= z; m.w ^= z;
          }
          if (q == 0) TS(30);
          if (q == 0 && wg >= 2) {
#pragma unroll
            for (int i = 0; i < 7; i++) raw[i] = lds16(wb + W_KT + i * 256 + (i < 6 ? wt : (2 * c + (wg & 1)) & 7) * 2);
          }
        }
        bar_arrive(10, 576);
        TS(1);
      } else bar_sync(1 + wg, 128);
      phase &= 1;
      if (phase) { phase = 0; continue; }
      TS(14);
      float acc[20];
      const uint32_t alo = (wb >> 4) | (8u << 16);
      uint4 k4 = lds128(wb + W_MISC + 16);
      uint32_t dk = lds16(OFF_WR + 1152 + slot * 2);
      wg_fence();
      wgmma40_ss_init(acc, alo, alo + 1024, 2048 >> 4);
#pragma unroll
      for (int k = 1; k < 8; k++) wgmma40_ss(acc, alo + k * 16, alo + 1024 + k * 16, 2048 >> 4);
      wg_commit();
      { const uint32_t z = clock() & p.off[7]; dk ^= z; k4.x ^= z; k4.z ^= z; }
      const float k2048 = (float)(int)((k4.x + k4.y) + (k4.z + k4.w)) * (1.f / 262144.f);
      const int ef = max(em, min((int)((dk >> 7) & 255u) - 7, 238));
      asm volatile("st.shared.u8 [%0], %1;" :: "r"(MISC_EM + slot), "r"(ef + 9) : "memory");
      const float un = __uint_as_float((uint32_t)max(114 + em - ef, 0) << 23), d0 = wt ? 0.f : bf_lo(dk) * __uint_as_float((uint32_t)(245 - ef) << 23);
      wg_wait<0>();
      kw.x = pack_h(fmaf(acc[0] - acc[3], un, d0), (acc[4] - acc[7]) * un);
      kw.y = pack_h((acc[8] - acc[11]) * un, (acc[12] - acc[15]) * un);
      kw.z = pack_h((acc[16] - acc[19]) * un, k2048 * un);
      TS(24);
      ep = 0;
      if (two) SPIN_WHILE(ep == 0, ep = lds32(MISC_EPOCH));
      if (five || !two) break;
      str128(kx, kw.x, kw.y, kw.z, ep);
      two = false;
      slot = 3;
      bar_sync(1 + wg, 128);
    }
    if (lane == 0) mbar_arrive(MB_KF + wg * 8);
    if (two) { mbar_wait(MB_KF); zero_pads(OFF_W + ALT, wt); }
    uint32_t tb = wb;
#pragma unroll 1
    for (;;) {
      kgen_build(tb, wg, wt, kw.x, kw.y, kw.z);
      TS(15);
      if (!two) break;
      two = false;
      kw.w = 0;
      SPIN_WHILE(kw.w != ep, kw = ldr128(kx));
      tb = OFF_W + ALT;
    }
    fence_async();
    TS(31);
    if (tb != wb) bar_arrive(7, 288);
    bar_sync(1 + wg, 128);
  }
  uint32_t tpub;
  ConvPre pre;
  conv_pre(pre, (wb ^ p.off[7]) + (cv.ca & 0xFFFFu), (wb ^ p.off[7]) + cv.qa, 3, true, warp & 2);
#pragma unroll 1
  for (int item = 0;; item++) {
    TS(2);
    conv_item(item ? OFF_W + ALT : wb, item ? OFF_W : OFF_T + (wg >> 1) * TILE, item ? 1 : 13 + (wg >> 1), item ? 128 : five && wg == 1 ? 192 : 256, pre, cv, p.off[7],
              &tm.m[item ? 9 : 7], item ? 512 + (c >> 1) : (wg >> 1) * 128 + c, warp, lane, five && wg >= X_GW, five && !wg && !item);
    tpub = clock() - (item ? X_YD : wg >= 2 ? X_YD2 : 0);
    if (wg || !five || item) break;
    TS(27);
  }
  TS(4);

  const int ln = lane ^ p.off[7], td = warp * 32 + ln, gg = ln >> 2, tt = ln & 3;
  const int tok = c * 16 + warp;
  const int fu = warp / 3, fk = warp - fu * 3;
  uint32_t wa[12][4];
  uint4 ha[3];
  const uint4* hsrc = &p.s->HS[td + (td / 24) * 48];
  {
    uint32_t hw[9], wr[9];
    const uint32_t row = keep(OFF_YT + warp * YT_PITCH + (warp >> 3) * 64 + ln * 16);
    const uint32_t wabase = keep(((ln & 8) ? OFF_W + (fk + 1) * W_BYTES : OFF_G + fk * 192 * pitch) + ((ln >> 4) * 8 + (ln & 7)) * pitch
                                 + (five ? ((fu ^ (ln >> 1)) & 3) : min(fu, 4)) * 16);
    float sw;
    {
      const bool three = wg == 1;
      const int ch = 8 * (tt >> 1) + gg;
      const uint32_t tr_addr = tr_base(ln);
      const uint4* ysrc = &p.s->X[c * DM * 2 + ch * 2 + (tt & 1)];
      uint32_t x[3][4], s[3];
      uint4 v[3];
#define TL(q) ((q) < 2 ? 2 * warp + (q) : 28 + warp)
      asm volatile("cp.async.bulk.wait_group.read 0;" ::: "memory");
      if (wg >= 2) { const uint32_t ts = lds32(MISC_T0); while ((int)(clock() - ts) < X_XS) {} }
      while ((int)(clock() - tpub) < X_YD) {}
      TS(5);
      v[0] = ldr128(ysrc + TL(0) * 32); v[1] = ldr128(ysrc + TL(1) * 32); v[2] = make_uint4(three, 0, 0, 0);
      mbar_wait(MB_REL);
#pragma unroll
      for (int i = 0; i < 6; i++) if (i < 4 || three) wr[i] = (gg & 2) ? ones : lds32(OFF_WR + TL(i >> 1) * 32 + (i & 1) * 16 + tt * 4);
      const uint32_t ha = keep(OFF_YT + (ln & 7) * YT_PITCH + (ln >> 4) * (8 * YT_PITCH + 64) + (ln & 8) * 2);
      const uint32_t pa = keep(OFF_PART + warp * 4 + ((gg & 2) * 8 + (gg & 4) * 2 + 2 * tt + (gg & 1)) * 80), pb = keep(OFF_PART + 2560 + warp * 4 + gg * 80);
      float dl[4] = {0.f, 0.f, 0.f, 0.f}, dh[4] = {0.f, 0.f, 0.f, 0.f};
      sw = __uint_as_float(lds32(MISC_SW));
#pragma unroll
      for (int q = 0; q < 3; q++) {
        if (q < 2 || three) {
          ldsm4t(tr_addr + TL(q) * 32, x[q][0], x[q][1], x[q][2], x[q][3]);
        }
      }
      mbar_wait(MB_SC);
#pragma unroll
      for (int q = 0; q < 3; q++) {
        asm volatile("ld.shared.u8 %0, [%1];" : "=r"(s[q]) : "r"((q < 2 ? sc_addr(warp) + q * 16 : sc_addr(16) + (warp & 3) * 16) + ch) : "memory");
        s[q] = keep(s[q] * 0x800080u);
      }
#define FIN(q) stsm4t(tr_addr + TL(q) * 32, bf_fma2(h2bf(v[q].x), s[q], x[q][0]), bf_fma2(h2bf(v[q].y), s[q], x[q][1]), bf_fma2(h2bf(v[q].z), s[q], x[q][2]), bf_fma2(h2bf(v[q].w), s[q], x[q][3]));
      SPIN_WHILE((v[0].x | v[1].x) & 1u, _Pragma("unroll") for (int q = 0; q < 3; q++) if (v[q].x & 1u) v[q] = ldr128(ysrc + TL(q) * 32));
      if (v[2].x & 1u) v[2] = ldr128(ysrc + TL(2) * 32);
#define STAT(q) { uint32_t r0, r1, r2, r3; ldsm4(ha + TL(q) * 32, r0, r1, r2, r3); \
        mma_bf16(dl, r0, wr[2 * q], r1, wr[2 * q + 1], r0, r1); mma_bf16(dh, r2, wr[2 * q], r3, wr[2 * q + 1], r2, r3); }
      FIN(0) FIN(1)
      __syncwarp();
      STAT(0) STAT(1)
      if (three) {
        SPIN_WHILE(v[2].x & 1u, if (v[2].x & 1u) v[2] = ldr128(ysrc + TL(2) * 32));
        FIN(2)
        __syncwarp();
        STAT(2)
      }
      if (gg & 1) { dl[0] = dl[1]; dl[2] = dl[3]; dh[0] = dh[1]; dh[2] = dh[3]; }
      sts32(pa, __float_as_uint((gg & 4) ? dh[2] : dl[2]));
      if (tt == (gg >> 1)) { sts32(pb, __float_as_uint(dl[0])); sts32(pb + 640, __float_as_uint(dh[0])); }
#undef STAT
#undef FIN
#undef TL
    }
    uint32_t ra = keep(OFF_PART + (ln & 15) * 80 + (ln & 16) * 2);
    uint16_t* rp = (uint16_t*)p.s->R + c * 16 + (ln & 15);
    const uint2* rsrc = (const uint2*)p.s->R + td;
    asm volatile("" : "+l"(rp), "+l"(rsrc), "+l"(hsrc));
    uint2 rv = make_uint2(0u, 0u);
    TS(28);
    if (warp != X_PW) bar_sync(0, 544);
    else {
      float z[3], rd;
      asm volatile("bar.sync 0, 544;" : "+r"(ra) :: "memory");
#pragma unroll
      for (int k = 2; k >= 0; k--) {
        const uint4 a = lds128(ra + k * 1280), b = lds128(ra + k * 1280 + 16);
        z[k] = ((__uint_as_float(a.x) + __uint_as_float(a.y)) + (__uint_as_float(a.z) + __uint_as_float(a.w))) + ((__uint_as_float(b.x) + __uint_as_float(b.y)) + (__uint_as_float(b.z) + __uint_as_float(b.w)));
      }
#pragma unroll
      for (int k = 2; k >= 0; k--) z[k] += __shfl_xor_sync(0xffffffffu, z[k], 16);
      const LnC l = ln_consts(z[1], z[2], rd);
      const uint32_t b = pack_bf(0.f, fmaf(-bf_lo(l.m2), sw, z[0]) * rd);
      const uint32_t k16 = max(min((b ^ (((int)b >> 31) | 0x80000000u)) >> 16, 0xFFFEu), 1u);
      if (ln < 16) str16(rp, k16);
      sts64(OFF_RK + (ln & 15) * 8, __byte_perm(l.m2, l.rh2, 0x5410), __byte_perm(l.rl2, k16, 0x5410));
      sts128(MISC_CNT + ln * 16, 0, 0, 0, 0);
    }
    mbar_wait(MB_GU);
#define LD_HW { const uint4 a = lds128(row), b = lds128(row + 512); hw[8] = lds32(row + 1024 - ln * 12); \
      hw[0] = a.x; hw[1] = a.y; hw[2] = a.z; hw[3] = a.w; hw[4] = b.x; hw[5] = b.y; hw[6] = b.z; hw[7] = b.w; }
    LD_HW
    const uint32_t tr0 = clock();
    bar_sync(5, 512);
    TS(7);
    const uint2 lk = lds64(OFF_RK + warp * 8);
    LnC l2;
    l2.m2 = __byte_perm(lk.x, 0, 0x1010); l2.rh2 = __byte_perm(lk.x, 0, 0x3232); l2.rl2 = __byte_perm(lk.y, 0, 0x1010);
    const uint32_t key = (lk.y & 0xFFFF0000u) | (2047 - tok);
    uint32_t loc = ln < 16 ? (lds32(OFF_RK + 4 + ln * 8) & 0xFFFF0000u) | (2047 - c * 16 - ln) : 0u;
    int rank = __popc(__ballot_sync(0xffffffffu, loc > key));
#pragma unroll
    for (int i = 0; i < 9; i++) { wr[i] = keep(ln_apply(hw[i], l2.m2, l2.rh2, l2.rl2)); hw[i] = bf_add2(hw[i], wr[i]); }
#define OUT_ROW { uint32_t* o = p.out + tok * 288 + ln * 4; \
      *(uint4*)o = make_uint4(hw[0], hw[1], hw[2], hw[3]); *(uint4*)(o + 128) = make_uint4(hw[4], hw[5], hw[6], hw[7]); o[256 - ln * 3] = hw[8]; }
    uint4* hs = p.s->HS + ln;
    asm volatile("" : "+l"(hs));
#pragma unroll 1
    for (int base = 0; base < 8; base += 2) {
      uint32_t T[2];
#pragma unroll
      for (int j = 0; j < 2; j++) {
        const uint32_t mx = __reduce_max_sync(0xffffffffu, loc);
        if (loc == mx) loc = 0;
        T[j] = (td >> 2) < c ? (mx & 0xFFFF0000u) - 1u : mx | 0xFFFFu;
      }
      const uint32_t sh = keep(rank == base ? 0x4410u : rank == base + 1 ? 0x4432u : 0x4445u), ca = keep(MISC_CNT + base * 64 + ln * 4);
      TS(29);
      if (base == 0) {
        while ((int)(clock() - tr0) < X_RD) {}
        if ((td >> 2) != c) rv = ldr64(rsrc);
        if (rank >= X_OR) OUT_ROW
        if (warp < (five ? 12 : 15)) {
#pragma unroll
          for (int k = 0; k < X_WS; k++) ldsm4t(wabase + k * 16 * pitch, wa[k][0], wa[k][1], wa[k][2], wa[k][3]);
        }
      }
      uint32_t cnt;
#pragma unroll 1
      for (int it = 0; it < SPIN_MAX; it++) {
        const uint32_t xs = rv.x << 16, ys = rv.y << 16;
        const bool bad = max(max(rv.x, xs), max(rv.y, ys)) >= 0xFFFF0000u;
        uint32_t cn2 = 0;
        cnt = bad ? 256u : 0u;
#pragma unroll
        for (int j = 0; j < 2; j++)
          asm("{ .reg .pred a, b, c, d; setp.gt.u32 a, %2, %6; setp.gt.u32 b, %3, %6; setp.gt.u32 c, %4, %6; setp.gt.u32 d, %5, %6; "
              "@a add.u32 %1, %1, %7; @b add.u32 %1, %1, %7; @c add.u32 %0, %0, %7; @d add.u32 %0, %0, %7; }"
              : "+r"(cnt), "+r"(cn2) : "r"(rv.x), "r"(rv.y), "r"(xs), "r"(ys), "r"(T[j]), "r"(1u << (16 * j)));
        cnt = __reduce_add_sync(0xffffffffu, cnt + cn2);
        asm volatile("{ .reg .pred q; setp.eq.u32 q, %2, 0; @q red.shared.add.u32 [%0], %1; }" :: "r"(ca), "r"(cnt), "r"(cnt & 0x3F00u) : "memory");
        if (!(cnt & 0x3F00u)) break;
        if (bad) rv = ldr64(rsrc);
      }
      TS(16);
      bar_sync(0, 512);
      cnt = lds32(ca);
      if (base == 0) tpub = clock();
      const int gr = rank + __byte_perm(cnt, 0x800u, sh);
      if (gr < 8) {
        uint4* ks = hs + 1152 + gr;
        hs = (uint4*)((char*)hs + gr * 1152);
        asm volatile("{ .reg .b128 t, u; .reg .b64 a, b, c, d; mov.b64 a, {%1,%2}; mov.b64 b, {%3,%4}; mov.b64 c, {%5,%6}; mov.b64 d, {%7,%8}; mov.b128 t, {a, b}; mov.b128 u, {c, d}; "
                     "st.relaxed.gpu.global.b128 [%0], t; st.relaxed.gpu.global.b128 [%0 + 512], u; }"
                     :: "l"(hs), "r"(wr[0]), "r"(wr[1]), "r"(wr[2]), "r"(wr[3]), "r"(wr[4]), "r"(wr[5]), "r"(wr[6]), "r"(wr[7]) : "memory");
        str32((uint32_t*)(hs + 64) - ln * 3, wr[8]);
        LD_HW
        str128(hs + 576, hw[0], hw[1], hw[2], hw[3]); str128(hs + 608, hw[4], hw[5], hw[6], hw[7]); str32((uint32_t*)(hs + 640) - ln * 3, hw[8]);
        if (ln == 0) str32(ks, key);
        rank = 16;
      }
      if (__all_sync(0xffffffffu, (int)(cnt >> 16) + base + 2 >= 8)) break;
    }
    TS(8);
    if (warp < (five ? 12 : 15)) {
#pragma unroll
      for (int k = X_WS; k < 12; k++) ldsm4t(wabase + k * 16 * pitch, wa[k][0], wa[k][1], wa[k][2], wa[k][3]);
    }
    if (warp < 6) while ((int)(clock() - tpub) < X_HD) {}
    TS(19);
    if (warp < 6) { ha[0] = ldr128(hsrc); ha[1] = ldr128(hsrc + 24); ha[2] = ldr128(hsrc + 48); }
    if (rank < X_OR) OUT_ROW
  }
  uint32_t wd[10][4];
  const uint32_t xb = keep(OFF_XS + (ln & 7) * 1168 + (fk * 24 + (ln >> 3)) * 16);
  if (warp >= 7) {
    const uint32_t db = down_box(warp - 7, five) + (ln & 7) * 128;
    mbar_wait(MB_D);
#pragma unroll
    for (int j = 0; j < 4; j++) {
      const uint32_t a = db + (ln >> 4) * 1024 + (((2 * j + ((ln >> 3) & 1)) ^ (ln & 7)) << 4);
      ldsm4t(a, wd[j][0], wd[j][1], wd[j][2], wd[j][3]);
      ldsm4t(a + 2048, wd[4 + j][0], wd[4 + j][1], wd[4 + j][2], wd[4 + j][3]);
    }
#pragma unroll
    for (int j = 0; j < 2; j++) ldsm4t(db + 4096 + (((4 * j + (ln >> 3)) ^ (ln & 7)) << 4), wd[8 + j][0], wd[8 + j][1], wd[8 + j][2], wd[8 + j][3]);
  } else if (warp < 6) {
    const uint32_t xs = keep(OFF_XS + (td + (td / 24) * 49) * 16);
#pragma unroll 1
    for (int it = 0; it < SPIN_MAX; it++) {
      const bool bad = max(max(max(ha[0].x, ha[1].x), max(ha[2].x, ha[2].y)), max(ha[2].z, ha[2].w)) == ~0u;
      if (!__any_sync(0xffffffffu, bad)) break;
      if (bad) { ha[0] = ldr128(hsrc); ha[1] = ldr128(hsrc + 24); ha[2] = ldr128(hsrc + 48); }
    }
#pragma unroll
    for (int q = 0; q < 3; q++) sts128(xs + q * 384, ha[q].x, ha[q].y, ha[q].z, ha[q].w);
  }
  TS(9);

  bar_sync(0, 512);
  if (warp < (five ? 12 : 15)) {
    float d0[4] = {0.f, 0.f, 0.f, 0.f}, d1[4] = {0.f, 0.f, 0.f, 0.f};
#pragma unroll
    for (int k = 0; k < 12; k += 2) {
      uint32_t b0, b1, b2, b3;
      ldsm4(xb + k * 32, b0, b1, b2, b3);
      mma_bf16(d0, wa[k][0], wa[k][1], wa[k][2], wa[k][3], b0, b1);
      mma_bf16(d1, wa[k + 1][0], wa[k + 1][1], wa[k + 1][2], wa[k + 1][3], b2, b3);
    }
    sts128(OFF_RED + td * 16, __float_as_uint(d0[0] + d1[0]), __float_as_uint(d0[1] + d1[1]), __float_as_uint(d0[2] + d1[2]), __float_as_uint(d0[3] + d1[3]));
  }
  TS(26);
  if (warp < 5) {
    const uint32_t rb = OFF_RED + warp * 1536 + ln * 16;
    bar_sync(9, 512);
    const uint4 pa = lds128(rb), pb = lds128(rb + 512), pc = lds128(rb + 1024);
    const float ga = bfr(__uint_as_float(pa.x) + __uint_as_float(pb.x) + __uint_as_float(pc.x));
    const float gb = bfr(__uint_as_float(pa.y) + __uint_as_float(pb.y) + __uint_as_float(pc.y));
    const uint32_t uu = pack_bf(__uint_as_float(pa.z) + __uint_as_float(pb.z) + __uint_as_float(pc.z), __uint_as_float(pa.w) + __uint_as_float(pb.w) + __uint_as_float(pc.w));
    float ra, rb2;
    asm("rcp.approx.ftz.f32 %0, %1;" : "=f"(ra) : "f"(1.f + ex2(ga * -1.4426950408889634f)));
    asm("rcp.approx.ftz.f32 %0, %1;" : "=f"(rb2) : "f"(1.f + ex2(gb * -1.4426950408889634f)));
    const uint32_t act = bf_mul2(pack_bf(ga * ra, gb * rb2), uu);
    sts32(OFF_ACT + td * 4, act);
  } else bar_arrive(9, 512);
  uint4* dst = &p.s->X[c * DM * 2 + (warp - 7) * 64 + tt * 8 + gg];
  asm volatile("" : "+l"(dst));
  bar_sync(8, 512);
  tpub = clock();
  if (warp >= 7) {
    uint32_t b0, b1, b2, b3, b4;
    ldsm4t(OFF_ACT + ln * 16, b0, b1, b2, b3);
    asm volatile("ldmatrix.sync.aligned.m8n8.x1.trans.shared.b16 {%0}, [%1];" : "=r"(b4) : "r"(OFF_ACT + 512 + ln * 16) : "memory");
    float y[4][4];
#pragma unroll
    for (int j = 0; j < 4; j++) {
      y[j][0] = y[j][1] = y[j][2] = y[j][3] = 0.f;
      mma_bf16(y[j], wd[j][0], wd[j][1], wd[j][2], wd[j][3], b0, b1);
    }
#pragma unroll
    for (int j = 0; j < 4; j++) mma_bf16(y[j], wd[4 + j][0], wd[4 + j][1], wd[4 + j][2], wd[4 + j][3], b2, b3);
    if (!five) {
#pragma unroll
      for (int j = 0; j < 4; j++) mma_bf16_k8(y[j], wd[8 + (j >> 1)][2 * (j & 1)], wd[8 + (j >> 1)][2 * (j & 1) + 1], b4);
    }
    str128(dst, (pack_bf(y[0][0], y[0][1]) & ~1u) | 0x10000u, pack_bf(y[0][2], y[0][3]), pack_bf(y[1][0], y[1][1]), pack_bf(y[1][2], y[1][3]));
    str128(dst + 32, (pack_bf(y[2][0], y[2][1]) & ~1u) | 0x10000u, pack_bf(y[2][2], y[2][3]), pack_bf(y[3][0], y[3][1]), pack_bf(y[3][2], y[3][3]));
  }
  TS(10);

  if (c < 72) {
    const uint4* src = &p.s->X[(warp * 4 + tt) * (DM * 2) + c * 8 + gg];
    const int slot = (c & 3) * 2 + (ln >> 4), dw = (c >> 2) * 16 + (ln & 15);
    uint32_t hv = 0, kv = 0, res = 0, rs2 = 0;
    uint32_t* o = p.out;
    if (warp == 0) {
      hv = ~0u;
      SPIN_WHILE(max(hv, kv) == ~0u, hv = ldr32((const uint32_t*)p.s->HS + 2304 + slot * 288 + dw); kv = ldr32(&p.s->HS[1152 + slot]));
      const float r = bf_hi(kv ^ (((int)~kv >> 31) | 0x80000000u));
      float rs;
      asm("rcp.approx.ftz.f32 %0, %1;" : "=f"(rs) : "f"(1.f + ex2(r * -1.4426950408889634f)));
      rs2 = keep(pack_bf(rs, rs));
      res = lds32(OFF_XS + slot * 1168 + dw * 4);
      o += (2047 - (int)(kv & 2047u)) * 288 + dw;
      asm volatile("" : "+l"(o));
    }
    const uint32_t sel = (gg & 1) ? 0x3F800000u : 0x00003F80u;
    const uint32_t q0 = keep((gg >> 1) == 0 ? sel : 0u), q1 = keep((gg >> 1) == 1 ? sel : 0u), q2 = keep((gg >> 1) == 2 ? sel : 0u), q3 = keep((gg >> 1) == 3 ? sel : 0u);
    const uint32_t fa = keep(OFF_RED + warp * 8 + ((gg & 1) * 16 + (gg >> 1) * 4 + tt) * 144), fb = keep(OFF_RED + ln * 144);
    uint4 a0 = make_uint4(0, 0, 0, 0), a1 = a0;
    while ((int)(clock() - tpub) < X_PD) {}
    SPIN_WHILE(!(a0.x & a1.x & 0x10000u), if (!(a0.x & 0x10000u)) a0 = ldr128(src); if (!(a1.x & 0x10000u)) a1 = ldr128(src + 64 * DM * 2));
    float d[4] = {0.f, 0.f, 0.f, 0.f}, e[4] = {0.f, 0.f, 0.f, 0.f}, d2[4] = {0.f, 0.f, 0.f, 0.f}, e2[4] = {0.f, 0.f, 0.f, 0.f};
    mma_bf16(d, q0, q2, q1, q3, a0.x, a0.y); mma_bf16(e, q0, q2, q1, q3, a0.z, a0.w);
    mma_bf16(d2, q0, q2, q1, q3, a1.x, a1.y); mma_bf16(e2, q0, q2, q1, q3, a1.z, a1.w);
    sts64(fa, __float_as_uint(d[0] + e[2] + d2[0] + e2[2]), __float_as_uint(d[1] + e[3] + d2[1] + e2[3]));
    TS(11);
    if (warp == 0) {
      bar_sync(0, 512);
      float2 s[16];
#pragma unroll
      for (int i = 0; i < 16; i += 2) { const uint4 q = lds128(fb + i * 8); s[i] = make_float2(__uint_as_float(q.x), __uint_as_float(q.y)); s[i + 1] = make_float2(__uint_as_float(q.z), __uint_as_float(q.w)); }
#pragma unroll
      for (int k = 1; k < 16; k *= 2)
#pragma unroll
        for (int i = 0; i < 16; i += 2 * k) { s[i].x += s[i + k].x; s[i].y += s[i + k].y; }
      asm volatile("st.global.b32 [%0], %1;" :: "l"(o), "r"(bf_add2(hv, bf_add2(res, bf_mul2(pack_bf(s[0].x, s[0].y), rs2)))) : "memory");
    } else bar_arrive(0, 512);
  }
  TS(12);
  TS_DUMP();
}

typedef CUresult (*EncodeFn)(CUtensorMap*, CUtensorMapDataType, cuuint32_t, void*, const cuuint64_t*, const cuuint64_t*, const cuuint32_t*,
                             const cuuint32_t*, CUtensorMapInterleave, CUtensorMapSwizzle, CUtensorMapL2promotion, CUtensorMapFloatOOBfill);

}

extern "C" void kernel_launch(void* const* d_in, const int* in_sizes, int n_in, void* d_out, int out_size) {
  (void)in_sizes; (void)n_in; (void)out_size;
  static EncodeFn enc = nullptr;
  static Scratch* scratch = nullptr;
  if (!enc) {
    void* fn = nullptr;
    cudaDriverEntryPointQueryResult qr;
    cudaGetDriverEntryPoint("cuTensorMapEncodeTiled", &fn, cudaEnableDefault, &qr);
    enc = (EncodeFn)fn;
    cudaGetSymbolAddress((void**)&scratch, g_S);
    cudaFuncSetAttribute(fused_kernel<false>, cudaFuncAttributeMaxDynamicSharedMemorySize, SMEM_BYTES);
    cudaFuncSetAttribute(fused_kernel<true>, cudaFuncAttributeMaxDynamicSharedMemorySize, SMEM_BYTES);
  }
  TMaps tm;
  for (int i = 0; i < 6; i++) {
    const bool dn = i % 3 == 2;
    const cuuint32_t w = i < 3 ? 40 : 32;
    cuuint64_t gd[3] = {(cuuint64_t)(dn ? 64 : FF), (cuuint64_t)(dn ? FF : DM), 9};
    cuuint64_t gs[2] = {(cuuint64_t)(dn ? DM * 2 : FF * 2), 128};
    cuuint32_t bx[3] = {dn ? 64 : w, dn ? w : 96, i < 3 ? 2u : 3u};
    cuuint32_t es[3] = {1, 1, 1};
    enc(&tm.m[i], CU_TENSOR_MAP_DATA_TYPE_BFLOAT16, dn ? 3 : 2, d_in[11 + i % 3], gd, gs, bx, es, CU_TENSOR_MAP_INTERLEAVE_NONE,
        dn ? CU_TENSOR_MAP_SWIZZLE_128B : i < 3 ? CU_TENSOR_MAP_SWIZZLE_NONE : CU_TENSOR_MAP_SWIZZLE_64B,
        (CUtensorMapL2promotion)X_PROMO, CU_TENSOR_MAP_FLOAT_OOB_FILL_NONE);
  }
  for (int i = 6; i < 10; i++) {
    cuuint64_t gd[3] = {i < 8 ? 32u : 16u, i < 8 ? DM / 2u : DM, NCTA};
    cuuint64_t gs[2] = {i < 8 ? 64u : 32u, DM * 32};
    cuuint32_t bx[3] = {32, 1, (i & 1) ? 128u : 136u};
    cuuint32_t es[3] = {1, 1, 1};
    enc(&tm.m[i], CU_TENSOR_MAP_DATA_TYPE_FLOAT16, 3, scratch->X, gd, gs, bx, es, CU_TENSOR_MAP_INTERLEAVE_NONE, CU_TENSOR_MAP_SWIZZLE_64B,
        CU_TENSOR_MAP_L2_PROMOTION_NONE, CU_TENSOR_MAP_FLOAT_OOB_FILL_NONE);
  }
  Params p;
  p.x = (const unsigned char*)d_in[0];
  bool far = false;
  for (int i = 0; i < 7; i++) {
    p.far[i] = (const unsigned char*)d_in[1 + i];
    const long long d = (long long)((intptr_t)d_in[1 + i] - (intptr_t)d_in[0]);
    p.off[i] = (int)(d / 16);
    if ((long long)p.off[i] * 16 != d || p.off[i] > (1 << 30)) far = true;
  }
  p.dskip = (const uint16_t*)d_in[8];
  p.w_r = (const uint32_t*)d_in[10];
  for (int f = 0; f < 2; f++) {
    static const int kind[17] = {0, 0, 0, 0, 2, 2, 0, 0, 1, 1, 1, 1, 1, 1, 2, 2, 2};
    static const int idx[2][17] = {{2, 3, 4, 5, 6, 8, 0, 1, 0, 1, 2, 3, 4, 5, 0, 2, 4}, {2, 3, 4, 5, 0, -1, 0, 1, 0, 1, 2, 3, 4, 5, 3, -1, 6}};
    static const int blk[2][17] = {{-1, -1, -1, -1, 0, -1, 4, -1, 1, -1, 2, -1, 3, -1, 16, -1, -1}, {-1, -1, -1, -1, 1, -1, 4, -1, -1, -1, 2, -1, 3, -1, 16, -1, -1}};
    const int pitch = f ? 64 : 80;
    for (int u = 0; u < 17; u++) {
      const int s = idx[f][u];
      const uint32_t dst = kind[u] == 0 ? OFF_G + s * 96 * pitch : kind[u] == 2 ? down_box(s, f) : OFF_W + W_BYTES + (s >> 1) * W_BYTES + (s & 1) * 96 * pitch;
      const uint32_t mb = u >= 14 ? (u >= X_HU ? MB_H - OFF_MISC : 0) : blk[f][u] >= 0 ? MB_KF - OFF_MISC + blk[f][u] * 8 : 0;
      p.sched[f][u] = s < 0 ? 3u : kind[u] | s << 2 | mb << 6 | dst << 14;
    }
  }
  p.out = (uint32_t*)d_out;
  p.off[7] = 0;
  p.ts = nullptr;
  p.s = scratch;
  if (far) { fused_kernel<true><<<NCTA, NT, SMEM_BYTES, cudaStreamPerThread>>>(p, tm); return; }
  fused_kernel<false><<<NCTA, NT, SMEM_BYTES, cudaStreamPerThread>>>(p, tm);
}
```

```cpp
#include <cuda_runtime.h>
#include <cuda.h>
#include <cuda_bf16.h>
#include <cuda_fp16.h>
#include <stdint.h>
#include <stddef.h>

namespace {

constexpr int NCTA = 128;
constexpr int NT = 640;
constexpr int DM = 576;
constexpr int FF = 4608;
constexpr int SPIN_MAX = 1 << 20;

struct Scratch {
  uint4 X[NCTA * DM * 2];
  uint4 KX[64 * 128];
  uint4 HS[1152 + 8];
  uint4 R[256];
  uint4 SC[256];
  uint32_t FLAG[NCTA * 8];
};
__device__ Scratch g_S;

#define CLKS(i)
#define TS(i)
#define TSX(i)
#define TS_DUMP()

constexpr int SB = 1024;
constexpr int BOX = 15360;
constexpr int OFF_G = SB;
constexpr int OFF_W = OFF_G + 3 * BOX;
constexpr int W_KT = 26624;
constexpr int W_QT = W_KT + 64 + 2048 + 80;
constexpr int W_L3 = W_KT + 4352;
constexpr int W_CW = W_L3 + 4160;
constexpr int W_MISC = W_CW + 640;
constexpr int W_BYTES = 35840;
constexpr int TILE = 10240;
constexpr int OFF_T = OFF_W + 4 * W_BYTES;
constexpr int ALT = TILE - W_KT;
static_assert(W_MISC + 32 <= W_BYTES && OFF_W % 1024 == 0 && W_BYTES % 1024 == 0 && W_BYTES + ALT <= 20480, "wg block");
constexpr int YT_PITCH = 1184;
constexpr int OFF_YT = OFF_T + 2 * TILE;
constexpr int OFF_WR = OFF_YT + 16 * YT_PITCH + 64;
constexpr int OFF_MISC = OFF_WR + 2304;
constexpr int SMEM_BYTES = OFF_MISC + 1024 - SB;
static_assert(OFF_YT % 16 == 0 && OFF_MISC % 16 == 0, "align");
static_assert(SMEM_BYTES <= 232448, "smem");
constexpr int MB_GU = OFF_MISC;
constexpr int MB_D = OFF_MISC + 8;
constexpr int MB_KF = OFF_MISC + 16;
constexpr int MB_GF = OFF_MISC + 48;
constexpr int MB_SC = OFF_MISC + 56;
constexpr int MB_UL = OFF_MISC + 64;
constexpr int MB_REL = OFF_MISC + 104;
constexpr int MB_GO = OFF_MISC + 112;
constexpr int MB_H = MB_KF + 128;
constexpr int MISC_EPOCH = OFF_MISC + 152;
constexpr int MISC_SW = OFF_MISC + 156;
constexpr int MISC_RT = OFF_MISC + 160;
constexpr int MISC_T0 = OFF_MISC + 296;
constexpr int MISC_EM = OFF_MISC + 288;
constexpr int OFF_PART = OFF_W + 20480;
constexpr int OFF_RK = OFF_PART + 3840;
constexpr int MISC_LN1 = OFF_MISC + 192;
constexpr int OFF_XS = OFF_T;
constexpr int OFF_RED = OFF_T + TILE;
constexpr int OFF_FIN = OFF_W + 3 * W_BYTES + W_KT;
constexpr int OFF_ACT = OFF_FIN + 4096;
constexpr int MISC_CNT = OFF_ACT + 1024;

__device__ __forceinline__ uint32_t smem_u32(const void* p) { return (uint32_t)__cvta_generic_to_shared(p); }
__device__ __forceinline__ uint32_t lds32(uint32_t a) { uint32_t v; asm volatile("ld.shared.b32 %0, [%1];" : "=r"(v) : "r"(a) : "memory"); return v; }
__device__ __forceinline__ uint32_t lds16(uint32_t a) { uint16_t v; asm volatile("ld.shared.u16 %0, [%1];" : "=h"(v) : "r"(a) : "memory"); return v; }
__device__ __forceinline__ uint2 lds64(uint32_t a) { uint2 v; asm volatile("ld.shared.v2.b32 {%0,%1}, [%2];" : "=r"(v.x), "=r"(v.y) : "r"(a) : "memory"); return v; }
__device__ __forceinline__ uint4 lds128(uint32_t a) { uint4 v; asm volatile("ld.shared.v4.b32 {%0,%1,%2,%3}, [%4];" : "=r"(v.x), "=r"(v.y), "=r"(v.z), "=r"(v.w) : "r"(a) : "memory"); return v; }
__device__ __forceinline__ void sts16(uint32_t a, uint32_t v) { asm volatile("st.shared.u16 [%0], %1;" :: "r"(a), "h"((uint16_t)v) : "memory"); }
__device__ __forceinline__ void sts32(uint32_t a, uint32_t v) { asm volatile("st.shared.b32 [%0], %1;" :: "r"(a), "r"(v) : "memory"); }
__device__ __forceinline__ void sts64(uint32_t a, uint32_t x, uint32_t y) { asm volatile("st.shared.v2.b32 [%0], {%1,%2};" :: "r"(a), "r"(x), "r"(y) : "memory"); }
__device__ __forceinline__ void sts128(uint32_t a, uint32_t x, uint32_t y, uint32_t z, uint32_t w) { asm volatile("st.shared.v4.b32 [%0], {%1,%2,%3,%4};" :: "r"(a), "r"(x), "r"(y), "r"(z), "r"(w) : "memory"); }
__device__ __forceinline__ void ldsm4(uint32_t a, uint32_t& r0, uint32_t& r1, uint32_t& r2, uint32_t& r3) {
  asm volatile("ldmatrix.sync.aligned.m8n8.x4.shared.b16 {%0,%1,%2,%3}, [%4];" : "=r"(r0), "=r"(r1), "=r"(r2), "=r"(r3) : "r"(a) : "memory");
}
__device__ __forceinline__ void ldsm4t(uint32_t a, uint32_t& r0, uint32_t& r1, uint32_t& r2, uint32_t& r3) {
  asm volatile("ldmatrix.sync.aligned.m8n8.x4.trans.shared.b16 {%0,%1,%2,%3}, [%4];" : "=r"(r0), "=r"(r1), "=r"(r2), "=r"(r3) : "r"(a) : "memory");
}
__device__ __forceinline__ void stsm4t(uint32_t a, uint32_t r0, uint32_t r1, uint32_t r2, uint32_t r3) {
  asm volatile("stmatrix.sync.aligned.m8n8.x4.trans.shared.b16 [%0], {%1,%2,%3,%4};" :: "r"(a), "r"(r0), "r"(r1), "r"(r2), "r"(r3) : "memory");
}
__device__ __forceinline__ uint4 ldr128(const void* p) {
  unsigned long long lo, hi;
  asm volatile("{ .reg .b128 t; ld.relaxed.gpu.global.b128 t, [%2]; mov.b128 {%0, %1}, t; }" : "=l"(lo), "=l"(hi) : "l"(p) : "memory");
  return make_uint4((uint32_t)lo, (uint32_t)(lo >> 32), (uint32_t)hi, (uint32_t)(hi >> 32));
}
__device__ __forceinline__ void str128(void* p, uint32_t x, uint32_t y, uint32_t z, uint32_t w) {
  asm volatile("{ .reg .b128 t; .reg .b64 lo, hi; mov.b64 lo, {%1,%2}; mov.b64 hi, {%3,%4}; mov.b128 t, {lo, hi}; st.relaxed.gpu.global.b128 [%0], t; }"
               :: "l"(p), "r"(x), "r"(y), "r"(z), "r"(w) : "memory");
}
__device__ __forceinline__ uint32_t ldr32(const void* p) { uint32_t v; asm volatile("ld.relaxed.gpu.global.b32 %0, [%1];" : "=r"(v) : "l"(p) : "memory"); return v; }
__device__ __forceinline__ void str32(void* p, uint32_t v) { asm volatile("st.relaxed.gpu.global.b32 [%0], %1;" :: "l"(p), "r"(v) : "memory"); }
__device__ __forceinline__ void str16(void* p, uint32_t v) { asm volatile("st.relaxed.gpu.global.u16 [%0], %1;" :: "l"(p), "h"((uint16_t)v) : "memory"); }
__device__ __forceinline__ void bar_sync(int id, int n) { asm volatile("bar.sync %0, %1;" :: "r"(id), "r"(n) : "memory"); }
__device__ __forceinline__ void bar_arrive(int id, int n) { asm volatile("bar.arrive %0, %1;" :: "r"(id), "r"(n) : "memory"); }

__device__ __forceinline__ float bf_lo(uint32_t w) { return __uint_as_float(w << 16); }
__device__ __forceinline__ float bf_hi(uint32_t w) { return __uint_as_float(w & 0xFFFF0000u); }
__device__ __forceinline__ uint32_t pack_bf(float lo, float hi) { uint32_t r; asm("cvt.rn.bf16x2.f32 %0, %1, %2;" : "=r"(r) : "f"(hi), "f"(lo)); return r; }
__device__ __forceinline__ uint32_t pack_h(float lo, float hi) { uint32_t r; asm("cvt.rn.f16x2.f32 %0, %1, %2;" : "=r"(r) : "f"(hi), "f"(lo)); return r; }
__device__ __forceinline__ float bfr(float x) { return bf_lo(pack_bf(x, 0.f)); }
__device__ __forceinline__ uint32_t bf_sub2(uint32_t a, uint32_t b) { __nv_bfloat162 r = __hsub2(*(__nv_bfloat162*)&a, *(__nv_bfloat162*)&b); return *(uint32_t*)&r; }
__device__ __forceinline__ uint32_t bf_add2(uint32_t a, uint32_t b) { __nv_bfloat162 r = __hadd2(*(__nv_bfloat162*)&a, *(__nv_bfloat162*)&b); return *(uint32_t*)&r; }
__device__ __forceinline__ uint32_t bf_mul2(uint32_t a, uint32_t b) { __nv_bfloat162 r = __hmul2(*(__nv_bfloat162*)&a, *(__nv_bfloat162*)&b); return *(uint32_t*)&r; }
__device__ __forceinline__ float2 h2f(uint32_t w) { return __half22float2(*(__half2*)&w); }
__device__ __forceinline__ float ex2(float x) { float r; asm("ex2.approx.ftz.f32 %0, %1;" : "=f"(r) : "f"(x)); return r; }
__device__ __forceinline__ float warp_sum(float v) {
#pragma unroll
  for (int o = 16; o > 0; o >>= 1) v += __shfl_xor_sync(0xffffffffu, v, o);
  return v;
}
__device__ __forceinline__ void mma_bf16(float* d, uint32_t a0, uint32_t a1, uint32_t a2, uint32_t a3, uint32_t b0, uint32_t b1) {
  asm volatile("mma.sync.aligned.m16n8k16.row.col.f32.bf16.bf16.f32 {%0,%1,%2,%3}, {%4,%5,%6,%7}, {%8,%9}, {%0,%1,%2,%3};"
               : "+f"(d[0]), "+f"(d[1]), "+f"(d[2]), "+f"(d[3]) : "r"(a0), "r"(a1), "r"(a2), "r"(a3), "r"(b0), "r"(b1));
}
__device__ __forceinline__ void mma_bf16_k8(float* d, uint32_t a0, uint32_t a1, uint32_t b0) {
  asm volatile("mma.sync.aligned.m16n8k8.row.col.f32.bf16.bf16.f32 {%0,%1,%2,%3}, {%4,%5}, {%6}, {%0,%1,%2,%3};"
               : "+f"(d[0]), "+f"(d[1]), "+f"(d[2]), "+f"(d[3]) : "r"(a0), "r"(a1), "r"(b0));
}

__device__ __forceinline__ void wg_fence() { asm volatile("wgmma.fence.sync.aligned;" ::: "memory"); }
__device__ __forceinline__ void wg_commit() { asm volatile("wgmma.commit_group.sync.aligned;" ::: "memory"); }
template <int N> __device__ __forceinline__ void wg_wait() { asm volatile("wgmma.wait_group.sync.aligned %0;" :: "n"(N) : "memory"); }
template <int TB> __device__ __forceinline__ void wgmma32(float* d, const uint32_t* a, uint32_t dlo, uint32_t dhi) {
  asm volatile("{ .reg .b64 dd; mov.b64 dd, {%20, %21}; wgmma.mma_async.sync.aligned.m64n32k16.f32.f16.f16 "
               "{%0,%1,%2,%3,%4,%5,%6,%7,%8,%9,%10,%11,%12,%13,%14,%15}, {%16,%17,%18,%19}, dd, 1, 1, 1, %22; }"
               : "+f"(d[0]), "+f"(d[1]), "+f"(d[2]), "+f"(d[3]), "+f"(d[4]), "+f"(d[5]), "+f"(d[6]), "+f"(d[7]), "+f"(d[8]), "+f"(d[9]), "+f"(d[10]), "+f"(d[11]), "+f"(d[12]), "+f"(d[13]), "+f"(d[14]), "+f"(d[15])
               : "r"(a[0]), "r"(a[1]), "r"(a[2]), "r"(a[3]), "r"(dlo), "r"(dhi), "n"(TB));
}
template <int TB> __device__ __forceinline__ void wgmma64(float* d, const uint32_t* a, uint32_t dlo, uint32_t dhi) {
  asm volatile("{ .reg .b64 dd; mov.b64 dd, {%36, %37}; wgmma.mma_async.sync.aligned.m64n64k16.f32.f16.f16 "
               "{%0,%1,%2,%3,%4,%5,%6,%7,%8,%9,%10,%11,%12,%13,%14,%15,%16,%17,%18,%19,%20,%21,%22,%23,%24,%25,%26,%27,%28,%29,%30,%31}, {%32,%33,%34,%35}, dd, 1, 1, 1, %38; }"
               : "+f"(d[0]), "+f"(d[1]), "+f"(d[2]), "+f"(d[3]), "+f"(d[4]), "+f"(d[5]), "+f"(d[6]), "+f"(d[7]), "+f"(d[8]), "+f"(d[9]), "+f"(d[10]), "+f"(d[11]), "+f"(d[12]), "+f"(d[13]), "+f"(d[14]), "+f"(d[15]), "+f"(d[16]), "+f"(d[17]), "+f"(d[18]), "+f"(d[19]), "+f"(d[20]), "+f"(d[21]), "+f"(d[22]), "+f"(d[23]), "+f"(d[24]), "+f"(d[25]), "+f"(d[26]), "+f"(d[27]), "+f"(d[28]), "+f"(d[29]), "+f"(d[30]), "+f"(d[31])
               : "r"(a[0]), "r"(a[1]), "r"(a[2]), "r"(a[3]), "r"(dlo), "r"(dhi), "n"(TB));
}
template <int TB> __device__ __forceinline__ void wgmma64_init(float* d, const uint32_t* a, uint32_t dlo, uint32_t dhi) {
  asm volatile("{ .reg .b64 dd; mov.b64 dd, {%36, %37}; wgmma.mma_async.sync.aligned.m64n64k16.f32.f16.f16 "
               "{%0,%1,%2,%3,%4,%5,%6,%7,%8,%9,%10,%11,%12,%13,%14,%15,%16,%17,%18,%19,%20,%21,%22,%23,%24,%25,%26,%27,%28,%29,%30,%31}, {%32,%33,%34,%35}, dd, 0, 1, 1, %38; }"
               : "=f"(d[0]), "=f"(d[1]), "=f"(d[2]), "=f"(d[3]), "=f"(d[4]), "=f"(d[5]), "=f"(d[6]), "=f"(d[7]), "=f"(d[8]), "=f"(d[9]), "=f"(d[10]), "=f"(d[11]), "=f"(d[12]), "=f"(d[13]), "=f"(d[14]), "=f"(d[15]), "=f"(d[16]), "=f"(d[17]), "=f"(d[18]), "=f"(d[19]), "=f"(d[20]), "=f"(d[21]), "=f"(d[22]), "=f"(d[23]), "=f"(d[24]), "=f"(d[25]), "=f"(d[26]), "=f"(d[27]), "=f"(d[28]), "=f"(d[29]), "=f"(d[30]), "=f"(d[31])
               : "r"(a[0]), "r"(a[1]), "r"(a[2]), "r"(a[3]), "r"(dlo), "r"(dhi), "n"(TB));
}
template <int TB> __device__ __forceinline__ void wgmma32_init(float* d, const uint32_t* a, uint32_t dlo, uint32_t dhi) {
  asm volatile("{ .reg .b64 dd; mov.b64 dd, {%20, %21}; wgmma.mma_async.sync.aligned.m64n32k16.f32.f16.f16 "
               "{%0,%1,%2,%3,%4,%5,%6,%7,%8,%9,%10,%11,%12,%13,%14,%15}, {%16,%17,%18,%19}, dd, 0, 1, 1, %22; }"
               : "=f"(d[0]), "=f"(d[1]), "=f"(d[2]), "=f"(d[3]), "=f"(d[4]), "=f"(d[5]), "=f"(d[6]), "=f"(d[7]), "=f"(d[8]), "=f"(d[9]), "=f"(d[10]), "=f"(d[11]), "=f"(d[12]), "=f"(d[13]), "=f"(d[14]), "=f"(d[15])
               : "r"(a[0]), "r"(a[1]), "r"(a[2]), "r"(a[3]), "r"(dlo), "r"(dhi), "n"(TB));
}
__device__ __forceinline__ void wgmma64h(uint32_t* d, uint32_t a0, uint32_t a1, uint32_t a2, uint32_t a3, uint32_t dlo, uint32_t dhi) {
  asm volatile("{ .reg .b64 dd; mov.b64 dd, {%20, %21}; wgmma.mma_async.sync.aligned.m64n64k16.f16.f16.f16 "
               "{%0,%1,%2,%3,%4,%5,%6,%7,%8,%9,%10,%11,%12,%13,%14,%15}, {%16,%17,%18,%19}, dd, 1, 1, 1, 0; }"
               : "+r"(d[0]), "+r"(d[1]), "+r"(d[2]), "+r"(d[3]), "+r"(d[4]), "+r"(d[5]), "+r"(d[6]), "+r"(d[7]), "+r"(d[8]), "+r"(d[9]), "+r"(d[10]), "+r"(d[11]), "+r"(d[12]), "+r"(d[13]), "+r"(d[14]), "+r"(d[15])
               : "r"(a0), "r"(a1), "r"(a2), "r"(a3), "r"(dlo), "r"(dhi));
}
__device__ __forceinline__ void wgmma64h_init(uint32_t* d, uint32_t a0, uint32_t a1, uint32_t a2, uint32_t a3, uint32_t dlo, uint32_t dhi) {
  asm volatile("{ .reg .b64 dd; mov.b64 dd, {%20, %21}; wgmma.mma_async.sync.aligned.m64n64k16.f16.f16.f16 "
               "{%0,%1,%2,%3,%4,%5,%6,%7,%8,%9,%10,%11,%12,%13,%14,%15}, {%16,%17,%18,%19}, dd, 0, 1, 1, 0; }"
               : "=r"(d[0]), "=r"(d[1]), "=r"(d[2]), "=r"(d[3]), "=r"(d[4]), "=r"(d[5]), "=r"(d[6]), "=r"(d[7]), "=r"(d[8]), "=r"(d[9]), "=r"(d[10]), "=r"(d[11]), "=r"(d[12]), "=r"(d[13]), "=r"(d[14]), "=r"(d[15])
               : "r"(a0), "r"(a1), "r"(a2), "r"(a3), "r"(dlo), "r"(dhi));
}
__device__ __forceinline__ void wgmma40_ss(float* d, uint32_t alo, uint32_t blo, uint32_t hi) {
  asm volatile("{ .reg .b64 da, db; mov.b64 da, {%20, %22}; mov.b64 db, {%21, %22}; "
               "wgmma.mma_async.sync.aligned.m64n40k16.f32.f16.f16 {%0,%1,%2,%3,%4,%5,%6,%7,%8,%9,%10,%11,%12,%13,%14,%15,%16,%17,%18,%19}, da, db, 1, 1, 1, 1, 1; }"
               : "+f"(d[0]), "+f"(d[1]), "+f"(d[2]), "+f"(d[3]), "+f"(d[4]), "+f"(d[5]), "+f"(d[6]), "+f"(d[7]), "+f"(d[8]), "+f"(d[9]), "+f"(d[10]), "+f"(d[11]), "+f"(d[12]), "+f"(d[13]), "+f"(d[14]), "+f"(d[15]), "+f"(d[16]), "+f"(d[17]), "+f"(d[18]), "+f"(d[19])
               : "r"(alo), "r"(blo), "r"(hi));
}
__device__ __forceinline__ void wgmma40_ss_init(float* d, uint32_t alo, uint32_t blo, uint32_t hi) {
  asm volatile("{ .reg .b64 da, db; mov.b64 da, {%20, %22}; mov.b64 db, {%21, %22}; "
               "wgmma.mma_async.sync.aligned.m64n40k16.f32.f16.f16 {%0,%1,%2,%3,%4,%5,%6,%7,%8,%9,%10,%11,%12,%13,%14,%15,%16,%17,%18,%19}, da, db, 0, 1, 1, 1, 1; }"
               : "=f"(d[0]), "=f"(d[1]), "=f"(d[2]), "=f"(d[3]), "=f"(d[4]), "=f"(d[5]), "=f"(d[6]), "=f"(d[7]), "=f"(d[8]), "=f"(d[9]), "=f"(d[10]), "=f"(d[11]), "=f"(d[12]), "=f"(d[13]), "=f"(d[14]), "=f"(d[15]), "=f"(d[16]), "=f"(d[17]), "=f"(d[18]), "=f"(d[19])
               : "r"(alo), "r"(blo), "r"(hi));
}
__device__ __forceinline__ void tma_box(uint32_t dst, const CUtensorMap* tm, uint32_t mb, int x, int y) {
  asm volatile("cp.async.bulk.tensor.2d.shared::cluster.global.mbarrier::complete_tx::bytes [%0], [%1, {%3, %4}], [%2];"
               :: "r"(dst), "l"(tm), "r"(mb), "r"(x), "r"(y) : "memory");
}
__device__ __forceinline__ uint32_t uni(uint32_t v) {
  uint32_t r; asm volatile("shfl.sync.idx.b32 %0, %1, 0, 0x1f, 0xffffffff;" : "=r"(r) : "r"(v)); return r;
}
__device__ __forceinline__ uint32_t pin(uint32_t v) {
  uint32_t r; asm volatile("shfl.sync.bfly.b32 %0, %1, 0, 0x1f, 0xffffffff;" : "=r"(r) : "r"(v)); return r;
}

struct Params {
  const unsigned char* x;
  Scratch* s;
  int off[8];
  uint32_t* out;
  const uint16_t* dskip;
  const uint32_t* w_r;
  long long* ts;
  const unsigned char* far[7];
  uint32_t sched[2][17];
};
__device__ __forceinline__ uint32_t ldnc32(const void* p) { uint32_t v; asm volatile("ld.global.nc.b32 %0, [%1];" : "=r"(v) : "l"(p)); return v; }
__device__ __forceinline__ uint32_t ldnc16(const void* p) { uint16_t v; asm volatile("ld.global.nc.u16 %0, [%1];" : "=h"(v) : "l"(p)); return v; }
__device__ __forceinline__ void mbar_wait(uint32_t mb, uint32_t ph = 0) {
#pragma unroll 1
  for (int it = 0; it < SPIN_MAX; it++) {
    uint32_t ok;
    asm volatile("{ .reg .pred q; mbarrier.try_wait.parity.shared::cta.b64 q, [%1], %2; selp.u32 %0, 1, 0, q; }" : "=r"(ok) : "r"(mb), "r"(ph) : "memory");
    if (ok) break;
  }
}
__device__ __forceinline__ void mbar_arrive(uint32_t mb) { asm volatile("mbarrier.arrive.shared::cta.b64 _, [%0];" :: "r"(mb) : "memory"); }
__device__ __forceinline__ void fence_async() { asm volatile("fence.proxy.async.shared::cta;" ::: "memory"); }
#define SPIN_WHILE(cond, body) _Pragma("unroll 1") for (int _it = 0; _it < SPIN_MAX && __any_sync(0xffffffffu, (cond)); _it++) { body; }

struct LnC { uint32_t m2, rh2, rl2; };
__device__ __forceinline__ LnC ln_consts(float s, float q, float& r) {
  const float mean = s * (1.f / DM);
  const float var = fmaxf(fmaf(-mean, mean, q * (1.f / DM)), 0.f);
  float sd;
  asm("sqrt.approx.ftz.f32 %0, %1;" : "=f"(sd) : "f"(bfr(bfr(var) + 1e-5f)));
  asm("rcp.approx.ftz.f32 %0, %1;" : "=f"(r) : "f"(bfr(sd)));
  LnC c;
  c.m2 = pack_bf(mean, mean);
  c.rh2 = pack_bf(r, r);
  const float rl = r - bf_lo(c.rh2);
  c.rl2 = pack_bf(rl, rl);
  return c;
}
__device__ __forceinline__ uint32_t bf_fma2(uint32_t a, uint32_t b, uint32_t c) {
  __nv_bfloat162 r = __hfma2(*(const __nv_bfloat162*)&a, *(const __nv_bfloat162*)&b, *(const __nv_bfloat162*)&c);
  return *(uint32_t*)&r;
}
__device__ __forceinline__ uint32_t ln_apply(uint32_t w, uint32_t m2, uint32_t rh2, uint32_t rl2) {
  const uint32_t d = bf_sub2(w, m2);
  return bf_fma2(d, rh2, bf_mul2(d, rl2));
}

__device__ __forceinline__ float2 cis(float mag_log2, float rev) {
  const float m = ex2(mag_log2), ang = rev * 6.283185307179586f;
  return make_float2(m * __cosf(ang), m * __sinf(ang));
}
__device__ __forceinline__ float2 csq(float2 a) { return make_float2(fmaf(a.x, a.x, -a.y * a.y), (a.x + a.x) * a.y); }
__device__ __forceinline__ float2 cmul(float2 a, float2 b) { return make_float2(fmaf(a.x, b.x, -a.y * b.y), fmaf(a.x, b.y, a.y * b.x)); }
__device__ __forceinline__ void pmul(uint32_t xr, uint32_t xi, uint32_t w, uint32_t& yr, uint32_t& yi) {
  const __half2 XR = *(__half2*)&xr, XI = *(__half2*)&xi, W = *(__half2*)&w;
  const __half2 a = __hfma2(__hneg2(XI), __high2half2(W), __hmul2(XR, __low2half2(W)));
  const __half2 b = __hfma2(XI, __low2half2(W), __hmul2(XR, __high2half2(W)));
  yr = *(const uint32_t*)&a; yi = *(const uint32_t*)&b;
}
__device__ __forceinline__ uint32_t pk(float2 a) { return pack_h(a.x, a.y); }

struct KgState { float2 c0, z8; float kl; uint32_t w64, w128, w192; };
__device__ __forceinline__ void kgen_tables_n(const uint32_t (&raw)[7], uint32_t scr, int wt, KgState& k) {
  const uint32_t dst = scr + 16384 + wt * 16;
  const float dt = bfr(ex2(bf_lo(raw[6]) * 1.4426950408889634f));
  const float th = dt * bf_lo(raw[1]);
  const float br = dt * bf_lo(raw[2]), bi = dt * bf_lo(raw[3]);
  const float Cr = bf_lo(raw[4]), Ci = bf_lo(raw[5]);
  k.c0 = make_float2(fmaf(Cr, br, -Ci * bi), fmaf(Cr, bi, Ci * br));
  const uint32_t mx = __reduce_max_sync(0xffffffffu, __float_as_uint(fmaxf(fabsf(k.c0.x), fabsf(k.c0.y))));
  const float a2 = dt * bf_lo(raw[0]) * 1.4426950408889634f;
  const float rh = th * 0.15915494309189535f;
  const float rl = fmaf(th, (float)(0.15915494309189535 - (double)0.15915494309189535f), fmaf(th, 0.15915494309189535f, -rh));
  const float rf = rh - rintf(rh);
  const float2 z1 = cis(a2, rf + rl);
  const float p64 = rf * 64.f;
  const float2 z64 = cis(a2 * 64.f, fmaf(64.f, rl, p64 - rintf(p64)));
  const float2 z2 = csq(z1), z128 = csq(z64), z3 = cmul(z2, z1), z4 = csq(z2), z256 = csq(z128), z6 = csq(z3), z512 = csq(z256);
  k.z8 = csq(z4);
  k.w64 = pk(z64); k.w128 = pk(z128); k.w192 = pk(cmul(z128, z64));
  sts128(dst, 0x00003C00u, pk(z2), pk(z4), pk(z6));
  const float2 z1024 = csq(z512), z768 = cmul(z512, z256);
  sts128(dst + 2048, pk(z1), pk(z3), pk(cmul(z4, z1)), pk(cmul(z4, z3)));
  const float2 z2048 = csq(z1024);
  k.kl = fmaf(k.c0.x, z2048.x, -k.c0.y * z2048.y);
  sts128(dst + 4096, pk(z256), pk(cmul(z256, z2)), pk(cmul(z256, z4)), pk(cmul(z256, z6)));
  sts128(dst + 6144, pk(z512), pk(cmul(z512, z4)), pk(z768), pk(cmul(z768, z4)));
  sts128(dst + 8192, pk(z1024), pk(cmul(z1024, z256)), pk(cmul(z1024, z512)), pk(cmul(z1024, z768)));
  sts32(scr + W_MISC + (wt >> 5) * 4, mx);
}
__device__ __forceinline__ int kgen_tables_m(uint32_t scr, int wt, const KgState& k) {
  const uint32_t dst = scr + wt * 16;
  const uint4 e4 = lds128(scr + W_MISC);
  const float2 z16 = csq(k.z8), z32 = csq(z16);
  const int em = max(min((int)(max(max(e4.x, e4.y), max(e4.z, e4.w)) >> 23), 238), 16);
  const float sc = __uint_as_float((uint32_t)(127 + 4 + 127 - em) << 23);
  sts32(scr + W_MISC + 16 + (wt >> 5) * 4, __reduce_add_sync(0xffffffffu, __float2int_rn(k.kl * sc * 262144.f)));
  const float2 c0 = make_float2(k.c0.x * sc, k.c0.y * sc);
  const float2 c1 = cmul(c0, k.z8), c2 = cmul(c0, z16), c4 = cmul(c0, z32), c3 = cmul(c1, z16), c5 = cmul(c1, z32), c6 = cmul(c2, z32), c7 = cmul(c3, z32);
  uint32_t pr[4], pi[4], yr[4], yi[4];
  pr[0] = pack_h(c0.x, c1.x); pi[0] = pack_h(c0.y, c1.y);
  pr[1] = pack_h(c2.x, c3.x); pi[1] = pack_h(c2.y, c3.y);
  pr[2] = pack_h(c4.x, c5.x); pi[2] = pack_h(c4.y, c5.y);
  pr[3] = pack_h(c6.x, c7.x); pi[3] = pack_h(c6.y, c7.y);
  sts128(dst, pr[0], pr[1], pr[2], pr[3]); sts128(dst + 2048, pi[0], pi[1], pi[2], pi[3]);
#pragma unroll
  for (int q = 1; q < 4; q++) {
    const uint32_t w = q == 1 ? k.w64 : q == 2 ? k.w128 : k.w192;
#pragma unroll
    for (int i = 0; i < 4; i++) pmul(pr[i], pi[i], w, yr[i], yi[i]);
    sts128(dst + q * 4096, yr[0], yr[1], yr[2], yr[3]); sts128(dst + q * 4096 + 2048, yi[0], yi[1], yi[2], yi[3]);
  }
  return em;
}
__device__ __forceinline__ uint32_t lds32_if(uint32_t a, bool on) {
  uint32_t v; asm volatile("{ .reg .pred q; setp.ne.u32 q, %2, 0; mov.b32 %0, 0; @q ld.shared.b32 %0, [%1]; }" : "=r"(v) : "r"(a), "r"((uint32_t)on) : "memory"); return v;
}
__device__ __forceinline__ uint32_t prmt(uint32_t a, uint32_t b, uint32_t s) { uint32_t r; asm("prmt.b32 %0, %1, %2, %3;" : "=r"(r) : "r"(a), "r"(b), "r"(s)); return r; }
__device__ __forceinline__ void kgen_build(uint32_t tb, int wg, int wt, uint32_t k0, uint32_t k1, uint32_t k2) {
  const uint32_t kt = tb + W_KT, sc = tb + W_L3 + 3072;
  const int ix = ((wt >> 2) + (wt & 3) * 32 - 1) & 127;
  const uint32_t a3 = tb + W_CW + 32 + ((ix & 1) ? 0 : 304) + (ix >> 1) * 4, a2 = sc + 544 + (wt & ~3) * 2 + (wt & 1) * 4 + (wt & 2) * 128;
  const uint32_t v3 = wt ? k2 : k2 >> 16;
  sts32(sc + 4 + wt * 4, __byte_perm(k0, k1, 0x5432));
  sts16(a2, k1 >> 16); sts16(a2 + 6, k1 >> 16);
  sts16(a3, v3); sts16(a3 + 6, v3);
  if ((unsigned)(wt - 32) < 14u) sts128(kt + (wt < 36 ? -512 : 64 + 4128 - 576) + wt * 16, 0, 0, 0, 0);
  if (wt == 127) sts32(sc, k0 & 0xFFFF0000u);
  if (wt == 0) { sts32(sc + 516, k1); sts16(sc + 1056, k2); }
  bar_sync(1 + wg, 128);
  const uint32_t cw = tb + W_CW + 32 + (wt >> 6) * 48 + wt * 4, g2 = sc + 540 + wt * 4;
  const bool odd = wt & 1, ends = (unsigned)(wt - 4) >= 120u;
  const uint32_t pv = lds32(sc + wt * 4), nx = lds32(sc + 8 + wt * 4), nc = lds32_if(g2 + 8, ends);
  const uint32_t l0 = lds32(cw), l1 = lds32(cw - 8), l2 = lds32(cw - 16), l3 = lds32(cw - 24), q0 = lds32(g2), q1 = lds32(g2 + 128), q2 = lds32(g2 - 8), q3 = lds32(g2 + 120);
  sts64(kt + 64 + wt * 8, __byte_perm(k0, pv, 0x5410), __byte_perm(k0, 0, 0x1032));
  sts64(kt + 64 + 1024 + wt * 8, __byte_perm(k1, pv, (odd || wt == 0) ? 0x7610 : 0x1010), __byte_perm(k1, nx, odd ? 0x1076 : 0x1010));
  const uint32_t cc = __byte_perm(nc, 0, 0x3232), nn = __byte_perm(nc, 0, 0x1010);
  if (ends) sts128(kt + 64 + 2048 + wt * 16, cc, cc, odd ? nc : cc, odd ? nn : nc);
  if (wt == 127) { sts128(kt + 64 + 4096, nn, nn, nn, nn); sts128(kt + 64 + 4112, nn, nn << 16, 0, 0); }
  sts128(tb + W_L3 + 512 + (wt >> 6) * 512 + wt * 16, l0, l1, l2, l3);
  if ((wt & 63) < 34) sts128(tb + W_QT - 16 + wt * 16, q0, q1, q2, q3);
}

__device__ __forceinline__ void load_a(uint32_t (&a)[4], uint32_t kp, int j) {
  a[0] = lds32(kp + 64 * j); a[1] = lds32(kp + 64 * j + 512); a[2] = lds32(kp + 64 * j - 32); a[3] = lds32(kp + 64 * j + 480);
}
__device__ __forceinline__ uint32_t band(int d, int lo, int hi) {
  return ((unsigned)(d - lo) <= (unsigned)(hi - lo) ? 1u : 0u) | ((unsigned)(d - 1 - lo) <= (unsigned)(hi - lo) ? 0x10000u : 0u);
}
__device__ __forceinline__ uint32_t hadd2u(uint32_t a, uint32_t b) { __half2 r = __hadd2(*(__half2*)&a, *(__half2*)&b); return *(uint32_t*)&r; }

__device__ __forceinline__ void zero_pads(uint32_t tb, int wt) {
  if (!(wt & 32)) sts128(tb + W_L3 + (wt >> 6) * 512 + wt * 16, 0, 0, 0, 0);
  if ((wt & 63) < 3) sts128(tb + W_CW + (wt >> 6) * 304 + (wt & 63) * 16, 0, 0, 0, 0);
}
__device__ __forceinline__ uint32_t tr_base(int lane) {
  return OFF_YT + (2 * (lane >> 3) + (lane & 1)) * YT_PITCH + ((lane >> 1) & 1) * (8 * YT_PITCH + 64) + ((lane >> 2) & 1) * 16;
}

__device__ __forceinline__ uint32_t sc_addr(int tp) { return OFF_YT + (tp < 16 ? tp * YT_PITCH + (tp >> 3) * 64 + 1152 : 8 * YT_PITCH - 512 + tp * 32); }
#define X_PW 15
#define X_HU 16
#define X_NE 2
#define X_SCT 10000
#define X_DELTA 0
#define X_DSTEP 2000
#define X_PF0 2700
#define X_PFD 600
#define X_TD 450
#define X_WS 6
#define X_OR 8
#define X_ABS 4870
#define X_XD 200
#define X_RD 630
#define X_HD 450
#define X_PD 1170
#define X_PROMO 2
#define X_YD2 1000
#define X_GO 1
#define X_GW 2
#define X_NS 4300
#define X_XS 13450
#define X_LAG 1300
#define X_YD 1550
struct TMaps { CUtensorMap m[10]; };
__device__ __forceinline__ uint32_t h2bf(uint32_t w) { const float2 f = h2f(w); return pack_bf(f.x, f.y); }
__device__ __forceinline__ uint32_t keep(uint32_t v) { asm volatile("" : "+r"(v)); return v; }
__device__ __forceinline__ uint2 ldr64(const void* p) { uint2 v; asm volatile("{ .reg .b64 t; ld.relaxed.gpu.global.b64 t, [%2]; mov.b64 {%0, %1}, t; }" : "=r"(v.x), "=r"(v.y) : "l"(p) : "memory"); return v; }
__host__ __device__ __forceinline__ uint32_t down_box(int s, bool five) {
  return five ? OFF_W + W_BYTES + 12288 + (s / 3) * (W_BYTES - 12288) + s * 4096 : s < 6 ? OFF_W + W_BYTES + BOX + (s >> 1) * (W_BYTES - 10240) + s * 5120 : OFF_W + (s - 6) * 5120;
}
__device__ __forceinline__ void load_tile(const CUtensorMap* tmx, int i, int c, int again = 0) {
  asm volatile("mbarrier.arrive.expect_tx.shared::cta.b64 _, [%0], 8704;" :: "r"(MB_UL + i * 16 + again) : "memory");
  asm volatile("cp.async.bulk.tensor.3d.shared::cluster.global.mbarrier::complete_tx::bytes [%0], [%1, {%3, %4, %5}], [%2];"
               :: "r"(i < 2 ? OFF_T + i * TILE : OFF_W), "l"(tmx), "r"(MB_UL + i * 16 + again), "r"(0), "r"(c), "r"(-8) : "memory");
}
template <bool FAR> __device__ __forceinline__ void load_params(const Params& p, uint32_t ch, int wt, uint32_t dst, bool on) {
  const int rel = wt < 96 ? ch * 16 + (wt & 15) : ch >> 3;
  const unsigned char* b = FAR ? p.far[min(wt >> 4, 6)] + rel * 16 : p.x + (long long)(p.off[wt >> 4] + rel) * 16;
  asm volatile("{ .reg .pred q; setp.ne.u32 q, %2, 0; @q cp.async.cg.shared.global [%0], [%1], 16; }"
               :: "r"(dst + wt * 16), "l"(b), "r"((uint32_t)(on && wt < 97)) : "memory");
}

struct ConvC { uint32_t ca, cb, bands, qa; };
__device__ __forceinline__ ConvC conv_consts(int w, int lane) {
  const int h = w & 1, P = (w >> 1) & 1, d0 = 8 * h + (lane >> 2) - 2 * (lane & 3);
  ConvC k;
  k.ca = keep((W_KT + (16 + 256 * P + d0) * 4) | (((8 + 64 * P + lane) * 64 + (((h + ((w >> 1) & 2)) ^ (lane >> 1)) & 3) * 16) << 16));
  const int u = d0 + 2 * (lane & 1) + 2, in = (u & 7) - ((u & 7) >= 5 ? 5 : 0) - 2 * (lane & 1);
  k.cb = keep(in > 0 ? 0x1010 : in == 0 ? 0x3210 : 0x3232);
  k.qa = keep(W_QT + (2 * (u >> 3) + ((u & 7) >= 5) + 64 * P) * 16);
  k.bands = keep(band(d0, 12, 20) + 2 * band(d0 + 8, 12, 20) + 4 * band(d0 + 16, 12, 20) + 8 * band(d0 + 24, 12, 20)
                 + 16 * band(d0 - 8, 5, 11) + 32 * band(d0, 5, 11) + 64 * band(d0 + 8, 5, 11) + 128 * band(d0 + 16, 5, 11));
  return k;
}
struct ConvPre { uint32_t e0, e2, f2, b0, b2, a[3][4]; };
__device__ __forceinline__ void conv_pre(ConvPre& r, uint32_t kp, uint32_t qp, int part, bool on, bool P) {
  if (part & 1) {
    r.e0 = lds32_if(kp + 4096, on && !P); r.e2 = lds32_if(kp + 4064, on && !P); r.f2 = lds32_if(kp + 4128, on && !P);
    r.b0 = lds32_if(kp + 2048, on && !P); r.b2 = lds32_if(kp + 2016, on && !P);
  }
#pragma unroll
  for (int j = 0; j < 3; j++) if (part & (j < 1 ? 1 : 2))
    asm volatile("{ .reg .pred q; setp.ne.u32 q, %5, 0; mov.b32 %0, 0; mov.b32 %1, 0; mov.b32 %2, 0; mov.b32 %3, 0; @q ld.shared.v4.b32 {%0,%1,%2,%3}, [%4]; }"
                 : "=r"(r.a[j][0]), "=r"(r.a[j][1]), "=r"(r.a[j][2]), "=r"(r.a[j][3]) : "r"(qp + 64 * j), "r"((uint32_t)on) : "memory");
}
__device__ __forceinline__ void conv_item(uint32_t tb, uint32_t tl, int bid, int bn, ConvPre& pre, const ConvC& cv, uint32_t zero, const CUtensorMap* tmx, int ch, int warp, int lane, bool hold, bool more) {
  const bool go = more && warp == 0 && lane == 0;
  const uint32_t kp = tb + (cv.ca & 0xFFFFu), qp = tb + cv.qa;
  const uint32_t dlo = (tl >> 4) + 32 + ((warp >> 1) & 2) + (1u << 16), dhi = 32u | (2u << 30);
  const bool P = warp & 2;
  float a32[16], b32[16], a64[32];
  uint32_t A[40][4];
#define STEP(J) { wgmma64<0>(a64, A[J], dlo + 256 - 4 * (J), dhi); \
    if ((J) == 32) wgmma32_init<0>(b32, A[J], dlo, dhi); else wgmma32<0>(b32, A[J], ((J) < 8 ? dlo ^ zero : dlo) + 128 - 4 * (J), dhi); \
    if ((J) == 0) wgmma32_init<0>(a32, A[J], dlo, dhi); else if ((J) < 8) wgmma32<0>(a32, A[J], (dlo ^ zero) - 4 * (J), dhi); }
#define LD(J) load_a(A[J], kp, J);
#define LQ(J) { const uint4 v = lds128(qp + 64 * ((J) - 32)); A[J][0] = v.x; A[J][1] = v.y; A[J][2] = v.z; A[J][3] = v.w; }
#define PQ(J) { A[J][0] = prmt(A[J][0], 0, cv.cb); A[J][1] = prmt(A[J][1], 0, cv.cb); A[J][2] = prmt(A[J][2], 0, cv.cb); A[J][3] = prmt(A[J][3], 0, cv.cb); }
#define FIRST(J) wg_fence(); STEP(J) wg_commit(); wg_wait<1>(); wg_fence();
  {
    uint32_t win[16], x9[4], x7[4], e[4], f[4];
    const uint32_t bz = keep(cv.bands);
#define BAND(i) keep((bz & (0x10001u << (i))) * (0x3C00u >> (i)))
    e[0] = pre.e0; e[2] = pre.e2; e[1] = keep(bz & 0x100u); e[3] = keep(bz & 0x200u);
    f[2] = pre.f2; f[0] = keep(bz & 0x4000u); f[1] = keep(bz & 0x8000u); f[3] = keep(bz & 0x300u);
#pragma unroll
    for (int j = 0; j < 12; j++) A[32 + j / 4][j & 3] = pre.a[j / 4][j & 3];
    PQ(32) PQ(33) PQ(34)
    if (!P) { A[32][0] = pre.b0; A[32][2] = pre.b2; }
    const uint32_t q[12] = {BAND(0), BAND(5), keep(bz & 0x400u), BAND(4), BAND(2), BAND(7), BAND(1), BAND(6), keep(bz & 0x800u), keep(bz & 0x1000u), BAND(3), keep(bz & 0x2000u)};
#undef BAND
    const uint32_t ta = keep(tl + 512 + (warp & 3) * 2048 + lane * 64 + (lane & 6) * 8);
    if (X_GO && hold) mbar_wait(MB_GO);
    uint32_t mbl = MB_UL + (warp & 8) * 2, ph = 0;
#pragma unroll 1
    for (int it = 0; it < SPIN_MAX; it++) {
      if (ch < 512) mbar_wait(mbl, ph);
      if (it == 1) TS(13);
      TS(3);
      wg_fence();
      wgmma64h_init(win, q[0], q[1], q[2], q[3], dlo, dhi);
      wgmma64h(win, q[4], q[5], q[6], q[7], dlo - 4, dhi);
      wgmma64h(win, q[8], q[9], q[10], q[11], dlo - 8, dhi);
      wg_commit();
      wgmma64_init<0>(a64, e, dlo, dhi);
      wgmma64<0>(a64, f, dlo - 4, dhi);
      wg_commit();
      if (ch >= 512) break;
      uint32_t r0, r1, r2, r3, ok;
      if (warp & 4) {
        mbar_wait(mbl + 8);
        if (__all_sync(0xffffffffu, it || lds32(MISC_RT + (warp & 8)) == 0)) break;
        wg_wait<0>();
        continue;
      }
      ldsm4(ta, r0, r1, r2, r3);
      ok = r0 & r1 & r2 & r3;
      ldsm4(ta ^ 32, r0, r1, r2, r3);
      asm volatile("{ .reg .pred q; setp.ne.u32 q, %1, 0; barrier.red.and.pred q, %2, 128, q; selp.u32 %0, 1, 0, q; }" : "=r"(ok) : "r"((ok & r0 & r1 & r2 & r3 & 1u) | (lane & 3)), "r"(1 + (warp >> 2)) : "memory");
      if (ok) { if ((warp & 3) == 0 && lane == 0) { sts32(MISC_RT + warp, it); mbar_arrive(MB_UL + 8 + warp * 2); } break; }
      wg_wait<0>();
      if ((warp & 3) == 0 && lane == 0) load_tile(tmx - 1, warp >> 3, ch, 56);
      mbl = MB_UL + 56 + (warp & 8) * 2; ph = it & 1;
    }
    wg_wait<1>();
#pragma unroll
    for (int i = 0; i < 4; i++) {
      const int tl = 2 * ((i & 1) + ((i & 2) ? 0 : 4));
      x9[i] = P ? win[tl + 4] : win[tl]; x7[i] = P ? win[tl + 5] : win[tl + 1];
    }
    const uint32_t l3lo = ((tb + W_L3) >> 4) + (32u << 16);
    wg_fence();
    wgmma64<0>(a64, x9, l3lo, 8);
    wgmma64<0>(a64, x7, l3lo + 96, 8);
    wg_commit();
  }
  STEP(32) STEP(33) STEP(34) wg_commit(); wg_wait<1>();
  LQ(35) LQ(36) LQ(37) LQ(38) LQ(39) LD(0) PQ(35) PQ(36) PQ(37) PQ(38) PQ(39)
  FIRST(35) STEP(36) STEP(37) STEP(38) wg_commit(); STEP(39) wg_commit();
  LD(1) LD(2) LD(3)
  if (X_GO == 1 && go) mbar_arrive(MB_GO);
  wg_wait<1>(); wg_fence(); STEP(0) wg_commit(); STEP(1) wg_commit(); STEP(2) wg_commit(); wg_wait<2>();
  LD(4) LD(5)
  wg_fence(); STEP(3) wg_commit(); wg_wait<1>();
  LD(6) LD(7)
  wg_fence(); STEP(4) STEP(5) wg_commit();
  wg_fence(); STEP(6) STEP(7) wg_commit();
#undef STEP
#undef LD
#undef LQ
#undef PQ
#undef FIRST
  TS(18);
  if (X_GO == 3 && go) mbar_arrive(MB_GO);
  const uint32_t xc = tb + W_KT + (warp & 3) * 1024 + lane * 16;
  if (more) bar_sync(7, 288);
  wg_wait<1>();
  conv_pre(pre, kp + ALT, qp + ALT, 1, more, P);
  wg_wait<0>();
  conv_pre(pre, kp + ALT, qp + ALT, 2, more, P);
  uint32_t E[16], o[8];
#define ACC(i) ((i) < 16 ? a32[i] : (i) < 32 ? b32[(i) - 16] : a64[(i) - 32])
  E[0] = pack_h(a32[0], a32[1]);
#pragma unroll
  for (int i = 1; i < 16; i++) E[i] = pack_h(ACC(4 * i) + ACC(4 * i - 2), ACC(4 * i + 1) + ACC(4 * i - 1));
#undef ACC
#pragma unroll
  for (int j = 0; j < 8; j++) o[j] = P ? (j < 2 ? 0u : E[j - 2]) : E[8 + j];
  sts128(xc, o[0], o[1], o[2], o[3]); sts128(xc + 512, o[4], o[5], o[6], o[7]);
#pragma unroll
  for (int j = 0; j < 8; j++) o[j] = P ? E[6 + j] : E[j];
  TS(25);
  if (more) {
    sts128(xc + 4096, o[0], o[1], o[2], o[3]); sts128(xc + 4608, o[4], o[5], o[6], o[7]);
    bar_arrive(12, 192);
    return;
  }
  bar_sync(1 + (warp >> 2), 128);
  const uint4 vv[2] = {lds128(xc + (P ? -2048 : 2048)), lds128(xc + (P ? -1536 : 2560))};
  const uint32_t mk = lane < 8 ? 0xFFFEFFFEu : ~0u;
#pragma unroll
  for (int q = 0; q < 2; q++) {
    const uint4 v = vv[q];
    stsm4t(tl + (cv.ca >> 16) + q * 2048, hadd2u(o[4 * q], v.x) & mk, hadd2u(o[4 * q + 1], v.y) & mk, hadd2u(o[4 * q + 2], v.z) & mk, hadd2u(o[4 * q + 3], v.w) & mk);
  }
  fence_async();
  bar_sync(bid, bn);
  if (warp == 0 && lane == 0) mbar_arrive(MB_REL);
  if ((warp & 7) == (ch < 512 ? 7 : 3) && lane == 0) {
    asm volatile("cp.async.bulk.tensor.3d.global.shared::cta.bulk_group [%0, {%3, %2, %3}], [%1];" :: "l"(tmx), "r"(tl + 512), "r"(ch), "r"(0) : "memory");
    asm volatile("cp.async.bulk.commit_group;" ::: "memory");
  }
}

template <bool FAR> __global__ void __launch_bounds__(NT, 1)
fused_kernel(const __grid_constant__ Params p, const __grid_constant__ TMaps tm) {
  extern __shared__ __align__(1024) unsigned char smem[];
  const int c = blockIdx.x;
  const bool five = (c & 1) == 0;
  const uint32_t pitch = five ? 64 : 80;
  const uint32_t ones = 0x3F803F80u;
  const int tid = threadIdx.x, lane = tid & 31;
  const uint32_t xrow = OFF_YT + ((tid & 127) >> 3) * YT_PITCH + (tid & 64) + (tid & 7) * 16;
  {
    const int w4 = tid >> 7;
    load_params<FAR>(p, w4 < 2 ? 2 * c + w4 : five ? 257 + 2 * c : 512 + (c >> 1), tid & 127, OFF_W + W_KT + (w4 < 2 ? w4 * W_BYTES : five ? 3 * W_BYTES : 3 * W_BYTES + 2048), (0xB >> w4) & 1);
  }
  if ((tid >> 7) == 2) {
    const unsigned char* xp = p.x + (uint32_t)((c * 16 - 32 + (tid >> 3)) * 1152 + (tid & 7) * 16);
    asm volatile("" : "+l"(xp));
    { const uint32_t tq = clock(); while ((int)(clock() - tq) < X_XD) {} }
#pragma unroll
    for (int k = 0; k < 9; k++) asm volatile("cp.async.cg.shared.global [%0], [%1], 16;" :: "r"(xrow + k * 128), "l"(xp + k * 128) : "memory");
  }
  const int warp = (int)uni(tid >> 5), wg = warp >> 2;
  TS(0);
  if (__builtin_expect(wg == 4, 0)) {
    asm volatile("setmaxnreg.dec.sync.aligned.u32 32;");
    const int role = warp;
    const int u0 = (c >> 1) * 9 + (five ? ((c & 2) ? 5 : 0) : ((c & 2) ? 0 : 4));
    const uint32_t t0 = clock() + c * 4;
    if (role == 16) {
      if (lane == 0) {
#pragma unroll
        for (int i = 0; i < 19; i++) if (i != 16) asm volatile("mbarrier.init.shared::cta.b64 [%0], %1;" :: "r"(OFF_MISC + i * 8), "r"((unsigned)(i - 2) < 4u ? 4 : 1) : "memory");
      }
      __syncwarp();
      if (lane < 2) asm volatile("mbarrier.arrive.expect_tx.shared::cta.b64 _, [%0], %1;" :: "r"(OFF_MISC + lane * 8), "r"(lane ? (five ? 36864 : 51200) : pitch * 1152) : "memory");
      fence_async();
      bar_arrive(5, 608);
      const CUtensorMap* tmb = &tm.m[five ? 3 : 0];
#pragma unroll 1
      for (int u = 0; u < 17; u++) {
        const uint32_t e = p.sched[five][u], kind = e & 3, s = (e >> 2) & 15, dst = e >> 14;
        if (kind == 3) continue;
        while ((int)(clock() - t0) < X_PF0 + (u < X_NE ? u * X_PFD : X_LAG + u * X_TD)) __nanosleep(20);
        if (e & 0x3FC0) mbar_wait(OFF_MISC + ((e >> 6) & 255));
        if (lane == 0) {
          if (kind == 2) asm volatile("cp.async.bulk.tensor.3d.shared::cluster.global.mbarrier::complete_tx::bytes [%0], [%1, {%3, %4, %5}], [%2];"
                                      :: "r"(dst), "l"(tmb + 2), "r"(MB_D), "r"(0), "r"(u0 * 8), "r"(s) : "memory");
          else tma_box(dst, tmb + kind, MB_GU, u0 * 8, s * 96);
        }
        if (u == 5) TS(2);
        if (u == 10) TS(3);
      }
      TS(4);
      TS_DUMP();
#define FINISH0 bar_sync(12, 192);        \
        _Pragma("unroll 1") for (int w = role & 2; w < (role & 2) + 2; w++) { \
          const uint32_t xa = OFF_W + W_KT + lane * 16, mk = lane < 8 ? 0xFFFEFFFEu : ~0u, ya = OFF_T + (8 + lane) * 64 + (((w & 1) ^ (lane >> 1)) & 3) * 16 + (w & 2) * 2048; \
          const uint4 a = lds128(xa + 4096 + w * 1024), b = lds128(xa + (w ^ 2) * 1024), d = lds128(xa + 4608 + w * 1024), e = lds128(xa + 512 + (w ^ 2) * 1024); \
          stsm4t(ya, hadd2u(a.x, b.x) & mk, hadd2u(a.y, b.y) & mk, hadd2u(a.z, b.z) & mk, hadd2u(a.w, b.w) & mk); \
          stsm4t(ya + 2048, hadd2u(d.x, e.x) & mk, hadd2u(d.y, e.y) & mk, hadd2u(d.z, e.z) & mk, hadd2u(d.w, e.w) & mk); \
        } \
        fence_async();
    } else if (role == 17) {
      if (smem_u32(smem) != SB) __trap();
      bar_sync(10, 576);
      if (lane == 0) {
        fence_async();
        while ((int)(clock() - t0) < X_NS - c * 4) {}
        asm volatile("cp.async.bulk.global.shared::cta.bulk_group [%0], [%1], 10240;" :: "l"(&p.s->X[c * DM * 2 + 512]), "r"(OFF_G) : "memory");
        asm volatile("cp.async.bulk.commit_group;" ::: "memory");
        asm volatile("cp.async.bulk.wait_group 0;" ::: "memory");
      }
      if (lane == 0) mbar_arrive(MB_GF);
      bar_arrive(11, 96);
      if (five) { FINISH0 bar_arrive(13, 192); }
    } else if (role == 18) {
      sts32(MISC_EPOCH, 0);
      sts32(MISC_T0, t0 - c * 4);
      bar_arrive(5, 608);
      uint4* q = lane < 2 ? &p.s->R[c * 2 + lane] : lane < 11 ? &p.s->HS[c * 9 + lane - 2] : lane == 11 ? &p.s->HS[1152 + (c & 7)] : (uint4*)&p.s->FLAG[c * 8];
      if (lane < (c < 8 ? 12 : 11)) str128(q, ~0u, ~0u, ~0u, ~0u);
      const uint32_t ep = __shfl_sync(0xffffffffu, ldr32(q), 31) + 1u;
      sts32(MISC_EPOCH, ep | 0x80000000u);
      TSX(21);
      if (lane == 31) str32(q, ep);
      bar_sync(11, 96);
      TSX(14);
      mbar_wait(MB_KF + (lane & 3) * 8);
      __syncwarp();
      { const uint2 e = lds64(MISC_EM); if (lane < 2) str128(&p.s->SC[c * 2 + lane], e.x, __byte_perm(e.y, ep, 0x6540), 0, 0); }
      TSX(17);
      while ((int)(clock() - t0) < X_SCT) __nanosleep(100);
      TSX(18);
      {
        uint2 v[4];
#pragma unroll 1
        for (int it = 0; it < SPIN_MAX; it++) {
          uint32_t bad = 0;
#pragma unroll
          for (int q = 0; q < 4; q++) v[q] = ldr64(&p.s->SC[lane * 2 + q * 64]);
#pragma unroll
          for (int q = 0; q < 4; q++) bad |= (v[q].y >> 8) ^ (ep & 0xFFFFFFu);
          if (!__any_sync(0xffffffffu, bad)) break;
        }
        TSX(25);
#pragma unroll
        for (int q = 0; q < 4; q++) {
          const uint32_t sa = (lane >> 4) * YT_PITCH + (lane & 15) * 2;
          sts16(sc_addr(2 * q) + sa, v[q].x); sts16(sc_addr(8 + 2 * q) + sa, v[q].x >> 16);
          if (lane & 1) asm volatile("st.shared.u8 [%0], %1;" :: "r"(sc_addr(16) + q * 16 + (lane >> 1)), "r"(v[q].y) : "memory");
        }
      }
      __syncwarp();
      if (lane == 0) mbar_arrive(MB_SC);
      TSX(27);
    } else {
      uint32_t w[9];
      const uint32_t dk = ldnc16(p.dskip + ((lane & 4) ? 512 + (c >> 1) : (lane & 2) * 128 + 2 * c + (lane & 1)));
      float s = 0.f;
#pragma unroll
      for (int i = 0; i < 9; i++) w[i] = ldnc32(p.w_r + lane + 32 * i);
      sts16(OFF_WR + 1152 + lane * 2, dk);
      bar_arrive(5, 608);
#pragma unroll
      for (int i = 0; i < 9; i++) { sts32(OFF_WR + lane * 4 + i * 128, w[i]); s += bf_lo(w[i]) + bf_hi(w[i]); }
      sts32(MISC_SW, __float_as_uint(warp_sum(s)));
      TSX(23);
      bar_sync(10, 576);
      if (lane == 0) {
        const uint32_t tp = clock();
        TSX(1);
        while ((int)(clock() - tp) < X_DELTA || (int)(clock() - t0) < X_ABS - c * 4) {}
        TSX(24);
        load_tile(&tm.m[6], 0, c);
        TSX(15);
        while ((int)(clock() - t0) < X_ABS + X_DSTEP - c * 4) {}
      }
      bar_sync(11, 96);
      if (lane == 0) {
        load_tile(&tm.m[6], 1, 128 + c);
      }
      if (five) {
        mbar_wait(MB_KF);
#pragma unroll 1
        for (int it = 0; it < SPIN_MAX; it++) {
          if (lane == 0) load_tile(&tm.m[8], 2, 512 + (c >> 1));
          mbar_wait(MB_UL + 32, it & 1);
          uint32_t m = 1;
#pragma unroll
          for (int q = 0; q < 4; q++) { uint32_t r0, r1, r2, r3; ldsm4(OFF_W + 512 + lane * 64 + (lane & 6) * 8 + q * 2048, r0, r1, r2, r3); m &= r0 & r1 & r2 & r3; }
          if (__all_sync(0xffffffffu, m || (lane & 3))) break;
        }
        bar_arrive(7, 288);
        FINISH0
        bar_arrive(13, 192);
      }
      bar_sync(0, 544);
      if (lane == 0) mbar_arrive(MB_H);
    }
    return;
  }
  const int wt = tid & 127, g = lane >> 2, t = lane & 3;
  const uint32_t wb = OFF_W + wg * W_BYTES;
  asm volatile("cp.async.commit_group;" ::: "memory");
  const ConvC cv = conv_consts(warp, lane);
  zero_pads(wb, wt);
  load_params<FAR>(p, 254 + 2 * c + wg, wt, wb + W_KT, wg == 2 || (wg == 3 && !five));
  asm volatile("cp.async.commit_group;" ::: "memory");
  asm volatile("setmaxnreg.inc.sync.aligned.u32 112;");
  {
    uint4 kw;
    uint4* kx = &p.s->KX[(c >> 1) * 128 + wt];
    bool two = wg == 3;
    uint32_t ep;
    int em = 0;
    uint32_t slot = wg + (two && !five);
    const uint32_t ra0 = wb + W_KT + (slot & 4) * 512 + wt * 2, ra6 = wb + W_KT + 1536 + (slot & 4) * 512 + (((slot & 4) ? c >> 1 : 2 * c + (wg & 1)) & 7) * 2;
    uint32_t raw[7];
    if (wg != 2) {
      asm volatile("cp.async.wait_group 1;" ::: "memory");
      bar_sync(1 + wg, 128);
#pragma unroll
      for (int i = 0; i < 7; i++) raw[i] = lds16(i < 6 ? ra0 + i * 256 : ra6);
    }
    int phase = wg == 2 ? 3 : 2;
#pragma unroll 1
    for (;;) {
      if (phase != 3) {
        KgState ks;
        TS(22);
        kgen_tables_n(raw, wb, wt, ks);
        TS(20);
        bar_sync(1 + wg, 128);
        em = kgen_tables_m(wb, wt, ks);
        fence_async();
      }
      if (phase & 2) {
        const int lz = lane ^ (clock() & p.off[7]);
        const uint32_t tr_addr = pin(tr_base(lz) + warp * 32), lca = pin(MISC_LN1 + (lz & 1) * 16);
        uint4* dst;
        { const unsigned long long a = (unsigned long long)&p.s->X[c * DM * 2 + warp * 32 + (8 * ((lz >> 1) & 1) + (lz >> 2)) * 2 + (lz & 1)];
          dst = (uint4*)(((unsigned long long)pin(a >> 32) << 32) | pin((uint32_t)a)); }
        if (phase == 3) {
        asm volatile("cp.async.wait_group 1;" ::: "memory");
        TS(21);
        float d[3][4], r;
        uint4 a[9];
#pragma unroll
        for (int k = 0; k < 9; k++) a[k] = lds128(xrow + k * 128);
#pragma unroll
        for (int i = 0; i < 4; i++) d[0][i] = d[1][i] = d[2][i] = 0.f;
#pragma unroll
        for (int k = 0; k < 9; k++) { mma_bf16(d[(2 * k) % 3], a[k].x, ones, a[k].y, ones, a[k].x, a[k].y); mma_bf16(d[(2 * k + 1) % 3], a[k].z, ones, a[k].w, ones, a[k].z, a[k].w); }
#pragma unroll
        for (int i = 0; i < 4; i++) d[0][i] += d[1][i] + d[2][i];
        const LnC lc = ln_consts(d[0][2] + d[0][3], __shfl_sync(0xffffffffu, d[0][0], 9 * t) + __shfl_sync(0xffffffffu, d[0][1], 9 * t + 4), r);
        if (lane < 12) sts16(MISC_LN1 + g * 32 + (warp & 3) * 8 + t * 2, lane < 4 ? lc.m2 : lane < 8 ? lc.rh2 : lc.rl2);
        }
        asm volatile("cp.async.wait_group 0;" ::: "memory");
        TS(23);
        bar_sync(5, 608);
        uint32_t x[3][4];
        ldsm4t(tr_addr, x[0][0], x[0][1], x[0][2], x[0][3]);
        uint4 m = lds128(lca);
        const uint4 rl = lds128(lca + 64), rh = lds128(lca + 32);
        ldsm4t(tr_addr + 512, x[1][0], x[1][1], x[1][2], x[1][3]);
        if (wg == 3) ldsm4t(tr_addr + 640, x[2][0], x[2][1], x[2][2], x[2][3]);
#pragma unroll
        for (int q = 0; q < 3; q++) {
          if (q < 2 || wg == 3) {
            const uint32_t r0 = ln_apply(x[q][0], m.x, rh.x, rl.x), r1 = ln_apply(x[q][1], m.y, rh.y, rl.y), r2 = ln_apply(x[q][2], m.z, rh.z, rl.z), r3 = ln_apply(x[q][3], m.w, rh.w, rl.w);
            const uint32_t w0 = (pack_h(bf_lo(r0), bf_hi(r0)) & 0xFFFEFFFEu) | 1u, w1 = pack_h(bf_lo(r1), bf_hi(r1)), w2 = pack_h(bf_lo(r2), bf_hi(r2)), w3 = pack_h(bf_lo(r3), bf_hi(r3));
            if (q == 0) str128(dst, w0, w1, w2, w3);
            else sts128(OFF_G + warp * 512 + (8 * (t >> 1) + g) * 32 + (t & 1) * 16 + (q == 2 ? 2048 : 0), w0, w1, w2, w3);
          }
          if (q == 0) {
            const uint32_t z = clock() & p.off[7];
            m.x ^= z; m.y ^= z; m.z ^= z; m.w ^= z;
          }
          if (q == 0) TS(30);
          if (q == 0 && wg >= 2) {
#pragma unroll
            for (int i = 0; i < 7; i++) raw[i] = lds16(wb + W_KT + i * 256 + (i < 6 ? wt : (2 * c + (wg & 1)) & 7) * 2);
          }
        }
        bar_arrive(10, 576);
        TS(1);
      } else bar_sync(1 + wg, 128);
      phase &= 1;
      if (phase) { phase = 0; continue; }
      TS(14);
      float acc[20];
      const uint32_t alo = (wb >> 4) | (8u << 16);
      uint4 k4 = lds128(wb + W_MISC + 16);
      uint32_t dk = lds16(OFF_WR + 1152 + slot * 2);
      wg_fence();
      wgmma40_ss_init(acc, alo, alo + 1024, 2048 >> 4);
#pragma unroll
      for (int k = 1; k < 8; k++) wgmma40_ss(acc, alo + k * 16, alo + 1024 + k * 16, 2048 >> 4);
      wg_commit();
      { const uint32_t z = clock() & p.off[7]; dk ^= z; k4.x ^= z; k4.z ^= z; }
      const float k2048 = (float)(int)((k4.x + k4.y) + (k4.z + k4.w)) * (1.f / 262144.f);
      const int ef = max(em, min((int)((dk >> 7) & 255u) - 7, 238));
      asm volatile("st.shared.u8 [%0], %1;" :: "r"(MISC_EM + slot), "r"(ef + 9) : "memory");
      const float un = __uint_as_float((uint32_t)max(114 + em - ef, 0) << 23), d0 = wt ? 0.f : bf_lo(dk) * __uint_as_float((uint32_t)(245 - ef) << 23);
      wg_wait<0>();
      kw.x = pack_h(fmaf(acc[0] - acc[3], un, d0), (acc[4] - acc[7]) * un);
      kw.y = pack_h((acc[8] - acc[11]) * un, (acc[12] - acc[15]) * un);
      kw.z = pack_h((acc[16] - acc[19]) * un, k2048 * un);
      TS(24);
      ep = 0;
      if (two) SPIN_WHILE(ep == 0, ep = lds32(MISC_EPOCH));
      if (five || !two) break;
      str128(kx, kw.x, kw.y, kw.z, ep);
      two = false;
      slot = 3;
      bar_sync(1 + wg, 128);
    }
    if (lane == 0) mbar_arrive(MB_KF + wg * 8);
    if (two) { mbar_wait(MB_KF); zero_pads(OFF_W + ALT, wt); }
    uint32_t tb = wb;
#pragma unroll 1
    for (;;) {
      kgen_build(tb, wg, wt, kw.x, kw.y, kw.z);
      TS(15);
      if (!two) break;
      two = false;
      kw.w = 0;
      SPIN_WHILE(kw.w != ep, kw = ldr128(kx));
      tb = OFF_W + ALT;
    }
    fence_async();
    TS(31);
    if (tb != wb) bar_arrive(7, 288);
    bar_sync(1 + wg, 128);
  }
  uint32_t tpub;
  ConvPre pre;
  conv_pre(pre, (wb ^ p.off[7]) + (cv.ca & 0xFFFFu), (wb ^ p.off[7]) + cv.qa, 3, true, warp & 2);
#pragma unroll 1
  for (int item = 0;; item++) {
    TS(2);
    conv_item(item ? OFF_W + ALT : wb, item ? OFF_W : OFF_T + (wg >> 1) * TILE, item ? 1 : 13 + (wg >> 1), item ? 128 : five && wg == 1 ? 192 : 256, pre, cv, p.off[7],
              &tm.m[item ? 9 : 7], item ? 512 + (c >> 1) : (wg >> 1) * 128 + c, warp, lane, five && wg >= X_GW, five && !wg && !item);
    tpub = clock() - (item ? X_YD : wg >= 2 ? X_YD2 : 0);
    if (wg || !five || item) break;
    TS(27);
  }
  TS(4);

  const int ln = lane ^ p.off[7], td = warp * 32 + ln, gg = ln >> 2, tt = ln & 3;
  const int tok = c * 16 + warp;
  const int fu = warp / 3, fk = warp - fu * 3;
  uint32_t wa[12][4];
  uint4 ha[3];
  const uint4* hsrc = &p.s->HS[td + (td / 24) * 48];
  {
    uint32_t hw[9], wr[9];
    const uint32_t row = keep(OFF_YT + warp * YT_PITCH + (warp >> 3) * 64 + ln * 16);
    const uint32_t wabase = keep(((ln & 8) ? OFF_W + (fk + 1) * W_BYTES : OFF_G + fk * 192 * pitch) + ((ln >> 4) * 8 + (ln & 7)) * pitch
                                 + (five ? ((fu ^ (ln >> 1)) & 3) : min(fu, 4)) * 16);
    float sw;
    {
      const bool three = wg == 1;
      const int ch = 8 * (tt >> 1) + gg;
      const uint32_t tr_addr = tr_base(ln);
      const uint4* ysrc = &p.s->X[c * DM * 2 + ch * 2 + (tt & 1)];
      uint32_t x[3][4], s[3];
      uint4 v[3];
#define TL(q) ((q) < 2 ? 2 * warp + (q) : 28 + warp)
      if (wg >= 2) { const uint32_t ts = lds32(MISC_T0); while ((int)(clock() - ts) < X_XS) {} }
      while ((int)(clock() - tpub) < X_YD) {}
      TS(5);
      v[0] = ldr128(ysrc + TL(0) * 32); v[1] = ldr128(ysrc + TL(1) * 32); v[2] = make_uint4(three, 0, 0, 0);
      mbar_wait(MB_REL);
#pragma unroll
      for (int i = 0; i < 6; i++) if (i < 4 || three) wr[i] = (gg & 2) ? ones : lds32(OFF_WR + TL(i >> 1) * 32 + (i & 1) * 16 + tt * 4);
      const uint32_t ha = keep(OFF_YT + (ln & 7) * YT_PITCH + (ln >> 4) * (8 * YT_PITCH + 64) + (ln & 8) * 2);
      const uint32_t pa = keep(OFF_PART + warp * 4 + ((gg & 2) * 8 + (gg & 4) * 2 + 2 * tt + (gg & 1)) * 80), pb = keep(OFF_PART + 2560 + warp * 4 + gg * 80);
      float dl[4] = {0.f, 0.f, 0.f, 0.f}, dh[4] = {0.f, 0.f, 0.f, 0.f};
      sw = __uint_as_float(lds32(MISC_SW));
#pragma unroll
      for (int q = 0; q < 3; q++) {
        if (q < 2 || three) {
          ldsm4t(tr_addr + TL(q) * 32, x[q][0], x[q][1], x[q][2], x[q][3]);
        }
      }
      asm volatile("cp.async.bulk.wait_group.read 0;" ::: "memory");
      mbar_wait(MB_SC);
#pragma unroll
      for (int q = 0; q < 3; q++) {
        asm volatile("ld.shared.u8 %0, [%1];" : "=r"(s[q]) : "r"((q < 2 ? sc_addr(warp) + q * 16 : sc_addr(16) + (warp & 3) * 16) + ch) : "memory");
        s[q] = keep(s[q] * 0x800080u);
      }
#define FIN(q) stsm4t(tr_addr + TL(q) * 32, bf_fma2(h2bf(v[q].x), s[q], x[q][0]), bf_fma2(h2bf(v[q].y), s[q], x[q][1]), bf_fma2(h2bf(v[q].z), s[q], x[q][2]), bf_fma2(h2bf(v[q].w), s[q], x[q][3]));
      SPIN_WHILE((v[0].x | v[1].x) & 1u, _Pragma("unroll") for (int q = 0; q < 3; q++) if (v[q].x & 1u) v[q] = ldr128(ysrc + TL(q) * 32));
      if (v[2].x & 1u) v[2] = ldr128(ysrc + TL(2) * 32);
#define STAT(q) { uint32_t r0, r1, r2, r3; ldsm4(ha + TL(q) * 32, r0, r1, r2, r3); \
        mma_bf16(dl, r0, wr[2 * q], r1, wr[2 * q + 1], r0, r1); mma_bf16(dh, r2, wr[2 * q], r3, wr[2 * q + 1], r2, r3); }
      FIN(0) FIN(1)
      __syncwarp();
      STAT(0) STAT(1)
      if (three) {
#pragma unroll 1
        for (int it = 0; it < SPIN_MAX; it++) {
          FIN(2)
          if (!__any_sync(0xffffffffu, v[2].x & 1u)) break;
          if (v[2].x & 1u) v[2] = ldr128(ysrc + TL(2) * 32);
        }
        __syncwarp();
        STAT(2)
      }
      if (gg & 1) { dl[0] = dl[1]; dl[2] = dl[3]; dh[0] = dh[1]; dh[2] = dh[3]; }
      sts32(pa, __float_as_uint((gg & 4) ? dh[2] : dl[2]));
      if (tt == (gg >> 1)) { sts32(pb, __float_as_uint(dl[0])); sts32(pb + 640, __float_as_uint(dh[0])); }
#undef STAT
#undef FIN
#undef TL
    }
    uint32_t ra = keep(OFF_PART + (ln & 15) * 80 + (ln & 16) * 2);
    uint16_t* rp = (uint16_t*)p.s->R + c * 16 + (ln & 15);
    const uint2* rsrc = (const uint2*)p.s->R + td;
    asm volatile("" : "+l"(rp), "+l"(rsrc), "+l"(hsrc));
    uint2 rv = make_uint2(0u, 0u);
    TS(28);
    if (warp != X_PW) bar_sync(0, 544);
    else {
      float z[3], rd;
      asm volatile("bar.sync 0, 544;" : "+r"(ra) :: "memory");
#pragma unroll
      for (int k = 2; k >= 0; k--) {
        const uint4 a = lds128(ra + k * 1280), b = lds128(ra + k * 1280 + 16);
        z[k] = ((__uint_as_float(a.x) + __uint_as_float(a.y)) + (__uint_as_float(a.z) + __uint_as_float(a.w))) + ((__uint_as_float(b.x) + __uint_as_float(b.y)) + (__uint_as_float(b.z) + __uint_as_float(b.w)));
      }
#pragma unroll
      for (int k = 2; k >= 0; k--) z[k] += __shfl_xor_sync(0xffffffffu, z[k], 16);
      const LnC l = ln_consts(z[1], z[2], rd);
      const uint32_t b = pack_bf(0.f, fmaf(-bf_lo(l.m2), sw, z[0]) * rd);
      const uint32_t k16 = max(min((b ^ (((int)b >> 31) | 0x80000000u)) >> 16, 0xFFFEu), 1u);
      if (ln < 16) str16(rp, k16);
      sts64(OFF_RK + (ln & 15) * 8, __byte_perm(l.m2, l.rh2, 0x5410), __byte_perm(l.rl2, k16, 0x5410));
      sts128(MISC_CNT + ln * 16, 0, 0, 0, 0);
    }
    mbar_wait(MB_GU);
#define LD_HW { const uint4 a = lds128(row), b = lds128(row + 512); hw[8] = lds32(row + 1024 - ln * 12); \
      hw[0] = a.x; hw[1] = a.y; hw[2] = a.z; hw[3] = a.w; hw[4] = b.x; hw[5] = b.y; hw[6] = b.z; hw[7] = b.w; }
    LD_HW
    const uint32_t tr0 = clock();
    bar_sync(5, 512);
    TS(7);
    const uint2 lk = lds64(OFF_RK + warp * 8);
    LnC l2;
    l2.m2 = __byte_perm(lk.x, 0, 0x1010); l2.rh2 = __byte_perm(lk.x, 0, 0x3232); l2.rl2 = __byte_perm(lk.y, 0, 0x1010);
    const uint32_t key = (lk.y & 0xFFFF0000u) | (2047 - tok);
    uint32_t loc = ln < 16 ? (lds32(OFF_RK + 4 + ln * 8) & 0xFFFF0000u) | (2047 - c * 16 - ln) : 0u;
    int rank = __popc(__ballot_sync(0xffffffffu, loc > key));
#pragma unroll
    for (int i = 0; i < 9; i++) { wr[i] = keep(ln_apply(hw[i], l2.m2, l2.rh2, l2.rl2)); hw[i] = bf_add2(hw[i], wr[i]); }
#define OUT_ROW { uint32_t* o = p.out + tok * 288 + ln * 4; \
      *(uint4*)o = make_uint4(hw[0], hw[1], hw[2], hw[3]); *(uint4*)(o + 128) = make_uint4(hw[4], hw[5], hw[6], hw[7]); o[256 - ln * 3] = hw[8]; }
    uint4* hs = p.s->HS + ln;
    asm volatile("" : "+l"(hs));
#pragma unroll 1
    for (int base = 0; base < 8; base += 2) {
      uint32_t T[2];
#pragma unroll
      for (int j = 0; j < 2; j++) {
        const uint32_t mx = __reduce_max_sync(0xffffffffu, loc);
        if (loc == mx) loc = 0;
        T[j] = (td >> 2) < c ? (mx & 0xFFFF0000u) - 1u : mx | 0xFFFFu;
      }
      const uint32_t sh = keep(rank == base ? 0x4410u : rank == base + 1 ? 0x4432u : 0x4445u), ca = keep(MISC_CNT + base * 64 + ln * 4);
      TS(29);
      if (base == 0) {
        while ((int)(clock() - tr0) < X_RD) {}
        if ((td >> 2) != c) rv = ldr64(rsrc);
        if (rank >= X_OR) OUT_ROW
        if (warp < (five ? 12 : 15)) {
#pragma unroll
          for (int k = 0; k < X_WS; k++) ldsm4t(wabase + k * 16 * pitch, wa[k][0], wa[k][1], wa[k][2], wa[k][3]);
        }
      }
      uint32_t cnt;
#pragma unroll 1
      for (int it = 0; it < SPIN_MAX; it++) {
        const uint32_t xs = rv.x << 16, ys = rv.y << 16;
        const bool bad = max(max(rv.x, xs), max(rv.y, ys)) >= 0xFFFF0000u;
        uint32_t cn2 = 0;
        cnt = bad ? 256u : 0u;
#pragma unroll
        for (int j = 0; j < 2; j++)
          asm("{ .reg .pred a, b, c, d; setp.gt.u32 a, %2, %6; setp.gt.u32 b, %3, %6; setp.gt.u32 c, %4, %6; setp.gt.u32 d, %5, %6; "
              "@a add.u32 %1, %1, %7; @b add.u32 %1, %1, %7; @c add.u32 %0, %0, %7; @d add.u32 %0, %0, %7; }"
              : "+r"(cnt), "+r"(cn2) : "r"(rv.x), "r"(rv.y), "r"(xs), "r"(ys), "r"(T[j]), "r"(1u << (16 * j)));
        cnt = __reduce_add_sync(0xffffffffu, cnt + cn2);
        asm volatile("{ .reg .pred q; setp.eq.u32 q, %2, 0; @q red.shared.add.u32 [%0], %1; }" :: "r"(ca), "r"(cnt), "r"(cnt & 0x3F00u) : "memory");
        if (!(cnt & 0x3F00u)) break;
        if (bad) rv = ldr64(rsrc);
      }
      TS(16);
      bar_sync(0, 512);
      cnt = lds32(ca);
      if (base == 0) tpub = clock();
      const int gr = rank + __byte_perm(cnt, 0x800u, sh);
      if (gr < 8) {
        uint4* ks = hs + 1152 + gr;
        hs = (uint4*)((char*)hs + gr * 1152);
        asm volatile("{ .reg .b128 t, u; .reg .b64 a, b, c, d; mov.b64 a, {%1,%2}; mov.b64 b, {%3,%4}; mov.b64 c, {%5,%6}; mov.b64 d, {%7,%8}; mov.b128 t, {a, b}; mov.b128 u, {c, d}; "
                     "st.relaxed.gpu.global.b128 [%0], t; st.relaxed.gpu.global.b128 [%0 + 512], u; }"
                     :: "l"(hs), "r"(wr[0]), "r"(wr[1]), "r"(wr[2]), "r"(wr[3]), "r"(wr[4]), "r"(wr[5]), "r"(wr[6]), "r"(wr[7]) : "memory");
        str32((uint32_t*)(hs + 64) - ln * 3, wr[8]);
        LD_HW
        str128(hs + 576, hw[0], hw[1], hw[2], hw[3]); str128(hs + 608, hw[4], hw[5], hw[6], hw[7]); str32((uint32_t*)(hs + 640) - ln * 3, hw[8]);
        if (ln == 0) str32(ks, key);
        rank = 16;
      }
      if (__all_sync(0xffffffffu, (int)(cnt >> 16) + base + 2 >= 8)) break;
    }
    TS(8);
    if (warp < (five ? 12 : 15)) {
#pragma unroll
      for (int k = X_WS; k < 12; k++) ldsm4t(wabase + k * 16 * pitch, wa[k][0], wa[k][1], wa[k][2], wa[k][3]);
    }
    if (warp < 6) while ((int)(clock() - tpub) < X_HD) {}
    TS(19);
    if (warp < 6) { ha[0] = ldr128(hsrc); ha[1] = ldr128(hsrc + 24); ha[2] = ldr128(hsrc + 48); }
    if (rank < X_OR) OUT_ROW
  }
  uint32_t wd[10][4];
  const uint32_t xb = keep(OFF_XS + (ln & 7) * 1168 + (fk * 24 + (ln >> 3)) * 16);
  if (warp >= 7) {
    const uint32_t db = down_box(warp - 7, five) + (ln & 7) * 128;
    mbar_wait(MB_D);
#pragma unroll
    for (int j = 0; j < 4; j++) {
      const uint32_t a = db + (ln >> 4) * 1024 + (((2 * j + ((ln >> 3) & 1)) ^ (ln & 7)) << 4);
      ldsm4t(a, wd[j][0], wd[j][1], wd[j][2], wd[j][3]);
      ldsm4t(a + 2048, wd[4 + j][0], wd[4 + j][1], wd[4 + j][2], wd[4 + j][3]);
    }
#pragma unroll
    for (int j = 0; j < 2; j++) ldsm4t(db + 4096 + (((4 * j + (ln >> 3)) ^ (ln & 7)) << 4), wd[8 + j][0], wd[8 + j][1], wd[8 + j][2], wd[8 + j][3]);
  } else if (warp < 6) {
    const uint32_t xs = keep(OFF_XS + (td + (td / 24) * 49) * 16);
#pragma unroll 1
    for (int it = 0; it < SPIN_MAX; it++) {
      const bool bad = max(max(max(ha[0].x, ha[1].x), max(ha[2].x, ha[2].y)), max(ha[2].z, ha[2].w)) == ~0u;
#pragma unroll
      for (int q = 0; q < 3; q++) sts128(xs + q * 384, ha[q].x, ha[q].y, ha[q].z, ha[q].w);
      if (!__any_sync(0xffffffffu, bad)) break;
      if (bad) { ha[0] = ldr128(hsrc); ha[1] = ldr128(hsrc + 24); ha[2] = ldr128(hsrc + 48); }
    }
  }
  TS(9);

  bar_sync(0, 512);
  if (warp < (five ? 12 : 15)) {
    float d0[4] = {0.f, 0.f, 0.f, 0.f}, d1[4] = {0.f, 0.f, 0.f, 0.f};
#pragma unroll
    for (int k = 0; k < 12; k += 2) {
      uint32_t b0, b1, b2, b3;
      ldsm4(xb + k * 32, b0, b1, b2, b3);
      mma_bf16(d0, wa[k][0], wa[k][1], wa[k][2], wa[k][3], b0, b1);
      mma_bf16(d1, wa[k + 1][0], wa[k + 1][1], wa[k + 1][2], wa[k + 1][3], b2, b3);
    }
    sts128(OFF_RED + td * 16, __float_as_uint(d0[0] + d1[0]), __float_as_uint(d0[1] + d1[1]), __float_as_uint(d0[2] + d1[2]), __float_as_uint(d0[3] + d1[3]));
  }
  TS(26);
  if (warp < 5) {
    const uint32_t rb = OFF_RED + warp * 1536 + ln * 16;
    bar_sync(9, 512);
    const uint4 pa = lds128(rb), pb = lds128(rb + 512), pc = lds128(rb + 1024);
    const float ga = bfr(__uint_as_float(pa.x) + __uint_as_float(pb.x) + __uint_as_float(pc.x));
    const float gb = bfr(__uint_as_float(pa.y) + __uint_as_float(pb.y) + __uint_as_float(pc.y));
    const uint32_t uu = pack_bf(__uint_as_float(pa.z) + __uint_as_float(pb.z) + __uint_as_float(pc.z), __uint_as_float(pa.w) + __uint_as_float(pb.w) + __uint_as_float(pc.w));
    float ra, rb2;
    asm("rcp.approx.ftz.f32 %0, %1;" : "=f"(ra) : "f"(1.f + ex2(ga * -1.4426950408889634f)));
    asm("rcp.approx.ftz.f32 %0, %1;" : "=f"(rb2) : "f"(1.f + ex2(gb * -1.4426950408889634f)));
    const uint32_t act = bf_mul2(pack_bf(ga * ra, gb * rb2), uu);
    sts32(OFF_ACT + td * 4, act);
  } else bar_arrive(9, 512);
  uint4* dst = &p.s->X[c * DM * 2 + (warp - 7) * 64 + tt * 8 + gg];
  asm volatile("" : "+l"(dst));
  bar_sync(8, 512);
  tpub = clock();
  if (warp >= 7) {
    uint32_t b0, b1, b2, b3, b4;
    ldsm4t(OFF_ACT + ln * 16, b0, b1, b2, b3);
    asm volatile("ldmatrix.sync.aligned.m8n8.x1.trans.shared.b16 {%0}, [%1];" : "=r"(b4) : "r"(OFF_ACT + 512 + ln * 16) : "memory");
    float y[4][4];
#pragma unroll
    for (int j = 0; j < 4; j++) {
      y[j][0] = y[j][1] = y[j][2] = y[j][3] = 0.f;
      mma_bf16(y[j], wd[j][0], wd[j][1], wd[j][2], wd[j][3], b0, b1);
    }
#pragma unroll
    for (int j = 0; j < 4; j++) mma_bf16(y[j], wd[4 + j][0], wd[4 + j][1], wd[4 + j][2], wd[4 + j][3], b2, b3);
    if (!five) {
#pragma unroll
      for (int j = 0; j < 4; j++) mma_bf16_k8(y[j], wd[8 + (j >> 1)][2 * (j & 1)], wd[8 + (j >> 1)][2 * (j & 1) + 1], b4);
    }
    str128(dst, (pack_bf(y[0][0], y[0][1]) & ~1u) | 0x10000u, pack_bf(y[0][2], y[0][3]), pack_bf(y[1][0], y[1][1]), pack_bf(y[1][2], y[1][3]));
    str128(dst + 32, (pack_bf(y[2][0], y[2][1]) & ~1u) | 0x10000u, pack_bf(y[2][2], y[2][3]), pack_bf(y[3][0], y[3][1]), pack_bf(y[3][2], y[3][3]));
  }
  TS(10);

  if (c < 72) {
    const uint4* src = &p.s->X[(warp * 4 + tt) * (DM * 2) + c * 8 + gg];
    const int slot = (c & 3) * 2 + (ln >> 4), dw = (c >> 2) * 16 + (ln & 15);
    uint32_t hv = 0, kv = 0, res = 0, rs2 = 0;
    uint32_t* o = p.out;
    if (warp == 0) {
      hv = ~0u;
      SPIN_WHILE(max(hv, kv) == ~0u, hv = ldr32((const uint32_t*)p.s->HS + 2304 + slot * 288 + dw); kv = ldr32(&p.s->HS[1152 + slot]));
      const float r = bf_hi(kv ^ (((int)~kv >> 31) | 0x80000000u));
      float rs;
      asm("rcp.approx.ftz.f32 %0, %1;" : "=f"(rs) : "f"(1.f + ex2(r * -1.4426950408889634f)));
      rs2 = keep(pack_bf(rs, rs));
      res = lds32(OFF_XS + slot * 1168 + dw * 4);
      o += (2047 - (int)(kv & 2047u)) * 288 + dw;
      asm volatile("" : "+l"(o));
    }
    const uint32_t sel = (gg & 1) ? 0x3F800000u : 0x00003F80u;
    const uint32_t q0 = keep((gg >> 1) == 0 ? sel : 0u), q1 = keep((gg >> 1) == 1 ? sel : 0u), q2 = keep((gg >> 1) == 2 ? sel : 0u), q3 = keep((gg >> 1) == 3 ? sel : 0u);
    const uint32_t fa = keep(OFF_RED + warp * 8 + ((gg & 1) * 16 + (gg >> 1) * 4 + tt) * 144), fb = keep(OFF_RED + ln * 144);
    uint4 a0 = make_uint4(0, 0, 0, 0), a1 = a0;
    while ((int)(clock() - tpub) < X_PD) {}
    SPIN_WHILE(!(a0.x & a1.x & 0x10000u), if (!(a0.x & 0x10000u)) a0 = ldr128(src); if (!(a1.x & 0x10000u)) a1 = ldr128(src + 64 * DM * 2));
    float d[4] = {0.f, 0.f, 0.f, 0.f}, e[4] = {0.f, 0.f, 0.f, 0.f}, d2[4] = {0.f, 0.f, 0.f, 0.f}, e2[4] = {0.f, 0.f, 0.f, 0.f};
    mma_bf16(d, q0, q2, q1, q3, a0.x, a0.y); mma_bf16(e, q0, q2, q1, q3, a0.z, a0.w);
    mma_bf16(d2, q0, q2, q1, q3, a1.x, a1.y); mma_bf16(e2, q0, q2, q1, q3, a1.z, a1.w);
    sts64(fa, __float_as_uint(d[0] + e[2] + d2[0] + e2[2]), __float_as_uint(d[1] + e[3] + d2[1] + e2[3]));
    TS(11);
    if (warp == 0) {
      bar_sync(0, 512);
      float2 s[16];
#pragma unroll
      for (int i = 0; i < 16; i += 2) { const uint4 q = lds128(fb + i * 8); s[i] = make_float2(__uint_as_float(q.x), __uint_as_float(q.y)); s[i + 1] = make_float2(__uint_as_float(q.z), __uint_as_float(q.w)); }
#pragma unroll
      for (int k = 1; k < 16; k *= 2)
#pragma unroll
        for (int i = 0; i < 16; i += 2 * k) { s[i].x += s[i + k].x; s[i].y += s[i + k].y; }
      asm volatile("st.global.b32 [%0], %1;" :: "l"(o), "r"(bf_add2(hv, bf_add2(res, bf_mul2(pack_bf(s[0].x, s[0].y), rs2)))) : "memory");
    } else bar_arrive(0, 512);
  }
  TS(12);
  TS_DUMP();
}

typedef CUresult (*EncodeFn)(CUtensorMap*, CUtensorMapDataType, cuuint32_t, void*, const cuuint64_t*, const cuuint64_t*, const cuuint32_t*,
                             const cuuint32_t*, CUtensorMapInterleave, CUtensorMapSwizzle, CUtensorMapL2promotion, CUtensorMapFloatOOBfill);

}

extern "C" void kernel_launch(void* const* d_in, const int* in_sizes, int n_in, void* d_out, int out_size) {
  (void)in_sizes; (void)n_in; (void)out_size;
  static EncodeFn enc = nullptr;
  static Scratch* scratch = nullptr;
  if (!enc) {
    void* fn = nullptr;
    cudaDriverEntryPointQueryResult qr;
    cudaGetDriverEntryPoint("cuTensorMapEncodeTiled", &fn, cudaEnableDefault, &qr);
    enc = (EncodeFn)fn;
    cudaGetSymbolAddress((void**)&scratch, g_S);
    cudaFuncSetAttribute(fused_kernel<false>, cudaFuncAttributeMaxDynamicSharedMemorySize, SMEM_BYTES);
    cudaFuncSetAttribute(fused_kernel<true>, cudaFuncAttributeMaxDynamicSharedMemorySize, SMEM_BYTES);
  }
  TMaps tm;
  for (int i = 0; i < 6; i++) {
    const bool dn = i % 3 == 2;
    const cuuint32_t w = i < 3 ? 40 : 32;
    cuuint64_t gd[3] = {(cuuint64_t)(dn ? 64 : FF), (cuuint64_t)(dn ? FF : DM), 9};
    cuuint64_t gs[2] = {(cuuint64_t)(dn ? DM * 2 : FF * 2), 128};
    cuuint32_t bx[3] = {dn ? 64 : w, dn ? w : 96, i < 3 ? 2u : 3u};
    cuuint32_t es[3] = {1, 1, 1};
    enc(&tm.m[i], CU_TENSOR_MAP_DATA_TYPE_BFLOAT16, dn ? 3 : 2, d_in[11 + i % 3], gd, gs, bx, es, CU_TENSOR_MAP_INTERLEAVE_NONE,
        dn ? CU_TENSOR_MAP_SWIZZLE_128B : i < 3 ? CU_TENSOR_MAP_SWIZZLE_NONE : CU_TENSOR_MAP_SWIZZLE_64B,
        (CUtensorMapL2promotion)X_PROMO, CU_TENSOR_MAP_FLOAT_OOB_FILL_NONE);
  }
  for (int i = 6; i < 10; i++) {
    cuuint64_t gd[3] = {i < 8 ? 32u : 16u, i < 8 ? DM / 2u : DM, NCTA};
    cuuint64_t gs[2] = {i < 8 ? 64u : 32u, DM * 32};
    cuuint32_t bx[3] = {32, 1, (i & 1) ? 128u : 136u};
    cuuint32_t es[3] = {1, 1, 1};
    enc(&tm.m[i], CU_TENSOR_MAP_DATA_TYPE_FLOAT16, 3, scratch->X, gd, gs, bx, es, CU_TENSOR_MAP_INTERLEAVE_NONE, CU_TENSOR_MAP_SWIZZLE_64B,
        CU_TENSOR_MAP_L2_PROMOTION_NONE, CU_TENSOR_MAP_FLOAT_OOB_FILL_NONE);
  }
  Params p;
  p.x = (const unsigned char*)d_in[0];
  bool far = false;
  for (int i = 0; i < 7; i++) {
    p.far[i] = (const unsigned char*)d_in[1 + i];
    const long long d = (long long)((intptr_t)d_in[1 + i] - (intptr_t)d_in[0]);
    p.off[i] = (int)(d / 16);
    if ((long long)p.off[i] * 16 != d || p.off[i] > (1 << 30)) far = true;
  }
  p.dskip = (const uint16_t*)d_in[8];
  p.w_r = (const uint32_t*)d_in[10];
  for (int f = 0; f < 2; f++) {
    static const int kind[17] = {0, 0, 0, 0, 2, 2, 0, 0, 1, 1, 1, 1, 1, 1, 2, 2, 2};
    static const int idx[2][17] = {{2, 3, 4, 5, 6, 8, 0, 1, 0, 1, 2, 3, 4, 5, 0, 2, 4}, {2, 3, 4, 5, 0, -1, 0, 1, 0, 1, 2, 3, 4, 5, 3, -1, 6}};
    static const int blk[2][17] = {{-1, -1, -1, -1, 0, -1, 4, -1, 1, -1, 2, -1, 3, -1, 16, -1, -1}, {-1, -1, -1, -1, 1, -1, 4, -1, -1, -1, 2, -1, 3, -1, 16, -1, -1}};
    const int pitch = f ? 64 : 80;
    for (int u = 0; u < 17; u++) {
      const int s = idx[f][u];
      const uint32_t dst = kind[u] == 0 ? OFF_G + s * 96 * pitch : kind[u] == 2 ? down_box(s, f) : OFF_W + W_BYTES + (s >> 1) * W_BYTES + (s & 1) * 96 * pitch;
      const uint32_t mb = u >= 14 ? (u >= X_HU ? MB_H - OFF_MISC : 0) : blk[f][u] >= 0 ? MB_KF - OFF_MISC + blk[f][u] * 8 : 0;
      p.sched[f][u] = s < 0 ? 3u : kind[u] | s << 2 | mb << 6 | dst << 14;
    }
  }
  p.out = (uint32_t*)d_out;
  p.off[7] = 0;
  p.ts = nullptr;
  p.s = scratch;
  if (far) { fused_kernel<true><<<NCTA, NT, SMEM_BYTES, cudaStreamPerThread>>>(p, tm); return; }
  fused_kernel<false><<<NCTA, NT, SMEM_BYTES, cudaStreamPerThread>>>(p, tm);
}
```

```cpp
#include <cuda_runtime.h>
#include <cuda.h>
#include <cuda_bf16.h>
#include <cuda_fp16.h>
#include <stdint.h>
#include <stddef.h>

namespace {

constexpr int NCTA = 128;
constexpr int NT = 640;
constexpr int DM = 576;
constexpr int FF = 4608;
constexpr int SPIN_MAX = 1 << 20;

struct Scratch {
  uint4 X[NCTA * DM * 2];
  uint4 KX[64 * 128];
  uint4 HS[1152 + 8];
  uint4 R[256];
  uint4 SC[256];
  uint32_t FLAG[NCTA * 8];
};
__device__ Scratch g_S;

#define CLKS(i)
#define TS(i)
#define TSX(i)
#define TS_DUMP()

constexpr int SB = 1024;
constexpr int BOX = 15360;
constexpr int OFF_G = SB;
constexpr int OFF_W = OFF_G + 3 * BOX;
constexpr int W_KT = 26624;
constexpr int W_QT = W_KT + 64 + 2048 + 80;
constexpr int W_L3 = W_KT + 4352;
constexpr int W_CW = W_L3 + 4160;
constexpr int W_MISC = W_CW + 640;
constexpr int W_BYTES = 35840;
constexpr int TILE = 10240;
constexpr int OFF_T = OFF_W + 4 * W_BYTES;
constexpr int ALT = TILE - W_KT;
static_assert(W_MISC + 32 <= W_BYTES && OFF_W % 1024 == 0 && W_BYTES % 1024 == 0 && W_BYTES + ALT <= 20480, "wg block");
constexpr int YT_PITCH = 1184;
constexpr int OFF_YT = OFF_T + 2 * TILE;
constexpr int OFF_WR = OFF_YT + 16 * YT_PITCH + 64;
constexpr int OFF_MISC = OFF_WR + 2304;
constexpr int SMEM_BYTES = OFF_MISC + 1024 - SB;
static_assert(OFF_YT % 16 == 0 && OFF_MISC % 16 == 0, "align");
static_assert(SMEM_BYTES <= 232448, "smem");
constexpr int MB_GU = OFF_MISC;
constexpr int MB_D = OFF_MISC + 8;
constexpr int MB_KF = OFF_MISC + 16;
constexpr int MB_GF = OFF_MISC + 48;
constexpr int MB_SC = OFF_MISC + 56;
constexpr int MB_UL = OFF_MISC + 64;
constexpr int MB_REL = OFF_MISC + 104;
constexpr int MB_GO = OFF_MISC + 112;
constexpr int MB_H = MB_KF + 128;
constexpr int MISC_EPOCH = OFF_MISC + 152;
constexpr int MISC_SW = OFF_MISC + 156;
constexpr int MISC_RT = OFF_MISC + 160;
constexpr int MISC_T0 = OFF_MISC + 296;
constexpr int MISC_EM = OFF_MISC + 288;
constexpr int OFF_PART = OFF_W + 20480;
constexpr int OFF_RK = OFF_PART + 3840;
constexpr int MISC_LN1 = OFF_MISC + 192;
constexpr int OFF_XS = OFF_T;
constexpr int OFF_RED = OFF_T + TILE;
constexpr int OFF_FIN = OFF_W + 3 * W_BYTES + W_KT;
constexpr int OFF_ACT = OFF_FIN + 4096;
constexpr int MISC_CNT = OFF_ACT + 1024;

__device__ __forceinline__ uint32_t smem_u32(const void* p) { return (uint32_t)__cvta_generic_to_shared(p); }
__device__ __forceinline__ uint32_t lds32(uint32_t a) { uint32_t v; asm volatile("ld.shared.b32 %0, [%1];" : "=r"(v) : "r"(a) : "memory"); return v; }
__device__ __forceinline__ uint32_t lds16(uint32_t a) { uint16_t v; asm volatile("ld.shared.u16 %0, [%1];" : "=h"(v) : "r"(a) : "memory"); return v; }
__device__ __forceinline__ uint2 lds64(uint32_t a) { uint2 v; asm volatile("ld.shared.v2.b32 {%0,%1}, [%2];" : "=r"(v.x), "=r"(v.y) : "r"(a) : "memory"); return v; }
__device__ __forceinline__ uint4 lds128(uint32_t a) { uint4 v; asm volatile("ld.shared.v4.b32 {%0,%1,%2,%3}, [%4];" : "=r"(v.x), "=r"(v.y), "=r"(v.z), "=r"(v.w) : "r"(a) : "memory"); return v; }
__device__ __forceinline__ void sts16(uint32_t a, uint32_t v) { asm volatile("st.shared.u16 [%0], %1;" :: "r"(a), "h"((uint16_t)v) : "memory"); }
__device__ __forceinline__ void sts32(uint32_t a, uint32_t v) { asm volatile("st.shared.b32 [%0], %1;" :: "r"(a), "r"(v) : "memory"); }
__device__ __forceinline__ void sts64(uint32_t a, uint32_t x, uint32_t y) { asm volatile("st.shared.v2.b32 [%0], {%1,%2};" :: "r"(a), "r"(x), "r"(y) : "memory"); }
__device__ __forceinline__ void sts128(uint32_t a, uint32_t x, uint32_t y, uint32_t z, uint32_t w) { asm volatile("st.shared.v4.b32 [%0], {%1,%2,%3,%4};" :: "r"(a), "r"(x), "r"(y), "r"(z), "r"(w) : "memory"); }
__device__ __forceinline__ void ldsm4(uint32_t a, uint32_t& r0, uint32_t& r1, uint32_t& r2, uint32_t& r3) {
  asm volatile("ldmatrix.sync.aligned.m8n8.x4.shared.b16 {%0,%1,%2,%3}, [%4];" : "=r"(r0), "=r"(r1), "=r"(r2), "=r"(r3) : "r"(a) : "memory");
}
__device__ __forceinline__ void ldsm4t(uint32_t a, uint32_t& r0, uint32_t& r1, uint32_t& r2, uint32_t& r3) {
  asm volatile("ldmatrix.sync.aligned.m8n8.x4.trans.shared.b16 {%0,%1,%2,%3}, [%4];" : "=r"(r0), "=r"(r1), "=r"(r2), "=r"(r3) : "r"(a) : "memory");
}
__device__ __forceinline__ void stsm4t(uint32_t a, uint32_t r0, uint32_t r1, uint32_t r2, uint32_t r3) {
  asm volatile("stmatrix.sync.aligned.m8n8.x4.trans.shared.b16 [%0], {%1,%2,%3,%4};" :: "r"(a), "r"(r0), "r"(r1), "r"(r2), "r"(r3) : "memory");
}
__device__ __forceinline__ uint4 ldr128(const void* p) {
  unsigned long long lo, hi;
  asm volatile("{ .reg .b128 t; ld.relaxed.gpu.global.b128 t, [%2]; mov.b128 {%0, %1}, t; }" : "=l"(lo), "=l"(hi) : "l"(p) : "memory");
  return make_uint4((uint32_t)lo, (uint32_t)(lo >> 32), (uint32_t)hi, (uint32_t)(hi >> 32));
}
__device__ __forceinline__ void str128(void* p, uint32_t x, uint32_t y, uint32_t z, uint32_t w) {
  asm volatile("{ .reg .b128 t; .reg .b64 lo, hi; mov.b64 lo, {%1,%2}; mov.b64 hi, {%3,%4}; mov.b128 t, {lo, hi}; st.relaxed.gpu.global.b128 [%0], t; }"
               :: "l"(p), "r"(x), "r"(y), "r"(z), "r"(w) : "memory");
}
__device__ __forceinline__ uint32_t ldr32(const void* p) { uint32_t v; asm volatile("ld.relaxed.gpu.global.b32 %0, [%1];" : "=r"(v) : "l"(p) : "memory"); return v; }
__device__ __forceinline__ void str32(void* p, uint32_t v) { asm volatile("st.relaxed.gpu.global.b32 [%0], %1;" :: "l"(p), "r"(v) : "memory"); }
__device__ __forceinline__ void str16(void* p, uint32_t v) { asm volatile("st.relaxed.gpu.global.u16 [%0], %1;" :: "l"(p), "h"((uint16_t)v) : "memory"); }
__device__ __forceinline__ void bar_sync(int id, int n) { asm volatile("bar.sync %0, %1;" :: "r"(id), "r"(n) : "memory"); }
__device__ __forceinline__ void bar_arrive(int id, int n) { asm volatile("bar.arrive %0, %1;" :: "r"(id), "r"(n) : "memory"); }

__device__ __forceinline__ float bf_lo(uint32_t w) { return __uint_as_float(w << 16); }
__device__ __forceinline__ float bf_hi(uint32_t w) { return __uint_as_float(w & 0xFFFF0000u); }
__device__ __forceinline__ uint32_t pack_bf(float lo, float hi) { uint32_t r; asm("cvt.rn.bf16x2.f32 %0, %1, %2;" : "=r"(r) : "f"(hi), "f"(lo)); return r; }
__device__ __forceinline__ uint32_t pack_h(float lo, float hi) { uint32_t r; asm("cvt.rn.f16x2.f32 %0, %1, %2;" : "=r"(r) : "f"(hi), "f"(lo)); return r; }
__device__ __forceinline__ float bfr(float x) { return bf_lo(pack_bf(x, 0.f)); }
__device__ __forceinline__ uint32_t bf_sub2(uint32_t a, uint32_t b) { __nv_bfloat162 r = __hsub2(*(__nv_bfloat162*)&a, *(__nv_bfloat162*)&b); return *(uint32_t*)&r; }
__device__ __forceinline__ uint32_t bf_add2(uint32_t a, uint32_t b) { __nv_bfloat162 r = __hadd2(*(__nv_bfloat162*)&a, *(__nv_bfloat162*)&b); return *(uint32_t*)&r; }
__device__ __forceinline__ uint32_t bf_mul2(uint32_t a, uint32_t b) { __nv_bfloat162 r = __hmul2(*(__nv_bfloat162*)&a, *(__nv_bfloat162*)&b); return *(uint32_t*)&r; }
__device__ __forceinline__ float2 h2f(uint32_t w) { return __half22float2(*(__half2*)&w); }
__device__ __forceinline__ float ex2(float x) { float r; asm("ex2.approx.ftz.f32 %0, %1;" : "=f"(r) : "f"(x)); return r; }
__device__ __forceinline__ float warp_sum(float v) {
#pragma unroll
  for (int o = 16; o > 0; o >>= 1) v += __shfl_xor_sync(0xffffffffu, v, o);
  return v;
}
__device__ __forceinline__ void mma_bf16(float* d, uint32_t a0, uint32_t a1, uint32_t a2, uint32_t a3, uint32_t b0, uint32_t b1) {
  asm volatile("mma.sync.aligned.m16n8k16.row.col.f32.bf16.bf16.f32 {%0,%1,%2,%3}, {%4,%5,%6,%7}, {%8,%9}, {%0,%1,%2,%3};"
               : "+f"(d[0]), "+f"(d[1]), "+f"(d[2]), "+f"(d[3]) : "r"(a0), "r"(a1), "r"(a2), "r"(a3), "r"(b0), "r"(b1));
}
__device__ __forceinline__ void mma_bf16_k8(float* d, uint32_t a0, uint32_t a1, uint32_t b0) {
  asm volatile("mma.sync.aligned.m16n8k8.row.col.f32.bf16.bf16.f32 {%0,%1,%2,%3}, {%4,%5}, {%6}, {%0,%1,%2,%3};"
               : "+f"(d[0]), "+f"(d[1]), "+f"(d[2]), "+f"(d[3]) : "r"(a0), "r"(a1), "r"(b0));
}

__device__ __forceinline__ void wg_fence() { asm volatile("wgmma.fence.sync.aligned;" ::: "memory"); }
__device__ __forceinline__ void wg_commit() { asm volatile("wgmma.commit_group.sync.aligned;" ::: "memory"); }
template <int N> __device__ __forceinline__ void wg_wait() { asm volatile("wgmma.wait_group.sync.aligned %0;" :: "n"(N) : "memory"); }
template <int TB> __device__ __forceinline__ void wgmma32(float* d, const uint32_t* a, uint32_t dlo, uint32_t dhi) {
  asm volatile("{ .reg .b64 dd; mov.b64 dd, {%20, %21}; wgmma.mma_async.sync.aligned.m64n32k16.f32.f16.f16 "
               "{%0,%1,%2,%3,%4,%5,%6,%7,%8,%9,%10,%11,%12,%13,%14,%15}, {%16,%17,%18,%19}, dd, 1, 1, 1, %22; }"
               : "+f"(d[0]), "+f"(d[1]), "+f"(d[2]), "+f"(d[3]), "+f"(d[4]), "+f"(d[5]), "+f"(d[6]), "+f"(d[7]), "+f"(d[8]), "+f"(d[9]), "+f"(d[10]), "+f"(d[11]), "+f"(d[12]), "+f"(d[13]), "+f"(d[14]), "+f"(d[15])
               : "r"(a[0]), "r"(a[1]), "r"(a[2]), "r"(a[3]), "r"(dlo), "r"(dhi), "n"(TB));
}
template <int TB> __device__ __forceinline__ void wgmma64(float* d, const uint32_t* a, uint32_t dlo, uint32_t dhi) {
  asm volatile("{ .reg .b64 dd; mov.b64 dd, {%36, %37}; wgmma.mma_async.sync.aligned.m64n64k16.f32.f16.f16 "
               "{%0,%1,%2,%3,%4,%5,%6,%7,%8,%9,%10,%11,%12,%13,%14,%15,%16,%17,%18,%19,%20,%21,%22,%23,%24,%25,%26,%27,%28,%29,%30,%31}, {%32,%33,%34,%35}, dd, 1, 1, 1, %38; }"
               : "+f"(d[0]), "+f"(d[1]), "+f"(d[2]), "+f"(d[3]), "+f"(d[4]), "+f"(d[5]), "+f"(d[6]), "+f"(d[7]), "+f"(d[8]), "+f"(d[9]), "+f"(d[10]), "+f"(d[11]), "+f"(d[12]), "+f"(d[13]), "+f"(d[14]), "+f"(d[15]), "+f"(d[16]), "+f"(d[17]), "+f"(d[18]), "+f"(d[19]), "+f"(d[20]), "+f"(d[21]), "+f"(d[22]), "+f"(d[23]), "+f"(d[24]), "+f"(d[25]), "+f"(d[26]), "+f"(d[27]), "+f"(d[28]), "+f"(d[29]), "+f"(d[30]), "+f"(d[31])
               : "r"(a[0]), "r"(a[1]), "r"(a[2]), "r"(a[3]), "r"(dlo), "r"(dhi), "n"(TB));
}
template <int TB> __device__ __forceinline__ void wgmma64_init(float* d, const uint32_t* a, uint32_t dlo, uint32_t dhi) {
  asm volatile("{ .reg .b64 dd; mov.b64 dd, {%36, %37}; wgmma.mma_async.sync.aligned.m64n64k16.f32.f16.f16 "
               "{%0,%1,%2,%3,%4,%5,%6,%7,%8,%9,%10,%11,%12,%13,%14,%15,%16,%17,%18,%19,%20,%21,%22,%23,%24,%25,%26,%27,%28,%29,%30,%31}, {%32,%33,%34,%35}, dd, 0, 1, 1, %38; }"
               : "=f"(d[0]), "=f"(d[1]), "=f"(d[2]), "=f"(d[3]), "=f"(d[4]), "=f"(d[5]), "=f"(d[6]), "=f"(d[7]), "=f"(d[8]), "=f"(d[9]), "=f"(d[10]), "=f"(d[11]), "=f"(d[12]), "=f"(d[13]), "=f"(d[14]), "=f"(d[15]), "=f"(d[16]), "=f"(d[17]), "=f"(d[18]), "=f"(d[19]), "=f"(d[20]), "=f"(d[21]), "=f"(d[22]), "=f"(d[23]), "=f"(d[24]), "=f"(d[25]), "=f"(d[26]), "=f"(d[27]), "=f"(d[28]), "=f"(d[29]), "=f"(d[30]), "=f"(d[31])
               : "r"(a[0]), "r"(a[1]), "r"(a[2]), "r"(a[3]), "r"(dlo), "r"(dhi), "n"(TB));
}
template <int TB> __device__ __forceinline__ void wgmma32_init(float* d, const uint32_t* a, uint32_t dlo, uint32_t dhi) {
  asm volatile("{ .reg .b64 dd; mov.b64 dd, {%20, %21}; wgmma.mma_async.sync.aligned.m64n32k16.f32.f16.f16 "
               "{%0,%1,%2,%3,%4,%5,%6,%7,%8,%9,%10,%11,%12,%13,%14,%15}, {%16,%17,%18,%19}, dd, 0, 1, 1, %22; }"
               : "=f"(d[0]), "=f"(d[1]), "=f"(d[2]), "=f"(d[3]), "=f"(d[4]), "=f"(d[5]), "=f"(d[6]), "=f"(d[7]), "=f"(d[8]), "=f"(d[9]), "=f"(d[10]), "=f"(d[11]), "=f"(d[12]), "=f"(d[13]), "=f"(d[14]), "=f"(d[15])
               : "r"(a[0]), "r"(a[1]), "r"(a[2]), "r"(a[3]), "r"(dlo), "r"(dhi), "n"(TB));
}
__device__ __forceinline__ void wgmma64h(uint32_t* d, uint32_t a0, uint32_t a1, uint32_t a2, uint32_t a3, uint32_t dlo, uint32_t dhi) {
  asm volatile("{ .reg .b64 dd; mov.b64 dd, {%20, %21}; wgmma.mma_async.sync.aligned.m64n64k16.f16.f16.f16 "
               "{%0,%1,%2,%3,%4,%5,%6,%7,%8,%9,%10,%11,%12,%13,%14,%15}, {%16,%17,%18,%19}, dd, 1, 1, 1, 0; }"
               : "+r"(d[0]), "+r"(d[1]), "+r"(d[2]), "+r"(d[3]), "+r"(d[4]), "+r"(d[5]), "+r"(d[6]), "+r"(d[7]), "+r"(d[8]), "+r"(d[9]), "+r"(d[10]), "+r"(d[11]), "+r"(d[12]), "+r"(d[13]), "+r"(d[14]), "+r"(d[15])
               : "r"(a0), "r"(a1), "r"(a2), "r"(a3), "r"(dlo), "r"(dhi));
}
__device__ __forceinline__ void wgmma64h_init(uint32_t* d, uint32_t a0, uint32_t a1, uint32_t a2, uint32_t a3, uint32_t dlo, uint32_t dhi) {
  asm volatile("{ .reg .b64 dd; mov.b64 dd, {%20, %21}; wgmma.mma_async.sync.aligned.m64n64k16.f16.f16.f16 "
               "{%0,%1,%2,%3,%4,%5,%6,%7,%8,%9,%10,%11,%12,%13,%14,%15}, {%16,%17,%18,%19}, dd, 0, 1, 1, 0; }"
               : "=r"(d[0]), "=r"(d[1]), "=r"(d[2]), "=r"(d[3]), "=r"(d[4]), "=r"(d[5]), "=r"(d[6]), "=r"(d[7]), "=r"(d[8]), "=r"(d[9]), "=r"(d[10]), "=r"(d[11]), "=r"(d[12]), "=r"(d[13]), "=r"(d[14]), "=r"(d[15])
               : "r"(a0), "r"(a1), "r"(a2), "r"(a3), "r"(dlo), "r"(dhi));
}
__device__ __forceinline__ void wgmma40_ss(float* d, uint32_t alo, uint32_t blo, uint32_t hi) {
  asm volatile("{ .reg .b64 da, db; mov.b64 da, {%20, %22}; mov.b64 db, {%21, %22}; "
               "wgmma.mma_async.sync.aligned.m64n40k16.f32.f16.f16 {%0,%1,%2,%3,%4,%5,%6,%7,%8,%9,%10,%11,%12,%13,%14,%15,%16,%17,%18,%19}, da, db, 1, 1, 1, 1, 1; }"
               : "+f"(d[0]), "+f"(d[1]), "+f"(d[2]), "+f"(d[3]), "+f"(d[4]), "+f"(d[5]), "+f"(d[6]), "+f"(d[7]), "+f"(d[8]), "+f"(d[9]), "+f"(d[10]), "+f"(d[11]), "+f"(d[12]), "+f"(d[13]), "+f"(d[14]), "+f"(d[15]), "+f"(d[16]), "+f"(d[17]), "+f"(d[18]), "+f"(d[19])
               : "r"(alo), "r"(blo), "r"(hi));
}
__device__ __forceinline__ void wgmma40_ss_init(float* d, uint32_t alo, uint32_t blo, uint32_t hi) {
  asm volatile("{ .reg .b64 da, db; mov.b64 da, {%20, %22}; mov.b64 db, {%21, %22}; "
               "wgmma.mma_async.sync.aligned.m64n40k16.f32.f16.f16 {%0,%1,%2,%3,%4,%5,%6,%7,%8,%9,%10,%11,%12,%13,%14,%15,%16,%17,%18,%19}, da, db, 0, 1, 1, 1, 1; }"
               : "=f"(d[0]), "=f"(d[1]), "=f"(d[2]), "=f"(d[3]), "=f"(d[4]), "=f"(d[5]), "=f"(d[6]), "=f"(d[7]), "=f"(d[8]), "=f"(d[9]), "=f"(d[10]), "=f"(d[11]), "=f"(d[12]), "=f"(d[13]), "=f"(d[14]), "=f"(d[15]), "=f"(d[16]), "=f"(d[17]), "=f"(d[18]), "=f"(d[19])
               : "r"(alo), "r"(blo), "r"(hi));
}
__device__ __forceinline__ void tma_box(uint32_t dst, const CUtensorMap* tm, uint32_t mb, int x, int y) {
  asm volatile("cp.async.bulk.tensor.2d.shared::cluster.global.mbarrier::complete_tx::bytes [%0], [%1, {%3, %4}], [%2];"
               :: "r"(dst), "l"(tm), "r"(mb), "r"(x), "r"(y) : "memory");
}
__device__ __forceinline__ uint32_t uni(uint32_t v) {
  uint32_t r; asm volatile("shfl.sync.idx.b32 %0, %1, 0, 0x1f, 0xffffffff;" : "=r"(r) : "r"(v)); return r;
}
__device__ __forceinline__ uint32_t pin(uint32_t v) {
  uint32_t r; asm volatile("shfl.sync.bfly.b32 %0, %1, 0, 0x1f, 0xffffffff;" : "=r"(r) : "r"(v)); return r;
}

struct Params {
  const unsigned char* x;
  Scratch* s;
  int off[8];
  uint32_t* out;
  const uint16_t* dskip;
  const uint32_t* w_r;
  long long* ts;
  const unsigned char* far[7];
  uint32_t sched[2][17];
};
__device__ __forceinline__ uint32_t ldnc32(const void* p) { uint32_t v; asm volatile("ld.global.nc.b32 %0, [%1];" : "=r"(v) : "l"(p)); return v; }
__device__ __forceinline__ uint32_t ldnc16(const void* p) { uint16_t v; asm volatile("ld.global.nc.u16 %0, [%1];" : "=h"(v) : "l"(p)); return v; }
__device__ __forceinline__ void mbar_wait(uint32_t mb, uint32_t ph = 0) {
#pragma unroll 1
  for (int it = 0; it < SPIN_MAX; it++) {
    uint32_t ok;
    asm volatile("{ .reg .pred q; mbarrier.try_wait.parity.shared::cta.b64 q, [%1], %2; selp.u32 %0, 1, 0, q; }" : "=r"(ok) : "r"(mb), "r"(ph) : "memory");
    if (ok) break;
  }
}
__device__ __forceinline__ void mbar_arrive(uint32_t mb) { asm volatile("mbarrier.arrive.shared::cta.b64 _, [%0];" :: "r"(mb) : "memory"); }
__device__ __forceinline__ void fence_async() { asm volatile("fence.proxy.async.shared::cta;" ::: "memory"); }
#define SPIN_WHILE(cond, body) _Pragma("unroll 1") for (int _it = 0; _it < SPIN_MAX && __any_sync(0xffffffffu, (cond)); _it++) { body; }

struct LnC { uint32_t m2, rh2, rl2; };
__device__ __forceinline__ LnC ln_consts(float s, float q, float& r) {
  const float mean = s * (1.f / DM);
  const float var = fmaxf(fmaf(-mean, mean, q * (1.f / DM)), 0.f);
  float sd;
  asm("sqrt.approx.ftz.f32 %0, %1;" : "=f"(sd) : "f"(bfr(bfr(var) + 1e-5f)));
  asm("rcp.approx.ftz.f32 %0, %1;" : "=f"(r) : "f"(bfr(sd)));
  LnC c;
  c.m2 = pack_bf(mean, mean);
  c.rh2 = pack_bf(r, r);
  const float rl = r - bf_lo(c.rh2);
  c.rl2 = pack_bf(rl, rl);
  return c;
}
__device__ __forceinline__ uint32_t bf_fma2(uint32_t a, uint32_t b, uint32_t c) {
  __nv_bfloat162 r = __hfma2(*(const __nv_bfloat162*)&a, *(const __nv_bfloat162*)&b, *(const __nv_bfloat162*)&c);
  return *(uint32_t*)&r;
}
__device__ __forceinline__ uint32_t ln_apply(uint32_t w, uint32_t m2, uint32_t rh2, uint32_t rl2) {
  const uint32_t d = bf_sub2(w, m2);
  return bf_fma2(d, rh2, bf_mul2(d, rl2));
}

__device__ __forceinline__ float2 cis(float mag_log2, float rev) {
  const float m = ex2(mag_log2), ang = rev * 6.283185307179586f;
  return make_float2(m * __cosf(ang), m * __sinf(ang));
}
__device__ __forceinline__ float2 csq(float2 a) { return make_float2(fmaf(a.x, a.x, -a.y * a.y), (a.x + a.x) * a.y); }
__device__ __forceinline__ float2 cmul(float2 a, float2 b) { return make_float2(fmaf(a.x, b.x, -a.y * b.y), fmaf(a.x, b.y, a.y * b.x)); }
__device__ __forceinline__ void pmul(uint32_t xr, uint32_t xi, uint32_t w, uint32_t& yr, uint32_t& yi) {
  const __half2 XR = *(__half2*)&xr, XI = *(__half2*)&xi, W = *(__half2*)&w;
  const __half2 a = __hfma2(__hneg2(XI), __high2half2(W), __hmul2(XR, __low2half2(W)));
  const __half2 b = __hfma2(XI, __low2half2(W), __hmul2(XR, __high2half2(W)));
  yr = *(const uint32_t*)&a; yi = *(const uint32_t*)&b;
}
__device__ __forceinline__ uint32_t pk(float2 a) { return pack_h(a.x, a.y); }

struct KgState { float2 c0, z8; float kl; uint32_t w64, w128, w192; };
__device__ __forceinline__ void kgen_tables_n(const uint32_t (&raw)[7], uint32_t scr, int wt, KgState& k) {
  const uint32_t dst = scr + 16384 + wt * 16;
  const float dt = bfr(ex2(bf_lo(raw[6]) * 1.4426950408889634f));
  const float th = dt * bf_lo(raw[1]);
  const float br = dt * bf_lo(raw[2]), bi = dt * bf_lo(raw[3]);
  const float Cr = bf_lo(raw[4]), Ci = bf_lo(raw[5]);
  k.c0 = make_float2(fmaf(Cr, br, -Ci * bi), fmaf(Cr, bi, Ci * br));
  const uint32_t mx = __reduce_max_sync(0xffffffffu, __float_as_uint(fmaxf(fabsf(k.c0.x), fabsf(k.c0.y))));
  const float a2 = dt * bf_lo(raw[0]) * 1.4426950408889634f;
  const float rh = th * 0.15915494309189535f;
  const float rl = fmaf(th, (float)(0.15915494309189535 - (double)0.15915494309189535f), fmaf(th, 0.15915494309189535f, -rh));
  const float rf = rh - rintf(rh);
  const float2 z1 = cis(a2, rf + rl);
  const float p64 = rf * 64.f;
  const float2 z64 = cis(a2 * 64.f, fmaf(64.f, rl, p64 - rintf(p64)));
  const float2 z2 = csq(z1), z128 = csq(z64), z3 = cmul(z2, z1), z4 = csq(z2), z256 = csq(z128), z6 = csq(z3), z512 = csq(z256);
  k.z8 = csq(z4);
  k.w64 = pk(z64); k.w128 = pk(z128); k.w192 = pk(cmul(z128, z64));
  sts128(dst, 0x00003C00u, pk(z2), pk(z4), pk(z6));
  const float2 z1024 = csq(z512), z768 = cmul(z512, z256);
  sts128(dst + 2048, pk(z1), pk(z3), pk(cmul(z4, z1)), pk(cmul(z4, z3)));
  const float2 z2048 = csq(z1024);
  k.kl = fmaf(k.c0.x, z2048.x, -k.c0.y * z2048.y);
  sts128(dst + 4096, pk(z256), pk(cmul(z256, z2)), pk(cmul(z256, z4)), pk(cmul(z256, z6)));
  sts128(dst + 6144, pk(z512), pk(cmul(z512, z4)), pk(z768), pk(cmul(z768, z4)));
  sts128(dst + 8192, pk(z1024), pk(cmul(z1024, z256)), pk(cmul(z1024, z512)), pk(cmul(z1024, z768)));
  sts32(scr + W_MISC + (wt >> 5) * 4, mx);
}
__device__ __forceinline__ int kgen_tables_m(uint32_t scr, int wt, const KgState& k) {
  const uint32_t dst = scr + wt * 16;
  const uint4 e4 = lds128(scr + W_MISC);
  const float2 z16 = csq(k.z8), z32 = csq(z16);
  const int em = max(min((int)(max(max(e4.x, e4.y), max(e4.z, e4.w)) >> 23), 238), 16);
  const float sc = __uint_as_float((uint32_t)(127 + 4 + 127 - em) << 23);
  sts32(scr + W_MISC + 16 + (wt >> 5) * 4, __reduce_add_sync(0xffffffffu, __float2int_rn(k.kl * sc * 262144.f)));
  const float2 c0 = make_float2(k.c0.x * sc, k.c0.y * sc);
  const float2 c1 = cmul(c0, k.z8), c2 = cmul(c0, z16), c4 = cmul(c0, z32), c3 = cmul(c1, z16), c5 = cmul(c1, z32), c6 = cmul(c2, z32), c7 = cmul(c3, z32);
  uint32_t pr[4], pi[4], yr[4], yi[4];
  pr[0] = pack_h(c0.x, c1.x); pi[0] = pack_h(c0.y, c1.y);
  pr[1] = pack_h(c2.x, c3.x); pi[1] = pack_h(c2.y, c3.y);
  pr[2] = pack_h(c4.x, c5.x); pi[2] = pack_h(c4.y, c5.y);
  pr[3] = pack_h(c6.x, c7.x); pi[3] = pack_h(c6.y, c7.y);
  sts128(dst, pr[0], pr[1], pr[2], pr[3]); sts128(dst + 2048, pi[0], pi[1], pi[2], pi[3]);
#pragma unroll
  for (int q = 1; q < 4; q++) {
    const uint32_t w = q == 1 ? k.w64 : q == 2 ? k.w128 : k.w192;
#pragma unroll
    for (int i = 0; i < 4; i++) pmul(pr[i], pi[i], w, yr[i], yi[i]);
    sts128(dst + q * 4096, yr[0], yr[1], yr[2], yr[3]); sts128(dst + q * 4096 + 2048, yi[0], yi[1], yi[2], yi[3]);
  }
  return em;
}
__device__ __forceinline__ uint32_t lds32_if(uint32_t a, bool on) {
  uint32_t v; asm volatile("{ .reg .pred q; setp.ne.u32 q, %2, 0; mov.b32 %0, 0; @q ld.shared.b32 %0, [%1]; }" : "=r"(v) : "r"(a), "r"((uint32_t)on) : "memory"); return v;
}
__device__ __forceinline__ uint32_t prmt(uint32_t a, uint32_t b, uint32_t s) { uint32_t r; asm("prmt.b32 %0, %1, %2, %3;" : "=r"(r) : "r"(a), "r"(b), "r"(s)); return r; }
__device__ __forceinline__ void kgen_build(uint32_t tb, int wg, int wt, uint32_t k0, uint32_t k1, uint32_t k2) {
  const uint32_t kt = tb + W_KT, sc = tb + W_L3 + 3072;
  const int ix = ((wt >> 2) + (wt & 3) * 32 - 1) & 127;
  const uint32_t a3 = tb + W_CW + 32 + ((ix & 1) ? 0 : 304) + (ix >> 1) * 4, a2 = sc + 544 + (wt & ~3) * 2 + (wt & 1) * 4 + (wt & 2) * 128;
  const uint32_t v3 = wt ? k2 : k2 >> 16;
  sts32(sc + 4 + wt * 4, __byte_perm(k0, k1, 0x5432));
  sts16(a2, k1 >> 16); sts16(a2 + 6, k1 >> 16);
  sts16(a3, v3); sts16(a3 + 6, v3);
  if ((unsigned)(wt - 32) < 14u) sts128(kt + (wt < 36 ? -512 : 64 + 4128 - 576) + wt * 16, 0, 0, 0, 0);
  if (wt == 127) sts32(sc, k0 & 0xFFFF0000u);
  if (wt == 0) { sts32(sc + 516, k1); sts16(sc + 1056, k2); }
  bar_sync(1 + wg, 128);
  const uint32_t cw = tb + W_CW + 32 + (wt >> 6) * 48 + wt * 4, g2 = sc + 540 + wt * 4;
  const bool odd = wt & 1, ends = (unsigned)(wt - 4) >= 120u;
  const uint32_t pv = lds32(sc + wt * 4), nx = lds32(sc + 8 + wt * 4), nc = lds32_if(g2 + 8, ends);
  const uint32_t l0 = lds32(cw), l1 = lds32(cw - 8), l2 = lds32(cw - 16), l3 = lds32(cw - 24), q0 = lds32(g2), q1 = lds32(g2 + 128), q2 = lds32(g2 - 8), q3 = lds32(g2 + 120);
  sts64(kt + 64 + wt * 8, __byte_perm(k0, pv, 0x5410), __byte_perm(k0, 0, 0x1032));
  sts64(kt + 64 + 1024 + wt * 8, __byte_perm(k1, pv, (odd || wt == 0) ? 0x7610 : 0x1010), __byte_perm(k1, nx, odd ? 0x1076 : 0x1010));
  const uint32_t cc = __byte_perm(nc, 0, 0x3232), nn = __byte_perm(nc, 0, 0x1010);
  if (ends) sts128(kt + 64 + 2048 + wt * 16, cc, cc, odd ? nc : cc, odd ? nn : nc);
  if (wt == 127) { sts128(kt + 64 + 4096, nn, nn, nn, nn); sts128(kt + 64 + 4112, nn, nn << 16, 0, 0); }
  sts128(tb + W_L3 + 512 + (wt >> 6) * 512 + wt * 16, l0, l1, l2, l3);
  if ((wt & 63) < 34) sts128(tb + W_QT - 16 + wt * 16, q0, q1, q2, q3);
}

__device__ __forceinline__ void load_a(uint32_t (&a)[4], uint32_t kp, int j) {
  a[0] = lds32(kp + 64 * j); a[1] = lds32(kp + 64 * j + 512); a[2] = lds32(kp + 64 * j - 32); a[3] = lds32(kp + 64 * j + 480);
}
__device__ __forceinline__ uint32_t band8(int s) { return ((((0x1FFu << 20) >> s) & 0x01010101u) | (((0x7Fu << 25) >> s) & 0x10101010u)) * 0x01020408u; }
__device__ __forceinline__ uint32_t hadd2u(uint32_t a, uint32_t b) { __half2 r = __hadd2(*(__half2*)&a, *(__half2*)&b); return *(uint32_t*)&r; }

__device__ __forceinline__ void zero_pads(uint32_t tb, int wt) {
  if (!(wt & 32)) sts128(tb + W_L3 + (wt >> 6) * 512 + wt * 16, 0, 0, 0, 0);
  if ((wt & 63) < 3) sts128(tb + W_CW + (wt >> 6) * 304 + (wt & 63) * 16, 0, 0, 0, 0);
}
__device__ __forceinline__ uint32_t tr_base(int lane) {
  return OFF_YT + (2 * (lane >> 3) + (lane & 1)) * YT_PITCH + ((lane >> 1) & 1) * (8 * YT_PITCH + 64) + ((lane >> 2) & 1) * 16;
}

__device__ __forceinline__ uint32_t sc_addr(int tp) { return OFF_YT + (tp < 16 ? tp * YT_PITCH + (tp >> 3) * 64 + 1152 : 8 * YT_PITCH - 512 + tp * 32); }
#define X_PW 15
#define X_HU 16
#define X_PN 1
#define X_NE 2
#define X_SCT 10000
#define X_DELTA 0
#define X_DSTEP 2000
#define X_PF0 2700
#define X_PFD 600
#define X_TD 450
#define X_WS 6
#define X_OR 8
#define X_ABS 4870
#define X_XD 200
#define X_RD 630
#define X_HD 450
#define X_PD 1170
#define X_PROMO 2
#define X_YD2 1000
#define X_GO 1
#define X_GW 2
#define X_NS 4300
#define X_XS 13450
#define X_LAG 1300
#define X_YD 1550
struct TMaps { CUtensorMap m[10]; };
__device__ __forceinline__ uint32_t h2bf(uint32_t w) { const float2 f = h2f(w); return pack_bf(f.x, f.y); }
__device__ __forceinline__ uint32_t keep(uint32_t v) { asm volatile("" : "+r"(v)); return v; }
__device__ __forceinline__ uint2 ldr64(const void* p) { uint2 v; asm volatile("{ .reg .b64 t; ld.relaxed.gpu.global.b64 t, [%2]; mov.b64 {%0, %1}, t; }" : "=r"(v.x), "=r"(v.y) : "l"(p) : "memory"); return v; }
__host__ __device__ __forceinline__ uint32_t down_box(int s, bool five) {
  return five ? OFF_W + W_BYTES + 12288 + (s / 3) * (W_BYTES - 12288) + s * 4096 : s < 6 ? OFF_W + W_BYTES + BOX + (s >> 1) * (W_BYTES - 10240) + s * 5120 : OFF_W + (s - 6) * 5120;
}
__device__ __forceinline__ void load_tile(const CUtensorMap* tmx, int i, int c, int again = 0) {
  asm volatile("mbarrier.arrive.expect_tx.shared::cta.b64 _, [%0], 8704;" :: "r"(MB_UL + i * 16 + again) : "memory");
  asm volatile("cp.async.bulk.tensor.3d.shared::cluster.global.mbarrier::complete_tx::bytes [%0], [%1, {%3, %4, %5}], [%2];"
               :: "r"(i < 2 ? OFF_T + i * TILE : OFF_W), "l"(tmx), "r"(MB_UL + i * 16 + again), "r"(0), "r"(c), "r"(-8) : "memory");
}
template <bool FAR> __device__ __forceinline__ void load_params(const Params& p, uint32_t ch, int wt, uint32_t dst, bool on) {
  const int rel = wt < 96 ? ch * 16 + (wt & 15) : ch >> 3;
  const unsigned char* b = FAR ? p.far[min(wt >> 4, 6)] + rel * 16 : p.x + (long long)(p.off[wt >> 4] + rel) * 16;
  asm volatile("{ .reg .pred q; setp.ne.u32 q, %2, 0; @q cp.async.cg.shared.global [%0], [%1], 16; }"
               :: "r"(dst + wt * 16), "l"(b), "r"((uint32_t)(on && wt < 97)) : "memory");
}

struct ConvC { uint32_t ca, cb, bands, qa; };
__device__ __forceinline__ ConvC conv_consts(int w, int lane) {
  const int h = w & 1, P = (w >> 1) & 1, d0 = 8 * h + (lane >> 2) - 2 * (lane & 3);
  ConvC k;
  k.ca = keep((W_KT + (16 + 256 * P + d0) * 4) | (((8 + 64 * P + lane) * 64 + (((h + ((w >> 1) & 2)) ^ (lane >> 1)) & 3) * 16) << 16));
  const int u = d0 + 2 * (lane & 1) + 2, in = (u & 7) - ((u & 7) >= 5 ? 5 : 0) - 2 * (lane & 1);
  k.cb = keep(in > 0 ? 0x1010 : in == 0 ? 0x3210 : 0x3232);
  k.qa = keep(W_QT + (2 * (u >> 3) + ((u & 7) >= 5) + 64 * P) * 16);
  k.bands = keep(__byte_perm(band8(d0 + 8), band8(d0 + 7), 0x7733) & 0x00FF00FFu);
  return k;
}
struct ConvPre { uint32_t e0, e2, f2, b0, b2, a[3][4]; };
__device__ __forceinline__ void conv_pre(ConvPre& r, uint32_t kp, uint32_t qp, int part, bool on, bool P) {
  if (part & 1) {
    r.e0 = lds32_if(kp + 4096, on && !P); r.e2 = lds32_if(kp + 4064, on && !P); r.f2 = lds32_if(kp + 4128, on && !P);
    r.b0 = lds32_if(kp + 2048, on && !P); r.b2 = lds32_if(kp + 2016, on && !P);
  }
#pragma unroll
  for (int j = 0; j < 3; j++) if (part & (j < 1 ? 1 : 2))
    asm volatile("{ .reg .pred q; setp.ne.u32 q, %5, 0; mov.b32 %0, 0; mov.b32 %1, 0; mov.b32 %2, 0; mov.b32 %3, 0; @q ld.shared.v4.b32 {%0,%1,%2,%3}, [%4]; }"
                 : "=r"(r.a[j][0]), "=r"(r.a[j][1]), "=r"(r.a[j][2]), "=r"(r.a[j][3]) : "r"(qp + 64 * j), "r"((uint32_t)on) : "memory");
}
__device__ __forceinline__ void conv_item(uint32_t tb, uint32_t tl, int bid, int bn, ConvPre& pre, const ConvC& cv, uint32_t zero, const CUtensorMap* tmx, int ch, int warp, int lane, bool hold, bool more) {
  const bool go = more && warp == 0 && lane == 0;
  const uint32_t kp = tb + (cv.ca & 0xFFFFu), qp = tb + cv.qa;
  const uint32_t dlo = (tl >> 4) + 32 + ((warp >> 1) & 2) + (1u << 16), dhi = 32u | (2u << 30);
  const bool P = warp & 2;
  float a32[16], b32[16], a64[32];
  uint32_t A[40][4];
#define STEP(J) { wgmma64<0>(a64, A[J], dlo + 256 - 4 * (J), dhi); \
    if ((J) == 32) wgmma32_init<0>(b32, A[J], dlo, dhi); else wgmma32<0>(b32, A[J], ((J) < 8 ? dlo ^ zero : dlo) + 128 - 4 * (J), dhi); \
    if ((J) == 0) wgmma32_init<0>(a32, A[J], dlo, dhi); else if ((J) < 8) wgmma32<0>(a32, A[J], (dlo ^ zero) - 4 * (J), dhi); }
#define LD(J) load_a(A[J], kp, J);
#define LQ(J) { const uint4 v = lds128(qp + 64 * ((J) - 32)); A[J][0] = v.x; A[J][1] = v.y; A[J][2] = v.z; A[J][3] = v.w; }
#define PQ(J) { A[J][0] = prmt(A[J][0], 0, cv.cb); A[J][1] = prmt(A[J][1], 0, cv.cb); A[J][2] = prmt(A[J][2], 0, cv.cb); A[J][3] = prmt(A[J][3], 0, cv.cb); }
#define FIRST(J) wg_fence(); STEP(J) wg_commit(); wg_wait<1>(); wg_fence();
  {
    uint32_t win[16], x9[4], x7[4], e[4], f[4];
    const uint32_t bz = keep(cv.bands);
#define BAND(i) keep((bz & (0x10001u << (i))) * (0x3C00u >> (i)))
    e[0] = pre.e0; e[2] = pre.e2; e[1] = keep(bz & 0x100u); e[3] = keep(bz & 0x200u);
    f[2] = pre.f2; f[0] = keep(bz & 0x4000u); f[1] = keep(bz & 0x8000u); f[3] = keep(bz & 0x300u);
#pragma unroll
    for (int j = 0; j < 12; j++) A[32 + j / 4][j & 3] = pre.a[j / 4][j & 3];
    PQ(32) PQ(33) PQ(34)
    if (!P) { A[32][0] = pre.b0; A[32][2] = pre.b2; }
    const uint32_t q[12] = {BAND(0), BAND(5), keep(bz & 0x400u), BAND(4), BAND(2), BAND(7), BAND(1), BAND(6), keep(bz & 0x800u), keep(bz & 0x1000u), BAND(3), keep(bz & 0x2000u)};
#undef BAND
    const uint32_t ta = keep(tl + 512 + (warp & 3) * 2048 + lane * 64 + (lane & 6) * 8);
    if (X_GO && hold) mbar_wait(MB_GO);
    uint32_t mbl = MB_UL + (warp & 8) * 2, ph = 0;
#pragma unroll 1
    for (int it = 0; it < SPIN_MAX; it++) {
      if (ch < 512) mbar_wait(mbl, ph);
      if (it == 1) TS(13);
      TS(3);
      wg_fence();
      wgmma64h_init(win, q[0], q[1], q[2], q[3], dlo, dhi);
      wgmma64h(win, q[4], q[5], q[6], q[7], dlo - 4, dhi);
      wgmma64h(win, q[8], q[9], q[10], q[11], dlo - 8, dhi);
      wg_commit();
      wgmma64_init<0>(a64, e, dlo, dhi);
      wgmma64<0>(a64, f, dlo - 4, dhi);
      wg_commit();
      if (ch >= 512) break;
      uint32_t r0, r1, r2, r3, ok;
      if (warp & 4) {
        mbar_wait(mbl + 8);
        if (__all_sync(0xffffffffu, it || lds32(MISC_RT + (warp & 8)) == 0)) break;
        wg_wait<0>();
        continue;
      }
      ldsm4(ta, r0, r1, r2, r3);
      ok = r0 & r1 & r2 & r3;
      ldsm4(ta ^ 32, r0, r1, r2, r3);
      asm volatile("{ .reg .pred q; setp.ne.u32 q, %1, 0; barrier.red.and.pred q, %2, 128, q; selp.u32 %0, 1, 0, q; }" : "=r"(ok) : "r"((ok & r0 & r1 & r2 & r3 & 1u) | (lane & 3)), "r"(1 + (warp >> 2)) : "memory");
      if (ok) { if ((warp & 3) == 0 && lane == 0) { sts32(MISC_RT + warp, it); mbar_arrive(MB_UL + 8 + warp * 2); } break; }
      wg_wait<0>();
      if ((warp & 3) == 0 && lane == 0) load_tile(tmx - 1, warp >> 3, ch, 56);
      mbl = MB_UL + 56 + (warp & 8) * 2; ph = it & 1;
    }
    wg_wait<1>();
#pragma unroll
    for (int i = 0; i < 4; i++) {
      const int tl = 2 * ((i & 1) + ((i & 2) ? 0 : 4));
      x9[i] = P ? win[tl + 4] : win[tl]; x7[i] = P ? win[tl + 5] : win[tl + 1];
    }
    const uint32_t l3lo = ((tb + W_L3) >> 4) + (32u << 16);
    wg_fence();
    wgmma64<0>(a64, x9, l3lo, 8);
    wgmma64<0>(a64, x7, l3lo + 96, 8);
    wg_commit();
  }
  STEP(32) STEP(33) STEP(34) wg_commit(); wg_wait<1>();
  LQ(35) LQ(36) LQ(37) LQ(38) LQ(39) LD(0) PQ(35) PQ(36) PQ(37) PQ(38) PQ(39)
  FIRST(35) STEP(36) STEP(37) STEP(38) wg_commit(); STEP(39) wg_commit();
  LD(1) LD(2) LD(3)
  if (X_GO == 1 && go) mbar_arrive(MB_GO);
  wg_wait<1>(); wg_fence(); STEP(0) wg_commit(); STEP(1) wg_commit(); STEP(2) wg_commit(); wg_wait<2>();
  LD(4) LD(5)
  wg_fence(); STEP(3) wg_commit(); wg_wait<1>();
  LD(6) LD(7)
  wg_fence(); STEP(4) STEP(5) wg_commit();
  wg_fence(); STEP(6) STEP(7) wg_commit();
#undef STEP
#undef LD
#undef LQ
#undef PQ
#undef FIRST
  TS(18);
  if (X_GO == 3 && go) mbar_arrive(MB_GO);
  const uint32_t xc = tb + W_KT + (warp & 3) * 1024 + lane * 16;
  if (more) bar_sync(7, 288);
  wg_wait<1>();
  conv_pre(pre, kp + ALT, qp + ALT, 1, more, P);
  wg_wait<0>();
  conv_pre(pre, kp + ALT, qp + ALT, 2, more, P);
  uint32_t E[16], o[8];
#define ACC(i) ((i) < 16 ? a32[i] : (i) < 32 ? b32[(i) - 16] : a64[(i) - 32])
  E[0] = pack_h(a32[0], a32[1]);
#pragma unroll
  for (int i = 1; i < 16; i++) E[i] = pack_h(ACC(4 * i) + ACC(4 * i - 2), ACC(4 * i + 1) + ACC(4 * i - 1));
#undef ACC
#pragma unroll
  for (int j = 0; j < 8; j++) o[j] = P ? (j < 2 ? 0u : E[j - 2]) : E[8 + j];
  sts128(xc, o[0], o[1], o[2], o[3]); sts128(xc + 512, o[4], o[5], o[6], o[7]);
#pragma unroll
  for (int j = 0; j < 8; j++) o[j] = P ? E[6 + j] : E[j];
  TS(25);
  if (more) {
    sts128(xc + 4096, o[0], o[1], o[2], o[3]); sts128(xc + 4608, o[4], o[5], o[6], o[7]);
    bar_arrive(12, 192);
    return;
  }
  bar_sync(1 + (warp >> 2), 128);
  const uint4 vv[2] = {lds128(xc + (P ? -2048 : 2048)), lds128(xc + (P ? -1536 : 2560))};
  const uint32_t mk = lane < 8 ? 0xFFFEFFFEu : ~0u;
#pragma unroll
  for (int q = 0; q < 2; q++) {
    const uint4 v = vv[q];
    stsm4t(tl + (cv.ca >> 16) + q * 2048, hadd2u(o[4 * q], v.x) & mk, hadd2u(o[4 * q + 1], v.y) & mk, hadd2u(o[4 * q + 2], v.z) & mk, hadd2u(o[4 * q + 3], v.w) & mk);
  }
  fence_async();
  bar_sync(bid, bn);
  if (warp == 0 && lane == 0) mbar_arrive(MB_REL);
  if ((warp & 7) == (ch < 512 ? 7 : 3) && lane == 0) {
    asm volatile("cp.async.bulk.tensor.3d.global.shared::cta.bulk_group [%0, {%3, %2, %3}], [%1];" :: "l"(tmx), "r"(tl + 512), "r"(ch), "r"(0) : "memory");
    asm volatile("cp.async.bulk.commit_group;" ::: "memory");
  }
}

template <bool FAR> __global__ void __launch_bounds__(NT, 1)
fused_kernel(const __grid_constant__ Params p, const __grid_constant__ TMaps tm) {
  extern __shared__ __align__(1024) unsigned char smem[];
  const int c = blockIdx.x;
  const bool five = (c & 1) == 0;
  const uint32_t pitch = five ? 64 : 80;
  const uint32_t ones = 0x3F803F80u;
  const int tid = threadIdx.x, lane = tid & 31;
  const uint32_t xrow = OFF_YT + ((tid & 127) >> 3) * YT_PITCH + (tid & 64) + (tid & 7) * 16;
  {
    const int w4 = tid >> 7;
    load_params<FAR>(p, w4 < 2 ? 2 * c + w4 : five ? 257 + 2 * c : 512 + (c >> 1), tid & 127, OFF_W + W_KT + (w4 < 2 ? w4 * W_BYTES : five ? 3 * W_BYTES : 3 * W_BYTES + 2048), (0xB >> w4) & 1);
  }
  if ((tid >> 7) == 2) {
    const unsigned char* xp = p.x + (uint32_t)((c * 16 - 32 + (tid >> 3)) * 1152 + (tid & 7) * 16);
    asm volatile("" : "+l"(xp));
    { const uint32_t tq = clock(); while ((int)(clock() - tq) < X_XD) {} }
#pragma unroll
    for (int k = 0; k < 9; k++) asm volatile("cp.async.cg.shared.global [%0], [%1], 16;" :: "r"(xrow + k * 128), "l"(xp + k * 128) : "memory");
  }
  const int warp = (int)uni(tid >> 5), wg = warp >> 2;
  TS(0);
  if (__builtin_expect(wg == 4, 0)) {
    asm volatile("setmaxnreg.dec.sync.aligned.u32 32;");
    const int role = warp;
    const int u0 = (c >> 1) * 9 + (five ? ((c & 2) ? 5 : 0) : ((c & 2) ? 0 : 4));
    const uint32_t t0 = clock() + c * 4;
    if (role == 16) {
      if (lane == 0) {
#pragma unroll
        for (int i = 0; i < 19; i++) if (i != 16) asm volatile("mbarrier.init.shared::cta.b64 [%0], %1;" :: "r"(OFF_MISC + i * 8), "r"((unsigned)(i - 2) < 4u ? 4 : 1) : "memory");
      }
      __syncwarp();
      if (lane < 2) asm volatile("mbarrier.arrive.expect_tx.shared::cta.b64 _, [%0], %1;" :: "r"(OFF_MISC + lane * 8), "r"(lane ? (five ? 36864 : 51200) : pitch * 1152) : "memory");
      fence_async();
      bar_arrive(5, 608);
      const CUtensorMap* tmb = &tm.m[five ? 3 : 0];
#pragma unroll 1
      for (int u = 0; u < 17; u++) {
        const uint32_t e = p.sched[five][u], kind = e & 3, s = (e >> 2) & 15, dst = e >> 14;
        if (kind == 3) continue;
        while ((int)(clock() - t0) < X_PF0 + (u < X_NE ? u * X_PFD : X_LAG + u * X_TD)) __nanosleep(20);
        if (e & 0x3FC0) mbar_wait(OFF_MISC + ((e >> 6) & 255));
        if (lane == 0) {
          if (kind == 2) asm volatile("cp.async.bulk.tensor.3d.shared::cluster.global.mbarrier::complete_tx::bytes [%0], [%1, {%3, %4, %5}], [%2];"
                                      :: "r"(dst), "l"(tmb + 2), "r"(MB_D), "r"(0), "r"(u0 * 8), "r"(s) : "memory");
          else tma_box(dst, tmb + kind, MB_GU, u0 * 8, s * 96);
        }
        if (u == 5) TS(2);
        if (u == 10) TS(3);
      }
      TS(4);
      TS_DUMP();
#define FINISH0 bar_sync(12, 192);        \
        _Pragma("unroll 1") for (int w = role & 2; w < (role & 2) + 2; w++) { \
          const uint32_t xa = OFF_W + W_KT + lane * 16, mk = lane < 8 ? 0xFFFEFFFEu : ~0u, ya = OFF_T + (8 + lane) * 64 + (((w & 1) ^ (lane >> 1)) & 3) * 16 + (w & 2) * 2048; \
          const uint4 a = lds128(xa + 4096 + w * 1024), b = lds128(xa + (w ^ 2) * 1024), d = lds128(xa + 4608 + w * 1024), e = lds128(xa + 512 + (w ^ 2) * 1024); \
          stsm4t(ya, hadd2u(a.x, b.x) & mk, hadd2u(a.y, b.y) & mk, hadd2u(a.z, b.z) & mk, hadd2u(a.w, b.w) & mk); \
          stsm4t(ya + 2048, hadd2u(d.x, e.x) & mk, hadd2u(d.y, e.y) & mk, hadd2u(d.z, e.z) & mk, hadd2u(d.w, e.w) & mk); \
        } \
        fence_async();
    } else if (role == 17) {
      if (smem_u32(smem) != SB) __trap();
      bar_sync(10, 576);
      if (lane == 0) {
        fence_async();
        while ((int)(clock() - t0) < X_NS - c * 4) {}
        asm volatile("cp.async.bulk.global.shared::cta.bulk_group [%0], [%1], 10240;" :: "l"(&p.s->X[c * DM * 2 + 512]), "r"(OFF_G) : "memory");
        asm volatile("cp.async.bulk.commit_group;" ::: "memory");
        asm volatile("cp.async.bulk.wait_group 0;" ::: "memory");
      }
      if (lane == 0) mbar_arrive(MB_GF);
      bar_arrive(11, 96);
      if (five) { FINISH0 bar_arrive(13, 192); }
    } else if (role == 18) {
      sts32(MISC_EPOCH, 0);
      sts32(MISC_T0, t0 - c * 4);
      bar_arrive(5, 608);
      uint4* q = lane < 2 ? &p.s->R[c * 2 + lane] : lane < 11 ? &p.s->HS[c * 9 + lane - 2] : lane == 11 ? &p.s->HS[1152 + (c & 7)] : (uint4*)&p.s->FLAG[c * 8];
      if (lane < (c < 8 ? 12 : 11)) str128(q, ~0u, ~0u, ~0u, ~0u);
      const uint32_t ep = __shfl_sync(0xffffffffu, ldr32(q), 31) + 1u;
      sts32(MISC_EPOCH, ep | 0x80000000u);
      TSX(21);
      if (lane == 31) str32(q, ep);
      bar_sync(11, 96);
      TSX(14);
      mbar_wait(MB_KF + (lane & 3) * 8);
      __syncwarp();
      { const uint2 e = lds64(MISC_EM); if (lane < 2) str128(&p.s->SC[c * 2 + lane], e.x, __byte_perm(e.y, ep, 0x6540), 0, 0); }
      TSX(17);
      while ((int)(clock() - t0) < X_SCT) __nanosleep(100);
      TSX(18);
      {
        uint2 v[4];
#pragma unroll 1
        for (int it = 0; it < SPIN_MAX; it++) {
          uint32_t bad = 0;
#pragma unroll
          for (int q = 0; q < 4; q++) v[q] = ldr64(&p.s->SC[lane * 2 + q * 64]);
#pragma unroll
          for (int q = 0; q < 4; q++) bad |= (v[q].y >> 8) ^ (ep & 0xFFFFFFu);
          if (!__any_sync(0xffffffffu, bad)) break;
        }
        TSX(25);
#pragma unroll
        for (int q = 0; q < 4; q++) {
          const uint32_t sa = (lane >> 4) * YT_PITCH + (lane & 15) * 2;
          sts16(sc_addr(2 * q) + sa, v[q].x); sts16(sc_addr(8 + 2 * q) + sa, v[q].x >> 16);
          if (lane & 1) asm volatile("st.shared.u8 [%0], %1;" :: "r"(sc_addr(16) + q * 16 + (lane >> 1)), "r"(v[q].y) : "memory");
        }
      }
      __syncwarp();
      if (lane == 0) mbar_arrive(MB_SC);
      TSX(27);
    } else {
      uint32_t w[9];
      const uint32_t dk = ldnc16(p.dskip + ((lane & 4) ? 512 + (c >> 1) : (lane & 2) * 128 + 2 * c + (lane & 1)));
      float s = 0.f;
#pragma unroll
      for (int i = 0; i < 9; i++) w[i] = ldnc32(p.w_r + lane + 32 * i);
      sts16(OFF_WR + 1152 + lane * 2, dk);
      bar_arrive(5, 608);
#pragma unroll
      for (int i = 0; i < 9; i++) { sts32(OFF_WR + lane * 4 + i * 128, w[i]); s += bf_lo(w[i]) + bf_hi(w[i]); }
      sts32(MISC_SW, __float_as_uint(warp_sum(s)));
      TSX(23);
      bar_sync(10, 576);
      if (lane == 0) {
        const uint32_t tp = clock();
        TSX(1);
        while ((int)(clock() - tp) < X_DELTA || (int)(clock() - t0) < X_ABS - c * 4) {}
        TSX(24);
        load_tile(&tm.m[6], 0, c);
        TSX(15);
        while ((int)(clock() - t0) < X_ABS + X_DSTEP - c * 4) {}
      }
      bar_sync(11, 96);
      if (lane == 0) {
        load_tile(&tm.m[6], 1, 128 + c);
      }
      if (five) {
        mbar_wait(MB_KF);
#pragma unroll 1
        for (int it = 0; it < SPIN_MAX; it++) {
          if (lane == 0) load_tile(&tm.m[8], 2, 512 + (c >> 1));
          mbar_wait(MB_UL + 32, it & 1);
          uint32_t m = 1;
#pragma unroll
          for (int q = 0; q < 4; q++) { uint32_t r0, r1, r2, r3; ldsm4(OFF_W + 512 + lane * 64 + (lane & 6) * 8 + q * 2048, r0, r1, r2, r3); m &= r0 & r1 & r2 & r3; }
          if (__all_sync(0xffffffffu, m || (lane & 3))) break;
        }
        bar_arrive(7, 288);
        FINISH0
        bar_arrive(13, 192);
      }
      bar_sync(0, 544);
      if (lane == 0) mbar_arrive(MB_H);
    }
    return;
  }
  const int wt = tid & 127, g = lane >> 2, t = lane & 3;
  const uint32_t wb = OFF_W + wg * W_BYTES;
  asm volatile("cp.async.commit_group;" ::: "memory");
  const ConvC cv = conv_consts(warp, lane);
  zero_pads(wb, wt);
  load_params<FAR>(p, 254 + 2 * c + wg, wt, wb + W_KT, wg == 2 || (wg == 3 && !five));
  asm volatile("cp.async.commit_group;" ::: "memory");
  asm volatile("setmaxnreg.inc.sync.aligned.u32 112;");
  {
    uint4 kw;
    uint4* kx = &p.s->KX[(c >> 1) * 128 + wt];
    bool two = wg == 3;
    uint32_t ep;
    int em = 0;
    uint32_t slot = wg + (two && !five);
    const uint32_t ra0 = wb + W_KT + (slot & 4) * 512 + wt * 2, ra6 = wb + W_KT + 1536 + (slot & 4) * 512 + (((slot & 4) ? c >> 1 : 2 * c + (wg & 1)) & 7) * 2;
        const int lz = lane;
        const uint32_t tr_addr = pin(tr_base(lz) + warp * 32), lca = pin(MISC_LN1 + (lz & 1) * 16);
        uint4* dst;
        { const unsigned long long a = (unsigned long long)&p.s->X[c * DM * 2 + warp * 32 + (8 * ((lz >> 1) & 1) + (lz >> 2)) * 2 + (lz & 1)];
          dst = (uint4*)(((unsigned long long)pin(a >> 32) << 32) | pin((uint32_t)a)); }
    uint32_t raw[7];
    if (wg != 2) {
      asm volatile("cp.async.wait_group 1;" ::: "memory");
      bar_sync(1 + wg, 128);
#pragma unroll
      for (int i = 0; i < 7; i++) raw[i] = lds16(i < 6 ? ra0 + i * 256 : ra6);
    }
    int phase = wg == 2 ? 3 : 2;
#pragma unroll 1
    for (;;) {
      if (phase != 3) {
        KgState ks;
        TS(22);
        kgen_tables_n(raw, wb, wt, ks);
        TS(20);
        bar_sync(1 + wg, 128);
        em = kgen_tables_m(wb, wt, ks);
        fence_async();
      }
      if (phase & 2) {
        if (phase == 3) {
        asm volatile("cp.async.wait_group 1;" ::: "memory");
        TS(21);
        float d[3][4], r;
        uint4 a[9];
#pragma unroll
        for (int k = 0; k < 9; k++) a[k] = lds128(xrow + k * 128);
#pragma unroll
        for (int i = 0; i < 4; i++) d[0][i] = d[1][i] = d[2][i] = 0.f;
#pragma unroll
        for (int k = 0; k < 9; k++) { mma_bf16(d[(2 * k) % 3], a[k].x, ones, a[k].y, ones, a[k].x, a[k].y); mma_bf16(d[(2 * k + 1) % 3], a[k].z, ones, a[k].w, ones, a[k].z, a[k].w); }
#pragma unroll
        for (int i = 0; i < 4; i++) d[0][i] += d[1][i] + d[2][i];
        const LnC lc = ln_consts(d[0][2] + d[0][3], __shfl_sync(0xffffffffu, d[0][0], 9 * t) + __shfl_sync(0xffffffffu, d[0][1], 9 * t + 4), r);
        if (lane < 12) sts16(MISC_LN1 + g * 32 + (warp & 3) * 8 + t * 2, lane < 4 ? lc.m2 : lane < 8 ? lc.rh2 : lc.rl2);
        }
        asm volatile("cp.async.wait_group 0;" ::: "memory");
        TS(23);
        bar_sync(5, 608);
        uint32_t x[3][4];
        ldsm4t(tr_addr, x[0][0], x[0][1], x[0][2], x[0][3]);
        uint4 m = lds128(lca);
        const uint4 rl = lds128(lca + 64), rh = lds128(lca + 32);
        ldsm4t(tr_addr + 512, x[1][0], x[1][1], x[1][2], x[1][3]);
        if (wg == 3) ldsm4t(tr_addr + 640, x[2][0], x[2][1], x[2][2], x[2][3]);
#pragma unroll
        for (int q = 0; q < 3; q++) {
          if (q < 2 || wg == 3) {
            const uint32_t r0 = ln_apply(x[q][0], m.x, rh.x, rl.x), r1 = ln_apply(x[q][1], m.y, rh.y, rl.y), r2 = ln_apply(x[q][2], m.z, rh.z, rl.z), r3 = ln_apply(x[q][3], m.w, rh.w, rl.w);
            const uint32_t w0 = (pack_h(bf_lo(r0), bf_hi(r0)) & 0xFFFEFFFEu) | 1u, w1 = pack_h(bf_lo(r1), bf_hi(r1)), w2 = pack_h(bf_lo(r2), bf_hi(r2)), w3 = pack_h(bf_lo(r3), bf_hi(r3));
            if (q == 0) str128(dst, w0, w1, w2, w3);
            else sts128(OFF_G + warp * 512 + (8 * (t >> 1) + g) * 32 + (t & 1) * 16 + (q == 2 ? 2048 : 0), w0, w1, w2, w3);
          }
          if (q == 0) {
            const uint32_t z = clock() & p.off[7];
            m.x ^= z; m.y ^= z; m.z ^= z; m.w ^= z;
          }
          if (q == 0) TS(30);
          if (q == 0 && wg >= 2) {
#pragma unroll
            for (int i = 0; i < 7; i++) raw[i] = lds16(wb + W_KT + i * 256 + (i < 6 ? wt : (2 * c + (wg & 1)) & 7) * 2);
          }
        }
        bar_arrive(10, 576);
        TS(1);
      } else bar_sync(1 + wg, 128);
      phase &= 1;
      if (phase) { phase = 0; continue; }
      TS(14);
      float acc[20];
      const uint32_t alo = (wb >> 4) | (8u << 16);
      uint4 k4 = lds128(wb + W_MISC + 16);
      uint32_t dk = lds16(OFF_WR + 1152 + slot * 2);
      wg_fence();
      wgmma40_ss_init(acc, alo, alo + 1024, 2048 >> 4);
#pragma unroll
      for (int k = 1; k < 8; k++) wgmma40_ss(acc, alo + k * 16, alo + 1024 + k * 16, 2048 >> 4);
      wg_commit();
      { const uint32_t z = clock() & p.off[7]; dk ^= z; k4.x ^= z; k4.z ^= z; }
      const float k2048 = (float)(int)((k4.x + k4.y) + (k4.z + k4.w)) * (1.f / 262144.f);
      const int ef = max(em, min((int)((dk >> 7) & 255u) - 7, 238));
      asm volatile("st.shared.u8 [%0], %1;" :: "r"(MISC_EM + slot), "r"(ef + 9) : "memory");
      const float un = __uint_as_float((uint32_t)max(114 + em - ef, 0) << 23), d0 = wt ? 0.f : bf_lo(dk) * __uint_as_float((uint32_t)(245 - ef) << 23);
      wg_wait<0>();
      kw.x = pack_h(fmaf(acc[0] - acc[3], un, d0), (acc[4] - acc[7]) * un);
      kw.y = pack_h((acc[8] - acc[11]) * un, (acc[12] - acc[15]) * un);
      kw.z = pack_h((acc[16] - acc[19]) * un, k2048 * un);
      TS(24);
      ep = 0;
      if (two) SPIN_WHILE(ep == 0, ep = lds32(MISC_EPOCH));
      if (five || !two) break;
      str128(kx, kw.x, kw.y, kw.z, ep);
      two = false;
      slot = 3;
      bar_sync(1 + wg, 128);
    }
    if (lane == 0) mbar_arrive(MB_KF + wg * 8);
    if (two) { mbar_wait(MB_KF); zero_pads(OFF_W + ALT, wt); }
    uint32_t tb = wb;
#pragma unroll 1
    for (;;) {
      kgen_build(tb, wg, wt, kw.x, kw.y, kw.z);
      TS(15);
      if (!two) break;
      two = false;
      kw.w = 0;
      SPIN_WHILE(kw.w != ep, kw = ldr128(kx));
      tb = OFF_W + ALT;
    }
    fence_async();
    TS(31);
    if (tb != wb) bar_arrive(7, 288);
    bar_sync(1 + wg, 128);
  }
  uint32_t tpub;
  ConvPre pre;
  conv_pre(pre, (wb ^ p.off[7]) + (cv.ca & 0xFFFFu), (wb ^ p.off[7]) + cv.qa, 3, true, warp & 2);
#pragma unroll 1
  for (int item = 0;; item++) {
    TS(2);
    conv_item(item ? OFF_W + ALT : wb, item ? OFF_W : OFF_T + (wg >> 1) * TILE, item ? 1 : 13 + (wg >> 1), item ? 128 : five && wg == 1 ? 192 : 256, pre, cv, p.off[7],
              &tm.m[item ? 9 : 7], item ? 512 + (c >> 1) : (wg >> 1) * 128 + c, warp, lane, five && wg >= X_GW, five && !wg && !item);
    tpub = clock() - (item ? X_YD : wg >= 2 ? X_YD2 : 0);
    if (wg || !five || item) break;
    TS(27);
  }
  TS(4);

  const int ln = lane ^ p.off[7], td = warp * 32 + ln, gg = ln >> 2, tt = ln & 3;
  const int tok = c * 16 + warp;
  const int fu = warp / 3, fk = warp - fu * 3;
  uint32_t wa[12][4];
  uint4 ha[3];
  const uint4* hsrc = &p.s->HS[td + (td / 24) * 48];
  {
    uint32_t hw[9], wr[9];
    const uint32_t row = keep(OFF_YT + warp * YT_PITCH + (warp >> 3) * 64 + ln * 16);
    const uint32_t wabase = keep(((ln & 8) ? OFF_W + (fk + 1) * W_BYTES : OFF_G + fk * 192 * pitch) + ((ln >> 4) * 8 + (ln & 7)) * pitch
                                 + (five ? ((fu ^ (ln >> 1)) & 3) : min(fu, 4)) * 16);
    float sw;
    {
      const bool three = wg == 1;
      const int ch = 8 * (tt >> 1) + gg;
      const uint32_t tr_addr = tr_base(ln);
      const uint4* ysrc = &p.s->X[c * DM * 2 + ch * 2 + (tt & 1)];
      uint32_t x[3][4], s[3];
      uint4 v[3];
#define TL(q) ((q) < 2 ? 2 * warp + (q) : 28 + warp)
      if (wg >= 2) { const uint32_t ts = lds32(MISC_T0); while ((int)(clock() - ts) < X_XS) {} }
      while ((int)(clock() - tpub) < X_YD) {}
      TS(5);
      v[0] = ldr128(ysrc + TL(0) * 32); v[1] = ldr128(ysrc + TL(1) * 32); v[2] = make_uint4(three, 0, 0, 0);
      mbar_wait(MB_REL);
#pragma unroll
      for (int i = 0; i < 6; i++) if (i < 4 || three) wr[i] = (gg & 2) ? ones : lds32(OFF_WR + TL(i >> 1) * 32 + (i & 1) * 16 + tt * 4);
      const uint32_t ha = keep(OFF_YT + (ln & 7) * YT_PITCH + (ln >> 4) * (8 * YT_PITCH + 64) + (ln & 8) * 2);
      const uint32_t pa = keep(OFF_PART + warp * 4 + ((gg & 2) * 8 + (gg & 4) * 2 + 2 * tt + (gg & 1)) * 80), pb = keep(OFF_PART + 2560 + warp * 4 + gg * 80);
      float dl[4] = {0.f, 0.f, 0.f, 0.f}, dh[4] = {0.f, 0.f, 0.f, 0.f};
      sw = __uint_as_float(lds32(MISC_SW));
#pragma unroll
      for (int q = 0; q < 3; q++) {
        if (q < 2 || three) {
          ldsm4t(tr_addr + TL(q) * 32, x[q][0], x[q][1], x[q][2], x[q][3]);
        }
      }
      asm volatile("cp.async.bulk.wait_group.read 0;" ::: "memory");
      mbar_wait(MB_SC);
#pragma unroll
      for (int q = 0; q < 3; q++) {
        asm volatile("ld.shared.u8 %0, [%1];" : "=r"(s[q]) : "r"((q < 2 ? sc_addr(warp) + q * 16 : sc_addr(16) + (warp & 3) * 16) + ch) : "memory");
        s[q] = keep(s[q] * 0x800080u);
      }
#define FIN(q) stsm4t(tr_addr + TL(q) * 32, bf_fma2(h2bf(v[q].x), s[q], x[q][0]), bf_fma2(h2bf(v[q].y), s[q], x[q][1]), bf_fma2(h2bf(v[q].z), s[q], x[q][2]), bf_fma2(h2bf(v[q].w), s[q], x[q][3]));
      SPIN_WHILE((v[0].x | v[1].x) & 1u, _Pragma("unroll") for (int q = 0; q < 3; q++) if (v[q].x & 1u) v[q] = ldr128(ysrc + TL(q) * 32));
      if (v[2].x & 1u) v[2] = ldr128(ysrc + TL(2) * 32);
#define STAT(q) { uint32_t r0, r1, r2, r3; ldsm4(ha + TL(q) * 32, r0, r1, r2, r3); \
        mma_bf16(dl, r0, wr[2 * q], r1, wr[2 * q + 1], r0, r1); mma_bf16(dh, r2, wr[2 * q], r3, wr[2 * q + 1], r2, r3); }
      FIN(0) FIN(1)
      __syncwarp();
      STAT(0) STAT(1)
      if (three) {
#pragma unroll 1
        for (int it = 0; it < SPIN_MAX; it++) {
          FIN(2)
          if (!__any_sync(0xffffffffu, v[2].x & 1u)) break;
          if (v[2].x & 1u) v[2] = ldr128(ysrc + TL(2) * 32);
        }
        __syncwarp();
        STAT(2)
      }
      if (gg & 1) { dl[0] = dl[1]; dl[2] = dl[3]; dh[0] = dh[1]; dh[2] = dh[3]; }
      sts32(pa, __float_as_uint((gg & 4) ? dh[2] : dl[2]));
      if (tt == (gg >> 1)) { sts32(pb, __float_as_uint(dl[0])); sts32(pb + 640, __float_as_uint(dh[0])); }
#undef STAT
#undef FIN
#undef TL
    }
    uint32_t ra = keep(OFF_PART + (ln & 15) * 80 + (ln & 16) * 2);
    uint16_t* rp = (uint16_t*)p.s->R + c * 16 + (ln & 15);
    const uint2* rsrc = (const uint2*)p.s->R + td;
    asm volatile("" : "+l"(rp), "+l"(rsrc), "+l"(hsrc));
    uint2 rv = make_uint2(0u, 0u);
    TS(28);
    if (warp != X_PW) bar_sync(0, 544);
    else {
      float z[3], rd;
      asm volatile("bar.sync 0, 544;" : "+r"(ra) :: "memory");
#pragma unroll
      for (int k = 2; k >= 0; k--) {
        const uint4 a = lds128(ra + k * 1280), b = lds128(ra + k * 1280 + 16);
        z[k] = ((__uint_as_float(a.x) + __uint_as_float(a.y)) + (__uint_as_float(a.z) + __uint_as_float(a.w))) + ((__uint_as_float(b.x) + __uint_as_float(b.y)) + (__uint_as_float(b.z) + __uint_as_float(b.w)));
      }
#pragma unroll
      for (int k = 2; k >= 0; k--) z[k] += __shfl_xor_sync(0xffffffffu, z[k], 16);
      const LnC l = ln_consts(z[1], z[2], rd);
      const uint32_t b = pack_bf(0.f, fmaf(-bf_lo(l.m2), sw, z[0]) * rd);
      const uint32_t k16 = max(min((b ^ (((int)b >> 31) | 0x80000000u)) >> 16, 0xFFFEu), 1u);
      if (ln < 16) str16(rp, k16);
      sts64(OFF_RK + (ln & 15) * 8, __byte_perm(l.m2, l.rh2, 0x5410), __byte_perm(l.rl2, k16, 0x5410));
      sts128(MISC_CNT + ln * 16, 0, 0, 0, 0);
    }
    mbar_wait(MB_GU);
#define LD_HW { const uint4 a = lds128(row), b = lds128(row + 512); hw[8] = lds32(row + 1024 - ln * 12); \
      hw[0] = a.x; hw[1] = a.y; hw[2] = a.z; hw[3] = a.w; hw[4] = b.x; hw[5] = b.y; hw[6] = b.z; hw[7] = b.w; }
    LD_HW
    const uint32_t tr0 = clock();
    bar_sync(5, 512);
    TS(7);
    const uint2 lk = lds64(OFF_RK + warp * 8);
    LnC l2;
    l2.m2 = __byte_perm(lk.x, 0, 0x1010); l2.rh2 = __byte_perm(lk.x, 0, 0x3232); l2.rl2 = __byte_perm(lk.y, 0, 0x1010);
    const uint32_t key = (lk.y & 0xFFFF0000u) | (2047 - tok);
    uint32_t loc = ln < 16 ? (lds32(OFF_RK + 4 + ln * 8) & 0xFFFF0000u) | (2047 - c * 16 - ln) : 0u;
    int rank = __popc(__ballot_sync(0xffffffffu, loc > key));
#pragma unroll
    for (int i = 0; i < 9; i++) { wr[i] = keep(ln_apply(hw[i], l2.m2, l2.rh2, l2.rl2)); hw[i] = bf_add2(hw[i], wr[i]); }
#define OUT_ROW { uint32_t* o = p.out + tok * 288 + ln * 4; \
      *(uint4*)o = make_uint4(hw[0], hw[1], hw[2], hw[3]); *(uint4*)(o + 128) = make_uint4(hw[4], hw[5], hw[6], hw[7]); o[256 - ln * 3] = hw[8]; }
    uint4* hs = p.s->HS + ln;
    asm volatile("" : "+l"(hs));
#pragma unroll 1
    for (int base = 0; base < 8; base += 2) {
      uint32_t T[2];
#pragma unroll
      for (int j = 0; j < 2; j++) {
        const uint32_t mx = __reduce_max_sync(0xffffffffu, loc);
        if (loc == mx) loc = 0;
        T[j] = (td >> 2) < c ? (mx & 0xFFFF0000u) - 1u : mx | 0xFFFFu;
      }
      const uint32_t sh = keep(rank == base ? 0x4410u : rank == base + 1 ? 0x4432u : 0x4445u), ca = keep(MISC_CNT + base * 64 + ln * 4);
      TS(29);
      if (base == 0) {
        while ((int)(clock() - tr0) < X_RD) {}
        if ((td >> 2) != c) rv = ldr64(rsrc);
        if (rank >= X_OR) OUT_ROW
        if (warp < (five ? 12 : 15)) {
#pragma unroll
          for (int k = 0; k < X_WS; k++) ldsm4t(wabase + k * 16 * pitch, wa[k][0], wa[k][1], wa[k][2], wa[k][3]);
        }
      }
      uint32_t cnt;
#pragma unroll 1
      for (int it = 0; it < SPIN_MAX; it++) {
        const uint32_t xs = rv.x << 16, ys = rv.y << 16;
        const bool bad = max(max(rv.x, xs), max(rv.y, ys)) >= 0xFFFF0000u;
        uint32_t cn2 = 0;
        cnt = bad ? 256u : 0u;
#pragma unroll
        for (int j = 0; j < 2; j++)
          asm("{ .reg .pred a, b, c, d; setp.gt.u32 a, %2, %6; setp.gt.u32 b, %3, %6; setp.gt.u32 c, %4, %6; setp.gt.u32 d, %5, %6; "
              "@a add.u32 %1, %1, %7; @b add.u32 %1, %1, %7; @c add.u32 %0, %0, %7; @d add.u32 %0, %0, %7; }"
              : "+r"(cnt), "+r"(cn2) : "r"(rv.x), "r"(rv.y), "r"(xs), "r"(ys), "r"(T[j]), "r"(1u << (16 * j)));
        cnt = __reduce_add_sync(0xffffffffu, cnt + cn2);
        asm volatile("{ .reg .pred q; setp.eq.u32 q, %2, 0; @q red.shared.add.u32 [%0], %1; }" :: "r"(ca), "r"(cnt), "r"(cnt & 0x3F00u) : "memory");
        if (!(cnt & 0x3F00u)) break;
        if (bad) rv = ldr64(rsrc);
      }
      TS(16);
      bar_sync(0, 512);
      cnt = lds32(ca);
      if (base == 0) tpub = clock();
      const int gr = rank + __byte_perm(cnt, 0x800u, sh);
      if (gr < 8) {
        uint4* ks = hs + 1152 + gr;
        hs = (uint4*)((char*)hs + gr * 1152);
        asm volatile("{ .reg .b128 t, u; .reg .b64 a, b, c, d; mov.b64 a, {%1,%2}; mov.b64 b, {%3,%4}; mov.b64 c, {%5,%6}; mov.b64 d, {%7,%8}; mov.b128 t, {a, b}; mov.b128 u, {c, d}; "
                     "st.relaxed.gpu.global.b128 [%0], t; st.relaxed.gpu.global.b128 [%0 + 512], u; }"
                     :: "l"(hs), "r"(wr[0]), "r"(wr[1]), "r"(wr[2]), "r"(wr[3]), "r"(wr[4]), "r"(wr[5]), "r"(wr[6]), "r"(wr[7]) : "memory");
        str32((uint32_t*)(hs + 64) - ln * 3, wr[8]);
        LD_HW
        str128(hs + 576, hw[0], hw[1], hw[2], hw[3]); str128(hs + 608, hw[4], hw[5], hw[6], hw[7]); str32((uint32_t*)(hs + 640) - ln * 3, hw[8]);
        if (ln == 0) str32(ks, key);
        rank = 16;
      }
      if (__all_sync(0xffffffffu, (int)(cnt >> 16) + base + 2 >= 8)) break;
    }
    TS(8);
    if (warp < (five ? 12 : 15)) {
#pragma unroll
      for (int k = X_WS; k < 12; k++) ldsm4t(wabase + k * 16 * pitch, wa[k][0], wa[k][1], wa[k][2], wa[k][3]);
    }
    if (warp < 6) while ((int)(clock() - tpub) < X_HD) {}
    TS(19);
    if (warp < 6) { ha[0] = ldr128(hsrc); ha[1] = ldr128(hsrc + 24); ha[2] = ldr128(hsrc + 48); }
    if (rank < X_OR) OUT_ROW
  }
  uint32_t wd[10][4];
  const uint32_t xb = keep(OFF_XS + (ln & 7) * 1168 + (fk * 24 + (ln >> 3)) * 16);
  if (warp >= 7) {
    const uint32_t db = down_box(warp - 7, five) + (ln & 7) * 128;
    mbar_wait(MB_D);
#pragma unroll
    for (int j = 0; j < 4; j++) {
      const uint32_t a = db + (ln >> 4) * 1024 + (((2 * j + ((ln >> 3) & 1)) ^ (ln & 7)) << 4);
      ldsm4t(a, wd[j][0], wd[j][1], wd[j][2], wd[j][3]);
      ldsm4t(a + 2048, wd[4 + j][0], wd[4 + j][1], wd[4 + j][2], wd[4 + j][3]);
    }
#pragma unroll
    for (int j = 0; j < 2; j++) ldsm4t(db + 4096 + (((4 * j + (ln >> 3)) ^ (ln & 7)) << 4), wd[8 + j][0], wd[8 + j][1], wd[8 + j][2], wd[8 + j][3]);
  } else if (warp < 6) {
    const uint32_t xs = keep(OFF_XS + (td + (td / 24) * 49) * 16);
#pragma unroll 1
    for (int it = 0; it < SPIN_MAX; it++) {
      const bool bad = max(max(max(ha[0].x, ha[1].x), max(ha[2].x, ha[2].y)), max(ha[2].z, ha[2].w)) == ~0u;
#pragma unroll
      for (int q = 0; q < 3; q++) sts128(xs + q * 384, ha[q].x, ha[q].y, ha[q].z, ha[q].w);
      if (!__any_sync(0xffffffffu, bad)) break;
      if (bad) { ha[0] = ldr128(hsrc); ha[1] = ldr128(hsrc + 24); ha[2] = ldr128(hsrc + 48); }
    }
  }
  TS(9);

  bar_sync(0, 512);
  if (warp < (five ? 12 : 15)) {
    float d0[4] = {0.f, 0.f, 0.f, 0.f}, d1[4] = {0.f, 0.f, 0.f, 0.f};
#pragma unroll
    for (int k = 0; k < 12; k += 2) {
      uint32_t b0, b1, b2, b3;
      ldsm4(xb + k * 32, b0, b1, b2, b3);
      mma_bf16(d0, wa[k][0], wa[k][1], wa[k][2], wa[k][3], b0, b1);
      mma_bf16(d1, wa[k + 1][0], wa[k + 1][1], wa[k + 1][2], wa[k + 1][3], b2, b3);
    }
    sts128(OFF_RED + td * 16, __float_as_uint(d0[0] + d1[0]), __float_as_uint(d0[1] + d1[1]), __float_as_uint(d0[2] + d1[2]), __float_as_uint(d0[3] + d1[3]));
  }
  TS(26);
  if (warp < 5) {
    const uint32_t rb = OFF_RED + warp * 1536 + ln * 16;
    bar_sync(9, 512);
    const uint4 pa = lds128(rb), pb = lds128(rb + 512), pc = lds128(rb + 1024);
    const float ga = bfr(__uint_as_float(pa.x) + __uint_as_float(pb.x) + __uint_as_float(pc.x));
    const float gb = bfr(__uint_as_float(pa.y) + __uint_as_float(pb.y) + __uint_as_float(pc.y));
    const uint32_t uu = pack_bf(__uint_as_float(pa.z) + __uint_as_float(pb.z) + __uint_as_float(pc.z), __uint_as_float(pa.w) + __uint_as_float(pb.w) + __uint_as_float(pc.w));
    float ra, rb2;
    asm("rcp.approx.ftz.f32 %0, %1;" : "=f"(ra) : "f"(1.f + ex2(ga * -1.4426950408889634f)));
    asm("rcp.approx.ftz.f32 %0, %1;" : "=f"(rb2) : "f"(1.f + ex2(gb * -1.4426950408889634f)));
    const uint32_t act = bf_mul2(pack_bf(ga * ra, gb * rb2), uu);
    sts32(OFF_ACT + td * 4, act);
  } else bar_arrive(9, 512);
  uint4* dst = &p.s->X[c * DM * 2 + (warp - 7) * 64 + tt * 8 + gg];
  asm volatile("" : "+l"(dst));
  bar_sync(8, 512);
  tpub = clock();
  if (warp >= 7) {
    uint32_t b0, b1, b2, b3, b4;
    ldsm4t(OFF_ACT + ln * 16, b0, b1, b2, b3);
    asm volatile("ldmatrix.sync.aligned.m8n8.x1.trans.shared.b16 {%0}, [%1];" : "=r"(b4) : "r"(OFF_ACT + 512 + ln * 16) : "memory");
    float y[4][4];
#pragma unroll
    for (int j = 0; j < 4; j++) {
      y[j][0] = y[j][1] = y[j][2] = y[j][3] = 0.f;
      mma_bf16(y[j], wd[j][0], wd[j][1], wd[j][2], wd[j][3], b0, b1);
    }
#pragma unroll
    for (int j = 0; j < 4; j++) mma_bf16(y[j], wd[4 + j][0], wd[4 + j][1], wd[4 + j][2], wd[4 + j][3], b2, b3);
    if (!five) {
#pragma unroll
      for (int j = 0; j < 4; j++) mma_bf16_k8(y[j], wd[8 + (j >> 1)][2 * (j & 1)], wd[8 + (j >> 1)][2 * (j & 1) + 1], b4);
    }
    str128(dst, (pack_bf(y[0][0], y[0][1]) & ~1u) | 0x10000u, pack_bf(y[0][2], y[0][3]), pack_bf(y[1][0], y[1][1]), pack_bf(y[1][2], y[1][3]));
    str128(dst + 32, (pack_bf(y[2][0], y[2][1]) & ~1u) | 0x10000u, pack_bf(y[2][2], y[2][3]), pack_bf(y[3][0], y[3][1]), pack_bf(y[3][2], y[3][3]));
  }
  TS(10);

  if (c < 72) {
    const uint4* src = &p.s->X[(warp * 4 + tt) * (DM * 2) + c * 8 + gg];
    const int slot = (c & 3) * 2 + (ln >> 4), dw = (c >> 2) * 16 + (ln & 15);
    uint32_t hv = 0, kv = 0, res = 0, rs2 = 0;
    uint32_t* o = p.out;
    if (warp == 0) {
      hv = ~0u;
      SPIN_WHILE(max(hv, kv) == ~0u, hv = ldr32((const uint32_t*)p.s->HS + 2304 + slot * 288 + dw); kv = ldr32(&p.s->HS[1152 + slot]));
      const float r = bf_hi(kv ^ (((int)~kv >> 31) | 0x80000000u));
      float rs;
      asm("rcp.approx.ftz.f32 %0, %1;" : "=f"(rs) : "f"(1.f + ex2(r * -1.4426950408889634f)));
      rs2 = keep(pack_bf(rs, rs));
      res = lds32(OFF_XS + slot * 1168 + dw * 4);
      o += (2047 - (int)(kv & 2047u)) * 288 + dw;
      asm volatile("" : "+l"(o));
    }
    const uint32_t sel = (gg & 1) ? 0x3F800000u : 0x00003F80u;
    const uint32_t q0 = keep((gg >> 1) == 0 ? sel : 0u), q1 = keep((gg >> 1) == 1 ? sel : 0u), q2 = keep((gg >> 1) == 2 ? sel : 0u), q3 = keep((gg >> 1) == 3 ? sel : 0u);
    const uint32_t fa = keep(OFF_RED + warp * 8 + ((gg & 1) * 16 + (gg >> 1) * 4 + tt) * 144), fb = keep(OFF_RED + ln * 144);
    uint4 a0 = make_uint4(0, 0, 0, 0), a1 = a0;
    while ((int)(clock() - tpub) < X_PD) {}
    SPIN_WHILE(!(a0.x & a1.x & 0x10000u), if (!(a0.x & 0x10000u)) a0 = ldr128(src); if (!(a1.x & 0x10000u)) a1 = ldr128(src + 64 * DM * 2));
    float d[4] = {0.f, 0.f, 0.f, 0.f}, e[4] = {0.f, 0.f, 0.f, 0.f}, d2[4] = {0.f, 0.f, 0.f, 0.f}, e2[4] = {0.f, 0.f, 0.f, 0.f};
    mma_bf16(d, q0, q2, q1, q3, a0.x, a0.y); mma_bf16(e, q0, q2, q1, q3, a0.z, a0.w);
    mma_bf16(d2, q0, q2, q1, q3, a1.x, a1.y); mma_bf16(e2, q0, q2, q1, q3, a1.z, a1.w);
    sts64(fa, __float_as_uint(d[0] + e[2] + d2[0] + e2[2]), __float_as_uint(d[1] + e[3] + d2[1] + e2[3]));
    TS(11);
    if (warp == 0) {
      bar_sync(0, 512);
      float2 s[16];
#pragma unroll
      for (int i = 0; i < 16; i += 2) { const uint4 q = lds128(fb + i * 8); s[i] = make_float2(__uint_as_float(q.x), __uint_as_float(q.y)); s[i + 1] = make_float2(__uint_as_float(q.z), __uint_as_float(q.w)); }
#pragma unroll
      for (int k = 1; k < 16; k *= 2)
#pragma unroll
        for (int i = 0; i < 16; i += 2 * k) { s[i].x += s[i + k].x; s[i].y += s[i + k].y; }
      asm volatile("st.global.b32 [%0], %1;" :: "l"(o), "r"(bf_add2(hv, bf_add2(res, bf_mul2(pack_bf(s[0].x, s[0].y), rs2)))) : "memory");
    } else bar_arrive(0, 512);
  }
  TS(12);
  TS_DUMP();
}

typedef CUresult (*EncodeFn)(CUtensorMap*, CUtensorMapDataType, cuuint32_t, void*, const cuuint64_t*, const cuuint64_t*, const cuuint32_t*,
                             const cuuint32_t*, CUtensorMapInterleave, CUtensorMapSwizzle, CUtensorMapL2promotion, CUtensorMapFloatOOBfill);

}

extern "C" void kernel_launch(void* const* d_in, const int* in_sizes, int n_in, void* d_out, int out_size) {
  (void)in_sizes; (void)n_in; (void)out_size;
  static EncodeFn enc = nullptr;
  static Scratch* scratch = nullptr;
  if (!enc) {
    void* fn = nullptr;
    cudaDriverEntryPointQueryResult qr;
    cudaGetDriverEntryPoint("cuTensorMapEncodeTiled", &fn, cudaEnableDefault, &qr);
    enc = (EncodeFn)fn;
    cudaGetSymbolAddress((void**)&scratch, g_S);
    cudaFuncSetAttribute(fused_kernel<false>, cudaFuncAttributeMaxDynamicSharedMemorySize, SMEM_BYTES);
    cudaFuncSetAttribute(fused_kernel<true>, cudaFuncAttributeMaxDynamicSharedMemorySize, SMEM_BYTES);
  }
  TMaps tm;
  for (int i = 0; i < 6; i++) {
    const bool dn = i % 3 == 2;
    const cuuint32_t w = i < 3 ? 40 : 32;
    cuuint64_t gd[3] = {(cuuint64_t)(dn ? 64 : FF), (cuuint64_t)(dn ? FF : DM), 9};
    cuuint64_t gs[2] = {(cuuint64_t)(dn ? DM * 2 : FF * 2), 128};
    cuuint32_t bx[3] = {dn ? 64 : w, dn ? w : 96, i < 3 ? 2u : 3u};
    cuuint32_t es[3] = {1, 1, 1};
    enc(&tm.m[i], CU_TENSOR_MAP_DATA_TYPE_BFLOAT16, dn ? 3 : 2, d_in[11 + i % 3], gd, gs, bx, es, CU_TENSOR_MAP_INTERLEAVE_NONE,
        dn ? CU_TENSOR_MAP_SWIZZLE_128B : i < 3 ? CU_TENSOR_MAP_SWIZZLE_NONE : CU_TENSOR_MAP_SWIZZLE_64B,
        (CUtensorMapL2promotion)X_PROMO, CU_TENSOR_MAP_FLOAT_OOB_FILL_NONE);
  }
  for (int i = 6; i < 10; i++) {
    cuuint64_t gd[3] = {i < 8 ? 32u : 16u, i < 8 ? DM / 2u : DM, NCTA};
    cuuint64_t gs[2] = {i < 8 ? 64u : 32u, DM * 32};
    cuuint32_t bx[3] = {32, 1, (i & 1) ? 128u : 136u};
    cuuint32_t es[3] = {1, 1, 1};
    enc(&tm.m[i], CU_TENSOR_MAP_DATA_TYPE_FLOAT16, 3, scratch->X, gd, gs, bx, es, CU_TENSOR_MAP_INTERLEAVE_NONE, CU_TENSOR_MAP_SWIZZLE_64B,
        CU_TENSOR_MAP_L2_PROMOTION_NONE, CU_TENSOR_MAP_FLOAT_OOB_FILL_NONE);
  }
  Params p;
  p.x = (const unsigned char*)d_in[0];
  bool far = false;
  for (int i = 0; i < 7; i++) {
    p.far[i] = (const unsigned char*)d_in[1 + i];
    const long long d = (long long)((intptr_t)d_in[1 + i] - (intptr_t)d_in[0]);
    p.off[i] = (int)(d / 16);
    if ((long long)p.off[i] * 16 != d || p.off[i] > (1 << 30)) far = true;
  }
  p.dskip = (const uint16_t*)d_in[8];
  p.w_r = (const uint32_t*)d_in[10];
  for (int f = 0; f < 2; f++) {
    static const int kind[17] = {0, 0, 0, 0, 2, 2, 0, 0, 1, 1, 1, 1, 1, 1, 2, 2, 2};
    static const int idx[2][17] = {{2, 3, 4, 5, 6, 8, 0, 1, 0, 1, 2, 3, 4, 5, 0, 2, 4}, {2, 3, 4, 5, 0, -1, 0, 1, 0, 1, 2, 3, 4, 5, 3, -1, 6}};
    static const int blk[2][17] = {{-1, -1, -1, -1, 0, -1, 4, -1, 1, -1, 2, -1, 3, -1, 16, -1, -1}, {-1, -1, -1, -1, 1, -1, 4, -1, -1, -1, 2, -1, 3, -1, 16, -1, -1}};
    const int pitch = f ? 64 : 80;
    for (int u = 0; u < 17; u++) {
      const int s = idx[f][u];
      const uint32_t dst = kind[u] == 0 ? OFF_G + s * 96 * pitch : kind[u] == 2 ? down_box(s, f) : OFF_W + W_BYTES + (s >> 1) * W_BYTES + (s & 1) * 96 * pitch;
      const uint32_t mb = u >= 14 ? (u >= X_HU ? MB_H - OFF_MISC : 0) : blk[f][u] >= 0 ? MB_KF - OFF_MISC + blk[f][u] * 8 : 0;
      p.sched[f][u] = s < 0 ? 3u : kind[u] | s << 2 | mb << 6 | dst << 14;
    }
  }
  p.out = (uint32_t*)d_out;
  p.off[7] = 0;
  p.ts = nullptr;
  p.s = scratch;
  if (far) { fused_kernel<true><<<NCTA, NT, SMEM_BYTES, cudaStreamPerThread>>>(p, tm); return; }
  fused_kernel<false><<<NCTA, NT, SMEM_BYTES, cudaStreamPerThread>>>(p, tm);
}
```

```cpp
#include <cuda_runtime.h>
#include <cuda.h>
#include <cuda_bf16.h>
#include <cuda_fp16.h>
#include <stdint.h>
#include <stddef.h>

namespace {

constexpr int NCTA = 128;
constexpr int NT = 640;
constexpr int DM = 576;
constexpr int FF = 4608;
constexpr int SPIN_MAX = 1 << 20;

struct Scratch {
  uint4 X[NCTA * DM * 2];
  uint4 KX[64 * 128];
  uint4 HS[1152 + 8];
  uint4 R[256];
  uint4 SC[256];
  uint32_t FLAG[NCTA * 8];
};
__device__ Scratch g_S;

#define CLKS(i)
#define TS(i)
#define TSX(i)
#define TS_DUMP()

constexpr int SB = 1024;
constexpr int BOX = 15360;
constexpr int OFF_G = SB;
constexpr int OFF_W = OFF_G + 3 * BOX;
constexpr int W_KT = 26624;
constexpr int W_QT = W_KT + 64 + 2048 + 80;
constexpr int W_L3 = W_KT + 4352;
constexpr int W_CW = W_L3 + 4160;
constexpr int W_MISC = W_CW + 640;
constexpr int W_BYTES = 35840;
constexpr int TILE = 10240;
constexpr int OFF_T = OFF_W + 4 * W_BYTES;
constexpr int ALT = TILE - W_KT;
static_assert(W_MISC + 32 <= W_BYTES && OFF_W % 1024 == 0 && W_BYTES % 1024 == 0 && W_BYTES + ALT <= 20480, "wg block");
constexpr int YT_PITCH = 1184;
constexpr int OFF_YT = OFF_T + 2 * TILE;
constexpr int OFF_WR = OFF_YT + 16 * YT_PITCH + 64;
constexpr int OFF_MISC = OFF_WR + 2304;
constexpr int SMEM_BYTES = OFF_MISC + 1024 - SB;
static_assert(OFF_YT % 16 == 0 && OFF_MISC % 16 == 0, "align");
static_assert(SMEM_BYTES <= 232448, "smem");
constexpr int MB_GU = OFF_MISC;
constexpr int MB_D = OFF_MISC + 8;
constexpr int MB_KF = OFF_MISC + 16;
constexpr int MB_GF = OFF_MISC + 48;
constexpr int MB_SC = OFF_MISC + 56;
constexpr int MB_UL = OFF_MISC + 64;
constexpr int MB_REL = OFF_MISC + 104;
constexpr int MB_GO = OFF_MISC + 112;
constexpr int MB_H = MB_KF + 128;
constexpr int MISC_EPOCH = OFF_MISC + 152;
constexpr int MISC_SW = OFF_MISC + 156;
constexpr int MISC_RT = OFF_MISC + 160;
constexpr int MISC_T0 = OFF_MISC + 296;
constexpr int MISC_EM = OFF_MISC + 288;
constexpr int OFF_PART = OFF_W + 20480;
constexpr int OFF_RK = OFF_PART + 3840;
constexpr int MISC_LN1 = OFF_MISC + 192;
constexpr int OFF_XS = OFF_T;
constexpr int OFF_RED = OFF_T + TILE;
constexpr int OFF_FIN = OFF_W + 3 * W_BYTES + W_KT;
constexpr int OFF_ACT = OFF_FIN + 4096;
constexpr int MISC_CNT = OFF_ACT + 1024;

__device__ __forceinline__ uint32_t smem_u32(const void* p) { return (uint32_t)__cvta_generic_to_shared(p); }
__device__ __forceinline__ uint32_t lds32(uint32_t a) { uint32_t v; asm volatile("ld.shared.b32 %0, [%1];" : "=r"(v) : "r"(a) : "memory"); return v; }
__device__ __forceinline__ uint32_t lds16(uint32_t a) { uint16_t v; asm volatile("ld.shared.u16 %0, [%1];" : "=h"(v) : "r"(a) : "memory"); return v; }
__device__ __forceinline__ uint2 lds64(uint32_t a) { uint2 v; asm volatile("ld.shared.v2.b32 {%0,%1}, [%2];" : "=r"(v.x), "=r"(v.y) : "r"(a) : "memory"); return v; }
__device__ __forceinline__ uint4 lds128(uint32_t a) { uint4 v; asm volatile("ld.shared.v4.b32 {%0,%1,%2,%3}, [%4];" : "=r"(v.x), "=r"(v.y), "=r"(v.z), "=r"(v.w) : "r"(a) : "memory"); return v; }
__device__ __forceinline__ void sts16(uint32_t a, uint32_t v) { asm volatile("st.shared.u16 [%0], %1;" :: "r"(a), "h"((uint16_t)v) : "memory"); }
__device__ __forceinline__ void sts32(uint32_t a, uint32_t v) { asm volatile("st.shared.b32 [%0], %1;" :: "r"(a), "r"(v) : "memory"); }
__device__ __forceinline__ void sts64(uint32_t a, uint32_t x, uint32_t y) { asm volatile("st.shared.v2.b32 [%0], {%1,%2};" :: "r"(a), "r"(x), "r"(y) : "memory"); }
__device__ __forceinline__ void sts128(uint32_t a, uint32_t x, uint32_t y, uint32_t z, uint32_t w) { asm volatile("st.shared.v4.b32 [%0], {%1,%2,%3,%4};" :: "r"(a), "r"(x), "r"(y), "r"(z), "r"(w) : "memory"); }
__device__ __forceinline__ void ldsm4(uint32_t a, uint32_t& r0, uint32_t& r1, uint32_t& r2, uint32_t& r3) {
  asm volatile("ldmatrix.sync.aligned.m8n8.x4.shared.b16 {%0,%1,%2,%3}, [%4];" : "=r"(r0), "=r"(r1), "=r"(r2), "=r"(r3) : "r"(a) : "memory");
}
__device__ __forceinline__ void ldsm4t(uint32_t a, uint32_t& r0, uint32_t& r1, uint32_t& r2, uint32_t& r3) {
  asm volatile("ldmatrix.sync.aligned.m8n8.x4.trans.shared.b16 {%0,%1,%2,%3}, [%4];" : "=r"(r0), "=r"(r1), "=r"(r2), "=r"(r3) : "r"(a) : "memory");
}
__device__ __forceinline__ void stsm4t(uint32_t a, uint32_t r0, uint32_t r1, uint32_t r2, uint32_t r3) {
  asm volatile("stmatrix.sync.aligned.m8n8.x4.trans.shared.b16 [%0], {%1,%2,%3,%4};" :: "r"(a), "r"(r0), "r"(r1), "r"(r2), "r"(r3) : "memory");
}
__device__ __forceinline__ uint4 ldr128(const void* p) {
  unsigned long long lo, hi;
  asm volatile("{ .reg .b128 t; ld.relaxed.gpu.global.b128 t, [%2]; mov.b128 {%0, %1}, t; }" : "=l"(lo), "=l"(hi) : "l"(p) : "memory");
  return make_uint4((uint32_t)lo, (uint32_t)(lo >> 32), (uint32_t)hi, (uint32_t)(hi >> 32));
}
__device__ __forceinline__ void str128(void* p, uint32_t x, uint32_t y, uint32_t z, uint32_t w) {
  asm volatile("{ .reg .b128 t; .reg .b64 lo, hi; mov.b64 lo, {%1,%2}; mov.b64 hi, {%3,%4}; mov.b128 t, {lo, hi}; st.relaxed.gpu.global.b128 [%0], t; }"
               :: "l"(p), "r"(x), "r"(y), "r"(z), "r"(w) : "memory");
}
__device__ __forceinline__ uint32_t ldr32(const void* p) { uint32_t v; asm volatile("ld.relaxed.gpu.global.b32 %0, [%1];" : "=r"(v) : "l"(p) : "memory"); return v; }
__device__ __forceinline__ void str32(void* p, uint32_t v) { asm volatile("st.relaxed.gpu.global.b32 [%0], %1;" :: "l"(p), "r"(v) : "memory"); }
__device__ __forceinline__ void str16(void* p, uint32_t v) { asm volatile("st.relaxed.gpu.global.u16 [%0], %1;" :: "l"(p), "h"((uint16_t)v) : "memory"); }
__device__ __forceinline__ void bar_sync(int id, int n) { asm volatile("bar.sync %0, %1;" :: "r"(id), "r"(n) : "memory"); }
__device__ __forceinline__ void bar_arrive(int id, int n) { asm volatile("bar.arrive %0, %1;" :: "r"(id), "r"(n) : "memory"); }

__device__ __forceinline__ float bf_lo(uint32_t w) { return __uint_as_float(w << 16); }
__device__ __forceinline__ float bf_hi(uint32_t w) { return __uint_as_float(w & 0xFFFF0000u); }
__device__ __forceinline__ uint32_t pack_bf(float lo, float hi) { uint32_t r; asm("cvt.rn.bf16x2.f32 %0, %1, %2;" : "=r"(r) : "f"(hi), "f"(lo)); return r; }
__device__ __forceinline__ uint32_t pack_h(float lo, float hi) { uint32_t r; asm("cvt.rn.f16x2.f32 %0, %1, %2;" : "=r"(r) : "f"(hi), "f"(lo)); return r; }
__device__ __forceinline__ float bfr(float x) { return bf_lo(pack_bf(x, 0.f)); }
__device__ __forceinline__ uint32_t bf_sub2(uint32_t a, uint32_t b) { __nv_bfloat162 r = __hsub2(*(__nv_bfloat162*)&a, *(__nv_bfloat162*)&b); return *(uint32_t*)&r; }
__device__ __forceinline__ uint32_t bf_add2(uint32_t a, uint32_t b) { __nv_bfloat162 r = __hadd2(*(__nv_bfloat162*)&a, *(__nv_bfloat162*)&b); return *(uint32_t*)&r; }
__device__ __forceinline__ uint32_t bf_mul2(uint32_t a, uint32_t b) { __nv_bfloat162 r = __hmul2(*(__nv_bfloat162*)&a, *(__nv_bfloat162*)&b); return *(uint32_t*)&r; }
__device__ __forceinline__ float2 h2f(uint32_t w) { return __half22float2(*(__half2*)&w); }
__device__ __forceinline__ float ex2(float x) { float r; asm("ex2.approx.ftz.f32 %0, %1;" : "=f"(r) : "f"(x)); return r; }
__device__ __forceinline__ float warp_sum(float v) {
#pragma unroll
  for (int o = 16; o > 0; o >>= 1) v += __shfl_xor_sync(0xffffffffu, v, o);
  return v;
}
__device__ __forceinline__ void mma_bf16(float* d, uint32_t a0, uint32_t a1, uint32_t a2, uint32_t a3, uint32_t b0, uint32_t b1) {
  asm volatile("mma.sync.aligned.m16n8k16.row.col.f32.bf16.bf16.f32 {%0,%1,%2,%3}, {%4,%5,%6,%7}, {%8,%9}, {%0,%1,%2,%3};"
               : "+f"(d[0]), "+f"(d[1]), "+f"(d[2]), "+f"(d[3]) : "r"(a0), "r"(a1), "r"(a2), "r"(a3), "r"(b0), "r"(b1));
}
__device__ __forceinline__ void mma_bf16_k8(float* d, uint32_t a0, uint32_t a1, uint32_t b0) {
  asm volatile("mma.sync.aligned.m16n8k8.row.col.f32.bf16.bf16.f32 {%0,%1,%2,%3}, {%4,%5}, {%6}, {%0,%1,%2,%3};"
               : "+f"(d[0]), "+f"(d[1]), "+f"(d[2]), "+f"(d[3]) : "r"(a0), "r"(a1), "r"(b0));
}

__device__ __forceinline__ void wg_fence() { asm volatile("wgmma.fence.sync.aligned;" ::: "memory"); }
__device__ __forceinline__ void wg_commit() { asm volatile("wgmma.commit_group.sync.aligned;" ::: "memory"); }
template <int N> __device__ __forceinline__ void wg_wait() { asm volatile("wgmma.wait_group.sync.aligned %0;" :: "n"(N) : "memory"); }
template <int TB> __device__ __forceinline__ void wgmma32(float* d, const uint32_t* a, uint32_t dlo, uint32_t dhi) {
  asm volatile("{ .reg .b64 dd; mov.b64 dd, {%20, %21}; wgmma.mma_async.sync.aligned.m64n32k16.f32.f16.f16 "
               "{%0,%1,%2,%3,%4,%5,%6,%7,%8,%9,%10,%11,%12,%13,%14,%15}, {%16,%17,%18,%19}, dd, 1, 1, 1, %22; }"
               : "+f"(d[0]), "+f"(d[1]), "+f"(d[2]), "+f"(d[3]), "+f"(d[4]), "+f"(d[5]), "+f"(d[6]), "+f"(d[7]), "+f"(d[8]), "+f"(d[9]), "+f"(d[10]), "+f"(d[11]), "+f"(d[12]), "+f"(d[13]), "+f"(d[14]), "+f"(d[15])
               : "r"(a[0]), "r"(a[1]), "r"(a[2]), "r"(a[3]), "r"(dlo), "r"(dhi), "n"(TB));
}
template <int TB> __device__ __forceinline__ void wgmma64(float* d, const uint32_t* a, uint32_t dlo, uint32_t dhi) {
  asm volatile("{ .reg .b64 dd; mov.b64 dd, {%36, %37}; wgmma.mma_async.sync.aligned.m64n64k16.f32.f16.f16 "
               "{%0,%1,%2,%3,%4,%5,%6,%7,%8,%9,%10,%11,%12,%13,%14,%15,%16,%17,%18,%19,%20,%21,%22,%23,%24,%25,%26,%27,%28,%29,%30,%31}, {%32,%33,%34,%35}, dd, 1, 1, 1, %38; }"
               : "+f"(d[0]), "+f"(d[1]), "+f"(d[2]), "+f"(d[3]), "+f"(d[4]), "+f"(d[5]), "+f"(d[6]), "+f"(d[7]), "+f"(d[8]), "+f"(d[9]), "+f"(d[10]), "+f"(d[11]), "+f"(d[12]), "+f"(d[13]), "+f"(d[14]), "+f"(d[15]), "+f"(d[16]), "+f"(d[17]), "+f"(d[18]), "+f"(d[19]), "+f"(d[20]), "+f"(d[21]), "+f"(d[22]), "+f"(d[23]), "+f"(d[24]), "+f"(d[25]), "+f"(d[26]), "+f"(d[27]), "+f"(d[28]), "+f"(d[29]), "+f"(d[30]), "+f"(d[31])
               : "r"(a[0]), "r"(a[1]), "r"(a[2]), "r"(a[3]), "r"(dlo), "r"(dhi), "n"(TB));
}
template <int TB> __device__ __forceinline__ void wgmma64_init(float* d, const uint32_t* a, uint32_t dlo, uint32_t dhi) {
  asm volatile("{ .reg .b64 dd; mov.b64 dd, {%36, %37}; wgmma.mma_async.sync.aligned.m64n64k16.f32.f16.f16 "
               "{%0,%1,%2,%3,%4,%5,%6,%7,%8,%9,%10,%11,%12,%13,%14,%15,%16,%17,%18,%19,%20,%21,%22,%23,%24,%25,%26,%27,%28,%29,%30,%31}, {%32,%33,%34,%35}, dd, 0, 1, 1, %38; }"
               : "=f"(d[0]), "=f"(d[1]), "=f"(d[2]), "=f"(d[3]), "=f"(d[4]), "=f"(d[5]), "=f"(d[6]), "=f"(d[7]), "=f"(d[8]), "=f"(d[9]), "=f"(d[10]), "=f"(d[11]), "=f"(d[12]), "=f"(d[13]), "=f"(d[14]), "=f"(d[15]), "=f"(d[16]), "=f"(d[17]), "=f"(d[18]), "=f"(d[19]), "=f"(d[20]), "=f"(d[21]), "=f"(d[22]), "=f"(d[23]), "=f"(d[24]), "=f"(d[25]), "=f"(d[26]), "=f"(d[27]), "=f"(d[28]), "=f"(d[29]), "=f"(d[30]), "=f"(d[31])
               : "r"(a[0]), "r"(a[1]), "r"(a[2]), "r"(a[3]), "r"(dlo), "r"(dhi), "n"(TB));
}
template <int TB> __device__ __forceinline__ void wgmma32_init(float* d, const uint32_t* a, uint32_t dlo, uint32_t dhi) {
  asm volatile("{ .reg .b64 dd; mov.b64 dd, {%20, %21}; wgmma.mma_async.sync.aligned.m64n32k16.f32.f16.f16 "
               "{%0,%1,%2,%3,%4,%5,%6,%7,%8,%9,%10,%11,%12,%13,%14,%15}, {%16,%17,%18,%19}, dd, 0, 1, 1, %22; }"
               : "=f"(d[0]), "=f"(d[1]), "=f"(d[2]), "=f"(d[3]), "=f"(d[4]), "=f"(d[5]), "=f"(d[6]), "=f"(d[7]), "=f"(d[8]), "=f"(d[9]), "=f"(d[10]), "=f"(d[11]), "=f"(d[12]), "=f"(d[13]), "=f"(d[14]), "=f"(d[15])
               : "r"(a[0]), "r"(a[1]), "r"(a[2]), "r"(a[3]), "r"(dlo), "r"(dhi), "n"(TB));
}
__device__ __forceinline__ void wgmma64h(uint32_t* d, uint32_t a0, uint32_t a1, uint32_t a2, uint32_t a3, uint32_t dlo, uint32_t dhi) {
  asm volatile("{ .reg .b64 dd; mov.b64 dd, {%20, %21}; wgmma.mma_async.sync.aligned.m64n64k16.f16.f16.f16 "
               "{%0,%1,%2,%3,%4,%5,%6,%7,%8,%9,%10,%11,%12,%13,%14,%15}, {%16,%17,%18,%19}, dd, 1, 1, 1, 0; }"
               : "+r"(d[0]), "+r"(d[1]), "+r"(d[2]), "+r"(d[3]), "+r"(d[4]), "+r"(d[5]), "+r"(d[6]), "+r"(d[7]), "+r"(d[8]), "+r"(d[9]), "+r"(d[10]), "+r"(d[11]), "+r"(d[12]), "+r"(d[13]), "+r"(d[14]), "+r"(d[15])
               : "r"(a0), "r"(a1), "r"(a2), "r"(a3), "r"(dlo), "r"(dhi));
}
__device__ __forceinline__ void wgmma64h_init(uint32_t* d, uint32_t a0, uint32_t a1, uint32_t a2, uint32_t a3, uint32_t dlo, uint32_t dhi) {
  asm volatile("{ .reg .b64 dd; mov.b64 dd, {%20, %21}; wgmma.mma_async.sync.aligned.m64n64k16.f16.f16.f16 "
               "{%0,%1,%2,%3,%4,%5,%6,%7,%8,%9,%10,%11,%12,%13,%14,%15}, {%16,%17,%18,%19}, dd, 0, 1, 1, 0; }"
               : "=r"(d[0]), "=r"(d[1]), "=r"(d[2]), "=r"(d[3]), "=r"(d[4]), "=r"(d[5]), "=r"(d[6]), "=r"(d[7]), "=r"(d[8]), "=r"(d[9]), "=r"(d[10]), "=r"(d[11]), "=r"(d[12]), "=r"(d[13]), "=r"(d[14]), "=r"(d[15])
               : "r"(a0), "r"(a1), "r"(a2), "r"(a3), "r"(dlo), "r"(dhi));
}
__device__ __forceinline__ void wgmma40_ss(float* d, uint32_t alo, uint32_t blo, uint32_t hi) {
  asm volatile("{ .reg .b64 da, db; mov.b64 da, {%20, %22}; mov.b64 db, {%21, %22}; "
               "wgmma.mma_async.sync.aligned.m64n40k16.f32.f16.f16 {%0,%1,%2,%3,%4,%5,%6,%7,%8,%9,%10,%11,%12,%13,%14,%15,%16,%17,%18,%19}, da, db, 1, 1, 1, 1, 1; }"
               : "+f"(d[0]), "+f"(d[1]), "+f"(d[2]), "+f"(d[3]), "+f"(d[4]), "+f"(d[5]), "+f"(d[6]), "+f"(d[7]), "+f"(d[8]), "+f"(d[9]), "+f"(d[10]), "+f"(d[11]), "+f"(d[12]), "+f"(d[13]), "+f"(d[14]), "+f"(d[15]), "+f"(d[16]), "+f"(d[17]), "+f"(d[18]), "+f"(d[19])
               : "r"(alo), "r"(blo), "r"(hi));
}
__device__ __forceinline__ void wgmma40_ss_init(float* d, uint32_t alo, uint32_t blo, uint32_t hi) {
  asm volatile("{ .reg .b64 da, db; mov.b64 da, {%20, %22}; mov.b64 db, {%21, %22}; "
               "wgmma.mma_async.sync.aligned.m64n40k16.f32.f16.f16 {%0,%1,%2,%3,%4,%5,%6,%7,%8,%9,%10,%11,%12,%13,%14,%15,%16,%17,%18,%19}, da, db, 0, 1, 1, 1, 1; }"
               : "=f"(d[0]), "=f"(d[1]), "=f"(d[2]), "=f"(d[3]), "=f"(d[4]), "=f"(d[5]), "=f"(d[6]), "=f"(d[7]), "=f"(d[8]), "=f"(d[9]), "=f"(d[10]), "=f"(d[11]), "=f"(d[12]), "=f"(d[13]), "=f"(d[14]), "=f"(d[15]), "=f"(d[16]), "=f"(d[17]), "=f"(d[18]), "=f"(d[19])
               : "r"(alo), "r"(blo), "r"(hi));
}
__device__ __forceinline__ void tma_box(uint32_t dst, const CUtensorMap* tm, uint32_t mb, int x, int y) {
  asm volatile("cp.async.bulk.tensor.2d.shared::cluster.global.mbarrier::complete_tx::bytes [%0], [%1, {%3, %4}], [%2];"
               :: "r"(dst), "l"(tm), "r"(mb), "r"(x), "r"(y) : "memory");
}
__device__ __forceinline__ uint32_t uni(uint32_t v) {
  uint32_t r; asm volatile("shfl.sync.idx.b32 %0, %1, 0, 0x1f, 0xffffffff;" : "=r"(r) : "r"(v)); return r;
}
__device__ __forceinline__ uint32_t pin(uint32_t v) {
  uint32_t r; asm volatile("shfl.sync.bfly.b32 %0, %1, 0, 0x1f, 0xffffffff;" : "=r"(r) : "r"(v)); return r;
}

struct Params {
  const unsigned char* x;
  Scratch* s;
  int off[8];
  uint32_t* out;
  const uint16_t* dskip;
  const uint32_t* w_r;
  long long* ts;
  const unsigned char* far[7];
  uint32_t sched[2][17];
};
__device__ __forceinline__ uint32_t ldnc32(const void* p) { uint32_t v; asm volatile("ld.global.nc.b32 %0, [%1];" : "=r"(v) : "l"(p)); return v; }
__device__ __forceinline__ uint32_t ldnc16(const void* p) { uint16_t v; asm volatile("ld.global.nc.u16 %0, [%1];" : "=h"(v) : "l"(p)); return v; }
__device__ __forceinline__ void mbar_wait(uint32_t mb, uint32_t ph = 0) {
#pragma unroll 1
  for (int it = 0; it < SPIN_MAX; it++) {
    uint32_t ok;
    asm volatile("{ .reg .pred q; mbarrier.try_wait.parity.shared::cta.b64 q, [%1], %2; selp.u32 %0, 1, 0, q; }" : "=r"(ok) : "r"(mb), "r"(ph) : "memory");
    if (ok) break;
  }
}
__device__ __forceinline__ void mbar_arrive(uint32_t mb) { asm volatile("mbarrier.arrive.shared::cta.b64 _, [%0];" :: "r"(mb) : "memory"); }
__device__ __forceinline__ void fence_async() { asm volatile("fence.proxy.async.shared::cta;" ::: "memory"); }
#define SPIN_WHILE(cond, body) _Pragma("unroll 1") for (int _it = 0; _it < SPIN_MAX && __any_sync(0xffffffffu, (cond)); _it++) { body; }

struct LnC { uint32_t m2, rh2, rl2; };
__device__ __forceinline__ LnC ln_consts(float s, float q, float& r) {
  const float mean = s * (1.f / DM);
  const float var = fmaxf(fmaf(-mean, mean, q * (1.f / DM)), 0.f);
  float sd;
  asm("sqrt.approx.ftz.f32 %0, %1;" : "=f"(sd) : "f"(bfr(bfr(var) + 1e-5f)));
  asm("rcp.approx.ftz.f32 %0, %1;" : "=f"(r) : "f"(bfr(sd)));
  LnC c;
  c.m2 = pack_bf(mean, mean);
  c.rh2 = pack_bf(r, r);
  const float rl = r - bf_lo(c.rh2);
  c.rl2 = pack_bf(rl, rl);
  return c;
}
__device__ __forceinline__ uint32_t bf_fma2(uint32_t a, uint32_t b, uint32_t c) {
  __nv_bfloat162 r = __hfma2(*(const __nv_bfloat162*)&a, *(const __nv_bfloat162*)&b, *(const __nv_bfloat162*)&c);
  return *(uint32_t*)&r;
}
__device__ __forceinline__ uint32_t ln_apply(uint32_t w, uint32_t m2, uint32_t rh2, uint32_t rl2) {
  const uint32_t d = bf_sub2(w, m2);
  return bf_fma2(d, rh2, bf_mul2(d, rl2));
}

__device__ __forceinline__ float2 cis(float mag_log2, float rev) {
  const float m = ex2(mag_log2), ang = rev * 6.283185307179586f;
  return make_float2(m * __cosf(ang), m * __sinf(ang));
}
__device__ __forceinline__ float2 csq(float2 a) { return make_float2(fmaf(a.x, a.x, -a.y * a.y), (a.x + a.x) * a.y); }
__device__ __forceinline__ float2 cmul(float2 a, float2 b) { return make_float2(fmaf(a.x, b.x, -a.y * b.y), fmaf(a.x, b.y, a.y * b.x)); }
__device__ __forceinline__ void pmul(uint32_t xr, uint32_t xi, uint32_t w, uint32_t& yr, uint32_t& yi) {
  const __half2 XR = *(__half2*)&xr, XI = *(__half2*)&xi, W = *(__half2*)&w;
  const __half2 a = __hfma2(__hneg2(XI), __high2half2(W), __hmul2(XR, __low2half2(W)));
  const __half2 b = __hfma2(XI, __low2half2(W), __hmul2(XR, __high2half2(W)));
  yr = *(const uint32_t*)&a; yi = *(const uint32_t*)&b;
}
__device__ __forceinline__ uint32_t pk(float2 a) { return pack_h(a.x, a.y); }

struct KgState { float2 c0, z8; float kl; uint32_t w64, w128, w192; };
__device__ __forceinline__ void kgen_tables_n(const uint32_t (&raw)[7], uint32_t scr, int wt, KgState& k) {
  const uint32_t dst = scr + 16384 + wt * 16;
  const float dt = bfr(ex2(bf_lo(raw[6]) * 1.4426950408889634f));
  const float th = dt * bf_lo(raw[1]);
  const float br = dt * bf_lo(raw[2]), bi = dt * bf_lo(raw[3]);
  const float Cr = bf_lo(raw[4]), Ci = bf_lo(raw[5]);
  k.c0 = make_float2(fmaf(Cr, br, -Ci * bi), fmaf(Cr, bi, Ci * br));
  const uint32_t mx = __reduce_max_sync(0xffffffffu, __float_as_uint(fmaxf(fabsf(k.c0.x), fabsf(k.c0.y))));
  const float a2 = dt * bf_lo(raw[0]) * 1.4426950408889634f;
  const float rh = th * 0.15915494309189535f;
  const float rl = fmaf(th, (float)(0.15915494309189535 - (double)0.15915494309189535f), fmaf(th, 0.15915494309189535f, -rh));
  const float rf = rh - rintf(rh);
  const float2 z1 = cis(a2, rf + rl);
  const float p64 = rf * 64.f;
  const float2 z64 = cis(a2 * 64.f, fmaf(64.f, rl, p64 - rintf(p64)));
  const float2 z2 = csq(z1), z128 = csq(z64), z3 = cmul(z2, z1), z4 = csq(z2), z256 = csq(z128), z6 = csq(z3), z512 = csq(z256);
  k.z8 = csq(z4);
  k.w64 = pk(z64); k.w128 = pk(z128); k.w192 = pk(cmul(z128, z64));
  sts128(dst, 0x00003C00u, pk(z2), pk(z4), pk(z6));
  const float2 z1024 = csq(z512), z768 = cmul(z512, z256);
  sts128(dst + 2048, pk(z1), pk(z3), pk(cmul(z4, z1)), pk(cmul(z4, z3)));
  const float2 z2048 = csq(z1024);
  k.kl = fmaf(k.c0.x, z2048.x, -k.c0.y * z2048.y);
  sts128(dst + 4096, pk(z256), pk(cmul(z256, z2)), pk(cmul(z256, z4)), pk(cmul(z256, z6)));
  sts128(dst + 6144, pk(z512), pk(cmul(z512, z4)), pk(z768), pk(cmul(z768, z4)));
  sts128(dst + 8192, pk(z1024), pk(cmul(z1024, z256)), pk(cmul(z1024, z512)), pk(cmul(z1024, z768)));
  sts32(scr + W_MISC + (wt >> 5) * 4, mx);
}
__device__ __forceinline__ int kgen_tables_m(uint32_t scr, int wt, const KgState& k) {
  const uint32_t dst = scr + wt * 16;
  const uint4 e4 = lds128(scr + W_MISC);
  const float2 z16 = csq(k.z8), z32 = csq(z16);
  const int em = max(min((int)(max(max(e4.x, e4.y), max(e4.z, e4.w)) >> 23), 238), 16);
  const float sc = __uint_as_float((uint32_t)(127 + 4 + 127 - em) << 23);
  sts32(scr + W_MISC + 16 + (wt >> 5) * 4, __reduce_add_sync(0xffffffffu, __float2int_rn(k.kl * sc * 262144.f)));
  const float2 c0 = make_float2(k.c0.x * sc, k.c0.y * sc);
  const float2 c1 = cmul(c0, k.z8), c2 = cmul(c0, z16), c4 = cmul(c0, z32), c3 = cmul(c1, z16), c5 = cmul(c1, z32), c6 = cmul(c2, z32), c7 = cmul(c3, z32);
  uint32_t pr[4], pi[4], yr[4], yi[4];
  pr[0] = pack_h(c0.x, c1.x); pi[0] = pack_h(c0.y, c1.y);
  pr[1] = pack_h(c2.x, c3.x); pi[1] = pack_h(c2.y, c3.y);
  pr[2] = pack_h(c4.x, c5.x); pi[2] = pack_h(c4.y, c5.y);
  pr[3] = pack_h(c6.x, c7.x); pi[3] = pack_h(c6.y, c7.y);
  sts128(dst, pr[0], pr[1], pr[2], pr[3]); sts128(dst + 2048, pi[0], pi[1], pi[2], pi[3]);
#pragma unroll
  for (int q = 1; q < 4; q++) {
    const uint32_t w = q == 1 ? k.w64 : q == 2 ? k.w128 : k.w192;
#pragma unroll
    for (int i = 0; i < 4; i++) pmul(pr[i], pi[i], w, yr[i], yi[i]);
    sts128(dst + q * 4096, yr[0], yr[1], yr[2], yr[3]); sts128(dst + q * 4096 + 2048, yi[0], yi[1], yi[2], yi[3]);
  }
  return em;
}
__device__ __forceinline__ uint32_t lds32_if(uint32_t a, bool on) {
  uint32_t v; asm volatile("{ .reg .pred q; setp.ne.u32 q, %2, 0; mov.b32 %0, 0; @q ld.shared.b32 %0, [%1]; }" : "=r"(v) : "r"(a), "r"((uint32_t)on) : "memory"); return v;
}
__device__ __forceinline__ uint32_t prmt(uint32_t a, uint32_t b, uint32_t s) { uint32_t r; asm("prmt.b32 %0, %1, %2, %3;" : "=r"(r) : "r"(a), "r"(b), "r"(s)); return r; }
#define X_BC 1
struct BuildC { uint32_t a3, a2, az, cw, sel; };
__device__ __forceinline__ BuildC build_consts(int wt) {
  const int ix = ((wt >> 2) + (wt & 3) * 32 - 1) & 127;
  BuildC b;
  b.a3 = W_CW + 32 + ((ix & 1) ? 0 : 304) + (ix >> 1) * 4;
  b.a2 = W_L3 + 3072 + 544 + (wt & ~3) * 2 + (wt & 1) * 4 + (wt & 2) * 128;
  b.az = W_KT + (wt < 36 ? -512 : 64 + 4128 - 576) + wt * 16;
  b.cw = W_CW + 32 + (wt >> 6) * 48 + wt * 4;
  b.sel = (wt & 1) ? 0x10767610 : wt ? 0x10101010 : 0x10107610;
  if (X_BC) { b.a3 = pin(b.a3); b.a2 = pin(b.a2); b.az = pin(b.az); b.cw = pin(b.cw); b.sel = pin(b.sel); }
  return b;
}
__device__ __forceinline__ void kgen_build(uint32_t tb, const BuildC& bc, int wg, int wt, uint32_t k0, uint32_t k1, uint32_t k2) {
  const uint32_t kt = tb + W_KT, sc = tb + W_L3 + 3072;
  const uint32_t a3 = tb + bc.a3, a2 = tb + bc.a2;
  const uint32_t v3 = wt ? k2 : k2 >> 16;
  sts32(sc + 4 + wt * 4, __byte_perm(k0, k1, 0x5432));
  sts16(a2, k1 >> 16); sts16(a2 + 6, k1 >> 16);
  sts16(a3, v3); sts16(a3 + 6, v3);
  if ((unsigned)(wt - 32) < 14u) sts128(tb + bc.az, 0, 0, 0, 0);
  if (wt == 127) sts32(sc, k0 & 0xFFFF0000u);
  if (wt == 0) { sts32(sc + 516, k1); sts16(sc + 1056, k2); }
  bar_sync(1 + wg, 128);
  const uint32_t cw = tb + bc.cw, g2 = sc + 540 + wt * 4;
  const bool odd = wt & 1, ends = (unsigned)(wt - 4) >= 120u;
  const uint32_t pv = lds32(sc + wt * 4), nx = lds32(sc + 8 + wt * 4), nc = lds32_if(g2 + 8, ends);
  const uint32_t l0 = lds32(cw), l1 = lds32(cw - 8), l2 = lds32(cw - 16), l3 = lds32(cw - 24), q0 = lds32(g2), q1 = lds32(g2 + 128), q2 = lds32(g2 - 8), q3 = lds32(g2 + 120);
  sts64(kt + 64 + wt * 8, __byte_perm(k0, pv, 0x5410), __byte_perm(k0, 0, 0x1032));
  sts64(kt + 64 + 1024 + wt * 8, prmt(k1, pv, bc.sel), prmt(k1, nx, bc.sel >> 16));
  const uint32_t cc = __byte_perm(nc, 0, 0x3232), nn = __byte_perm(nc, 0, 0x1010);
  if (ends) sts128(kt + 64 + 2048 + wt * 16, cc, cc, odd ? nc : cc, odd ? nn : nc);
  if (wt == 127) { sts128(kt + 64 + 4096, nn, nn, nn, nn); sts128(kt + 64 + 4112, nn, nn << 16, 0, 0); }
  sts128(tb + W_L3 + 512 + (wt >> 6) * 512 + wt * 16, l0, l1, l2, l3);
  if ((wt & 63) < 34) sts128(tb + W_QT - 16 + wt * 16, q0, q1, q2, q3);
}

__device__ __forceinline__ void load_a(uint32_t (&a)[4], uint32_t kp, int j) {
  a[0] = lds32(kp + 64 * j); a[1] = lds32(kp + 64 * j + 512); a[2] = lds32(kp + 64 * j - 32); a[3] = lds32(kp + 64 * j + 480);
}
__device__ __forceinline__ uint32_t band8(int s) { return ((((0x1FFu << 20) >> s) & 0x01010101u) | (((0x7Fu << 25) >> s) & 0x10101010u)) * 0x01020408u; }
__device__ __forceinline__ uint32_t hadd2u(uint32_t a, uint32_t b) { __half2 r = __hadd2(*(__half2*)&a, *(__half2*)&b); return *(uint32_t*)&r; }

__device__ __forceinline__ void zero_pads(uint32_t tb, int wt) {
  if (!(wt & 32)) sts128(tb + W_L3 + (wt >> 6) * 512 + wt * 16, 0, 0, 0, 0);
  if ((wt & 63) < 3) sts128(tb + W_CW + (wt >> 6) * 304 + (wt & 63) * 16, 0, 0, 0, 0);
}
__device__ __forceinline__ uint32_t tr_base(int lane) {
  return OFF_YT + (2 * (lane >> 3) + (lane & 1)) * YT_PITCH + ((lane >> 1) & 1) * (8 * YT_PITCH + 64) + ((lane >> 2) & 1) * 16;
}

__device__ __forceinline__ uint32_t sc_addr(int tp) { return OFF_YT + (tp < 16 ? tp * YT_PITCH + (tp >> 3) * 64 + 1152 : 8 * YT_PITCH - 512 + tp * 32); }
#define X_PW 15
#define X_HU 16
#define X_PN 1
#define X_NE 2
#define X_SCT 10000
#define X_DELTA 0
#define X_DSTEP 2000
#define X_PF0 2700
#define X_PFD 600
#define X_TD 450
#define X_WS 6
#define X_OR 8
#define X_ABS 4870
#define X_XD 200
#define X_RD 630
#define X_HD 450
#define X_PD 1170
#define X_PROMO 2
#define X_YD2 1000
#define X_GO 1
#define X_GW 2
#define X_NS 4300
#define X_XS 13450
#define X_LAG 1300
#define X_YD 1550
struct TMaps { CUtensorMap m[10]; };
__device__ __forceinline__ uint32_t h2bf(uint32_t w) { const float2 f = h2f(w); return pack_bf(f.x, f.y); }
__device__ __forceinline__ uint32_t keep(uint32_t v) { asm volatile("" : "+r"(v)); return v; }
__device__ __forceinline__ uint2 ldr64(const void* p) { uint2 v; asm volatile("{ .reg .b64 t; ld.relaxed.gpu.global.b64 t, [%2]; mov.b64 {%0, %1}, t; }" : "=r"(v.x), "=r"(v.y) : "l"(p) : "memory"); return v; }
__host__ __device__ __forceinline__ uint32_t down_box(int s, bool five) {
  return five ? OFF_W + W_BYTES + 12288 + (s / 3) * (W_BYTES - 12288) + s * 4096 : s < 6 ? OFF_W + W_BYTES + BOX + (s >> 1) * (W_BYTES - 10240) + s * 5120 : OFF_W + (s - 6) * 5120;
}
__device__ __forceinline__ void load_tile(const CUtensorMap* tmx, int i, int c, int again = 0) {
  asm volatile("mbarrier.arrive.expect_tx.shared::cta.b64 _, [%0], 8704;" :: "r"(MB_UL + i * 16 + again) : "memory");
  asm volatile("cp.async.bulk.tensor.3d.shared::cluster.global.mbarrier::complete_tx::bytes [%0], [%1, {%3, %4, %5}], [%2];"
               :: "r"(i < 2 ? OFF_T + i * TILE : OFF_W), "l"(tmx), "r"(MB_UL + i * 16 + again), "r"(0), "r"(c), "r"(-8) : "memory");
}
template <bool FAR> __device__ __forceinline__ void load_params(const Params& p, uint32_t ch, int wt, uint32_t dst, bool on) {
  const int rel = wt < 96 ? ch * 16 + (wt & 15) : ch >> 3;
  const unsigned char* b = FAR ? p.far[min(wt >> 4, 6)] + rel * 16 : p.x + (long long)(p.off[wt >> 4] + rel) * 16;
  asm volatile("{ .reg .pred q; setp.ne.u32 q, %2, 0; @q cp.async.cg.shared.global [%0], [%1], 16; }"
               :: "r"(dst + wt * 16), "l"(b), "r"((uint32_t)(on && wt < 97)) : "memory");
}

struct ConvC { uint32_t ca, cb, bands, qa; };
__device__ __forceinline__ ConvC conv_consts(int w, int lane) {
  const int h = w & 1, P = (w >> 1) & 1, d0 = 8 * h + (lane >> 2) - 2 * (lane & 3);
  ConvC k;
  k.ca = keep((W_KT + (16 + 256 * P + d0) * 4) | (((8 + 64 * P + lane) * 64 + (((h + ((w >> 1) & 2)) ^ (lane >> 1)) & 3) * 16) << 16));
  const int u = d0 + 2 * (lane & 1) + 2, in = (u & 7) - ((u & 7) >= 5 ? 5 : 0) - 2 * (lane & 1);
  k.cb = keep(in > 0 ? 0x1010 : in == 0 ? 0x3210 : 0x3232);
  k.qa = keep(W_QT + (2 * (u >> 3) + ((u & 7) >= 5) + 64 * P) * 16);
  k.bands = keep(__byte_perm(band8(d0 + 8), band8(d0 + 7), 0x7733) & 0x00FF00FFu);
  return k;
}
struct ConvPre { uint32_t e0, e2, f2, b0, b2, a[3][4]; };
__device__ __forceinline__ void conv_pre(ConvPre& r, uint32_t kp, uint32_t qp, int part, bool on, bool P) {
  if (part & 1) {
    r.e0 = lds32_if(kp + 4096, on && !P); r.e2 = lds32_if(kp + 4064, on && !P); r.f2 = lds32_if(kp + 4128, on && !P);
    r.b0 = lds32_if(kp + 2048, on && !P); r.b2 = lds32_if(kp + 2016, on && !P);
  }
#pragma unroll
  for (int j = 0; j < 3; j++) if (part & (j < 1 ? 1 : 2))
    asm volatile("{ .reg .pred q; setp.ne.u32 q, %5, 0; mov.b32 %0, 0; mov.b32 %1, 0; mov.b32 %2, 0; mov.b32 %3, 0; @q ld.shared.v4.b32 {%0,%1,%2,%3}, [%4]; }"
                 : "=r"(r.a[j][0]), "=r"(r.a[j][1]), "=r"(r.a[j][2]), "=r"(r.a[j][3]) : "r"(qp + 64 * j), "r"((uint32_t)on) : "memory");
}
__device__ __forceinline__ void conv_item(uint32_t tb, uint32_t tl, int bid, int bn, ConvPre& pre, const ConvC& cv, uint32_t zero, const CUtensorMap* tmx, int ch, int warp, int lane, bool hold, bool more) {
  const bool go = more && warp == 0 && lane == 0;
  const uint32_t kp = tb + (cv.ca & 0xFFFFu), qp = tb + cv.qa;
  const uint32_t dlo = (tl >> 4) + 32 + ((warp >> 1) & 2) + (1u << 16), dhi = 32u | (2u << 30);
  const bool P = warp & 2;
  float a32[16], b32[16], a64[32];
  uint32_t A[40][4];
#define STEP(J) { wgmma64<0>(a64, A[J], dlo + 256 - 4 * (J), dhi); \
    if ((J) == 32) wgmma32_init<0>(b32, A[J], dlo, dhi); else wgmma32<0>(b32, A[J], ((J) < 8 ? dlo ^ zero : dlo) + 128 - 4 * (J), dhi); \
    if ((J) == 0) wgmma32_init<0>(a32, A[J], dlo, dhi); else if ((J) < 8) wgmma32<0>(a32, A[J], (dlo ^ zero) - 4 * (J), dhi); }
#define LD(J) load_a(A[J], kp, J);
#define LQ(J) { const uint4 v = lds128(qp + 64 * ((J) - 32)); A[J][0] = v.x; A[J][1] = v.y; A[J][2] = v.z; A[J][3] = v.w; }
#define PQ(J) { A[J][0] = prmt(A[J][0], 0, cv.cb); A[J][1] = prmt(A[J][1], 0, cv.cb); A[J][2] = prmt(A[J][2], 0, cv.cb); A[J][3] = prmt(A[J][3], 0, cv.cb); }
#define FIRST(J) wg_fence(); STEP(J) wg_commit(); wg_wait<1>(); wg_fence();
  {
    uint32_t win[16], x9[4], x7[4], e[4], f[4];
    const uint32_t bz = keep(cv.bands);
#define BAND(i) keep((bz & (0x10001u << (i))) * (0x3C00u >> (i)))
    e[0] = pre.e0; e[2] = pre.e2; e[1] = keep(bz & 0x100u); e[3] = keep(bz & 0x200u);
    f[2] = pre.f2; f[0] = keep(bz & 0x4000u); f[1] = keep(bz & 0x8000u); f[3] = keep(bz & 0x300u);
#pragma unroll
    for (int j = 0; j < 12; j++) A[32 + j / 4][j & 3] = pre.a[j / 4][j & 3];
    PQ(32) PQ(33) PQ(34)
    if (!P) { A[32][0] = pre.b0; A[32][2] = pre.b2; }
    const uint32_t q[12] = {BAND(0), BAND(5), keep(bz & 0x400u), BAND(4), BAND(2), BAND(7), BAND(1), BAND(6), keep(bz & 0x800u), keep(bz & 0x1000u), BAND(3), keep(bz & 0x2000u)};
#undef BAND
    const uint32_t ta = keep(tl + 512 + (warp & 3) * 2048 + lane * 64 + (lane & 6) * 8);
    if (X_GO && hold) mbar_wait(MB_GO);
    uint32_t mbl = MB_UL + (warp & 8) * 2, ph = 0;
#pragma unroll 1
    for (int it = 0; it < SPIN_MAX; it++) {
      if (ch < 512) mbar_wait(mbl, ph);
      if (it == 1) TS(13);
      TS(3);
      wg_fence();
      wgmma64h_init(win, q[0], q[1], q[2], q[3], dlo, dhi);
      wgmma64h(win, q[4], q[5], q[6], q[7], dlo - 4, dhi);
      wgmma64h(win, q[8], q[9], q[10], q[11], dlo - 8, dhi);
      wg_commit();
      wgmma64_init<0>(a64, e, dlo, dhi);
      wgmma64<0>(a64, f, dlo - 4, dhi);
      wg_commit();
      if (ch >= 512) break;
      uint32_t r0, r1, r2, r3, ok;
      if (warp & 4) {
        mbar_wait(mbl + 8);
        if (__all_sync(0xffffffffu, it || lds32(MISC_RT + (warp & 8)) == 0)) break;
        wg_wait<0>();
        continue;
      }
      ldsm4(ta, r0, r1, r2, r3);
      ok = r0 & r1 & r2 & r3;
      ldsm4(ta ^ 32, r0, r1, r2, r3);
      asm volatile("{ .reg .pred q; setp.ne.u32 q, %1, 0; barrier.red.and.pred q, %2, 128, q; selp.u32 %0, 1, 0, q; }" : "=r"(ok) : "r"((ok & r0 & r1 & r2 & r3 & 1u) | (lane & 3)), "r"(1 + (warp >> 2)) : "memory");
      if (ok) { if ((warp & 3) == 0 && lane == 0) { sts32(MISC_RT + warp, it); mbar_arrive(MB_UL + 8 + warp * 2); } break; }
      wg_wait<0>();
      if ((warp & 3) == 0 && lane == 0) load_tile(tmx - 1, warp >> 3, ch, 56);
      mbl = MB_UL + 56 + (warp & 8) * 2; ph = it & 1;
    }
    wg_wait<1>();
#pragma unroll
    for (int i = 0; i < 4; i++) {
      const int tl = 2 * ((i & 1) + ((i & 2) ? 0 : 4));
      x9[i] = P ? win[tl + 4] : win[tl]; x7[i] = P ? win[tl + 5] : win[tl + 1];
    }
    const uint32_t l3lo = ((tb + W_L3) >> 4) + (32u << 16);
    wg_fence();
    wgmma64<0>(a64, x9, l3lo, 8);
    wgmma64<0>(a64, x7, l3lo + 96, 8);
    wg_commit();
  }
  STEP(32) STEP(33) STEP(34) wg_commit(); wg_wait<1>();
  LQ(35) LQ(36) LQ(37) LQ(38) LQ(39) LD(0) PQ(35) PQ(36) PQ(37) PQ(38) PQ(39)
  FIRST(35) STEP(36) STEP(37) STEP(38) wg_commit(); STEP(39) wg_commit();
  LD(1) LD(2) LD(3)
  if (X_GO == 1 && go) mbar_arrive(MB_GO);
  wg_wait<1>(); wg_fence(); STEP(0) wg_commit(); STEP(1) wg_commit(); STEP(2) wg_commit(); wg_wait<2>();
  LD(4) LD(5)
  wg_fence(); STEP(3) wg_commit(); wg_wait<1>();
  LD(6) LD(7)
  wg_fence(); STEP(4) STEP(5) wg_commit();
  wg_fence(); STEP(6) STEP(7) wg_commit();
#undef STEP
#undef LD
#undef LQ
#undef PQ
#undef FIRST
  TS(18);
  if (X_GO == 3 && go) mbar_arrive(MB_GO);
  const uint32_t xc = tb + W_KT + (warp & 3) * 1024 + lane * 16;
  if (more) bar_sync(7, 288);
  wg_wait<1>();
  conv_pre(pre, kp + ALT, qp + ALT, 1, more, P);
  wg_wait<0>();
  conv_pre(pre, kp + ALT, qp + ALT, 2, more, P);
  uint32_t E[16], o[8];
#define ACC(i) ((i) < 16 ? a32[i] : (i) < 32 ? b32[(i) - 16] : a64[(i) - 32])
  E[0] = pack_h(a32[0], a32[1]);
#pragma unroll
  for (int i = 1; i < 16; i++) E[i] = pack_h(ACC(4 * i) + ACC(4 * i - 2), ACC(4 * i + 1) + ACC(4 * i - 1));
#undef ACC
#pragma unroll
  for (int j = 0; j < 8; j++) o[j] = P ? (j < 2 ? 0u : E[j - 2]) : E[8 + j];
  sts128(xc, o[0], o[1], o[2], o[3]); sts128(xc + 512, o[4], o[5], o[6], o[7]);
#pragma unroll
  for (int j = 0; j < 8; j++) o[j] = P ? E[6 + j] : E[j];
  TS(25);
  if (more) {
    sts128(xc + 4096, o[0], o[1], o[2], o[3]); sts128(xc + 4608, o[4], o[5], o[6], o[7]);
    bar_arrive(12, 192);
    return;
  }
  bar_sync(1 + (warp >> 2), 128);
  const uint4 vv[2] = {lds128(xc + (P ? -2048 : 2048)), lds128(xc + (P ? -1536 : 2560))};
  const uint32_t mk = lane < 8 ? 0xFFFEFFFEu : ~0u;
#pragma unroll
  for (int q = 0; q < 2; q++) {
    const uint4 v = vv[q];
    stsm4t(tl + (cv.ca >> 16) + q * 2048, hadd2u(o[4 * q], v.x) & mk, hadd2u(o[4 * q + 1], v.y) & mk, hadd2u(o[4 * q + 2], v.z) & mk, hadd2u(o[4 * q + 3], v.w) & mk);
  }
  fence_async();
  bar_sync(bid, bn);
  if (warp == 0 && lane == 0) mbar_arrive(MB_REL);
  if ((warp & 7) == (ch < 512 ? 7 : 3) && lane == 0) {
    asm volatile("cp.async.bulk.tensor.3d.global.shared::cta.bulk_group [%0, {%3, %2, %3}], [%1];" :: "l"(tmx), "r"(tl + 512), "r"(ch), "r"(0) : "memory");
    asm volatile("cp.async.bulk.commit_group;" ::: "memory");
  }
}

template <bool FAR> __global__ void __launch_bounds__(NT, 1)
fused_kernel(const __grid_constant__ Params p, const __grid_constant__ TMaps tm) {
  extern __shared__ __align__(1024) unsigned char smem[];
  const int c = blockIdx.x;
  const bool five = (c & 1) == 0;
  const uint32_t pitch = five ? 64 : 80;
  const uint32_t ones = 0x3F803F80u;
  const int tid = threadIdx.x, lane = tid & 31;
  const uint32_t xrow = OFF_YT + ((tid & 127) >> 3) * YT_PITCH + (tid & 64) + (tid & 7) * 16;
  {
    const int w4 = tid >> 7;
    load_params<FAR>(p, w4 < 2 ? 2 * c + w4 : five ? 257 + 2 * c : 512 + (c >> 1), tid & 127, OFF_W + W_KT + (w4 < 2 ? w4 * W_BYTES : five ? 3 * W_BYTES : 3 * W_BYTES + 2048), (0xB >> w4) & 1);
  }
  if ((tid >> 7) == 2) {
    const unsigned char* xp = p.x + (uint32_t)((c * 16 - 32 + (tid >> 3)) * 1152 + (tid & 7) * 16);
    asm volatile("" : "+l"(xp));
    { const uint32_t tq = clock(); while ((int)(clock() - tq) < X_XD) {} }
#pragma unroll
    for (int k = 0; k < 9; k++) asm volatile("cp.async.cg.shared.global [%0], [%1], 16;" :: "r"(xrow + k * 128), "l"(xp + k * 128) : "memory");
  }
  const int warp = (int)uni(tid >> 5), wg = warp >> 2;
  TS(0);
  if (__builtin_expect(wg == 4, 0)) {
    asm volatile("setmaxnreg.dec.sync.aligned.u32 32;");
    const int role = warp;
    const int u0 = (c >> 1) * 9 + (five ? ((c & 2) ? 5 : 0) : ((c & 2) ? 0 : 4));
    const uint32_t t0 = clock() + c * 4;
    if (role == 16) {
      if (lane == 0) {
#pragma unroll
        for (int i = 0; i < 19; i++) if (i != 16) asm volatile("mbarrier.init.shared::cta.b64 [%0], %1;" :: "r"(OFF_MISC + i * 8), "r"((unsigned)(i - 2) < 4u ? 4 : 1) : "memory");
      }
      __syncwarp();
      if (lane < 2) asm volatile("mbarrier.arrive.expect_tx.shared::cta.b64 _, [%0], %1;" :: "r"(OFF_MISC + lane * 8), "r"(lane ? (five ? 36864 : 51200) : pitch * 1152) : "memory");
      fence_async();
      bar_arrive(5, 608);
      const CUtensorMap* tmb = &tm.m[five ? 3 : 0];
#pragma unroll 1
      for (int u = 0; u < 17; u++) {
        const uint32_t e = p.sched[five][u], kind = e & 3, s = (e >> 2) & 15, dst = e >> 14;
        if (kind == 3) continue;
        while ((int)(clock() - t0) < X_PF0 + (u < X_NE ? u * X_PFD : X_LAG + u * X_TD)) __nanosleep(20);
        if (e & 0x3FC0) mbar_wait(OFF_MISC + ((e >> 6) & 255));
        if (lane == 0) {
          if (kind == 2) asm volatile("cp.async.bulk.tensor.3d.shared::cluster.global.mbarrier::complete_tx::bytes [%0], [%1, {%3, %4, %5}], [%2];"
                                      :: "r"(dst), "l"(tmb + 2), "r"(MB_D), "r"(0), "r"(u0 * 8), "r"(s) : "memory");
          else tma_box(dst, tmb + kind, MB_GU, u0 * 8, s * 96);
        }
        if (u == 5) TS(2);
        if (u == 10) TS(3);
      }
      TS(4);
      TS_DUMP();
#define FINISH0 bar_sync(12, 192);        \
        _Pragma("unroll 1") for (int w = role & 2; w < (role & 2) + 2; w++) { \
          const uint32_t xa = OFF_W + W_KT + lane * 16, mk = lane < 8 ? 0xFFFEFFFEu : ~0u, ya = OFF_T + (8 + lane) * 64 + (((w & 1) ^ (lane >> 1)) & 3) * 16 + (w & 2) * 2048; \
          const uint4 a = lds128(xa + 4096 + w * 1024), b = lds128(xa + (w ^ 2) * 1024), d = lds128(xa + 4608 + w * 1024), e = lds128(xa + 512 + (w ^ 2) * 1024); \
          stsm4t(ya, hadd2u(a.x, b.x) & mk, hadd2u(a.y, b.y) & mk, hadd2u(a.z, b.z) & mk, hadd2u(a.w, b.w) & mk); \
          stsm4t(ya + 2048, hadd2u(d.x, e.x) & mk, hadd2u(d.y, e.y) & mk, hadd2u(d.z, e.z) & mk, hadd2u(d.w, e.w) & mk); \
        } \
        fence_async();
    } else if (role == 17) {
      if (smem_u32(smem) != SB) __trap();
      bar_sync(10, 576);
      if (lane == 0) {
        fence_async();
        while ((int)(clock() - t0) < X_NS - c * 4) {}
        asm volatile("cp.async.bulk.global.shared::cta.bulk_group [%0], [%1], 10240;" :: "l"(&p.s->X[c * DM * 2 + 512]), "r"(OFF_G) : "memory");
        asm volatile("cp.async.bulk.commit_group;" ::: "memory");
        asm volatile("cp.async.bulk.wait_group 0;" ::: "memory");
      }
      if (lane == 0) mbar_arrive(MB_GF);
      bar_arrive(11, 96);
      if (five) { FINISH0 bar_arrive(13, 192); }
    } else if (role == 18) {
      sts32(MISC_EPOCH, 0);
      sts32(MISC_T0, t0 - c * 4);
      bar_arrive(5, 608);
      uint4* q = lane < 2 ? &p.s->R[c * 2 + lane] : lane < 11 ? &p.s->HS[c * 9 + lane - 2] : lane == 11 ? &p.s->HS[1152 + (c & 7)] : (uint4*)&p.s->FLAG[c * 8];
      if (lane < (c < 8 ? 12 : 11)) str128(q, ~0u, ~0u, ~0u, ~0u);
      const uint32_t ep = __shfl_sync(0xffffffffu, ldr32(q), 31) + 1u;
      sts32(MISC_EPOCH, ep | 0x80000000u);
      TSX(21);
      if (lane == 31) str32(q, ep);
      bar_sync(11, 96);
      TSX(14);
      mbar_wait(MB_KF + (lane & 3) * 8);
      __syncwarp();
      { const uint2 e = lds64(MISC_EM); if (lane < 2) str128(&p.s->SC[c * 2 + lane], e.x, __byte_perm(e.y, ep, 0x6540), 0, 0); }
      TSX(17);
      while ((int)(clock() - t0) < X_SCT) __nanosleep(100);
      TSX(18);
      {
        uint2 v[4];
#pragma unroll 1
        for (int it = 0; it < SPIN_MAX; it++) {
          uint32_t bad = 0;
#pragma unroll
          for (int q = 0; q < 4; q++) v[q] = ldr64(&p.s->SC[lane * 2 + q * 64]);
#pragma unroll
          for (int q = 0; q < 4; q++) bad |= (v[q].y >> 8) ^ (ep & 0xFFFFFFu);
          if (!__any_sync(0xffffffffu, bad)) break;
        }
        TSX(25);
#pragma unroll
        for (int q = 0; q < 4; q++) {
          const uint32_t sa = (lane >> 4) * YT_PITCH + (lane & 15) * 2;
          sts16(sc_addr(2 * q) + sa, v[q].x); sts16(sc_addr(8 + 2 * q) + sa, v[q].x >> 16);
          if (lane & 1) asm volatile("st.shared.u8 [%0], %1;" :: "r"(sc_addr(16) + q * 16 + (lane >> 1)), "r"(v[q].y) : "memory");
        }
      }
      __syncwarp();
      if (lane == 0) mbar_arrive(MB_SC);
      TSX(27);
    } else {
      uint32_t w[9];
      const uint32_t dk = ldnc16(p.dskip + ((lane & 4) ? 512 + (c >> 1) : (lane & 2) * 128 + 2 * c + (lane & 1)));
      float s = 0.f;
#pragma unroll
      for (int i = 0; i < 9; i++) w[i] = ldnc32(p.w_r + lane + 32 * i);
      sts16(OFF_WR + 1152 + lane * 2, dk);
      bar_arrive(5, 608);
#pragma unroll
      for (int i = 0; i < 9; i++) { sts32(OFF_WR + lane * 4 + i * 128, w[i]); s += bf_lo(w[i]) + bf_hi(w[i]); }
      sts32(MISC_SW, __float_as_uint(warp_sum(s)));
      TSX(23);
      bar_sync(10, 576);
      if (lane == 0) {
        const uint32_t tp = clock();
        TSX(1);
        while ((int)(clock() - tp) < X_DELTA || (int)(clock() - t0) < X_ABS - c * 4) {}
        TSX(24);
        load_tile(&tm.m[6], 0, c);
        TSX(15);
        while ((int)(clock() - t0) < X_ABS + X_DSTEP - c * 4) {}
      }
      bar_sync(11, 96);
      if (lane == 0) {
        load_tile(&tm.m[6], 1, 128 + c);
      }
      if (five) {
        mbar_wait(MB_KF);
#pragma unroll 1
        for (int it = 0; it < SPIN_MAX; it++) {
          if (lane == 0) load_tile(&tm.m[8], 2, 512 + (c >> 1));
          mbar_wait(MB_UL + 32, it & 1);
          uint32_t m = 1;
#pragma unroll
          for (int q = 0; q < 4; q++) { uint32_t r0, r1, r2, r3; ldsm4(OFF_W + 512 + lane * 64 + (lane & 6) * 8 + q * 2048, r0, r1, r2, r3); m &= r0 & r1 & r2 & r3; }
          if (__all_sync(0xffffffffu, m || (lane & 3))) break;
        }
        bar_arrive(7, 288);
        FINISH0
        bar_arrive(13, 192);
      }
      bar_sync(0, 544);
      if (lane == 0) mbar_arrive(MB_H);
    }
    return;
  }
  const int wt = tid & 127, g = lane >> 2, t = lane & 3;
  const uint32_t wb = OFF_W + wg * W_BYTES;
  asm volatile("cp.async.commit_group;" ::: "memory");
  const ConvC cv = conv_consts(warp, lane);
  zero_pads(wb, wt);
  load_params<FAR>(p, 254 + 2 * c + wg, wt, wb + W_KT, wg == 2 || (wg == 3 && !five));
  asm volatile("cp.async.commit_group;" ::: "memory");
  asm volatile("setmaxnreg.inc.sync.aligned.u32 112;");
  {
    uint4 kw;
    uint4* kx = &p.s->KX[(c >> 1) * 128 + wt];
    bool two = wg == 3;
    uint32_t ep;
    int em = 0;
    uint32_t slot = wg + (two && !five);
    const uint32_t ra0 = wb + W_KT + (slot & 4) * 512 + wt * 2, ra6 = wb + W_KT + 1536 + (slot & 4) * 512 + (((slot & 4) ? c >> 1 : 2 * c + (wg & 1)) & 7) * 2;
        const int lz = lane;
        const uint32_t tr_addr = pin(tr_base(lz) + warp * 32), lca = pin(MISC_LN1 + (lz & 1) * 16);
        uint4* dst;
        { const unsigned long long a = (unsigned long long)&p.s->X[c * DM * 2 + warp * 32 + (8 * ((lz >> 1) & 1) + (lz >> 2)) * 2 + (lz & 1)];
          dst = (uint4*)(((unsigned long long)pin(a >> 32) << 32) | pin((uint32_t)a)); }
    BuildC bc;
    if (X_BC != 2) bc = build_consts(wt);
    uint32_t raw[7];
    if (wg != 2) {
      asm volatile("cp.async.wait_group 1;" ::: "memory");
      bar_sync(1 + wg, 128);
#pragma unroll
      for (int i = 0; i < 7; i++) raw[i] = lds16(i < 6 ? ra0 + i * 256 : ra6);
    }
    int phase = wg == 2 ? 3 : 2;
#pragma unroll 1
    for (;;) {
      if (phase != 3) {
        KgState ks;
        TS(22);
        kgen_tables_n(raw, wb, wt, ks);
        TS(20);
        bar_sync(1 + wg, 128);
        em = kgen_tables_m(wb, wt, ks);
        fence_async();
      }
      if (phase & 2) {
        if (X_BC == 2) bc = build_consts(wt ^ (clock() & p.off[7]));
        if (phase == 3) {
        asm volatile("cp.async.wait_group 1;" ::: "memory");
        TS(21);
        float d[3][4], r;
        uint4 a[9];
#pragma unroll
        for (int k = 0; k < 9; k++) a[k] = lds128(xrow + k * 128);
#pragma unroll
        for (int i = 0; i < 4; i++) d[0][i] = d[1][i] = d[2][i] = 0.f;
#pragma unroll
        for (int k = 0; k < 9; k++) { mma_bf16(d[(2 * k) % 3], a[k].x, ones, a[k].y, ones, a[k].x, a[k].y); mma_bf16(d[(2 * k + 1) % 3], a[k].z, ones, a[k].w, ones, a[k].z, a[k].w); }
#pragma unroll
        for (int i = 0; i < 4; i++) d[0][i] += d[1][i] + d[2][i];
        const LnC lc = ln_consts(d[0][2] + d[0][3], __shfl_sync(0xffffffffu, d[0][0], 9 * t) + __shfl_sync(0xffffffffu, d[0][1], 9 * t + 4), r);
        if (lane < 12) sts16(MISC_LN1 + g * 32 + (warp & 3) * 8 + t * 2, lane < 4 ? lc.m2 : lane < 8 ? lc.rh2 : lc.rl2);
        }
        asm volatile("cp.async.wait_group 0;" ::: "memory");
        TS(23);
        bar_sync(5, 608);
        uint32_t x[3][4];
        ldsm4t(tr_addr, x[0][0], x[0][1], x[0][2], x[0][3]);
        uint4 m = lds128(lca);
        const uint4 rl = lds128(lca + 64), rh = lds128(lca + 32);
        ldsm4t(tr_addr + 512, x[1][0], x[1][1], x[1][2], x[1][3]);
        if (wg == 3) ldsm4t(tr_addr + 640, x[2][0], x[2][1], x[2][2], x[2][3]);
#pragma unroll
        for (int q = 0; q < 3; q++) {
          if (q < 2 || wg == 3) {
            const uint32_t r0 = ln_apply(x[q][0], m.x, rh.x, rl.x), r1 = ln_apply(x[q][1], m.y, rh.y, rl.y), r2 = ln_apply(x[q][2], m.z, rh.z, rl.z), r3 = ln_apply(x[q][3], m.w, rh.w, rl.w);
            const uint32_t w0 = (pack_h(bf_lo(r0), bf_hi(r0)) & 0xFFFEFFFEu) | 1u, w1 = pack_h(bf_lo(r1), bf_hi(r1)), w2 = pack_h(bf_lo(r2), bf_hi(r2)), w3 = pack_h(bf_lo(r3), bf_hi(r3));
            if (q == 0) str128(dst, w0, w1, w2, w3);
            else sts128(OFF_G + warp * 512 + (8 * (t >> 1) + g) * 32 + (t & 1) * 16 + (q == 2 ? 2048 : 0), w0, w1, w2, w3);
          }
          if (q == 0) {
            const uint32_t z = clock() & p.off[7];
            m.x ^= z; m.y ^= z; m.z ^= z; m.w ^= z;
          }
          if (q == 0) TS(30);
          if (q == 0 && wg >= 2) {
#pragma unroll
            for (int i = 0; i < 7; i++) raw[i] = lds16(wb + W_KT + i * 256 + (i < 6 ? wt : (2 * c + (wg & 1)) & 7) * 2);
          }
        }
        bar_arrive(10, 576);
        TS(1);
      } else bar_sync(1 + wg, 128);
      phase &= 1;
      if (phase) { phase = 0; continue; }
      TS(14);
      float acc[20];
      const uint32_t alo = (wb >> 4) | (8u << 16);
      uint4 k4 = lds128(wb + W_MISC + 16);
      uint32_t dk = lds16(OFF_WR + 1152 + slot * 2);
      wg_fence();
      wgmma40_ss_init(acc, alo, alo + 1024, 2048 >> 4);
#pragma unroll
      for (int k = 1; k < 8; k++) wgmma40_ss(acc, alo + k * 16, alo + 1024 + k * 16, 2048 >> 4);
      wg_commit();
      { const uint32_t z = clock() & p.off[7]; dk ^= z; k4.x ^= z; k4.z ^= z; }
      const float k2048 = (float)(int)((k4.x + k4.y) + (k4.z + k4.w)) * (1.f / 262144.f);
      const int ef = max(em, min((int)((dk >> 7) & 255u) - 7, 238));
      asm volatile("st.shared.u8 [%0], %1;" :: "r"(MISC_EM + slot), "r"(ef + 9) : "memory");
      const float un = __uint_as_float((uint32_t)max(114 + em - ef, 0) << 23), d0 = wt ? 0.f : bf_lo(dk) * __uint_as_float((uint32_t)(245 - ef) << 23);
      wg_wait<0>();
      kw.x = pack_h(fmaf(acc[0] - acc[3], un, d0), (acc[4] - acc[7]) * un);
      kw.y = pack_h((acc[8] - acc[11]) * un, (acc[12] - acc[15]) * un);
      kw.z = pack_h((acc[16] - acc[19]) * un, k2048 * un);
      TS(24);
      ep = 0;
      if (two) SPIN_WHILE(ep == 0, ep = lds32(MISC_EPOCH));
      if (five || !two) break;
      str128(kx, kw.x, kw.y, kw.z, ep);
      two = false;
      slot = 3;
      bar_sync(1 + wg, 128);
    }
    if (lane == 0) mbar_arrive(MB_KF + wg * 8);
    if (two) { mbar_wait(MB_KF); zero_pads(OFF_W + ALT, wt); }
    uint32_t tb = wb;
#pragma unroll 1
    for (;;) {
      kgen_build(tb, bc, wg, wt, kw.x, kw.y, kw.z);
      TS(15);
      if (!two) break;
      two = false;
      kw.w = 0;
      SPIN_WHILE(kw.w != ep, kw = ldr128(kx));
      tb = OFF_W + ALT;
    }
    fence_async();
    TS(31);
    if (tb != wb) bar_arrive(7, 288);
    bar_sync(1 + wg, 128);
  }
  uint32_t tpub;
  ConvPre pre;
  conv_pre(pre, (wb ^ p.off[7]) + (cv.ca & 0xFFFFu), (wb ^ p.off[7]) + cv.qa, 3, true, warp & 2);
#pragma unroll 1
  for (int item = 0;; item++) {
    TS(2);
    conv_item(item ? OFF_W + ALT : wb, item ? OFF_W : OFF_T + (wg >> 1) * TILE, item ? 1 : 13 + (wg >> 1), item ? 128 : five && wg == 1 ? 192 : 256, pre, cv, p.off[7],
              &tm.m[item ? 9 : 7], item ? 512 + (c >> 1) : (wg >> 1) * 128 + c, warp, lane, five && wg >= X_GW, five && !wg && !item);
    tpub = clock() - (item ? X_YD : wg >= 2 ? X_YD2 : 0);
    if (wg || !five || item) break;
    TS(27);
  }
  TS(4);

  const int ln = lane ^ p.off[7], td = warp * 32 + ln, gg = ln >> 2, tt = ln & 3;
  const int tok = c * 16 + warp;
  const int fu = warp / 3, fk = warp - fu * 3;
  uint32_t wa[12][4];
  uint4 ha[3];
  const uint4* hsrc = &p.s->HS[td + (td / 24) * 48];
  {
    uint32_t hw[9], wr[9];
    const uint32_t row = keep(OFF_YT + warp * YT_PITCH + (warp >> 3) * 64 + ln * 16);
    const uint32_t wabase = keep(((ln & 8) ? OFF_W + (fk + 1) * W_BYTES : OFF_G + fk * 192 * pitch) + ((ln >> 4) * 8 + (ln & 7)) * pitch
                                 + (five ? ((fu ^ (ln >> 1)) & 3) : min(fu, 4)) * 16);
    float sw;
    {
      const bool three = wg == 1;
      const int ch = 8 * (tt >> 1) + gg;
      const uint32_t tr_addr = tr_base(ln);
      const uint4* ysrc = &p.s->X[c * DM * 2 + ch * 2 + (tt & 1)];
      uint32_t x[3][4], s[3];
      uint4 v[3];
#define TL(q) ((q) < 2 ? 2 * warp + (q) : 28 + warp)
      if (wg >= 2) { const uint32_t ts = lds32(MISC_T0); while ((int)(clock() - ts) < X_XS) {} }
      while ((int)(clock() - tpub) < X_YD) {}
      TS(5);
      v[0] = ldr128(ysrc + TL(0) * 32); v[1] = ldr128(ysrc + TL(1) * 32); v[2] = make_uint4(three, 0, 0, 0);
      mbar_wait(MB_REL);
#pragma unroll
      for (int i = 0; i < 6; i++) if (i < 4 || three) wr[i] = (gg & 2) ? ones : lds32(OFF_WR + TL(i >> 1) * 32 + (i & 1) * 16 + tt * 4);
      const uint32_t ha = keep(OFF_YT + (ln & 7) * YT_PITCH + (ln >> 4) * (8 * YT_PITCH + 64) + (ln & 8) * 2);
      const uint32_t pa = keep(OFF_PART + warp * 4 + ((gg & 2) * 8 + (gg & 4) * 2 + 2 * tt + (gg & 1)) * 80), pb = keep(OFF_PART + 2560 + warp * 4 + gg * 80);
      float dl[4] = {0.f, 0.f, 0.f, 0.f}, dh[4] = {0.f, 0.f, 0.f, 0.f};
      sw = __uint_as_float(lds32(MISC_SW));
#pragma unroll
      for (int q = 0; q < 3; q++) {
        if (q < 2 || three) {
          ldsm4t(tr_addr + TL(q) * 32, x[q][0], x[q][1], x[q][2], x[q][3]);
        }
      }
      asm volatile("cp.async.bulk.wait_group.read 0;" ::: "memory");
      mbar_wait(MB_SC);
#pragma unroll
      for (int q = 0; q < 3; q++) {
        asm volatile("ld.shared.u8 %0, [%1];" : "=r"(s[q]) : "r"((q < 2 ? sc_addr(warp) + q * 16 : sc_addr(16) + (warp & 3) * 16) + ch) : "memory");
        s[q] = keep(s[q] * 0x800080u);
      }
#define FIN(q) stsm4t(tr_addr + TL(q) * 32, bf_fma2(h2bf(v[q].x), s[q], x[q][0]), bf_fma2(h2bf(v[q].y), s[q], x[q][1]), bf_fma2(h2bf(v[q].z), s[q], x[q][2]), bf_fma2(h2bf(v[q].w), s[q], x[q][3]));
      SPIN_WHILE((v[0].x | v[1].x) & 1u, _Pragma("unroll") for (int q = 0; q < 3; q++) if (v[q].x & 1u) v[q] = ldr128(ysrc + TL(q) * 32));
      if (v[2].x & 1u) v[2] = ldr128(ysrc + TL(2) * 32);
#define STAT(q) { uint32_t r0, r1, r2, r3; ldsm4(ha + TL(q) * 32, r0, r1, r2, r3); \
        mma_bf16(dl, r0, wr[2 * q], r1, wr[2 * q + 1], r0, r1); mma_bf16(dh, r2, wr[2 * q], r3, wr[2 * q + 1], r2, r3); }
      FIN(0) FIN(1)
      __syncwarp();
      STAT(0) STAT(1)
      if (three) {
#pragma unroll 1
        for (int it = 0; it < SPIN_MAX; it++) {
          FIN(2)
          if (!__any_sync(0xffffffffu, v[2].x & 1u)) break;
          if (v[2].x & 1u) v[2] = ldr128(ysrc + TL(2) * 32);
        }
        __syncwarp();
        STAT(2)
      }
      if (gg & 1) { dl[0] = dl[1]; dl[2] = dl[3]; dh[0] = dh[1]; dh[2] = dh[3]; }
      sts32(pa, __float_as_uint((gg & 4) ? dh[2] : dl[2]));
      if (tt == (gg >> 1)) { sts32(pb, __float_as_uint(dl[0])); sts32(pb + 640, __float_as_uint(dh[0])); }
#undef STAT
#undef FIN
#undef TL
    }
    uint32_t ra = keep(OFF_PART + (ln & 15) * 80 + (ln & 16) * 2);
    uint16_t* rp = (uint16_t*)p.s->R + c * 16 + (ln & 15);
    const uint2* rsrc = (const uint2*)p.s->R + td;
    asm volatile("" : "+l"(rp), "+l"(rsrc), "+l"(hsrc));
    uint2 rv = make_uint2(0u, 0u);
    TS(28);
    if (warp != X_PW) bar_sync(0, 544);
    else {
      float z[3], rd;
      asm volatile("bar.sync 0, 544;" : "+r"(ra) :: "memory");
#pragma unroll
      for (int k = 2; k >= 0; k--) {
        const uint4 a = lds128(ra + k * 1280), b = lds128(ra + k * 1280 + 16);
        z[k] = ((__uint_as_float(a.x) + __uint_as_float(a.y)) + (__uint_as_float(a.z) + __uint_as_float(a.w))) + ((__uint_as_float(b.x) + __uint_as_float(b.y)) + (__uint_as_float(b.z) + __uint_as_float(b.w)));
      }
#pragma unroll
      for (int k = 2; k >= 0; k--) z[k] += __shfl_xor_sync(0xffffffffu, z[k], 16);
      const LnC l = ln_consts(z[1], z[2], rd);
      const uint32_t b = pack_bf(0.f, fmaf(-bf_lo(l.m2), sw, z[0]) * rd);
      const uint32_t k16 = max(min((b ^ (((int)b >> 31) | 0x80000000u)) >> 16, 0xFFFEu), 1u);
      if (ln < 16) str16(rp, k16);
      sts64(OFF_RK + (ln & 15) * 8, __byte_perm(l.m2, l.rh2, 0x5410), __byte_perm(l.rl2, k16, 0x5410));
      sts128(MISC_CNT + ln * 16, 0, 0, 0, 0);
    }
    mbar_wait(MB_GU);
#define LD_HW { const uint4 a = lds128(row), b = lds128(row + 512); hw[8] = lds32(row + 1024 - ln * 12); \
      hw[0] = a.x; hw[1] = a.y; hw[2] = a.z; hw[3] = a.w; hw[4] = b.x; hw[5] = b.y; hw[6] = b.z; hw[7] = b.w; }
    LD_HW
    const uint32_t tr0 = clock();
    bar_sync(5, 512);
    TS(7);
    const uint2 lk = lds64(OFF_RK + warp * 8);
    LnC l2;
    l2.m2 = __byte_perm(lk.x, 0, 0x1010); l2.rh2 = __byte_perm(lk.x, 0, 0x3232); l2.rl2 = __byte_perm(lk.y, 0, 0x1010);
    const uint32_t key = (lk.y & 0xFFFF0000u) | (2047 - tok);
    uint32_t loc = ln < 16 ? (lds32(OFF_RK + 4 + ln * 8) & 0xFFFF0000u) | (2047 - c * 16 - ln) : 0u;
    int rank = __popc(__ballot_sync(0xffffffffu, loc > key));
#pragma unroll
    for (int i = 0; i < 9; i++) { wr[i] = keep(ln_apply(hw[i], l2.m2, l2.rh2, l2.rl2)); hw[i] = bf_add2(hw[i], wr[i]); }
#define OUT_ROW { uint32_t* o = p.out + tok * 288 + ln * 4; \
      *(uint4*)o = make_uint4(hw[0], hw[1], hw[2], hw[3]); *(uint4*)(o + 128) = make_uint4(hw[4], hw[5], hw[6], hw[7]); o[256 - ln * 3] = hw[8]; }
    uint4* hs = p.s->HS + ln;
    asm volatile("" : "+l"(hs));
#pragma unroll 1
    for (int base = 0; base < 8; base += 2) {
      uint32_t T[2];
#pragma unroll
      for (int j = 0; j < 2; j++) {
        const uint32_t mx = __reduce_max_sync(0xffffffffu, loc);
        if (loc == mx) loc = 0;
        T[j] = (td >> 2) < c ? (mx & 0xFFFF0000u) - 1u : mx | 0xFFFFu;
      }
      const uint32_t sh = keep(rank == base ? 0x4410u : rank == base + 1 ? 0x4432u : 0x4445u), ca = keep(MISC_CNT + base * 64 + ln * 4);
      TS(29);
      if (base == 0) {
        while ((int)(clock() - tr0) < X_RD) {}
        if ((td >> 2) != c) rv = ldr64(rsrc);
        if (rank >= X_OR) OUT_ROW
        if (warp < (five ? 12 : 15)) {
#pragma unroll
          for (int k = 0; k < X_WS; k++) ldsm4t(wabase + k * 16 * pitch, wa[k][0], wa[k][1], wa[k][2], wa[k][3]);
        }
      }
      uint32_t cnt;
#pragma unroll 1
      for (int it = 0; it < SPIN_MAX; it++) {
        const uint32_t xs = rv.x << 16, ys = rv.y << 16;
        const bool bad = max(max(rv.x, xs), max(rv.y, ys)) >= 0xFFFF0000u;
        uint32_t cn2 = 0;
        cnt = bad ? 256u : 0u;
#pragma unroll
        for (int j = 0; j < 2; j++)
          asm("{ .reg .pred a, b, c, d; setp.gt.u32 a, %2, %6; setp.gt.u32 b, %3, %6; setp.gt.u32 c, %4, %6; setp.gt.u32 d, %5, %6; "
              "@a add.u32 %1, %1, %7; @b add.u32 %1, %1, %7; @c add.u32 %0, %0, %7; @d add.u32 %0, %0, %7; }"
              : "+r"(cnt), "+r"(cn2) : "r"(rv.x), "r"(rv.y), "r"(xs), "r"(ys), "r"(T[j]), "r"(1u << (16 * j)));
        cnt = __reduce_add_sync(0xffffffffu, cnt + cn2);
        asm volatile("{ .reg .pred q; setp.eq.u32 q, %2, 0; @q red.shared.add.u32 [%0], %1; }" :: "r"(ca), "r"(cnt), "r"(cnt & 0x3F00u) : "memory");
        if (!(cnt & 0x3F00u)) break;
        if (bad) rv = ldr64(rsrc);
      }
      TS(16);
      bar_sync(0, 512);
      cnt = lds32(ca);
      if (base == 0) tpub = clock();
      const int gr = rank + __byte_perm(cnt, 0x800u, sh);
      if (gr < 8) {
        uint4* ks = hs + 1152 + gr;
        hs = (uint4*)((char*)hs + gr * 1152);
        asm volatile("{ .reg .b128 t, u; .reg .b64 a, b, c, d; mov.b64 a, {%1,%2}; mov.b64 b, {%3,%4}; mov.b64 c, {%5,%6}; mov.b64 d, {%7,%8}; mov.b128 t, {a, b}; mov.b128 u, {c, d}; "
                     "st.relaxed.gpu.global.b128 [%0], t; st.relaxed.gpu.global.b128 [%0 + 512], u; }"
                     :: "l"(hs), "r"(wr[0]), "r"(wr[1]), "r"(wr[2]), "r"(wr[3]), "r"(wr[4]), "r"(wr[5]), "r"(wr[6]), "r"(wr[7]) : "memory");
        str32((uint32_t*)(hs + 64) - ln * 3, wr[8]);
        LD_HW
        str128(hs + 576, hw[0], hw[1], hw[2], hw[3]); str128(hs + 608, hw[4], hw[5], hw[6], hw[7]); str32((uint32_t*)(hs + 640) - ln * 3, hw[8]);
        if (ln == 0) str32(ks, key);
        rank = 16;
      }
      if (__all_sync(0xffffffffu, (int)(cnt >> 16) + base + 2 >= 8)) break;
    }
    TS(8);
    if (warp < (five ? 12 : 15)) {
#pragma unroll
      for (int k = X_WS; k < 12; k++) ldsm4t(wabase + k * 16 * pitch, wa[k][0], wa[k][1], wa[k][2], wa[k][3]);
    }
    if (warp < 6) while ((int)(clock() - tpub) < X_HD) {}
    TS(19);
    if (warp < 6) { ha[0] = ldr128(hsrc); ha[1] = ldr128(hsrc + 24); ha[2] = ldr128(hsrc + 48); }
    if (rank < X_OR) OUT_ROW
  }
  uint32_t wd[10][4];
  const uint32_t xb = keep(OFF_XS + (ln & 7) * 1168 + (fk * 24 + (ln >> 3)) * 16);
  if (warp >= 7) {
    const uint32_t db = down_box(warp - 7, five) + (ln & 7) * 128;
    mbar_wait(MB_D);
#pragma unroll
    for (int j = 0; j < 4; j++) {
      const uint32_t a = db + (ln >> 4) * 1024 + (((2 * j + ((ln >> 3) & 1)) ^ (ln & 7)) << 4);
      ldsm4t(a, wd[j][0], wd[j][1], wd[j][2], wd[j][3]);
      ldsm4t(a + 2048, wd[4 + j][0], wd[4 + j][1], wd[4 + j][2], wd[4 + j][3]);
    }
#pragma unroll
    for (int j = 0; j < 2; j++) ldsm4t(db + 4096 + (((4 * j + (ln >> 3)) ^ (ln & 7)) << 4), wd[8 + j][0], wd[8 + j][1], wd[8 + j][2], wd[8 + j][3]);
  } else if (warp < 6) {
    const uint32_t xs = keep(OFF_XS + (td + (td / 24) * 49) * 16);
#pragma unroll 1
    for (int it = 0; it < SPIN_MAX; it++) {
      const bool bad = max(max(max(ha[0].x, ha[1].x), max(ha[2].x, ha[2].y)), max(ha[2].z, ha[2].w)) == ~0u;
#pragma unroll
      for (int q = 0; q < 3; q++) sts128(xs + q * 384, ha[q].x, ha[q].y, ha[q].z, ha[q].w);
      if (!__any_sync(0xffffffffu, bad)) break;
      if (bad) { ha[0] = ldr128(hsrc); ha[1] = ldr128(hsrc + 24); ha[2] = ldr128(hsrc + 48); }
    }
  }
  TS(9);

  bar_sync(0, 512);
  if (warp < (five ? 12 : 15)) {
    float d0[4] = {0.f, 0.f, 0.f, 0.f}, d1[4] = {0.f, 0.f, 0.f, 0.f};
#pragma unroll
    for (int k = 0; k < 12; k += 2) {
      uint32_t b0, b1, b2, b3;
      ldsm4(xb + k * 32, b0, b1, b2, b3);
      mma_bf16(d0, wa[k][0], wa[k][1], wa[k][2], wa[k][3], b0, b1);
      mma_bf16(d1, wa[k + 1][0], wa[k + 1][1], wa[k + 1][2], wa[k + 1][3], b2, b3);
    }
    sts128(OFF_RED + td * 16, __float_as_uint(d0[0] + d1[0]), __float_as_uint(d0[1] + d1[1]), __float_as_uint(d0[2] + d1[2]), __float_as_uint(d0[3] + d1[3]));
  }
  TS(26);
  if (warp < 5) {
    const uint32_t rb = OFF_RED + warp * 1536 + ln * 16;
    bar_sync(9, 512);
    const uint4 pa = lds128(rb), pb = lds128(rb + 512), pc = lds128(rb + 1024);
    const float ga = bfr(__uint_as_float(pa.x) + __uint_as_float(pb.x) + __uint_as_float(pc.x));
    const float gb = bfr(__uint_as_float(pa.y) + __uint_as_float(pb.y) + __uint_as_float(pc.y));
    const uint32_t uu = pack_bf(__uint_as_float(pa.z) + __uint_as_float(pb.z) + __uint_as_float(pc.z), __uint_as_float(pa.w) + __uint_as_float(pb.w) + __uint_as_float(pc.w));
    float ra, rb2;
    asm("rcp.approx.ftz.f32 %0, %1;" : "=f"(ra) : "f"(1.f + ex2(ga * -1.4426950408889634f)));
    asm("rcp.approx.ftz.f32 %0, %1;" : "=f"(rb2) : "f"(1.f + ex2(gb * -1.4426950408889634f)));
    const uint32_t act = bf_mul2(pack_bf(ga * ra, gb * rb2), uu);
    sts32(OFF_ACT + td * 4, act);
  } else bar_arrive(9, 512);
  uint4* dst = &p.s->X[c * DM * 2 + (warp - 7) * 64 + tt * 8 + gg];
  asm volatile("" : "+l"(dst));
  bar_sync(8, 512);
  tpub = clock();
  if (warp >= 7) {
    uint32_t b0, b1, b2, b3, b4;
    ldsm4t(OFF_ACT + ln * 16, b0, b1, b2, b3);
    asm volatile("ldmatrix.sync.aligned.m8n8.x1.trans.shared.b16 {%0}, [%1];" : "=r"(b4) : "r"(OFF_ACT + 512 + ln * 16) : "memory");
    float y[4][4];
#pragma unroll
    for (int j = 0; j < 4; j++) {
      y[j][0] = y[j][1] = y[j][2] = y[j][3] = 0.f;
      mma_bf16(y[j], wd[j][0], wd[j][1], wd[j][2], wd[j][3], b0, b1);
    }
#pragma unroll
    for (int j = 0; j < 4; j++) mma_bf16(y[j], wd[4 + j][0], wd[4 + j][1], wd[4 + j][2], wd[4 + j][3], b2, b3);
    if (!five) {
#pragma unroll
      for (int j = 0; j < 4; j++) mma_bf16_k8(y[j], wd[8 + (j >> 1)][2 * (j & 1)], wd[8 + (j >> 1)][2 * (j & 1) + 1], b4);
    }
    str128(dst, (pack_bf(y[0][0], y[0][1]) & ~1u) | 0x10000u, pack_bf(y[0][2], y[0][3]), pack_bf(y[1][0], y[1][1]), pack_bf(y[1][2], y[1][3]));
    str128(dst + 32, (pack_bf(y[2][0], y[2][1]) & ~1u) | 0x10000u, pack_bf(y[2][2], y[2][3]), pack_bf(y[3][0], y[3][1]), pack_bf(y[3][2], y[3][3]));
  }
  TS(10);

  if (c < 72) {
    const uint4* src = &p.s->X[(warp * 4 + tt) * (DM * 2) + c * 8 + gg];
    const int slot = (c & 3) * 2 + (ln >> 4), dw = (c >> 2) * 16 + (ln & 15);
    uint32_t hv = 0, kv = 0, res = 0, rs2 = 0;
    uint32_t* o = p.out;
    if (warp == 0) {
      hv = ~0u;
      SPIN_WHILE(max(hv, kv) == ~0u, hv = ldr32((const uint32_t*)p.s->HS + 2304 + slot * 288 + dw); kv = ldr32(&p.s->HS[1152 + slot]));
      const float r = bf_hi(kv ^ (((int)~kv >> 31) | 0x80000000u));
      float rs;
      asm("rcp.approx.ftz.f32 %0, %1;" : "=f"(rs) : "f"(1.f + ex2(r * -1.4426950408889634f)));
      rs2 = keep(pack_bf(rs, rs));
      res = lds32(OFF_XS + slot * 1168 + dw * 4);
      o += (2047 - (int)(kv & 2047u)) * 288 + dw;
      asm volatile("" : "+l"(o));
    }
    const uint32_t sel = (gg & 1) ? 0x3F800000u : 0x00003F80u;
    const uint32_t q0 = keep((gg >> 1) == 0 ? sel : 0u), q1 = keep((gg >> 1) == 1 ? sel : 0u), q2 = keep((gg >> 1) == 2 ? sel : 0u), q3 = keep((gg >> 1) == 3 ? sel : 0u);
    const uint32_t fa = keep(OFF_RED + warp * 8 + ((gg & 1) * 16 + (gg >> 1) * 4 + tt) * 144), fb = keep(OFF_RED + ln * 144);
    uint4 a0 = make_uint4(0, 0, 0, 0), a1 = a0;
    while ((int)(clock() - tpub) < X_PD) {}
    SPIN_WHILE(!(a0.x & a1.x & 0x10000u), if (!(a0.x & 0x10000u)) a0 = ldr128(src); if (!(a1.x & 0x10000u)) a1 = ldr128(src + 64 * DM * 2));
    float d[4] = {0.f, 0.f, 0.f, 0.f}, e[4] = {0.f, 0.f, 0.f, 0.f}, d2[4] = {0.f, 0.f, 0.f, 0.f}, e2[4] = {0.f, 0.f, 0.f, 0.f};
    mma_bf16(d, q0, q2, q1, q3, a0.x, a0.y); mma_bf16(e, q0, q2, q1, q3, a0.z, a0.w);
    mma_bf16(d2, q0, q2, q1, q3, a1.x, a1.y); mma_bf16(e2, q0, q2, q1, q3, a1.z, a1.w);
    sts64(fa, __float_as_uint(d[0] + e[2] + d2[0] + e2[2]), __float_as_uint(d[1] + e[3] + d2[1] + e2[3]));
    TS(11);
    if (warp == 0) {
      bar_sync(0, 512);
      float2 s[16];
#pragma unroll
      for (int i = 0; i < 16; i += 2) { const uint4 q = lds128(fb + i * 8); s[i] = make_float2(__uint_as_float(q.x), __uint_as_float(q.y)); s[i + 1] = make_float2(__uint_as_float(q.z), __uint_as_float(q.w)); }
#pragma unroll
      for (int k = 1; k < 16; k *= 2)
#pragma unroll
        for (int i = 0; i < 16; i += 2 * k) { s[i].x += s[i + k].x; s[i].y += s[i + k].y; }
      asm volatile("st.global.b32 [%0], %1;" :: "l"(o), "r"(bf_add2(hv, bf_add2(res, bf_mul2(pack_bf(s[0].x, s[0].y), rs2)))) : "memory");
    } else bar_arrive(0, 512);
  }
  TS(12);
  TS_DUMP();
}

typedef CUresult (*EncodeFn)(CUtensorMap*, CUtensorMapDataType, cuuint32_t, void*, const cuuint64_t*, const cuuint64_t*, const cuuint32_t*,
                             const cuuint32_t*, CUtensorMapInterleave, CUtensorMapSwizzle, CUtensorMapL2promotion, CUtensorMapFloatOOBfill);

}

extern "C" void kernel_launch(void* const* d_in, const int* in_sizes, int n_in, void* d_out, int out_size) {
  (void)in_sizes; (void)n_in; (void)out_size;
  static EncodeFn enc = nullptr;
  static Scratch* scratch = nullptr;
  if (!enc) {
    void* fn = nullptr;
    cudaDriverEntryPointQueryResult qr;
    cudaGetDriverEntryPoint("cuTensorMapEncodeTiled", &fn, cudaEnableDefault, &qr);
    enc = (EncodeFn)fn;
    cudaGetSymbolAddress((void**)&scratch, g_S);
    cudaFuncSetAttribute(fused_kernel<false>, cudaFuncAttributeMaxDynamicSharedMemorySize, SMEM_BYTES);
    cudaFuncSetAttribute(fused_kernel<true>, cudaFuncAttributeMaxDynamicSharedMemorySize, SMEM_BYTES);
  }
  TMaps tm;
  for (int i = 0; i < 6; i++) {
    const bool dn = i % 3 == 2;
    const cuuint32_t w = i < 3 ? 40 : 32;
    cuuint64_t gd[3] = {(cuuint64_t)(dn ? 64 : FF), (cuuint64_t)(dn ? FF : DM), 9};
    cuuint64_t gs[2] = {(cuuint64_t)(dn ? DM * 2 : FF * 2), 128};
    cuuint32_t bx[3] = {dn ? 64 : w, dn ? w : 96, i < 3 ? 2u : 3u};
    cuuint32_t es[3] = {1, 1, 1};
    enc(&tm.m[i], CU_TENSOR_MAP_DATA_TYPE_BFLOAT16, dn ? 3 : 2, d_in[11 + i % 3], gd, gs, bx, es, CU_TENSOR_MAP_INTERLEAVE_NONE,
        dn ? CU_TENSOR_MAP_SWIZZLE_128B : i < 3 ? CU_TENSOR_MAP_SWIZZLE_NONE : CU_TENSOR_MAP_SWIZZLE_64B,
        (CUtensorMapL2promotion)X_PROMO, CU_TENSOR_MAP_FLOAT_OOB_FILL_NONE);
  }
  for (int i = 6; i < 10; i++) {
    cuuint64_t gd[3] = {i < 8 ? 32u : 16u, i < 8 ? DM / 2u : DM, NCTA};
    cuuint64_t gs[2] = {i < 8 ? 64u : 32u, DM * 32};
    cuuint32_t bx[3] = {32, 1, (i & 1) ? 128u : 136u};
    cuuint32_t es[3] = {1, 1, 1};
    enc(&tm.m[i], CU_TENSOR_MAP_DATA_TYPE_FLOAT16, 3, scratch->X, gd, gs, bx, es, CU_TENSOR_MAP_INTERLEAVE_NONE, CU_TENSOR_MAP_SWIZZLE_64B,
        CU_TENSOR_MAP_L2_PROMOTION_NONE, CU_TENSOR_MAP_FLOAT_OOB_FILL_NONE);
  }
  Params p;
  p.x = (const unsigned char*)d_in[0];
  bool far = false;
  for (int i = 0; i < 7; i++) {
    p.far[i] = (const unsigned char*)d_in[1 + i];
    const long long d = (long long)((intptr_t)d_in[1 + i] - (intptr_t)d_in[0]);
    p.off[i] = (int)(d / 16);
    if ((long long)p.off[i] * 16 != d || p.off[i] > (1 << 30)) far = true;
  }
  p.dskip = (const uint16_t*)d_in[8];
  p.w_r = (const uint32_t*)d_in[10];
  for (int f = 0; f < 2; f++) {
    static const int kind[17] = {0, 0, 0, 0, 2, 2, 0, 0, 1, 1, 1, 1, 1, 1, 2, 2, 2};
    static const int idx[2][17] = {{2, 3, 4, 5, 6, 8, 0, 1, 0, 1, 2, 3, 4, 5, 0, 2, 4}, {2, 3, 4, 5, 0, -1, 0, 1, 0, 1, 2, 3, 4, 5, 3, -1, 6}};
    static const int blk[2][17] = {{-1, -1, -1, -1, 0, -1, 4, -1, 1, -1, 2, -1, 3, -1, 16, -1, -1}, {-1, -1, -1, -1, 1, -1, 4, -1, -1, -1, 2, -1, 3, -1, 16, -1, -1}};
    const int pitch = f ? 64 : 80;
    for (int u = 0; u < 17; u++) {
      const int s = idx[f][u];
      const uint32_t dst = kind[u] == 0 ? OFF_G + s * 96 * pitch : kind[u] == 2 ? down_box(s, f) : OFF_W + W_BYTES + (s >> 1) * W_BYTES + (s & 1) * 96 * pitch;
      const uint32_t mb = u >= 14 ? (u >= X_HU ? MB_H - OFF_MISC : 0) : blk[f][u] >= 0 ? MB_KF - OFF_MISC + blk[f][u] * 8 : 0;
      p.sched[f][u] = s < 0 ? 3u : kind[u] | s << 2 | mb << 6 | dst << 14;
    }
  }
  p.out = (uint32_t*)d_out;
  p.off[7] = 0;
  p.ts = nullptr;
  p.s = scratch;
  if (far) { fused_kernel<true><<<NCTA, NT, SMEM_BYTES, cudaStreamPerThread>>>(p, tm); return; }
  fused_kernel<false><<<NCTA, NT, SMEM_BYTES, cudaStreamPerThread>>>(p, tm);
}
```

```cpp
#include <cuda_runtime.h>
#include <cuda.h>
#include <cuda_bf16.h>
#include <cuda_fp16.h>
#include <stdint.h>
#include <stddef.h>

namespace {

constexpr int NCTA = 128;
constexpr int NT = 640;
constexpr int DM = 576;
constexpr int FF = 4608;
constexpr int SPIN_MAX = 1 << 20;

struct Scratch {
  uint4 X[NCTA * DM * 2];
  uint4 KX[64 * 128];
  uint4 HS[1152 + 8];
  uint4 R[256];
  uint4 SC[256];
  uint32_t FLAG[NCTA * 8];
};
__device__ Scratch g_S;

#define CLKS(i)
#define TS(i)
#define TSX(i)
#define TS_DUMP()

constexpr int SB = 1024;
constexpr int BOX = 15360;
constexpr int OFF_G = SB;
constexpr int OFF_W = OFF_G + 3 * BOX;
constexpr int W_KT = 26624;
constexpr int W_QT = W_KT + 64 + 2048 + 80;
constexpr int W_L3 = W_KT + 4352;
constexpr int W_CW = W_L3 + 4160;
constexpr int W_MISC = W_CW + 640;
constexpr int W_BYTES = 35840;
constexpr int TILE = 10240;
constexpr int OFF_T = OFF_W + 4 * W_BYTES;
constexpr int ALT = TILE - W_KT;
static_assert(W_MISC + 32 <= W_BYTES && OFF_W % 1024 == 0 && W_BYTES % 1024 == 0 && W_BYTES + ALT <= 20480, "wg block");
constexpr int YT_PITCH = 1184;
constexpr int OFF_YT = OFF_T + 2 * TILE;
constexpr int OFF_WR = OFF_YT + 16 * YT_PITCH + 64;
constexpr int OFF_MISC = OFF_WR + 2304;
constexpr int SMEM_BYTES = OFF_MISC + 1024 - SB;
static_assert(OFF_YT % 16 == 0 && OFF_MISC % 16 == 0, "align");
static_assert(SMEM_BYTES <= 232448, "smem");
constexpr int MB_GU = OFF_MISC;
constexpr int MB_D = OFF_MISC + 8;
constexpr int MB_KF = OFF_MISC + 16;
constexpr int MB_GF = OFF_MISC + 48;
constexpr int MB_SC = OFF_MISC + 56;
constexpr int MB_UL = OFF_MISC + 64;
constexpr int MB_REL = OFF_MISC + 104;
constexpr int MB_GO = OFF_MISC + 112;
constexpr int MB_H = MB_KF + 128;
constexpr int MISC_EPOCH = OFF_MISC + 152;
constexpr int MISC_SW = OFF_MISC + 156;
constexpr int MISC_RT = OFF_MISC + 160;
constexpr int MISC_T0 = OFF_MISC + 296;
constexpr int MISC_EM = OFF_MISC + 288;
constexpr int OFF_PART = OFF_W + 20480;
constexpr int OFF_RK = OFF_PART + 3840;
constexpr int MISC_LN1 = OFF_MISC + 192;
constexpr int OFF_XS = OFF_T;
constexpr int OFF_RED = OFF_T + TILE;
constexpr int OFF_FIN = OFF_W + 3 * W_BYTES + W_KT;
constexpr int OFF_ACT = OFF_FIN + 4096;
constexpr int MISC_CNT = OFF_ACT + 1024;

__device__ __forceinline__ uint32_t smem_u32(const void* p) { return (uint32_t)__cvta_generic_to_shared(p); }
__device__ __forceinline__ uint32_t lds32(uint32_t a) { uint32_t v; asm volatile("ld.shared.b32 %0, [%1];" : "=r"(v) : "r"(a) : "memory"); return v; }
__device__ __forceinline__ uint32_t lds16(uint32_t a) { uint16_t v; asm volatile("ld.shared.u16 %0, [%1];" : "=h"(v) : "r"(a) : "memory"); return v; }
__device__ __forceinline__ uint2 lds64(uint32_t a) { uint2 v; asm volatile("ld.shared.v2.b32 {%0,%1}, [%2];" : "=r"(v.x), "=r"(v.y) : "r"(a) : "memory"); return v; }
__device__ __forceinline__ uint4 lds128(uint32_t a) { uint4 v; asm volatile("ld.shared.v4.b32 {%0,%1,%2,%3}, [%4];" : "=r"(v.x), "=r"(v.y), "=r"(v.z), "=r"(v.w) : "r"(a) : "memory"); return v; }
__device__ __forceinline__ void sts16(uint32_t a, uint32_t v) { asm volatile("st.shared.u16 [%0], %1;" :: "r"(a), "h"((uint16_t)v) : "memory"); }
__device__ __forceinline__ void sts32(uint32_t a, uint32_t v) { asm volatile("st.shared.b32 [%0], %1;" :: "r"(a), "r"(v) : "memory"); }
__device__ __forceinline__ void sts64(uint32_t a, uint32_t x, uint32_t y) { asm volatile("st.shared.v2.b32 [%0], {%1,%2};" :: "r"(a), "r"(x), "r"(y) : "memory"); }
__device__ __forceinline__ void sts128(uint32_t a, uint32_t x, uint32_t y, uint32_t z, uint32_t w) { asm volatile("st.shared.v4.b32 [%0], {%1,%2,%3,%4};" :: "r"(a), "r"(x), "r"(y), "r"(z), "r"(w) : "memory"); }
__device__ __forceinline__ void ldsm4(uint32_t a, uint32_t& r0, uint32_t& r1, uint32_t& r2, uint32_t& r3) {
  asm volatile("ldmatrix.sync.aligned.m8n8.x4.shared.b16 {%0,%1,%2,%3}, [%4];" : "=r"(r0), "=r"(r1), "=r"(r2), "=r"(r3) : "r"(a) : "memory");
}
__device__ __forceinline__ void ldsm4t(uint32_t a, uint32_t& r0, uint32_t& r1, uint32_t& r2, uint32_t& r3) {
  asm volatile("ldmatrix.sync.aligned.m8n8.x4.trans.shared.b16 {%0,%1,%2,%3}, [%4];" : "=r"(r0), "=r"(r1), "=r"(r2), "=r"(r3) : "r"(a) : "memory");
}
__device__ __forceinline__ void stsm4t(uint32_t a, uint32_t r0, uint32_t r1, uint32_t r2, uint32_t r3) {
  asm volatile("stmatrix.sync.aligned.m8n8.x4.trans.shared.b16 [%0], {%1,%2,%3,%4};" :: "r"(a), "r"(r0), "r"(r1), "r"(r2), "r"(r3) : "memory");
}
__device__ __forceinline__ uint4 ldr128(const void* p) {
  unsigned long long lo, hi;
  asm volatile("{ .reg .b128 t; ld.relaxed.gpu.global.b128 t, [%2]; mov.b128 {%0, %1}, t; }" : "=l"(lo), "=l"(hi) : "l"(p) : "memory");
  return make_uint4((uint32_t)lo, (uint32_t)(lo >> 32), (uint32_t)hi, (uint32_t)(hi >> 32));
}
__device__ __forceinline__ void str128(void* p, uint32_t x, uint32_t y, uint32_t z, uint32_t w) {
  asm volatile("{ .reg .b128 t; .reg .b64 lo, hi; mov.b64 lo, {%1,%2}; mov.b64 hi, {%3,%4}; mov.b128 t, {lo, hi}; st.relaxed.gpu.global.b128 [%0], t; }"
               :: "l"(p), "r"(x), "r"(y), "r"(z), "r"(w) : "memory");
}
__device__ __forceinline__ uint32_t ldr32(const void* p) { uint32_t v; asm volatile("ld.relaxed.gpu.global.b32 %0, [%1];" : "=r"(v) : "l"(p) : "memory"); return v; }
__device__ __forceinline__ void str32(void* p, uint32_t v) { asm volatile("st.relaxed.gpu.global.b32 [%0], %1;" :: "l"(p), "r"(v) : "memory"); }
__device__ __forceinline__ void str16(void* p, uint32_t v) { asm volatile("st.relaxed.gpu.global.u16 [%0], %1;" :: "l"(p), "h"((uint16_t)v) : "memory"); }
__device__ __forceinline__ void bar_sync(int id, int n) { asm volatile("bar.sync %0, %1;" :: "r"(id), "r"(n) : "memory"); }
__device__ __forceinline__ void bar_arrive(int id, int n) { asm volatile("bar.arrive %0, %1;" :: "r"(id), "r"(n) : "memory"); }

__device__ __forceinline__ float bf_lo(uint32_t w) { return __uint_as_float(w << 16); }
__device__ __forceinline__ float bf_hi(uint32_t w) { return __uint_as_float(w & 0xFFFF0000u); }
__device__ __forceinline__ uint32_t pack_bf(float lo, float hi) { uint32_t r; asm("cvt.rn.bf16x2.f32 %0, %1, %2;" : "=r"(r) : "f"(hi), "f"(lo)); return r; }
__device__ __forceinline__ uint32_t pack_h(float lo, float hi) { uint32_t r; asm("cvt.rn.f16x2.f32 %0, %1, %2;" : "=r"(r) : "f"(hi), "f"(lo)); return r; }
__device__ __forceinline__ float bfr(float x) { return bf_lo(pack_bf(x, 0.f)); }
__device__ __forceinline__ uint32_t bf_sub2(uint32_t a, uint32_t b) { __nv_bfloat162 r = __hsub2(*(__nv_bfloat162*)&a, *(__nv_bfloat162*)&b); return *(uint32_t*)&r; }
__device__ __forceinline__ uint32_t bf_add2(uint32_t a, uint32_t b) { __nv_bfloat162 r = __hadd2(*(__nv_bfloat162*)&a, *(__nv_bfloat162*)&b); return *(uint32_t*)&r; }
__device__ __forceinline__ uint32_t bf_mul2(uint32_t a, uint32_t b) { __nv_bfloat162 r = __hmul2(*(__nv_bfloat162*)&a, *(__nv_bfloat162*)&b); return *(uint32_t*)&r; }
__device__ __forceinline__ float2 h2f(uint32_t w) { return __half22float2(*(__half2*)&w); }
__device__ __forceinline__ float ex2(float x) { float r; asm("ex2.approx.ftz.f32 %0, %1;" : "=f"(r) : "f"(x)); return r; }
__device__ __forceinline__ float warp_sum(float v) {
#pragma unroll
  for (int o = 16; o > 0; o >>= 1) v += __shfl_xor_sync(0xffffffffu, v, o);
  return v;
}
__device__ __forceinline__ void mma_bf16(float* d, uint32_t a0, uint32_t a1, uint32_t a2, uint32_t a3, uint32_t b0, uint32_t b1) {
  asm volatile("mma.sync.aligned.m16n8k16.row.col.f32.bf16.bf16.f32 {%0,%1,%2,%3}, {%4,%5,%6,%7}, {%8,%9}, {%0,%1,%2,%3};"
               : "+f"(d[0]), "+f"(d[1]), "+f"(d[2]), "+f"(d[3]) : "r"(a0), "r"(a1), "r"(a2), "r"(a3), "r"(b0), "r"(b1));
}
__device__ __forceinline__ void mma_bf16_k8(float* d, uint32_t a0, uint32_t a1, uint32_t b0) {
  asm volatile("mma.sync.aligned.m16n8k8.row.col.f32.bf16.bf16.f32 {%0,%1,%2,%3}, {%4,%5}, {%6}, {%0,%1,%2,%3};"
               : "+f"(d[0]), "+f"(d[1]), "+f"(d[2]), "+f"(d[3]) : "r"(a0), "r"(a1), "r"(b0));
}

__device__ __forceinline__ void wg_fence() { asm volatile("wgmma.fence.sync.aligned;" ::: "memory"); }
__device__ __forceinline__ void wg_commit() { asm volatile("wgmma.commit_group.sync.aligned;" ::: "memory"); }
template <int N> __device__ __forceinline__ void wg_wait() { asm volatile("wgmma.wait_group.sync.aligned %0;" :: "n"(N) : "memory"); }
template <int TB> __device__ __forceinline__ void wgmma32(float* d, const uint32_t* a, uint32_t dlo, uint32_t dhi) {
  asm volatile("{ .reg .b64 dd; mov.b64 dd, {%20, %21}; wgmma.mma_async.sync.aligned.m64n32k16.f32.f16.f16 "
               "{%0,%1,%2,%3,%4,%5,%6,%7,%8,%9,%10,%11,%12,%13,%14,%15}, {%16,%17,%18,%19}, dd, 1, 1, 1, %22; }"
               : "+f"(d[0]), "+f"(d[1]), "+f"(d[2]), "+f"(d[3]), "+f"(d[4]), "+f"(d[5]), "+f"(d[6]), "+f"(d[7]), "+f"(d[8]), "+f"(d[9]), "+f"(d[10]), "+f"(d[11]), "+f"(d[12]), "+f"(d[13]), "+f"(d[14]), "+f"(d[15])
               : "r"(a[0]), "r"(a[1]), "r"(a[2]), "r"(a[3]), "r"(dlo), "r"(dhi), "n"(TB));
}
template <int TB> __device__ __forceinline__ void wgmma64(float* d, const uint32_t* a, uint32_t dlo, uint32_t dhi) {
  asm volatile("{ .reg .b64 dd; mov.b64 dd, {%36, %37}; wgmma.mma_async.sync.aligned.m64n64k16.f32.f16.f16 "
               "{%0,%1,%2,%3,%4,%5,%6,%7,%8,%9,%10,%11,%12,%13,%14,%15,%16,%17,%18,%19,%20,%21,%22,%23,%24,%25,%26,%27,%28,%29,%30,%31}, {%32,%33,%34,%35}, dd, 1, 1, 1, %38; }"
               : "+f"(d[0]), "+f"(d[1]), "+f"(d[2]), "+f"(d[3]), "+f"(d[4]), "+f"(d[5]), "+f"(d[6]), "+f"(d[7]), "+f"(d[8]), "+f"(d[9]), "+f"(d[10]), "+f"(d[11]), "+f"(d[12]), "+f"(d[13]), "+f"(d[14]), "+f"(d[15]), "+f"(d[16]), "+f"(d[17]), "+f"(d[18]), "+f"(d[19]), "+f"(d[20]), "+f"(d[21]), "+f"(d[22]), "+f"(d[23]), "+f"(d[24]), "+f"(d[25]), "+f"(d[26]), "+f"(d[27]), "+f"(d[28]), "+f"(d[29]), "+f"(d[30]), "+f"(d[31])
               : "r"(a[0]), "r"(a[1]), "r"(a[2]), "r"(a[3]), "r"(dlo), "r"(dhi), "n"(TB));
}
template <int TB> __device__ __forceinline__ void wgmma64_init(float* d, const uint32_t* a, uint32_t dlo, uint32_t dhi) {
  asm volatile("{ .reg .b64 dd; mov.b64 dd, {%36, %37}; wgmma.mma_async.sync.aligned.m64n64k16.f32.f16.f16 "
               "{%0,%1,%2,%3,%4,%5,%6,%7,%8,%9,%10,%11,%12,%13,%14,%15,%16,%17,%18,%19,%20,%21,%22,%23,%24,%25,%26,%27,%28,%29,%30,%31}, {%32,%33,%34,%35}, dd, 0, 1, 1, %38; }"
               : "=f"(d[0]), "=f"(d[1]), "=f"(d[2]), "=f"(d[3]), "=f"(d[4]), "=f"(d[5]), "=f"(d[6]), "=f"(d[7]), "=f"(d[8]), "=f"(d[9]), "=f"(d[10]), "=f"(d[11]), "=f"(d[12]), "=f"(d[13]), "=f"(d[14]), "=f"(d[15]), "=f"(d[16]), "=f"(d[17]), "=f"(d[18]), "=f"(d[19]), "=f"(d[20]), "=f"(d[21]), "=f"(d[22]), "=f"(d[23]), "=f"(d[24]), "=f"(d[25]), "=f"(d[26]), "=f"(d[27]), "=f"(d[28]), "=f"(d[29]), "=f"(d[30]), "=f"(d[31])
               : "r"(a[0]), "r"(a[1]), "r"(a[2]), "r"(a[3]), "r"(dlo), "r"(dhi), "n"(TB));
}
template <int TB> __device__ __forceinline__ void wgmma32_init(float* d, const uint32_t* a, uint32_t dlo, uint32_t dhi) {
  asm volatile("{ .reg .b64 dd; mov.b64 dd, {%20, %21}; wgmma.mma_async.sync.aligned.m64n32k16.f32.f16.f16 "
               "{%0,%1,%2,%3,%4,%5,%6,%7,%8,%9,%10,%11,%12,%13,%14,%15}, {%16,%17,%18,%19}, dd, 0, 1, 1, %22; }"
               : "=f"(d[0]), "=f"(d[1]), "=f"(d[2]), "=f"(d[3]), "=f"(d[4]), "=f"(d[5]), "=f"(d[6]), "=f"(d[7]), "=f"(d[8]), "=f"(d[9]), "=f"(d[10]), "=f"(d[11]), "=f"(d[12]), "=f"(d[13]), "=f"(d[14]), "=f"(d[15])
               : "r"(a[0]), "r"(a[1]), "r"(a[2]), "r"(a[3]), "r"(dlo), "r"(dhi), "n"(TB));
}
__device__ __forceinline__ void wgmma64h(uint32_t* d, uint32_t a0, uint32_t a1, uint32_t a2, uint32_t a3, uint32_t dlo, uint32_t dhi) {
  asm volatile("{ .reg .b64 dd; mov.b64 dd, {%20, %21}; wgmma.mma_async.sync.aligned.m64n64k16.f16.f16.f16 "
               "{%0,%1,%2,%3,%4,%5,%6,%7,%8,%9,%10,%11,%12,%13,%14,%15}, {%16,%17,%18,%19}, dd, 1, 1, 1, 0; }"
               : "+r"(d[0]), "+r"(d[1]), "+r"(d[2]), "+r"(d[3]), "+r"(d[4]), "+r"(d[5]), "+r"(d[6]), "+r"(d[7]), "+r"(d[8]), "+r"(d[9]), "+r"(d[10]), "+r"(d[11]), "+r"(d[12]), "+r"(d[13]), "+r"(d[14]), "+r"(d[15])
               : "r"(a0), "r"(a1), "r"(a2), "r"(a3), "r"(dlo), "r"(dhi));
}
__device__ __forceinline__ void wgmma64h_init(uint32_t* d, uint32_t a0, uint32_t a1, uint32_t a2, uint32_t a3, uint32_t dlo, uint32_t dhi) {
  asm volatile("{ .reg .b64 dd; mov.b64 dd, {%20, %21}; wgmma.mma_async.sync.aligned.m64n64k16.f16.f16.f16 "
               "{%0,%1,%2,%3,%4,%5,%6,%7,%8,%9,%10,%11,%12,%13,%14,%15}, {%16,%17,%18,%19}, dd, 0, 1, 1, 0; }"
               : "=r"(d[0]), "=r"(d[1]), "=r"(d[2]), "=r"(d[3]), "=r"(d[4]), "=r"(d[5]), "=r"(d[6]), "=r"(d[7]), "=r"(d[8]), "=r"(d[9]), "=r"(d[10]), "=r"(d[11]), "=r"(d[12]), "=r"(d[13]), "=r"(d[14]), "=r"(d[15])
               : "r"(a0), "r"(a1), "r"(a2), "r"(a3), "r"(dlo), "r"(dhi));
}
__device__ __forceinline__ void wgmma40_ss(float* d, uint32_t alo, uint32_t blo, uint32_t hi) {
  asm volatile("{ .reg .b64 da, db; mov.b64 da, {%20, %22}; mov.b64 db, {%21, %22}; "
               "wgmma.mma_async.sync.aligned.m64n40k16.f32.f16.f16 {%0,%1,%2,%3,%4,%5,%6,%7,%8,%9,%10,%11,%12,%13,%14,%15,%16,%17,%18,%19}, da, db, 1, 1, 1, 1, 1; }"
               : "+f"(d[0]), "+f"(d[1]), "+f"(d[2]), "+f"(d[3]), "+f"(d[4]), "+f"(d[5]), "+f"(d[6]), "+f"(d[7]), "+f"(d[8]), "+f"(d[9]), "+f"(d[10]), "+f"(d[11]), "+f"(d[12]), "+f"(d[13]), "+f"(d[14]), "+f"(d[15]), "+f"(d[16]), "+f"(d[17]), "+f"(d[18]), "+f"(d[19])
               : "r"(alo), "r"(blo), "r"(hi));
}
__device__ __forceinline__ void wgmma40_ss_init(float* d, uint32_t alo, uint32_t blo, uint32_t hi) {
  asm volatile("{ .reg .b64 da, db; mov.b64 da, {%20, %22}; mov.b64 db, {%21, %22}; "
               "wgmma.mma_async.sync.aligned.m64n40k16.f32.f16.f16 {%0,%1,%2,%3,%4,%5,%6,%7,%8,%9,%10,%11,%12,%13,%14,%15,%16,%17,%18,%19}, da, db, 0, 1, 1, 1, 1; }"
               : "=f"(d[0]), "=f"(d[1]), "=f"(d[2]), "=f"(d[3]), "=f"(d[4]), "=f"(d[5]), "=f"(d[6]), "=f"(d[7]), "=f"(d[8]), "=f"(d[9]), "=f"(d[10]), "=f"(d[11]), "=f"(d[12]), "=f"(d[13]), "=f"(d[14]), "=f"(d[15]), "=f"(d[16]), "=f"(d[17]), "=f"(d[18]), "=f"(d[19])
               : "r"(alo), "r"(blo), "r"(hi));
}
__device__ __forceinline__ void tma_box(uint32_t dst, const CUtensorMap* tm, uint32_t mb, int x, int y) {
  asm volatile("cp.async.bulk.tensor.2d.shared::cluster.global.mbarrier::complete_tx::bytes [%0], [%1, {%3, %4}], [%2];"
               :: "r"(dst), "l"(tm), "r"(mb), "r"(x), "r"(y) : "memory");
}
__device__ __forceinline__ uint32_t uni(uint32_t v) {
  uint32_t r; asm volatile("shfl.sync.idx.b32 %0, %1, 0, 0x1f, 0xffffffff;" : "=r"(r) : "r"(v)); return r;
}
__device__ __forceinline__ uint32_t pin(uint32_t v) {
  uint32_t r; asm volatile("shfl.sync.bfly.b32 %0, %1, 0, 0x1f, 0xffffffff;" : "=r"(r) : "r"(v)); return r;
}

struct Params {
  const unsigned char* x;
  Scratch* s;
  int off[8];
  uint32_t* out;
  const uint16_t* dskip;
  const uint32_t* w_r;
  long long* ts;
  const unsigned char* far[7];
  uint32_t sched[2][17];
};
__device__ __forceinline__ uint32_t ldnc32(const void* p) { uint32_t v; asm volatile("ld.global.nc.b32 %0, [%1];" : "=r"(v) : "l"(p)); return v; }
__device__ __forceinline__ uint32_t ldnc16(const void* p) { uint16_t v; asm volatile("ld.global.nc.u16 %0, [%1];" : "=h"(v) : "l"(p)); return v; }
__device__ __forceinline__ void mbar_wait(uint32_t mb, uint32_t ph = 0) {
#pragma unroll 1
  for (int it = 0; it < SPIN_MAX; it++) {
    uint32_t ok;
    asm volatile("{ .reg .pred q; mbarrier.try_wait.parity.shared::cta.b64 q, [%1], %2; selp.u32 %0, 1, 0, q; }" : "=r"(ok) : "r"(mb), "r"(ph) : "memory");
    if (ok) break;
  }
}
__device__ __forceinline__ void mbar_arrive(uint32_t mb) { asm volatile("mbarrier.arrive.shared::cta.b64 _, [%0];" :: "r"(mb) : "memory"); }
__device__ __forceinline__ void fence_async() { asm volatile("fence.proxy.async.shared::cta;" ::: "memory"); }
#define SPIN_WHILE(cond, body) _Pragma("unroll 1") for (int _it = 0; _it < SPIN_MAX && __any_sync(0xffffffffu, (cond)); _it++) { body; }

struct LnC { uint32_t m2, rh2, rl2; };
__device__ __forceinline__ LnC ln_consts(float s, float q, float& r) {
  const float mean = s * (1.f / DM);
  const float var = fmaxf(fmaf(-mean, mean, q * (1.f / DM)), 0.f);
  float sd;
  asm("sqrt.approx.ftz.f32 %0, %1;" : "=f"(sd) : "f"(bfr(bfr(var) + 1e-5f)));
  asm("rcp.approx.ftz.f32 %0, %1;" : "=f"(r) : "f"(bfr(sd)));
  LnC c;
  c.m2 = pack_bf(mean, mean);
  c.rh2 = pack_bf(r, r);
  const float rl = r - bf_lo(c.rh2);
  c.rl2 = pack_bf(rl, rl);
  return c;
}
__device__ __forceinline__ uint32_t bf_fma2(uint32_t a, uint32_t b, uint32_t c) {
  __nv_bfloat162 r = __hfma2(*(const __nv_bfloat162*)&a, *(const __nv_bfloat162*)&b, *(const __nv_bfloat162*)&c);
  return *(uint32_t*)&r;
}
__device__ __forceinline__ uint32_t ln_apply(uint32_t w, uint32_t m2, uint32_t rh2, uint32_t rl2) {
  const uint32_t d = bf_sub2(w, m2);
  return bf_fma2(d, rh2, bf_mul2(d, rl2));
}

__device__ __forceinline__ float2 cis(float mag_log2, float rev) {
  const float m = ex2(mag_log2), ang = rev * 6.283185307179586f;
  return make_float2(m * __cosf(ang), m * __sinf(ang));
}
__device__ __forceinline__ float2 csq(float2 a) { return make_float2(fmaf(a.x, a.x, -a.y * a.y), (a.x + a.x) * a.y); }
__device__ __forceinline__ float2 cmul(float2 a, float2 b) { return make_float2(fmaf(a.x, b.x, -a.y * b.y), fmaf(a.x, b.y, a.y * b.x)); }
__device__ __forceinline__ void pmul(uint32_t xr, uint32_t xi, uint32_t w, uint32_t& yr, uint32_t& yi) {
  const __half2 XR = *(__half2*)&xr, XI = *(__half2*)&xi, W = *(__half2*)&w;
  const __half2 a = __hfma2(__hneg2(XI), __high2half2(W), __hmul2(XR, __low2half2(W)));
  const __half2 b = __hfma2(XI, __low2half2(W), __hmul2(XR, __high2half2(W)));
  yr = *(const uint32_t*)&a; yi = *(const uint32_t*)&b;
}
__device__ __forceinline__ uint32_t pk(float2 a) { return pack_h(a.x, a.y); }

struct KgState { float2 c0, z8; float kl; uint32_t w64, w128, w192; };
__device__ __forceinline__ void kgen_tables_n(const uint32_t (&raw)[7], uint32_t scr, int wt, KgState& k) {
  const uint32_t dst = scr + 16384 + wt * 16;
  const float dt = bfr(ex2(bf_lo(raw[6]) * 1.4426950408889634f));
  const float th = dt * bf_lo(raw[1]);
  const float br = dt * bf_lo(raw[2]), bi = dt * bf_lo(raw[3]);
  const float Cr = bf_lo(raw[4]), Ci = bf_lo(raw[5]);
  k.c0 = make_float2(fmaf(Cr, br, -Ci * bi), fmaf(Cr, bi, Ci * br));
  const uint32_t mx = __reduce_max_sync(0xffffffffu, __float_as_uint(fmaxf(fabsf(k.c0.x), fabsf(k.c0.y))));
  const float a2 = dt * bf_lo(raw[0]) * 1.4426950408889634f;
  const float rh = th * 0.15915494309189535f;
  const float rl = fmaf(th, (float)(0.15915494309189535 - (double)0.15915494309189535f), fmaf(th, 0.15915494309189535f, -rh));
  const float rf = rh - rintf(rh);
  const float2 z1 = cis(a2, rf + rl);
  const float p64 = rf * 64.f;
  const float2 z64 = cis(a2 * 64.f, fmaf(64.f, rl, p64 - rintf(p64)));
  const float2 z2 = csq(z1), z128 = csq(z64), z3 = cmul(z2, z1), z4 = csq(z2), z256 = csq(z128), z6 = csq(z3), z512 = csq(z256);
  k.z8 = csq(z4);
  k.w64 = pk(z64); k.w128 = pk(z128); k.w192 = pk(cmul(z128, z64));
  sts128(dst, 0x00003C00u, pk(z2), pk(z4), pk(z6));
  const float2 z1024 = csq(z512), z768 = cmul(z512, z256);
  sts128(dst + 2048, pk(z1), pk(z3), pk(cmul(z4, z1)), pk(cmul(z4, z3)));
  const float2 z2048 = csq(z1024);
  k.kl = fmaf(k.c0.x, z2048.x, -k.c0.y * z2048.y);
  sts128(dst + 4096, pk(z256), pk(cmul(z256, z2)), pk(cmul(z256, z4)), pk(cmul(z256, z6)));
  sts128(dst + 6144, pk(z512), pk(cmul(z512, z4)), pk(z768), pk(cmul(z768, z4)));
  sts128(dst + 8192, pk(z1024), pk(cmul(z1024, z256)), pk(cmul(z1024, z512)), pk(cmul(z1024, z768)));
  sts32(scr + W_MISC + (wt >> 5) * 4, mx);
}
__device__ __forceinline__ int kgen_tables_m(uint32_t scr, int wt, const KgState& k) {
  const uint32_t dst = scr + wt * 16;
  const uint4 e4 = lds128(scr + W_MISC);
  const float2 z16 = csq(k.z8), z32 = csq(z16);
  const int em = max(min((int)(max(max(e4.x, e4.y), max(e4.z, e4.w)) >> 23), 238), 16);
  const float sc = __uint_as_float((uint32_t)(127 + 4 + 127 - em) << 23);
  sts32(scr + W_MISC + 16 + (wt >> 5) * 4, __reduce_add_sync(0xffffffffu, __float2int_rn(k.kl * sc * 262144.f)));
  const float2 c0 = make_float2(k.c0.x * sc, k.c0.y * sc);
  const float2 c1 = cmul(c0, k.z8), c2 = cmul(c0, z16), c4 = cmul(c0, z32), c3 = cmul(c1, z16), c5 = cmul(c1, z32), c6 = cmul(c2, z32), c7 = cmul(c3, z32);
  uint32_t pr[4], pi[4], yr[4], yi[4];
  pr[0] = pack_h(c0.x, c1.x); pi[0] = pack_h(c0.y, c1.y);
  pr[1] = pack_h(c2.x, c3.x); pi[1] = pack_h(c2.y, c3.y);
  pr[2] = pack_h(c4.x, c5.x); pi[2] = pack_h(c4.y, c5.y);
  pr[3] = pack_h(c6.x, c7.x); pi[3] = pack_h(c6.y, c7.y);
  sts128(dst, pr[0], pr[1], pr[2], pr[3]); sts128(dst + 2048, pi[0], pi[1], pi[2], pi[3]);
#pragma unroll
  for (int q = 1; q < 4; q++) {
    const uint32_t w = q == 1 ? k.w64 : q == 2 ? k.w128 : k.w192;
#pragma unroll
    for (int i = 0; i < 4; i++) pmul(pr[i], pi[i], w, yr[i], yi[i]);
    sts128(dst + q * 4096, yr[0], yr[1], yr[2], yr[3]); sts128(dst + q * 4096 + 2048, yi[0], yi[1], yi[2], yi[3]);
  }
  return em;
}
__device__ __forceinline__ uint32_t lds32_if(uint32_t a, bool on) {
  uint32_t v; asm volatile("{ .reg .pred q; setp.ne.u32 q, %2, 0; mov.b32 %0, 0; @q ld.shared.b32 %0, [%1]; }" : "=r"(v) : "r"(a), "r"((uint32_t)on) : "memory"); return v;
}
__device__ __forceinline__ uint32_t prmt(uint32_t a, uint32_t b, uint32_t s) { uint32_t r; asm("prmt.b32 %0, %1, %2, %3;" : "=r"(r) : "r"(a), "r"(b), "r"(s)); return r; }
struct BuildC { uint32_t a3, a2, az, cw, sel; };
__device__ __forceinline__ BuildC build_consts(int wt) {
  const int ix = ((wt >> 2) + (wt & 3) * 32 - 1) & 127;
  BuildC b;
  b.a3 = W_CW + 32 + ((ix & 1) ? 0 : 304) + (ix >> 1) * 4;
  b.a2 = W_L3 + 3072 + 544 + (wt & ~3) * 2 + (wt & 1) * 4 + (wt & 2) * 128;
  b.az = W_KT + (wt < 36 ? -512 : 64 + 4128 - 576) + wt * 16;
  b.cw = W_CW + 32 + (wt >> 6) * 48 + wt * 4;
  b.sel = (wt & 1) ? 0x10767610 : wt ? 0x10101010 : 0x10107610;
  return b;
}
__device__ __forceinline__ void kgen_build(uint32_t tb, const BuildC& bc, int wg, int wt, uint32_t k0, uint32_t k1, uint32_t k2) {
  const uint32_t kt = tb + W_KT, sc = tb + W_L3 + 3072;
  const uint32_t a3 = tb + bc.a3, a2 = tb + bc.a2;
  const uint32_t v3 = wt ? k2 : k2 >> 16;
  sts32(sc + 4 + wt * 4, __byte_perm(k0, k1, 0x5432));
  sts16(a2, k1 >> 16); sts16(a2 + 6, k1 >> 16);
  sts16(a3, v3); sts16(a3 + 6, v3);
  if ((unsigned)(wt - 32) < 14u) sts128(tb + bc.az, 0, 0, 0, 0);
  if (wt == 127) sts32(sc, k0 & 0xFFFF0000u);
  if (wt == 0) { sts32(sc + 516, k1); sts16(sc + 1056, k2); }
  bar_sync(1 + wg, 128);
  const uint32_t cw = tb + bc.cw, g2 = sc + 540 + wt * 4;
  const bool odd = wt & 1, ends = (unsigned)(wt - 4) >= 120u;
  const uint32_t pv = lds32(sc + wt * 4), nx = lds32(sc + 8 + wt * 4), nc = lds32_if(g2 + 8, ends);
  const uint32_t l0 = lds32(cw), l1 = lds32(cw - 8), l2 = lds32(cw - 16), l3 = lds32(cw - 24), q0 = lds32(g2), q1 = lds32(g2 + 128), q2 = lds32(g2 - 8), q3 = lds32(g2 + 120);
  sts64(kt + 64 + wt * 8, __byte_perm(k0, pv, 0x5410), __byte_perm(k0, 0, 0x1032));
  sts64(kt + 64 + 1024 + wt * 8, prmt(k1, pv, bc.sel), prmt(k1, nx, bc.sel >> 16));
  const uint32_t cc = __byte_perm(nc, 0, 0x3232), nn = __byte_perm(nc, 0, 0x1010);
  if (ends) sts128(kt + 64 + 2048 + wt * 16, cc, cc, odd ? nc : cc, odd ? nn : nc);
  if (wt == 127) { sts128(kt + 64 + 4096, nn, nn, nn, nn); sts128(kt + 64 + 4112, nn, nn << 16, 0, 0); }
  sts128(tb + W_L3 + 512 + (wt >> 6) * 512 + wt * 16, l0, l1, l2, l3);
  if ((wt & 63) < 34) sts128(tb + W_QT - 16 + wt * 16, q0, q1, q2, q3);
}

__device__ __forceinline__ void load_a(uint32_t (&a)[4], uint32_t kp, int j) {
  a[0] = lds32(kp + 64 * j); a[1] = lds32(kp + 64 * j + 512); a[2] = lds32(kp + 64 * j - 32); a[3] = lds32(kp + 64 * j + 480);
}
__device__ __forceinline__ uint32_t band8(int s) { return ((((0x1FFu << 20) >> s) & 0x01010101u) | (((0x7Fu << 25) >> s) & 0x10101010u)) * 0x01020408u; }
__device__ __forceinline__ uint32_t hadd2u(uint32_t a, uint32_t b) { __half2 r = __hadd2(*(__half2*)&a, *(__half2*)&b); return *(uint32_t*)&r; }

__device__ __forceinline__ void zero_pads(uint32_t tb, int wt) {
  if (!(wt & 32)) sts128(tb + W_L3 + (wt >> 6) * 512 + wt * 16, 0, 0, 0, 0);
  if ((wt & 63) < 3) sts128(tb + W_CW + (wt >> 6) * 304 + (wt & 63) * 16, 0, 0, 0, 0);
}
__device__ __forceinline__ uint32_t tr_base(int lane) {
  return OFF_YT + (2 * (lane >> 3) + (lane & 1)) * YT_PITCH + ((lane >> 1) & 1) * (8 * YT_PITCH + 64) + ((lane >> 2) & 1) * 16;
}

__device__ __forceinline__ uint32_t sc_addr(int tp) { return OFF_YT + (tp < 16 ? tp * YT_PITCH + (tp >> 3) * 64 + 1152 : 8 * YT_PITCH - 512 + tp * 32); }
#define X_PW 15
#define X_HU 16
#define X_NE 2
#define X_SCT 10000
#define X_DELTA 0
#define X_DSTEP 2000
#define X_PF0 2700
#define X_PFD 600
#define X_TD 450
#define X_WS 6
#define X_OR 8
#define X_ABS 4870
#define X_XD 200
#define X_RD 630
#define X_HD 450
#define X_PD 1170
#define X_PROMO 2
#define X_YD2 1000
#define X_GO 1
#define X_GW 2
#define X_NS 4300
#define X_XS 13450
#define X_LAG 1300
#define X_YD 1550
struct TMaps { CUtensorMap m[10]; };
__device__ __forceinline__ uint32_t h2bf(uint32_t w) { const float2 f = h2f(w); return pack_bf(f.x, f.y); }
__device__ __forceinline__ uint32_t keep(uint32_t v) { asm volatile("" : "+r"(v)); return v; }
__device__ __forceinline__ uint2 ldr64(const void* p) { uint2 v; asm volatile("{ .reg .b64 t; ld.relaxed.gpu.global.b64 t, [%2]; mov.b64 {%0, %1}, t; }" : "=r"(v.x), "=r"(v.y) : "l"(p) : "memory"); return v; }
__host__ __device__ __forceinline__ uint32_t down_box(int s, bool five) {
  return five ? OFF_W + W_BYTES + 12288 + (s / 3) * (W_BYTES - 12288) + s * 4096 : s < 6 ? OFF_W + W_BYTES + BOX + (s >> 1) * (W_BYTES - 10240) + s * 5120 : OFF_W + (s - 6) * 5120;
}
__device__ __forceinline__ void load_tile(const CUtensorMap* tmx, int i, int c, int again = 0) {
  asm volatile("mbarrier.arrive.expect_tx.shared::cta.b64 _, [%0], 8704;" :: "r"(MB_UL + i * 16 + again) : "memory");
  asm volatile("cp.async.bulk.tensor.3d.shared::cluster.global.mbarrier::complete_tx::bytes [%0], [%1, {%3, %4, %5}], [%2];"
               :: "r"(i < 2 ? OFF_T + i * TILE : OFF_W), "l"(tmx), "r"(MB_UL + i * 16 + again), "r"(0), "r"(c), "r"(-8) : "memory");
}
template <bool FAR> __device__ __forceinline__ void load_params(const Params& p, uint32_t ch, int wt, uint32_t dst, bool on) {
  const int rel = wt < 96 ? ch * 16 + (wt & 15) : ch >> 3;
  const unsigned char* b = FAR ? p.far[min(wt >> 4, 6)] + rel * 16 : p.x + (long long)(p.off[wt >> 4] + rel) * 16;
  asm volatile("{ .reg .pred q; setp.ne.u32 q, %2, 0; @q cp.async.cg.shared.global [%0], [%1], 16; }"
               :: "r"(dst + wt * 16), "l"(b), "r"((uint32_t)(on && wt < 97)) : "memory");
}

struct ConvC { uint32_t ca, cb, bands, qa; };
__device__ __forceinline__ ConvC conv_consts(int w, int lane) {
  const int h = w & 1, P = (w >> 1) & 1, d0 = 8 * h + (lane >> 2) - 2 * (lane & 3);
  ConvC k;
  k.ca = keep((W_KT + (16 + 256 * P + d0) * 4) | (((8 + 64 * P + lane) * 64 + (((h + ((w >> 1) & 2)) ^ (lane >> 1)) & 3) * 16) << 16));
  const int u = d0 + 2 * (lane & 1) + 2, in = (u & 7) - ((u & 7) >= 5 ? 5 : 0) - 2 * (lane & 1);
  k.cb = keep(in > 0 ? 0x1010 : in == 0 ? 0x3210 : 0x3232);
  k.qa = keep(W_QT + (2 * (u >> 3) + ((u & 7) >= 5) + 64 * P) * 16);
  k.bands = keep(__byte_perm(band8(d0 + 8), band8(d0 + 7), 0x7733) & 0x00FF00FFu);
  return k;
}
struct ConvPre { uint32_t e0, e2, f2, b0, b2, a[3][4]; };
__device__ __forceinline__ void conv_pre(ConvPre& r, uint32_t kp, uint32_t qp, int part, bool on, bool P) {
  if (part & 1) {
    r.e0 = lds32_if(kp + 4096, on && !P); r.e2 = lds32_if(kp + 4064, on && !P); r.f2 = lds32_if(kp + 4128, on && !P);
    r.b0 = lds32_if(kp + 2048, on && !P); r.b2 = lds32_if(kp + 2016, on && !P);
  }
#pragma unroll
  for (int j = 0; j < 3; j++) if (part & (j < 1 ? 1 : 2))
    asm volatile("{ .reg .pred q; setp.ne.u32 q, %5, 0; mov.b32 %0, 0; mov.b32 %1, 0; mov.b32 %2, 0; mov.b32 %3, 0; @q ld.shared.v4.b32 {%0,%1,%2,%3}, [%4]; }"
                 : "=r"(r.a[j][0]), "=r"(r.a[j][1]), "=r"(r.a[j][2]), "=r"(r.a[j][3]) : "r"(qp + 64 * j), "r"((uint32_t)on) : "memory");
}
__device__ __forceinline__ void conv_item(uint32_t tb, uint32_t tl, int bid, int bn, ConvPre& pre, const ConvC& cv, uint32_t zero, const CUtensorMap* tmx, int ch, int warp, int lane, bool hold, bool more) {
  const bool go = more && warp == 0 && lane == 0;
  const uint32_t kp = tb + (cv.ca & 0xFFFFu), qp = tb + cv.qa;
  const uint32_t dlo = (tl >> 4) + 32 + ((warp >> 1) & 2) + (1u << 16), dhi = 32u | (2u << 30);
  const bool P = warp & 2;
  float a32[16], b32[16], a64[32];
  uint32_t A[40][4];
#define STEP(J) { wgmma64<0>(a64, A[J], dlo + 256 - 4 * (J), dhi); \
    if ((J) == 32) wgmma32_init<0>(b32, A[J], dlo, dhi); else wgmma32<0>(b32, A[J], ((J) < 8 ? dlo ^ zero : dlo) + 128 - 4 * (J), dhi); \
    if ((J) == 0) wgmma32_init<0>(a32, A[J], dlo, dhi); else if ((J) < 8) wgmma32<0>(a32, A[J], (dlo ^ zero) - 4 * (J), dhi); }
#define LD(J) load_a(A[J], kp, J);
#define LQ(J) { const uint4 v = lds128(qp + 64 * ((J) - 32)); A[J][0] = v.x; A[J][1] = v.y; A[J][2] = v.z; A[J][3] = v.w; }
#define PQ(J) { A[J][0] = prmt(A[J][0], 0, cv.cb); A[J][1] = prmt(A[J][1], 0, cv.cb); A[J][2] = prmt(A[J][2], 0, cv.cb); A[J][3] = prmt(A[J][3], 0, cv.cb); }
#define FIRST(J) wg_fence(); STEP(J) wg_commit(); wg_wait<1>(); wg_fence();
  {
    uint32_t win[16], x9[4], x7[4], e[4], f[4];
    const uint32_t bz = keep(cv.bands);
#define BAND(i) keep((bz & (0x10001u << (i))) * (0x3C00u >> (i)))
    e[0] = pre.e0; e[2] = pre.e2; e[1] = keep(bz & 0x100u); e[3] = keep(bz & 0x200u);
    f[2] = pre.f2; f[0] = keep(bz & 0x4000u); f[1] = keep(bz & 0x8000u); f[3] = keep(bz & 0x300u);
#pragma unroll
    for (int j = 0; j < 12; j++) A[32 + j / 4][j & 3] = pre.a[j / 4][j & 3];
    PQ(32) PQ(33) PQ(34)
    if (!P) { A[32][0] = pre.b0; A[32][2] = pre.b2; }
    const uint32_t q[12] = {BAND(0), BAND(5), keep(bz & 0x400u), BAND(4), BAND(2), BAND(7), BAND(1), BAND(6), keep(bz & 0x800u), keep(bz & 0x1000u), BAND(3), keep(bz & 0x2000u)};
#undef BAND
    const uint32_t ta = keep(tl + 512 + (warp & 3) * 2048 + lane * 64 + (lane & 6) * 8);
    if (X_GO && hold) mbar_wait(MB_GO);
    uint32_t mbl = MB_UL + (warp & 8) * 2, ph = 0;
#pragma unroll 1
    for (int it = 0; it < SPIN_MAX; it++) {
      if (ch < 512) mbar_wait(mbl, ph);
      if (it == 1) TS(13);
      TS(3);
      wg_fence();
      wgmma64h_init(win, q[0], q[1], q[2], q[3], dlo, dhi);
      wgmma64h(win, q[4], q[5], q[6], q[7], dlo - 4, dhi);
      wgmma64h(win, q[8], q[9], q[10], q[11], dlo - 8, dhi);
      wg_commit();
      wgmma64_init<0>(a64, e, dlo, dhi);
      wgmma64<0>(a64, f, dlo - 4, dhi);
      wg_commit();
      if (ch >= 512) break;
      uint32_t r0, r1, r2, r3, ok;
      if (warp & 4) {
        mbar_wait(mbl + 8);
        if (__all_sync(0xffffffffu, it || lds32(MISC_RT + (warp & 8)) == 0)) break;
        wg_wait<0>();
        continue;
      }
      ldsm4(ta, r0, r1, r2, r3);
      ok = r0 & r1 & r2 & r3;
      ldsm4(ta ^ 32, r0, r1, r2, r3);
      asm volatile("{ .reg .pred q; setp.ne.u32 q, %1, 0; barrier.red.and.pred q, %2, 128, q; selp.u32 %0, 1, 0, q; }" : "=r"(ok) : "r"((ok & r0 & r1 & r2 & r3 & 1u) | (lane & 3)), "r"(1 + (warp >> 2)) : "memory");
      if (ok) { if ((warp & 3) == 0 && lane == 0) { sts32(MISC_RT + warp, it); mbar_arrive(MB_UL + 8 + warp * 2); } break; }
      wg_wait<0>();
      if ((warp & 3) == 0 && lane == 0) load_tile(tmx - 1, warp >> 3, ch, 56);
      mbl = MB_UL + 56 + (warp & 8) * 2; ph = it & 1;
    }
    wg_wait<1>();
#pragma unroll
    for (int i = 0; i < 4; i++) {
      const int tl = 2 * ((i & 1) + ((i & 2) ? 0 : 4));
      x9[i] = P ? win[tl + 4] : win[tl]; x7[i] = P ? win[tl + 5] : win[tl + 1];
    }
    const uint32_t l3lo = ((tb + W_L3) >> 4) + (32u << 16);
    wg_fence();
    wgmma64<0>(a64, x9, l3lo, 8);
    wgmma64<0>(a64, x7, l3lo + 96, 8);
    wg_commit();
  }
  STEP(32) STEP(33) STEP(34) wg_commit(); wg_wait<1>();
  LQ(35) LQ(36) LQ(37) LQ(38) LQ(39) LD(0) PQ(35) PQ(36) PQ(37) PQ(38) PQ(39)
  FIRST(35) STEP(36) STEP(37) STEP(38) wg_commit(); STEP(39) wg_commit();
  LD(1) LD(2) LD(3)
  if (X_GO == 1 && go) mbar_arrive(MB_GO);
  wg_wait<1>(); wg_fence(); STEP(0) wg_commit(); STEP(1) wg_commit(); STEP(2) wg_commit(); wg_wait<2>();
  LD(4) LD(5)
  wg_fence(); STEP(3) wg_commit(); wg_wait<1>();
  LD(6) LD(7)
  wg_fence(); STEP(4) STEP(5) wg_commit();
  wg_fence(); STEP(6) STEP(7) wg_commit();
#undef STEP
#undef LD
#undef LQ
#undef PQ
#undef FIRST
  TS(18);
  if (X_GO == 3 && go) mbar_arrive(MB_GO);
  const uint32_t xc = tb + W_KT + (warp & 3) * 1024 + lane * 16;
  if (more) bar_sync(7, 288);
  wg_wait<1>();
  conv_pre(pre, kp + ALT, qp + ALT, 1, more, P);
  wg_wait<0>();
  conv_pre(pre, kp + ALT, qp + ALT, 2, more, P);
  uint32_t E[16], o[8];
#define ACC(i) ((i) < 16 ? a32[i] : (i) < 32 ? b32[(i) - 16] : a64[(i) - 32])
  E[0] = pack_h(a32[0], a32[1]);
#pragma unroll
  for (int i = 1; i < 16; i++) E[i] = pack_h(ACC(4 * i) + ACC(4 * i - 2), ACC(4 * i + 1) + ACC(4 * i - 1));
#undef ACC
#pragma unroll
  for (int j = 0; j < 8; j++) o[j] = P ? (j < 2 ? 0u : E[j - 2]) : E[8 + j];
  sts128(xc, o[0], o[1], o[2], o[3]); sts128(xc + 512, o[4], o[5], o[6], o[7]);
#pragma unroll
  for (int j = 0; j < 8; j++) o[j] = P ? E[6 + j] : E[j];
  TS(25);
  if (more) {
    sts128(xc + 4096, o[0], o[1], o[2], o[3]); sts128(xc + 4608, o[4], o[5], o[6], o[7]);
    bar_arrive(12, 192);
    return;
  }
  bar_sync(1 + (warp >> 2), 128);
  const uint4 vv[2] = {lds128(xc + (P ? -2048 : 2048)), lds128(xc + (P ? -1536 : 2560))};
  const uint32_t mk = lane < 8 ? 0xFFFEFFFEu : ~0u;
#pragma unroll
  for (int q = 0; q < 2; q++) {
    const uint4 v = vv[q];
    stsm4t(tl + (cv.ca >> 16) + q * 2048, hadd2u(o[4 * q], v.x) & mk, hadd2u(o[4 * q + 1], v.y) & mk, hadd2u(o[4 * q + 2], v.z) & mk, hadd2u(o[4 * q + 3], v.w) & mk);
  }
  fence_async();
  bar_sync(bid, bn);
  if (warp == 0 && lane == 0) mbar_arrive(MB_REL);
  if ((warp & 7) == (ch < 512 ? 7 : 3) && lane == 0) {
    asm volatile("cp.async.bulk.tensor.3d.global.shared::cta.bulk_group [%0, {%3, %2, %3}], [%1];" :: "l"(tmx), "r"(tl + 512), "r"(ch), "r"(0) : "memory");
    asm volatile("cp.async.bulk.commit_group;" ::: "memory");
  }
}

template <bool FAR> __global__ void __launch_bounds__(NT, 1)
fused_kernel(const __grid_constant__ Params p, const __grid_constant__ TMaps tm) {
  extern __shared__ __align__(1024) unsigned char smem[];
  const int c = blockIdx.x;
  const bool five = (c & 1) == 0;
  const uint32_t pitch = five ? 64 : 80;
  const uint32_t ones = 0x3F803F80u;
  const int tid = threadIdx.x, lane = tid & 31;
  const uint32_t xrow = OFF_YT + ((tid & 127) >> 3) * YT_PITCH + (tid & 64) + (tid & 7) * 16;
  {
    const int w4 = tid >> 7;
    load_params<FAR>(p, w4 < 2 ? 2 * c + w4 : five ? 257 + 2 * c : 512 + (c >> 1), tid & 127, OFF_W + W_KT + (w4 < 2 ? w4 * W_BYTES : five ? 3 * W_BYTES : 3 * W_BYTES + 2048), (0xB >> w4) & 1);
  }
  if ((tid >> 7) == 2) {
    const unsigned char* xp = p.x + (uint32_t)((c * 16 - 32 + (tid >> 3)) * 1152 + (tid & 7) * 16);
    asm volatile("" : "+l"(xp));
    { const uint32_t tq = clock(); while ((int)(clock() - tq) < X_XD) {} }
#pragma unroll
    for (int k = 0; k < 9; k++) asm volatile("cp.async.cg.shared.global [%0], [%1], 16;" :: "r"(xrow + k * 128), "l"(xp + k * 128) : "memory");
  }
  const int warp = (int)uni(tid >> 5), wg = warp >> 2;
  TS(0);
  if (__builtin_expect(wg == 4, 0)) {
    asm volatile("setmaxnreg.dec.sync.aligned.u32 32;");
    const int role = warp;
    const int u0 = (c >> 1) * 9 + (five ? ((c & 2) ? 5 : 0) : ((c & 2) ? 0 : 4));
    const uint32_t t0 = clock() + c * 4;
    if (role == 16) {
      if (lane == 0) {
#pragma unroll
        for (int i = 0; i < 19; i++) if (i != 16) asm volatile("mbarrier.init.shared::cta.b64 [%0], %1;" :: "r"(OFF_MISC + i * 8), "r"((unsigned)(i - 2) < 4u ? 4 : 1) : "memory");
      }
      __syncwarp();
      if (lane < 2) asm volatile("mbarrier.arrive.expect_tx.shared::cta.b64 _, [%0], %1;" :: "r"(OFF_MISC + lane * 8), "r"(lane ? (five ? 36864 : 51200) : pitch * 1152) : "memory");
      fence_async();
      bar_arrive(5, 608);
      const CUtensorMap* tmb = &tm.m[five ? 3 : 0];
#pragma unroll 1
      for (int u = 0; u < 17; u++) {
        const uint32_t e = p.sched[five][u], kind = e & 3, s = (e >> 2) & 15, dst = e >> 14;
        if (kind == 3) continue;
        while ((int)(clock() - t0) < X_PF0 + (u < X_NE ? u * X_PFD : X_LAG + u * X_TD)) __nanosleep(20);
        if (e & 0x3FC0) mbar_wait(OFF_MISC + ((e >> 6) & 255));
        if (lane == 0) {
          if (kind == 2) asm volatile("cp.async.bulk.tensor.3d.shared::cluster.global.mbarrier::complete_tx::bytes [%0], [%1, {%3, %4, %5}], [%2];"
                                      :: "r"(dst), "l"(tmb + 2), "r"(MB_D), "r"(0), "r"(u0 * 8), "r"(s) : "memory");
          else tma_box(dst, tmb + kind, MB_GU, u0 * 8, s * 96);
        }
        if (u == 5) TS(2);
        if (u == 10) TS(3);
      }
      TS(4);
      TS_DUMP();
#define FINISH0 bar_sync(12, 192);        \
        _Pragma("unroll 1") for (int w = role & 2; w < (role & 2) + 2; w++) { \
          const uint32_t xa = OFF_W + W_KT + lane * 16, mk = lane < 8 ? 0xFFFEFFFEu : ~0u, ya = OFF_T + (8 + lane) * 64 + (((w & 1) ^ (lane >> 1)) & 3) * 16 + (w & 2) * 2048; \
          const uint4 a = lds128(xa + 4096 + w * 1024), b = lds128(xa + (w ^ 2) * 1024), d = lds128(xa + 4608 + w * 1024), e = lds128(xa + 512 + (w ^ 2) * 1024); \
          stsm4t(ya, hadd2u(a.x, b.x) & mk, hadd2u(a.y, b.y) & mk, hadd2u(a.z, b.z) & mk, hadd2u(a.w, b.w) & mk); \
          stsm4t(ya + 2048, hadd2u(d.x, e.x) & mk, hadd2u(d.y, e.y) & mk, hadd2u(d.z, e.z) & mk, hadd2u(d.w, e.w) & mk); \
        } \
        fence_async();
    } else if (role == 17) {
      if (smem_u32(smem) != SB) __trap();
      bar_sync(10, 576);
      if (lane == 0) {
        fence_async();
        while ((int)(clock() - t0) < X_NS - c * 4) {}
        asm volatile("cp.async.bulk.global.shared::cta.bulk_group [%0], [%1], 10240;" :: "l"(&p.s->X[c * DM * 2 + 512]), "r"(OFF_G) : "memory");
        asm volatile("cp.async.bulk.commit_group;" ::: "memory");
        asm volatile("cp.async.bulk.wait_group 0;" ::: "memory");
      }
      if (lane == 0) mbar_arrive(MB_GF);
      bar_arrive(11, 96);
      if (five) { FINISH0 bar_arrive(13, 192); }
    } else if (role == 18) {
      sts32(MISC_EPOCH, 0);
      sts32(MISC_T0, t0 - c * 4);
      bar_arrive(5, 608);
      uint4* q = lane < 2 ? &p.s->R[c * 2 + lane] : lane < 11 ? &p.s->HS[c * 9 + lane - 2] : lane == 11 ? &p.s->HS[1152 + (c & 7)] : (uint4*)&p.s->FLAG[c * 8];
      if (lane < (c < 8 ? 12 : 11)) str128(q, ~0u, ~0u, ~0u, ~0u);
      const uint32_t ep = __shfl_sync(0xffffffffu, ldr32(q), 31) + 1u;
      sts32(MISC_EPOCH, ep | 0x80000000u);
      TSX(21);
      if (lane == 31) str32(q, ep);
      bar_sync(11, 96);
      TSX(14);
      mbar_wait(MB_KF + (lane & 3) * 8);
      __syncwarp();
      { const uint2 e = lds64(MISC_EM); if (lane < 2) str128(&p.s->SC[c * 2 + lane], e.x, __byte_perm(e.y, ep, 0x6540), 0, 0); }
      TSX(17);
      while ((int)(clock() - t0) < X_SCT) __nanosleep(100);
      TSX(18);
      {
        uint2 v[4];
#pragma unroll 1
        for (int it = 0; it < SPIN_MAX; it++) {
          uint32_t bad = 0;
#pragma unroll
          for (int q = 0; q < 4; q++) v[q] = ldr64(&p.s->SC[lane * 2 + q * 64]);
#pragma unroll
          for (int q = 0; q < 4; q++) bad |= (v[q].y >> 8) ^ (ep & 0xFFFFFFu);
          if (!__any_sync(0xffffffffu, bad)) break;
        }
        TSX(25);
#pragma unroll
        for (int q = 0; q < 4; q++) {
          const uint32_t sa = (lane >> 4) * YT_PITCH + (lane & 15) * 2;
          sts16(sc_addr(2 * q) + sa, v[q].x); sts16(sc_addr(8 + 2 * q) + sa, v[q].x >> 16);
          if (lane & 1) asm volatile("st.shared.u8 [%0], %1;" :: "r"(sc_addr(16) + q * 16 + (lane >> 1)), "r"(v[q].y) : "memory");
        }
      }
      __syncwarp();
      if (lane == 0) mbar_arrive(MB_SC);
      TSX(27);
    } else {
      uint32_t w[9];
      const uint32_t dk = ldnc16(p.dskip + ((lane & 4) ? 512 + (c >> 1) : (lane & 2) * 128 + 2 * c + (lane & 1)));
      float s = 0.f;
#pragma unroll
      for (int i = 0; i < 9; i++) w[i] = ldnc32(p.w_r + lane + 32 * i);
      sts16(OFF_WR + 1152 + lane * 2, dk);
      bar_arrive(5, 608);
#pragma unroll
      for (int i = 0; i < 9; i++) { sts32(OFF_WR + lane * 4 + i * 128, w[i]); s += bf_lo(w[i]) + bf_hi(w[i]); }
      sts32(MISC_SW, __float_as_uint(warp_sum(s)));
      TSX(23);
      bar_sync(10, 576);
      if (lane == 0) {
        const uint32_t tp = clock();
        TSX(1);
        while ((int)(clock() - tp) < X_DELTA || (int)(clock() - t0) < X_ABS - c * 4) {}
        TSX(24);
        load_tile(&tm.m[6], 0, c);
        TSX(15);
        while ((int)(clock() - t0) < X_ABS + X_DSTEP - c * 4) {}
      }
      bar_sync(11, 96);
      if (lane == 0) {
        load_tile(&tm.m[6], 1, 128 + c);
      }
      if (five) {
        mbar_wait(MB_KF);
#pragma unroll 1
        for (int it = 0; it < SPIN_MAX; it++) {
          if (lane == 0) load_tile(&tm.m[8], 2, 512 + (c >> 1));
          mbar_wait(MB_UL + 32, it & 1);
          uint32_t m = 1;
#pragma unroll
          for (int q = 0; q < 4; q++) { uint32_t r0, r1, r2, r3; ldsm4(OFF_W + 512 + lane * 64 + (lane & 6) * 8 + q * 2048, r0, r1, r2, r3); m &= r0 & r1 & r2 & r3; }
          if (__all_sync(0xffffffffu, m || (lane & 3))) break;
        }
        bar_arrive(7, 288);
        FINISH0
        bar_arrive(13, 192);
      }
      bar_sync(0, 544);
      if (lane == 0) mbar_arrive(MB_H);
    }
    return;
  }
  const int wt = tid & 127, g = lane >> 2, t = lane & 3;
  const uint32_t wb = OFF_W + wg * W_BYTES;
  asm volatile("cp.async.commit_group;" ::: "memory");
  const ConvC cv = conv_consts(warp, lane);
  zero_pads(wb, wt);
  load_params<FAR>(p, 254 + 2 * c + wg, wt, wb + W_KT, wg == 2 || (wg == 3 && !five));
  asm volatile("cp.async.commit_group;" ::: "memory");
  asm volatile("setmaxnreg.inc.sync.aligned.u32 112;");
  {
    uint4 kw;
    uint4* kx = &p.s->KX[(c >> 1) * 128 + wt];
    bool two = wg == 3;
    uint32_t ep;
    int em = 0;
    uint32_t slot = wg + (two && !five);
    const uint32_t ra0 = wb + W_KT + (slot & 4) * 512 + wt * 2, ra6 = wb + W_KT + 1536 + (slot & 4) * 512 + (((slot & 4) ? c >> 1 : 2 * c + (wg & 1)) & 7) * 2;
        const int lz = lane;
        const uint32_t tr_addr = pin(tr_base(lz) + warp * 32), lca = pin(MISC_LN1 + (lz & 1) * 16);
        uint4* dst;
        { const unsigned long long a = (unsigned long long)&p.s->X[c * DM * 2 + warp * 32 + (8 * ((lz >> 1) & 1) + (lz >> 2)) * 2 + (lz & 1)];
          dst = (uint4*)(((unsigned long long)pin(a >> 32) << 32) | pin((uint32_t)a)); }
    const BuildC bc = build_consts(wt);
    uint32_t raw[7];
    if (wg != 2) {
      asm volatile("cp.async.wait_group 1;" ::: "memory");
      bar_sync(1 + wg, 128);
#pragma unroll
      for (int i = 0; i < 7; i++) raw[i] = lds16(i < 6 ? ra0 + i * 256 : ra6);
    }
    int phase = wg == 2 ? 3 : 2;
#pragma unroll 1
    for (;;) {
      if (phase != 3) {
        KgState ks;
        TS(22);
        kgen_tables_n(raw, wb, wt, ks);
        TS(20);
        bar_sync(1 + wg, 128);
        em = kgen_tables_m(wb, wt, ks);
        fence_async();
      }
      if (phase & 2) {
        if (phase == 3) {
        asm volatile("cp.async.wait_group 1;" ::: "memory");
        TS(21);
        float d[3][4], r;
        uint4 a[9];
#pragma unroll
        for (int k = 0; k < 9; k++) a[k] = lds128(xrow + k * 128);
#pragma unroll
        for (int i = 0; i < 4; i++) d[0][i] = d[1][i] = d[2][i] = 0.f;
#pragma unroll
        for (int k = 0; k < 9; k++) { mma_bf16(d[(2 * k) % 3], a[k].x, ones, a[k].y, ones, a[k].x, a[k].y); mma_bf16(d[(2 * k + 1) % 3], a[k].z, ones, a[k].w, ones, a[k].z, a[k].w); }
#pragma unroll
        for (int i = 0; i < 4; i++) d[0][i] += d[1][i] + d[2][i];
        const LnC lc = ln_consts(d[0][2] + d[0][3], __shfl_sync(0xffffffffu, d[0][0], 9 * t) + __shfl_sync(0xffffffffu, d[0][1], 9 * t + 4), r);
        if (lane < 12) sts16(MISC_LN1 + g * 32 + (warp & 3) * 8 + t * 2, lane < 4 ? lc.m2 : lane < 8 ? lc.rh2 : lc.rl2);
        }
        asm volatile("cp.async.wait_group 0;" ::: "memory");
        TS(23);
        bar_sync(5, 608);
        uint32_t x[3][4];
        ldsm4t(tr_addr, x[0][0], x[0][1], x[0][2], x[0][3]);
        uint4 m = lds128(lca);
        const uint4 rl = lds128(lca + 64), rh = lds128(lca + 32);
        ldsm4t(tr_addr + 512, x[1][0], x[1][1], x[1][2], x[1][3]);
        if (wg == 3) ldsm4t(tr_addr + 640, x[2][0], x[2][1], x[2][2], x[2][3]);
#pragma unroll
        for (int q = 0; q < 3; q++) {
          if (q < 2 || wg == 3) {
            const uint32_t r0 = ln_apply(x[q][0], m.x, rh.x, rl.x), r1 = ln_apply(x[q][1], m.y, rh.y, rl.y), r2 = ln_apply(x[q][2], m.z, rh.z, rl.z), r3 = ln_apply(x[q][3], m.w, rh.w, rl.w);
            const uint32_t w0 = (pack_h(bf_lo(r0), bf_hi(r0)) & 0xFFFEFFFEu) | 1u, w1 = pack_h(bf_lo(r1), bf_hi(r1)), w2 = pack_h(bf_lo(r2), bf_hi(r2)), w3 = pack_h(bf_lo(r3), bf_hi(r3));
            if (q == 0) str128(dst, w0, w1, w2, w3);
            else sts128(OFF_G + warp * 512 + (8 * (t >> 1) + g) * 32 + (t & 1) * 16 + (q == 2 ? 2048 : 0), w0, w1, w2, w3);
          }
          if (q == 0) {
            const uint32_t z = clock() & p.off[7];
            m.x ^= z; m.y ^= z; m.z ^= z; m.w ^= z;
          }
          if (q == 0) TS(30);
          if (q == 0 && wg >= 2) {
#pragma unroll
            for (int i = 0; i < 7; i++) raw[i] = lds16(wb + W_KT + i * 256 + (i < 6 ? wt : (2 * c + (wg & 1)) & 7) * 2);
          }
        }
        bar_arrive(10, 576);
        TS(1);
      } else bar_sync(1 + wg, 128);
      phase &= 1;
      if (phase) { phase = 0; continue; }
      TS(14);
      float acc[20];
      const uint32_t alo = (wb >> 4) | (8u << 16);
      uint4 k4 = lds128(wb + W_MISC + 16);
      uint32_t dk = lds16(OFF_WR + 1152 + slot * 2);
      wg_fence();
      wgmma40_ss_init(acc, alo, alo + 1024, 2048 >> 4);
#pragma unroll
      for (int k = 1; k < 8; k++) wgmma40_ss(acc, alo + k * 16, alo + 1024 + k * 16, 2048 >> 4);
      wg_commit();
      { const uint32_t z = clock() & p.off[7]; dk ^= z; k4.x ^= z; k4.z ^= z; }
      const float k2048 = (float)(int)((k4.x + k4.y) + (k4.z + k4.w)) * (1.f / 262144.f);
      const int ef = max(em, min((int)((dk >> 7) & 255u) - 7, 238));
      asm volatile("st.shared.u8 [%0], %1;" :: "r"(MISC_EM + slot), "r"(ef + 9) : "memory");
      const float un = __uint_as_float((uint32_t)max(114 + em - ef, 0) << 23), d0 = wt ? 0.f : bf_lo(dk) * __uint_as_float((uint32_t)(245 - ef) << 23);
      wg_wait<0>();
      kw.x = pack_h(fmaf(acc[0] - acc[3], un, d0), (acc[4] - acc[7]) * un);
      kw.y = pack_h((acc[8] - acc[11]) * un, (acc[12] - acc[15]) * un);
      kw.z = pack_h((acc[16] - acc[19]) * un, k2048 * un);
      TS(24);
      ep = 0;
      if (two) SPIN_WHILE(ep == 0, ep = lds32(MISC_EPOCH));
      if (five || !two) break;
      str128(kx, kw.x, kw.y, kw.z, ep);
      two = false;
      slot = 3;
      bar_sync(1 + wg, 128);
    }
    if (lane == 0) mbar_arrive(MB_KF + wg * 8);
    if (two) { mbar_wait(MB_KF); zero_pads(OFF_W + ALT, wt); }
    uint32_t tb = wb;
#pragma unroll 1
    for (;;) {
      kgen_build(tb, bc, wg, wt, kw.x, kw.y, kw.z);
      TS(15);
      if (!two) break;
      two = false;
      kw.w = 0;
      SPIN_WHILE(kw.w != ep, kw = ldr128(kx));
      tb = OFF_W + ALT;
    }
    fence_async();
    TS(31);
    if (tb != wb) bar_arrive(7, 288);
    bar_sync(1 + wg, 128);
  }
  uint32_t tpub;
  ConvPre pre;
  conv_pre(pre, (wb ^ p.off[7]) + (cv.ca & 0xFFFFu), (wb ^ p.off[7]) + cv.qa, 3, true, warp & 2);
#pragma unroll 1
  for (int item = 0;; item++) {
    TS(2);
    conv_item(item ? OFF_W + ALT : wb, item ? OFF_W : OFF_T + (wg >> 1) * TILE, item ? 1 : 13 + (wg >> 1), item ? 128 : five && wg == 1 ? 192 : 256, pre, cv, p.off[7],
              &tm.m[item ? 9 : 7], item ? 512 + (c >> 1) : (wg >> 1) * 128 + c, warp, lane, five && wg >= X_GW, five && !wg && !item);
    tpub = clock() - (item ? X_YD : wg >= 2 ? X_YD2 : 0);
    if (wg || !five || item) break;
    TS(27);
  }
  TS(4);

  const int ln = lane ^ p.off[7], td = warp * 32 + ln, gg = ln >> 2, tt = ln & 3;
  const int tok = c * 16 + warp;
  const int fu = warp / 3, fk = warp - fu * 3;
  uint32_t wa[12][4];
  uint4 ha[3];
  const uint4* hsrc = &p.s->HS[td + (td / 24) * 48];
  {
    uint32_t hw[9], wr[9];
    const uint32_t row = keep(OFF_YT + warp * YT_PITCH + (warp >> 3) * 64 + ln * 16);
    const uint32_t wabase = keep(((ln & 8) ? OFF_W + (fk + 1) * W_BYTES : OFF_G + fk * 192 * pitch) + ((ln >> 4) * 8 + (ln & 7)) * pitch
                                 + (five ? ((fu ^ (ln >> 1)) & 3) : min(fu, 4)) * 16);
    float sw;
    {
      const bool three = wg == 1;
      const int ch = 8 * (tt >> 1) + gg;
      const uint32_t tr_addr = tr_base(ln);
      const uint4* ysrc = &p.s->X[c * DM * 2 + ch * 2 + (tt & 1)];
      uint32_t x[3][4], s[3];
      uint4 v[3];
#define TL(q) ((q) < 2 ? 2 * warp + (q) : 28 + warp)
      if (wg >= 2) { const uint32_t ts = lds32(MISC_T0); while ((int)(clock() - ts) < X_XS) {} }
      while ((int)(clock() - tpub) < X_YD) {}
      TS(5);
      v[0] = ldr128(ysrc + TL(0) * 32); v[1] = ldr128(ysrc + TL(1) * 32); v[2] = make_uint4(three, 0, 0, 0);
      mbar_wait(MB_REL);
#pragma unroll
      for (int i = 0; i < 6; i++) if (i < 4 || three) wr[i] = (gg & 2) ? ones : lds32(OFF_WR + TL(i >> 1) * 32 + (i & 1) * 16 + tt * 4);
      const uint32_t ha = keep(OFF_YT + (ln & 7) * YT_PITCH + (ln >> 4) * (8 * YT_PITCH + 64) + (ln & 8) * 2);
      const uint32_t pa = keep(OFF_PART + warp * 4 + ((gg & 2) * 8 + (gg & 4) * 2 + 2 * tt + (gg & 1)) * 80), pb = keep(OFF_PART + 2560 + warp * 4 + gg * 80);
      float dl[4] = {0.f, 0.f, 0.f, 0.f}, dh[4] = {0.f, 0.f, 0.f, 0.f};
      sw = __uint_as_float(lds32(MISC_SW));
#pragma unroll
      for (int q = 0; q < 3; q++) {
        if (q < 2 || three) {
          ldsm4t(tr_addr + TL(q) * 32, x[q][0], x[q][1], x[q][2], x[q][3]);
        }
      }
      asm volatile("cp.async.bulk.wait_group.read 0;" ::: "memory");
      mbar_wait(MB_SC);
#pragma unroll
      for (int q = 0; q < 3; q++) {
        asm volatile("ld.shared.u8 %0, [%1];" : "=r"(s[q]) : "r"((q < 2 ? sc_addr(warp) + q * 16 : sc_addr(16) + (warp & 3) * 16) + ch) : "memory");
        s[q] = keep(s[q] * 0x800080u);
      }
#define FIN(q) stsm4t(tr_addr + TL(q) * 32, bf_fma2(h2bf(v[q].x), s[q], x[q][0]), bf_fma2(h2bf(v[q].y), s[q], x[q][1]), bf_fma2(h2bf(v[q].z), s[q], x[q][2]), bf_fma2(h2bf(v[q].w), s[q], x[q][3]));
      SPIN_WHILE((v[0].x | v[1].x) & 1u, _Pragma("unroll") for (int q = 0; q < 3; q++) if (v[q].x & 1u) v[q] = ldr128(ysrc + TL(q) * 32));
      if (v[2].x & 1u) v[2] = ldr128(ysrc + TL(2) * 32);
#define STAT(q) { uint32_t r0, r1, r2, r3; ldsm4(ha + TL(q) * 32, r0, r1, r2, r3); \
        mma_bf16(dl, r0, wr[2 * q], r1, wr[2 * q + 1], r0, r1); mma_bf16(dh, r2, wr[2 * q], r3, wr[2 * q + 1], r2, r3); }
      FIN(0) FIN(1)
      __syncwarp();
      STAT(0) STAT(1)
      if (three) {
#pragma unroll 1
        for (int it = 0; it < SPIN_MAX; it++) {
          FIN(2)
          if (!__any_sync(0xffffffffu, v[2].x & 1u)) break;
          if (v[2].x & 1u) v[2] = ldr128(ysrc + TL(2) * 32);
        }
        __syncwarp();
        STAT(2)
      }
      if (gg & 1) { dl[0] = dl[1]; dl[2] = dl[3]; dh[0] = dh[1]; dh[2] = dh[3]; }
      sts32(pa, __float_as_uint((gg & 4) ? dh[2] : dl[2]));
      if (tt == (gg >> 1)) { sts32(pb, __float_as_uint(dl[0])); sts32(pb + 640, __float_as_uint(dh[0])); }
#undef STAT
#undef FIN
#undef TL
    }
    uint32_t ra = keep(OFF_PART + (ln & 15) * 80 + (ln & 16) * 2);
    uint16_t* rp = (uint16_t*)p.s->R + c * 16 + (ln & 15);
    const uint2* rsrc = (const uint2*)p.s->R + td;
    asm volatile("" : "+l"(rp), "+l"(rsrc), "+l"(hsrc));
    uint2 rv = make_uint2(0u, 0u);
    TS(28);
    if (warp != X_PW) bar_sync(0, 544);
    else {
      float z[3], rd;
      asm volatile("bar.sync 0, 544;" : "+r"(ra) :: "memory");
#pragma unroll
      for (int k = 2; k >= 0; k--) {
        const uint4 a = lds128(ra + k * 1280), b = lds128(ra + k * 1280 + 16);
        z[k] = ((__uint_as_float(a.x) + __uint_as_float(a.y)) + (__uint_as_float(a.z) + __uint_as_float(a.w))) + ((__uint_as_float(b.x) + __uint_as_float(b.y)) + (__uint_as_float(b.z) + __uint_as_float(b.w)));
      }
#pragma unroll
      for (int k = 2; k >= 0; k--) z[k] += __shfl_xor_sync(0xffffffffu, z[k], 16);
      const LnC l = ln_consts(z[1], z[2], rd);
      const uint32_t b = pack_bf(0.f, fmaf(-bf_lo(l.m2), sw, z[0]) * rd);
      const uint32_t k16 = max(min((b ^ (((int)b >> 31) | 0x80000000u)) >> 16, 0xFFFEu), 1u);
      if (ln < 16) str16(rp, k16);
      sts64(OFF_RK + (ln & 15) * 8, __byte_perm(l.m2, l.rh2, 0x5410), __byte_perm(l.rl2, k16, 0x5410));
      sts128(MISC_CNT + ln * 16, 0, 0, 0, 0);
    }
    mbar_wait(MB_GU);
#define LD_HW { const uint4 a = lds128(row), b = lds128(row + 512); hw[8] = lds32(row + 1024 - ln * 12); \
      hw[0] = a.x; hw[1] = a.y; hw[2] = a.z; hw[3] = a.w; hw[4] = b.x; hw[5] = b.y; hw[6] = b.z; hw[7] = b.w; }
    LD_HW
    const uint32_t tr0 = clock();
    bar_sync(5, 512);
    TS(7);
    const uint2 lk = lds64(OFF_RK + warp * 8);
    LnC l2;
    l2.m2 = __byte_perm(lk.x, 0, 0x1010); l2.rh2 = __byte_perm(lk.x, 0, 0x3232); l2.rl2 = __byte_perm(lk.y, 0, 0x1010);
    const uint32_t key = (lk.y & 0xFFFF0000u) | (2047 - tok);
    uint32_t loc = ln < 16 ? (lds32(OFF_RK + 4 + ln * 8) & 0xFFFF0000u) | (2047 - c * 16 - ln) : 0u;
    int rank = __popc(__ballot_sync(0xffffffffu, loc > key));
#pragma unroll
    for (int i = 0; i < 9; i++) { wr[i] = keep(ln_apply(hw[i], l2.m2, l2.rh2, l2.rl2)); hw[i] = bf_add2(hw[i], wr[i]); }
#define OUT_ROW { uint32_t* o = p.out + tok * 288 + ln * 4; \
      *(uint4*)o = make_uint4(hw[0], hw[1], hw[2], hw[3]); *(uint4*)(o + 128) = make_uint4(hw[4], hw[5], hw[6], hw[7]); o[256 - ln * 3] = hw[8]; }
    uint4* hs = p.s->HS + ln;
    asm volatile("" : "+l"(hs));
#pragma unroll 1
    for (int base = 0; base < 8; base += 2) {
      uint32_t T[2];
#pragma unroll
      for (int j = 0; j < 2; j++) {
        const uint32_t mx = __reduce_max_sync(0xffffffffu, loc);
        if (loc == mx) loc = 0;
        T[j] = (td >> 2) < c ? (mx & 0xFFFF0000u) - 1u : mx | 0xFFFFu;
      }
      const uint32_t sh = keep(rank == base ? 0x4410u : rank == base + 1 ? 0x4432u : 0x4445u), ca = keep(MISC_CNT + base * 64 + ln * 4);
      TS(29);
      if (base == 0) {
        while ((int)(clock() - tr0) < X_RD) {}
        if ((td >> 2) != c) rv = ldr64(rsrc);
        if (rank >= X_OR) OUT_ROW
        if (warp < (five ? 12 : 15)) {
#pragma unroll
          for (int k = 0; k < X_WS; k++) ldsm4t(wabase + k * 16 * pitch, wa[k][0], wa[k][1], wa[k][2], wa[k][3]);
        }
      }
      uint32_t cnt;
#pragma unroll 1
      for (int it = 0; it < SPIN_MAX; it++) {
        const uint32_t xs = rv.x << 16, ys = rv.y << 16;
        const bool bad = max(max(rv.x, xs), max(rv.y, ys)) >= 0xFFFF0000u;
        uint32_t cn2 = 0;
        cnt = bad ? 256u : 0u;
#pragma unroll
        for (int j = 0; j < 2; j++)
          asm("{ .reg .pred a, b, c, d; setp.gt.u32 a, %2, %6; setp.gt.u32 b, %3, %6; setp.gt.u32 c, %4, %6; setp.gt.u32 d, %5, %6; "
              "@a add.u32 %1, %1, %7; @b add.u32 %1, %1, %7; @c add.u32 %0, %0, %7; @d add.u32 %0, %0, %7; }"
              : "+r"(cnt), "+r"(cn2) : "r"(rv.x), "r"(rv.y), "r"(xs), "r"(ys), "r"(T[j]), "r"(1u << (16 * j)));
        cnt = __reduce_add_sync(0xffffffffu, cnt + cn2);
        asm volatile("{ .reg .pred q; setp.eq.u32 q, %2, 0; @q red.shared.add.u32 [%0], %1; }" :: "r"(ca), "r"(cnt), "r"(cnt & 0x3F00u) : "memory");
        if (!(cnt & 0x3F00u)) break;
        if (bad) rv = ldr64(rsrc);
      }
      TS(16);
      bar_sync(0, 512);
      cnt = lds32(ca);
      if (base == 0) tpub = clock();
      const int gr = rank + __byte_perm(cnt, 0x800u, sh);
      if (gr < 8) {
        uint4* ks = hs + 1152 + gr;
        hs = (uint4*)((char*)hs + gr * 1152);
        asm volatile("{ .reg .b128 t, u; .reg .b64 a, b, c, d; mov.b64 a, {%1,%2}; mov.b64 b, {%3,%4}; mov.b64 c, {%5,%6}; mov.b64 d, {%7,%8}; mov.b128 t, {a, b}; mov.b128 u, {c, d}; "
                     "st.relaxed.gpu.global.b128 [%0], t; st.relaxed.gpu.global.b128 [%0 + 512], u; }"
                     :: "l"(hs), "r"(wr[0]), "r"(wr[1]), "r"(wr[2]), "r"(wr[3]), "r"(wr[4]), "r"(wr[5]), "r"(wr[6]), "r"(wr[7]) : "memory");
        str32((uint32_t*)(hs + 64) - ln * 3, wr[8]);
        LD_HW
        str128(hs + 576, hw[0], hw[1], hw[2], hw[3]); str128(hs + 608, hw[4], hw[5], hw[6], hw[7]); str32((uint32_t*)(hs + 640) - ln * 3, hw[8]);
        if (ln == 0) str32(ks, key);
        rank = 16;
      }
      if (__all_sync(0xffffffffu, (int)(cnt >> 16) + base + 2 >= 8)) break;
    }
    TS(8);
    if (warp < (five ? 12 : 15)) {
#pragma unroll
      for (int k = X_WS; k < 12; k++) ldsm4t(wabase + k * 16 * pitch, wa[k][0], wa[k][1], wa[k][2], wa[k][3]);
    }
    if (warp < 6) while ((int)(clock() - tpub) < X_HD) {}
    TS(19);
    if (warp < 6) { ha[0] = ldr128(hsrc); ha[1] = ldr128(hsrc + 24); ha[2] = ldr128(hsrc + 48); }
    if (rank < X_OR) OUT_ROW
  }
  uint32_t wd[10][4];
  const uint32_t xb = keep(OFF_XS + (ln & 7) * 1168 + (fk * 24 + (ln >> 3)) * 16);
  if (warp >= 7) {
    const uint32_t db = down_box(warp - 7, five) + (ln & 7) * 128;
    mbar_wait(MB_D);
#pragma unroll
    for (int j = 0; j < 4; j++) {
      const uint32_t a = db + (ln >> 4) * 1024 + (((2 * j + ((ln >> 3) & 1)) ^ (ln & 7)) << 4);
      ldsm4t(a, wd[j][0], wd[j][1], wd[j][2], wd[j][3]);
      ldsm4t(a + 2048, wd[4 + j][0], wd[4 + j][1], wd[4 + j][2], wd[4 + j][3]);
    }
#pragma unroll
    for (int j = 0; j < 2; j++) ldsm4t(db + 4096 + (((4 * j + (ln >> 3)) ^ (ln & 7)) << 4), wd[8 + j][0], wd[8 + j][1], wd[8 + j][2], wd[8 + j][3]);
  } else if (warp < 6) {
    const uint32_t xs = keep(OFF_XS + (td + (td / 24) * 49) * 16);
#pragma unroll 1
    for (int it = 0; it < SPIN_MAX; it++) {
      const bool bad = max(max(max(ha[0].x, ha[1].x), max(ha[2].x, ha[2].y)), max(ha[2].z, ha[2].w)) == ~0u;
#pragma unroll
      for (int q = 0; q < 3; q++) sts128(xs + q * 384, ha[q].x, ha[q].y, ha[q].z, ha[q].w);
      if (!__any_sync(0xffffffffu, bad)) break;
      if (bad) { ha[0] = ldr128(hsrc); ha[1] = ldr128(hsrc + 24); ha[2] = ldr128(hsrc + 48); }
    }
  }
  TS(9);

  bar_sync(0, 512);
  if (warp < (five ? 12 : 15)) {
    float d0[4] = {0.f, 0.f, 0.f, 0.f}, d1[4] = {0.f, 0.f, 0.f, 0.f};
#pragma unroll
    for (int k = 0; k < 12; k += 2) {
      uint32_t b0, b1, b2, b3;
      ldsm4(xb + k * 32, b0, b1, b2, b3);
      mma_bf16(d0, wa[k][0], wa[k][1], wa[k][2], wa[k][3], b0, b1);
      mma_bf16(d1, wa[k + 1][0], wa[k + 1][1], wa[k + 1][2], wa[k + 1][3], b2, b3);
    }
    sts128(OFF_RED + td * 16, __float_as_uint(d0[0] + d1[0]), __float_as_uint(d0[1] + d1[1]), __float_as_uint(d0[2] + d1[2]), __float_as_uint(d0[3] + d1[3]));
  }
  TS(26);
  if (warp < 5) {
    const uint32_t rb = OFF_RED + warp * 1536 + ln * 16;
    bar_sync(9, 512);
    const uint4 pa = lds128(rb), pb = lds128(rb + 512), pc = lds128(rb + 1024);
    const float ga = bfr(__uint_as_float(pa.x) + __uint_as_float(pb.x) + __uint_as_float(pc.x));
    const float gb = bfr(__uint_as_float(pa.y) + __uint_as_float(pb.y) + __uint_as_float(pc.y));
    const uint32_t uu = pack_bf(__uint_as_float(pa.z) + __uint_as_float(pb.z) + __uint_as_float(pc.z), __uint_as_float(pa.w) + __uint_as_float(pb.w) + __uint_as_float(pc.w));
    float ra, rb2;
    asm("rcp.approx.ftz.f32 %0, %1;" : "=f"(ra) : "f"(1.f + ex2(ga * -1.4426950408889634f)));
    asm("rcp.approx.ftz.f32 %0, %1;" : "=f"(rb2) : "f"(1.f + ex2(gb * -1.4426950408889634f)));
    const uint32_t act = bf_mul2(pack_bf(ga * ra, gb * rb2), uu);
    sts32(OFF_ACT + td * 4, act);
  } else bar_arrive(9, 512);
  uint4* dst = &p.s->X[c * DM * 2 + (warp - 7) * 64 + tt * 8 + gg];
  asm volatile("" : "+l"(dst));
  bar_sync(8, 512);
  tpub = clock();
  if (warp >= 7) {
    uint32_t b0, b1, b2, b3, b4;
    ldsm4t(OFF_ACT + ln * 16, b0, b1, b2, b3);
    asm volatile("ldmatrix.sync.aligned.m8n8.x1.trans.shared.b16 {%0}, [%1];" : "=r"(b4) : "r"(OFF_ACT + 512 + ln * 16) : "memory");
    float y[4][4];
#pragma unroll
    for (int j = 0; j < 4; j++) {
      y[j][0] = y[j][1] = y[j][2] = y[j][3] = 0.f;
      mma_bf16(y[j], wd[j][0], wd[j][1], wd[j][2], wd[j][3], b0, b1);
    }
#pragma unroll
    for (int j = 0; j < 4; j++) mma_bf16(y[j], wd[4 + j][0], wd[4 + j][1], wd[4 + j][2], wd[4 + j][3], b2, b3);
    if (!five) {
#pragma unroll
      for (int j = 0; j < 4; j++) mma_bf16_k8(y[j], wd[8 + (j >> 1)][2 * (j & 1)], wd[8 + (j >> 1)][2 * (j & 1) + 1], b4);
    }
    str128(dst, (pack_bf(y[0][0], y[0][1]) & ~1u) | 0x10000u, pack_bf(y[0][2], y[0][3]), pack_bf(y[1][0], y[1][1]), pack_bf(y[1][2], y[1][3]));
    str128(dst + 32, (pack_bf(y[2][0], y[2][1]) & ~1u) | 0x10000u, pack_bf(y[2][2], y[2][3]), pack_bf(y[3][0], y[3][1]), pack_bf(y[3][2], y[3][3]));
  }
  TS(10);

  if (c < 72) {
    const uint4* src = &p.s->X[(warp * 4 + tt) * (DM * 2) + c * 8 + gg];
    const int slot = (c & 3) * 2 + (ln >> 4), dw = (c >> 2) * 16 + (ln & 15);
    uint32_t hv = 0, kv = 0, res = 0, rs2 = 0;
    uint32_t* o = p.out;
    if (warp == 0) {
      hv = ~0u;
      SPIN_WHILE(max(hv, kv) == ~0u, hv = ldr32((const uint32_t*)p.s->HS + 2304 + slot * 288 + dw); kv = ldr32(&p.s->HS[1152 + slot]));
      const float r = bf_hi(kv ^ (((int)~kv >> 31) | 0x80000000u));
      float rs;
      asm("rcp.approx.ftz.f32 %0, %1;" : "=f"(rs) : "f"(1.f + ex2(r * -1.4426950408889634f)));
      rs2 = keep(pack_bf(rs, rs));
      res = lds32(OFF_XS + slot * 1168 + dw * 4);
      o += (2047 - (int)(kv & 2047u)) * 288 + dw;
      asm volatile("" : "+l"(o));
    }
    const uint32_t sel = (gg & 1) ? 0x3F800000u : 0x00003F80u;
    const uint32_t q0 = keep((gg >> 1) == 0 ? sel : 0u), q1 = keep((gg >> 1) == 1 ? sel : 0u), q2 = keep((gg >> 1) == 2 ? sel : 0u), q3 = keep((gg >> 1) == 3 ? sel : 0u);
    const uint32_t fa = keep(OFF_RED + warp * 8 + ((gg & 1) * 16 + (gg >> 1) * 4 + tt) * 144), fb = keep(OFF_RED + ln * 144);
    uint4 a0 = make_uint4(0, 0, 0, 0), a1 = a0;
    while ((int)(clock() - tpub) < X_PD) {}
    SPIN_WHILE(!(a0.x & a1.x & 0x10000u), if (!(a0.x & 0x10000u)) a0 = ldr128(src); if (!(a1.x & 0x10000u)) a1 = ldr128(src + 64 * DM * 2));
    float d[4] = {0.f, 0.f, 0.f, 0.f}, e[4] = {0.f, 0.f, 0.f, 0.f}, d2[4] = {0.f, 0.f, 0.f, 0.f}, e2[4] = {0.f, 0.f, 0.f, 0.f};
    mma_bf16(d, q0, q2, q1, q3, a0.x, a0.y); mma_bf16(e, q0, q2, q1, q3, a0.z, a0.w);
    mma_bf16(d2, q0, q2, q1, q3, a1.x, a1.y); mma_bf16(e2, q0, q2, q1, q3, a1.z, a1.w);
    sts64(fa, __float_as_uint(d[0] + e[2] + d2[0] + e2[2]), __float_as_uint(d[1] + e[3] + d2[1] + e2[3]));
    TS(11);
    if (warp == 0) {
      bar_sync(0, 512);
      float2 s[16];
#pragma unroll
      for (int i = 0; i < 16; i += 2) { const uint4 q = lds128(fb + i * 8); s[i] = make_float2(__uint_as_float(q.x), __uint_as_float(q.y)); s[i + 1] = make_float2(__uint_as_float(q.z), __uint_as_float(q.w)); }
#pragma unroll
      for (int k = 1; k < 16; k *= 2)
#pragma unroll
        for (int i = 0; i < 16; i += 2 * k) { s[i].x += s[i + k].x; s[i].y += s[i + k].y; }
      asm volatile("st.global.b32 [%0], %1;" :: "l"(o), "r"(bf_add2(hv, bf_add2(res, bf_mul2(pack_bf(s[0].x, s[0].y), rs2)))) : "memory");
    } else bar_arrive(0, 512);
  }
  TS(12);
  TS_DUMP();
}

typedef CUresult (*EncodeFn)(CUtensorMap*, CUtensorMapDataType, cuuint32_t, void*, const cuuint64_t*, const cuuint64_t*, const cuuint32_t*,
                             const cuuint32_t*, CUtensorMapInterleave, CUtensorMapSwizzle, CUtensorMapL2promotion, CUtensorMapFloatOOBfill);

}

extern "C" void kernel_launch(void* const* d_in, const int* in_sizes, int n_in, void* d_out, int out_size) {
  (void)in_sizes; (void)n_in; (void)out_size;
  static EncodeFn enc = nullptr;
  static Scratch* scratch = nullptr;
  if (!enc) {
    void* fn = nullptr;
    cudaDriverEntryPointQueryResult qr;
    cudaGetDriverEntryPoint("cuTensorMapEncodeTiled", &fn, cudaEnableDefault, &qr);
    enc = (EncodeFn)fn;
    cudaGetSymbolAddress((void**)&scratch, g_S);
    cudaFuncSetAttribute(fused_kernel<false>, cudaFuncAttributeMaxDynamicSharedMemorySize, SMEM_BYTES);
    cudaFuncSetAttribute(fused_kernel<true>, cudaFuncAttributeMaxDynamicSharedMemorySize, SMEM_BYTES);
  }
  TMaps tm;
  for (int i = 0; i < 6; i++) {
    const bool dn = i % 3 == 2;
    const cuuint32_t w = i < 3 ? 40 : 32;
    cuuint64_t gd[3] = {(cuuint64_t)(dn ? 64 : FF), (cuuint64_t)(dn ? FF : DM), 9};
    cuuint64_t gs[2] = {(cuuint64_t)(dn ? DM * 2 : FF * 2), 128};
    cuuint32_t bx[3] = {dn ? 64 : w, dn ? w : 96, i < 3 ? 2u : 3u};
    cuuint32_t es[3] = {1, 1, 1};
    enc(&tm.m[i], CU_TENSOR_MAP_DATA_TYPE_BFLOAT16, dn ? 3 : 2, d_in[11 + i % 3], gd, gs, bx, es, CU_TENSOR_MAP_INTERLEAVE_NONE,
        dn ? CU_TENSOR_MAP_SWIZZLE_128B : i < 3 ? CU_TENSOR_MAP_SWIZZLE_NONE : CU_TENSOR_MAP_SWIZZLE_64B,
        (CUtensorMapL2promotion)X_PROMO, CU_TENSOR_MAP_FLOAT_OOB_FILL_NONE);
  }
  for (int i = 6; i < 10; i++) {
    cuuint64_t gd[3] = {i < 8 ? 32u : 16u, i < 8 ? DM / 2u : DM, NCTA};
    cuuint64_t gs[2] = {i < 8 ? 64u : 32u, DM * 32};
    cuuint32_t bx[3] = {32, 1, (i & 1) ? 128u : 136u};
    cuuint32_t es[3] = {1, 1, 1};
    enc(&tm.m[i], CU_TENSOR_MAP_DATA_TYPE_FLOAT16, 3, scratch->X, gd, gs, bx, es, CU_TENSOR_MAP_INTERLEAVE_NONE, CU_TENSOR_MAP_SWIZZLE_64B,
        CU_TENSOR_MAP_L2_PROMOTION_NONE, CU_TENSOR_MAP_FLOAT_OOB_FILL_NONE);
  }
  Params p;
  p.x = (const unsigned char*)d_in[0];
  bool far = false;
  for (int i = 0; i < 7; i++) {
    p.far[i] = (const unsigned char*)d_in[1 + i];
    const long long d = (long long)((intptr_t)d_in[1 + i] - (intptr_t)d_in[0]);
    p.off[i] = (int)(d / 16);
    if ((long long)p.off[i] * 16 != d || p.off[i] > (1 << 30)) far = true;
  }
  p.dskip = (const uint16_t*)d_in[8];
  p.w_r = (const uint32_t*)d_in[10];
  for (int f = 0; f < 2; f++) {
    static const int kind[17] = {0, 0, 0, 0, 2, 2, 0, 0, 1, 1, 1, 1, 1, 1, 2, 2, 2};
    static const int idx[2][17] = {{2, 3, 4, 5, 6, 8, 0, 1, 0, 1, 2, 3, 4, 5, 0, 2, 4}, {2, 3, 4, 5, 0, -1, 0, 1, 0, 1, 2, 3, 4, 5, 3, -1, 6}};
    static const int blk[2][17] = {{-1, -1, -1, -1, 0, -1, 4, -1, 1, -1, 2, -1, 3, -1, 16, -1, -1}, {-1, -1, -1, -1, 1, -1, 4, -1, -1, -1, 2, -1, 3, -1, 16, -1, -1}};
    const int pitch = f ? 64 : 80;
    for (int u = 0; u < 17; u++) {
      const int s = idx[f][u];
      const uint32_t dst = kind[u] == 0 ? OFF_G + s * 96 * pitch : kind[u] == 2 ? down_box(s, f) : OFF_W + W_BYTES + (s >> 1) * W_BYTES + (s & 1) * 96 * pitch;
      const uint32_t mb = u >= 14 ? (u >= X_HU ? MB_H - OFF_MISC : 0) : blk[f][u] >= 0 ? MB_KF - OFF_MISC + blk[f][u] * 8 : 0;
      p.sched[f][u] = s < 0 ? 3u : kind[u] | s << 2 | mb << 6 | dst << 14;
    }
  }
  p.out = (uint32_t*)d_out;
  p.off[7] = 0;
  p.ts = nullptr;
  p.s = scratch;
  if (far) { fused_kernel<true><<<NCTA, NT, SMEM_BYTES, cudaStreamPerThread>>>(p, tm); return; }
  fused_kernel<false><<<NCTA, NT, SMEM_BYTES, cudaStreamPerThread>>>(p, tm);
}
```

```cpp
#include <cuda_runtime.h>
#include <cuda.h>
#include <cuda_bf16.h>
#include <cuda_fp16.h>
#include <stdint.h>
#include <stddef.h>

namespace {

constexpr int NCTA = 128;
constexpr int NT = 640;
constexpr int DM = 576;
constexpr int FF = 4608;
constexpr int SPIN_MAX = 1 << 20;

struct Scratch {
  uint4 X[NCTA * DM * 2];
  uint4 KX[64 * 128];
  uint4 HS[1152 + 8];
  uint4 R[256];
  uint4 SC[256];
  uint32_t FLAG[NCTA * 8];
};
__device__ Scratch g_S;

#define CLKS(i)
#define TS(i)
#define TSX(i)
#define TS_DUMP()

constexpr int SB = 1024;
constexpr int BOX = 15360;
constexpr int OFF_G = SB;
constexpr int OFF_W = OFF_G + 3 * BOX;
constexpr int W_KT = 26624;
constexpr int W_QT = W_KT + 64 + 2048 + 80;
constexpr int W_L3 = W_KT + 4352;
constexpr int W_CW = W_L3 + 4160;
constexpr int W_MISC = W_CW + 640;
constexpr int W_BYTES = 35840;
constexpr int TILE = 10240;
constexpr int OFF_T = OFF_W + 4 * W_BYTES;
constexpr int ALT = TILE - W_KT;
static_assert(W_MISC + 32 <= W_BYTES && OFF_W % 1024 == 0 && W_BYTES % 1024 == 0 && W_BYTES + ALT <= 20480, "wg block");
constexpr int YT_PITCH = 1184;
constexpr int OFF_YT = OFF_T + 2 * TILE;
constexpr int OFF_WR = OFF_YT + 16 * YT_PITCH + 64;
constexpr int OFF_MISC = OFF_WR + 2304;
constexpr int SMEM_BYTES = OFF_MISC + 1024 - SB;
static_assert(OFF_YT % 16 == 0 && OFF_MISC % 16 == 0, "align");
static_assert(SMEM_BYTES <= 232448, "smem");
constexpr int MB_GU = OFF_MISC;
constexpr int MB_D = OFF_MISC + 8;
constexpr int MB_KF = OFF_MISC + 16;
constexpr int MB_GF = OFF_MISC + 48;
constexpr int MB_SC = OFF_MISC + 56;
constexpr int MB_UL = OFF_MISC + 64;
constexpr int MB_REL = OFF_MISC + 104;
constexpr int MB_GO = OFF_MISC + 112;
constexpr int MB_H = MB_KF + 128;
constexpr int MISC_EPOCH = OFF_MISC + 152;
constexpr int MISC_SW = OFF_MISC + 156;
constexpr int MISC_RT = OFF_MISC + 160;
constexpr int MISC_T0 = OFF_MISC + 296;
constexpr int MISC_EM = OFF_MISC + 288;
constexpr int OFF_PART = OFF_W + 20480;
constexpr int OFF_RK = OFF_PART + 3840;
constexpr int MISC_LN1 = OFF_MISC + 192;
constexpr int OFF_XS = OFF_T;
constexpr int OFF_RED = OFF_T + TILE;
constexpr int OFF_FIN = OFF_W + 3 * W_BYTES + W_KT;
constexpr int OFF_ACT = OFF_FIN + 4096;
constexpr int MISC_CNT = OFF_ACT + 1024;

__device__ __forceinline__ uint32_t smem_u32(const void* p) { return (uint32_t)__cvta_generic_to_shared(p); }
__device__ __forceinline__ uint32_t lds32(uint32_t a) { uint32_t v; asm volatile("ld.shared.b32 %0, [%1];" : "=r"(v) : "r"(a) : "memory"); return v; }
__device__ __forceinline__ uint32_t lds16(uint32_t a) { uint16_t v; asm volatile("ld.shared.u16 %0, [%1];" : "=h"(v) : "r"(a) : "memory"); return v; }
__device__ __forceinline__ uint2 lds64(uint32_t a) { uint2 v; asm volatile("ld.shared.v2.b32 {%0,%1}, [%2];" : "=r"(v.x), "=r"(v.y) : "r"(a) : "memory"); return v; }
__device__ __forceinline__ uint4 lds128(uint32_t a) { uint4 v; asm volatile("ld.shared.v4.b32 {%0,%1,%2,%3}, [%4];" : "=r"(v.x), "=r"(v.y), "=r"(v.z), "=r"(v.w) : "r"(a) : "memory"); return v; }
__device__ __forceinline__ void sts16(uint32_t a, uint32_t v) { asm volatile("st.shared.u16 [%0], %1;" :: "r"(a), "h"((uint16_t)v) : "memory"); }
__device__ __forceinline__ void sts32(uint32_t a, uint32_t v) { asm volatile("st.shared.b32 [%0], %1;" :: "r"(a), "r"(v) : "memory"); }
__device__ __forceinline__ void sts64(uint32_t a, uint32_t x, uint32_t y) { asm volatile("st.shared.v2.b32 [%0], {%1,%2};" :: "r"(a), "r"(x), "r"(y) : "memory"); }
__device__ __forceinline__ void sts128(uint32_t a, uint32_t x, uint32_t y, uint32_t z, uint32_t w) { asm volatile("st.shared.v4.b32 [%0], {%1,%2,%3,%4};" :: "r"(a), "r"(x), "r"(y), "r"(z), "r"(w) : "memory"); }
__device__ __forceinline__ void ldsm4(uint32_t a, uint32_t& r0, uint32_t& r1, uint32_t& r2, uint32_t& r3) {
  asm volatile("ldmatrix.sync.aligned.m8n8.x4.shared.b16 {%0,%1,%2,%3}, [%4];" : "=r"(r0), "=r"(r1), "=r"(r2), "=r"(r3) : "r"(a) : "memory");
}
__device__ __forceinline__ void ldsm4t(uint32_t a, uint32_t& r0, uint32_t& r1, uint32_t& r2, uint32_t& r3) {
  asm volatile("ldmatrix.sync.aligned.m8n8.x4.trans.shared.b16 {%0,%1,%2,%3}, [%4];" : "=r"(r0), "=r"(r1), "=r"(r2), "=r"(r3) : "r"(a) : "memory");
}
__device__ __forceinline__ void stsm4t(uint32_t a, uint32_t r0, uint32_t r1, uint32_t r2, uint32_t r3) {
  asm volatile("stmatrix.sync.aligned.m8n8.x4.trans.shared.b16 [%0], {%1,%2,%3,%4};" :: "r"(a), "r"(r0), "r"(r1), "r"(r2), "r"(r3) : "memory");
}
__device__ __forceinline__ uint4 ldr128(const void* p) {
  unsigned long long lo, hi;
  asm volatile("{ .reg .b128 t; ld.relaxed.gpu.global.b128 t, [%2]; mov.b128 {%0, %1}, t; }" : "=l"(lo), "=l"(hi) : "l"(p) : "memory");
  return make_uint4((uint32_t)lo, (uint32_t)(lo >> 32), (uint32_t)hi, (uint32_t)(hi >> 32));
}
__device__ __forceinline__ void str128(void* p, uint32_t x, uint32_t y, uint32_t z, uint32_t w) {
  asm volatile("{ .reg .b128 t; .reg .b64 lo, hi; mov.b64 lo, {%1,%2}; mov.b64 hi, {%3,%4}; mov.b128 t, {lo, hi}; st.relaxed.gpu.global.b128 [%0], t; }"
               :: "l"(p), "r"(x), "r"(y), "r"(z), "r"(w) : "memory");
}
__device__ __forceinline__ uint32_t ldr32(const void* p) { uint32_t v; asm volatile("ld.relaxed.gpu.global.b32 %0, [%1];" : "=r"(v) : "l"(p) : "memory"); return v; }
__device__ __forceinline__ void str32(void* p, uint32_t v) { asm volatile("st.relaxed.gpu.global.b32 [%0], %1;" :: "l"(p), "r"(v) : "memory"); }
__device__ __forceinline__ void str16(void* p, uint32_t v) { asm volatile("st.relaxed.gpu.global.u16 [%0], %1;" :: "l"(p), "h"((uint16_t)v) : "memory"); }
__device__ __forceinline__ void bar_sync(int id, int n) { asm volatile("bar.sync %0, %1;" :: "r"(id), "r"(n) : "memory"); }
__device__ __forceinline__ void bar_arrive(int id, int n) { asm volatile("bar.arrive %0, %1;" :: "r"(id), "r"(n) : "memory"); }

__device__ __forceinline__ float bf_lo(uint32_t w) { return __uint_as_float(w << 16); }
__device__ __forceinline__ float bf_hi(uint32_t w) { return __uint_as_float(w & 0xFFFF0000u); }
__device__ __forceinline__ uint32_t pack_bf(float lo, float hi) { uint32_t r; asm("cvt.rn.bf16x2.f32 %0, %1, %2;" : "=r"(r) : "f"(hi), "f"(lo)); return r; }
__device__ __forceinline__ uint32_t pack_h(float lo, float hi) { uint32_t r; asm("cvt.rn.f16x2.f32 %0, %1, %2;" : "=r"(r) : "f"(hi), "f"(lo)); return r; }
__device__ __forceinline__ float bfr(float x) { return bf_lo(pack_bf(x, 0.f)); }
__device__ __forceinline__ uint32_t bf_sub2(uint32_t a, uint32_t b) { __nv_bfloat162 r = __hsub2(*(__nv_bfloat162*)&a, *(__nv_bfloat162*)&b); return *(uint32_t*)&r; }
__device__ __forceinline__ uint32_t bf_add2(uint32_t a, uint32_t b) { __nv_bfloat162 r = __hadd2(*(__nv_bfloat162*)&a, *(__nv_bfloat162*)&b); return *(uint32_t*)&r; }
__device__ __forceinline__ uint32_t bf_mul2(uint32_t a, uint32_t b) { __nv_bfloat162 r = __hmul2(*(__nv_bfloat162*)&a, *(__nv_bfloat162*)&b); return *(uint32_t*)&r; }
__device__ __forceinline__ float2 h2f(uint32_t w) { return __half22float2(*(__half2*)&w); }
__device__ __forceinline__ float ex2(float x) { float r; asm("ex2.approx.ftz.f32 %0, %1;" : "=f"(r) : "f"(x)); return r; }
__device__ __forceinline__ float warp_sum(float v) {
#pragma unroll
  for (int o = 16; o > 0; o >>= 1) v += __shfl_xor_sync(0xffffffffu, v, o);
  return v;
}
__device__ __forceinline__ void mma_bf16(float* d, uint32_t a0, uint32_t a1, uint32_t a2, uint32_t a3, uint32_t b0, uint32_t b1) {
  asm volatile("mma.sync.aligned.m16n8k16.row.col.f32.bf16.bf16.f32 {%0,%1,%2,%3}, {%4,%5,%6,%7}, {%8,%9}, {%0,%1,%2,%3};"
               : "+f"(d[0]), "+f"(d[1]), "+f"(d[2]), "+f"(d[3]) : "r"(a0), "r"(a1), "r"(a2), "r"(a3), "r"(b0), "r"(b1));
}
__device__ __forceinline__ void mma_bf16_k8(float* d, uint32_t a0, uint32_t a1, uint32_t b0) {
  asm volatile("mma.sync.aligned.m16n8k8.row.col.f32.bf16.bf16.f32 {%0,%1,%2,%3}, {%4,%5}, {%6}, {%0,%1,%2,%3};"
               : "+f"(d[0]), "+f"(d[1]), "+f"(d[2]), "+f"(d[3]) : "r"(a0), "r"(a1), "r"(b0));
}

__device__ __forceinline__ void wg_fence() { asm volatile("wgmma.fence.sync.aligned;" ::: "memory"); }
__device__ __forceinline__ void wg_commit() { asm volatile("wgmma.commit_group.sync.aligned;" ::: "memory"); }
template <int N> __device__ __forceinline__ void wg_wait() { asm volatile("wgmma.wait_group.sync.aligned %0;" :: "n"(N) : "memory"); }
template <int TB> __device__ __forceinline__ void wgmma32(float* d, const uint32_t* a, uint32_t dlo, uint32_t dhi) {
  asm volatile("{ .reg .b64 dd; mov.b64 dd, {%20, %21}; wgmma.mma_async.sync.aligned.m64n32k16.f32.f16.f16 "
               "{%0,%1,%2,%3,%4,%5,%6,%7,%8,%9,%10,%11,%12,%13,%14,%15}, {%16,%17,%18,%19}, dd, 1, 1, 1, %22; }"
               : "+f"(d[0]), "+f"(d[1]), "+f"(d[2]), "+f"(d[3]), "+f"(d[4]), "+f"(d[5]), "+f"(d[6]), "+f"(d[7]), "+f"(d[8]), "+f"(d[9]), "+f"(d[10]), "+f"(d[11]), "+f"(d[12]), "+f"(d[13]), "+f"(d[14]), "+f"(d[15])
               : "r"(a[0]), "r"(a[1]), "r"(a[2]), "r"(a[3]), "r"(dlo), "r"(dhi), "n"(TB));
}
template <int TB> __device__ __forceinline__ void wgmma64(float* d, const uint32_t* a, uint32_t dlo, uint32_t dhi) {
  asm volatile("{ .reg .b64 dd; mov.b64 dd, {%36, %37}; wgmma.mma_async.sync.aligned.m64n64k16.f32.f16.f16 "
               "{%0,%1,%2,%3,%4,%5,%6,%7,%8,%9,%10,%11,%12,%13,%14,%15,%16,%17,%18,%19,%20,%21,%22,%23,%24,%25,%26,%27,%28,%29,%30,%31}, {%32,%33,%34,%35}, dd, 1, 1, 1, %38; }"
               : "+f"(d[0]), "+f"(d[1]), "+f"(d[2]), "+f"(d[3]), "+f"(d[4]), "+f"(d[5]), "+f"(d[6]), "+f"(d[7]), "+f"(d[8]), "+f"(d[9]), "+f"(d[10]), "+f"(d[11]), "+f"(d[12]), "+f"(d[13]), "+f"(d[14]), "+f"(d[15]), "+f"(d[16]), "+f"(d[17]), "+f"(d[18]), "+f"(d[19]), "+f"(d[20]), "+f"(d[21]), "+f"(d[22]), "+f"(d[23]), "+f"(d[24]), "+f"(d[25]), "+f"(d[26]), "+f"(d[27]), "+f"(d[28]), "+f"(d[29]), "+f"(d[30]), "+f"(d[31])
               : "r"(a[0]), "r"(a[1]), "r"(a[2]), "r"(a[3]), "r"(dlo), "r"(dhi), "n"(TB));
}
template <int TB> __device__ __forceinline__ void wgmma64_init(float* d, const uint32_t* a, uint32_t dlo, uint32_t dhi) {
  asm volatile("{ .reg .b64 dd; mov.b64 dd, {%36, %37}; wgmma.mma_async.sync.aligned.m64n64k16.f32.f16.f16 "
               "{%0,%1,%2,%3,%4,%5,%6,%7,%8,%9,%10,%11,%12,%13,%14,%15,%16,%17,%18,%19,%20,%21,%22,%23,%24,%25,%26,%27,%28,%29,%30,%31}, {%32,%33,%34,%35}, dd, 0, 1, 1, %38; }"
               : "=f"(d[0]), "=f"(d[1]), "=f"(d[2]), "=f"(d[3]), "=f"(d[4]), "=f"(d[5]), "=f"(d[6]), "=f"(d[7]), "=f"(d[8]), "=f"(d[9]), "=f"(d[10]), "=f"(d[11]), "=f"(d[12]), "=f"(d[13]), "=f"(d[14]), "=f"(d[15]), "=f"(d[16]), "=f"(d[17]), "=f"(d[18]), "=f"(d[19]), "=f"(d[20]), "=f"(d[21]), "=f"(d[22]), "=f"(d[23]), "=f"(d[24]), "=f"(d[25]), "=f"(d[26]), "=f"(d[27]), "=f"(d[28]), "=f"(d[29]), "=f"(d[30]), "=f"(d[31])
               : "r"(a[0]), "r"(a[1]), "r"(a[2]), "r"(a[3]), "r"(dlo), "r"(dhi), "n"(TB));
}
template <int TB> __device__ __forceinline__ void wgmma32_init(float* d, const uint32_t* a, uint32_t dlo, uint32_t dhi) {
  asm volatile("{ .reg .b64 dd; mov.b64 dd, {%20, %21}; wgmma.mma_async.sync.aligned.m64n32k16.f32.f16.f16 "
               "{%0,%1,%2,%3,%4,%5,%6,%7,%8,%9,%10,%11,%12,%13,%14,%15}, {%16,%17,%18,%19}, dd, 0, 1, 1, %22; }"
               : "=f"(d[0]), "=f"(d[1]), "=f"(d[2]), "=f"(d[3]), "=f"(d[4]), "=f"(d[5]), "=f"(d[6]), "=f"(d[7]), "=f"(d[8]), "=f"(d[9]), "=f"(d[10]), "=f"(d[11]), "=f"(d[12]), "=f"(d[13]), "=f"(d[14]), "=f"(d[15])
               : "r"(a[0]), "r"(a[1]), "r"(a[2]), "r"(a[3]), "r"(dlo), "r"(dhi), "n"(TB));
}
__device__ __forceinline__ void wgmma64h(uint32_t* d, uint32_t a0, uint32_t a1, uint32_t a2, uint32_t a3, uint32_t dlo, uint32_t dhi) {
  asm volatile("{ .reg .b64 dd; mov.b64 dd, {%20, %21}; wgmma.mma_async.sync.aligned.m64n64k16.f16.f16.f16 "
               "{%0,%1,%2,%3,%4,%5,%6,%7,%8,%9,%10,%11,%12,%13,%14,%15}, {%16,%17,%18,%19}, dd, 1, 1, 1, 0; }"
               : "+r"(d[0]), "+r"(d[1]), "+r"(d[2]), "+r"(d[3]), "+r"(d[4]), "+r"(d[5]), "+r"(d[6]), "+r"(d[7]), "+r"(d[8]), "+r"(d[9]), "+r"(d[10]), "+r"(d[11]), "+r"(d[12]), "+r"(d[13]), "+r"(d[14]), "+r"(d[15])
               : "r"(a0), "r"(a1), "r"(a2), "r"(a3), "r"(dlo), "r"(dhi));
}
__device__ __forceinline__ void wgmma64h_init(uint32_t* d, uint32_t a0, uint32_t a1, uint32_t a2, uint32_t a3, uint32_t dlo, uint32_t dhi) {
  asm volatile("{ .reg .b64 dd; mov.b64 dd, {%20, %21}; wgmma.mma_async.sync.aligned.m64n64k16.f16.f16.f16 "
               "{%0,%1,%2,%3,%4,%5,%6,%7,%8,%9,%10,%11,%12,%13,%14,%15}, {%16,%17,%18,%19}, dd, 0, 1, 1, 0; }"
               : "=r"(d[0]), "=r"(d[1]), "=r"(d[2]), "=r"(d[3]), "=r"(d[4]), "=r"(d[5]), "=r"(d[6]), "=r"(d[7]), "=r"(d[8]), "=r"(d[9]), "=r"(d[10]), "=r"(d[11]), "=r"(d[12]), "=r"(d[13]), "=r"(d[14]), "=r"(d[15])
               : "r"(a0), "r"(a1), "r"(a2), "r"(a3), "r"(dlo), "r"(dhi));
}
__device__ __forceinline__ void wgmma40_ss(float* d, uint32_t alo, uint32_t blo, uint32_t hi) {
  asm volatile("{ .reg .b64 da, db; mov.b64 da, {%20, %22}; mov.b64 db, {%21, %22}; "
               "wgmma.mma_async.sync.aligned.m64n40k16.f32.f16.f16 {%0,%1,%2,%3,%4,%5,%6,%7,%8,%9,%10,%11,%12,%13,%14,%15,%16,%17,%18,%19}, da, db, 1, 1, 1, 1, 1; }"
               : "+f"(d[0]), "+f"(d[1]), "+f"(d[2]), "+f"(d[3]), "+f"(d[4]), "+f"(d[5]), "+f"(d[6]), "+f"(d[7]), "+f"(d[8]), "+f"(d[9]), "+f"(d[10]), "+f"(d[11]), "+f"(d[12]), "+f"(d[13]), "+f"(d[14]), "+f"(d[15]), "+f"(d[16]), "+f"(d[17]), "+f"(d[18]), "+f"(d[19])
               : "r"(alo), "r"(blo), "r"(hi));
}
__device__ __forceinline__ void wgmma40_ss_init(float* d, uint32_t alo, uint32_t blo, uint32_t hi) {
  asm volatile("{ .reg .b64 da, db; mov.b64 da, {%20, %22}; mov.b64 db, {%21, %22}; "
               "wgmma.mma_async.sync.aligned.m64n40k16.f32.f16.f16 {%0,%1,%2,%3,%4,%5,%6,%7,%8,%9,%10,%11,%12,%13,%14,%15,%16,%17,%18,%19}, da, db, 0, 1, 1, 1, 1; }"
               : "=f"(d[0]), "=f"(d[1]), "=f"(d[2]), "=f"(d[3]), "=f"(d[4]), "=f"(d[5]), "=f"(d[6]), "=f"(d[7]), "=f"(d[8]), "=f"(d[9]), "=f"(d[10]), "=f"(d[11]), "=f"(d[12]), "=f"(d[13]), "=f"(d[14]), "=f"(d[15]), "=f"(d[16]), "=f"(d[17]), "=f"(d[18]), "=f"(d[19])
               : "r"(alo), "r"(blo), "r"(hi));
}
__device__ __forceinline__ void tma_box(uint32_t dst, const CUtensorMap* tm, uint32_t mb, int x, int y) {
  asm volatile("cp.async.bulk.tensor.2d.shared::cluster.global.mbarrier::complete_tx::bytes [%0], [%1, {%3, %4}], [%2];"
               :: "r"(dst), "l"(tm), "r"(mb), "r"(x), "r"(y) : "memory");
}
__device__ __forceinline__ uint32_t uni(uint32_t v) {
  uint32_t r; asm volatile("shfl.sync.idx.b32 %0, %1, 0, 0x1f, 0xffffffff;" : "=r"(r) : "r"(v)); return r;
}
__device__ __forceinline__ uint32_t pin(uint32_t v) {
  uint32_t r; asm volatile("shfl.sync.bfly.b32 %0, %1, 0, 0x1f, 0xffffffff;" : "=r"(r) : "r"(v)); return r;
}

struct Params {
  const unsigned char* x;
  Scratch* s;
  int off[8];
  uint32_t* out;
  const uint16_t* dskip;
  const uint32_t* w_r;
  long long* ts;
  const unsigned char* far[7];
  uint32_t sched[2][17];
};
__device__ __forceinline__ uint32_t ldnc32(const void* p) { uint32_t v; asm volatile("ld.global.nc.b32 %0, [%1];" : "=r"(v) : "l"(p)); return v; }
__device__ __forceinline__ uint32_t ldnc16(const void* p) { uint16_t v; asm volatile("ld.global.nc.u16 %0, [%1];" : "=h"(v) : "l"(p)); return v; }
__device__ __forceinline__ void mbar_wait(uint32_t mb, uint32_t ph = 0) {
#pragma unroll 1
  for (int it = 0; it < SPIN_MAX; it++) {
    uint32_t ok;
    asm volatile("{ .reg .pred q; mbarrier.try_wait.parity.shared::cta.b64 q, [%1], %2; selp.u32 %0, 1, 0, q; }" : "=r"(ok) : "r"(mb), "r"(ph) : "memory");
    if (ok) break;
  }
}
__device__ __forceinline__ void mbar_arrive(uint32_t mb) { asm volatile("mbarrier.arrive.shared::cta.b64 _, [%0];" :: "r"(mb) : "memory"); }
__device__ __forceinline__ void fence_async() { asm volatile("fence.proxy.async.shared::cta;" ::: "memory"); }
#define SPIN_WHILE(cond, body) _Pragma("unroll 1") for (int _it = 0; _it < SPIN_MAX && __any_sync(0xffffffffu, (cond)); _it++) { body; }

struct LnC { uint32_t m2, rh2, rl2; };
__device__ __forceinline__ LnC ln_consts(float s, float q, float& r) {
  const float mean = s * (1.f / DM);
  const float var = fmaxf(fmaf(-mean, mean, q * (1.f / DM)), 0.f);
  float sd;
  asm("sqrt.approx.ftz.f32 %0, %1;" : "=f"(sd) : "f"(bfr(bfr(var) + 1e-5f)));
  asm("rcp.approx.ftz.f32 %0, %1;" : "=f"(r) : "f"(bfr(sd)));
  LnC c;
  c.m2 = pack_bf(mean, mean);
  c.rh2 = pack_bf(r, r);
  const float rl = r - bf_lo(c.rh2);
  c.rl2 = pack_bf(rl, rl);
  return c;
}
__device__ __forceinline__ uint32_t bf_fma2(uint32_t a, uint32_t b, uint32_t c) {
  __nv_bfloat162 r = __hfma2(*(const __nv_bfloat162*)&a, *(const __nv_bfloat162*)&b, *(const __nv_bfloat162*)&c);
  return *(uint32_t*)&r;
}
__device__ __forceinline__ uint32_t ln_apply(uint32_t w, uint32_t m2, uint32_t rh2, uint32_t rl2) {
  const uint32_t d = bf_sub2(w, m2);
  return bf_fma2(d, rh2, bf_mul2(d, rl2));
}

__device__ __forceinline__ float2 cis(float mag_log2, float rev) {
  const float m = ex2(mag_log2), ang = rev * 6.283185307179586f;
  return make_float2(m * __cosf(ang), m * __sinf(ang));
}
__device__ __forceinline__ float2 csq(float2 a) { return make_float2(fmaf(a.x, a.x, -a.y * a.y), (a.x + a.x) * a.y); }
__device__ __forceinline__ float2 cmul(float2 a, float2 b) { return make_float2(fmaf(a.x, b.x, -a.y * b.y), fmaf(a.x, b.y, a.y * b.x)); }
__device__ __forceinline__ void pmul(uint32_t xr, uint32_t xi, uint32_t w, uint32_t& yr, uint32_t& yi) {
  const __half2 XR = *(__half2*)&xr, XI = *(__half2*)&xi, W = *(__half2*)&w;
  const __half2 a = __hfma2(__hneg2(XI), __high2half2(W), __hmul2(XR, __low2half2(W)));
  const __half2 b = __hfma2(XI, __low2half2(W), __hmul2(XR, __high2half2(W)));
  yr = *(const uint32_t*)&a; yi = *(const uint32_t*)&b;
}
__device__ __forceinline__ uint32_t pk(float2 a) { return pack_h(a.x, a.y); }

struct KgState { float2 c0, z8; float kl; uint32_t w64, w128, w192; };
__device__ __forceinline__ void kgen_tables_n(const uint32_t (&raw)[7], uint32_t scr, int wt, KgState& k) {
  const uint32_t dst = scr + 16384 + wt * 16;
  const float dt = bfr(ex2(bf_lo(raw[6]) * 1.4426950408889634f));
  const float th = dt * bf_lo(raw[1]);
  const float br = dt * bf_lo(raw[2]), bi = dt * bf_lo(raw[3]);
  const float Cr = bf_lo(raw[4]), Ci = bf_lo(raw[5]);
  k.c0 = make_float2(fmaf(Cr, br, -Ci * bi), fmaf(Cr, bi, Ci * br));
  const uint32_t mx = __reduce_max_sync(0xffffffffu, __float_as_uint(fmaxf(fabsf(k.c0.x), fabsf(k.c0.y))));
  const float a2 = dt * bf_lo(raw[0]) * 1.4426950408889634f;
  const float rh = th * 0.15915494309189535f;
  const float rl = fmaf(th, (float)(0.15915494309189535 - (double)0.15915494309189535f), fmaf(th, 0.15915494309189535f, -rh));
  const float rf = rh - rintf(rh);
  const float2 z1 = cis(a2, rf + rl);
  const float p64 = rf * 64.f;
  const float2 z64 = cis(a2 * 64.f, fmaf(64.f, rl, p64 - rintf(p64)));
  const float2 z2 = csq(z1), z128 = csq(z64), z3 = cmul(z2, z1), z4 = csq(z2), z256 = csq(z128), z6 = csq(z3), z512 = csq(z256);
  k.z8 = csq(z4);
  k.w64 = pk(z64); k.w128 = pk(z128); k.w192 = pk(cmul(z128, z64));
  sts128(dst, 0x00003C00u, pk(z2), pk(z4), pk(z6));
  const float2 z1024 = csq(z512), z768 = cmul(z512, z256);
  sts128(dst + 2048, pk(z1), pk(z3), pk(cmul(z4, z1)), pk(cmul(z4, z3)));
  const float2 z2048 = csq(z1024);
  k.kl = fmaf(k.c0.x, z2048.x, -k.c0.y * z2048.y);
  sts128(dst + 4096, pk(z256), pk(cmul(z256, z2)), pk(cmul(z256, z4)), pk(cmul(z256, z6)));
  sts128(dst + 6144, pk(z512), pk(cmul(z512, z4)), pk(z768), pk(cmul(z768, z4)));
  sts128(dst + 8192, pk(z1024), pk(cmul(z1024, z256)), pk(cmul(z1024, z512)), pk(cmul(z1024, z768)));
  sts32(scr + W_MISC + (wt >> 5) * 4, mx);
}
__device__ __forceinline__ int kgen_tables_m(uint32_t scr, int wt, const KgState& k) {
  const uint32_t dst = scr + wt * 16;
  const uint4 e4 = lds128(scr + W_MISC);
  const float2 z16 = csq(k.z8), z32 = csq(z16);
  const int em = max(min((int)(max(max(e4.x, e4.y), max(e4.z, e4.w)) >> 23), 238), 16);
  const float sc = __uint_as_float((uint32_t)(127 + 4 + 127 - em) << 23);
  sts32(scr + W_MISC + 16 + (wt >> 5) * 4, __reduce_add_sync(0xffffffffu, __float2int_rn(k.kl * sc * 262144.f)));
  const float2 c0 = make_float2(k.c0.x * sc, k.c0.y * sc);
  const float2 c1 = cmul(c0, k.z8), c2 = cmul(c0, z16), c4 = cmul(c0, z32), c3 = cmul(c1, z16), c5 = cmul(c1, z32), c6 = cmul(c2, z32), c7 = cmul(c3, z32);
  uint32_t pr[4], pi[4], yr[4], yi[4];
  pr[0] = pack_h(c0.x, c1.x); pi[0] = pack_h(c0.y, c1.y);
  pr[1] = pack_h(c2.x, c3.x); pi[1] = pack_h(c2.y, c3.y);
  pr[2] = pack_h(c4.x, c5.x); pi[2] = pack_h(c4.y, c5.y);
  pr[3] = pack_h(c6.x, c7.x); pi[3] = pack_h(c6.y, c7.y);
  sts128(dst, pr[0], pr[1], pr[2], pr[3]); sts128(dst + 2048, pi[0], pi[1], pi[2], pi[3]);
#pragma unroll
  for (int q = 1; q < 4; q++) {
    const uint32_t w = q == 1 ? k.w64 : q == 2 ? k.w128 : k.w192;
#pragma unroll
    for (int i = 0; i < 4; i++) pmul(pr[i], pi[i], w, yr[i], yi[i]);
    sts128(dst + q * 4096, yr[0], yr[1], yr[2], yr[3]); sts128(dst + q * 4096 + 2048, yi[0], yi[1], yi[2], yi[3]);
  }
  return em;
}
__device__ __forceinline__ uint32_t lds32_if(uint32_t a, bool on) {
  uint32_t v; asm volatile("{ .reg .pred q; setp.ne.u32 q, %2, 0; mov.b32 %0, 0; @q ld.shared.b32 %0, [%1]; }" : "=r"(v) : "r"(a), "r"((uint32_t)on) : "memory"); return v;
}
__device__ __forceinline__ uint32_t prmt(uint32_t a, uint32_t b, uint32_t s) { uint32_t r; asm("prmt.b32 %0, %1, %2, %3;" : "=r"(r) : "r"(a), "r"(b), "r"(s)); return r; }
struct BuildC { uint32_t a3, a2, az, cw, sel; };
__device__ __forceinline__ BuildC build_consts(int wt) {
  const int ix = ((wt >> 2) + (wt & 3) * 32 - 1) & 127;
  BuildC b;
  b.a3 = W_CW + 32 + ((ix & 1) ? 0 : 304) + (ix >> 1) * 4;
  b.a2 = W_L3 + 3072 + 544 + (wt & ~3) * 2 + (wt & 1) * 4 + (wt & 2) * 128;
  b.az = W_KT + (wt < 36 ? -512 : 64 + 4128 - 576) + wt * 16;
  b.cw = W_CW + 32 + (wt >> 6) * 48 + wt * 4;
  b.sel = (wt & 1) ? 0x10767610 : wt ? 0x10101010 : 0x10107610;
  return b;
}
__device__ __forceinline__ void kgen_build(uint32_t tb, const BuildC& bc, int wg, int wt, uint32_t k0, uint32_t k1, uint32_t k2) {
  const uint32_t kt = tb + W_KT, sc = tb + W_L3 + 3072;
  const uint32_t a3 = tb + bc.a3, a2 = tb + bc.a2;
  const uint32_t v3 = wt ? k2 : k2 >> 16;
  sts32(sc + 4 + wt * 4, __byte_perm(k0, k1, 0x5432));
  sts16(a2, k1 >> 16); sts16(a2 + 6, k1 >> 16);
  sts16(a3, v3); sts16(a3 + 6, v3);
  if ((unsigned)(wt - 32) < 14u) sts128(tb + bc.az, 0, 0, 0, 0);
  if (wt == 127) sts32(sc, k0 & 0xFFFF0000u);
  if (wt == 0) { sts32(sc + 516, k1); sts16(sc + 1056, k2); }
  bar_sync(1 + wg, 128);
  const uint32_t cw = tb + bc.cw, g2 = sc + 540 + wt * 4;
  const bool odd = wt & 1, ends = (unsigned)(wt - 4) >= 120u;
  const uint32_t pv = lds32(sc + wt * 4), nx = lds32(sc + 8 + wt * 4), nc = lds32_if(g2 + 8, ends);
  const uint32_t l0 = lds32(cw), l1 = lds32(cw - 8), l2 = lds32(cw - 16), l3 = lds32(cw - 24), q0 = lds32(g2), q1 = lds32(g2 + 128), q2 = lds32(g2 - 8), q3 = lds32(g2 + 120);
  sts64(kt + 64 + wt * 8, __byte_perm(k0, pv, 0x5410), __byte_perm(k0, 0, 0x1032));
  sts64(kt + 64 + 1024 + wt * 8, prmt(k1, pv, bc.sel), prmt(k1, nx, bc.sel >> 16));
  const uint32_t cc = __byte_perm(nc, 0, 0x3232), nn = __byte_perm(nc, 0, 0x1010);
  if (ends) sts128(kt + 64 + 2048 + wt * 16, cc, cc, odd ? nc : cc, odd ? nn : nc);
  if (wt == 127) { sts128(kt + 64 + 4096, nn, nn, nn, nn); sts128(kt + 64 + 4112, nn, nn << 16, 0, 0); }
  sts128(tb + W_L3 + 512 + (wt >> 6) * 512 + wt * 16, l0, l1, l2, l3);
  if ((wt & 63) < 34) sts128(tb + W_QT - 16 + wt * 16, q0, q1, q2, q3);
}

__device__ __forceinline__ void load_a(uint32_t (&a)[4], uint32_t kp, int j) {
  a[0] = lds32(kp + 64 * j); a[1] = lds32(kp + 64 * j + 512); a[2] = lds32(kp + 64 * j - 32); a[3] = lds32(kp + 64 * j + 480);
}
__device__ __forceinline__ uint32_t band8(int s) { return ((((0x1FFu << 20) >> s) & 0x01010101u) | (((0x7Fu << 25) >> s) & 0x10101010u)) * 0x01020408u; }
__device__ __forceinline__ uint32_t hadd2u(uint32_t a, uint32_t b) { __half2 r = __hadd2(*(__half2*)&a, *(__half2*)&b); return *(uint32_t*)&r; }

__device__ __forceinline__ void zero_pads(uint32_t tb, int wt) {
  if (!(wt & 32)) sts128(tb + W_L3 + (wt >> 6) * 512 + wt * 16, 0, 0, 0, 0);
  if ((wt & 63) < 3) sts128(tb + W_CW + (wt >> 6) * 304 + (wt & 63) * 16, 0, 0, 0, 0);
}
__device__ __forceinline__ uint32_t tr_base(int lane) {
  return OFF_YT + (2 * (lane >> 3) + (lane & 1)) * YT_PITCH + ((lane >> 1) & 1) * (8 * YT_PITCH + 64) + ((lane >> 2) & 1) * 16;
}

__device__ __forceinline__ uint32_t sc_addr(int tp) { return OFF_YT + (tp < 16 ? tp * YT_PITCH + (tp >> 3) * 64 + 1152 : 8 * YT_PITCH - 512 + tp * 32); }
#define X_PW 15
#define X_HU 16
#define X_NP 2
#define X_SK 100
#define X_NE 2
#define X_SCT 10000
#define X_DELTA 0
#define X_DSTEP 2000
#define X_PF0 2700
#define X_PFD 600
#define X_TD 450
#define X_WS 6
#define X_OR 8
#define X_ABS 4870
#define X_XD 200
#define X_RD 630
#define X_HD 450
#define X_PD 1170
#define X_PROMO 2
#define X_YD2 1000
#define X_GO 1
#define X_GW 2
#define X_NS 4300
#define X_XS 13450
#define X_LAG 1300
#define X_YD 1550
struct TMaps { CUtensorMap m[10]; };
__device__ __forceinline__ uint32_t h2bf(uint32_t w) { const float2 f = h2f(w); return pack_bf(f.x, f.y); }
__device__ __forceinline__ uint32_t keep(uint32_t v) { asm volatile("" : "+r"(v)); return v; }
__device__ __forceinline__ uint2 ldr64(const void* p) { uint2 v; asm volatile("{ .reg .b64 t; ld.relaxed.gpu.global.b64 t, [%2]; mov.b64 {%0, %1}, t; }" : "=r"(v.x), "=r"(v.y) : "l"(p) : "memory"); return v; }
__host__ __device__ __forceinline__ uint32_t down_box(int s, bool five) {
  return five ? OFF_W + W_BYTES + 12288 + (s / 3) * (W_BYTES - 12288) + s * 4096 : s < 6 ? OFF_W + W_BYTES + BOX + (s >> 1) * (W_BYTES - 10240) + s * 5120 : OFF_W + (s - 6) * 5120;
}
__device__ __forceinline__ void load_tile(const CUtensorMap* tmx, int i, int c, int again = 0) {
  asm volatile("mbarrier.arrive.expect_tx.shared::cta.b64 _, [%0], 8704;" :: "r"(MB_UL + i * 16 + again) : "memory");
  asm volatile("cp.async.bulk.tensor.3d.shared::cluster.global.mbarrier::complete_tx::bytes [%0], [%1, {%3, %4, %5}], [%2];"
               :: "r"(i < 2 ? OFF_T + i * TILE : OFF_W), "l"(tmx), "r"(MB_UL + i * 16 + again), "r"(0), "r"(c), "r"(-8) : "memory");
}
template <bool FAR> __device__ __forceinline__ void load_params(const Params& p, uint32_t ch, int wt, uint32_t dst, bool on) {
  const int rel = wt < 96 ? ch * 16 + (wt & 15) : ch >> 3;
  const unsigned char* b = FAR ? p.far[min(wt >> 4, 6)] + rel * 16 : p.x + (long long)(p.off[wt >> 4] + rel) * 16;
  asm volatile("{ .reg .pred q; setp.ne.u32 q, %2, 0; @q cp.async.cg.shared.global [%0], [%1], 16; }"
               :: "r"(dst + wt * 16), "l"(b), "r"((uint32_t)(on && wt < 97)) : "memory");
}

struct ConvC { uint32_t ca, cb, bands, qa; };
__device__ __forceinline__ ConvC conv_consts(int w, int lane) {
  const int h = w & 1, P = (w >> 1) & 1, d0 = 8 * h + (lane >> 2) - 2 * (lane & 3);
  ConvC k;
  k.ca = keep((W_KT + (16 + 256 * P + d0) * 4) | (((8 + 64 * P + lane) * 64 + (((h + ((w >> 1) & 2)) ^ (lane >> 1)) & 3) * 16) << 16));
  const int u = d0 + 2 * (lane & 1) + 2, in = (u & 7) - ((u & 7) >= 5 ? 5 : 0) - 2 * (lane & 1);
  k.cb = keep(in > 0 ? 0x1010 : in == 0 ? 0x3210 : 0x3232);
  k.qa = keep(W_QT + (2 * (u >> 3) + ((u & 7) >= 5) + 64 * P) * 16);
  k.bands = keep(__byte_perm(band8(d0 + 8), band8(d0 + 7), 0x7733) & 0x00FF00FFu);
  return k;
}
struct ConvPre { uint32_t e0, e2, f2, b0, b2, a[3][4]; };
__device__ __forceinline__ void conv_pre(ConvPre& r, uint32_t kp, uint32_t qp, int part, bool on, bool P) {
  if (part & 1) {
    r.e0 = lds32_if(kp + 4096, on && !P); r.e2 = lds32_if(kp + 4064, on && !P); r.f2 = lds32_if(kp + 4128, on && !P);
    r.b0 = lds32_if(kp + 2048, on && !P); r.b2 = lds32_if(kp + 2016, on && !P);
  }
#pragma unroll
  for (int j = 0; j < 3; j++) if (part & (j < 1 ? 1 : 2))
    asm volatile("{ .reg .pred q; setp.ne.u32 q, %5, 0; mov.b32 %0, 0; mov.b32 %1, 0; mov.b32 %2, 0; mov.b32 %3, 0; @q ld.shared.v4.b32 {%0,%1,%2,%3}, [%4]; }"
                 : "=r"(r.a[j][0]), "=r"(r.a[j][1]), "=r"(r.a[j][2]), "=r"(r.a[j][3]) : "r"(qp + 64 * j), "r"((uint32_t)on) : "memory");
}
__device__ __forceinline__ void conv_item(uint32_t tb, uint32_t tl, int bid, int bn, ConvPre& pre, const ConvC& cv, uint32_t zero, const CUtensorMap* tmx, int ch, int warp, int lane, bool hold, bool more) {
  const bool go = more && warp == 0 && lane == 0;
  const uint32_t kp = tb + (cv.ca & 0xFFFFu), qp = tb + cv.qa;
  const uint32_t dlo = (tl >> 4) + 32 + ((warp >> 1) & 2) + (1u << 16), dhi = 32u | (2u << 30);
  const bool P = warp & 2;
  float a32[16], b32[16], a64[32];
  uint32_t A[40][4];
#define STEP(J) { wgmma64<0>(a64, A[J], dlo + 256 - 4 * (J), dhi); \
    if ((J) == 32) wgmma32_init<0>(b32, A[J], dlo, dhi); else wgmma32<0>(b32, A[J], ((J) < 8 ? dlo ^ zero : dlo) + 128 - 4 * (J), dhi); \
    if ((J) == 0) wgmma32_init<0>(a32, A[J], dlo, dhi); else if ((J) < 8) wgmma32<0>(a32, A[J], (dlo ^ zero) - 4 * (J), dhi); }
#define LD(J) load_a(A[J], kp, J);
#define LQ(J) { const uint4 v = lds128(qp + 64 * ((J) - 32)); A[J][0] = v.x; A[J][1] = v.y; A[J][2] = v.z; A[J][3] = v.w; }
#define PQ(J) { A[J][0] = prmt(A[J][0], 0, cv.cb); A[J][1] = prmt(A[J][1], 0, cv.cb); A[J][2] = prmt(A[J][2], 0, cv.cb); A[J][3] = prmt(A[J][3], 0, cv.cb); }
#define FIRST(J) wg_fence(); STEP(J) wg_commit(); wg_wait<1>(); wg_fence();
  {
    uint32_t win[16], x9[4], x7[4], e[4], f[4];
    const uint32_t bz = keep(cv.bands);
#define BAND(i) keep((bz & (0x10001u << (i))) * (0x3C00u >> (i)))
    e[0] = pre.e0; e[2] = pre.e2; e[1] = keep(bz & 0x100u); e[3] = keep(bz & 0x200u);
    f[2] = pre.f2; f[0] = keep(bz & 0x4000u); f[1] = keep(bz & 0x8000u); f[3] = keep(bz & 0x300u);
#pragma unroll
    for (int j = 0; j < 12; j++) A[32 + j / 4][j & 3] = pre.a[j / 4][j & 3];
    PQ(32) PQ(33) PQ(34)
    if (!P) { A[32][0] = pre.b0; A[32][2] = pre.b2; }
    const uint32_t q[12] = {BAND(0), BAND(5), keep(bz & 0x400u), BAND(4), BAND(2), BAND(7), BAND(1), BAND(6), keep(bz & 0x800u), keep(bz & 0x1000u), BAND(3), keep(bz & 0x2000u)};
#undef BAND
    const uint32_t ta = keep(tl + 512 + (warp & 3) * 2048 + lane * 64 + (lane & 6) * 8);
    if (X_GO && hold) mbar_wait(MB_GO);
    uint32_t mbl = MB_UL + (warp & 8) * 2, ph = 0;
#pragma unroll 1
    for (int it = 0; it < SPIN_MAX; it++) {
      if (ch < 512) mbar_wait(mbl, ph);
      if (it == 1) TS(13);
      TS(3);
      wg_fence();
      wgmma64h_init(win, q[0], q[1], q[2], q[3], dlo, dhi);
      wgmma64h(win, q[4], q[5], q[6], q[7], dlo - 4, dhi);
      wgmma64h(win, q[8], q[9], q[10], q[11], dlo - 8, dhi);
      wg_commit();
      wgmma64_init<0>(a64, e, dlo, dhi);
      wgmma64<0>(a64, f, dlo - 4, dhi);
      wg_commit();
      if (ch >= 512) break;
      uint32_t r0, r1, r2, r3, ok;
      if (warp & 4) {
        mbar_wait(mbl + 8);
        if (__all_sync(0xffffffffu, it || lds32(MISC_RT + (warp & 8)) == 0)) break;
        wg_wait<0>();
        continue;
      }
      ldsm4(ta, r0, r1, r2, r3);
      ok = r0 & r1 & r2 & r3;
      ldsm4(ta ^ 32, r0, r1, r2, r3);
      asm volatile("{ .reg .pred q; setp.ne.u32 q, %1, 0; barrier.red.and.pred q, %2, 128, q; selp.u32 %0, 1, 0, q; }" : "=r"(ok) : "r"((ok & r0 & r1 & r2 & r3 & 1u) | (lane & 3)), "r"(1 + (warp >> 2)) : "memory");
      if (ok) { if ((warp & 3) == 0 && lane == 0) { sts32(MISC_RT + warp, it); mbar_arrive(MB_UL + 8 + warp * 2); } break; }
      wg_wait<0>();
      if ((warp & 3) == 0 && lane == 0) load_tile(tmx - 1, warp >> 3, ch, 56);
      mbl = MB_UL + 56 + (warp & 8) * 2; ph = it & 1;
    }
    wg_wait<1>();
#pragma unroll
    for (int i = 0; i < 4; i++) {
      const int tl = 2 * ((i & 1) + ((i & 2) ? 0 : 4));
      x9[i] = P ? win[tl + 4] : win[tl]; x7[i] = P ? win[tl + 5] : win[tl + 1];
    }
    const uint32_t l3lo = ((tb + W_L3) >> 4) + (32u << 16);
    wg_fence();
    wgmma64<0>(a64, x9, l3lo, 8);
    wgmma64<0>(a64, x7, l3lo + 96, 8);
    wg_commit();
  }
  STEP(32) STEP(33) STEP(34) wg_commit(); wg_wait<1>();
  LQ(35) LQ(36) LQ(37) LQ(38) LQ(39) LD(0) PQ(35) PQ(36) PQ(37) PQ(38) PQ(39)
  FIRST(35) STEP(36) STEP(37) STEP(38) wg_commit(); STEP(39) wg_commit();
  LD(1) LD(2) LD(3)
  if (X_GO == 1 && go) mbar_arrive(MB_GO);
  wg_wait<1>(); wg_fence(); STEP(0) wg_commit(); STEP(1) wg_commit(); STEP(2) wg_commit(); wg_wait<2>();
  LD(4) LD(5)
  wg_fence(); STEP(3) wg_commit(); wg_wait<1>();
  LD(6) LD(7)
  wg_fence(); STEP(4) STEP(5) wg_commit();
  wg_fence(); STEP(6) STEP(7) wg_commit();
#undef STEP
#undef LD
#undef LQ
#undef PQ
#undef FIRST
  TS(18);
  if (X_GO == 3 && go) mbar_arrive(MB_GO);
  const uint32_t xc = tb + W_KT + (warp & 3) * 1024 + lane * 16;
  if (more) bar_sync(7, 288);
  wg_wait<1>();
  conv_pre(pre, kp + ALT, qp + ALT, 1, more, P);
  wg_wait<0>();
  conv_pre(pre, kp + ALT, qp + ALT, 2, more, P);
  uint32_t E[16], o[8];
#define ACC(i) ((i) < 16 ? a32[i] : (i) < 32 ? b32[(i) - 16] : a64[(i) - 32])
  E[0] = pack_h(a32[0], a32[1]);
#pragma unroll
  for (int i = 1; i < 16; i++) E[i] = pack_h(ACC(4 * i) + ACC(4 * i - 2), ACC(4 * i + 1) + ACC(4 * i - 1));
#undef ACC
#pragma unroll
  for (int j = 0; j < 8; j++) o[j] = P ? (j < 2 ? 0u : E[j - 2]) : E[8 + j];
  sts128(xc, o[0], o[1], o[2], o[3]); sts128(xc + 512, o[4], o[5], o[6], o[7]);
#pragma unroll
  for (int j = 0; j < 8; j++) o[j] = P ? E[6 + j] : E[j];
  TS(25);
  if (more) {
    sts128(xc + 4096, o[0], o[1], o[2], o[3]); sts128(xc + 4608, o[4], o[5], o[6], o[7]);
    bar_arrive(12, 192);
    return;
  }
  bar_sync(1 + (warp >> 2), 128);
  const uint4 vv[2] = {lds128(xc + (P ? -2048 : 2048)), lds128(xc + (P ? -1536 : 2560))};
  const uint32_t mk = lane < 8 ? 0xFFFEFFFEu : ~0u;
#pragma unroll
  for (int q = 0; q < 2; q++) {
    const uint4 v = vv[q];
    stsm4t(tl + (cv.ca >> 16) + q * 2048, hadd2u(o[4 * q], v.x) & mk, hadd2u(o[4 * q + 1], v.y) & mk, hadd2u(o[4 * q + 2], v.z) & mk, hadd2u(o[4 * q + 3], v.w) & mk);
  }
  fence_async();
  bar_sync(bid, bn);
  if (warp == 0 && lane == 0) mbar_arrive(MB_REL);
  if ((warp & 7) == (ch < 512 ? 7 : 3) && lane == 0) {
    asm volatile("cp.async.bulk.tensor.3d.global.shared::cta.bulk_group [%0, {%3, %2, %3}], [%1];" :: "l"(tmx), "r"(tl + 512), "r"(ch), "r"(0) : "memory");
    asm volatile("cp.async.bulk.commit_group;" ::: "memory");
  }
}

template <bool FAR> __global__ void __launch_bounds__(NT, 1)
fused_kernel(const __grid_constant__ Params p, const __grid_constant__ TMaps tm) {
  extern __shared__ __align__(1024) unsigned char smem[];
  const int c = blockIdx.x;
  const bool five = (c & 1) == 0;
  const uint32_t pitch = five ? 64 : 80;
  const uint32_t ones = 0x3F803F80u;
  const int tid = threadIdx.x, lane = tid & 31;
  const uint32_t xrow = OFF_YT + ((tid & 127) >> 3) * YT_PITCH + (tid & 64) + (tid & 7) * 16;
  {
    const int w4 = tid >> 7;
    load_params<FAR>(p, w4 < 2 ? 2 * c + w4 : five ? 257 + 2 * c : 512 + (c >> 1), tid & 127, OFF_W + W_KT + (w4 < 2 ? w4 * W_BYTES : five ? 3 * W_BYTES : 3 * W_BYTES + 2048), (0xB >> w4) & 1);
  }
  if ((tid >> 7) == 2) {
    const unsigned char* xp = p.x + (uint32_t)((c * 16 - 32 + (tid >> 3)) * 1152 + (tid & 7) * 16);
    asm volatile("" : "+l"(xp));
    { const uint32_t tq = clock(); while ((int)(clock() - tq) < X_XD) {} }
#pragma unroll
    for (int k = 0; k < 9; k++) asm volatile("cp.async.cg.shared.global [%0], [%1], 16;" :: "r"(xrow + k * 128), "l"(xp + k * 128) : "memory");
  }
  const int warp = (int)uni(tid >> 5), wg = warp >> 2;
  TS(0);
  if (__builtin_expect(wg == 4, 0)) {
    asm volatile("setmaxnreg.dec.sync.aligned.u32 32;");
    const int role = warp;
    const int u0 = (c >> 1) * 9 + (five ? ((c & 2) ? 5 : 0) : ((c & 2) ? 0 : 4));
    const uint32_t t0 = clock() + c * 4;
    if (role == 16) {
      if (lane == 0) {
#pragma unroll
        for (int i = 0; i < 19; i++) if (i != 16) asm volatile("mbarrier.init.shared::cta.b64 [%0], %1;" :: "r"(OFF_MISC + i * 8), "r"((unsigned)(i - 2) < 4u ? 4 : 1) : "memory");
      }
      __syncwarp();
      if (lane < 2) asm volatile("mbarrier.arrive.expect_tx.shared::cta.b64 _, [%0], %1;" :: "r"(OFF_MISC + lane * 8), "r"(lane ? (five ? 36864 : 51200) : pitch * 1152) : "memory");
      fence_async();
      bar_arrive(5, 608);
      const CUtensorMap* tmb = &tm.m[five ? 3 : 0];
#pragma unroll 1
      for (int u = 0; u < 17; u++) {
        const uint32_t e = p.sched[five][u], kind = e & 3, s = (e >> 2) & 15, dst = e >> 14;
        if (kind == 3) continue;
        if (X_NP && u == 2) {
#pragma unroll 1
          for (int k = 0; k < X_NP; k++) {
            while ((int)(clock() - t0) < X_PF0 + (2 + k) * X_PFD) __nanosleep(20);
            if (lane == 0) asm volatile("cp.async.bulk.prefetch.tensor.2d.L2.global [%0, {%1, %2}];" :: "l"(tmb), "r"(u0 * 8), "r"((4 + k) * 96) : "memory");
          }
        }
        while ((int)(clock() - t0) < X_PF0 + (u < X_NE ? u * X_PFD : X_LAG + u * X_TD - min(u - 2, 4) * X_SK)) __nanosleep(20);
        if (e & 0x3FC0) mbar_wait(OFF_MISC + ((e >> 6) & 255));
        if (lane == 0) {
          if (kind == 2) asm volatile("cp.async.bulk.tensor.3d.shared::cluster.global.mbarrier::complete_tx::bytes [%0], [%1, {%3, %4, %5}], [%2];"
                                      :: "r"(dst), "l"(tmb + 2), "r"(MB_D), "r"(0), "r"(u0 * 8), "r"(s) : "memory");
          else tma_box(dst, tmb + kind, MB_GU, u0 * 8, s * 96);
        }
        if (u == 5) TS(2);
        if (u == 10) TS(3);
      }
      TS(4);
      TS_DUMP();
#define FINISH0 bar_sync(12, 192);        \
        _Pragma("unroll 1") for (int w = role & 2; w < (role & 2) + 2; w++) { \
          const uint32_t xa = OFF_W + W_KT + lane * 16, mk = lane < 8 ? 0xFFFEFFFEu : ~0u, ya = OFF_T + (8 + lane) * 64 + (((w & 1) ^ (lane >> 1)) & 3) * 16 + (w & 2) * 2048; \
          const uint4 a = lds128(xa + 4096 + w * 1024), b = lds128(xa + (w ^ 2) * 1024), d = lds128(xa + 4608 + w * 1024), e = lds128(xa + 512 + (w ^ 2) * 1024); \
          stsm4t(ya, hadd2u(a.x, b.x) & mk, hadd2u(a.y, b.y) & mk, hadd2u(a.z, b.z) & mk, hadd2u(a.w, b.w) & mk); \
          stsm4t(ya + 2048, hadd2u(d.x, e.x) & mk, hadd2u(d.y, e.y) & mk, hadd2u(d.z, e.z) & mk, hadd2u(d.w, e.w) & mk); \
        } \
        fence_async();
    } else if (role == 17) {
      if (smem_u32(smem) != SB) __trap();
      bar_sync(10, 576);
      if (lane == 0) {
        fence_async();
        while ((int)(clock() - t0) < X_NS - c * 4) {}
        asm volatile("cp.async.bulk.global.shared::cta.bulk_group [%0], [%1], 10240;" :: "l"(&p.s->X[c * DM * 2 + 512]), "r"(OFF_G) : "memory");
        asm volatile("cp.async.bulk.commit_group;" ::: "memory");
        asm volatile("cp.async.bulk.wait_group 0;" ::: "memory");
      }
      if (lane == 0) mbar_arrive(MB_GF);
      bar_arrive(11, 96);
      if (five) { FINISH0 bar_arrive(13, 192); }
    } else if (role == 18) {
      sts32(MISC_EPOCH, 0);
      sts32(MISC_T0, t0 - c * 4);
      bar_arrive(5, 608);
      uint4* q = lane < 2 ? &p.s->R[c * 2 + lane] : lane < 11 ? &p.s->HS[c * 9 + lane - 2] : lane == 11 ? &p.s->HS[1152 + (c & 7)] : (uint4*)&p.s->FLAG[c * 8];
      if (lane < (c < 8 ? 12 : 11)) str128(q, ~0u, ~0u, ~0u, ~0u);
      const uint32_t ep = __shfl_sync(0xffffffffu, ldr32(q), 31) + 1u;
      sts32(MISC_EPOCH, ep | 0x80000000u);
      TSX(21);
      if (lane == 31) str32(q, ep);
      bar_sync(11, 96);
      TSX(14);
      mbar_wait(MB_KF + (lane & 3) * 8);
      __syncwarp();
      { const uint2 e = lds64(MISC_EM); if (lane < 2) str128(&p.s->SC[c * 2 + lane], e.x, __byte_perm(e.y, ep, 0x6540), 0, 0); }
      TSX(17);
      while ((int)(clock() - t0) < X_SCT) __nanosleep(100);
      TSX(18);
      {
        uint2 v[4];
#pragma unroll 1
        for (int it = 0; it < SPIN_MAX; it++) {
          uint32_t bad = 0;
#pragma unroll
          for (int q = 0; q < 4; q++) v[q] = ldr64(&p.s->SC[lane * 2 + q * 64]);
#pragma unroll
          for (int q = 0; q < 4; q++) bad |= (v[q].y >> 8) ^ (ep & 0xFFFFFFu);
          if (!__any_sync(0xffffffffu, bad)) break;
        }
        TSX(25);
#pragma unroll
        for (int q = 0; q < 4; q++) {
          const uint32_t sa = (lane >> 4) * YT_PITCH + (lane & 15) * 2;
          sts16(sc_addr(2 * q) + sa, v[q].x); sts16(sc_addr(8 + 2 * q) + sa, v[q].x >> 16);
          if (lane & 1) asm volatile("st.shared.u8 [%0], %1;" :: "r"(sc_addr(16) + q * 16 + (lane >> 1)), "r"(v[q].y) : "memory");
        }
      }
      __syncwarp();
      if (lane == 0) mbar_arrive(MB_SC);
      TSX(27);
    } else {
      uint32_t w[9];
      const uint32_t dk = ldnc16(p.dskip + ((lane & 4) ? 512 + (c >> 1) : (lane & 2) * 128 + 2 * c + (lane & 1)));
      float s = 0.f;
#pragma unroll
      for (int i = 0; i < 9; i++) w[i] = ldnc32(p.w_r + lane + 32 * i);
      sts16(OFF_WR + 1152 + lane * 2, dk);
      bar_arrive(5, 608);
#pragma unroll
      for (int i = 0; i < 9; i++) { sts32(OFF_WR + lane * 4 + i * 128, w[i]); s += bf_lo(w[i]) + bf_hi(w[i]); }
      sts32(MISC_SW, __float_as_uint(warp_sum(s)));
      TSX(23);
      bar_sync(10, 576);
      if (lane == 0) {
        const uint32_t tp = clock();
        TSX(1);
        while ((int)(clock() - tp) < X_DELTA || (int)(clock() - t0) < X_ABS - c * 4) {}
        TSX(24);
        load_tile(&tm.m[6], 0, c);
        TSX(15);
        while ((int)(clock() - t0) < X_ABS + X_DSTEP - c * 4) {}
      }
      bar_sync(11, 96);
      if (lane == 0) {
        load_tile(&tm.m[6], 1, 128 + c);
      }
      if (five) {
        mbar_wait(MB_KF);
#pragma unroll 1
        for (int it = 0; it < SPIN_MAX; it++) {
          if (lane == 0) load_tile(&tm.m[8], 2, 512 + (c >> 1));
          mbar_wait(MB_UL + 32, it & 1);
          uint32_t m = 1;
#pragma unroll
          for (int q = 0; q < 4; q++) { uint32_t r0, r1, r2, r3; ldsm4(OFF_W + 512 + lane * 64 + (lane & 6) * 8 + q * 2048, r0, r1, r2, r3); m &= r0 & r1 & r2 & r3; }
          if (__all_sync(0xffffffffu, m || (lane & 3))) break;
        }
        bar_arrive(7, 288);
        FINISH0
        bar_arrive(13, 192);
      }
      bar_sync(0, 544);
      if (lane == 0) mbar_arrive(MB_H);
    }
    return;
  }
  const int wt = tid & 127, g = lane >> 2, t = lane & 3;
  const uint32_t wb = OFF_W + wg * W_BYTES;
  asm volatile("cp.async.commit_group;" ::: "memory");
  const ConvC cv = conv_consts(warp, lane);
  zero_pads(wb, wt);
  load_params<FAR>(p, 254 + 2 * c + wg, wt, wb + W_KT, wg == 2 || (wg == 3 && !five));
  asm volatile("cp.async.commit_group;" ::: "memory");
  asm volatile("setmaxnreg.inc.sync.aligned.u32 112;");
  {
    uint4 kw;
    uint4* kx = &p.s->KX[(c >> 1) * 128 + wt];
    bool two = wg == 3;
    uint32_t ep;
    int em = 0;
    uint32_t slot = wg + (two && !five);
    const uint32_t ra0 = wb + W_KT + (slot & 4) * 512 + wt * 2, ra6 = wb + W_KT + 1536 + (slot & 4) * 512 + (((slot & 4) ? c >> 1 : 2 * c + (wg & 1)) & 7) * 2;
        const int lz = lane;
        const uint32_t tr_addr = pin(tr_base(lz) + warp * 32), lca = pin(MISC_LN1 + (lz & 1) * 16);
        uint4* dst;
        { const unsigned long long a = (unsigned long long)&p.s->X[c * DM * 2 + warp * 32 + (8 * ((lz >> 1) & 1) + (lz >> 2)) * 2 + (lz & 1)];
          dst = (uint4*)(((unsigned long long)pin(a >> 32) << 32) | pin((uint32_t)a)); }
    const BuildC bc = build_consts(wt);
    uint32_t raw[7];
    if (wg != 2) {
      asm volatile("cp.async.wait_group 1;" ::: "memory");
      bar_sync(1 + wg, 128);
#pragma unroll
      for (int i = 0; i < 7; i++) raw[i] = lds16(i < 6 ? ra0 + i * 256 : ra6);
    }
    int phase = wg == 2 ? 3 : 2;
#pragma unroll 1
    for (;;) {
      if (phase != 3) {
        KgState ks;
        TS(22);
        kgen_tables_n(raw, wb, wt, ks);
        TS(20);
        bar_sync(1 + wg, 128);
        em = kgen_tables_m(wb, wt, ks);
        fence_async();
      }
      if (phase & 2) {
        if (phase == 3) {
        asm volatile("cp.async.wait_group 1;" ::: "memory");
        TS(21);
        float d[3][4], r;
        uint4 a[9];
#pragma unroll
        for (int k = 0; k < 9; k++) a[k] = lds128(xrow + k * 128);
#pragma unroll
        for (int i = 0; i < 4; i++) d[0][i] = d[1][i] = d[2][i] = 0.f;
#pragma unroll
        for (int k = 0; k < 9; k++) { mma_bf16(d[(2 * k) % 3], a[k].x, ones, a[k].y, ones, a[k].x, a[k].y); mma_bf16(d[(2 * k + 1) % 3], a[k].z, ones, a[k].w, ones, a[k].z, a[k].w); }
#pragma unroll
        for (int i = 0; i < 4; i++) d[0][i] += d[1][i] + d[2][i];
        const LnC lc = ln_consts(d[0][2] + d[0][3], __shfl_sync(0xffffffffu, d[0][0], 9 * t) + __shfl_sync(0xffffffffu, d[0][1], 9 * t + 4), r);
        if (lane < 12) sts16(MISC_LN1 + g * 32 + (warp & 3) * 8 + t * 2, lane < 4 ? lc.m2 : lane < 8 ? lc.rh2 : lc.rl2);
        }
        asm volatile("cp.async.wait_group 0;" ::: "memory");
        TS(23);
        bar_sync(5, 608);
        uint32_t x[3][4];
        ldsm4t(tr_addr, x[0][0], x[0][1], x[0][2], x[0][3]);
        uint4 m = lds128(lca);
        const uint4 rl = lds128(lca + 64), rh = lds128(lca + 32);
        ldsm4t(tr_addr + 512, x[1][0], x[1][1], x[1][2], x[1][3]);
        if (wg == 3) ldsm4t(tr_addr + 640, x[2][0], x[2][1], x[2][2], x[2][3]);
#pragma unroll
        for (int q = 0; q < 3; q++) {
          if (q < 2 || wg == 3) {
            const uint32_t r0 = ln_apply(x[q][0], m.x, rh.x, rl.x), r1 = ln_apply(x[q][1], m.y, rh.y, rl.y), r2 = ln_apply(x[q][2], m.z, rh.z, rl.z), r3 = ln_apply(x[q][3], m.w, rh.w, rl.w);
            const uint32_t w0 = (pack_h(bf_lo(r0), bf_hi(r0)) & 0xFFFEFFFEu) | 1u, w1 = pack_h(bf_lo(r1), bf_hi(r1)), w2 = pack_h(bf_lo(r2), bf_hi(r2)), w3 = pack_h(bf_lo(r3), bf_hi(r3));
            if (q == 0) str128(dst, w0, w1, w2, w3);
            else sts128(OFF_G + warp * 512 + (8 * (t >> 1) + g) * 32 + (t & 1) * 16 + (q == 2 ? 2048 : 0), w0, w1, w2, w3);
          }
          if (q == 0) {
            const uint32_t z = clock() & p.off[7];
            m.x ^= z; m.y ^= z; m.z ^= z; m.w ^= z;
          }
          if (q == 0) TS(30);
          if (q == 0 && wg >= 2) {
#pragma unroll
            for (int i = 0; i < 7; i++) raw[i] = lds16(wb + W_KT + i * 256 + (i < 6 ? wt : (2 * c + (wg & 1)) & 7) * 2);
          }
        }
        bar_arrive(10, 576);
        TS(1);
      } else bar_sync(1 + wg, 128);
      phase &= 1;
      if (phase) { phase = 0; continue; }
      TS(14);
      float acc[20];
      const uint32_t alo = (wb >> 4) | (8u << 16);
      uint4 k4 = lds128(wb + W_MISC + 16);
      uint32_t dk = lds16(OFF_WR + 1152 + slot * 2);
      wg_fence();
      wgmma40_ss_init(acc, alo, alo + 1024, 2048 >> 4);
#pragma unroll
      for (int k = 1; k < 8; k++) wgmma40_ss(acc, alo + k * 16, alo + 1024 + k * 16, 2048 >> 4);
      wg_commit();
      { const uint32_t z = clock() & p.off[7]; dk ^= z; k4.x ^= z; k4.z ^= z; }
      const float k2048 = (float)(int)((k4.x + k4.y) + (k4.z + k4.w)) * (1.f / 262144.f);
      const int ef = max(em, min((int)((dk >> 7) & 255u) - 7, 238));
      asm volatile("st.shared.u8 [%0], %1;" :: "r"(MISC_EM + slot), "r"(ef + 9) : "memory");
      const float un = __uint_as_float((uint32_t)max(114 + em - ef, 0) << 23), d0 = wt ? 0.f : bf_lo(dk) * __uint_as_float((uint32_t)(245 - ef) << 23);
      wg_wait<0>();
      kw.x = pack_h(fmaf(acc[0] - acc[3], un, d0), (acc[4] - acc[7]) * un);
      kw.y = pack_h((acc[8] - acc[11]) * un, (acc[12] - acc[15]) * un);
      kw.z = pack_h((acc[16] - acc[19]) * un, k2048 * un);
      TS(24);
      ep = 0;
      if (two) SPIN_WHILE(ep == 0, ep = lds32(MISC_EPOCH));
      if (five || !two) break;
      str128(kx, kw.x, kw.y, kw.z, ep);
      two = false;
      slot = 3;
      bar_sync(1 + wg, 128);
    }
    if (lane == 0) mbar_arrive(MB_KF + wg * 8);
    if (two) { mbar_wait(MB_KF); zero_pads(OFF_W + ALT, wt); }
    uint32_t tb = wb;
#pragma unroll 1
    for (;;) {
      kgen_build(tb, bc, wg, wt, kw.x, kw.y, kw.z);
      TS(15);
      if (!two) break;
      two = false;
      kw.w = 0;
      SPIN_WHILE(kw.w != ep, kw = ldr128(kx));
      tb = OFF_W + ALT;
    }
    fence_async();
    TS(31);
    if (tb != wb) bar_arrive(7, 288);
    bar_sync(1 + wg, 128);
  }
  uint32_t tpub;
  ConvPre pre;
  conv_pre(pre, (wb ^ p.off[7]) + (cv.ca & 0xFFFFu), (wb ^ p.off[7]) + cv.qa, 3, true, warp & 2);
#pragma unroll 1
  for (int item = 0;; item++) {
    TS(2);
    conv_item(item ? OFF_W + ALT : wb, item ? OFF_W : OFF_T + (wg >> 1) * TILE, item ? 1 : 13 + (wg >> 1), item ? 128 : five && wg == 1 ? 192 : 256, pre, cv, p.off[7],
              &tm.m[item ? 9 : 7], item ? 512 + (c >> 1) : (wg >> 1) * 128 + c, warp, lane, five && wg >= X_GW, five && !wg && !item);
    tpub = clock() - (item ? X_YD : wg >= 2 ? X_YD2 : 0);
    if (wg || !five || item) break;
    TS(27);
  }
  TS(4);

  const int ln = lane ^ p.off[7], td = warp * 32 + ln, gg = ln >> 2, tt = ln & 3;
  const int tok = c * 16 + warp;
  const int fu = warp / 3, fk = warp - fu * 3;
  uint32_t wa[12][4];
  uint4 ha[3];
  const uint4* hsrc = &p.s->HS[td + (td / 24) * 48];
  {
    uint32_t hw[9], wr[9];
    const uint32_t row = keep(OFF_YT + warp * YT_PITCH + (warp >> 3) * 64 + ln * 16);
    const uint32_t wabase = keep(((ln & 8) ? OFF_W + (fk + 1) * W_BYTES : OFF_G + fk * 192 * pitch) + ((ln >> 4) * 8 + (ln & 7)) * pitch
                                 + (five ? ((fu ^ (ln >> 1)) & 3) : min(fu, 4)) * 16);
    float sw;
    {
      const bool three = wg == 1;
      const int ch = 8 * (tt >> 1) + gg;
      const uint32_t tr_addr = tr_base(ln);
      const uint4* ysrc = &p.s->X[c * DM * 2 + ch * 2 + (tt & 1)];
      uint32_t x[3][4], s[3];
      uint4 v[3];
#define TL(q) ((q) < 2 ? 2 * warp + (q) : 28 + warp)
      if (wg >= 2) { const uint32_t ts = lds32(MISC_T0); while ((int)(clock() - ts) < X_XS) {} }
      while ((int)(clock() - tpub) < X_YD) {}
      TS(5);
      v[0] = ldr128(ysrc + TL(0) * 32); v[1] = ldr128(ysrc + TL(1) * 32); v[2] = make_uint4(three, 0, 0, 0);
      mbar_wait(MB_REL);
#pragma unroll
      for (int i = 0; i < 6; i++) if (i < 4 || three) wr[i] = (gg & 2) ? ones : lds32(OFF_WR + TL(i >> 1) * 32 + (i & 1) * 16 + tt * 4);
      const uint32_t ha = keep(OFF_YT + (ln & 7) * YT_PITCH + (ln >> 4) * (8 * YT_PITCH + 64) + (ln & 8) * 2);
      const uint32_t pa = keep(OFF_PART + warp * 4 + ((gg & 2) * 8 + (gg & 4) * 2 + 2 * tt + (gg & 1)) * 80), pb = keep(OFF_PART + 2560 + warp * 4 + gg * 80);
      float dl[4] = {0.f, 0.f, 0.f, 0.f}, dh[4] = {0.f, 0.f, 0.f, 0.f};
      sw = __uint_as_float(lds32(MISC_SW));
#pragma unroll
      for (int q = 0; q < 3; q++) {
        if (q < 2 || three) {
          ldsm4t(tr_addr + TL(q) * 32, x[q][0], x[q][1], x[q][2], x[q][3]);
        }
      }
      asm volatile("cp.async.bulk.wait_group.read 0;" ::: "memory");
      mbar_wait(MB_SC);
#pragma unroll
      for (int q = 0; q < 3; q++) {
        asm volatile("ld.shared.u8 %0, [%1];" : "=r"(s[q]) : "r"((q < 2 ? sc_addr(warp) + q * 16 : sc_addr(16) + (warp & 3) * 16) + ch) : "memory");
        s[q] = keep(s[q] * 0x800080u);
      }
#define FIN(q) stsm4t(tr_addr + TL(q) * 32, bf_fma2(h2bf(v[q].x), s[q], x[q][0]), bf_fma2(h2bf(v[q].y), s[q], x[q][1]), bf_fma2(h2bf(v[q].z), s[q], x[q][2]), bf_fma2(h2bf(v[q].w), s[q], x[q][3]));
      SPIN_WHILE((v[0].x | v[1].x) & 1u, _Pragma("unroll") for (int q = 0; q < 3; q++) if (v[q].x & 1u) v[q] = ldr128(ysrc + TL(q) * 32));
      if (v[2].x & 1u) v[2] = ldr128(ysrc + TL(2) * 32);
#define STAT(q) { uint32_t r0, r1, r2, r3; ldsm4(ha + TL(q) * 32, r0, r1, r2, r3); \
        mma_bf16(dl, r0, wr[2 * q], r1, wr[2 * q + 1], r0, r1); mma_bf16(dh, r2, wr[2 * q], r3, wr[2 * q + 1], r2, r3); }
      FIN(0) FIN(1)
      __syncwarp();
      STAT(0) STAT(1)
      if (three) {
#pragma unroll 1
        for (int it = 0; it < SPIN_MAX; it++) {
          FIN(2)
          if (!__any_sync(0xffffffffu, v[2].x & 1u)) break;
          if (v[2].x & 1u) v[2] = ldr128(ysrc + TL(2) * 32);
        }
        __syncwarp();
        STAT(2)
      }
      if (gg & 1) { dl[0] = dl[1]; dl[2] = dl[3]; dh[0] = dh[1]; dh[2] = dh[3]; }
      sts32(pa, __float_as_uint((gg & 4) ? dh[2] : dl[2]));
      if (tt == (gg >> 1)) { sts32(pb, __float_as_uint(dl[0])); sts32(pb + 640, __float_as_uint(dh[0])); }
#undef STAT
#undef FIN
#undef TL
    }
    uint32_t ra = keep(OFF_PART + (ln & 15) * 80 + (ln & 16) * 2);
    uint16_t* rp = (uint16_t*)p.s->R + c * 16 + (ln & 15);
    const uint2* rsrc = (const uint2*)p.s->R + td;
    asm volatile("" : "+l"(rp), "+l"(rsrc), "+l"(hsrc));
    uint2 rv = make_uint2(0u, 0u);
    TS(28);
    if (warp != X_PW) bar_sync(0, 544);
    else {
      float z[3], rd;
      asm volatile("bar.sync 0, 544;" : "+r"(ra) :: "memory");
#pragma unroll
      for (int k = 2; k >= 0; k--) {
        const uint4 a = lds128(ra + k * 1280), b = lds128(ra + k * 1280 + 16);
        z[k] = ((__uint_as_float(a.x) + __uint_as_float(a.y)) + (__uint_as_float(a.z) + __uint_as_float(a.w))) + ((__uint_as_float(b.x) + __uint_as_float(b.y)) + (__uint_as_float(b.z) + __uint_as_float(b.w)));
      }
#pragma unroll
      for (int k = 2; k >= 0; k--) z[k] += __shfl_xor_sync(0xffffffffu, z[k], 16);
      const LnC l = ln_consts(z[1], z[2], rd);
      const uint32_t b = pack_bf(0.f, fmaf(-bf_lo(l.m2), sw, z[0]) * rd);
      const uint32_t k16 = max(min((b ^ (((int)b >> 31) | 0x80000000u)) >> 16, 0xFFFEu), 1u);
      if (ln < 16) str16(rp, k16);
      sts64(OFF_RK + (ln & 15) * 8, __byte_perm(l.m2, l.rh2, 0x5410), __byte_perm(l.rl2, k16, 0x5410));
      sts128(MISC_CNT + ln * 16, 0, 0, 0, 0);
    }
    mbar_wait(MB_GU);
#define LD_HW { const uint4 a = lds128(row), b = lds128(row + 512); hw[8] = lds32(row + 1024 - ln * 12); \
      hw[0] = a.x; hw[1] = a.y; hw[2] = a.z; hw[3] = a.w; hw[4] = b.x; hw[5] = b.y; hw[6] = b.z; hw[7] = b.w; }
    LD_HW
    const uint32_t tr0 = clock();
    bar_sync(5, 512);
    TS(7);
    const uint2 lk = lds64(OFF_RK + warp * 8);
    LnC l2;
    l2.m2 = __byte_perm(lk.x, 0, 0x1010); l2.rh2 = __byte_perm(lk.x, 0, 0x3232); l2.rl2 = __byte_perm(lk.y, 0, 0x1010);
    const uint32_t key = (lk.y & 0xFFFF0000u) | (2047 - tok);
    uint32_t loc = ln < 16 ? (lds32(OFF_RK + 4 + ln * 8) & 0xFFFF0000u) | (2047 - c * 16 - ln) : 0u;
    int rank = __popc(__ballot_sync(0xffffffffu, loc > key));
#pragma unroll
    for (int i = 0; i < 9; i++) { wr[i] = keep(ln_apply(hw[i], l2.m2, l2.rh2, l2.rl2)); hw[i] = bf_add2(hw[i], wr[i]); }
#define OUT_ROW { uint32_t* o = p.out + tok * 288 + ln * 4; \
      *(uint4*)o = make_uint4(hw[0], hw[1], hw[2], hw[3]); *(uint4*)(o + 128) = make_uint4(hw[4], hw[5], hw[6], hw[7]); o[256 - ln * 3] = hw[8]; }
    uint4* hs = p.s->HS + ln;
    asm volatile("" : "+l"(hs));
#pragma unroll 1
    for (int base = 0; base < 8; base += 2) {
      uint32_t T[2];
#pragma unroll
      for (int j = 0; j < 2; j++) {
        const uint32_t mx = __reduce_max_sync(0xffffffffu, loc);
        if (loc == mx) loc = 0;
        T[j] = (td >> 2) < c ? (mx & 0xFFFF0000u) - 1u : mx | 0xFFFFu;
      }
      const uint32_t sh = keep(rank == base ? 0x4410u : rank == base + 1 ? 0x4432u : 0x4445u), ca = keep(MISC_CNT + base * 64 + ln * 4);
      TS(29);
      if (base == 0) {
        while ((int)(clock() - tr0) < X_RD) {}
        if ((td >> 2) != c) rv = ldr64(rsrc);
        if (rank >= X_OR) OUT_ROW
        if (warp < (five ? 12 : 15)) {
#pragma unroll
          for (int k = 0; k < X_WS; k++) ldsm4t(wabase + k * 16 * pitch, wa[k][0], wa[k][1], wa[k][2], wa[k][3]);
        }
      }
      uint32_t cnt;
#pragma unroll 1
      for (int it = 0; it < SPIN_MAX; it++) {
        const uint32_t xs = rv.x << 16, ys = rv.y << 16;
        const bool bad = max(max(rv.x, xs), max(rv.y, ys)) >= 0xFFFF0000u;
        uint32_t cn2 = 0;
        cnt = bad ? 256u : 0u;
#pragma unroll
        for (int j = 0; j < 2; j++)
          asm("{ .reg .pred a, b, c, d; setp.gt.u32 a, %2, %6; setp.gt.u32 b, %3, %6; setp.gt.u32 c, %4, %6; setp.gt.u32 d, %5, %6; "
              "@a add.u32 %1, %1, %7; @b add.u32 %1, %1, %7; @c add.u32 %0, %0, %7; @d add.u32 %0, %0, %7; }"
              : "+r"(cnt), "+r"(cn2) : "r"(rv.x), "r"(rv.y), "r"(xs), "r"(ys), "r"(T[j]), "r"(1u << (16 * j)));
        cnt = __reduce_add_sync(0xffffffffu, cnt + cn2);
        asm volatile("{ .reg .pred q; setp.eq.u32 q, %2, 0; @q red.shared.add.u32 [%0], %1; }" :: "r"(ca), "r"(cnt), "r"(cnt & 0x3F00u) : "memory");
        if (!(cnt & 0x3F00u)) break;
        if (bad) rv = ldr64(rsrc);
      }
      TS(16);
      bar_sync(0, 512);
      cnt = lds32(ca);
      if (base == 0) tpub = clock();
      const int gr = rank + __byte_perm(cnt, 0x800u, sh);
      if (gr < 8) {
        uint4* ks = hs + 1152 + gr;
        hs = (uint4*)((char*)hs + gr * 1152);
        asm volatile("{ .reg .b128 t, u; .reg .b64 a, b, c, d; mov.b64 a, {%1,%2}; mov.b64 b, {%3,%4}; mov.b64 c, {%5,%6}; mov.b64 d, {%7,%8}; mov.b128 t, {a, b}; mov.b128 u, {c, d}; "
                     "st.relaxed.gpu.global.b128 [%0], t; st.relaxed.gpu.global.b128 [%0 + 512], u; }"
                     :: "l"(hs), "r"(wr[0]), "r"(wr[1]), "r"(wr[2]), "r"(wr[3]), "r"(wr[4]), "r"(wr[5]), "r"(wr[6]), "r"(wr[7]) : "memory");
        str32((uint32_t*)(hs + 64) - ln * 3, wr[8]);
        LD_HW
        str128(hs + 576, hw[0], hw[1], hw[2], hw[3]); str128(hs + 608, hw[4], hw[5], hw[6], hw[7]); str32((uint32_t*)(hs + 640) - ln * 3, hw[8]);
        if (ln == 0) str32(ks, key);
        rank = 16;
      }
      if (__all_sync(0xffffffffu, (int)(cnt >> 16) + base + 2 >= 8)) break;
    }
    TS(8);
    if (warp < (five ? 12 : 15)) {
#pragma unroll
      for (int k = X_WS; k < 12; k++) ldsm4t(wabase + k * 16 * pitch, wa[k][0], wa[k][1], wa[k][2], wa[k][3]);
    }
    if (warp < 6) while ((int)(clock() - tpub) < X_HD) {}
    TS(19);
    if (warp < 6) { ha[0] = ldr128(hsrc); ha[1] = ldr128(hsrc + 24); ha[2] = ldr128(hsrc + 48); }
    if (rank < X_OR) OUT_ROW
  }
  uint32_t wd[10][4];
  const uint32_t xb = keep(OFF_XS + (ln & 7) * 1168 + (fk * 24 + (ln >> 3)) * 16);
  if (warp >= 7) {
    const uint32_t db = down_box(warp - 7, five) + (ln & 7) * 128;
    mbar_wait(MB_D);
#pragma unroll
    for (int j = 0; j < 4; j++) {
      const uint32_t a = db + (ln >> 4) * 1024 + (((2 * j + ((ln >> 3) & 1)) ^ (ln & 7)) << 4);
      ldsm4t(a, wd[j][0], wd[j][1], wd[j][2], wd[j][3]);
      ldsm4t(a + 2048, wd[4 + j][0], wd[4 + j][1], wd[4 + j][2], wd[4 + j][3]);
    }
#pragma unroll
    for (int j = 0; j < 2; j++) ldsm4t(db + 4096 + (((4 * j + (ln >> 3)) ^ (ln & 7)) << 4), wd[8 + j][0], wd[8 + j][1], wd[8 + j][2], wd[8 + j][3]);
  } else if (warp < 6) {
    const uint32_t xs = keep(OFF_XS + (td + (td / 24) * 49) * 16);
#pragma unroll 1
    for (int it = 0; it < SPIN_MAX; it++) {
      const bool bad = max(max(max(ha[0].x, ha[1].x), max(ha[2].x, ha[2].y)), max(ha[2].z, ha[2].w)) == ~0u;
#pragma unroll
      for (int q = 0; q < 3; q++) sts128(xs + q * 384, ha[q].x, ha[q].y, ha[q].z, ha[q].w);
      if (!__any_sync(0xffffffffu, bad)) break;
      if (bad) { ha[0] = ldr128(hsrc); ha[1] = ldr128(hsrc + 24); ha[2] = ldr128(hsrc + 48); }
    }
  }
  TS(9);

  bar_sync(0, 512);
  if (warp < (five ? 12 : 15)) {
    float d0[4] = {0.f, 0.f, 0.f, 0.f}, d1[4] = {0.f, 0.f, 0.f, 0.f};
#pragma unroll
    for (int k = 0; k < 12; k += 2) {
      uint32_t b0, b1, b2, b3;
      ldsm4(xb + k * 32, b0, b1, b2, b3);
      mma_bf16(d0, wa[k][0], wa[k][1], wa[k][2], wa[k][3], b0, b1);
      mma_bf16(d1, wa[k + 1][0], wa[k + 1][1], wa[k + 1][2], wa[k + 1][3], b2, b3);
    }
    sts128(OFF_RED + td * 16, __float_as_uint(d0[0] + d1[0]), __float_as_uint(d0[1] + d1[1]), __float_as_uint(d0[2] + d1[2]), __float_as_uint(d0[3] + d1[3]));
  }
  TS(26);
  if (warp < 5) {
    const uint32_t rb = OFF_RED + warp * 1536 + ln * 16;
    bar_sync(9, 512);
    const uint4 pa = lds128(rb), pb = lds128(rb + 512), pc = lds128(rb + 1024);
    const float ga = bfr(__uint_as_float(pa.x) + __uint_as_float(pb.x) + __uint_as_float(pc.x));
    const float gb = bfr(__uint_as_float(pa.y) + __uint_as_float(pb.y) + __uint_as_float(pc.y));
    const uint32_t uu = pack_bf(__uint_as_float(pa.z) + __uint_as_float(pb.z) + __uint_as_float(pc.z), __uint_as_float(pa.w) + __uint_as_float(pb.w) + __uint_as_float(pc.w));
    float ra, rb2;
    asm("rcp.approx.ftz.f32 %0, %1;" : "=f"(ra) : "f"(1.f + ex2(ga * -1.4426950408889634f)));
    asm("rcp.approx.ftz.f32 %0, %1;" : "=f"(rb2) : "f"(1.f + ex2(gb * -1.4426950408889634f)));
    const uint32_t act = bf_mul2(pack_bf(ga * ra, gb * rb2), uu);
    sts32(OFF_ACT + td * 4, act);
  } else bar_arrive(9, 512);
  uint4* dst = &p.s->X[c * DM * 2 + (warp - 7) * 64 + tt * 8 + gg];
  asm volatile("" : "+l"(dst));
  bar_sync(8, 512);
  tpub = clock();
  if (warp >= 7) {
    uint32_t b0, b1, b2, b3, b4;
    ldsm4t(OFF_ACT + ln * 16, b0, b1, b2, b3);
    asm volatile("ldmatrix.sync.aligned.m8n8.x1.trans.shared.b16 {%0}, [%1];" : "=r"(b4) : "r"(OFF_ACT + 512 + ln * 16) : "memory");
    float y[4][4];
#pragma unroll
    for (int j = 0; j < 4; j++) {
      y[j][0] = y[j][1] = y[j][2] = y[j][3] = 0.f;
      mma_bf16(y[j], wd[j][0], wd[j][1], wd[j][2], wd[j][3], b0, b1);
    }
#pragma unroll
    for (int j = 0; j < 4; j++) mma_bf16(y[j], wd[4 + j][0], wd[4 + j][1], wd[4 + j][2], wd[4 + j][3], b2, b3);
    if (!five) {
#pragma unroll
      for (int j = 0; j < 4; j++) mma_bf16_k8(y[j], wd[8 + (j >> 1)][2 * (j & 1)], wd[8 + (j >> 1)][2 * (j & 1) + 1], b4);
    }
    str128(dst, (pack_bf(y[0][0], y[0][1]) & ~1u) | 0x10000u, pack_bf(y[0][2], y[0][3]), pack_bf(y[1][0], y[1][1]), pack_bf(y[1][2], y[1][3]));
    str128(dst + 32, (pack_bf(y[2][0], y[2][1]) & ~1u) | 0x10000u, pack_bf(y[2][2], y[2][3]), pack_bf(y[3][0], y[3][1]), pack_bf(y[3][2], y[3][3]));
  }
  TS(10);

  if (c < 72) {
    const uint4* src = &p.s->X[(warp * 4 + tt) * (DM * 2) + c * 8 + gg];
    const int slot = (c & 3) * 2 + (ln >> 4), dw = (c >> 2) * 16 + (ln & 15);
    uint32_t hv = 0, kv = 0, res = 0, rs2 = 0;
    uint32_t* o = p.out;
    if (warp == 0) {
      hv = ~0u;
      SPIN_WHILE(max(hv, kv) == ~0u, hv = ldr32((const uint32_t*)p.s->HS + 2304 + slot * 288 + dw); kv = ldr32(&p.s->HS[1152 + slot]));
      const float r = bf_hi(kv ^ (((int)~kv >> 31) | 0x80000000u));
      float rs;
      asm("rcp.approx.ftz.f32 %0, %1;" : "=f"(rs) : "f"(1.f + ex2(r * -1.4426950408889634f)));
      rs2 = keep(pack_bf(rs, rs));
      res = lds32(OFF_XS + slot * 1168 + dw * 4);
      o += (2047 - (int)(kv & 2047u)) * 288 + dw;
      asm volatile("" : "+l"(o));
    }
    const uint32_t sel = (gg & 1) ? 0x3F800000u : 0x00003F80u;
    const uint32_t q0 = keep((gg >> 1) == 0 ? sel : 0u), q1 = keep((gg >> 1) == 1 ? sel : 0u), q2 = keep((gg >> 1) == 2 ? sel : 0u), q3 = keep((gg >> 1) == 3 ? sel : 0u);
    const uint32_t fa = keep(OFF_RED + warp * 8 + ((gg & 1) * 16 + (gg >> 1) * 4 + tt) * 144), fb = keep(OFF_RED + ln * 144);
    uint4 a0 = make_uint4(0, 0, 0, 0), a1 = a0;
    while ((int)(clock() - tpub) < X_PD) {}
    SPIN_WHILE(!(a0.x & a1.x & 0x10000u), if (!(a0.x & 0x10000u)) a0 = ldr128(src); if (!(a1.x & 0x10000u)) a1 = ldr128(src + 64 * DM * 2));
    float d[4] = {0.f, 0.f, 0.f, 0.f}, e[4] = {0.f, 0.f, 0.f, 0.f}, d2[4] = {0.f, 0.f, 0.f, 0.f}, e2[4] = {0.f, 0.f, 0.f, 0.f};
    mma_bf16(d, q0, q2, q1, q3, a0.x, a0.y); mma_bf16(e, q0, q2, q1, q3, a0.z, a0.w);
    mma_bf16(d2, q0, q2, q1, q3, a1.x, a1.y); mma_bf16(e2, q0, q2, q1, q3, a1.z, a1.w);
    sts64(fa, __float_as_uint(d[0] + e[2] + d2[0] + e2[2]), __float_as_uint(d[1] + e[3] + d2[1] + e2[3]));
    TS(11);
    if (warp == 0) {
      bar_sync(0, 512);
      float2 s[16];
#pragma unroll
      for (int i = 0; i < 16; i += 2) { const uint4 q = lds128(fb + i * 8); s[i] = make_float2(__uint_as_float(q.x), __uint_as_float(q.y)); s[i + 1] = make_float2(__uint_as_float(q.z), __uint_as_float(q.w)); }
#pragma unroll
      for (int k = 1; k < 16; k *= 2)
#pragma unroll
        for (int i = 0; i < 16; i += 2 * k) { s[i].x += s[i + k].x; s[i].y += s[i + k].y; }
      asm volatile("st.global.b32 [%0], %1;" :: "l"(o), "r"(bf_add2(hv, bf_add2(res, bf_mul2(pack_bf(s[0].x, s[0].y), rs2)))) : "memory");
    } else bar_arrive(0, 512);
  }
  TS(12);
  TS_DUMP();
}

typedef CUresult (*EncodeFn)(CUtensorMap*, CUtensorMapDataType, cuuint32_t, void*, const cuuint64_t*, const cuuint64_t*, const cuuint32_t*,
                             const cuuint32_t*, CUtensorMapInterleave, CUtensorMapSwizzle, CUtensorMapL2promotion, CUtensorMapFloatOOBfill);

}

extern "C" void kernel_launch(void* const* d_in, const int* in_sizes, int n_in, void* d_out, int out_size) {
  (void)in_sizes; (void)n_in; (void)out_size;
  static EncodeFn enc = nullptr;
  static Scratch* scratch = nullptr;
  if (!enc) {
    void* fn = nullptr;
    cudaDriverEntryPointQueryResult qr;
    cudaGetDriverEntryPoint("cuTensorMapEncodeTiled", &fn, cudaEnableDefault, &qr);
    enc = (EncodeFn)fn;
    cudaGetSymbolAddress((void**)&scratch, g_S);
    cudaFuncSetAttribute(fused_kernel<false>, cudaFuncAttributeMaxDynamicSharedMemorySize, SMEM_BYTES);
    cudaFuncSetAttribute(fused_kernel<true>, cudaFuncAttributeMaxDynamicSharedMemorySize, SMEM_BYTES);
  }
  TMaps tm;
  for (int i = 0; i < 6; i++) {
    const bool dn = i % 3 == 2;
    const cuuint32_t w = i < 3 ? 40 : 32;
    cuuint64_t gd[3] = {(cuuint64_t)(dn ? 64 : FF), (cuuint64_t)(dn ? FF : DM), 9};
    cuuint64_t gs[2] = {(cuuint64_t)(dn ? DM * 2 : FF * 2), 128};
    cuuint32_t bx[3] = {dn ? 64 : w, dn ? w : 96, i < 3 ? 2u : 3u};
    cuuint32_t es[3] = {1, 1, 1};
    enc(&tm.m[i], CU_TENSOR_MAP_DATA_TYPE_BFLOAT16, dn ? 3 : 2, d_in[11 + i % 3], gd, gs, bx, es, CU_TENSOR_MAP_INTERLEAVE_NONE,
        dn ? CU_TENSOR_MAP_SWIZZLE_128B : i < 3 ? CU_TENSOR_MAP_SWIZZLE_NONE : CU_TENSOR_MAP_SWIZZLE_64B,
        (CUtensorMapL2promotion)X_PROMO, CU_TENSOR_MAP_FLOAT_OOB_FILL_NONE);
  }
  for (int i = 6; i < 10; i++) {
    cuuint64_t gd[3] = {i < 8 ? 32u : 16u, i < 8 ? DM / 2u : DM, NCTA};
    cuuint64_t gs[2] = {i < 8 ? 64u : 32u, DM * 32};
    cuuint32_t bx[3] = {32, 1, (i & 1) ? 128u : 136u};
    cuuint32_t es[3] = {1, 1, 1};
    enc(&tm.m[i], CU_TENSOR_MAP_DATA_TYPE_FLOAT16, 3, scratch->X, gd, gs, bx, es, CU_TENSOR_MAP_INTERLEAVE_NONE, CU_TENSOR_MAP_SWIZZLE_64B,
        CU_TENSOR_MAP_L2_PROMOTION_NONE, CU_TENSOR_MAP_FLOAT_OOB_FILL_NONE);
  }
  Params p;
  p.x = (const unsigned char*)d_in[0];
  bool far = false;
  for (int i = 0; i < 7; i++) {
    p.far[i] = (const unsigned char*)d_in[1 + i];
    const long long d = (long long)((intptr_t)d_in[1 + i] - (intptr_t)d_in[0]);
    p.off[i] = (int)(d / 16);
    if ((long long)p.off[i] * 16 != d || p.off[i] > (1 << 30)) far = true;
  }
  p.dskip = (const uint16_t*)d_in[8];
  p.w_r = (const uint32_t*)d_in[10];
  for (int f = 0; f < 2; f++) {
    static const int kind[17] = {0, 0, 0, 0, 2, 2, 0, 0, 1, 1, 1, 1, 1, 1, 2, 2, 2};
    static const int idx[2][17] = {{2, 3, 4, 5, 6, 8, 0, 1, 0, 1, 2, 3, 4, 5, 0, 2, 4}, {2, 3, 4, 5, 0, -1, 0, 1, 0, 1, 2, 3, 4, 5, 3, -1, 6}};
    static const int blk[2][17] = {{-1, -1, -1, -1, 0, -1, 4, -1, 1, -1, 2, -1, 3, -1, 16, -1, -1}, {-1, -1, -1, -1, 1, -1, 4, -1, -1, -1, 2, -1, 3, -1, 16, -1, -1}};
    const int pitch = f ? 64 : 80;
    for (int u = 0; u < 17; u++) {
      const int s = idx[f][u];
      const uint32_t dst = kind[u] == 0 ? OFF_G + s * 96 * pitch : kind[u] == 2 ? down_box(s, f) : OFF_W + W_BYTES + (s >> 1) * W_BYTES + (s & 1) * 96 * pitch;
      const uint32_t mb = u >= 14 ? (u >= X_HU ? MB_H - OFF_MISC : 0) : blk[f][u] >= 0 ? MB_KF - OFF_MISC + blk[f][u] * 8 : 0;
      p.sched[f][u] = s < 0 ? 3u : kind[u] | s << 2 | mb << 6 | dst << 14;
    }
  }
  p.out = (uint32_t*)d_out;
  p.off[7] = 0;
  p.ts = nullptr;
  p.s = scratch;
  if (far) { fused_kernel<true><<<NCTA, NT, SMEM_BYTES, cudaStreamPerThread>>>(p, tm); return; }
  fused_kernel<false><<<NCTA, NT, SMEM_BYTES, cudaStreamPerThread>>>(p, tm);
}
```

```cpp
#include <cuda_runtime.h>
#include <cuda.h>
#include <cuda_bf16.h>
#include <cuda_fp16.h>
#include <stdint.h>
#include <stddef.h>

namespace {

constexpr int NCTA = 128;
constexpr int NT = 640;
constexpr int DM = 576;
constexpr int FF = 4608;
constexpr int SPIN_MAX = 1 << 20;

struct Scratch {
  uint4 X[NCTA * DM * 2];
  uint4 KX[64 * 128];
  uint4 HS[1152 + 8];
  uint4 R[256];
  uint4 SC[256];
  uint32_t FLAG[NCTA * 8];
};
__device__ Scratch g_S;

#define CLKS(i)
#define TS(i)
#define TSX(i)
#define TS_DUMP()

constexpr int SB = 1024;
constexpr int BOX = 15360;
constexpr int OFF_G = SB;
constexpr int OFF_W = OFF_G + 3 * BOX;
constexpr int W_KT = 26624;
constexpr int W_QT = W_KT + 64 + 2048 + 80;
constexpr int W_L3 = W_KT + 4352;
constexpr int W_CW = W_L3 + 4160;
constexpr int W_MISC = W_CW + 640;
constexpr int W_BYTES = 35840;
constexpr int TILE = 10240;
constexpr int OFF_T = OFF_W + 4 * W_BYTES;
constexpr int ALT = TILE - W_KT;
static_assert(W_MISC + 32 <= W_BYTES && OFF_W % 1024 == 0 && W_BYTES % 1024 == 0 && W_BYTES + ALT <= 20480, "wg block");
constexpr int YT_PITCH = 1184;
constexpr int OFF_YT = OFF_T + 2 * TILE;
constexpr int OFF_WR = OFF_YT + 16 * YT_PITCH + 64;
constexpr int OFF_MISC = OFF_WR + 2304;
constexpr int SMEM_BYTES = OFF_MISC + 1024 - SB;
static_assert(OFF_YT % 16 == 0 && OFF_MISC % 16 == 0, "align");
static_assert(SMEM_BYTES <= 232448, "smem");
constexpr int MB_GU = OFF_MISC;
constexpr int MB_D = OFF_MISC + 8;
constexpr int MB_KF = OFF_MISC + 16;
constexpr int MB_GF = OFF_MISC + 48;
constexpr int MB_SC = OFF_MISC + 56;
constexpr int MB_UL = OFF_MISC + 64;
constexpr int MB_REL = OFF_MISC + 104;
constexpr int MB_GO = OFF_MISC + 112;
constexpr int MB_H = MB_KF + 128;
constexpr int MISC_EPOCH = OFF_MISC + 152;
constexpr int MISC_SW = OFF_MISC + 156;
constexpr int MISC_RT = OFF_MISC + 160;
constexpr int MISC_T0 = OFF_MISC + 296;
constexpr int MISC_EM = OFF_MISC + 288;
constexpr int OFF_PART = OFF_W + 20480;
constexpr int OFF_RK = OFF_PART + 3840;
constexpr int MISC_LN1 = OFF_MISC + 192;
constexpr int OFF_XS = OFF_T;
constexpr int OFF_RED = OFF_T + TILE;
constexpr int OFF_FIN = OFF_W + 3 * W_BYTES + W_KT;
constexpr int OFF_ACT = OFF_FIN + 4096;
constexpr int MISC_CNT = OFF_ACT + 1024;

__device__ __forceinline__ uint32_t smem_u32(const void* p) { return (uint32_t)__cvta_generic_to_shared(p); }
__device__ __forceinline__ uint32_t lds32(uint32_t a) { uint32_t v; asm volatile("ld.shared.b32 %0, [%1];" : "=r"(v) : "r"(a) : "memory"); return v; }
__device__ __forceinline__ uint32_t lds16(uint32_t a) { uint16_t v; asm volatile("ld.shared.u16 %0, [%1];" : "=h"(v) : "r"(a) : "memory"); return v; }
__device__ __forceinline__ uint2 lds64(uint32_t a) { uint2 v; asm volatile("ld.shared.v2.b32 {%0,%1}, [%2];" : "=r"(v.x), "=r"(v.y) : "r"(a) : "memory"); return v; }
__device__ __forceinline__ uint4 lds128(uint32_t a) { uint4 v; asm volatile("ld.shared.v4.b32 {%0,%1,%2,%3}, [%4];" : "=r"(v.x), "=r"(v.y), "=r"(v.z), "=r"(v.w) : "r"(a) : "memory"); return v; }
__device__ __forceinline__ void sts16(uint32_t a, uint32_t v) { asm volatile("st.shared.u16 [%0], %1;" :: "r"(a), "h"((uint16_t)v) : "memory"); }
__device__ __forceinline__ void sts32(uint32_t a, uint32_t v) { asm volatile("st.shared.b32 [%0], %1;" :: "r"(a), "r"(v) : "memory"); }
__device__ __forceinline__ void sts64(uint32_t a, uint32_t x, uint32_t y) { asm volatile("st.shared.v2.b32 [%0], {%1,%2};" :: "r"(a), "r"(x), "r"(y) : "memory"); }
__device__ __forceinline__ void sts128(uint32_t a, uint32_t x, uint32_t y, uint32_t z, uint32_t w) { asm volatile("st.shared.v4.b32 [%0], {%1,%2,%3,%4};" :: "r"(a), "r"(x), "r"(y), "r"(z), "r"(w) : "memory"); }
__device__ __forceinline__ void ldsm4(uint32_t a, uint32_t& r0, uint32_t& r1, uint32_t& r2, uint32_t& r3) {
  asm volatile("ldmatrix.sync.aligned.m8n8.x4.shared.b16 {%0,%1,%2,%3}, [%4];" : "=r"(r0), "=r"(r1), "=r"(r2), "=r"(r3) : "r"(a) : "memory");
}
__device__ __forceinline__ void ldsm4t(uint32_t a, uint32_t& r0, uint32_t& r1, uint32_t& r2, uint32_t& r3) {
  asm volatile("ldmatrix.sync.aligned.m8n8.x4.trans.shared.b16 {%0,%1,%2,%3}, [%4];" : "=r"(r0), "=r"(r1), "=r"(r2), "=r"(r3) : "r"(a) : "memory");
}
__device__ __forceinline__ void stsm4t(uint32_t a, uint32_t r0, uint32_t r1, uint32_t r2, uint32_t r3) {
  asm volatile("stmatrix.sync.aligned.m8n8.x4.trans.shared.b16 [%0], {%1,%2,%3,%4};" :: "r"(a), "r"(r0), "r"(r1), "r"(r2), "r"(r3) : "memory");
}
__device__ __forceinline__ uint4 ldr128(const void* p) {
  unsigned long long lo, hi;
  asm volatile("{ .reg .b128 t; ld.relaxed.gpu.global.b128 t, [%2]; mov.b128 {%0, %1}, t; }" : "=l"(lo), "=l"(hi) : "l"(p) : "memory");
  return make_uint4((uint32_t)lo, (uint32_t)(lo >> 32), (uint32_t)hi, (uint32_t)(hi >> 32));
}
__device__ __forceinline__ void str128(void* p, uint32_t x, uint32_t y, uint32_t z, uint32_t w) {
  asm volatile("{ .reg .b128 t; .reg .b64 lo, hi; mov.b64 lo, {%1,%2}; mov.b64 hi, {%3,%4}; mov.b128 t, {lo, hi}; st.relaxed.gpu.global.b128 [%0], t; }"
               :: "l"(p), "r"(x), "r"(y), "r"(z), "r"(w) : "memory");
}
__device__ __forceinline__ uint32_t ldr32(const void* p) { uint32_t v; asm volatile("ld.relaxed.gpu.global.b32 %0, [%1];" : "=r"(v) : "l"(p) : "memory"); return v; }
__device__ __forceinline__ void str32(void* p, uint32_t v) { asm volatile("st.relaxed.gpu.global.b32 [%0], %1;" :: "l"(p), "r"(v) : "memory"); }
__device__ __forceinline__ void str16(void* p, uint32_t v) { asm volatile("st.relaxed.gpu.global.u16 [%0], %1;" :: "l"(p), "h"((uint16_t)v) : "memory"); }
__device__ __forceinline__ void bar_sync(int id, int n) { asm volatile("bar.sync %0, %1;" :: "r"(id), "r"(n) : "memory"); }
__device__ __forceinline__ void bar_arrive(int id, int n) { asm volatile("bar.arrive %0, %1;" :: "r"(id), "r"(n) : "memory"); }

__device__ __forceinline__ float bf_lo(uint32_t w) { return __uint_as_float(w << 16); }
__device__ __forceinline__ float bf_hi(uint32_t w) { return __uint_as_float(w & 0xFFFF0000u); }
__device__ __forceinline__ uint32_t pack_bf(float lo, float hi) { uint32_t r; asm("cvt.rn.bf16x2.f32 %0, %1, %2;" : "=r"(r) : "f"(hi), "f"(lo)); return r; }
__device__ __forceinline__ uint32_t pack_h(float lo, float hi) { uint32_t r; asm("cvt.rn.f16x2.f32 %0, %1, %2;" : "=r"(r) : "f"(hi), "f"(lo)); return r; }
__device__ __forceinline__ float bfr(float x) { return bf_lo(pack_bf(x, 0.f)); }
__device__ __forceinline__ uint32_t bf_sub2(uint32_t a, uint32_t b) { __nv_bfloat162 r = __hsub2(*(__nv_bfloat162*)&a, *(__nv_bfloat162*)&b); return *(uint32_t*)&r; }
__device__ __forceinline__ uint32_t bf_add2(uint32_t a, uint32_t b) { __nv_bfloat162 r = __hadd2(*(__nv_bfloat162*)&a, *(__nv_bfloat162*)&b); return *(uint32_t*)&r; }
__device__ __forceinline__ uint32_t bf_mul2(uint32_t a, uint32_t b) { __nv_bfloat162 r = __hmul2(*(__nv_bfloat162*)&a, *(__nv_bfloat162*)&b); return *(uint32_t*)&r; }
__device__ __forceinline__ float2 h2f(uint32_t w) { return __half22float2(*(__half2*)&w); }
__device__ __forceinline__ float ex2(float x) { float r; asm("ex2.approx.ftz.f32 %0, %1;" : "=f"(r) : "f"(x)); return r; }
__device__ __forceinline__ float warp_sum(float v) {
#pragma unroll
  for (int o = 16; o > 0; o >>= 1) v += __shfl_xor_sync(0xffffffffu, v, o);
  return v;
}
__device__ __forceinline__ void mma_bf16(float* d, uint32_t a0, uint32_t a1, uint32_t a2, uint32_t a3, uint32_t b0, uint32_t b1) {
  asm volatile("mma.sync.aligned.m16n8k16.row.col.f32.bf16.bf16.f32 {%0,%1,%2,%3}, {%4,%5,%6,%7}, {%8,%9}, {%0,%1,%2,%3};"
               : "+f"(d[0]), "+f"(d[1]), "+f"(d[2]), "+f"(d[3]) : "r"(a0), "r"(a1), "r"(a2), "r"(a3), "r"(b0), "r"(b1));
}
__device__ __forceinline__ void mma_bf16_k8(float* d, uint32_t a0, uint32_t a1, uint32_t b0) {
  asm volatile("mma.sync.aligned.m16n8k8.row.col.f32.bf16.bf16.f32 {%0,%1,%2,%3}, {%4,%5}, {%6}, {%0,%1,%2,%3};"
               : "+f"(d[0]), "+f"(d[1]), "+f"(d[2]), "+f"(d[3]) : "r"(a0), "r"(a1), "r"(b0));
}

__device__ __forceinline__ void wg_fence() { asm volatile("wgmma.fence.sync.aligned;" ::: "memory"); }
__device__ __forceinline__ void wg_commit() { asm volatile("wgmma.commit_group.sync.aligned;" ::: "memory"); }
template <int N> __device__ __forceinline__ void wg_wait() { asm volatile("wgmma.wait_group.sync.aligned %0;" :: "n"(N) : "memory"); }
template <int TB> __device__ __forceinline__ void wgmma32(float* d, const uint32_t* a, uint32_t dlo, uint32_t dhi) {
  asm volatile("{ .reg .b64 dd; mov.b64 dd, {%20, %21}; wgmma.mma_async.sync.aligned.m64n32k16.f32.f16.f16 "
               "{%0,%1,%2,%3,%4,%5,%6,%7,%8,%9,%10,%11,%12,%13,%14,%15}, {%16,%17,%18,%19}, dd, 1, 1, 1, %22; }"
               : "+f"(d[0]), "+f"(d[1]), "+f"(d[2]), "+f"(d[3]), "+f"(d[4]), "+f"(d[5]), "+f"(d[6]), "+f"(d[7]), "+f"(d[8]), "+f"(d[9]), "+f"(d[10]), "+f"(d[11]), "+f"(d[12]), "+f"(d[13]), "+f"(d[14]), "+f"(d[15])
               : "r"(a[0]), "r"(a[1]), "r"(a[2]), "r"(a[3]), "r"(dlo), "r"(dhi), "n"(TB));
}
template <int TB> __device__ __forceinline__ void wgmma64(float* d, const uint32_t* a, uint32_t dlo, uint32_t dhi) {
  asm volatile("{ .reg .b64 dd; mov.b64 dd, {%36, %37}; wgmma.mma_async.sync.aligned.m64n64k16.f32.f16.f16 "
               "{%0,%1,%2,%3,%4,%5,%6,%7,%8,%9,%10,%11,%12,%13,%14,%15,%16,%17,%18,%19,%20,%21,%22,%23,%24,%25,%26,%27,%28,%29,%30,%31}, {%32,%33,%34,%35}, dd, 1, 1, 1, %38; }"
               : "+f"(d[0]), "+f"(d[1]), "+f"(d[2]), "+f"(d[3]), "+f"(d[4]), "+f"(d[5]), "+f"(d[6]), "+f"(d[7]), "+f"(d[8]), "+f"(d[9]), "+f"(d[10]), "+f"(d[11]), "+f"(d[12]), "+f"(d[13]), "+f"(d[14]), "+f"(d[15]), "+f"(d[16]), "+f"(d[17]), "+f"(d[18]), "+f"(d[19]), "+f"(d[20]), "+f"(d[21]), "+f"(d[22]), "+f"(d[23]), "+f"(d[24]), "+f"(d[25]), "+f"(d[26]), "+f"(d[27]), "+f"(d[28]), "+f"(d[29]), "+f"(d[30]), "+f"(d[31])
               : "r"(a[0]), "r"(a[1]), "r"(a[2]), "r"(a[3]), "r"(dlo), "r"(dhi), "n"(TB));
}
template <int TB> __device__ __forceinline__ void wgmma64_init(float* d, const uint32_t* a, uint32_t dlo, uint32_t dhi) {
  asm volatile("{ .reg .b64 dd; mov.b64 dd, {%36, %37}; wgmma.mma_async.sync.aligned.m64n64k16.f32.f16.f16 "
               "{%0,%1,%2,%3,%4,%5,%6,%7,%8,%9,%10,%11,%12,%13,%14,%15,%16,%17,%18,%19,%20,%21,%22,%23,%24,%25,%26,%27,%28,%29,%30,%31}, {%32,%33,%34,%35}, dd, 0, 1, 1, %38; }"
               : "=f"(d[0]), "=f"(d[1]), "=f"(d[2]), "=f"(d[3]), "=f"(d[4]), "=f"(d[5]), "=f"(d[6]), "=f"(d[7]), "=f"(d[8]), "=f"(d[9]), "=f"(d[10]), "=f"(d[11]), "=f"(d[12]), "=f"(d[13]), "=f"(d[14]), "=f"(d[15]), "=f"(d[16]), "=f"(d[17]), "=f"(d[18]), "=f"(d[19]), "=f"(d[20]), "=f"(d[21]), "=f"(d[22]), "=f"(d[23]), "=f"(d[24]), "=f"(d[25]), "=f"(d[26]), "=f"(d[27]), "=f"(d[28]), "=f"(d[29]), "=f"(d[30]), "=f"(d[31])
               : "r"(a[0]), "r"(a[1]), "r"(a[2]), "r"(a[3]), "r"(dlo), "r"(dhi), "n"(TB));
}
template <int TB> __device__ __forceinline__ void wgmma32_init(float* d, const uint32_t* a, uint32_t dlo, uint32_t dhi) {
  asm volatile("{ .reg .b64 dd; mov.b64 dd, {%20, %21}; wgmma.mma_async.sync.aligned.m64n32k16.f32.f16.f16 "
               "{%0,%1,%2,%3,%4,%5,%6,%7,%8,%9,%10,%11,%12,%13,%14,%15}, {%16,%17,%18,%19}, dd, 0, 1, 1, %22; }"
               : "=f"(d[0]), "=f"(d[1]), "=f"(d[2]), "=f"(d[3]), "=f"(d[4]), "=f"(d[5]), "=f"(d[6]), "=f"(d[7]), "=f"(d[8]), "=f"(d[9]), "=f"(d[10]), "=f"(d[11]), "=f"(d[12]), "=f"(d[13]), "=f"(d[14]), "=f"(d[15])
               : "r"(a[0]), "r"(a[1]), "r"(a[2]), "r"(a[3]), "r"(dlo), "r"(dhi), "n"(TB));
}
__device__ __forceinline__ void wgmma64h(uint32_t* d, uint32_t a0, uint32_t a1, uint32_t a2, uint32_t a3, uint32_t dlo, uint32_t dhi) {
  asm volatile("{ .reg .b64 dd; mov.b64 dd, {%20, %21}; wgmma.mma_async.sync.aligned.m64n64k16.f16.f16.f16 "
               "{%0,%1,%2,%3,%4,%5,%6,%7,%8,%9,%10,%11,%12,%13,%14,%15}, {%16,%17,%18,%19}, dd, 1, 1, 1, 0; }"
               : "+r"(d[0]), "+r"(d[1]), "+r"(d[2]), "+r"(d[3]), "+r"(d[4]), "+r"(d[5]), "+r"(d[6]), "+r"(d[7]), "+r"(d[8]), "+r"(d[9]), "+r"(d[10]), "+r"(d[11]), "+r"(d[12]), "+r"(d[13]), "+r"(d[14]), "+r"(d[15])
               : "r"(a0), "r"(a1), "r"(a2), "r"(a3), "r"(dlo), "r"(dhi));
}
__device__ __forceinline__ void wgmma64h_init(uint32_t* d, uint32_t a0, uint32_t a1, uint32_t a2, uint32_t a3, uint32_t dlo, uint32_t dhi) {
  asm volatile("{ .reg .b64 dd; mov.b64 dd, {%20, %21}; wgmma.mma_async.sync.aligned.m64n64k16.f16.f16.f16 "
               "{%0,%1,%2,%3,%4,%5,%6,%7,%8,%9,%10,%11,%12,%13,%14,%15}, {%16,%17,%18,%19}, dd, 0, 1, 1, 0; }"
               : "=r"(d[0]), "=r"(d[1]), "=r"(d[2]), "=r"(d[3]), "=r"(d[4]), "=r"(d[5]), "=r"(d[6]), "=r"(d[7]), "=r"(d[8]), "=r"(d[9]), "=r"(d[10]), "=r"(d[11]), "=r"(d[12]), "=r"(d[13]), "=r"(d[14]), "=r"(d[15])
               : "r"(a0), "r"(a1), "r"(a2), "r"(a3), "r"(dlo), "r"(dhi));
}
__device__ __forceinline__ void wgmma40_ss(float* d, uint32_t alo, uint32_t blo, uint32_t hi) {
  asm volatile("{ .reg .b64 da, db; mov.b64 da, {%20, %22}; mov.b64 db, {%21, %22}; "
               "wgmma.mma_async.sync.aligned.m64n40k16.f32.f16.f16 {%0,%1,%2,%3,%4,%5,%6,%7,%8,%9,%10,%11,%12,%13,%14,%15,%16,%17,%18,%19}, da, db, 1, 1, 1, 1, 1; }"
               : "+f"(d[0]), "+f"(d[1]), "+f"(d[2]), "+f"(d[3]), "+f"(d[4]), "+f"(d[5]), "+f"(d[6]), "+f"(d[7]), "+f"(d[8]), "+f"(d[9]), "+f"(d[10]), "+f"(d[11]), "+f"(d[12]), "+f"(d[13]), "+f"(d[14]), "+f"(d[15]), "+f"(d[16]), "+f"(d[17]), "+f"(d[18]), "+f"(d[19])
               : "r"(alo), "r"(blo), "r"(hi));
}
__device__ __forceinline__ void wgmma40_ss_init(float* d, uint32_t alo, uint32_t blo, uint32_t hi) {
  asm volatile("{ .reg .b64 da, db; mov.b64 da, {%20, %22}; mov.b64 db, {%21, %22}; "
               "wgmma.mma_async.sync.aligned.m64n40k16.f32.f16.f16 {%0,%1,%2,%3,%4,%5,%6,%7,%8,%9,%10,%11,%12,%13,%14,%15,%16,%17,%18,%19}, da, db, 0, 1, 1, 1, 1; }"
               : "=f"(d[0]), "=f"(d[1]), "=f"(d[2]), "=f"(d[3]), "=f"(d[4]), "=f"(d[5]), "=f"(d[6]), "=f"(d[7]), "=f"(d[8]), "=f"(d[9]), "=f"(d[10]), "=f"(d[11]), "=f"(d[12]), "=f"(d[13]), "=f"(d[14]), "=f"(d[15]), "=f"(d[16]), "=f"(d[17]), "=f"(d[18]), "=f"(d[19])
               : "r"(alo), "r"(blo), "r"(hi));
}
__device__ __forceinline__ void tma_box(uint32_t dst, const CUtensorMap* tm, uint32_t mb, int x, int y) {
  asm volatile("cp.async.bulk.tensor.2d.shared::cluster.global.mbarrier::complete_tx::bytes [%0], [%1, {%3, %4}], [%2];"
               :: "r"(dst), "l"(tm), "r"(mb), "r"(x), "r"(y) : "memory");
}
__device__ __forceinline__ uint32_t uni(uint32_t v) {
  uint32_t r; asm volatile("shfl.sync.idx.b32 %0, %1, 0, 0x1f, 0xffffffff;" : "=r"(r) : "r"(v)); return r;
}
__device__ __forceinline__ uint32_t pin(uint32_t v) {
  uint32_t r; asm volatile("shfl.sync.bfly.b32 %0, %1, 0, 0x1f, 0xffffffff;" : "=r"(r) : "r"(v)); return r;
}

struct Params {
  const unsigned char* x;
  Scratch* s;
  int off[8];
  uint32_t* out;
  const uint16_t* dskip;
  const uint32_t* w_r;
  long long* ts;
  const unsigned char* far[7];
  uint32_t sched[2][17];
};
__device__ __forceinline__ uint32_t ldnc32(const void* p) { uint32_t v; asm volatile("ld.global.nc.b32 %0, [%1];" : "=r"(v) : "l"(p)); return v; }
__device__ __forceinline__ uint32_t ldnc16(const void* p) { uint16_t v; asm volatile("ld.global.nc.u16 %0, [%1];" : "=h"(v) : "l"(p)); return v; }
__device__ __forceinline__ void mbar_wait(uint32_t mb, uint32_t ph = 0) {
#pragma unroll 1
  for (int it = 0; it < SPIN_MAX; it++) {
    uint32_t ok;
    asm volatile("{ .reg .pred q; mbarrier.try_wait.parity.shared::cta.b64 q, [%1], %2; selp.u32 %0, 1, 0, q; }" : "=r"(ok) : "r"(mb), "r"(ph) : "memory");
    if (ok) break;
  }
}
__device__ __forceinline__ void mbar_arrive(uint32_t mb) { asm volatile("mbarrier.arrive.shared::cta.b64 _, [%0];" :: "r"(mb) : "memory"); }
__device__ __forceinline__ void fence_async() { asm volatile("fence.proxy.async.shared::cta;" ::: "memory"); }
#define SPIN_WHILE(cond, body) _Pragma("unroll 1") for (int _it = 0; _it < SPIN_MAX && __any_sync(0xffffffffu, (cond)); _it++) { body; }

struct LnC { uint32_t m2, rh2, rl2; };
__device__ __forceinline__ LnC ln_consts(float s, float q, float& r) {
  const float mean = s * (1.f / DM);
  const float var = fmaxf(fmaf(-mean, mean, q * (1.f / DM)), 0.f);
  float sd;
  asm("sqrt.approx.ftz.f32 %0, %1;" : "=f"(sd) : "f"(bfr(bfr(var) + 1e-5f)));
  asm("rcp.approx.ftz.f32 %0, %1;" : "=f"(r) : "f"(bfr(sd)));
  LnC c;
  c.m2 = pack_bf(mean, mean);
  c.rh2 = pack_bf(r, r);
  const float rl = r - bf_lo(c.rh2);
  c.rl2 = pack_bf(rl, rl);
  return c;
}
__device__ __forceinline__ uint32_t bf_fma2(uint32_t a, uint32_t b, uint32_t c) {
  __nv_bfloat162 r = __hfma2(*(const __nv_bfloat162*)&a, *(const __nv_bfloat162*)&b, *(const __nv_bfloat162*)&c);
  return *(uint32_t*)&r;
}
__device__ __forceinline__ uint32_t ln_apply(uint32_t w, uint32_t m2, uint32_t rh2, uint32_t rl2) {
  const uint32_t d = bf_sub2(w, m2);
  return bf_fma2(d, rh2, bf_mul2(d, rl2));
}

__device__ __forceinline__ float2 cis(float mag_log2, float rev) {
  const float m = ex2(mag_log2), ang = rev * 6.283185307179586f;
  return make_float2(m * __cosf(ang), m * __sinf(ang));
}
__device__ __forceinline__ float2 csq(float2 a) { return make_float2(fmaf(a.x, a.x, -a.y * a.y), (a.x + a.x) * a.y); }
__device__ __forceinline__ float2 cmul(float2 a, float2 b) { return make_float2(fmaf(a.x, b.x, -a.y * b.y), fmaf(a.x, b.y, a.y * b.x)); }
__device__ __forceinline__ void pmul(uint32_t xr, uint32_t xi, uint32_t w, uint32_t& yr, uint32_t& yi) {
  const __half2 XR = *(__half2*)&xr, XI = *(__half2*)&xi, W = *(__half2*)&w;
  const __half2 a = __hfma2(__hneg2(XI), __high2half2(W), __hmul2(XR, __low2half2(W)));
  const __half2 b = __hfma2(XI, __low2half2(W), __hmul2(XR, __high2half2(W)));
  yr = *(const uint32_t*)&a; yi = *(const uint32_t*)&b;
}
__device__ __forceinline__ uint32_t pk(float2 a) { return pack_h(a.x, a.y); }

struct KgState { float2 c0, z8; float kl; uint32_t w64, w128, w192; };
__device__ __forceinline__ void kgen_tables_n(const uint32_t (&raw)[7], uint32_t scr, int wt, KgState& k) {
  const uint32_t dst = scr + 16384 + wt * 16;
  const float dt = bfr(ex2(bf_lo(raw[6]) * 1.4426950408889634f));
  const float th = dt * bf_lo(raw[1]);
  const float br = dt * bf_lo(raw[2]), bi = dt * bf_lo(raw[3]);
  const float Cr = bf_lo(raw[4]), Ci = bf_lo(raw[5]);
  k.c0 = make_float2(fmaf(Cr, br, -Ci * bi), fmaf(Cr, bi, Ci * br));
  const uint32_t mx = __reduce_max_sync(0xffffffffu, __float_as_uint(fmaxf(fabsf(k.c0.x), fabsf(k.c0.y))));
  const float a2 = dt * bf_lo(raw[0]) * 1.4426950408889634f;
  const float rh = th * 0.15915494309189535f;
  const float rl = fmaf(th, (float)(0.15915494309189535 - (double)0.15915494309189535f), fmaf(th, 0.15915494309189535f, -rh));
  const float rf = rh - rintf(rh);
  const float2 z1 = cis(a2, rf + rl);
  const float p64 = rf * 64.f;
  const float2 z64 = cis(a2 * 64.f, fmaf(64.f, rl, p64 - rintf(p64)));
  const float2 z2 = csq(z1), z128 = csq(z64), z3 = cmul(z2, z1), z4 = csq(z2), z256 = csq(z128), z6 = csq(z3), z512 = csq(z256);
  k.z8 = csq(z4);
  k.w64 = pk(z64); k.w128 = pk(z128); k.w192 = pk(cmul(z128, z64));
  sts128(dst, 0x00003C00u, pk(z2), pk(z4), pk(z6));
  const float2 z1024 = csq(z512), z768 = cmul(z512, z256);
  sts128(dst + 2048, pk(z1), pk(z3), pk(cmul(z4, z1)), pk(cmul(z4, z3)));
  const float2 z2048 = csq(z1024);
  k.kl = fmaf(k.c0.x, z2048.x, -k.c0.y * z2048.y);
  sts128(dst + 4096, pk(z256), pk(cmul(z256, z2)), pk(cmul(z256, z4)), pk(cmul(z256, z6)));
  sts128(dst + 6144, pk(z512), pk(cmul(z512, z4)), pk(z768), pk(cmul(z768, z4)));
  sts128(dst + 8192, pk(z1024), pk(cmul(z1024, z256)), pk(cmul(z1024, z512)), pk(cmul(z1024, z768)));
  sts32(scr + W_MISC + (wt >> 5) * 4, mx);
}
__device__ __forceinline__ int kgen_tables_m(uint32_t scr, int wt, const KgState& k) {
  const uint32_t dst = scr + wt * 16;
  const uint4 e4 = lds128(scr + W_MISC);
  const float2 z16 = csq(k.z8), z32 = csq(z16);
  const int em = max(min((int)(max(max(e4.x, e4.y), max(e4.z, e4.w)) >> 23), 238), 16);
  const float sc = __uint_as_float((uint32_t)(127 + 4 + 127 - em) << 23);
  sts32(scr + W_MISC + 16 + (wt >> 5) * 4, __reduce_add_sync(0xffffffffu, __float2int_rn(k.kl * sc * 262144.f)));
  const float2 c0 = make_float2(k.c0.x * sc, k.c0.y * sc);
  const float2 c1 = cmul(c0, k.z8), c2 = cmul(c0, z16), c4 = cmul(c0, z32), c3 = cmul(c1, z16), c5 = cmul(c1, z32), c6 = cmul(c2, z32), c7 = cmul(c3, z32);
  uint32_t pr[4], pi[4], yr[4], yi[4];
  pr[0] = pack_h(c0.x, c1.x); pi[0] = pack_h(c0.y, c1.y);
  pr[1] = pack_h(c2.x, c3.x); pi[1] = pack_h(c2.y, c3.y);
  pr[2] = pack_h(c4.x, c5.x); pi[2] = pack_h(c4.y, c5.y);
  pr[3] = pack_h(c6.x, c7.x); pi[3] = pack_h(c6.y, c7.y);
  sts128(dst, pr[0], pr[1], pr[2], pr[3]); sts128(dst + 2048, pi[0], pi[1], pi[2], pi[3]);
#pragma unroll
  for (int q = 1; q < 4; q++) {
    const uint32_t w = q == 1 ? k.w64 : q == 2 ? k.w128 : k.w192;
#pragma unroll
    for (int i = 0; i < 4; i++) pmul(pr[i], pi[i], w, yr[i], yi[i]);
    sts128(dst + q * 4096, yr[0], yr[1], yr[2], yr[3]); sts128(dst + q * 4096 + 2048, yi[0], yi[1], yi[2], yi[3]);
  }
  return em;
}
__device__ __forceinline__ uint32_t lds32_if(uint32_t a, bool on) {
  uint32_t v; asm volatile("{ .reg .pred q; setp.ne.u32 q, %2, 0; mov.b32 %0, 0; @q ld.shared.b32 %0, [%1]; }" : "=r"(v) : "r"(a), "r"((uint32_t)on) : "memory"); return v;
}
__device__ __forceinline__ uint32_t prmt(uint32_t a, uint32_t b, uint32_t s) { uint32_t r; asm("prmt.b32 %0, %1, %2, %3;" : "=r"(r) : "r"(a), "r"(b), "r"(s)); return r; }
struct BuildC { uint32_t a3, a2, az, cw, sel; };
__device__ __forceinline__ BuildC build_consts(int wt) {
  const int ix = ((wt >> 2) + (wt & 3) * 32 - 1) & 127;
  BuildC b;
  b.a3 = W_CW + 32 + ((ix & 1) ? 0 : 304) + (ix >> 1) * 4;
  b.a2 = W_L3 + 3072 + 544 + (wt & ~3) * 2 + (wt & 1) * 4 + (wt & 2) * 128;
  b.az = W_KT + (wt < 36 ? -512 : 64 + 4128 - 576) + wt * 16;
  b.cw = W_CW + 32 + (wt >> 6) * 48 + wt * 4;
  b.sel = (wt & 1) ? 0x10767610 : wt ? 0x10101010 : 0x10107610;
  return b;
}
__device__ __forceinline__ void kgen_build(uint32_t tb, const BuildC& bc, int wg, int wt, uint32_t k0, uint32_t k1, uint32_t k2) {
  const uint32_t kt = tb + W_KT, sc = tb + W_L3 + 3072;
  const uint32_t a3 = tb + bc.a3, a2 = tb + bc.a2;
  const uint32_t v3 = wt ? k2 : k2 >> 16;
  sts32(sc + 4 + wt * 4, __byte_perm(k0, k1, 0x5432));
  sts16(a2, k1 >> 16); sts16(a2 + 6, k1 >> 16);
  sts16(a3, v3); sts16(a3 + 6, v3);
  if ((unsigned)(wt - 32) < 14u) sts128(tb + bc.az, 0, 0, 0, 0);
  if (wt == 127) sts32(sc, k0 & 0xFFFF0000u);
  if (wt == 0) { sts32(sc + 516, k1); sts16(sc + 1056, k2); }
  bar_sync(1 + wg, 128);
  const uint32_t cw = tb + bc.cw, g2 = sc + 540 + wt * 4;
  const bool odd = wt & 1, ends = (unsigned)(wt - 4) >= 120u;
  const uint32_t pv = lds32(sc + wt * 4), nx = lds32(sc + 8 + wt * 4), nc = lds32_if(g2 + 8, ends);
  const uint32_t l0 = lds32(cw), l1 = lds32(cw - 8), l2 = lds32(cw - 16), l3 = lds32(cw - 24), q0 = lds32(g2), q1 = lds32(g2 + 128), q2 = lds32(g2 - 8), q3 = lds32(g2 + 120);
  sts64(kt + 64 + wt * 8, __byte_perm(k0, pv, 0x5410), __byte_perm(k0, 0, 0x1032));
  sts64(kt + 64 + 1024 + wt * 8, prmt(k1, pv, bc.sel), prmt(k1, nx, bc.sel >> 16));
  const uint32_t cc = __byte_perm(nc, 0, 0x3232), nn = __byte_perm(nc, 0, 0x1010);
  if (ends) sts128(kt + 64 + 2048 + wt * 16, cc, cc, odd ? nc : cc, odd ? nn : nc);
  if (wt == 127) { sts128(kt + 64 + 4096, nn, nn, nn, nn); sts128(kt + 64 + 4112, nn, nn << 16, 0, 0); }
  sts128(tb + W_L3 + 512 + (wt >> 6) * 512 + wt * 16, l0, l1, l2, l3);
  if ((wt & 63) < 34) sts128(tb + W_QT - 16 + wt * 16, q0, q1, q2, q3);
}

__device__ __forceinline__ void load_a(uint32_t (&a)[4], uint32_t kp, int j) {
  a[0] = lds32(kp + 64 * j); a[1] = lds32(kp + 64 * j + 512); a[2] = lds32(kp + 64 * j - 32); a[3] = lds32(kp + 64 * j + 480);
}
__device__ __forceinline__ uint32_t band8(int s) { return ((((0x1FFu << 20) >> s) & 0x01010101u) | (((0x7Fu << 25) >> s) & 0x10101010u)) * 0x01020408u; }
__device__ __forceinline__ uint32_t hadd2u(uint32_t a, uint32_t b) { __half2 r = __hadd2(*(__half2*)&a, *(__half2*)&b); return *(uint32_t*)&r; }

__device__ __forceinline__ void zero_pads(uint32_t tb, int wt) {
  if (!(wt & 32)) sts128(tb + W_L3 + (wt >> 6) * 512 + wt * 16, 0, 0, 0, 0);
  if ((wt & 63) < 3) sts128(tb + W_CW + (wt >> 6) * 304 + (wt & 63) * 16, 0, 0, 0, 0);
}
__device__ __forceinline__ uint32_t tr_base(int lane) {
  return OFF_YT + (2 * (lane >> 3) + (lane & 1)) * YT_PITCH + ((lane >> 1) & 1) * (8 * YT_PITCH + 64) + ((lane >> 2) & 1) * 16;
}

__device__ __forceinline__ uint32_t sc_addr(int tp) { return OFF_YT + (tp < 16 ? tp * YT_PITCH + (tp >> 3) * 64 + 1152 : 8 * YT_PITCH - 512 + tp * 32); }
#define X_PW 15
#define X_HU 16
#define X_NE 2
#define X_SCT 10000
#define X_DELTA 0
#define X_DSTEP 2000
#define X_PF0 2700
#define X_PFD 600
#define X_TD 450
#define X_WS 6
#define X_OR 8
#define X_ABS 4870
#define X_XD 200
#define X_RD 630
#define X_HD 450
#define X_PD 1170
#define X_PROMO 2
#define X_YD2 1000
#define X_GO 1
#define X_GW 2
#define X_NS 4300
#define X_XS 13450
#define X_LAG 1300
#define X_YD 1550
struct TMaps { CUtensorMap m[10]; };
__device__ __forceinline__ uint32_t h2bf(uint32_t w) { const float2 f = h2f(w); return pack_bf(f.x, f.y); }
__device__ __forceinline__ uint32_t keep(uint32_t v) { asm volatile("" : "+r"(v)); return v; }
__device__ __forceinline__ uint2 ldr64(const void* p) { uint2 v; asm volatile("{ .reg .b64 t; ld.relaxed.gpu.global.b64 t, [%2]; mov.b64 {%0, %1}, t; }" : "=r"(v.x), "=r"(v.y) : "l"(p) : "memory"); return v; }
__host__ __device__ __forceinline__ uint32_t down_box(int s, bool five) {
  return five ? OFF_W + W_BYTES + 12288 + (s / 3) * (W_BYTES - 12288) + s * 4096 : s < 6 ? OFF_W + W_BYTES + BOX + (s >> 1) * (W_BYTES - 10240) + s * 5120 : OFF_W + (s - 6) * 5120;
}
__device__ __forceinline__ void load_tile(const CUtensorMap* tmx, int i, int c, int again = 0) {
  asm volatile("mbarrier.arrive.expect_tx.shared::cta.b64 _, [%0], 8704;" :: "r"(MB_UL + i * 16 + again) : "memory");
  asm volatile("cp.async.bulk.tensor.3d.shared::cluster.global.mbarrier::complete_tx::bytes [%0], [%1, {%3, %4, %5}], [%2];"
               :: "r"(i < 2 ? OFF_T + i * TILE : OFF_W), "l"(tmx), "r"(MB_UL + i * 16 + again), "r"(0), "r"(c), "r"(-8) : "memory");
}
template <bool FAR> __device__ __forceinline__ void load_params(const Params& p, uint32_t ch, int wt, uint32_t dst, bool on) {
  const int rel = wt < 96 ? ch * 16 + (wt & 15) : ch >> 3;
  const unsigned char* b = FAR ? p.far[min(wt >> 4, 6)] + rel * 16 : p.x + (long long)(p.off[wt >> 4] + rel) * 16;
  asm volatile("{ .reg .pred q; setp.ne.u32 q, %2, 0; @q cp.async.cg.shared.global [%0], [%1], 16; }"
               :: "r"(dst + wt * 16), "l"(b), "r"((uint32_t)(on && wt < 97)) : "memory");
}

struct ConvC { uint32_t ca, cb, bands, qa; };
__device__ __forceinline__ ConvC conv_consts(int w, int lane) {
  const int h = w & 1, P = (w >> 1) & 1, d0 = 8 * h + (lane >> 2) - 2 * (lane & 3);
  ConvC k;
  k.ca = keep((W_KT + (16 + 256 * P + d0) * 4) | (((8 + 64 * P + lane) * 64 + (((h + ((w >> 1) & 2)) ^ (lane >> 1)) & 3) * 16) << 16));
  const int u = d0 + 2 * (lane & 1) + 2, in = (u & 7) - ((u & 7) >= 5 ? 5 : 0) - 2 * (lane & 1);
  k.cb = keep(in > 0 ? 0x1010 : in == 0 ? 0x3210 : 0x3232);
  k.qa = keep(W_QT + (2 * (u >> 3) + ((u & 7) >= 5) + 64 * P) * 16);
  k.bands = keep(__byte_perm(band8(d0 + 8), band8(d0 + 7), 0x7733) & 0x00FF00FFu);
  return k;
}
struct ConvPre { uint32_t e0, e2, f2, b0, b2, a[3][4]; };
__device__ __forceinline__ void conv_pre(ConvPre& r, uint32_t kp, uint32_t qp, int part, bool on, bool P) {
  if (part & 1) {
    r.e0 = lds32_if(kp + 4096, on && !P); r.e2 = lds32_if(kp + 4064, on && !P); r.f2 = lds32_if(kp + 4128, on && !P);
    r.b0 = lds32_if(kp + 2048, on && !P); r.b2 = lds32_if(kp + 2016, on && !P);
  }
#pragma unroll
  for (int j = 0; j < 3; j++) if (part & (j < 1 ? 1 : 2))
    asm volatile("{ .reg .pred q; setp.ne.u32 q, %5, 0; mov.b32 %0, 0; mov.b32 %1, 0; mov.b32 %2, 0; mov.b32 %3, 0; @q ld.shared.v4.b32 {%0,%1,%2,%3}, [%4]; }"
                 : "=r"(r.a[j][0]), "=r"(r.a[j][1]), "=r"(r.a[j][2]), "=r"(r.a[j][3]) : "r"(qp + 64 * j), "r"((uint32_t)on) : "memory");
}
__device__ __forceinline__ void conv_item(uint32_t tb, uint32_t tl, int bid, int bn, ConvPre& pre, const ConvC& cv, uint32_t zero, const CUtensorMap* tmx, int ch, int warp, int lane, bool hold, bool more) {
  const bool go = more && warp == 0 && lane == 0;
  const uint32_t kp = tb + (cv.ca & 0xFFFFu), qp = tb + cv.qa;
  const uint32_t dlo = (tl >> 4) + 32 + ((warp >> 1) & 2) + (1u << 16), dhi = 32u | (2u << 30);
  const bool P = warp & 2;
  float a32[16], b32[16], a64[32];
  uint32_t A[40][4];
#define STEP(J) { wgmma64<0>(a64, A[J], dlo + 256 - 4 * (J), dhi); \
    if ((J) == 32) wgmma32_init<0>(b32, A[J], dlo, dhi); else wgmma32<0>(b32, A[J], ((J) < 8 ? dlo ^ zero : dlo) + 128 - 4 * (J), dhi); \
    if ((J) == 0) wgmma32_init<0>(a32, A[J], dlo, dhi); else if ((J) < 8) wgmma32<0>(a32, A[J], (dlo ^ zero) - 4 * (J), dhi); }
#define LD(J) load_a(A[J], kp, J);
#define LQ(J) { const uint4 v = lds128(qp + 64 * ((J) - 32)); A[J][0] = v.x; A[J][1] = v.y; A[J][2] = v.z; A[J][3] = v.w; }
#define PQ(J) { A[J][0] = prmt(A[J][0], 0, cv.cb); A[J][1] = prmt(A[J][1], 0, cv.cb); A[J][2] = prmt(A[J][2], 0, cv.cb); A[J][3] = prmt(A[J][3], 0, cv.cb); }
#define FIRST(J) wg_fence(); STEP(J) wg_commit(); wg_wait<1>(); wg_fence();
  {
    uint32_t win[16], x9[4], x7[4], e[4], f[4];
    const uint32_t bz = keep(cv.bands);
#define BAND(i) keep((bz & (0x10001u << (i))) * (0x3C00u >> (i)))
    e[0] = pre.e0; e[2] = pre.e2; e[1] = keep(bz & 0x100u); e[3] = keep(bz & 0x200u);
    f[2] = pre.f2; f[0] = keep(bz & 0x4000u); f[1] = keep(bz & 0x8000u); f[3] = keep(bz & 0x300u);
#pragma unroll
    for (int j = 0; j < 12; j++) A[32 + j / 4][j & 3] = pre.a[j / 4][j & 3];
    PQ(32) PQ(33) PQ(34)
    if (!P) { A[32][0] = pre.b0; A[32][2] = pre.b2; }
    const uint32_t q[12] = {BAND(0), BAND(5), keep(bz & 0x400u), BAND(4), BAND(2), BAND(7), BAND(1), BAND(6), keep(bz & 0x800u), keep(bz & 0x1000u), BAND(3), keep(bz & 0x2000u)};
#undef BAND
    const uint32_t ta = keep(tl + 512 + (warp & 3) * 2048 + lane * 64 + (lane & 6) * 8);
    if (X_GO && hold) mbar_wait(MB_GO);
    uint32_t mbl = MB_UL + (warp & 8) * 2, ph = 0;
#pragma unroll 1
    for (int it = 0; it < SPIN_MAX; it++) {
      if (ch < 512) mbar_wait(mbl, ph);
      if (it == 1) TS(13);
      TS(3);
      wg_fence();
      wgmma64h_init(win, q[0], q[1], q[2], q[3], dlo, dhi);
      wgmma64h(win, q[4], q[5], q[6], q[7], dlo - 4, dhi);
      wgmma64h(win, q[8], q[9], q[10], q[11], dlo - 8, dhi);
      wg_commit();
      wgmma64_init<0>(a64, e, dlo, dhi);
      wgmma64<0>(a64, f, dlo - 4, dhi);
      wg_commit();
      if (ch >= 512) break;
      uint32_t r0, r1, r2, r3, ok;
      if (warp & 4) {
        mbar_wait(mbl + 8);
        if (__all_sync(0xffffffffu, it || lds32(MISC_RT + (warp & 8)) == 0)) break;
        wg_wait<0>();
        continue;
      }
      ldsm4(ta, r0, r1, r2, r3);
      ok = r0 & r1 & r2 & r3;
      ldsm4(ta ^ 32, r0, r1, r2, r3);
      asm volatile("{ .reg .pred q; setp.ne.u32 q, %1, 0; barrier.red.and.pred q, %2, 128, q; selp.u32 %0, 1, 0, q; }" : "=r"(ok) : "r"((ok & r0 & r1 & r2 & r3 & 1u) | (lane & 3)), "r"(1 + (warp >> 2)) : "memory");
      if (ok) { if ((warp & 3) == 0 && lane == 0) { sts32(MISC_RT + warp, it); mbar_arrive(MB_UL + 8 + warp * 2); } break; }
      wg_wait<0>();
      if ((warp & 3) == 0 && lane == 0) load_tile(tmx - 1, warp >> 3, ch, 56);
      mbl = MB_UL + 56 + (warp & 8) * 2; ph = it & 1;
    }
    wg_wait<1>();
#pragma unroll
    for (int i = 0; i < 4; i++) {
      const int tl = 2 * ((i & 1) + ((i & 2) ? 0 : 4));
      x9[i] = P ? win[tl + 4] : win[tl]; x7[i] = P ? win[tl + 5] : win[tl + 1];
    }
    const uint32_t l3lo = ((tb + W_L3) >> 4) + (32u << 16);
    wg_fence();
    wgmma64<0>(a64, x9, l3lo, 8);
    wgmma64<0>(a64, x7, l3lo + 96, 8);
    wg_commit();
  }
  STEP(32) STEP(33) STEP(34) wg_commit(); wg_wait<1>();
  LQ(35) LQ(36) LQ(37) LQ(38) LQ(39) LD(0) PQ(35) PQ(36) PQ(37) PQ(38) PQ(39)
  FIRST(35) STEP(36) STEP(37) STEP(38) wg_commit(); STEP(39) wg_commit();
  LD(1) LD(2) LD(3)
  if (X_GO == 1 && go) mbar_arrive(MB_GO);
  wg_wait<1>(); wg_fence(); STEP(0) wg_commit(); STEP(1) wg_commit(); STEP(2) wg_commit(); wg_wait<2>();
  LD(4) LD(5)
  wg_fence(); STEP(3) wg_commit(); wg_wait<1>();
  LD(6) LD(7)
  wg_fence(); STEP(4) STEP(5) wg_commit();
  wg_fence(); STEP(6) STEP(7) wg_commit();
#undef STEP
#undef LD
#undef LQ
#undef PQ
#undef FIRST
  TS(18);
  if (X_GO == 3 && go) mbar_arrive(MB_GO);
  const uint32_t xc = tb + W_KT + (warp & 3) * 1024 + lane * 16;
  if (more) bar_sync(7, 288);
  wg_wait<1>();
  conv_pre(pre, kp + ALT, qp + ALT, 1, more, P);
  wg_wait<0>();
  conv_pre(pre, kp + ALT, qp + ALT, 2, more, P);
  uint32_t E[16], o[8];
#define ACC(i) ((i) < 16 ? a32[i] : (i) < 32 ? b32[(i) - 16] : a64[(i) - 32])
  E[0] = pack_h(a32[0], a32[1]);
#pragma unroll
  for (int i = 1; i < 16; i++) E[i] = pack_h(ACC(4 * i) + ACC(4 * i - 2), ACC(4 * i + 1) + ACC(4 * i - 1));
#undef ACC
#pragma unroll
  for (int j = 0; j < 8; j++) o[j] = P ? (j < 2 ? 0u : E[j - 2]) : E[8 + j];
  sts128(xc, o[0], o[1], o[2], o[3]); sts128(xc + 512, o[4], o[5], o[6], o[7]);
#pragma unroll
  for (int j = 0; j < 8; j++) o[j] = P ? E[6 + j] : E[j];
  TS(25);
  if (more) {
    sts128(xc + 4096, o[0], o[1], o[2], o[3]); sts128(xc + 4608, o[4], o[5], o[6], o[7]);
    bar_arrive(12, 192);
    return;
  }
  bar_sync(1 + (warp >> 2), 128);
  const uint4 vv[2] = {lds128(xc + (P ? -2048 : 2048)), lds128(xc + (P ? -1536 : 2560))};
  const uint32_t mk = lane < 8 ? 0xFFFEFFFEu : ~0u;
#pragma unroll
  for (int q = 0; q < 2; q++) {
    const uint4 v = vv[q];
    stsm4t(tl + (cv.ca >> 16) + q * 2048, hadd2u(o[4 * q], v.x) & mk, hadd2u(o[4 * q + 1], v.y) & mk, hadd2u(o[4 * q + 2], v.z) & mk, hadd2u(o[4 * q + 3], v.w) & mk);
  }
  fence_async();
  bar_sync(bid, bn);
  if (warp == 0 && lane == 0) mbar_arrive(MB_REL);
  if ((warp & 7) == (ch < 512 ? 7 : 3) && lane == 0) {
    asm volatile("cp.async.bulk.tensor.3d.global.shared::cta.bulk_group [%0, {%3, %2, %3}], [%1];" :: "l"(tmx), "r"(tl + 512), "r"(ch), "r"(0) : "memory");
    asm volatile("cp.async.bulk.commit_group;" ::: "memory");
  }
}

template <bool FAR> __global__ void __launch_bounds__(NT, 1)
fused_kernel(const __grid_constant__ Params p, const __grid_constant__ TMaps tm) {
  extern __shared__ __align__(1024) unsigned char smem[];
  const int c = blockIdx.x;
  const bool five = (c & 1) == 0;
  const uint32_t pitch = five ? 64 : 80;
  const uint32_t ones = 0x3F803F80u;
  const int tid = threadIdx.x, lane = tid & 31;
  const uint32_t xrow = OFF_YT + ((tid & 127) >> 3) * YT_PITCH + (tid & 64) + (tid & 7) * 16;
  {
    const int w4 = tid >> 7;
    load_params<FAR>(p, w4 < 2 ? 2 * c + w4 : five ? 257 + 2 * c : 512 + (c >> 1), tid & 127, OFF_W + W_KT + (w4 < 2 ? w4 * W_BYTES : five ? 3 * W_BYTES : 3 * W_BYTES + 2048), (0xB >> w4) & 1);
  }
  if ((tid >> 7) == 2) {
    const unsigned char* xp = p.x + (uint32_t)((c * 16 - 32 + (tid >> 3)) * 1152 + (tid & 7) * 16);
    asm volatile("" : "+l"(xp));
    { const uint32_t tq = clock(); while ((int)(clock() - tq) < X_XD) {} }
#pragma unroll
    for (int k = 0; k < 9; k++) asm volatile("cp.async.cg.shared.global [%0], [%1], 16;" :: "r"(xrow + k * 128), "l"(xp + k * 128) : "memory");
  }
  const int warp = (int)uni(tid >> 5), wg = warp >> 2;
  TS(0);
  if (__builtin_expect(wg == 4, 0)) {
    asm volatile("setmaxnreg.dec.sync.aligned.u32 32;");
    const int role = warp;
    const int u0 = (c >> 1) * 9 + (five ? ((c & 2) ? 5 : 0) : ((c & 2) ? 0 : 4));
    const uint32_t t0 = clock() + c * 4;
    if (role == 16) {
      if (lane == 0) {
#pragma unroll
        for (int i = 0; i < 19; i++) if (i != 16) asm volatile("mbarrier.init.shared::cta.b64 [%0], %1;" :: "r"(OFF_MISC + i * 8), "r"((unsigned)(i - 2) < 4u ? 4 : 1) : "memory");
      }
      __syncwarp();
      if (lane < 2) asm volatile("mbarrier.arrive.expect_tx.shared::cta.b64 _, [%0], %1;" :: "r"(OFF_MISC + lane * 8), "r"(lane ? (five ? 36864 : 51200) : pitch * 1152) : "memory");
      fence_async();
      bar_arrive(5, 608);
      const CUtensorMap* tmb = &tm.m[five ? 3 : 0];
#pragma unroll 1
      for (int u = 0; u < 17; u++) {
        const uint32_t e = p.sched[five][u], kind = e & 3, s = (e >> 2) & 15, dst = e >> 14;
        if (kind == 3) continue;
        while ((int)(clock() - t0) < X_PF0 + (u < X_NE ? u * X_PFD : X_LAG + u * X_TD)) __nanosleep(20);
        if (e & 0x3FC0) mbar_wait(OFF_MISC + ((e >> 6) & 255));
        if (lane == 0) {
          if (kind == 2) asm volatile("cp.async.bulk.tensor.3d.shared::cluster.global.mbarrier::complete_tx::bytes [%0], [%1, {%3, %4, %5}], [%2];"
                                      :: "r"(dst), "l"(tmb + 2), "r"(MB_D), "r"(0), "r"(u0 * 8), "r"(s) : "memory");
          else tma_box(dst, tmb + kind, MB_GU, u0 * 8, s * 96);
        }
        if (u == 5) TS(2);
        if (u == 10) TS(3);
      }
      TS(4);
      TS_DUMP();
#define FINISH0 bar_sync(12, 192);        \
        _Pragma("unroll 1") for (int w = role & 2; w < (role & 2) + 2; w++) { \
          const uint32_t xa = OFF_W + W_KT + lane * 16, mk = lane < 8 ? 0xFFFEFFFEu : ~0u, ya = OFF_T + (8 + lane) * 64 + (((w & 1) ^ (lane >> 1)) & 3) * 16 + (w & 2) * 2048; \
          const uint4 a = lds128(xa + 4096 + w * 1024), b = lds128(xa + (w ^ 2) * 1024), d = lds128(xa + 4608 + w * 1024), e = lds128(xa + 512 + (w ^ 2) * 1024); \
          stsm4t(ya, hadd2u(a.x, b.x) & mk, hadd2u(a.y, b.y) & mk, hadd2u(a.z, b.z) & mk, hadd2u(a.w, b.w) & mk); \
          stsm4t(ya + 2048, hadd2u(d.x, e.x) & mk, hadd2u(d.y, e.y) & mk, hadd2u(d.z, e.z) & mk, hadd2u(d.w, e.w) & mk); \
        } \
        fence_async();
    } else if (role == 17) {
      if (smem_u32(smem) != SB) __trap();
      bar_sync(10, 576);
      if (lane == 0) {
        fence_async();
        while ((int)(clock() - t0) < X_NS - c * 4) {}
        asm volatile("cp.async.bulk.global.shared::cta.bulk_group [%0], [%1], 10240;" :: "l"(&p.s->X[c * DM * 2 + 512]), "r"(OFF_G) : "memory");
        asm volatile("cp.async.bulk.commit_group;" ::: "memory");
        asm volatile("cp.async.bulk.wait_group 0;" ::: "memory");
      }
      if (lane == 0) mbar_arrive(MB_GF);
      bar_arrive(11, 96);
      if (five) { FINISH0 bar_arrive(13, 192); }
    } else if (role == 18) {
      sts32(MISC_EPOCH, 0);
      sts32(MISC_T0, t0 - c * 4);
      bar_arrive(5, 608);
      uint4* q = lane < 2 ? &p.s->R[c * 2 + lane] : lane < 11 ? &p.s->HS[c * 9 + lane - 2] : lane == 11 ? &p.s->HS[1152 + (c & 7)] : (uint4*)&p.s->FLAG[c * 8];
      if (lane < (c < 8 ? 12 : 11)) str128(q, ~0u, ~0u, ~0u, ~0u);
      const uint32_t ep = __shfl_sync(0xffffffffu, ldr32(q), 31) + 1u;
      sts32(MISC_EPOCH, ep | 0x80000000u);
      TSX(21);
      if (lane == 31) str32(q, ep);
      bar_sync(11, 96);
      TSX(14);
      mbar_wait(MB_KF + (lane & 3) * 8);
      __syncwarp();
      { const uint2 e = lds64(MISC_EM); if (lane < 2) str128(&p.s->SC[c * 2 + lane], e.x, __byte_perm(e.y, ep, 0x6540), 0, 0); }
      TSX(17);
      while ((int)(clock() - t0) < X_SCT) __nanosleep(100);
      TSX(18);
      {
        uint2 v[4];
#pragma unroll 1
        for (int it = 0; it < SPIN_MAX; it++) {
          uint32_t bad = 0;
#pragma unroll
          for (int q = 0; q < 4; q++) v[q] = ldr64(&p.s->SC[lane * 2 + q * 64]);
#pragma unroll
          for (int q = 0; q < 4; q++) bad |= (v[q].y >> 8) ^ (ep & 0xFFFFFFu);
          if (!__any_sync(0xffffffffu, bad)) break;
        }
        TSX(25);
#pragma unroll
        for (int q = 0; q < 4; q++) {
          const uint32_t sa = (lane >> 4) * YT_PITCH + (lane & 15) * 2;
          sts16(sc_addr(2 * q) + sa, v[q].x); sts16(sc_addr(8 + 2 * q) + sa, v[q].x >> 16);
          if (lane & 1) asm volatile("st.shared.u8 [%0], %1;" :: "r"(sc_addr(16) + q * 16 + (lane >> 1)), "r"(v[q].y) : "memory");
        }
      }
      __syncwarp();
      if (lane == 0) mbar_arrive(MB_SC);
      TSX(27);
    } else {
      uint32_t w[9];
      const uint32_t dk = ldnc16(p.dskip + ((lane & 4) ? 512 + (c >> 1) : (lane & 2) * 128 + 2 * c + (lane & 1)));
      float s = 0.f;
#pragma unroll
      for (int i = 0; i < 9; i++) w[i] = ldnc32(p.w_r + lane + 32 * i);
      sts16(OFF_WR + 1152 + lane * 2, dk);
      bar_arrive(5, 608);
#pragma unroll
      for (int i = 0; i < 9; i++) { sts32(OFF_WR + lane * 4 + i * 128, w[i]); s += bf_lo(w[i]) + bf_hi(w[i]); }
      sts32(MISC_SW, __float_as_uint(warp_sum(s)));
      TSX(23);
      bar_sync(10, 576);
      if (lane == 0) {
        const uint32_t tp = clock();
        TSX(1);
        while ((int)(clock() - tp) < X_DELTA || (int)(clock() - t0) < X_ABS - c * 4) {}
        TSX(24);
        load_tile(&tm.m[6], 0, c);
        TSX(15);
        while ((int)(clock() - t0) < X_ABS + X_DSTEP - c * 4) {}
      }
      bar_sync(11, 96);
      if (lane == 0) {
        load_tile(&tm.m[6], 1, 128 + c);
      }
      if (five) {
        mbar_wait(MB_KF);
#pragma unroll 1
        for (int it = 0; it < SPIN_MAX; it++) {
          if (lane == 0) load_tile(&tm.m[8], 2, 512 + (c >> 1));
          mbar_wait(MB_UL + 32, it & 1);
          uint32_t m = 1;
#pragma unroll
          for (int q = 0; q < 4; q++) { uint32_t r0, r1, r2, r3; ldsm4(OFF_W + 512 + lane * 64 + (lane & 6) * 8 + q * 2048, r0, r1, r2, r3); m &= r0 & r1 & r2 & r3; }
          if (__all_sync(0xffffffffu, m || (lane & 3))) break;
        }
        bar_arrive(7, 288);
        FINISH0
        bar_arrive(13, 192);
      }
      bar_sync(0, 544);
      if (lane == 0) mbar_arrive(MB_H);
    }
    return;
  }
  const int wt = tid & 127, g = lane >> 2, t = lane & 3;
  const uint32_t wb = OFF_W + wg * W_BYTES;
  asm volatile("cp.async.commit_group;" ::: "memory");
  const ConvC cv = conv_consts(warp, lane);
  zero_pads(wb, wt);
  load_params<FAR>(p, 254 + 2 * c + wg, wt, wb + W_KT, wg == 2 || (wg == 3 && !five));
  asm volatile("cp.async.commit_group;" ::: "memory");
  asm volatile("setmaxnreg.inc.sync.aligned.u32 112;");
  {
    uint4 kw;
    uint4* kx = &p.s->KX[(c >> 1) * 128 + wt];
    bool two = wg == 3;
    uint32_t ep;
    int em = 0;
    uint32_t slot = wg + (two && !five);
    const uint32_t ra0 = wb + W_KT + (slot & 4) * 512 + wt * 2, ra6 = wb + W_KT + 1536 + (slot & 4) * 512 + (((slot & 4) ? c >> 1 : 2 * c + (wg & 1)) & 7) * 2;
    const uint32_t tr_addr = pin(tr_base(lane) + warp * 32), lca = pin(MISC_LN1 + (lane & 1) * 16);
    uint4* dst;
    { const unsigned long long a = (unsigned long long)&p.s->X[c * DM * 2 + warp * 32 + (8 * ((lane >> 1) & 1) + (lane >> 2)) * 2 + (lane & 1)];
      dst = (uint4*)(((unsigned long long)pin(a >> 32) << 32) | pin((uint32_t)a)); }
    const BuildC bc = build_consts(wt);
    uint32_t raw[7];
    if (wg != 2) {
      asm volatile("cp.async.wait_group 1;" ::: "memory");
      bar_sync(1 + wg, 128);
#pragma unroll
      for (int i = 0; i < 7; i++) raw[i] = lds16(i < 6 ? ra0 + i * 256 : ra6);
    }
    int phase = wg == 2 ? 3 : 2;
#pragma unroll 1
    for (;;) {
      if (phase != 3) {
        KgState ks;
        TS(22);
        kgen_tables_n(raw, wb, wt, ks);
        TS(20);
        bar_sync(1 + wg, 128);
        em = kgen_tables_m(wb, wt, ks);
        fence_async();
      }
      if (phase & 2) {
        if (phase == 3) {
        asm volatile("cp.async.wait_group 1;" ::: "memory");
        TS(21);
        float d[3][4], r;
        uint4 a[9];
#pragma unroll
        for (int k = 0; k < 9; k++) a[k] = lds128(xrow + k * 128);
#pragma unroll
        for (int i = 0; i < 4; i++) d[0][i] = d[1][i] = d[2][i] = 0.f;
#pragma unroll
        for (int k = 0; k < 9; k++) { mma_bf16(d[(2 * k) % 3], a[k].x, ones, a[k].y, ones, a[k].x, a[k].y); mma_bf16(d[(2 * k + 1) % 3], a[k].z, ones, a[k].w, ones, a[k].z, a[k].w); }
#pragma unroll
        for (int i = 0; i < 4; i++) d[0][i] += d[1][i] + d[2][i];
        const LnC lc = ln_consts(d[0][2] + d[0][3], __shfl_sync(0xffffffffu, d[0][0], 9 * t) + __shfl_sync(0xffffffffu, d[0][1], 9 * t + 4), r);
        if (lane < 12) sts16(MISC_LN1 + g * 32 + (warp & 3) * 8 + t * 2, lane < 4 ? lc.m2 : lane < 8 ? lc.rh2 : lc.rl2);
        }
        asm volatile("cp.async.wait_group 0;" ::: "memory");
        TS(23);
        bar_sync(5, 608);
        uint32_t x[3][4];
        ldsm4t(tr_addr, x[0][0], x[0][1], x[0][2], x[0][3]);
        uint4 m = lds128(lca);
        const uint4 rl = lds128(lca + 64), rh = lds128(lca + 32);
        ldsm4t(tr_addr + 512, x[1][0], x[1][1], x[1][2], x[1][3]);
        if (wg == 3) ldsm4t(tr_addr + 640, x[2][0], x[2][1], x[2][2], x[2][3]);
#pragma unroll
        for (int q = 0; q < 3; q++) {
          if (q < 2 || wg == 3) {
            const uint32_t r0 = ln_apply(x[q][0], m.x, rh.x, rl.x), r1 = ln_apply(x[q][1], m.y, rh.y, rl.y), r2 = ln_apply(x[q][2], m.z, rh.z, rl.z), r3 = ln_apply(x[q][3], m.w, rh.w, rl.w);
            const uint32_t w0 = (pack_h(bf_lo(r0), bf_hi(r0)) & 0xFFFEFFFEu) | 1u, w1 = pack_h(bf_lo(r1), bf_hi(r1)), w2 = pack_h(bf_lo(r2), bf_hi(r2)), w3 = pack_h(bf_lo(r3), bf_hi(r3));
            if (q == 0) str128(dst, w0, w1, w2, w3);
            else sts128(OFF_G + warp * 512 + (8 * (t >> 1) + g) * 32 + (t & 1) * 16 + (q == 2 ? 2048 : 0), w0, w1, w2, w3);
          }
          if (q == 0) {
            const uint32_t z = clock() & p.off[7];
            m.x ^= z; m.y ^= z; m.z ^= z; m.w ^= z;
          }
          if (q == 0) TS(30);
          if (q == 0 && wg >= 2) {
#pragma unroll
            for (int i = 0; i < 7; i++) raw[i] = lds16(wb + W_KT + i * 256 + (i < 6 ? wt : (2 * c + (wg & 1)) & 7) * 2);
          }
        }
        bar_arrive(10, 576);
        TS(1);
      } else bar_sync(1 + wg, 128);
      phase &= 1;
      if (phase) { phase = 0; continue; }
      TS(14);
      float acc[20];
      const uint32_t alo = (wb >> 4) | (8u << 16);
      uint4 k4 = lds128(wb + W_MISC + 16);
      uint32_t dk = lds16(OFF_WR + 1152 + slot * 2);
      wg_fence();
      wgmma40_ss_init(acc, alo, alo + 1024, 2048 >> 4);
#pragma unroll
      for (int k = 1; k < 8; k++) wgmma40_ss(acc, alo + k * 16, alo + 1024 + k * 16, 2048 >> 4);
      wg_commit();
      { const uint32_t z = clock() & p.off[7]; dk ^= z; k4.x ^= z; k4.z ^= z; }
      const float k2048 = (float)(int)((k4.x + k4.y) + (k4.z + k4.w)) * (1.f / 262144.f);
      const int ef = max(em, min((int)((dk >> 7) & 255u) - 7, 238));
      asm volatile("st.shared.u8 [%0], %1;" :: "r"(MISC_EM + slot), "r"(ef + 9) : "memory");
      const float un = __uint_as_float((uint32_t)max(114 + em - ef, 0) << 23), d0 = wt ? 0.f : bf_lo(dk) * __uint_as_float((uint32_t)(245 - ef) << 23);
      wg_wait<0>();
      kw.x = pack_h(fmaf(acc[0] - acc[3], un, d0), (acc[4] - acc[7]) * un);
      kw.y = pack_h((acc[8] - acc[11]) * un, (acc[12] - acc[15]) * un);
      kw.z = pack_h((acc[16] - acc[19]) * un, k2048 * un);
      TS(24);
      ep = 0;
      if (two) SPIN_WHILE(ep == 0, ep = lds32(MISC_EPOCH));
      if (five || !two) break;
      str128(kx, kw.x, kw.y, kw.z, ep);
      two = false;
      slot = 3;
      bar_sync(1 + wg, 128);
    }
    if (lane == 0) mbar_arrive(MB_KF + wg * 8);
    if (two) { mbar_wait(MB_KF); zero_pads(OFF_W + ALT, wt); }
    uint32_t tb = wb;
#pragma unroll 1
    for (;;) {
      kgen_build(tb, bc, wg, wt, kw.x, kw.y, kw.z);
      TS(15);
      if (!two) break;
      two = false;
      kw.w = 0;
      SPIN_WHILE(kw.w != ep, kw = ldr128(kx));
      tb = OFF_W + ALT;
    }
    fence_async();
    TS(31);
    if (tb != wb) bar_arrive(7, 288);
    bar_sync(1 + wg, 128);
  }
  uint32_t tpub;
  ConvPre pre;
  conv_pre(pre, (wb ^ p.off[7]) + (cv.ca & 0xFFFFu), (wb ^ p.off[7]) + cv.qa, 3, true, warp & 2);
#pragma unroll 1
  for (int item = 0;; item++) {
    TS(2);
    conv_item(item ? OFF_W + ALT : wb, item ? OFF_W : OFF_T + (wg >> 1) * TILE, item ? 1 : 13 + (wg >> 1), item ? 128 : five && wg == 1 ? 192 : 256, pre, cv, p.off[7],
              &tm.m[item ? 9 : 7], item ? 512 + (c >> 1) : (wg >> 1) * 128 + c, warp, lane, five && wg >= X_GW, five && !wg && !item);
    tpub = clock() - (item ? X_YD : wg >= 2 ? X_YD2 : 0);
    if (wg || !five || item) break;
    TS(27);
  }
  TS(4);

  const int ln = lane ^ p.off[7], td = warp * 32 + ln, gg = ln >> 2, tt = ln & 3;
  const int tok = c * 16 + warp;
  const int fu = warp / 3, fk = warp - fu * 3;
  uint32_t wa[12][4];
  uint4 ha[3];
  const uint4* hsrc = &p.s->HS[td + (td / 24) * 48];
  {
    uint32_t hw[9], wr[9];
    const uint32_t row = keep(OFF_YT + warp * YT_PITCH + (warp >> 3) * 64 + ln * 16);
    const uint32_t wabase = keep(((ln & 8) ? OFF_W + (fk + 1) * W_BYTES : OFF_G + fk * 192 * pitch) + ((ln >> 4) * 8 + (ln & 7)) * pitch
                                 + (five ? ((fu ^ (ln >> 1)) & 3) : min(fu, 4)) * 16);
    float sw;
    {
      const bool three = wg == 1;
      const int ch = 8 * (tt >> 1) + gg;
      const uint32_t tr_addr = tr_base(ln);
      const uint4* ysrc = &p.s->X[c * DM * 2 + ch * 2 + (tt & 1)];
      uint32_t x[3][4], s[3];
      uint4 v[3];
#define TL(q) ((q) < 2 ? 2 * warp + (q) : 28 + warp)
      if (wg >= 2) { const uint32_t ts = lds32(MISC_T0); while ((int)(clock() - ts) < X_XS) {} }
      while ((int)(clock() - tpub) < X_YD) {}
      TS(5);
      v[0] = ldr128(ysrc + TL(0) * 32); v[1] = ldr128(ysrc + TL(1) * 32); v[2] = make_uint4(three, 0, 0, 0);
      mbar_wait(MB_REL);
#pragma unroll
      for (int i = 0; i < 6; i++) if (i < 4 || three) wr[i] = (gg & 2) ? ones : lds32(OFF_WR + TL(i >> 1) * 32 + (i & 1) * 16 + tt * 4);
      const uint32_t ha = keep(OFF_YT + (ln & 7) * YT_PITCH + (ln >> 4) * (8 * YT_PITCH + 64) + (ln & 8) * 2);
      const uint32_t pa = keep(OFF_PART + warp * 4 + ((gg & 2) * 8 + (gg & 4) * 2 + 2 * tt + (gg & 1)) * 80), pb = keep(OFF_PART + 2560 + warp * 4 + gg * 80);
      float dl[4] = {0.f, 0.f, 0.f, 0.f}, dh[4] = {0.f, 0.f, 0.f, 0.f};
      sw = __uint_as_float(lds32(MISC_SW));
#pragma unroll
      for (int q = 0; q < 3; q++) {
        if (q < 2 || three) {
          ldsm4t(tr_addr + TL(q) * 32, x[q][0], x[q][1], x[q][2], x[q][3]);
        }
      }
      asm volatile("cp.async.bulk.wait_group.read 0;" ::: "memory");
      mbar_wait(MB_SC);
#pragma unroll
      for (int q = 0; q < 3; q++) {
        asm volatile("ld.shared.u8 %0, [%1];" : "=r"(s[q]) : "r"((q < 2 ? sc_addr(warp) + q * 16 : sc_addr(16) + (warp & 3) * 16) + ch) : "memory");
        s[q] = keep(s[q] * 0x800080u);
      }
#define FIN(q) stsm4t(tr_addr + TL(q) * 32, bf_fma2(h2bf(v[q].x), s[q], x[q][0]), bf_fma2(h2bf(v[q].y), s[q], x[q][1]), bf_fma2(h2bf(v[q].z), s[q], x[q][2]), bf_fma2(h2bf(v[q].w), s[q], x[q][3]));
      SPIN_WHILE((v[0].x | v[1].x) & 1u, _Pragma("unroll") for (int q = 0; q < 3; q++) if (v[q].x & 1u) v[q] = ldr128(ysrc + TL(q) * 32));
      if (v[2].x & 1u) v[2] = ldr128(ysrc + TL(2) * 32);
#define STAT(q) { uint32_t r0, r1, r2, r3; ldsm4(ha + TL(q) * 32, r0, r1, r2, r3); \
        mma_bf16(dl, r0, wr[2 * q], r1, wr[2 * q + 1], r0, r1); mma_bf16(dh, r2, wr[2 * q], r3, wr[2 * q + 1], r2, r3); }
      FIN(0) FIN(1)
      __syncwarp();
      STAT(0) STAT(1)
      if (three) {
#pragma unroll 1
        for (int it = 0; it < SPIN_MAX; it++) {
          FIN(2)
          if (!__any_sync(0xffffffffu, v[2].x & 1u)) break;
          if (v[2].x & 1u) v[2] = ldr128(ysrc + TL(2) * 32);
        }
        __syncwarp();
        STAT(2)
      }
      if (gg & 1) { dl[0] = dl[1]; dl[2] = dl[3]; dh[0] = dh[1]; dh[2] = dh[3]; }
      sts32(pa, __float_as_uint((gg & 4) ? dh[2] : dl[2]));
      if (tt == (gg >> 1)) { sts32(pb, __float_as_uint(dl[0])); sts32(pb + 640, __float_as_uint(dh[0])); }
#undef STAT
#undef FIN
#undef TL
    }
    uint32_t ra = keep(OFF_PART + (ln & 15) * 80 + (ln & 16) * 2);
    uint16_t* rp = (uint16_t*)p.s->R + c * 16 + (ln & 15);
    const uint2* rsrc = (const uint2*)p.s->R + td;
    asm volatile("" : "+l"(rp), "+l"(rsrc), "+l"(hsrc));
    uint2 rv = make_uint2(0u, 0u);
    TS(28);
    if (warp != X_PW) bar_sync(0, 544);
    else {
      float z[3], rd;
      asm volatile("bar.sync 0, 544;" : "+r"(ra) :: "memory");
#pragma unroll
      for (int k = 2; k >= 0; k--) {
        const uint4 a = lds128(ra + k * 1280), b = lds128(ra + k * 1280 + 16);
        z[k] = ((__uint_as_float(a.x) + __uint_as_float(a.y)) + (__uint_as_float(a.z) + __uint_as_float(a.w))) + ((__uint_as_float(b.x) + __uint_as_float(b.y)) + (__uint_as_float(b.z) + __uint_as_float(b.w)));
      }
#pragma unroll
      for (int k = 2; k >= 0; k--) z[k] += __shfl_xor_sync(0xffffffffu, z[k], 16);
      const LnC l = ln_consts(z[1], z[2], rd);
      const uint32_t b = pack_bf(0.f, fmaf(-bf_lo(l.m2), sw, z[0]) * rd);
      const uint32_t k16 = max(min((b ^ (((int)b >> 31) | 0x80000000u)) >> 16, 0xFFFEu), 1u);
      if (ln < 16) str16(rp, k16);
      sts64(OFF_RK + (ln & 15) * 8, __byte_perm(l.m2, l.rh2, 0x5410), __byte_perm(l.rl2, k16, 0x5410));
      sts128(MISC_CNT + ln * 16, 0, 0, 0, 0);
    }
    mbar_wait(MB_GU);
#define LD_HW { const uint4 a = lds128(row), b = lds128(row + 512); hw[8] = lds32(row + 1024 - ln * 12); \
      hw[0] = a.x; hw[1] = a.y; hw[2] = a.z; hw[3] = a.w; hw[4] = b.x; hw[5] = b.y; hw[6] = b.z; hw[7] = b.w; }
    LD_HW
    const uint32_t tr0 = clock();
    bar_sync(5, 512);
    TS(7);
    const uint2 lk = lds64(OFF_RK + warp * 8);
    LnC l2;
    l2.m2 = __byte_perm(lk.x, 0, 0x1010); l2.rh2 = __byte_perm(lk.x, 0, 0x3232); l2.rl2 = __byte_perm(lk.y, 0, 0x1010);
    const uint32_t key = (lk.y & 0xFFFF0000u) | (2047 - tok);
    uint32_t loc = ln < 16 ? (lds32(OFF_RK + 4 + ln * 8) & 0xFFFF0000u) | (2047 - c * 16 - ln) : 0u;
    int rank = __popc(__ballot_sync(0xffffffffu, loc > key));
#pragma unroll
    for (int i = 0; i < 9; i++) { wr[i] = keep(ln_apply(hw[i], l2.m2, l2.rh2, l2.rl2)); hw[i] = bf_add2(hw[i], wr[i]); }
#define OUT_ROW { uint32_t* o = p.out + tok * 288 + ln * 4; \
      *(uint4*)o = make_uint4(hw[0], hw[1], hw[2], hw[3]); *(uint4*)(o + 128) = make_uint4(hw[4], hw[5], hw[6], hw[7]); o[256 - ln * 3] = hw[8]; }
    uint4* hs = p.s->HS + ln;
    asm volatile("" : "+l"(hs));
#pragma unroll 1
    for (int base = 0; base < 8; base += 2) {
      uint32_t T[2];
#pragma unroll
      for (int j = 0; j < 2; j++) {
        const uint32_t mx = __reduce_max_sync(0xffffffffu, loc);
        if (loc == mx) loc = 0;
        T[j] = (td >> 2) < c ? (mx & 0xFFFF0000u) - 1u : mx | 0xFFFFu;
      }
      const uint32_t sh = keep(rank == base ? 0x4410u : rank == base + 1 ? 0x4432u : 0x4445u), ca = keep(MISC_CNT + base * 64 + ln * 4);
      TS(29);
      if (base == 0) {
        while ((int)(clock() - tr0) < X_RD) {}
        if ((td >> 2) != c) rv = ldr64(rsrc);
        if (rank >= X_OR) OUT_ROW
        if (warp < (five ? 12 : 15)) {
#pragma unroll
          for (int k = 0; k < X_WS; k++) ldsm4t(wabase + k * 16 * pitch, wa[k][0], wa[k][1], wa[k][2], wa[k][3]);
        }
      }
      uint32_t cnt;
#pragma unroll 1
      for (int it = 0; it < SPIN_MAX; it++) {
        const uint32_t xs = rv.x << 16, ys = rv.y << 16;
        const bool bad = max(max(rv.x, xs), max(rv.y, ys)) >= 0xFFFF0000u;
        uint32_t cn2 = 0;
        cnt = bad ? 256u : 0u;
#pragma unroll
        for (int j = 0; j < 2; j++)
          asm("{ .reg .pred a, b, c, d; setp.gt.u32 a, %2, %6; setp.gt.u32 b, %3, %6; setp.gt.u32 c, %4, %6; setp.gt.u32 d, %5, %6; "
              "@a add.u32 %1, %1, %7; @b add.u32 %1, %1, %7; @c add.u32 %0, %0, %7; @d add.u32 %0, %0, %7; }"
              : "+r"(cnt), "+r"(cn2) : "r"(rv.x), "r"(rv.y), "r"(xs), "r"(ys), "r"(T[j]), "r"(1u << (16 * j)));
        cnt = __reduce_add_sync(0xffffffffu, cnt + cn2);
        asm volatile("{ .reg .pred q; setp.eq.u32 q, %2, 0; @q red.shared.add.u32 [%0], %1; }" :: "r"(ca), "r"(cnt), "r"(cnt & 0x3F00u) : "memory");
        if (!(cnt & 0x3F00u)) break;
        if (bad) rv = ldr64(rsrc);
      }
      TS(16);
      bar_sync(0, 512);
      cnt = lds32(ca);
      if (base == 0) tpub = clock();
      const int gr = rank + __byte_perm(cnt, 0x800u, sh);
      if (gr < 8) {
        uint4* ks = hs + 1152 + gr;
        hs = (uint4*)((char*)hs + gr * 1152);
        asm volatile("{ .reg .b128 t, u; .reg .b64 a, b, c, d; mov.b64 a, {%1,%2}; mov.b64 b, {%3,%4}; mov.b64 c, {%5,%6}; mov.b64 d, {%7,%8}; mov.b128 t, {a, b}; mov.b128 u, {c, d}; "
                     "st.relaxed.gpu.global.b128 [%0], t; st.relaxed.gpu.global.b128 [%0 + 512], u; }"
                     :: "l"(hs), "r"(wr[0]), "r"(wr[1]), "r"(wr[2]), "r"(wr[3]), "r"(wr[4]), "r"(wr[5]), "r"(wr[6]), "r"(wr[7]) : "memory");
        str32((uint32_t*)(hs + 64) - ln * 3, wr[8]);
        LD_HW
        str128(hs + 576, hw[0], hw[1], hw[2], hw[3]); str128(hs + 608, hw[4], hw[5], hw[6], hw[7]); str32((uint32_t*)(hs + 640) - ln * 3, hw[8]);
        if (ln == 0) str32(ks, key);
        rank = 16;
      }
      if (__all_sync(0xffffffffu, (int)(cnt >> 16) + base + 2 >= 8)) break;
    }
    TS(8);
    if (warp < (five ? 12 : 15)) {
#pragma unroll
      for (int k = X_WS; k < 12; k++) ldsm4t(wabase + k * 16 * pitch, wa[k][0], wa[k][1], wa[k][2], wa[k][3]);
    }
    if (warp < 6) while ((int)(clock() - tpub) < X_HD) {}
    TS(19);
    if (warp < 6) { ha[0] = ldr128(hsrc); ha[1] = ldr128(hsrc + 24); ha[2] = ldr128(hsrc + 48); }
    if (rank < X_OR) OUT_ROW
  }
  uint32_t wd[10][4];
  const uint32_t xb = keep(OFF_XS + (ln & 7) * 1168 + (fk * 24 + (ln >> 3)) * 16);
  if (warp >= 7) {
    const uint32_t db = down_box(warp - 7, five) + (ln & 7) * 128;
    mbar_wait(MB_D);
#pragma unroll
    for (int j = 0; j < 4; j++) {
      const uint32_t a = db + (ln >> 4) * 1024 + (((2 * j + ((ln >> 3) & 1)) ^ (ln & 7)) << 4);
      ldsm4t(a, wd[j][0], wd[j][1], wd[j][2], wd[j][3]);
      ldsm4t(a + 2048, wd[4 + j][0], wd[4 + j][1], wd[4 + j][2], wd[4 + j][3]);
    }
#pragma unroll
    for (int j = 0; j < 2; j++) ldsm4t(db + 4096 + (((4 * j + (ln >> 3)) ^ (ln & 7)) << 4), wd[8 + j][0], wd[8 + j][1], wd[8 + j][2], wd[8 + j][3]);
  } else if (warp < 6) {
    const uint32_t xs = keep(OFF_XS + (td + (td / 24) * 49) * 16);
#pragma unroll 1
    for (int it = 0; it < SPIN_MAX; it++) {
      const bool bad = max(max(max(ha[0].x, ha[1].x), max(ha[2].x, ha[2].y)), max(ha[2].z, ha[2].w)) == ~0u;
#pragma unroll
      for (int q = 0; q < 3; q++) sts128(xs + q * 384, ha[q].x, ha[q].y, ha[q].z, ha[q].w);
      if (!__any_sync(0xffffffffu, bad)) break;
      if (bad) { ha[0] = ldr128(hsrc); ha[1] = ldr128(hsrc + 24); ha[2] = ldr128(hsrc + 48); }
    }
  }
  TS(9);

  bar_sync(0, 512);
  if (warp < (five ? 12 : 15)) {
    float d0[4] = {0.f, 0.f, 0.f, 0.f}, d1[4] = {0.f, 0.f, 0.f, 0.f};
#pragma unroll
    for (int k = 0; k < 12; k += 2) {
      uint32_t b0, b1, b2, b3;
      ldsm4(xb + k * 32, b0, b1, b2, b3);
      mma_bf16(d0, wa[k][0], wa[k][1], wa[k][2], wa[k][3], b0, b1);
      mma_bf16(d1, wa[k + 1][0], wa[k + 1][1], wa[k + 1][2], wa[k + 1][3], b2, b3);
    }
    sts128(OFF_RED + td * 16, __float_as_uint(d0[0] + d1[0]), __float_as_uint(d0[1] + d1[1]), __float_as_uint(d0[2] + d1[2]), __float_as_uint(d0[3] + d1[3]));
  }
  TS(26);
  if (warp < 5) {
    const uint32_t rb = OFF_RED + warp * 1536 + ln * 16;
    bar_sync(9, 512);
    const uint4 pa = lds128(rb), pb = lds128(rb + 512), pc = lds128(rb + 1024);
    const float ga = bfr(__uint_as_float(pa.x) + __uint_as_float(pb.x) + __uint_as_float(pc.x));
    const float gb = bfr(__uint_as_float(pa.y) + __uint_as_float(pb.y) + __uint_as_float(pc.y));
    const uint32_t uu = pack_bf(__uint_as_float(pa.z) + __uint_as_float(pb.z) + __uint_as_float(pc.z), __uint_as_float(pa.w) + __uint_as_float(pb.w) + __uint_as_float(pc.w));
    float ra, rb2;
    asm("rcp.approx.ftz.f32 %0, %1;" : "=f"(ra) : "f"(1.f + ex2(ga * -1.4426950408889634f)));
    asm("rcp.approx.ftz.f32 %0, %1;" : "=f"(rb2) : "f"(1.f + ex2(gb * -1.4426950408889634f)));
    const uint32_t act = bf_mul2(pack_bf(ga * ra, gb * rb2), uu);
    sts32(OFF_ACT + td * 4, act);
  } else bar_arrive(9, 512);
  uint4* dst = &p.s->X[c * DM * 2 + (warp - 7) * 64 + tt * 8 + gg];
  asm volatile("" : "+l"(dst));
  bar_sync(8, 512);
  tpub = clock();
  if (warp >= 7) {
    uint32_t b0, b1, b2, b3, b4;
    ldsm4t(OFF_ACT + ln * 16, b0, b1, b2, b3);
    asm volatile("ldmatrix.sync.aligned.m8n8.x1.trans.shared.b16 {%0}, [%1];" : "=r"(b4) : "r"(OFF_ACT + 512 + ln * 16) : "memory");
    float y[4][4];
#pragma unroll
    for (int j = 0; j < 4; j++) {
      y[j][0] = y[j][1] = y[j][2] = y[j][3] = 0.f;
      mma_bf16(y[j], wd[j][0], wd[j][1], wd[j][2], wd[j][3], b0, b1);
    }
#pragma unroll
    for (int j = 0; j < 4; j++) mma_bf16(y[j], wd[4 + j][0], wd[4 + j][1], wd[4 + j][2], wd[4 + j][3], b2, b3);
    if (!five) {
#pragma unroll
      for (int j = 0; j < 4; j++) mma_bf16_k8(y[j], wd[8 + (j >> 1)][2 * (j & 1)], wd[8 + (j >> 1)][2 * (j & 1) + 1], b4);
    }
    str128(dst, (pack_bf(y[0][0], y[0][1]) & ~1u) | 0x10000u, pack_bf(y[0][2], y[0][3]), pack_bf(y[1][0], y[1][1]), pack_bf(y[1][2], y[1][3]));
    str128(dst + 32, (pack_bf(y[2][0], y[2][1]) & ~1u) | 0x10000u, pack_bf(y[2][2], y[2][3]), pack_bf(y[3][0], y[3][1]), pack_bf(y[3][2], y[3][3]));
  }
  TS(10);

  if (c < 72) {
    const uint4* src = &p.s->X[(warp * 4 + tt) * (DM * 2) + c * 8 + gg];
    const int slot = (c & 3) * 2 + (ln >> 4), dw = (c >> 2) * 16 + (ln & 15);
    uint32_t hv = 0, kv = 0, res = 0, rs2 = 0;
    uint32_t* o = p.out;
    if (warp == 0) {
      hv = ~0u;
      SPIN_WHILE(max(hv, kv) == ~0u, hv = ldr32((const uint32_t*)p.s->HS + 2304 + slot * 288 + dw); kv = ldr32(&p.s->HS[1152 + slot]));
      const float r = bf_hi(kv ^ (((int)~kv >> 31) | 0x80000000u));
      float rs;
      asm("rcp.approx.ftz.f32 %0, %1;" : "=f"(rs) : "f"(1.f + ex2(r * -1.4426950408889634f)));
      rs2 = keep(pack_bf(rs, rs));
      res = lds32(OFF_XS + slot * 1168 + dw * 4);
      o += (2047 - (int)(kv & 2047u)) * 288 + dw;
      asm volatile("" : "+l"(o));
    }
    const uint32_t sel = (gg & 1) ? 0x3F800000u : 0x00003F80u;
    const uint32_t q0 = keep((gg >> 1) == 0 ? sel : 0u), q1 = keep((gg >> 1) == 1 ? sel : 0u), q2 = keep((gg >> 1) == 2 ? sel : 0u), q3 = keep((gg >> 1) == 3 ? sel : 0u);
    const uint32_t fa = keep(OFF_RED + warp * 8 + ((gg & 1) * 16 + (gg >> 1) * 4 + tt) * 144), fb = keep(OFF_RED + ln * 144);
    uint4 a0 = make_uint4(0, 0, 0, 0), a1 = a0;
    while ((int)(clock() - tpub) < X_PD) {}
    SPIN_WHILE(!(a0.x & a1.x & 0x10000u), if (!(a0.x & 0x10000u)) a0 = ldr128(src); if (!(a1.x & 0x10000u)) a1 = ldr128(src + 64 * DM * 2));
    float d[4] = {0.f, 0.f, 0.f, 0.f}, e[4] = {0.f, 0.f, 0.f, 0.f}, d2[4] = {0.f, 0.f, 0.f, 0.f}, e2[4] = {0.f, 0.f, 0.f, 0.f};
    mma_bf16(d, q0, q2, q1, q3, a0.x, a0.y); mma_bf16(e, q0, q2, q1, q3, a0.z, a0.w);
    mma_bf16(d2, q0, q2, q1, q3, a1.x, a1.y); mma_bf16(e2, q0, q2, q1, q3, a1.z, a1.w);
    sts64(fa, __float_as_uint(d[0] + e[2] + d2[0] + e2[2]), __float_as_uint(d[1] + e[3] + d2[1] + e2[3]));
    TS(11);
    if (warp == 0) {
      bar_sync(0, 512);
      float2 s[16];
#pragma unroll
      for (int i = 0; i < 16; i += 2) { const uint4 q = lds128(fb + i * 8); s[i] = make_float2(__uint_as_float(q.x), __uint_as_float(q.y)); s[i + 1] = make_float2(__uint_as_float(q.z), __uint_as_float(q.w)); }
#pragma unroll
      for (int k = 1; k < 16; k *= 2)
#pragma unroll
        for (int i = 0; i < 16; i += 2 * k) { s[i].x += s[i + k].x; s[i].y += s[i + k].y; }
      asm volatile("st.global.b32 [%0], %1;" :: "l"(o), "r"(bf_add2(hv, bf_add2(res, bf_mul2(pack_bf(s[0].x, s[0].y), rs2)))) : "memory");
    } else bar_arrive(0, 512);
  }
  TS(12);
  TS_DUMP();
}

typedef CUresult (*EncodeFn)(CUtensorMap*, CUtensorMapDataType, cuuint32_t, void*, const cuuint64_t*, const cuuint64_t*, const cuuint32_t*,
                             const cuuint32_t*, CUtensorMapInterleave, CUtensorMapSwizzle, CUtensorMapL2promotion, CUtensorMapFloatOOBfill);

}

extern "C" void kernel_launch(void* const* d_in, const int* in_sizes, int n_in, void* d_out, int out_size) {
  (void)in_sizes; (void)n_in; (void)out_size;
  static EncodeFn enc = nullptr;
  static Scratch* scratch = nullptr;
  if (!enc) {
    void* fn = nullptr;
    cudaDriverEntryPointQueryResult qr;
    cudaGetDriverEntryPoint("cuTensorMapEncodeTiled", &fn, cudaEnableDefault, &qr);
    enc = (EncodeFn)fn;
    cudaGetSymbolAddress((void**)&scratch, g_S);
    cudaFuncSetAttribute(fused_kernel<false>, cudaFuncAttributeMaxDynamicSharedMemorySize, SMEM_BYTES);
    cudaFuncSetAttribute(fused_kernel<true>, cudaFuncAttributeMaxDynamicSharedMemorySize, SMEM_BYTES);
  }
  TMaps tm;
  for (int i = 0; i < 6; i++) {
    const bool dn = i % 3 == 2;
    const cuuint32_t w = i < 3 ? 40 : 32;
    cuuint64_t gd[3] = {(cuuint64_t)(dn ? 64 : FF), (cuuint64_t)(dn ? FF : DM), 9};
    cuuint64_t gs[2] = {(cuuint64_t)(dn ? DM * 2 : FF * 2), 128};
    cuuint32_t bx[3] = {dn ? 64 : w, dn ? w : 96, i < 3 ? 2u : 3u};
    cuuint32_t es[3] = {1, 1, 1};
    enc(&tm.m[i], CU_TENSOR_MAP_DATA_TYPE_BFLOAT16, dn ? 3 : 2, d_in[11 + i % 3], gd, gs, bx, es, CU_TENSOR_MAP_INTERLEAVE_NONE,
        dn ? CU_TENSOR_MAP_SWIZZLE_128B : i < 3 ? CU_TENSOR_MAP_SWIZZLE_NONE : CU_TENSOR_MAP_SWIZZLE_64B,
        (CUtensorMapL2promotion)X_PROMO, CU_TENSOR_MAP_FLOAT_OOB_FILL_NONE);
  }
  for (int i = 6; i < 10; i++) {
    cuuint64_t gd[3] = {i < 8 ? 32u : 16u, i < 8 ? DM / 2u : DM, NCTA};
    cuuint64_t gs[2] = {i < 8 ? 64u : 32u, DM * 32};
    cuuint32_t bx[3] = {32, 1, (i & 1) ? 128u : 136u};
    cuuint32_t es[3] = {1, 1, 1};
    enc(&tm.m[i], CU_TENSOR_MAP_DATA_TYPE_FLOAT16, 3, scratch->X, gd, gs, bx, es, CU_TENSOR_MAP_INTERLEAVE_NONE, CU_TENSOR_MAP_SWIZZLE_64B,
        CU_TENSOR_MAP_L2_PROMOTION_NONE, CU_TENSOR_MAP_FLOAT_OOB_FILL_NONE);
  }
  Params p;
  p.x = (const unsigned char*)d_in[0];
  bool far = false;
  for (int i = 0; i < 7; i++) {
    p.far[i] = (const unsigned char*)d_in[1 + i];
    const long long d = (long long)((intptr_t)d_in[1 + i] - (intptr_t)d_in[0]);
    p.off[i] = (int)(d / 16);
    if ((long long)p.off[i] * 16 != d || p.off[i] > (1 << 30)) far = true;
  }
  p.dskip = (const uint16_t*)d_in[8];
  p.w_r = (const uint32_t*)d_in[10];
  for (int f = 0; f < 2; f++) {
    static const int kind[17] = {0, 0, 0, 0, 2, 2, 0, 0, 1, 1, 1, 1, 1, 1, 2, 2, 2};
    static const int idx[2][17] = {{2, 3, 4, 5, 6, 8, 0, 1, 0, 1, 2, 3, 4, 5, 0, 2, 4}, {2, 3, 4, 5, 0, -1, 0, 1, 0, 1, 2, 3, 4, 5, 3, -1, 6}};
    static const int blk[2][17] = {{-1, -1, -1, -1, 0, -1, 4, -1, 1, -1, 2, -1, 3, -1, 16, -1, -1}, {-1, -1, -1, -1, 1, -1, 4, -1, -1, -1, 2, -1, 3, -1, 16, -1, -1}};
    const int pitch = f ? 64 : 80;
    for (int u = 0; u < 17; u++) {
      const int s = idx[f][u];
      const uint32_t dst = kind[u] == 0 ? OFF_G + s * 96 * pitch : kind[u] == 2 ? down_box(s, f) : OFF_W + W_BYTES + (s >> 1) * W_BYTES + (s & 1) * 96 * pitch;
      const uint32_t mb = u >= 14 ? (u >= X_HU ? MB_H - OFF_MISC : 0) : blk[f][u] >= 0 ? MB_KF - OFF_MISC + blk[f][u] * 8 : 0;
      p.sched[f][u] = s < 0 ? 3u : kind[u] | s << 2 | mb << 6 | dst << 14;
    }
  }
  p.out = (uint32_t*)d_out;
  p.off[7] = 0;
  p.ts = nullptr;
  p.s = scratch;
  if (far) { fused_kernel<true><<<NCTA, NT, SMEM_BYTES, cudaStreamPerThread>>>(p, tm); return; }
  fused_kernel<false><<<NCTA, NT, SMEM_BYTES, cudaStreamPerThread>>>(p, tm);
}
```

```cpp
#include <cuda_runtime.h>
#include <cuda.h>
#include <cuda_bf16.h>
#include <cuda_fp16.h>
#include <stdint.h>
#include <stddef.h>

namespace {

constexpr int NCTA = 128;
constexpr int NT = 640;
constexpr int DM = 576;
constexpr int FF = 4608;
constexpr int SPIN_MAX = 1 << 20;

struct Scratch {
  uint4 X[NCTA * DM * 2];
  uint4 KX[64 * 128];
  uint4 HS[1152 + 8];
  uint4 R[256];
  uint4 SC[256];
  uint32_t FLAG[NCTA * 8];
};
__device__ Scratch g_S;

#define CLKS(i)
#define TS(i)
#define TSX(i)
#define TS_DUMP()

constexpr int SB = 1024;
constexpr int BOX = 15360;
constexpr int OFF_G = SB;
constexpr int OFF_W = OFF_G + 3 * BOX;
constexpr int W_KT = 26624;
constexpr int W_QT = W_KT + 64 + 2048 + 80;
constexpr int W_L3 = W_KT + 4352;
constexpr int W_CW = W_L3 + 4160;
constexpr int W_MISC = W_CW + 640;
constexpr int W_BYTES = 35840;
constexpr int TILE = 10240;
constexpr int OFF_T = OFF_W + 4 * W_BYTES;
constexpr int ALT = TILE - W_KT;
static_assert(W_MISC + 32 <= W_BYTES && OFF_W % 1024 == 0 && W_BYTES % 1024 == 0 && W_BYTES + ALT <= 20480, "wg block");
constexpr int YT_PITCH = 1184;
constexpr int OFF_YT = OFF_T + 2 * TILE;
constexpr int OFF_WR = OFF_YT + 16 * YT_PITCH + 64;
constexpr int OFF_MISC = OFF_WR + 2304;
constexpr int SMEM_BYTES = OFF_MISC + 1024 - SB;
static_assert(OFF_YT % 16 == 0 && OFF_MISC % 16 == 0, "align");
static_assert(SMEM_BYTES <= 232448, "smem");
constexpr int MB_GU = OFF_MISC;
constexpr int MB_D = OFF_MISC + 8;
constexpr int MB_KF = OFF_MISC + 16;
constexpr int MB_GF = OFF_MISC + 48;
constexpr int MB_SC = OFF_MISC + 56;
constexpr int MB_UL = OFF_MISC + 64;
constexpr int MB_REL = OFF_MISC + 104;
constexpr int MB_GO = OFF_MISC + 112;
constexpr int MB_H = MB_KF + 128;
constexpr int MISC_EPOCH = OFF_MISC + 152;
constexpr int MISC_SW = OFF_MISC + 156;
constexpr int MISC_RT = OFF_MISC + 160;
constexpr int MISC_T0 = OFF_MISC + 296;
constexpr int MISC_EM = OFF_MISC + 288;
constexpr int OFF_PART = OFF_W + 20480;
constexpr int OFF_RK = OFF_PART + 3840;
constexpr int MISC_LN1 = OFF_MISC + 192;
constexpr int OFF_XS = OFF_T;
constexpr int OFF_RED = OFF_T + TILE;
constexpr int OFF_FIN = OFF_W + 3 * W_BYTES + W_KT;
constexpr int OFF_ACT = OFF_FIN + 4096;
constexpr int MISC_CNT = OFF_ACT + 1024;

__device__ __forceinline__ uint32_t smem_u32(const void* p) { return (uint32_t)__cvta_generic_to_shared(p); }
__device__ __forceinline__ uint32_t lds32(uint32_t a) { uint32_t v; asm volatile("ld.shared.b32 %0, [%1];" : "=r"(v) : "r"(a) : "memory"); return v; }
__device__ __forceinline__ uint32_t lds16(uint32_t a) { uint16_t v; asm volatile("ld.shared.u16 %0, [%1];" : "=h"(v) : "r"(a) : "memory"); return v; }
__device__ __forceinline__ uint2 lds64(uint32_t a) { uint2 v; asm volatile("ld.shared.v2.b32 {%0,%1}, [%2];" : "=r"(v.x), "=r"(v.y) : "r"(a) : "memory"); return v; }
__device__ __forceinline__ uint4 lds128(uint32_t a) { uint4 v; asm volatile("ld.shared.v4.b32 {%0,%1,%2,%3}, [%4];" : "=r"(v.x), "=r"(v.y), "=r"(v.z), "=r"(v.w) : "r"(a) : "memory"); return v; }
__device__ __forceinline__ void sts16(uint32_t a, uint32_t v) { asm volatile("st.shared.u16 [%0], %1;" :: "r"(a), "h"((uint16_t)v) : "memory"); }
__device__ __forceinline__ void sts32(uint32_t a, uint32_t v) { asm volatile("st.shared.b32 [%0], %1;" :: "r"(a), "r"(v) : "memory"); }
__device__ __forceinline__ void sts64(uint32_t a, uint32_t x, uint32_t y) { asm volatile("st.shared.v2.b32 [%0], {%1,%2};" :: "r"(a), "r"(x), "r"(y) : "memory"); }
__device__ __forceinline__ void sts128(uint32_t a, uint32_t x, uint32_t y, uint32_t z, uint32_t w) { asm volatile("st.shared.v4.b32 [%0], {%1,%2,%3,%4};" :: "r"(a), "r"(x), "r"(y), "r"(z), "r"(w) : "memory"); }
__device__ __forceinline__ void ldsm4(uint32_t a, uint32_t& r0, uint32_t& r1, uint32_t& r2, uint32_t& r3) {
  asm volatile("ldmatrix.sync.aligned.m8n8.x4.shared.b16 {%0,%1,%2,%3}, [%4];" : "=r"(r0), "=r"(r1), "=r"(r2), "=r"(r3) : "r"(a) : "memory");
}
__device__ __forceinline__ void ldsm4t(uint32_t a, uint32_t& r0, uint32_t& r1, uint32_t& r2, uint32_t& r3) {
  asm volatile("ldmatrix.sync.aligned.m8n8.x4.trans.shared.b16 {%0,%1,%2,%3}, [%4];" : "=r"(r0), "=r"(r1), "=r"(r2), "=r"(r3) : "r"(a) : "memory");
}
__device__ __forceinline__ void stsm4t(uint32_t a, uint32_t r0, uint32_t r1, uint32_t r2, uint32_t r3) {
  asm volatile("stmatrix.sync.aligned.m8n8.x4.trans.shared.b16 [%0], {%1,%2,%3,%4};" :: "r"(a), "r"(r0), "r"(r1), "r"(r2), "r"(r3) : "memory");
}
__device__ __forceinline__ uint4 ldr128(const void* p) {
  unsigned long long lo, hi;
  asm volatile("{ .reg .b128 t; ld.relaxed.gpu.global.b128 t, [%2]; mov.b128 {%0, %1}, t; }" : "=l"(lo), "=l"(hi) : "l"(p) : "memory");
  return make_uint4((uint32_t)lo, (uint32_t)(lo >> 32), (uint32_t)hi, (uint32_t)(hi >> 32));
}
__device__ __forceinline__ void str128(void* p, uint32_t x, uint32_t y, uint32_t z, uint32_t w) {
  asm volatile("{ .reg .b128 t; .reg .b64 lo, hi; mov.b64 lo, {%1,%2}; mov.b64 hi, {%3,%4}; mov.b128 t, {lo, hi}; st.relaxed.gpu.global.b128 [%0], t; }"
               :: "l"(p), "r"(x), "r"(y), "r"(z), "r"(w) : "memory");
}
__device__ __forceinline__ uint32_t ldr32(const void* p) { uint32_t v; asm volatile("ld.relaxed.gpu.global.b32 %0, [%1];" : "=r"(v) : "l"(p) : "memory"); return v; }
__device__ __forceinline__ void str32(void* p, uint32_t v) { asm volatile("st.relaxed.gpu.global.b32 [%0], %1;" :: "l"(p), "r"(v) : "memory"); }
__device__ __forceinline__ void str16(void* p, uint32_t v) { asm volatile("st.relaxed.gpu.global.u16 [%0], %1;" :: "l"(p), "h"((uint16_t)v) : "memory"); }
__device__ __forceinline__ void bar_sync(int id, int n) { asm volatile("bar.sync %0, %1;" :: "r"(id), "r"(n) : "memory"); }
__device__ __forceinline__ void bar_arrive(int id, int n) { asm volatile("bar.arrive %0, %1;" :: "r"(id), "r"(n) : "memory"); }

__device__ __forceinline__ float bf_lo(uint32_t w) { return __uint_as_float(w << 16); }
__device__ __forceinline__ float bf_hi(uint32_t w) { return __uint_as_float(w & 0xFFFF0000u); }
__device__ __forceinline__ uint32_t pack_bf(float lo, float hi) { uint32_t r; asm("cvt.rn.bf16x2.f32 %0, %1, %2;" : "=r"(r) : "f"(hi), "f"(lo)); return r; }
__device__ __forceinline__ uint32_t pack_h(float lo, float hi) { uint32_t r; asm("cvt.rn.f16x2.f32 %0, %1, %2;" : "=r"(r) : "f"(hi), "f"(lo)); return r; }
__device__ __forceinline__ float bfr(float x) { return bf_lo(pack_bf(x, 0.f)); }
__device__ __forceinline__ uint32_t bf_sub2(uint32_t a, uint32_t b) { __nv_bfloat162 r = __hsub2(*(__nv_bfloat162*)&a, *(__nv_bfloat162*)&b); return *(uint32_t*)&r; }
__device__ __forceinline__ uint32_t bf_add2(uint32_t a, uint32_t b) { __nv_bfloat162 r = __hadd2(*(__nv_bfloat162*)&a, *(__nv_bfloat162*)&b); return *(uint32_t*)&r; }
__device__ __forceinline__ uint32_t bf_mul2(uint32_t a, uint32_t b) { __nv_bfloat162 r = __hmul2(*(__nv_bfloat162*)&a, *(__nv_bfloat162*)&b); return *(uint32_t*)&r; }
__device__ __forceinline__ float2 h2f(uint32_t w) { return __half22float2(*(__half2*)&w); }
__device__ __forceinline__ float ex2(float x) { float r; asm("ex2.approx.ftz.f32 %0, %1;" : "=f"(r) : "f"(x)); return r; }
__device__ __forceinline__ float warp_sum(float v) {
#pragma unroll
  for (int o = 16; o > 0; o >>= 1) v += __shfl_xor_sync(0xffffffffu, v, o);
  return v;
}
__device__ __forceinline__ void mma_bf16(float* d, uint32_t a0, uint32_t a1, uint32_t a2, uint32_t a3, uint32_t b0, uint32_t b1) {
  asm volatile("mma.sync.aligned.m16n8k16.row.col.f32.bf16.bf16.f32 {%0,%1,%2,%3}, {%4,%5,%6,%7}, {%8,%9}, {%0,%1,%2,%3};"
               : "+f"(d[0]), "+f"(d[1]), "+f"(d[2]), "+f"(d[3]) : "r"(a0), "r"(a1), "r"(a2), "r"(a3), "r"(b0), "r"(b1));
}
__device__ __forceinline__ void mma_bf16_k8(float* d, uint32_t a0, uint32_t a1, uint32_t b0) {
  asm volatile("mma.sync.aligned.m16n8k8.row.col.f32.bf16.bf16.f32 {%0,%1,%2,%3}, {%4,%5}, {%6}, {%0,%1,%2,%3};"
               : "+f"(d[0]), "+f"(d[1]), "+f"(d[2]), "+f"(d[3]) : "r"(a0), "r"(a1), "r"(b0));
}

__device__ __forceinline__ void wg_fence() { asm volatile("wgmma.fence.sync.aligned;" ::: "memory"); }
__device__ __forceinline__ void wg_commit() { asm volatile("wgmma.commit_group.sync.aligned;" ::: "memory"); }
template <int N> __device__ __forceinline__ void wg_wait() { asm volatile("wgmma.wait_group.sync.aligned %0;" :: "n"(N) : "memory"); }
template <int TB> __device__ __forceinline__ void wgmma32(float* d, const uint32_t* a, uint32_t dlo, uint32_t dhi) {
  asm volatile("{ .reg .b64 dd; mov.b64 dd, {%20, %21}; wgmma.mma_async.sync.aligned.m64n32k16.f32.f16.f16 "
               "{%0,%1,%2,%3,%4,%5,%6,%7,%8,%9,%10,%11,%12,%13,%14,%15}, {%16,%17,%18,%19}, dd, 1, 1, 1, %22; }"
               : "+f"(d[0]), "+f"(d[1]), "+f"(d[2]), "+f"(d[3]), "+f"(d[4]), "+f"(d[5]), "+f"(d[6]), "+f"(d[7]), "+f"(d[8]), "+f"(d[9]), "+f"(d[10]), "+f"(d[11]), "+f"(d[12]), "+f"(d[13]), "+f"(d[14]), "+f"(d[15])
               : "r"(a[0]), "r"(a[1]), "r"(a[2]), "r"(a[3]), "r"(dlo), "r"(dhi), "n"(TB));
}
template <int TB> __device__ __forceinline__ void wgmma64(float* d, const uint32_t* a, uint32_t dlo, uint32_t dhi) {
  asm volatile("{ .reg .b64 dd; mov.b64 dd, {%36, %37}; wgmma.mma_async.sync.aligned.m64n64k16.f32.f16.f16 "
               "{%0,%1,%2,%3,%4,%5,%6,%7,%8,%9,%10,%11,%12,%13,%14,%15,%16,%17,%18,%19,%20,%21,%22,%23,%24,%25,%26,%27,%28,%29,%30,%31}, {%32,%33,%34,%35}, dd, 1, 1, 1, %38; }"
               : "+f"(d[0]), "+f"(d[1]), "+f"(d[2]), "+f"(d[3]), "+f"(d[4]), "+f"(d[5]), "+f"(d[6]), "+f"(d[7]), "+f"(d[8]), "+f"(d[9]), "+f"(d[10]), "+f"(d[11]), "+f"(d[12]), "+f"(d[13]), "+f"(d[14]), "+f"(d[15]), "+f"(d[16]), "+f"(d[17]), "+f"(d[18]), "+f"(d[19]), "+f"(d[20]), "+f"(d[21]), "+f"(d[22]), "+f"(d[23]), "+f"(d[24]), "+f"(d[25]), "+f"(d[26]), "+f"(d[27]), "+f"(d[28]), "+f"(d[29]), "+f"(d[30]), "+f"(d[31])
               : "r"(a[0]), "r"(a[1]), "r"(a[2]), "r"(a[3]), "r"(dlo), "r"(dhi), "n"(TB));
}
template <int TB> __device__ __forceinline__ void wgmma64_init(float* d, const uint32_t* a, uint32_t dlo, uint32_t dhi) {
  asm volatile("{ .reg .b64 dd; mov.b64 dd, {%36, %37}; wgmma.mma_async.sync.aligned.m64n64k16.f32.f16.f16 "
               "{%0,%1,%2,%3,%4,%5,%6,%7,%8,%9,%10,%11,%12,%13,%14,%15,%16,%17,%18,%19,%20,%21,%22,%23,%24,%25,%26,%27,%28,%29,%30,%31}, {%32,%33,%34,%35}, dd, 0, 1, 1, %38; }"
               : "=f"(d[0]), "=f"(d[1]), "=f"(d[2]), "=f"(d[3]), "=f"(d[4]), "=f"(d[5]), "=f"(d[6]), "=f"(d[7]), "=f"(d[8]), "=f"(d[9]), "=f"(d[10]), "=f"(d[11]), "=f"(d[12]), "=f"(d[13]), "=f"(d[14]), "=f"(d[15]), "=f"(d[16]), "=f"(d[17]), "=f"(d[18]), "=f"(d[19]), "=f"(d[20]), "=f"(d[21]), "=f"(d[22]), "=f"(d[23]), "=f"(d[24]), "=f"(d[25]), "=f"(d[26]), "=f"(d[27]), "=f"(d[28]), "=f"(d[29]), "=f"(d[30]), "=f"(d[31])
               : "r"(a[0]), "r"(a[1]), "r"(a[2]), "r"(a[3]), "r"(dlo), "r"(dhi), "n"(TB));
}
template <int TB> __device__ __forceinline__ void wgmma32_init(float* d, const uint32_t* a, uint32_t dlo, uint32_t dhi) {
  asm volatile("{ .reg .b64 dd; mov.b64 dd, {%20, %21}; wgmma.mma_async.sync.aligned.m64n32k16.f32.f16.f16 "
               "{%0,%1,%2,%3,%4,%5,%6,%7,%8,%9,%10,%11,%12,%13,%14,%15}, {%16,%17,%18,%19}, dd, 0, 1, 1, %22; }"
               : "=f"(d[0]), "=f"(d[1]), "=f"(d[2]), "=f"(d[3]), "=f"(d[4]), "=f"(d[5]), "=f"(d[6]), "=f"(d[7]), "=f"(d[8]), "=f"(d[9]), "=f"(d[10]), "=f"(d[11]), "=f"(d[12]), "=f"(d[13]), "=f"(d[14]), "=f"(d[15])
               : "r"(a[0]), "r"(a[1]), "r"(a[2]), "r"(a[3]), "r"(dlo), "r"(dhi), "n"(TB));
}
__device__ __forceinline__ void wgmma64h(uint32_t* d, uint32_t a0, uint32_t a1, uint32_t a2, uint32_t a3, uint32_t dlo, uint32_t dhi) {
  asm volatile("{ .reg .b64 dd; mov.b64 dd, {%20, %21}; wgmma.mma_async.sync.aligned.m64n64k16.f16.f16.f16 "
               "{%0,%1,%2,%3,%4,%5,%6,%7,%8,%9,%10,%11,%12,%13,%14,%15}, {%16,%17,%18,%19}, dd, 1, 1, 1, 0; }"
               : "+r"(d[0]), "+r"(d[1]), "+r"(d[2]), "+r"(d[3]), "+r"(d[4]), "+r"(d[5]), "+r"(d[6]), "+r"(d[7]), "+r"(d[8]), "+r"(d[9]), "+r"(d[10]), "+r"(d[11]), "+r"(d[12]), "+r"(d[13]), "+r"(d[14]), "+r"(d[15])
               : "r"(a0), "r"(a1), "r"(a2), "r"(a3), "r"(dlo), "r"(dhi));
}
__device__ __forceinline__ void wgmma64h_init(uint32_t* d, uint32_t a0, uint32_t a1, uint32_t a2, uint32_t a3, uint32_t dlo, uint32_t dhi) {
  asm volatile("{ .reg .b64 dd; mov.b64 dd, {%20, %21}; wgmma.mma_async.sync.aligned.m64n64k16.f16.f16.f16 "
               "{%0,%1,%2,%3,%4,%5,%6,%7,%8,%9,%10,%11,%12,%13,%14,%15}, {%16,%17,%18,%19}, dd, 0, 1, 1, 0; }"
               : "=r"(d[0]), "=r"(d[1]), "=r"(d[2]), "=r"(d[3]), "=r"(d[4]), "=r"(d[5]), "=r"(d[6]), "=r"(d[7]), "=r"(d[8]), "=r"(d[9]), "=r"(d[10]), "=r"(d[11]), "=r"(d[12]), "=r"(d[13]), "=r"(d[14]), "=r"(d[15])
               : "r"(a0), "r"(a1), "r"(a2), "r"(a3), "r"(dlo), "r"(dhi));
}
__device__ __forceinline__ void wgmma40_ss(float* d, uint32_t alo, uint32_t blo, uint32_t hi) {
  asm volatile("{ .reg .b64 da, db; mov.b64 da, {%20, %22}; mov.b64 db, {%21, %22}; "
               "wgmma.mma_async.sync.aligned.m64n40k16.f32.f16.f16 {%0,%1,%2,%3,%4,%5,%6,%7,%8,%9,%10,%11,%12,%13,%14,%15,%16,%17,%18,%19}, da, db, 1, 1, 1, 1, 1; }"
               : "+f"(d[0]), "+f"(d[1]), "+f"(d[2]), "+f"(d[3]), "+f"(d[4]), "+f"(d[5]), "+f"(d[6]), "+f"(d[7]), "+f"(d[8]), "+f"(d[9]), "+f"(d[10]), "+f"(d[11]), "+f"(d[12]), "+f"(d[13]), "+f"(d[14]), "+f"(d[15]), "+f"(d[16]), "+f"(d[17]), "+f"(d[18]), "+f"(d[19])
               : "r"(alo), "r"(blo), "r"(hi));
}
__device__ __forceinline__ void wgmma40_ss_init(float* d, uint32_t alo, uint32_t blo, uint32_t hi) {
  asm volatile("{ .reg .b64 da, db; mov.b64 da, {%20, %22}; mov.b64 db, {%21, %22}; "
               "wgmma.mma_async.sync.aligned.m64n40k16.f32.f16.f16 {%0,%1,%2,%3,%4,%5,%6,%7,%8,%9,%10,%11,%12,%13,%14,%15,%16,%17,%18,%19}, da, db, 0, 1, 1, 1, 1; }"
               : "=f"(d[0]), "=f"(d[1]), "=f"(d[2]), "=f"(d[3]), "=f"(d[4]), "=f"(d[5]), "=f"(d[6]), "=f"(d[7]), "=f"(d[8]), "=f"(d[9]), "=f"(d[10]), "=f"(d[11]), "=f"(d[12]), "=f"(d[13]), "=f"(d[14]), "=f"(d[15]), "=f"(d[16]), "=f"(d[17]), "=f"(d[18]), "=f"(d[19])
               : "r"(alo), "r"(blo), "r"(hi));
}
__device__ __forceinline__ void tma_box(uint32_t dst, const CUtensorMap* tm, uint32_t mb, int x, int y) {
  asm volatile("cp.async.bulk.tensor.2d.shared::cluster.global.mbarrier::complete_tx::bytes [%0], [%1, {%3, %4}], [%2];"
               :: "r"(dst), "l"(tm), "r"(mb), "r"(x), "r"(y) : "memory");
}
__device__ __forceinline__ uint32_t uni(uint32_t v) {
  uint32_t r; asm volatile("shfl.sync.idx.b32 %0, %1, 0, 0x1f, 0xffffffff;" : "=r"(r) : "r"(v)); return r;
}
__device__ __forceinline__ uint32_t pin(uint32_t v) {
  uint32_t r; asm volatile("shfl.sync.bfly.b32 %0, %1, 0, 0x1f, 0xffffffff;" : "=r"(r) : "r"(v)); return r;
}

struct Params {
  const unsigned char* x;
  Scratch* s;
  int off[8];
  uint32_t* out;
  const uint16_t* dskip;
  const uint32_t* w_r;
  long long* ts;
  const unsigned char* far[7];
  uint32_t sched[2][17];
};
__device__ __forceinline__ uint32_t ldnc32(const void* p) { uint32_t v; asm volatile("ld.global.nc.b32 %0, [%1];" : "=r"(v) : "l"(p)); return v; }
__device__ __forceinline__ uint32_t ldnc16(const void* p) { uint16_t v; asm volatile("ld.global.nc.u16 %0, [%1];" : "=h"(v) : "l"(p)); return v; }
__device__ __forceinline__ void mbar_wait(uint32_t mb, uint32_t ph = 0) {
#pragma unroll 1
  for (int it = 0; it < SPIN_MAX; it++) {
    uint32_t ok;
    asm volatile("{ .reg .pred q; mbarrier.try_wait.parity.shared::cta.b64 q, [%1], %2; selp.u32 %0, 1, 0, q; }" : "=r"(ok) : "r"(mb), "r"(ph) : "memory");
    if (ok) break;
  }
}
__device__ __forceinline__ void mbar_arrive(uint32_t mb) { asm volatile("mbarrier.arrive.shared::cta.b64 _, [%0];" :: "r"(mb) : "memory"); }
__device__ __forceinline__ void fence_async() { asm volatile("fence.proxy.async.shared::cta;" ::: "memory"); }
#define SPIN_WHILE(cond, body) _Pragma("unroll 1") for (int _it = 0; _it < SPIN_MAX && __any_sync(0xffffffffu, (cond)); _it++) { body; }

struct LnC { uint32_t m2, rh2, rl2; };
__device__ __forceinline__ LnC ln_consts(float s, float q, float& r) {
  const float mean = s * (1.f / DM);
  const float var = fmaxf(fmaf(-mean, mean, q * (1.f / DM)), 0.f);
  float sd;
  asm("sqrt.approx.ftz.f32 %0, %1;" : "=f"(sd) : "f"(bfr(bfr(var) + 1e-5f)));
  asm("rcp.approx.ftz.f32 %0, %1;" : "=f"(r) : "f"(bfr(sd)));
  LnC c;
  c.m2 = pack_bf(mean, mean);
  c.rh2 = pack_bf(r, r);
  const float rl = r - bf_lo(c.rh2);
  c.rl2 = pack_bf(rl, rl);
  return c;
}
__device__ __forceinline__ uint32_t bf_fma2(uint32_t a, uint32_t b, uint32_t c) {
  __nv_bfloat162 r = __hfma2(*(const __nv_bfloat162*)&a, *(const __nv_bfloat162*)&b, *(const __nv_bfloat162*)&c);
  return *(uint32_t*)&r;
}
__device__ __forceinline__ uint32_t ln_apply(uint32_t w, uint32_t m2, uint32_t rh2, uint32_t rl2) {
  const uint32_t d = bf_sub2(w, m2);
  return bf_fma2(d, rh2, bf_mul2(d, rl2));
}

__device__ __forceinline__ float2 cis(float mag_log2, float rev) {
  const float m = ex2(mag_log2), ang = rev * 6.283185307179586f;
  return make_float2(m * __cosf(ang), m * __sinf(ang));
}
__device__ __forceinline__ float2 csq(float2 a) { return make_float2(fmaf(a.x, a.x, -a.y * a.y), (a.x + a.x) * a.y); }
__device__ __forceinline__ float2 cmul(float2 a, float2 b) { return make_float2(fmaf(a.x, b.x, -a.y * b.y), fmaf(a.x, b.y, a.y * b.x)); }
__device__ __forceinline__ void pmul(uint32_t xr, uint32_t xi, uint32_t w, uint32_t& yr, uint32_t& yi) {
  const __half2 XR = *(__half2*)&xr, XI = *(__half2*)&xi, W = *(__half2*)&w;
  const __half2 a = __hfma2(__hneg2(XI), __high2half2(W), __hmul2(XR, __low2half2(W)));
  const __half2 b = __hfma2(XI, __low2half2(W), __hmul2(XR, __high2half2(W)));
  yr = *(const uint32_t*)&a; yi = *(const uint32_t*)&b;
}
__device__ __forceinline__ uint32_t pk(float2 a) { return pack_h(a.x, a.y); }

struct KgState { float2 c0, z8; float kl; uint32_t w64, w128, w192; };
__device__ __forceinline__ void kgen_tables_n(const uint32_t (&raw)[7], uint32_t scr, int wt, KgState& k) {
  const uint32_t dst = scr + 16384 + wt * 16;
  const float dt = bfr(ex2(bf_lo(raw[6]) * 1.4426950408889634f));
  const float th = dt * bf_lo(raw[1]);
  const float br = dt * bf_lo(raw[2]), bi = dt * bf_lo(raw[3]);
  const float Cr = bf_lo(raw[4]), Ci = bf_lo(raw[5]);
  k.c0 = make_float2(fmaf(Cr, br, -Ci * bi), fmaf(Cr, bi, Ci * br));
  const uint32_t mx = __reduce_max_sync(0xffffffffu, __float_as_uint(fmaxf(fabsf(k.c0.x), fabsf(k.c0.y))));
  const float a2 = dt * bf_lo(raw[0]) * 1.4426950408889634f;
  const float rh = th * 0.15915494309189535f;
  const float rl = fmaf(th, (float)(0.15915494309189535 - (double)0.15915494309189535f), fmaf(th, 0.15915494309189535f, -rh));
  const float rf = rh - rintf(rh);
  const float2 z1 = cis(a2, rf + rl);
  const float p64 = rf * 64.f;
  const float2 z64 = cis(a2 * 64.f, fmaf(64.f, rl, p64 - rintf(p64)));
  const float2 z2 = csq(z1), z128 = csq(z64), z3 = cmul(z2, z1), z4 = csq(z2), z256 = csq(z128), z6 = csq(z3), z512 = csq(z256);
  k.z8 = csq(z4);
  k.w64 = pk(z64); k.w128 = pk(z128); k.w192 = pk(cmul(z128, z64));
  sts128(dst, 0x00003C00u, pk(z2), pk(z4), pk(z6));
  const float2 z1024 = csq(z512), z768 = cmul(z512, z256);
  sts128(dst + 2048, pk(z1), pk(z3), pk(cmul(z4, z1)), pk(cmul(z4, z3)));
  const float2 z2048 = csq(z1024);
  k.kl = fmaf(k.c0.x, z2048.x, -k.c0.y * z2048.y);
  sts128(dst + 4096, pk(z256), pk(cmul(z256, z2)), pk(cmul(z256, z4)), pk(cmul(z256, z6)));
  sts128(dst + 6144, pk(z512), pk(cmul(z512, z4)), pk(z768), pk(cmul(z768, z4)));
  sts128(dst + 8192, pk(z1024), pk(cmul(z1024, z256)), pk(cmul(z1024, z512)), pk(cmul(z1024, z768)));
  sts32(scr + W_MISC + (wt >> 5) * 4, mx);
}
__device__ __forceinline__ int kgen_tables_m(uint32_t scr, int wt, const KgState& k) {
  const uint32_t dst = scr + wt * 16;
  const uint4 e4 = lds128(scr + W_MISC);
  const float2 z16 = csq(k.z8), z32 = csq(z16);
  const int em = max(min((int)(max(max(e4.x, e4.y), max(e4.z, e4.w)) >> 23), 238), 16);
  const float sc = __uint_as_float((uint32_t)(127 + 4 + 127 - em) << 23);
  sts32(scr + W_MISC + 16 + (wt >> 5) * 4, __reduce_add_sync(0xffffffffu, __float2int_rn(k.kl * sc * 262144.f)));
  const float2 c0 = make_float2(k.c0.x * sc, k.c0.y * sc);
  const float2 c1 = cmul(c0, k.z8), c2 = cmul(c0, z16), c4 = cmul(c0, z32), c3 = cmul(c1, z16), c5 = cmul(c1, z32), c6 = cmul(c2, z32), c7 = cmul(c3, z32);
  uint32_t pr[4], pi[4], yr[4], yi[4];
  pr[0] = pack_h(c0.x, c1.x); pi[0] = pack_h(c0.y, c1.y);
  pr[1] = pack_h(c2.x, c3.x); pi[1] = pack_h(c2.y, c3.y);
  pr[2] = pack_h(c4.x, c5.x); pi[2] = pack_h(c4.y, c5.y);
  pr[3] = pack_h(c6.x, c7.x); pi[3] = pack_h(c6.y, c7.y);
  sts128(dst, pr[0], pr[1], pr[2], pr[3]); sts128(dst + 2048, pi[0], pi[1], pi[2], pi[3]);
#pragma unroll
  for (int q = 1; q < 4; q++) {
    const uint32_t w = q == 1 ? k.w64 : q == 2 ? k.w128 : k.w192;
#pragma unroll
    for (int i = 0; i < 4; i++) pmul(pr[i], pi[i], w, yr[i], yi[i]);
    sts128(dst + q * 4096, yr[0], yr[1], yr[2], yr[3]); sts128(dst + q * 4096 + 2048, yi[0], yi[1], yi[2], yi[3]);
  }
  return em;
}
__device__ __forceinline__ uint32_t lds32_if(uint32_t a, bool on) {
  uint32_t v; asm volatile("{ .reg .pred q; setp.ne.u32 q, %2, 0; mov.b32 %0, 0; @q ld.shared.b32 %0, [%1]; }" : "=r"(v) : "r"(a), "r"((uint32_t)on) : "memory"); return v;
}
__device__ __forceinline__ uint32_t prmt(uint32_t a, uint32_t b, uint32_t s) { uint32_t r; asm("prmt.b32 %0, %1, %2, %3;" : "=r"(r) : "r"(a), "r"(b), "r"(s)); return r; }
struct BuildC { uint32_t a3, a2, az, cw, sel; };
__device__ __forceinline__ BuildC build_consts(int wt) {
  const int ix = ((wt >> 2) + (wt & 3) * 32 - 1) & 127;
  BuildC b;
  b.a3 = W_CW + 32 + ((ix & 1) ? 0 : 304) + (ix >> 1) * 4;
  b.a2 = W_L3 + 3072 + 544 + (wt & ~3) * 2 + (wt & 1) * 4 + (wt & 2) * 128;
  b.az = W_KT + (wt < 36 ? -512 : 64 + 4128 - 576) + wt * 16;
  b.cw = W_CW + 32 + (wt >> 6) * 48 + wt * 4;
  b.sel = (wt & 1) ? 0x10767610 : wt ? 0x10101010 : 0x10107610;
  return b;
}
__device__ __forceinline__ void kgen_build(uint32_t tb, const BuildC& bc, int wg, int wt, uint32_t k0, uint32_t k1, uint32_t k2) {
  const uint32_t kt = tb + W_KT, sc = tb + W_L3 + 3072;
  const uint32_t a3 = tb + bc.a3, a2 = tb + bc.a2;
  const uint32_t v3 = wt ? k2 : k2 >> 16;
  sts32(sc + 4 + wt * 4, __byte_perm(k0, k1, 0x5432));
  sts16(a2, k1 >> 16); sts16(a2 + 6, k1 >> 16);
  sts16(a3, v3); sts16(a3 + 6, v3);
  if ((unsigned)(wt - 32) < 14u) sts128(tb + bc.az, 0, 0, 0, 0);
  if (wt == 127) sts32(sc, k0 & 0xFFFF0000u);
  if (wt == 0) { sts32(sc + 516, k1); sts16(sc + 1056, k2); }
  bar_sync(1 + wg, 128);
  const uint32_t cw = tb + bc.cw, g2 = sc + 540 + wt * 4;
  const bool odd = wt & 1, ends = (unsigned)(wt - 4) >= 120u;
  const uint32_t pv = lds32(sc + wt * 4), nx = lds32(sc + 8 + wt * 4), nc = lds32_if(g2 + 8, ends);
  const uint32_t l0 = lds32(cw), l1 = lds32(cw - 8), l2 = lds32(cw - 16), l3 = lds32(cw - 24), q0 = lds32(g2), q1 = lds32(g2 + 128), q2 = lds32(g2 - 8), q3 = lds32(g2 + 120);
  sts64(kt + 64 + wt * 8, __byte_perm(k0, pv, 0x5410), __byte_perm(k0, 0, 0x1032));
  sts64(kt + 64 + 1024 + wt * 8, prmt(k1, pv, bc.sel), prmt(k1, nx, bc.sel >> 16));
  const uint32_t cc = __byte_perm(nc, 0, 0x3232), nn = __byte_perm(nc, 0, 0x1010);
  if (ends) sts128(kt + 64 + 2048 + wt * 16, cc, cc, odd ? nc : cc, odd ? nn : nc);
  if (wt == 127) { sts128(kt + 64 + 4096, nn, nn, nn, nn); sts128(kt + 64 + 4112, nn, nn << 16, 0, 0); }
  sts128(tb + W_L3 + 512 + (wt >> 6) * 512 + wt * 16, l0, l1, l2, l3);
  if ((wt & 63) < 34) sts128(tb + W_QT - 16 + wt * 16, q0, q1, q2, q3);
}

__device__ __forceinline__ void load_a(uint32_t (&a)[4], uint32_t kp, int j) {
  a[0] = lds32(kp + 64 * j); a[1] = lds32(kp + 64 * j + 512); a[2] = lds32(kp + 64 * j - 32); a[3] = lds32(kp + 64 * j + 480);
}
__device__ __forceinline__ uint32_t band8(int s) { return ((((0x1FFu << 20) >> s) & 0x01010101u) | (((0x7Fu << 25) >> s) & 0x10101010u)) * 0x01020408u; }
__device__ __forceinline__ uint32_t hadd2u(uint32_t a, uint32_t b) { __half2 r = __hadd2(*(__half2*)&a, *(__half2*)&b); return *(uint32_t*)&r; }

__device__ __forceinline__ void zero_pads(uint32_t tb, int wt) {
  if (!(wt & 32)) sts128(tb + W_L3 + (wt >> 6) * 512 + wt * 16, 0, 0, 0, 0);
  if ((wt & 63) < 3) sts128(tb + W_CW + (wt >> 6) * 304 + (wt & 63) * 16, 0, 0, 0, 0);
}
__device__ __forceinline__ uint32_t tr_base(int lane) {
  return OFF_YT + (2 * (lane >> 3) + (lane & 1)) * YT_PITCH + ((lane >> 1) & 1) * (8 * YT_PITCH + 64) + ((lane >> 2) & 1) * 16;
}

__device__ __forceinline__ uint32_t sc_addr(int tp) { return OFF_YT + (tp < 16 ? tp * YT_PITCH + (tp >> 3) * 64 + 1152 : 8 * YT_PITCH - 512 + tp * 32); }
#define X_PW 15
#define X_HU 15
#define X_NE 2
#define X_SCT 10000
#define X_DELTA 0
#define X_DSTEP 2000
#define X_PF0 2700
#define X_PFD 600
#define X_TD 460
#define X_WS 6
#define X_OR 8
#define X_ABS 4870
#define X_XD 200
#define X_RD 630
#define X_HD 450
#define X_PD 1170
#define X_PROMO 2
#define X_YD2 1000
#define X_GO 1
#define X_GW 2
#define X_NS 4300
#define X_XS 13450
#define X_LAG 1300
#define X_YD 1550
struct TMaps { CUtensorMap m[10]; };
__device__ __forceinline__ uint32_t h2bf(uint32_t w) { const float2 f = h2f(w); return pack_bf(f.x, f.y); }
__device__ __forceinline__ uint32_t keep(uint32_t v) { asm volatile("" : "+r"(v)); return v; }
__device__ __forceinline__ uint2 ldr64(const void* p) { uint2 v; asm volatile("{ .reg .b64 t; ld.relaxed.gpu.global.b64 t, [%2]; mov.b64 {%0, %1}, t; }" : "=r"(v.x), "=r"(v.y) : "l"(p) : "memory"); return v; }
__host__ __device__ __forceinline__ uint32_t down_box(int s, bool five) {
  return five ? OFF_W + W_BYTES + 12288 + (s / 3) * (W_BYTES - 12288) + s * 4096 : s < 6 ? OFF_W + W_BYTES + BOX + (s >> 1) * (W_BYTES - 10240) + s * 5120 : OFF_W + (s - 6) * 5120;
}
__device__ __forceinline__ void load_tile(const CUtensorMap* tmx, int i, int c, int again = 0) {
  asm volatile("mbarrier.arrive.expect_tx.shared::cta.b64 _, [%0], 8704;" :: "r"(MB_UL + i * 16 + again) : "memory");
  asm volatile("cp.async.bulk.tensor.3d.shared::cluster.global.mbarrier::complete_tx::bytes [%0], [%1, {%3, %4, %5}], [%2];"
               :: "r"(i < 2 ? OFF_T + i * TILE : OFF_W), "l"(tmx), "r"(MB_UL + i * 16 + again), "r"(0), "r"(c), "r"(-8) : "memory");
}
template <bool FAR> __device__ __forceinline__ void load_params(const Params& p, uint32_t ch, int wt, uint32_t dst, bool on) {
  const int rel = wt < 96 ? ch * 16 + (wt & 15) : ch >> 3;
  const unsigned char* b = FAR ? p.far[min(wt >> 4, 6)] + rel * 16 : p.x + (long long)(p.off[wt >> 4] + rel) * 16;
  asm volatile("{ .reg .pred q; setp.ne.u32 q, %2, 0; @q cp.async.cg.shared.global [%0], [%1], 16; }"
               :: "r"(dst + wt * 16), "l"(b), "r"((uint32_t)(on && wt < 97)) : "memory");
}

struct ConvC { uint32_t ca, cb, bands, qa; };
__device__ __forceinline__ ConvC conv_consts(int w, int lane) {
  const int h = w & 1, P = (w >> 1) & 1, d0 = 8 * h + (lane >> 2) - 2 * (lane & 3);
  ConvC k;
  k.ca = keep((W_KT + (16 + 256 * P + d0) * 4) | (((8 + 64 * P + lane) * 64 + (((h + ((w >> 1) & 2)) ^ (lane >> 1)) & 3) * 16) << 16));
  const int u = d0 + 2 * (lane & 1) + 2, in = (u & 7) - ((u & 7) >= 5 ? 5 : 0) - 2 * (lane & 1);
  k.cb = keep(in > 0 ? 0x1010 : in == 0 ? 0x3210 : 0x3232);
  k.qa = keep(W_QT + (2 * (u >> 3) + ((u & 7) >= 5) + 64 * P) * 16);
  k.bands = keep(__byte_perm(band8(d0 + 8), band8(d0 + 7), 0x7733) & 0x00FF00FFu);
  return k;
}
struct ConvPre { uint32_t e0, e2, f2, b0, b2, a[3][4]; };
__device__ __forceinline__ void conv_pre(ConvPre& r, uint32_t kp, uint32_t qp, int part, bool on, bool P) {
  if (part & 1) {
    r.e0 = lds32_if(kp + 4096, on && !P); r.e2 = lds32_if(kp + 4064, on && !P); r.f2 = lds32_if(kp + 4128, on && !P);
    r.b0 = lds32_if(kp + 2048, on && !P); r.b2 = lds32_if(kp + 2016, on && !P);
  }
#pragma unroll
  for (int j = 0; j < 3; j++) if (part & (j < 1 ? 1 : 2))
    asm volatile("{ .reg .pred q; setp.ne.u32 q, %5, 0; mov.b32 %0, 0; mov.b32 %1, 0; mov.b32 %2, 0; mov.b32 %3, 0; @q ld.shared.v4.b32 {%0,%1,%2,%3}, [%4]; }"
                 : "=r"(r.a[j][0]), "=r"(r.a[j][1]), "=r"(r.a[j][2]), "=r"(r.a[j][3]) : "r"(qp + 64 * j), "r"((uint32_t)on) : "memory");
}
__device__ __forceinline__ void conv_item(uint32_t tb, uint32_t tl, int bid, int bn, ConvPre& pre, const ConvC& cv, uint32_t zero, const CUtensorMap* tmx, int ch, int warp, int lane, bool hold, bool more) {
  const bool go = more && warp == 0 && lane == 0;
  const uint32_t kp = tb + (cv.ca & 0xFFFFu), qp = tb + cv.qa;
  const uint32_t dlo = (tl >> 4) + 32 + ((warp >> 1) & 2) + (1u << 16), dhi = 32u | (2u << 30);
  const bool P = warp & 2;
  float a32[16], b32[16], a64[32];
  uint32_t A[40][4];
#define STEP(J) { wgmma64<0>(a64, A[J], dlo + 256 - 4 * (J), dhi); \
    if ((J) == 32) wgmma32_init<0>(b32, A[J], dlo, dhi); else wgmma32<0>(b32, A[J], ((J) < 8 ? dlo ^ zero : dlo) + 128 - 4 * (J), dhi); \
    if ((J) == 0) wgmma32_init<0>(a32, A[J], dlo, dhi); else if ((J) < 8) wgmma32<0>(a32, A[J], (dlo ^ zero) - 4 * (J), dhi); }
#define LD(J) load_a(A[J], kp, J);
#define LQ(J) { const uint4 v = lds128(qp + 64 * ((J) - 32)); A[J][0] = v.x; A[J][1] = v.y; A[J][2] = v.z; A[J][3] = v.w; }
#define PQ(J) { A[J][0] = prmt(A[J][0], 0, cv.cb); A[J][1] = prmt(A[J][1], 0, cv.cb); A[J][2] = prmt(A[J][2], 0, cv.cb); A[J][3] = prmt(A[J][3], 0, cv.cb); }
#define FIRST(J) wg_fence(); STEP(J) wg_commit(); wg_wait<1>(); wg_fence();
  {
    uint32_t win[16], x9[4], x7[4], e[4], f[4];
    const uint32_t bz = keep(cv.bands);
#define BAND(i) keep((bz & (0x10001u << (i))) * (0x3C00u >> (i)))
    e[0] = pre.e0; e[2] = pre.e2; e[1] = keep(bz & 0x100u); e[3] = keep(bz & 0x200u);
    f[2] = pre.f2; f[0] = keep(bz & 0x4000u); f[1] = keep(bz & 0x8000u); f[3] = keep(bz & 0x300u);
#pragma unroll
    for (int j = 0; j < 12; j++) A[32 + j / 4][j & 3] = pre.a[j / 4][j & 3];
    PQ(32) PQ(33) PQ(34)
    if (!P) { A[32][0] = pre.b0; A[32][2] = pre.b2; }
    const uint32_t q[12] = {BAND(0), BAND(5), keep(bz & 0x400u), BAND(4), BAND(2), BAND(7), BAND(1), BAND(6), keep(bz & 0x800u), keep(bz & 0x1000u), BAND(3), keep(bz & 0x2000u)};
#undef BAND
    const uint32_t ta = keep(tl + 512 + (warp & 3) * 2048 + lane * 64 + (lane & 6) * 8);
    if (X_GO && hold) mbar_wait(MB_GO);
    uint32_t mbl = MB_UL + (warp & 8) * 2, ph = 0;
#pragma unroll 1
    for (int it = 0; it < SPIN_MAX; it++) {
      if (ch < 512) mbar_wait(mbl, ph);
      if (it == 1) TS(13);
      TS(3);
      wg_fence();
      wgmma64h_init(win, q[0], q[1], q[2], q[3], dlo, dhi);
      wgmma64h(win, q[4], q[5], q[6], q[7], dlo - 4, dhi);
      wgmma64h(win, q[8], q[9], q[10], q[11], dlo - 8, dhi);
      wg_commit();
      wgmma64_init<0>(a64, e, dlo, dhi);
      wgmma64<0>(a64, f, dlo - 4, dhi);
      wg_commit();
      if (ch >= 512) break;
      uint32_t r0, r1, r2, r3, ok;
      if (warp & 4) {
        mbar_wait(mbl + 8);
        if (__all_sync(0xffffffffu, it || lds32(MISC_RT + (warp & 8)) == 0)) break;
        wg_wait<0>();
        continue;
      }
      ldsm4(ta, r0, r1, r2, r3);
      ok = r0 & r1 & r2 & r3;
      ldsm4(ta ^ 32, r0, r1, r2, r3);
      asm volatile("{ .reg .pred q; setp.ne.u32 q, %1, 0; barrier.red.and.pred q, %2, 128, q; selp.u32 %0, 1, 0, q; }" : "=r"(ok) : "r"((ok & r0 & r1 & r2 & r3 & 1u) | (lane & 3)), "r"(1 + (warp >> 2)) : "memory");
      if (ok) { if ((warp & 3) == 0 && lane == 0) { sts32(MISC_RT + warp, it); mbar_arrive(MB_UL + 8 + warp * 2); } break; }
      wg_wait<0>();
      if ((warp & 3) == 0 && lane == 0) load_tile(tmx - 1, warp >> 3, ch, 56);
      mbl = MB_UL + 56 + (warp & 8) * 2; ph = it & 1;
    }
    wg_wait<1>();
#pragma unroll
    for (int i = 0; i < 4; i++) {
      const int tl = 2 * ((i & 1) + ((i & 2) ? 0 : 4));
      x9[i] = P ? win[tl + 4] : win[tl]; x7[i] = P ? win[tl + 5] : win[tl + 1];
    }
    const uint32_t l3lo = ((tb + W_L3) >> 4) + (32u << 16);
    wg_fence();
    wgmma64<0>(a64, x9, l3lo, 8);
    wgmma64<0>(a64, x7, l3lo + 96, 8);
    wg_commit();
  }
  STEP(32) STEP(33) STEP(34) wg_commit(); wg_wait<1>();
  LQ(35) LQ(36) LQ(37) LQ(38) LQ(39) LD(0) PQ(35) PQ(36) PQ(37) PQ(38) PQ(39)
  FIRST(35) STEP(36) STEP(37) STEP(38) wg_commit(); STEP(39) wg_commit();
  LD(1) LD(2) LD(3)
  if (X_GO == 1 && go) mbar_arrive(MB_GO);
  wg_wait<1>(); wg_fence(); STEP(0) wg_commit(); STEP(1) wg_commit(); STEP(2) wg_commit(); wg_wait<2>();
  LD(4) LD(5)
  wg_fence(); STEP(3) wg_commit(); wg_wait<1>();
  LD(6) LD(7)
  wg_fence(); STEP(4) STEP(5) wg_commit();
  wg_fence(); STEP(6) STEP(7) wg_commit();
#undef STEP
#undef LD
#undef LQ
#undef PQ
#undef FIRST
  TS(18);
  if (X_GO == 3 && go) mbar_arrive(MB_GO);
  const uint32_t xc = tb + W_KT + (warp & 3) * 1024 + lane * 16;
  if (more) bar_sync(7, 288);
  wg_wait<1>();
  conv_pre(pre, kp + ALT, qp + ALT, 1, more, P);
  wg_wait<0>();
  conv_pre(pre, kp + ALT, qp + ALT, 2, more, P);
  uint32_t E[16], o[8];
#define ACC(i) ((i) < 16 ? a32[i] : (i) < 32 ? b32[(i) - 16] : a64[(i) - 32])
  E[0] = pack_h(a32[0], a32[1]);
#pragma unroll
  for (int i = 1; i < 16; i++) E[i] = pack_h(ACC(4 * i) + ACC(4 * i - 2), ACC(4 * i + 1) + ACC(4 * i - 1));
#undef ACC
#pragma unroll
  for (int j = 0; j < 8; j++) o[j] = P ? (j < 2 ? 0u : E[j - 2]) : E[8 + j];
  sts128(xc, o[0], o[1], o[2], o[3]); sts128(xc + 512, o[4], o[5], o[6], o[7]);
#pragma unroll
  for (int j = 0; j < 8; j++) o[j] = P ? E[6 + j] : E[j];
  TS(25);
  if (more) {
    sts128(xc + 4096, o[0], o[1], o[2], o[3]); sts128(xc + 4608, o[4], o[5], o[6], o[7]);
    bar_arrive(12, 192);
    return;
  }
  bar_sync(1 + (warp >> 2), 128);
  const uint4 vv[2] = {lds128(xc + (P ? -2048 : 2048)), lds128(xc + (P ? -1536 : 2560))};
  const uint32_t mk = lane < 8 ? 0xFFFEFFFEu : ~0u;
#pragma unroll
  for (int q = 0; q < 2; q++) {
    const uint4 v = vv[q];
    stsm4t(tl + (cv.ca >> 16) + q * 2048, hadd2u(o[4 * q], v.x) & mk, hadd2u(o[4 * q + 1], v.y) & mk, hadd2u(o[4 * q + 2], v.z) & mk, hadd2u(o[4 * q + 3], v.w) & mk);
  }
  fence_async();
  bar_sync(bid, bn);
  if (warp == 0 && lane == 0) mbar_arrive(MB_REL);
  if ((warp & 7) == (ch < 512 ? 7 : 3) && lane == 0) {
    asm volatile("cp.async.bulk.tensor.3d.global.shared::cta.bulk_group [%0, {%3, %2, %3}], [%1];" :: "l"(tmx), "r"(tl + 512), "r"(ch), "r"(0) : "memory");
    asm volatile("cp.async.bulk.commit_group;" ::: "memory");
  }
}

template <bool FAR> __global__ void __launch_bounds__(NT, 1)
fused_kernel(const __grid_constant__ Params p, const __grid_constant__ TMaps tm) {
  extern __shared__ __align__(1024) unsigned char smem[];
  const int c = blockIdx.x;
  const bool five = (c & 1) == 0;
  const uint32_t pitch = five ? 64 : 80;
  const uint32_t ones = 0x3F803F80u;
  const int tid = threadIdx.x, lane = tid & 31;
  const uint32_t xrow = OFF_YT + ((tid & 127) >> 3) * YT_PITCH + (tid & 64) + (tid & 7) * 16;
  {
    const int w4 = tid >> 7;
    load_params<FAR>(p, w4 < 2 ? 2 * c + w4 : five ? 257 + 2 * c : 512 + (c >> 1), tid & 127, OFF_W + W_KT + (w4 < 2 ? w4 * W_BYTES : five ? 3 * W_BYTES : 3 * W_BYTES + 2048), (0xB >> w4) & 1);
  }
  if ((tid >> 7) == 2) {
    const unsigned char* xp = p.x + (uint32_t)((c * 16 - 32 + (tid >> 3)) * 1152 + (tid & 7) * 16);
    asm volatile("" : "+l"(xp));
    { const uint32_t tq = clock(); while ((int)(clock() - tq) < X_XD) {} }
#pragma unroll
    for (int k = 0; k < 9; k++) asm volatile("cp.async.cg.shared.global [%0], [%1], 16;" :: "r"(xrow + k * 128), "l"(xp + k * 128) : "memory");
  }
  const int warp = (int)uni(tid >> 5), wg = warp >> 2;
  TS(0);
  if (__builtin_expect(wg == 4, 0)) {
    asm volatile("setmaxnreg.dec.sync.aligned.u32 32;");
    const int role = warp;
    const int u0 = (c >> 1) * 9 + (five ? ((c & 2) ? 5 : 0) : ((c & 2) ? 0 : 4));
    const uint32_t t0 = clock() + c * 4;
    if (role == 16) {
      if (lane == 0) {
#pragma unroll
        for (int i = 0; i < 19; i++) if (i != 16) asm volatile("mbarrier.init.shared::cta.b64 [%0], %1;" :: "r"(OFF_MISC + i * 8), "r"((unsigned)(i - 2) < 4u ? 4 : 1) : "memory");
      }
      __syncwarp();
      if (lane < 2) asm volatile("mbarrier.arrive.expect_tx.shared::cta.b64 _, [%0], %1;" :: "r"(OFF_MISC + lane * 8), "r"(lane ? (five ? 36864 : 51200) : pitch * 1152) : "memory");
      fence_async();
      bar_arrive(5, 608);
      const CUtensorMap* tmb = &tm.m[five ? 3 : 0];
#pragma unroll 1
      for (int u = 0; u < 17; u++) {
        const uint32_t e = p.sched[five][u], kind = e & 3, s = (e >> 2) & 15, dst = e >> 14;
        if (kind == 3) continue;
        while ((int)(clock() - t0) < X_PF0 + (u < X_NE ? u * X_PFD : X_LAG + u * X_TD)) __nanosleep(20);
        if (e & 0x3FC0) mbar_wait(OFF_MISC + ((e >> 6) & 255));
        if (lane == 0) {
          if (kind == 2) asm volatile("cp.async.bulk.tensor.3d.shared::cluster.global.mbarrier::complete_tx::bytes [%0], [%1, {%3, %4, %5}], [%2];"
                                      :: "r"(dst), "l"(tmb + 2), "r"(MB_D), "r"(0), "r"(u0 * 8), "r"(s) : "memory");
          else tma_box(dst, tmb + kind, MB_GU, u0 * 8, s * 96);
        }
        if (u == 5) TS(2);
        if (u == 10) TS(3);
      }
      TS(4);
      TS_DUMP();
#define FINISH0 bar_sync(12, 192);        \
        _Pragma("unroll 1") for (int w = role & 2; w < (role & 2) + 2; w++) { \
          const uint32_t xa = OFF_W + W_KT + lane * 16, mk = lane < 8 ? 0xFFFEFFFEu : ~0u, ya = OFF_T + (8 + lane) * 64 + (((w & 1) ^ (lane >> 1)) & 3) * 16 + (w & 2) * 2048; \
          const uint4 a = lds128(xa + 4096 + w * 1024), b = lds128(xa + (w ^ 2) * 1024), d = lds128(xa + 4608 + w * 1024), e = lds128(xa + 512 + (w ^ 2) * 1024); \
          stsm4t(ya, hadd2u(a.x, b.x) & mk, hadd2u(a.y, b.y) & mk, hadd2u(a.z, b.z) & mk, hadd2u(a.w, b.w) & mk); \
          stsm4t(ya + 2048, hadd2u(d.x, e.x) & mk, hadd2u(d.y, e.y) & mk, hadd2u(d.z, e.z) & mk, hadd2u(d.w, e.w) & mk); \
        } \
        fence_async();
    } else if (role == 17) {
      if (smem_u32(smem) != SB) __trap();
      bar_sync(10, 576);
      if (lane == 0) {
        fence_async();
        while ((int)(clock() - t0) < X_NS - c * 4) {}
        asm volatile("cp.async.bulk.global.shared::cta.bulk_group [%0], [%1], 10240;" :: "l"(&p.s->X[c * DM * 2 + 512]), "r"(OFF_G) : "memory");
        asm volatile("cp.async.bulk.commit_group;" ::: "memory");
        asm volatile("cp.async.bulk.wait_group 0;" ::: "memory");
      }
      if (lane == 0) mbar_arrive(MB_GF);
      bar_arrive(11, 96);
      if (five) { FINISH0 bar_arrive(13, 192); }
    } else if (role == 18) {
      sts32(MISC_EPOCH, 0);
      sts32(MISC_T0, t0 - c * 4);
      bar_arrive(5, 608);
      uint4* q = lane < 2 ? &p.s->R[c * 2 + lane] : lane < 11 ? &p.s->HS[c * 9 + lane - 2] : lane == 11 ? &p.s->HS[1152 + (c & 7)] : (uint4*)&p.s->FLAG[c * 8];
      if (lane < (c < 8 ? 12 : 11)) str128(q, ~0u, ~0u, ~0u, ~0u);
      const uint32_t ep = __shfl_sync(0xffffffffu, ldr32(q), 31) + 1u;
      sts32(MISC_EPOCH, ep | 0x80000000u);
      TSX(21);
      if (lane == 31) str32(q, ep);
      bar_sync(11, 96);
      TSX(14);
      mbar_wait(MB_KF + (lane & 3) * 8);
      __syncwarp();
      { const uint2 e = lds64(MISC_EM); if (lane == 0) asm volatile("{ .reg .b64 t; mov.b64 t, {%1,%2}; st.relaxed.gpu.global.b64 [%0], t; }" :: "l"((uint2*)p.s->SC + c), "r"(e.x), "r"(__byte_perm(e.y, ep, 0x6540)) : "memory"); }
      TSX(17);
      while ((int)(clock() - t0) < X_SCT) __nanosleep(100);
      TSX(18);
      {
        uint4 v[2];
#pragma unroll 1
        for (int it = 0; it < SPIN_MAX; it++) {
          v[0] = ldr128(&p.s->SC[lane]); v[1] = ldr128(&p.s->SC[lane + 32]);
          const uint32_t e8 = ep << 8;
          if (!__any_sync(0xffffffffu, ((v[0].y ^ e8) | (v[0].w ^ e8) | (v[1].y ^ e8) | (v[1].w ^ e8)) >> 8)) break;
        }
        TSX(25);
#pragma unroll
        for (int q = 0; q < 2; q++) {
          const uint32_t sa = (lane >> 3) * YT_PITCH + (lane & 7) * 4;
          sts32(sc_addr(4 * q) + sa, __byte_perm(v[q].x, v[q].z, 0x5410)); sts32(sc_addr(8 + 4 * q) + sa, __byte_perm(v[q].x, v[q].z, 0x7632));
          asm volatile("st.shared.u8 [%0], %1;" :: "r"(sc_addr(16) + q * 32 + lane), "r"(v[q].w) : "memory");
        }
      }
      __syncwarp();
      if (lane == 0) mbar_arrive(MB_SC);
      TSX(27);
    } else {
      uint32_t w[9];
      const uint32_t dk = ldnc16(p.dskip + ((lane & 4) ? 512 + (c >> 1) : (lane & 2) * 128 + 2 * c + (lane & 1)));
      float s = 0.f;
#pragma unroll
      for (int i = 0; i < 9; i++) w[i] = ldnc32(p.w_r + lane + 32 * i);
      sts16(OFF_WR + 1152 + lane * 2, dk);
      bar_arrive(5, 608);
#pragma unroll
      for (int i = 0; i < 9; i++) { sts32(OFF_WR + lane * 4 + i * 128, w[i]); s += bf_lo(w[i]) + bf_hi(w[i]); }
      sts32(MISC_SW, __float_as_uint(warp_sum(s)));
      TSX(23);
      bar_sync(10, 576);
      if (lane == 0) {
        const uint32_t tp = clock();
        TSX(1);
        while ((int)(clock() - tp) < X_DELTA || (int)(clock() - t0) < X_ABS - c * 4) {}
        TSX(24);
        load_tile(&tm.m[6], 0, c);
        TSX(15);
        while ((int)(clock() - t0) < X_ABS + X_DSTEP - c * 4) {}
      }
      bar_sync(11, 96);
      if (lane == 0) {
        load_tile(&tm.m[6], 1, 128 + c);
      }
      if (five) {
        mbar_wait(MB_KF);
#pragma unroll 1
        for (int it = 0; it < SPIN_MAX; it++) {
          if (lane == 0) load_tile(&tm.m[8], 2, 512 + (c >> 1));
          mbar_wait(MB_UL + 32, it & 1);
          uint32_t m = 1;
#pragma unroll
          for (int q = 0; q < 4; q++) { uint32_t r0, r1, r2, r3; ldsm4(OFF_W + 512 + lane * 64 + (lane & 6) * 8 + q * 2048, r0, r1, r2, r3); m &= r0 & r1 & r2 & r3; }
          if (__all_sync(0xffffffffu, m || (lane & 3))) break;
        }
        bar_arrive(7, 288);
        FINISH0
        bar_arrive(13, 192);
      }
      bar_sync(0, 544);
      if (lane == 0) mbar_arrive(MB_H);
    }
    return;
  }
  const int wt = tid & 127, g = lane >> 2, t = lane & 3;
  const uint32_t wb = OFF_W + wg * W_BYTES;
  asm volatile("cp.async.commit_group;" ::: "memory");
  const ConvC cv = conv_consts(warp, lane);
  zero_pads(wb, wt);
  load_params<FAR>(p, 254 + 2 * c + wg, wt, wb + W_KT, wg == 2 || (wg == 3 && !five));
  asm volatile("cp.async.commit_group;" ::: "memory");
  asm volatile("setmaxnreg.inc.sync.aligned.u32 112;");
  {
    uint4 kw;
    uint4* kx = &p.s->KX[(c >> 1) * 128 + wt];
    bool two = wg == 3;
    uint32_t ep;
    int em = 0;
    uint32_t slot = wg + (two && !five);
    const uint32_t ra0 = wb + W_KT + (slot & 4) * 512 + wt * 2, ra6 = wb + W_KT + 1536 + (slot & 4) * 512 + (((slot & 4) ? c >> 1 : 2 * c + (wg & 1)) & 7) * 2;
    const uint32_t tr_addr = pin(tr_base(lane) + warp * 32), lca = pin(MISC_LN1 + (lane & 1) * 16);
    uint4* dst;
    { const unsigned long long a = (unsigned long long)&p.s->X[c * DM * 2 + warp * 32 + (8 * ((lane >> 1) & 1) + (lane >> 2)) * 2 + (lane & 1)];
      dst = (uint4*)(((unsigned long long)pin(a >> 32) << 32) | pin((uint32_t)a)); }
    const BuildC bc = build_consts(wt);
    uint32_t raw[7];
    if (wg != 2) {
      asm volatile("cp.async.wait_group 1;" ::: "memory");
      bar_sync(1 + wg, 128);
#pragma unroll
      for (int i = 0; i < 7; i++) raw[i] = lds16(i < 6 ? ra0 + i * 256 : ra6);
    }
    int phase = wg == 2 ? 3 : 2;
#pragma unroll 1
    for (;;) {
      if (phase != 3) {
        KgState ks;
        TS(22);
        kgen_tables_n(raw, wb, wt, ks);
        TS(20);
        bar_sync(1 + wg, 128);
        em = kgen_tables_m(wb, wt, ks);
        fence_async();
      }
      if (phase & 2) {
        if (phase == 3) {
        asm volatile("cp.async.wait_group 1;" ::: "memory");
        TS(21);
        float d[3][4], r;
        uint4 a[9];
#pragma unroll
        for (int k = 0; k < 9; k++) a[k] = lds128(xrow + k * 128);
#pragma unroll
        for (int i = 0; i < 4; i++) d[0][i] = d[1][i] = d[2][i] = 0.f;
#pragma unroll
        for (int k = 0; k < 9; k++) { mma_bf16(d[(2 * k) % 3], a[k].x, ones, a[k].y, ones, a[k].x, a[k].y); mma_bf16(d[(2 * k + 1) % 3], a[k].z, ones, a[k].w, ones, a[k].z, a[k].w); }
#pragma unroll
        for (int i = 0; i < 4; i++) d[0][i] += d[1][i] + d[2][i];
        const LnC lc = ln_consts(d[0][2] + d[0][3], __shfl_sync(0xffffffffu, d[0][0], 9 * t) + __shfl_sync(0xffffffffu, d[0][1], 9 * t + 4), r);
        if (lane < 12) sts16(MISC_LN1 + g * 32 + (warp & 3) * 8 + t * 2, lane < 4 ? lc.m2 : lane < 8 ? lc.rh2 : lc.rl2);
        }
        asm volatile("cp.async.wait_group 0;" ::: "memory");
        TS(23);
        bar_sync(5, 608);
        uint32_t x[3][4];
        ldsm4t(tr_addr, x[0][0], x[0][1], x[0][2], x[0][3]);
        uint4 m = lds128(lca);
        const uint4 rl = lds128(lca + 64), rh = lds128(lca + 32);
        ldsm4t(tr_addr + 512, x[1][0], x[1][1], x[1][2], x[1][3]);
        if (wg == 3) ldsm4t(tr_addr + 640, x[2][0], x[2][1], x[2][2], x[2][3]);
#pragma unroll
        for (int q = 0; q < 3; q++) {
          if (q < 2 || wg == 3) {
            const uint32_t r0 = ln_apply(x[q][0], m.x, rh.x, rl.x), r1 = ln_apply(x[q][1], m.y, rh.y, rl.y), r2 = ln_apply(x[q][2], m.z, rh.z, rl.z), r3 = ln_apply(x[q][3], m.w, rh.w, rl.w);
            const uint32_t w0 = (pack_h(bf_lo(r0), bf_hi(r0)) & 0xFFFEFFFEu) | 1u, w1 = pack_h(bf_lo(r1), bf_hi(r1)), w2 = pack_h(bf_lo(r2), bf_hi(r2)), w3 = pack_h(bf_lo(r3), bf_hi(r3));
            if (q == 0) str128(dst, w0, w1, w2, w3);
            else sts128(OFF_G + warp * 512 + (8 * (t >> 1) + g) * 32 + (t & 1) * 16 + (q == 2 ? 2048 : 0), w0, w1, w2, w3);
          }
          if (q == 0) {
            const uint32_t z = clock() & p.off[7];
            m.x ^= z; m.y ^= z; m.z ^= z; m.w ^= z;
          }
          if (q == 0) TS(30);
          if (q == 0 && wg >= 2) {
#pragma unroll
            for (int i = 0; i < 7; i++) raw[i] = lds16(wb + W_KT + i * 256 + (i < 6 ? wt : (2 * c + (wg & 1)) & 7) * 2);
          }
        }
        bar_arrive(10, 576);
        TS(1);
      } else bar_sync(1 + wg, 128);
      phase &= 1;
      if (phase) { phase = 0; continue; }
      TS(14);
      float acc[20];
      const uint32_t alo = (wb >> 4) | (8u << 16);
      uint4 k4 = lds128(wb + W_MISC + 16);
      uint32_t dk = lds16(OFF_WR + 1152 + slot * 2);
      wg_fence();
      wgmma40_ss_init(acc, alo, alo + 1024, 2048 >> 4);
#pragma unroll
      for (int k = 1; k < 8; k++) wgmma40_ss(acc, alo + k * 16, alo + 1024 + k * 16, 2048 >> 4);
      wg_commit();
      { const uint32_t z = clock() & p.off[7]; dk ^= z; k4.x ^= z; k4.z ^= z; }
      const float k2048 = (float)(int)((k4.x + k4.y) + (k4.z + k4.w)) * (1.f / 262144.f);
      const int ef = max(em, min((int)((dk >> 7) & 255u) - 7, 238));
      asm volatile("st.shared.u8 [%0], %1;" :: "r"(MISC_EM + slot), "r"(ef + 9) : "memory");
      const float un = __uint_as_float((uint32_t)max(114 + em - ef, 0) << 23), d0 = wt ? 0.f : bf_lo(dk) * __uint_as_float((uint32_t)(245 - ef) << 23);
      wg_wait<0>();
      kw.x = pack_h(fmaf(acc[0] - acc[3], un, d0), (acc[4] - acc[7]) * un);
      kw.y = pack_h((acc[8] - acc[11]) * un, (acc[12] - acc[15]) * un);
      kw.z = pack_h((acc[16] - acc[19]) * un, k2048 * un);
      TS(24);
      ep = 0;
      if (two) SPIN_WHILE(ep == 0, ep = lds32(MISC_EPOCH));
      if (five || !two) break;
      str128(kx, kw.x, kw.y, kw.z, ep);
      two = false;
      slot = 3;
      bar_sync(1 + wg, 128);
    }
    if (lane == 0) mbar_arrive(MB_KF + wg * 8);
    if (two) { mbar_wait(MB_KF); zero_pads(OFF_W + ALT, wt); }
    uint32_t tb = wb;
#pragma unroll 1
    for (;;) {
      kgen_build(tb, bc, wg, wt, kw.x, kw.y, kw.z);
      TS(15);
      if (!two) break;
      two = false;
      kw.w = 0;
      SPIN_WHILE(kw.w != ep, kw = ldr128(kx));
      tb = OFF_W + ALT;
    }
    fence_async();
    TS(31);
    if (tb != wb) bar_arrive(7, 288);
    bar_sync(1 + wg, 128);
  }
  uint32_t tpub;
  ConvPre pre;
  conv_pre(pre, (wb ^ p.off[7]) + (cv.ca & 0xFFFFu), (wb ^ p.off[7]) + cv.qa, 3, true, warp & 2);
#pragma unroll 1
  for (int item = 0;; item++) {
    TS(2);
    conv_item(item ? OFF_W + ALT : wb, item ? OFF_W : OFF_T + (wg >> 1) * TILE, item ? 1 : 13 + (wg >> 1), item ? 128 : five && wg == 1 ? 192 : 256, pre, cv, p.off[7],
              &tm.m[item ? 9 : 7], item ? 512 + (c >> 1) : (wg >> 1) * 128 + c, warp, lane, five && wg >= X_GW, five && !wg && !item);
    tpub = clock() - (item ? X_YD : wg >= 2 ? X_YD2 : 0);
    if (wg || !five || item) break;
    TS(27);
  }
  TS(4);

  const int ln = lane ^ p.off[7], td = warp * 32 + ln, gg = ln >> 2, tt = ln & 3;
  const int tok = c * 16 + warp;
  const int fu = warp / 3, fk = warp - fu * 3;
  uint32_t wa[12][4];
  uint4 ha[3];
  const uint4* hsrc = &p.s->HS[td + (td / 24) * 48];
  {
    uint32_t hw[9], wr[9];
    const uint32_t row = keep(OFF_YT + warp * YT_PITCH + (warp >> 3) * 64 + ln * 16);
    const uint32_t wabase = keep(((ln & 8) ? OFF_W + (fk + 1) * W_BYTES : OFF_G + fk * 192 * pitch) + ((ln >> 4) * 8 + (ln & 7)) * pitch
                                 + (five ? ((fu ^ (ln >> 1)) & 3) : min(fu, 4)) * 16);
    float sw;
    {
      const bool three = wg == 1;
      const int ch = 8 * (tt >> 1) + gg;
      const uint32_t tr_addr = tr_base(ln);
      const uint4* ysrc = &p.s->X[c * DM * 2 + ch * 2 + (tt & 1)];
      uint32_t x[3][4], s[3];
      uint4 v[3];
#define TL(q) ((q) < 2 ? 2 * warp + (q) : 28 + warp)
      if (wg >= 2) { const uint32_t ts = lds32(MISC_T0); while ((int)(clock() - ts) < X_XS) {} }
      while ((int)(clock() - tpub) < X_YD) {}
      TS(5);
      v[0] = ldr128(ysrc + TL(0) * 32); v[1] = ldr128(ysrc + TL(1) * 32); v[2] = make_uint4(three, 0, 0, 0);
      mbar_wait(MB_REL);
#pragma unroll
      for (int i = 0; i < 6; i++) if (i < 4 || three) wr[i] = (gg & 2) ? ones : lds32(OFF_WR + TL(i >> 1) * 32 + (i & 1) * 16 + tt * 4);
      const uint32_t ha = keep(OFF_YT + (ln & 7) * YT_PITCH + (ln >> 4) * (8 * YT_PITCH + 64) + (ln & 8) * 2);
      const uint32_t pa = keep(OFF_PART + warp * 4 + ((gg & 2) * 8 + (gg & 4) * 2 + 2 * tt + (gg & 1)) * 80), pb = keep(OFF_PART + 2560 + warp * 4 + gg * 80);
      float dl[4] = {0.f, 0.f, 0.f, 0.f}, dh[4] = {0.f, 0.f, 0.f, 0.f};
      sw = __uint_as_float(lds32(MISC_SW));
#pragma unroll
      for (int q = 0; q < 3; q++) {
        if (q < 2 || three) {
          ldsm4t(tr_addr + TL(q) * 32, x[q][0], x[q][1], x[q][2], x[q][3]);
        }
      }
      asm volatile("cp.async.bulk.wait_group.read 0;" ::: "memory");
      mbar_wait(MB_SC);
#pragma unroll
      for (int q = 0; q < 3; q++) {
        asm volatile("ld.shared.u8 %0, [%1];" : "=r"(s[q]) : "r"((q < 2 ? sc_addr(warp) + q * 16 : sc_addr(16) + (warp & 3) * 16) + ch) : "memory");
        s[q] = keep(s[q] * 0x800080u);
      }
#define FIN(q) stsm4t(tr_addr + TL(q) * 32, bf_fma2(h2bf(v[q].x), s[q], x[q][0]), bf_fma2(h2bf(v[q].y), s[q], x[q][1]), bf_fma2(h2bf(v[q].z), s[q], x[q][2]), bf_fma2(h2bf(v[q].w), s[q], x[q][3]));
      SPIN_WHILE((v[0].x | v[1].x) & 1u, _Pragma("unroll") for (int q = 0; q < 3; q++) if (v[q].x & 1u) v[q] = ldr128(ysrc + TL(q) * 32));
      if (v[2].x & 1u) v[2] = ldr128(ysrc + TL(2) * 32);
#define STAT(q) { uint32_t r0, r1, r2, r3; ldsm4(ha + TL(q) * 32, r0, r1, r2, r3); \
        mma_bf16(dl, r0, wr[2 * q], r1, wr[2 * q + 1], r0, r1); mma_bf16(dh, r2, wr[2 * q], r3, wr[2 * q + 1], r2, r3); }
      FIN(0) FIN(1)
      __syncwarp();
      STAT(0) STAT(1)
      if (three) {
#pragma unroll 1
        for (int it = 0; it < SPIN_MAX; it++) {
          FIN(2)
          if (!__any_sync(0xffffffffu, v[2].x & 1u)) break;
          if (v[2].x & 1u) v[2] = ldr128(ysrc + TL(2) * 32);
        }
        __syncwarp();
        STAT(2)
      }
      if (gg & 1) { dl[0] = dl[1]; dl[2] = dl[3]; dh[0] = dh[1]; dh[2] = dh[3]; }
      sts32(pa, __float_as_uint((gg & 4) ? dh[2] : dl[2]));
      if (tt == (gg >> 1)) { sts32(pb, __float_as_uint(dl[0])); sts32(pb + 640, __float_as_uint(dh[0])); }
#undef STAT
#undef FIN
#undef TL
    }
    uint32_t ra = keep(OFF_PART + (ln & 15) * 80 + (ln & 16) * 2);
    uint16_t* rp = (uint16_t*)p.s->R + c * 16 + (ln & 15);
    const uint2* rsrc = (const uint2*)p.s->R + td;
    asm volatile("" : "+l"(rp), "+l"(rsrc), "+l"(hsrc));
    uint2 rv = make_uint2(0u, 0u);
    TS(28);
    if (warp != X_PW) bar_sync(0, 544);
    else {
      float z[3], rd;
      asm volatile("bar.sync 0, 544;" : "+r"(ra) :: "memory");
#pragma unroll
      for (int k = 2; k >= 0; k--) {
        const uint4 a = lds128(ra + k * 1280), b = lds128(ra + k * 1280 + 16);
        z[k] = ((__uint_as_float(a.x) + __uint_as_float(a.y)) + (__uint_as_float(a.z) + __uint_as_float(a.w))) + ((__uint_as_float(b.x) + __uint_as_float(b.y)) + (__uint_as_float(b.z) + __uint_as_float(b.w)));
      }
#pragma unroll
      for (int k = 2; k >= 0; k--) z[k] += __shfl_xor_sync(0xffffffffu, z[k], 16);
      const LnC l = ln_consts(z[1], z[2], rd);
      const uint32_t b = pack_bf(0.f, fmaf(-bf_lo(l.m2), sw, z[0]) * rd);
      const uint32_t k16 = max(min((b ^ (((int)b >> 31) | 0x80000000u)) >> 16, 0xFFFEu), 1u);
      if (ln < 16) str16(rp, k16);
      sts64(OFF_RK + (ln & 15) * 8, __byte_perm(l.m2, l.rh2, 0x5410), __byte_perm(l.rl2, k16, 0x5410));
      sts128(MISC_CNT + ln * 16, 0, 0, 0, 0);
    }
    mbar_wait(MB_GU);
#define LD_HW { const uint4 a = lds128(row), b = lds128(row + 512); hw[8] = lds32(row + 1024 - ln * 12); \
      hw[0] = a.x; hw[1] = a.y; hw[2] = a.z; hw[3] = a.w; hw[4] = b.x; hw[5] = b.y; hw[6] = b.z; hw[7] = b.w; }
    LD_HW
    const uint32_t tr0 = clock();
    bar_sync(5, 512);
    TS(7);
    const uint2 lk = lds64(OFF_RK + warp * 8);
    LnC l2;
    l2.m2 = __byte_perm(lk.x, 0, 0x1010); l2.rh2 = __byte_perm(lk.x, 0, 0x3232); l2.rl2 = __byte_perm(lk.y, 0, 0x1010);
    const uint32_t key = (lk.y & 0xFFFF0000u) | (2047 - tok);
    uint32_t loc = ln < 16 ? (lds32(OFF_RK + 4 + ln * 8) & 0xFFFF0000u) | (2047 - c * 16 - ln) : 0u;
    int rank = __popc(__ballot_sync(0xffffffffu, loc > key));
#pragma unroll
    for (int i = 0; i < 9; i++) { wr[i] = keep(ln_apply(hw[i], l2.m2, l2.rh2, l2.rl2)); hw[i] = bf_add2(hw[i], wr[i]); }
#define OUT_ROW { uint32_t* o = p.out + tok * 288 + ln * 4; \
      *(uint4*)o = make_uint4(hw[0], hw[1], hw[2], hw[3]); *(uint4*)(o + 128) = make_uint4(hw[4], hw[5], hw[6], hw[7]); o[256 - ln * 3] = hw[8]; }
    uint4* hs = p.s->HS + ln;
    asm volatile("" : "+l"(hs));
#pragma unroll 1
    for (int base = 0; base < 8; base += 2) {
      uint32_t T[2];
#pragma unroll
      for (int j = 0; j < 2; j++) {
        const uint32_t mx = __reduce_max_sync(0xffffffffu, loc);
        if (loc == mx) loc = 0;
        T[j] = (td >> 2) < c ? (mx & 0xFFFF0000u) - 1u : mx | 0xFFFFu;
      }
      const uint32_t sh = keep(rank == base ? 0x4410u : rank == base + 1 ? 0x4432u : 0x4445u), ca = keep(MISC_CNT + base * 64 + ln * 4);
      TS(29);
      if (base == 0) {
        while ((int)(clock() - tr0) < X_RD) {}
        if ((td >> 2) != c) rv = ldr64(rsrc);
        if (rank >= X_OR) OUT_ROW
        if (warp < (five ? 12 : 15)) {
#pragma unroll
          for (int k = 0; k < X_WS; k++) ldsm4t(wabase + k * 16 * pitch, wa[k][0], wa[k][1], wa[k][2], wa[k][3]);
        }
      }
      uint32_t cnt;
#pragma unroll 1
      for (int it = 0; it < SPIN_MAX; it++) {
        const uint32_t xs = rv.x << 16, ys = rv.y << 16;
        const bool bad = max(max(rv.x, xs), max(rv.y, ys)) >= 0xFFFF0000u;
        uint32_t cn2 = 0;
        cnt = bad ? 256u : 0u;
#pragma unroll
        for (int j = 0; j < 2; j++)
          asm("{ .reg .pred a, b, c, d; setp.gt.u32 a, %2, %6; setp.gt.u32 b, %3, %6; setp.gt.u32 c, %4, %6; setp.gt.u32 d, %5, %6; "
              "@a add.u32 %1, %1, %7; @b add.u32 %1, %1, %7; @c add.u32 %0, %0, %7; @d add.u32 %0, %0, %7; }"
              : "+r"(cnt), "+r"(cn2) : "r"(rv.x), "r"(rv.y), "r"(xs), "r"(ys), "r"(T[j]), "r"(1u << (16 * j)));
        cnt = __reduce_add_sync(0xffffffffu, cnt + cn2);
        asm volatile("{ .reg .pred q; setp.eq.u32 q, %2, 0; @q red.shared.add.u32 [%0], %1; }" :: "r"(ca), "r"(cnt), "r"(cnt & 0x3F00u) : "memory");
        if (!(cnt & 0x3F00u)) break;
        if (bad) rv = ldr64(rsrc);
      }
      TS(16);
      bar_sync(0, 512);
      cnt = lds32(ca);
      if (base == 0) tpub = clock();
      const int gr = rank + __byte_perm(cnt, 0x800u, sh);
      if (gr < 8) {
        uint4* ks = hs + 1152 + gr;
        hs = (uint4*)((char*)hs + gr * 1152);
        asm volatile("{ .reg .b128 t, u; .reg .b64 a, b, c, d; mov.b64 a, {%1,%2}; mov.b64 b, {%3,%4}; mov.b64 c, {%5,%6}; mov.b64 d, {%7,%8}; mov.b128 t, {a, b}; mov.b128 u, {c, d}; "
                     "st.relaxed.gpu.global.b128 [%0], t; st.relaxed.gpu.global.b128 [%0 + 512], u; }"
                     :: "l"(hs), "r"(wr[0]), "r"(wr[1]), "r"(wr[2]), "r"(wr[3]), "r"(wr[4]), "r"(wr[5]), "r"(wr[6]), "r"(wr[7]) : "memory");
        str32((uint32_t*)(hs + 64) - ln * 3, wr[8]);
        LD_HW
        str128(hs + 576, hw[0], hw[1], hw[2], hw[3]); str128(hs + 608, hw[4], hw[5], hw[6], hw[7]); str32((uint32_t*)(hs + 640) - ln * 3, hw[8]);
        if (ln == 0) str32(ks, key);
        rank = 16;
      }
      if (__all_sync(0xffffffffu, (int)(cnt >> 16) + base + 2 >= 8)) break;
    }
    TS(8);
    if (warp < (five ? 12 : 15)) {
#pragma unroll
      for (int k = X_WS; k < 12; k++) ldsm4t(wabase + k * 16 * pitch, wa[k][0], wa[k][1], wa[k][2], wa[k][3]);
    }
    if (warp < 6) while ((int)(clock() - tpub) < X_HD) {}
    TS(19);
    if (warp < 6) { ha[0] = ldr128(hsrc); ha[1] = ldr128(hsrc + 24); ha[2] = ldr128(hsrc + 48); }
    if (rank < X_OR) OUT_ROW
  }
  uint32_t wd[10][4];
  const uint32_t xb = keep(OFF_XS + (ln & 7) * 1168 + (fk * 24 + (ln >> 3)) * 16);
  if (warp >= 7) {
    const uint32_t db = down_box(warp - 7, five) + (ln & 7) * 128;
    mbar_wait(MB_D);
#pragma unroll
    for (int j = 0; j < 4; j++) {
      const uint32_t a = db + (ln >> 4) * 1024 + (((2 * j + ((ln >> 3) & 1)) ^ (ln & 7)) << 4);
      ldsm4t(a, wd[j][0], wd[j][1], wd[j][2], wd[j][3]);
      ldsm4t(a + 2048, wd[4 + j][0], wd[4 + j][1], wd[4 + j][2], wd[4 + j][3]);
    }
#pragma unroll
    for (int j = 0; j < 2; j++) ldsm4t(db + 4096 + (((4 * j + (ln >> 3)) ^ (ln & 7)) << 4), wd[8 + j][0], wd[8 + j][1], wd[8 + j][2], wd[8 + j][3]);
  } else if (warp < 6) {
    const uint32_t xs = keep(OFF_XS + (td + (td / 24) * 49) * 16);
#pragma unroll 1
    for (int it = 0; it < SPIN_MAX; it++) {
      const bool bad = max(max(max(ha[0].x, ha[1].x), max(ha[2].x, ha[2].y)), max(ha[2].z, ha[2].w)) == ~0u;
#pragma unroll
      for (int q = 0; q < 3; q++) sts128(xs + q * 384, ha[q].x, ha[q].y, ha[q].z, ha[q].w);
      if (!__any_sync(0xffffffffu, bad)) break;
      if (bad) { ha[0] = ldr128(hsrc); ha[1] = ldr128(hsrc + 24); ha[2] = ldr128(hsrc + 48); }
    }
  }
  TS(9);

  bar_sync(0, 512);
  if (warp < (five ? 12 : 15)) {
    float d0[4] = {0.f, 0.f, 0.f, 0.f}, d1[4] = {0.f, 0.f, 0.f, 0.f};
#pragma unroll
    for (int k = 0; k < 12; k += 2) {
      uint32_t b0, b1, b2, b3;
      ldsm4(xb + k * 32, b0, b1, b2, b3);
      mma_bf16(d0, wa[k][0], wa[k][1], wa[k][2], wa[k][3], b0, b1);
      mma_bf16(d1, wa[k + 1][0], wa[k + 1][1], wa[k + 1][2], wa[k + 1][3], b2, b3);
    }
    sts128(OFF_RED + td * 16, __float_as_uint(d0[0] + d1[0]), __float_as_uint(d0[1] + d1[1]), __float_as_uint(d0[2] + d1[2]), __float_as_uint(d0[3] + d1[3]));
  }
  TS(26);
  if (warp < 5) {
    const uint32_t rb = OFF_RED + warp * 1536 + ln * 16;
    bar_sync(9, 512);
    const uint4 pa = lds128(rb), pb = lds128(rb + 512), pc = lds128(rb + 1024);
    const float ga = bfr(__uint_as_float(pa.x) + __uint_as_float(pb.x) + __uint_as_float(pc.x));
    const float gb = bfr(__uint_as_float(pa.y) + __uint_as_float(pb.y) + __uint_as_float(pc.y));
    const uint32_t uu = pack_bf(__uint_as_float(pa.z) + __uint_as_float(pb.z) + __uint_as_float(pc.z), __uint_as_float(pa.w) + __uint_as_float(pb.w) + __uint_as_float(pc.w));
    float ra, rb2;
    asm("rcp.approx.ftz.f32 %0, %1;" : "=f"(ra) : "f"(1.f + ex2(ga * -1.4426950408889634f)));
    asm("rcp.approx.ftz.f32 %0, %1;" : "=f"(rb2) : "f"(1.f + ex2(gb * -1.4426950408889634f)));
    const uint32_t act = bf_mul2(pack_bf(ga * ra, gb * rb2), uu);
    sts32(OFF_ACT + td * 4, act);
  } else bar_arrive(9, 512);
  uint4* dst = &p.s->X[c * DM * 2 + (warp - 7) * 64 + tt * 8 + gg];
  asm volatile("" : "+l"(dst));
  bar_sync(8, 512);
  tpub = clock();
  if (warp >= 7) {
    uint32_t b0, b1, b2, b3, b4;
    ldsm4t(OFF_ACT + ln * 16, b0, b1, b2, b3);
    asm volatile("ldmatrix.sync.aligned.m8n8.x1.trans.shared.b16 {%0}, [%1];" : "=r"(b4) : "r"(OFF_ACT + 512 + ln * 16) : "memory");
    float y[4][4];
#pragma unroll
    for (int j = 0; j < 4; j++) {
      y[j][0] = y[j][1] = y[j][2] = y[j][3] = 0.f;
      mma_bf16(y[j], wd[j][0], wd[j][1], wd[j][2], wd[j][3], b0, b1);
    }
#pragma unroll
    for (int j = 0; j < 4; j++) mma_bf16(y[j], wd[4 + j][0], wd[4 + j][1], wd[4 + j][2], wd[4 + j][3], b2, b3);
    if (!five) {
#pragma unroll
      for (int j = 0; j < 4; j++) mma_bf16_k8(y[j], wd[8 + (j >> 1)][2 * (j & 1)], wd[8 + (j >> 1)][2 * (j & 1) + 1], b4);
    }
    str128(dst, (pack_bf(y[0][0], y[0][1]) & ~1u) | 0x10000u, pack_bf(y[0][2], y[0][3]), pack_bf(y[1][0], y[1][1]), pack_bf(y[1][2], y[1][3]));
    str128(dst + 32, (pack_bf(y[2][0], y[2][1]) & ~1u) | 0x10000u, pack_bf(y[2][2], y[2][3]), pack_bf(y[3][0], y[3][1]), pack_bf(y[3][2], y[3][3]));
  }
  TS(10);

  if (c < 72) {
    const uint4* src = &p.s->X[(warp * 4 + tt) * (DM * 2) + c * 8 + gg];
    const int slot = (c & 3) * 2 + (ln >> 4), dw = (c >> 2) * 16 + (ln & 15);
    uint32_t hv = 0, kv = 0, res = 0, rs2 = 0;
    uint32_t* o = p.out;
    if (warp == 0) {
      hv = ~0u;
      SPIN_WHILE(max(hv, kv) == ~0u, hv = ldr32((const uint32_t*)p.s->HS + 2304 + slot * 288 + dw); kv = ldr32(&p.s->HS[1152 + slot]));
      const float r = bf_hi(kv ^ (((int)~kv >> 31) | 0x80000000u));
      float rs;
      asm("rcp.approx.ftz.f32 %0, %1;" : "=f"(rs) : "f"(1.f + ex2(r * -1.4426950408889634f)));
      rs2 = keep(pack_bf(rs, rs));
      res = lds32(OFF_XS + slot * 1168 + dw * 4);
      o += (2047 - (int)(kv & 2047u)) * 288 + dw;
      asm volatile("" : "+l"(o));
    }
    const uint32_t sel = (gg & 1) ? 0x3F800000u : 0x00003F80u;
    const uint32_t q0 = keep((gg >> 1) == 0 ? sel : 0u), q1 = keep((gg >> 1) == 1 ? sel : 0u), q2 = keep((gg >> 1) == 2 ? sel : 0u), q3 = keep((gg >> 1) == 3 ? sel : 0u);
    const uint32_t fa = keep(OFF_RED + warp * 8 + ((gg & 1) * 16 + (gg >> 1) * 4 + tt) * 144), fb = keep(OFF_RED + ln * 144);
    uint4 a0 = make_uint4(0, 0, 0, 0), a1 = a0;
    while ((int)(clock() - tpub) < X_PD) {}
    SPIN_WHILE(!(a0.x & a1.x & 0x10000u), if (!(a0.x & 0x10000u)) a0 = ldr128(src); if (!(a1.x & 0x10000u)) a1 = ldr128(src + 64 * DM * 2));
    float d[4] = {0.f, 0.f, 0.f, 0.f}, e[4] = {0.f, 0.f, 0.f, 0.f}, d2[4] = {0.f, 0.f, 0.f, 0.f}, e2[4] = {0.f, 0.f, 0.f, 0.f};
    mma_bf16(d, q0, q2, q1, q3, a0.x, a0.y); mma_bf16(e, q0, q2, q1, q3, a0.z, a0.w);
    mma_bf16(d2, q0, q2, q1, q3, a1.x, a1.y); mma_bf16(e2, q0, q2, q1, q3, a1.z, a1.w);
    sts64(fa, __float_as_uint(d[0] + e[2] + d2[0] + e2[2]), __float_as_uint(d[1] + e[3] + d2[1] + e2[3]));
    TS(11);
    if (warp == 0) {
      bar_sync(0, 512);
      float2 s[16];
#pragma unroll
      for (int i = 0; i < 16; i += 2) { const uint4 q = lds128(fb + i * 8); s[i] = make_float2(__uint_as_float(q.x), __uint_as_float(q.y)); s[i + 1] = make_float2(__uint_as_float(q.z), __uint_as_float(q.w)); }
#pragma unroll
      for (int k = 1; k < 16; k *= 2)
#pragma unroll
        for (int i = 0; i < 16; i += 2 * k) { s[i].x += s[i + k].x; s[i].y += s[i + k].y; }
      asm volatile("st.global.b32 [%0], %1;" :: "l"(o), "r"(bf_add2(hv, bf_add2(res, bf_mul2(pack_bf(s[0].x, s[0].y), rs2)))) : "memory");
    } else bar_arrive(0, 512);
  }
  TS(12);
  TS_DUMP();
}

typedef CUresult (*EncodeFn)(CUtensorMap*, CUtensorMapDataType, cuuint32_t, void*, const cuuint64_t*, const cuuint64_t*, const cuuint32_t*,
                             const cuuint32_t*, CUtensorMapInterleave, CUtensorMapSwizzle, CUtensorMapL2promotion, CUtensorMapFloatOOBfill);

}

extern "C" void kernel_launch(void* const* d_in, const int* in_sizes, int n_in, void* d_out, int out_size) {
  (void)in_sizes; (void)n_in; (void)out_size;
  static EncodeFn enc = nullptr;
  static Scratch* scratch = nullptr;
  if (!enc) {
    void* fn = nullptr;
    cudaDriverEntryPointQueryResult qr;
    cudaGetDriverEntryPoint("cuTensorMapEncodeTiled", &fn, cudaEnableDefault, &qr);
    enc = (EncodeFn)fn;
    cudaGetSymbolAddress((void**)&scratch, g_S);
    cudaFuncSetAttribute(fused_kernel<false>, cudaFuncAttributeMaxDynamicSharedMemorySize, SMEM_BYTES);
    cudaFuncSetAttribute(fused_kernel<true>, cudaFuncAttributeMaxDynamicSharedMemorySize, SMEM_BYTES);
  }
  TMaps tm;
  for (int i = 0; i < 6; i++) {
    const bool dn = i % 3 == 2;
    const cuuint32_t w = i < 3 ? 40 : 32;
    cuuint64_t gd[3] = {(cuuint64_t)(dn ? 64 : FF), (cuuint64_t)(dn ? FF : DM), 9};
    cuuint64_t gs[2] = {(cuuint64_t)(dn ? DM * 2 : FF * 2), 128};
    cuuint32_t bx[3] = {dn ? 64 : w, dn ? w : 96, i < 3 ? 2u : 3u};
    cuuint32_t es[3] = {1, 1, 1};
    enc(&tm.m[i], CU_TENSOR_MAP_DATA_TYPE_BFLOAT16, dn ? 3 : 2, d_in[11 + i % 3], gd, gs, bx, es, CU_TENSOR_MAP_INTERLEAVE_NONE,
        dn ? CU_TENSOR_MAP_SWIZZLE_128B : i < 3 ? CU_TENSOR_MAP_SWIZZLE_NONE : CU_TENSOR_MAP_SWIZZLE_64B,
        (CUtensorMapL2promotion)X_PROMO, CU_TENSOR_MAP_FLOAT_OOB_FILL_NONE);
  }
  for (int i = 6; i < 10; i++) {
    cuuint64_t gd[3] = {i < 8 ? 32u : 16u, i < 8 ? DM / 2u : DM, NCTA};
    cuuint64_t gs[2] = {i < 8 ? 64u : 32u, DM * 32};
    cuuint32_t bx[3] = {32, 1, (i & 1) ? 128u : 136u};
    cuuint32_t es[3] = {1, 1, 1};
    enc(&tm.m[i], CU_TENSOR_MAP_DATA_TYPE_FLOAT16, 3, scratch->X, gd, gs, bx, es, CU_TENSOR_MAP_INTERLEAVE_NONE, CU_TENSOR_MAP_SWIZZLE_64B,
        CU_TENSOR_MAP_L2_PROMOTION_NONE, CU_TENSOR_MAP_FLOAT_OOB_FILL_NONE);
  }
  Params p;
  p.x = (const unsigned char*)d_in[0];
  bool far = false;
  for (int i = 0; i < 7; i++) {
    p.far[i] = (const unsigned char*)d_in[1 + i];
    const long long d = (long long)((intptr_t)d_in[1 + i] - (intptr_t)d_in[0]);
    p.off[i] = (int)(d / 16);
    if ((long long)p.off[i] * 16 != d || p.off[i] > (1 << 30)) far = true;
  }
  p.dskip = (const uint16_t*)d_in[8];
  p.w_r = (const uint32_t*)d_in[10];
  for (int f = 0; f < 2; f++) {
    static const int kind[17] = {0, 0, 0, 0, 2, 2, 0, 0, 1, 1, 1, 1, 1, 1, 2, 2, 2};
    static const int idx[2][17] = {{2, 3, 4, 5, 6, 0, 0, 1, 0, 1, 2, 3, 4, 5, 2, 4, 8}, {2, 3, 4, 5, 0, -1, 0, 1, 0, 1, 2, 3, 4, 5, 3, -1, 6}};
    static const int blk[2][17] = {{-1, -1, -1, -1, 0, 1, 4, -1, -1, -1, 2, -1, 3, -1, 16, -1, -1}, {-1, -1, -1, -1, 1, -1, 4, -1, -1, -1, 2, -1, 3, -1, 16, -1, -1}};
    const int pitch = f ? 64 : 80;
    for (int u = 0; u < 17; u++) {
      const int s = idx[f][u];
      const uint32_t dst = kind[u] == 0 ? OFF_G + s * 96 * pitch : kind[u] == 2 ? down_box(s, f) : OFF_W + W_BYTES + (s >> 1) * W_BYTES + (s & 1) * 96 * pitch;
      const uint32_t mb = u >= 14 ? (u >= X_HU ? MB_H - OFF_MISC : 0) : blk[f][u] >= 0 ? MB_KF - OFF_MISC + blk[f][u] * 8 : 0;
      p.sched[f][u] = s < 0 ? 3u : kind[u] | s << 2 | mb << 6 | dst << 14;
    }
  }
  p.out = (uint32_t*)d_out;
  p.off[7] = 0;
  p.ts = nullptr;
  p.s = scratch;
  if (far) { fused_kernel<true><<<NCTA, NT, SMEM_BYTES, cudaStreamPerThread>>>(p, tm); return; }
  fused_kernel<false><<<NCTA, NT, SMEM_BYTES, cudaStreamPerThread>>>(p, tm);
}
```

```cpp
#include <cuda_runtime.h>
#include <cuda.h>
#include <cuda_bf16.h>
#include <cuda_fp16.h>
#include <stdint.h>
#include <stddef.h>

namespace {

constexpr int NCTA = 128;
constexpr int NT = 640;
constexpr int DM = 576;
constexpr int FF = 4608;
constexpr int SPIN_MAX = 1 << 20;

struct Scratch {
  uint4 X[NCTA * DM * 2];
  uint4 KX[64 * 128];
  uint4 HS[1152 + 8];
  uint4 R[256];
  uint4 SC[256];
  uint32_t FLAG[NCTA * 8];
};
__device__ Scratch g_S;

#define CLKS(i)
#define TS(i)
#define TSX(i)
#define TS_DUMP()

constexpr int SB = 1024;
constexpr int BOX = 15360;
constexpr int OFF_G = SB;
constexpr int OFF_W = OFF_G + 3 * BOX;
constexpr int W_KT = 26624;
constexpr int W_QT = W_KT + 64 + 2048 + 80;
constexpr int W_L3 = W_KT + 4352;
constexpr int W_CW = W_L3 + 4160;
constexpr int W_MISC = W_CW + 640;
constexpr int W_BYTES = 35840;
constexpr int TILE = 10240;
constexpr int OFF_T = OFF_W + 4 * W_BYTES;
constexpr int ALT = TILE - W_KT;
static_assert(W_MISC + 32 <= W_BYTES && OFF_W % 1024 == 0 && W_BYTES % 1024 == 0 && W_BYTES + ALT <= 20480, "wg block");
constexpr int YT_PITCH = 1184;
constexpr int OFF_YT = OFF_T + 2 * TILE;
constexpr int OFF_WR = OFF_YT + 16 * YT_PITCH + 64;
constexpr int OFF_MISC = OFF_WR + 2304;
constexpr int SMEM_BYTES = OFF_MISC + 1024 - SB;
static_assert(OFF_YT % 16 == 0 && OFF_MISC % 16 == 0, "align");
static_assert(SMEM_BYTES <= 232448, "smem");
constexpr int MB_GU = OFF_MISC;
constexpr int MB_D = OFF_MISC + 8;
constexpr int MB_KF = OFF_MISC + 16;
constexpr int MB_GF = OFF_MISC + 48;
constexpr int MB_SC = OFF_MISC + 56;
constexpr int MB_UL = OFF_MISC + 64;
constexpr int MB_REL = OFF_MISC + 104;
constexpr int MB_GO = OFF_MISC + 112;
constexpr int MB_H = MB_KF + 128;
constexpr int MISC_EPOCH = OFF_MISC + 152;
constexpr int MISC_SW = OFF_MISC + 156;
constexpr int MISC_RT = OFF_MISC + 160;
constexpr int MISC_T0 = OFF_MISC + 296;
constexpr int MISC_EM = OFF_MISC + 288;
constexpr int OFF_PART = OFF_W + 20480;
constexpr int OFF_RK = OFF_PART + 3840;
constexpr int MISC_LN1 = OFF_MISC + 192;
constexpr int OFF_XS = OFF_T;
constexpr int OFF_RED = OFF_T + TILE;
constexpr int OFF_FIN = OFF_W + 3 * W_BYTES + W_KT;
constexpr int OFF_ACT = OFF_FIN + 4096;
constexpr int MISC_CNT = OFF_ACT + 1024;

__device__ __forceinline__ uint32_t smem_u32(const void* p) { return (uint32_t)__cvta_generic_to_shared(p); }
__device__ __forceinline__ uint32_t lds32(uint32_t a) { uint32_t v; asm volatile("ld.shared.b32 %0, [%1];" : "=r"(v) : "r"(a) : "memory"); return v; }
__device__ __forceinline__ uint32_t lds16(uint32_t a) { uint16_t v; asm volatile("ld.shared.u16 %0, [%1];" : "=h"(v) : "r"(a) : "memory"); return v; }
__device__ __forceinline__ uint2 lds64(uint32_t a) { uint2 v; asm volatile("ld.shared.v2.b32 {%0,%1}, [%2];" : "=r"(v.x), "=r"(v.y) : "r"(a) : "memory"); return v; }
__device__ __forceinline__ uint4 lds128(uint32_t a) { uint4 v; asm volatile("ld.shared.v4.b32 {%0,%1,%2,%3}, [%4];" : "=r"(v.x), "=r"(v.y), "=r"(v.z), "=r"(v.w) : "r"(a) : "memory"); return v; }
__device__ __forceinline__ void sts16(uint32_t a, uint32_t v) { asm volatile("st.shared.u16 [%0], %1;" :: "r"(a), "h"((uint16_t)v) : "memory"); }
__device__ __forceinline__ void sts32(uint32_t a, uint32_t v) { asm volatile("st.shared.b32 [%0], %1;" :: "r"(a), "r"(v) : "memory"); }
__device__ __forceinline__ void sts64(uint32_t a, uint32_t x, uint32_t y) { asm volatile("st.shared.v2.b32 [%0], {%1,%2};" :: "r"(a), "r"(x), "r"(y) : "memory"); }
__device__ __forceinline__ void sts128(uint32_t a, uint32_t x, uint32_t y, uint32_t z, uint32_t w) { asm volatile("st.shared.v4.b32 [%0], {%1,%2,%3,%4};" :: "r"(a), "r"(x), "r"(y), "r"(z), "r"(w) : "memory"); }
__device__ __forceinline__ void ldsm4(uint32_t a, uint32_t& r0, uint32_t& r1, uint32_t& r2, uint32_t& r3) {
  asm volatile("ldmatrix.sync.aligned.m8n8.x4.shared.b16 {%0,%1,%2,%3}, [%4];" : "=r"(r0), "=r"(r1), "=r"(r2), "=r"(r3) : "r"(a) : "memory");
}
__device__ __forceinline__ void ldsm4t(uint32_t a, uint32_t& r0, uint32_t& r1, uint32_t& r2, uint32_t& r3) {
  asm volatile("ldmatrix.sync.aligned.m8n8.x4.trans.shared.b16 {%0,%1,%2,%3}, [%4];" : "=r"(r0), "=r"(r1), "=r"(r2), "=r"(r3) : "r"(a) : "memory");
}
__device__ __forceinline__ void stsm4t(uint32_t a, uint32_t r0, uint32_t r1, uint32_t r2, uint32_t r3) {
  asm volatile("stmatrix.sync.aligned.m8n8.x4.trans.shared.b16 [%0], {%1,%2,%3,%4};" :: "r"(a), "r"(r0), "r"(r1), "r"(r2), "r"(r3) : "memory");
}
__device__ __forceinline__ uint4 ldr128(const void* p) {
  unsigned long long lo, hi;
  asm volatile("{ .reg .b128 t; ld.relaxed.gpu.global.b128 t, [%2]; mov.b128 {%0, %1}, t; }" : "=l"(lo), "=l"(hi) : "l"(p) : "memory");
  return make_uint4((uint32_t)lo, (uint32_t)(lo >> 32), (uint32_t)hi, (uint32_t)(hi >> 32));
}
__device__ __forceinline__ void str128(void* p, uint32_t x, uint32_t y, uint32_t z, uint32_t w) {
  asm volatile("{ .reg .b128 t; .reg .b64 lo, hi; mov.b64 lo, {%1,%2}; mov.b64 hi, {%3,%4}; mov.b128 t, {lo, hi}; st.relaxed.gpu.global.b128 [%0], t; }"
               :: "l"(p), "r"(x), "r"(y), "r"(z), "r"(w) : "memory");
}
__device__ __forceinline__ uint32_t ldr32(const void* p) { uint32_t v; asm volatile("ld.relaxed.gpu.global.b32 %0, [%1];" : "=r"(v) : "l"(p) : "memory"); return v; }
__device__ __forceinline__ void str32(void* p, uint32_t v) { asm volatile("st.relaxed.gpu.global.b32 [%0], %1;" :: "l"(p), "r"(v) : "memory"); }
__device__ __forceinline__ void str16(void* p, uint32_t v) { asm volatile("st.relaxed.gpu.global.u16 [%0], %1;" :: "l"(p), "h"((uint16_t)v) : "memory"); }
__device__ __forceinline__ void bar_sync(int id, int n) { asm volatile("bar.sync %0, %1;" :: "r"(id), "r"(n) : "memory"); }
__device__ __forceinline__ void bar_arrive(int id, int n) { asm volatile("bar.arrive %0, %1;" :: "r"(id), "r"(n) : "memory"); }

__device__ __forceinline__ float bf_lo(uint32_t w) { return __uint_as_float(w << 16); }
__device__ __forceinline__ float bf_hi(uint32_t w) { return __uint_as_float(w & 0xFFFF0000u); }
__device__ __forceinline__ uint32_t pack_bf(float lo, float hi) { uint32_t r; asm("cvt.rn.bf16x2.f32 %0, %1, %2;" : "=r"(r) : "f"(hi), "f"(lo)); return r; }
__device__ __forceinline__ uint32_t pack_h(float lo, float hi) { uint32_t r; asm("cvt.rn.f16x2.f32 %0, %1, %2;" : "=r"(r) : "f"(hi), "f"(lo)); return r; }
__device__ __forceinline__ float bfr(float x) { return bf_lo(pack_bf(x, 0.f)); }
__device__ __forceinline__ uint32_t bf_sub2(uint32_t a, uint32_t b) { __nv_bfloat162 r = __hsub2(*(__nv_bfloat162*)&a, *(__nv_bfloat162*)&b); return *(uint32_t*)&r; }
__device__ __forceinline__ uint32_t bf_add2(uint32_t a, uint32_t b) { __nv_bfloat162 r = __hadd2(*(__nv_bfloat162*)&a, *(__nv_bfloat162*)&b); return *(uint32_t*)&r; }
__device__ __forceinline__ uint32_t bf_mul2(uint32_t a, uint32_t b) { __nv_bfloat162 r = __hmul2(*(__nv_bfloat162*)&a, *(__nv_bfloat162*)&b); return *(uint32_t*)&r; }
__device__ __forceinline__ float2 h2f(uint32_t w) { return __half22float2(*(__half2*)&w); }
__device__ __forceinline__ float ex2(float x) { float r; asm("ex2.approx.ftz.f32 %0, %1;" : "=f"(r) : "f"(x)); return r; }
__device__ __forceinline__ float warp_sum(float v) {
#pragma unroll
  for (int o = 16; o > 0; o >>= 1) v += __shfl_xor_sync(0xffffffffu, v, o);
  return v;
}
__device__ __forceinline__ void mma_bf16(float* d, uint32_t a0, uint32_t a1, uint32_t a2, uint32_t a3, uint32_t b0, uint32_t b1) {
  asm volatile("mma.sync.aligned.m16n8k16.row.col.f32.bf16.bf16.f32 {%0,%1,%2,%3}, {%4,%5,%6,%7}, {%8,%9}, {%0,%1,%2,%3};"
               : "+f"(d[0]), "+f"(d[1]), "+f"(d[2]), "+f"(d[3]) : "r"(a0), "r"(a1), "r"(a2), "r"(a3), "r"(b0), "r"(b1));
}
__device__ __forceinline__ void mma_bf16_k8(float* d, uint32_t a0, uint32_t a1, uint32_t b0) {
  asm volatile("mma.sync.aligned.m16n8k8.row.col.f32.bf16.bf16.f32 {%0,%1,%2,%3}, {%4,%5}, {%6}, {%0,%1,%2,%3};"
               : "+f"(d[0]), "+f"(d[1]), "+f"(d[2]), "+f"(d[3]) : "r"(a0), "r"(a1), "r"(b0));
}

__device__ __forceinline__ void wg_fence() { asm volatile("wgmma.fence.sync.aligned;" ::: "memory"); }
__device__ __forceinline__ void wg_commit() { asm volatile("wgmma.commit_group.sync.aligned;" ::: "memory"); }
template <int N> __device__ __forceinline__ void wg_wait() { asm volatile("wgmma.wait_group.sync.aligned %0;" :: "n"(N) : "memory"); }
template <int TB> __device__ __forceinline__ void wgmma32(float* d, const uint32_t* a, uint32_t dlo, uint32_t dhi) {
  asm volatile("{ .reg .b64 dd; mov.b64 dd, {%20, %21}; wgmma.mma_async.sync.aligned.m64n32k16.f32.f16.f16 "
               "{%0,%1,%2,%3,%4,%5,%6,%7,%8,%9,%10,%11,%12,%13,%14,%15}, {%16,%17,%18,%19}, dd, 1, 1, 1, %22; }"
               : "+f"(d[0]), "+f"(d[1]), "+f"(d[2]), "+f"(d[3]), "+f"(d[4]), "+f"(d[5]), "+f"(d[6]), "+f"(d[7]), "+f"(d[8]), "+f"(d[9]), "+f"(d[10]), "+f"(d[11]), "+f"(d[12]), "+f"(d[13]), "+f"(d[14]), "+f"(d[15])
               : "r"(a[0]), "r"(a[1]), "r"(a[2]), "r"(a[3]), "r"(dlo), "r"(dhi), "n"(TB));
}
template <int TB> __device__ __forceinline__ void wgmma64(float* d, const uint32_t* a, uint32_t dlo, uint32_t dhi) {
  asm volatile("{ .reg .b64 dd; mov.b64 dd, {%36, %37}; wgmma.mma_async.sync.aligned.m64n64k16.f32.f16.f16 "
               "{%0,%1,%2,%3,%4,%5,%6,%7,%8,%9,%10,%11,%12,%13,%14,%15,%16,%17,%18,%19,%20,%21,%22,%23,%24,%25,%26,%27,%28,%29,%30,%31}, {%32,%33,%34,%35}, dd, 1, 1, 1, %38; }"
               : "+f"(d[0]), "+f"(d[1]), "+f"(d[2]), "+f"(d[3]), "+f"(d[4]), "+f"(d[5]), "+f"(d[6]), "+f"(d[7]), "+f"(d[8]), "+f"(d[9]), "+f"(d[10]), "+f"(d[11]), "+f"(d[12]), "+f"(d[13]), "+f"(d[14]), "+f"(d[15]), "+f"(d[16]), "+f"(d[17]), "+f"(d[18]), "+f"(d[19]), "+f"(d[20]), "+f"(d[21]), "+f"(d[22]), "+f"(d[23]), "+f"(d[24]), "+f"(d[25]), "+f"(d[26]), "+f"(d[27]), "+f"(d[28]), "+f"(d[29]), "+f"(d[30]), "+f"(d[31])
               : "r"(a[0]), "r"(a[1]), "r"(a[2]), "r"(a[3]), "r"(dlo), "r"(dhi), "n"(TB));
}
template <int TB> __device__ __forceinline__ void wgmma64_init(float* d, const uint32_t* a, uint32_t dlo, uint32_t dhi) {
  asm volatile("{ .reg .b64 dd; mov.b64 dd, {%36, %37}; wgmma.mma_async.sync.aligned.m64n64k16.f32.f16.f16 "
               "{%0,%1,%2,%3,%4,%5,%6,%7,%8,%9,%10,%11,%12,%13,%14,%15,%16,%17,%18,%19,%20,%21,%22,%23,%24,%25,%26,%27,%28,%29,%30,%31}, {%32,%33,%34,%35}, dd, 0, 1, 1, %38; }"
               : "=f"(d[0]), "=f"(d[1]), "=f"(d[2]), "=f"(d[3]), "=f"(d[4]), "=f"(d[5]), "=f"(d[6]), "=f"(d[7]), "=f"(d[8]), "=f"(d[9]), "=f"(d[10]), "=f"(d[11]), "=f"(d[12]), "=f"(d[13]), "=f"(d[14]), "=f"(d[15]), "=f"(d[16]), "=f"(d[17]), "=f"(d[18]), "=f"(d[19]), "=f"(d[20]), "=f"(d[21]), "=f"(d[22]), "=f"(d[23]), "=f"(d[24]), "=f"(d[25]), "=f"(d[26]), "=f"(d[27]), "=f"(d[28]), "=f"(d[29]), "=f"(d[30]), "=f"(d[31])
               : "r"(a[0]), "r"(a[1]), "r"(a[2]), "r"(a[3]), "r"(dlo), "r"(dhi), "n"(TB));
}
template <int TB> __device__ __forceinline__ void wgmma32_init(float* d, const uint32_t* a, uint32_t dlo, uint32_t dhi) {
  asm volatile("{ .reg .b64 dd; mov.b64 dd, {%20, %21}; wgmma.mma_async.sync.aligned.m64n32k16.f32.f16.f16 "
               "{%0,%1,%2,%3,%4,%5,%6,%7,%8,%9,%10,%11,%12,%13,%14,%15}, {%16,%17,%18,%19}, dd, 0, 1, 1, %22; }"
               : "=f"(d[0]), "=f"(d[1]), "=f"(d[2]), "=f"(d[3]), "=f"(d[4]), "=f"(d[5]), "=f"(d[6]), "=f"(d[7]), "=f"(d[8]), "=f"(d[9]), "=f"(d[10]), "=f"(d[11]), "=f"(d[12]), "=f"(d[13]), "=f"(d[14]), "=f"(d[15])
               : "r"(a[0]), "r"(a[1]), "r"(a[2]), "r"(a[3]), "r"(dlo), "r"(dhi), "n"(TB));
}
__device__ __forceinline__ void wgmma64h(uint32_t* d, uint32_t a0, uint32_t a1, uint32_t a2, uint32_t a3, uint32_t dlo, uint32_t dhi) {
  asm volatile("{ .reg .b64 dd; mov.b64 dd, {%20, %21}; wgmma.mma_async.sync.aligned.m64n64k16.f16.f16.f16 "
               "{%0,%1,%2,%3,%4,%5,%6,%7,%8,%9,%10,%11,%12,%13,%14,%15}, {%16,%17,%18,%19}, dd, 1, 1, 1, 0; }"
               : "+r"(d[0]), "+r"(d[1]), "+r"(d[2]), "+r"(d[3]), "+r"(d[4]), "+r"(d[5]), "+r"(d[6]), "+r"(d[7]), "+r"(d[8]), "+r"(d[9]), "+r"(d[10]), "+r"(d[11]), "+r"(d[12]), "+r"(d[13]), "+r"(d[14]), "+r"(d[15])
               : "r"(a0), "r"(a1), "r"(a2), "r"(a3), "r"(dlo), "r"(dhi));
}
__device__ __forceinline__ void wgmma64h_init(uint32_t* d, uint32_t a0, uint32_t a1, uint32_t a2, uint32_t a3, uint32_t dlo, uint32_t dhi) {
  asm volatile("{ .reg .b64 dd; mov.b64 dd, {%20, %21}; wgmma.mma_async.sync.aligned.m64n64k16.f16.f16.f16 "
               "{%0,%1,%2,%3,%4,%5,%6,%7,%8,%9,%10,%11,%12,%13,%14,%15}, {%16,%17,%18,%19}, dd, 0, 1, 1, 0; }"
               : "=r"(d[0]), "=r"(d[1]), "=r"(d[2]), "=r"(d[3]), "=r"(d[4]), "=r"(d[5]), "=r"(d[6]), "=r"(d[7]), "=r"(d[8]), "=r"(d[9]), "=r"(d[10]), "=r"(d[11]), "=r"(d[12]), "=r"(d[13]), "=r"(d[14]), "=r"(d[15])
               : "r"(a0), "r"(a1), "r"(a2), "r"(a3), "r"(dlo), "r"(dhi));
}
__device__ __forceinline__ void wgmma40_ss(float* d, uint32_t alo, uint32_t blo, uint32_t hi) {
  asm volatile("{ .reg .b64 da, db; mov.b64 da, {%20, %22}; mov.b64 db, {%21, %22}; "
               "wgmma.mma_async.sync.aligned.m64n40k16.f32.f16.f16 {%0,%1,%2,%3,%4,%5,%6,%7,%8,%9,%10,%11,%12,%13,%14,%15,%16,%17,%18,%19}, da, db, 1, 1, 1, 1, 1; }"
               : "+f"(d[0]), "+f"(d[1]), "+f"(d[2]), "+f"(d[3]), "+f"(d[4]), "+f"(d[5]), "+f"(d[6]), "+f"(d[7]), "+f"(d[8]), "+f"(d[9]), "+f"(d[10]), "+f"(d[11]), "+f"(d[12]), "+f"(d[13]), "+f"(d[14]), "+f"(d[15]), "+f"(d[16]), "+f"(d[17]), "+f"(d[18]), "+f"(d[19])
               : "r"(alo), "r"(blo), "r"(hi));
}
__device__ __forceinline__ void wgmma40_ss_init(float* d, uint32_t alo, uint32_t blo, uint32_t hi) {
  asm volatile("{ .reg .b64 da, db; mov.b64 da, {%20, %22}; mov.b64 db, {%21, %22}; "
               "wgmma.mma_async.sync.aligned.m64n40k16.f32.f16.f16 {%0,%1,%2,%3,%4,%5,%6,%7,%8,%9,%10,%11,%12,%13,%14,%15,%16,%17,%18,%19}, da, db, 0, 1, 1, 1, 1; }"
               : "=f"(d[0]), "=f"(d[1]), "=f"(d[2]), "=f"(d[3]), "=f"(d[4]), "=f"(d[5]), "=f"(d[6]), "=f"(d[7]), "=f"(d[8]), "=f"(d[9]), "=f"(d[10]), "=f"(d[11]), "=f"(d[12]), "=f"(d[13]), "=f"(d[14]), "=f"(d[15]), "=f"(d[16]), "=f"(d[17]), "=f"(d[18]), "=f"(d[19])
               : "r"(alo), "r"(blo), "r"(hi));
}
__device__ __forceinline__ void tma_box(uint32_t dst, const CUtensorMap* tm, uint32_t mb, int x, int y) {
  asm volatile("cp.async.bulk.tensor.2d.shared::cluster.global.mbarrier::complete_tx::bytes [%0], [%1, {%3, %4}], [%2];"
               :: "r"(dst), "l"(tm), "r"(mb), "r"(x), "r"(y) : "memory");
}
__device__ __forceinline__ uint32_t uni(uint32_t v) {
  uint32_t r; asm volatile("shfl.sync.idx.b32 %0, %1, 0, 0x1f, 0xffffffff;" : "=r"(r) : "r"(v)); return r;
}
__device__ __forceinline__ uint32_t pin(uint32_t v) {
  uint32_t r; asm volatile("shfl.sync.bfly.b32 %0, %1, 0, 0x1f, 0xffffffff;" : "=r"(r) : "r"(v)); return r;
}

struct Params {
  const unsigned char* x;
  Scratch* s;
  int off[8];
  uint32_t* out;
  const uint16_t* dskip;
  const uint32_t* w_r;
  long long* ts;
  const unsigned char* far[7];
  uint32_t sched[2][17];
};
__device__ __forceinline__ uint32_t ldnc32(const void* p) { uint32_t v; asm volatile("ld.global.nc.b32 %0, [%1];" : "=r"(v) : "l"(p)); return v; }
__device__ __forceinline__ uint32_t ldnc16(const void* p) { uint16_t v; asm volatile("ld.global.nc.u16 %0, [%1];" : "=h"(v) : "l"(p)); return v; }
__device__ __forceinline__ void mbar_wait(uint32_t mb, uint32_t ph = 0) {
#pragma unroll 1
  for (int it = 0; it < SPIN_MAX; it++) {
    uint32_t ok;
    asm volatile("{ .reg .pred q; mbarrier.try_wait.parity.shared::cta.b64 q, [%1], %2; selp.u32 %0, 1, 0, q; }" : "=r"(ok) : "r"(mb), "r"(ph) : "memory");
    if (ok) break;
  }
}
__device__ __forceinline__ void mbar_arrive(uint32_t mb) { asm volatile("mbarrier.arrive.shared::cta.b64 _, [%0];" :: "r"(mb) : "memory"); }
__device__ __forceinline__ void fence_async() { asm volatile("fence.proxy.async.shared::cta;" ::: "memory"); }
#define SPIN_WHILE(cond, body) _Pragma("unroll 1") for (int _it = 0; _it < SPIN_MAX && __any_sync(0xffffffffu, (cond)); _it++) { body; }

struct LnC { uint32_t m2, rh2, rl2; };
__device__ __forceinline__ LnC ln_consts(float s, float q, float& r) {
  const float mean = s * (1.f / DM);
  const float var = fmaxf(fmaf(-mean, mean, q * (1.f / DM)), 0.f);
  float sd;
  asm("sqrt.approx.ftz.f32 %0, %1;" : "=f"(sd) : "f"(bfr(bfr(var) + 1e-5f)));
  asm("rcp.approx.ftz.f32 %0, %1;" : "=f"(r) : "f"(bfr(sd)));
  LnC c;
  c.m2 = pack_bf(mean, mean);
  c.rh2 = pack_bf(r, r);
  const float rl = r - bf_lo(c.rh2);
  c.rl2 = pack_bf(rl, rl);
  return c;
}
__device__ __forceinline__ uint32_t bf_fma2(uint32_t a, uint32_t b, uint32_t c) {
  __nv_bfloat162 r = __hfma2(*(const __nv_bfloat162*)&a, *(const __nv_bfloat162*)&b, *(const __nv_bfloat162*)&c);
  return *(uint32_t*)&r;
}
__device__ __forceinline__ uint32_t ln_apply(uint32_t w, uint32_t m2, uint32_t rh2, uint32_t rl2) {
  const uint32_t d = bf_sub2(w, m2);
  return bf_fma2(d, rh2, bf_mul2(d, rl2));
}

__device__ __forceinline__ float2 cis(float mag_log2, float rev) {
  const float m = ex2(mag_log2), ang = rev * 6.283185307179586f;
  return make_float2(m * __cosf(ang), m * __sinf(ang));
}
__device__ __forceinline__ float2 csq(float2 a) { return make_float2(fmaf(a.x, a.x, -a.y * a.y), (a.x + a.x) * a.y); }
__device__ __forceinline__ float2 cmul(float2 a, float2 b) { return make_float2(fmaf(a.x, b.x, -a.y * b.y), fmaf(a.x, b.y, a.y * b.x)); }
__device__ __forceinline__ void pmul(uint32_t xr, uint32_t xi, uint32_t w, uint32_t& yr, uint32_t& yi) {
  const __half2 XR = *(__half2*)&xr, XI = *(__half2*)&xi, W = *(__half2*)&w;
  const __half2 a = __hfma2(__hneg2(XI), __high2half2(W), __hmul2(XR, __low2half2(W)));
  const __half2 b = __hfma2(XI, __low2half2(W), __hmul2(XR, __high2half2(W)));
  yr = *(const uint32_t*)&a; yi = *(const uint32_t*)&b;
}
__device__ __forceinline__ uint32_t pk(float2 a) { return pack_h(a.x, a.y); }

struct KgState { float2 c0, z8; float kl; uint32_t w64, w128, w192; };
__device__ __forceinline__ void kgen_tables_n(const uint32_t (&raw)[7], uint32_t scr, int wt, KgState& k) {
  const uint32_t dst = scr + 16384 + wt * 16;
  const float dt = bfr(ex2(bf_lo(raw[6]) * 1.4426950408889634f));
  const float th = dt * bf_lo(raw[1]);
  const float br = dt * bf_lo(raw[2]), bi = dt * bf_lo(raw[3]);
  const float Cr = bf_lo(raw[4]), Ci = bf_lo(raw[5]);
  k.c0 = make_float2(fmaf(Cr, br, -Ci * bi), fmaf(Cr, bi, Ci * br));
  const uint32_t mx = __reduce_max_sync(0xffffffffu, __float_as_uint(fmaxf(fabsf(k.c0.x), fabsf(k.c0.y))));
  const float a2 = dt * bf_lo(raw[0]) * 1.4426950408889634f;
  const float rh = th * 0.15915494309189535f;
  const float rl = fmaf(th, (float)(0.15915494309189535 - (double)0.15915494309189535f), fmaf(th, 0.15915494309189535f, -rh));
  const float rf = rh - rintf(rh);
  const float2 z1 = cis(a2, rf + rl);
  const float p64 = rf * 64.f;
  const float2 z64 = cis(a2 * 64.f, fmaf(64.f, rl, p64 - rintf(p64)));
  const float2 z2 = csq(z1), z128 = csq(z64), z3 = cmul(z2, z1), z4 = csq(z2), z256 = csq(z128), z6 = csq(z3), z512 = csq(z256);
  k.z8 = csq(z4);
  k.w64 = pk(z64); k.w128 = pk(z128); k.w192 = pk(cmul(z128, z64));
  sts128(dst, 0x00003C00u, pk(z2), pk(z4), pk(z6));
  const float2 z1024 = csq(z512), z768 = cmul(z512, z256);
  sts128(dst + 2048, pk(z1), pk(z3), pk(cmul(z4, z1)), pk(cmul(z4, z3)));
  const float2 z2048 = csq(z1024);
  k.kl = fmaf(k.c0.x, z2048.x, -k.c0.y * z2048.y);
  sts128(dst + 4096, pk(z256), pk(cmul(z256, z2)), pk(cmul(z256, z4)), pk(cmul(z256, z6)));
  sts128(dst + 6144, pk(z512), pk(cmul(z512, z4)), pk(z768), pk(cmul(z768, z4)));
  sts128(dst + 8192, pk(z1024), pk(cmul(z1024, z256)), pk(cmul(z1024, z512)), pk(cmul(z1024, z768)));
  sts32(scr + W_MISC + (wt >> 5) * 4, mx);
}
__device__ __forceinline__ int kgen_tables_m(uint32_t scr, int wt, const KgState& k) {
  const uint32_t dst = scr + wt * 16;
  const uint4 e4 = lds128(scr + W_MISC);
  const float2 z16 = csq(k.z8), z32 = csq(z16);
  const int em = max(min((int)(max(max(e4.x, e4.y), max(e4.z, e4.w)) >> 23), 238), 16);
  const float sc = __uint_as_float((uint32_t)(127 + 4 + 127 - em) << 23);
  sts32(scr + W_MISC + 16 + (wt >> 5) * 4, __reduce_add_sync(0xffffffffu, __float2int_rn(k.kl * sc * 262144.f)));
  const float2 c0 = make_float2(k.c0.x * sc, k.c0.y * sc);
  const float2 c1 = cmul(c0, k.z8), c2 = cmul(c0, z16), c4 = cmul(c0, z32), c3 = cmul(c1, z16), c5 = cmul(c1, z32), c6 = cmul(c2, z32), c7 = cmul(c3, z32);
  uint32_t pr[4], pi[4], yr[4], yi[4];
  pr[0] = pack_h(c0.x, c1.x); pi[0] = pack_h(c0.y, c1.y);
  pr[1] = pack_h(c2.x, c3.x); pi[1] = pack_h(c2.y, c3.y);
  pr[2] = pack_h(c4.x, c5.x); pi[2] = pack_h(c4.y, c5.y);
  pr[3] = pack_h(c6.x, c7.x); pi[3] = pack_h(c6.y, c7.y);
  sts128(dst, pr[0], pr[1], pr[2], pr[3]); sts128(dst + 2048, pi[0], pi[1], pi[2], pi[3]);
#pragma unroll
  for (int q = 1; q < 4; q++) {
    const uint32_t w = q == 1 ? k.w64 : q == 2 ? k.w128 : k.w192;
#pragma unroll
    for (int i = 0; i < 4; i++) pmul(pr[i], pi[i], w, yr[i], yi[i]);
    sts128(dst + q * 4096, yr[0], yr[1], yr[2], yr[3]); sts128(dst + q * 4096 + 2048, yi[0], yi[1], yi[2], yi[3]);
  }
  return em;
}
__device__ __forceinline__ uint32_t lds32_if(uint32_t a, bool on) {
  uint32_t v; asm volatile("{ .reg .pred q; setp.ne.u32 q, %2, 0; mov.b32 %0, 0; @q ld.shared.b32 %0, [%1]; }" : "=r"(v) : "r"(a), "r"((uint32_t)on) : "memory"); return v;
}
__device__ __forceinline__ uint32_t prmt(uint32_t a, uint32_t b, uint32_t s) { uint32_t r; asm("prmt.b32 %0, %1, %2, %3;" : "=r"(r) : "r"(a), "r"(b), "r"(s)); return r; }
struct BuildC { uint32_t a3, a2, az, cw, sel; };
__device__ __forceinline__ BuildC build_consts(int wt) {
  const int ix = ((wt >> 2) + (wt & 3) * 32 - 1) & 127;
  BuildC b;
  b.a3 = W_CW + 32 + ((ix & 1) ? 0 : 304) + (ix >> 1) * 4;
  b.a2 = W_L3 + 3072 + 544 + (wt & ~3) * 2 + (wt & 1) * 4 + (wt & 2) * 128;
  b.az = W_KT + (wt < 36 ? -512 : 64 + 4128 - 576) + wt * 16;
  b.cw = W_CW + 32 + (wt >> 6) * 48 + wt * 4;
  b.sel = (wt & 1) ? 0x10767610 : wt ? 0x10101010 : 0x10107610;
  return b;
}
__device__ __forceinline__ void kgen_build(uint32_t tb, const BuildC& bc, int wg, int wt, uint32_t k0, uint32_t k1, uint32_t k2) {
  const uint32_t kt = tb + W_KT, sc = tb + W_L3 + 3072;
  const uint32_t a3 = tb + bc.a3, a2 = tb + bc.a2;
  const uint32_t v3 = wt ? k2 : k2 >> 16;
  sts32(sc + 4 + wt * 4, __byte_perm(k0, k1, 0x5432));
  sts16(a2, k1 >> 16); sts16(a2 + 6, k1 >> 16);
  sts16(a3, v3); sts16(a3 + 6, v3);
  if ((unsigned)(wt - 32) < 14u) sts128(tb + bc.az, 0, 0, 0, 0);
  if (wt == 127) sts32(sc, k0 & 0xFFFF0000u);
  if (wt == 0) { sts32(sc + 516, k1); sts16(sc + 1056, k2); }
  bar_sync(1 + wg, 128);
  const uint32_t cw = tb + bc.cw, g2 = sc + 540 + wt * 4;
  const bool odd = wt & 1, ends = (unsigned)(wt - 4) >= 120u;
  const uint32_t pv = lds32(sc + wt * 4), nx = lds32(sc + 8 + wt * 4), nc = lds32_if(g2 + 8, ends);
  const uint32_t l0 = lds32(cw), l1 = lds32(cw - 8), l2 = lds32(cw - 16), l3 = lds32(cw - 24), q0 = lds32(g2), q1 = lds32(g2 + 128), q2 = lds32(g2 - 8), q3 = lds32(g2 + 120);
  sts64(kt + 64 + wt * 8, __byte_perm(k0, pv, 0x5410), __byte_perm(k0, 0, 0x1032));
  sts64(kt + 64 + 1024 + wt * 8, prmt(k1, pv, bc.sel), prmt(k1, nx, bc.sel >> 16));
  const uint32_t cc = __byte_perm(nc, 0, 0x3232), nn = __byte_perm(nc, 0, 0x1010);
  if (ends) sts128(kt + 64 + 2048 + wt * 16, cc, cc, odd ? nc : cc, odd ? nn : nc);
  if (wt == 127) { sts128(kt + 64 + 4096, nn, nn, nn, nn); sts128(kt + 64 + 4112, nn, nn << 16, 0, 0); }
  sts128(tb + W_L3 + 512 + (wt >> 6) * 512 + wt * 16, l0, l1, l2, l3);
  if ((wt & 63) < 34) sts128(tb + W_QT - 16 + wt * 16, q0, q1, q2, q3);
}

__device__ __forceinline__ void load_a(uint32_t (&a)[4], uint32_t kp, int j) {
  a[0] = lds32(kp + 64 * j); a[1] = lds32(kp + 64 * j + 512); a[2] = lds32(kp + 64 * j - 32); a[3] = lds32(kp + 64 * j + 480);
}
__device__ __forceinline__ uint32_t band8(int s) { return ((((0x1FFu << 20) >> s) & 0x01010101u) | (((0x7Fu << 25) >> s) & 0x10101010u)) * 0x01020408u; }
__device__ __forceinline__ uint32_t hadd2u(uint32_t a, uint32_t b) { __half2 r = __hadd2(*(__half2*)&a, *(__half2*)&b); return *(uint32_t*)&r; }

__device__ __forceinline__ void zero_pads(uint32_t tb, int wt) {
  if (!(wt & 32)) sts128(tb + W_L3 + (wt >> 6) * 512 + wt * 16, 0, 0, 0, 0);
  if ((wt & 63) < 3) sts128(tb + W_CW + (wt >> 6) * 304 + (wt & 63) * 16, 0, 0, 0, 0);
}
__device__ __forceinline__ uint32_t tr_base(int lane) {
  return OFF_YT + (2 * (lane >> 3) + (lane & 1)) * YT_PITCH + ((lane >> 1) & 1) * (8 * YT_PITCH + 64) + ((lane >> 2) & 1) * 16;
}

__device__ __forceinline__ uint32_t sc_addr(int tp) { return OFF_YT + (tp < 16 ? tp * YT_PITCH + (tp >> 3) * 64 + 1152 : 8 * YT_PITCH - 512 + tp * 32); }
#define X_PW 15
#define X_HU 15
#define X_NE 2
#define X_SCT 10000
#define X_DELTA 0
#define X_DSTEP 2000
#define X_PF0 2700
#define X_PFD 600
#define X_TD 460
#define X_WS 6
#define X_OR 8
#define X_ABS 4870
#define X_XD 200
#define X_RD 630
#define X_HD 450
#define X_PD 1170
#define X_PROMO 2
#define X_YD2 1000
#define X_GO 1
#define X_GW 2
#define X_NS 4300
#define X_XS 13450
#define X_LAG 1300
#define X_YD 1550
struct TMaps { CUtensorMap m[10]; };
__device__ __forceinline__ uint32_t h2bf(uint32_t w) { const float2 f = h2f(w); return pack_bf(f.x, f.y); }
__device__ __forceinline__ uint32_t keep(uint32_t v) { asm volatile("" : "+r"(v)); return v; }
__device__ __forceinline__ uint2 ldr64(const void* p) { uint2 v; asm volatile("{ .reg .b64 t; ld.relaxed.gpu.global.b64 t, [%2]; mov.b64 {%0, %1}, t; }" : "=r"(v.x), "=r"(v.y) : "l"(p) : "memory"); return v; }
__host__ __device__ __forceinline__ uint32_t down_box(int s, bool five) {
  return five ? OFF_W + W_BYTES + 12288 + (s / 3) * (W_BYTES - 12288) + s * 4096 : s < 6 ? OFF_W + W_BYTES + BOX + (s >> 1) * (W_BYTES - 10240) + s * 5120 : OFF_W + (s - 6) * 5120;
}
__device__ __forceinline__ void load_tile(const CUtensorMap* tmx, int i, int c, int again = 0) {
  asm volatile("mbarrier.arrive.expect_tx.shared::cta.b64 _, [%0], 8704;" :: "r"(MB_UL + i * 16 + again) : "memory");
  asm volatile("cp.async.bulk.tensor.3d.shared::cluster.global.mbarrier::complete_tx::bytes [%0], [%1, {%3, %4, %5}], [%2];"
               :: "r"(i < 2 ? OFF_T + i * TILE : OFF_W), "l"(tmx), "r"(MB_UL + i * 16 + again), "r"(0), "r"(c), "r"(-8) : "memory");
}
template <bool FAR> __device__ __forceinline__ void load_params(const Params& p, uint32_t ch, int wt, uint32_t dst, bool on) {
  const int rel = wt < 96 ? ch * 16 + (wt & 15) : ch >> 3;
  const unsigned char* b = FAR ? p.far[min(wt >> 4, 6)] + rel * 16 : p.x + (long long)(p.off[wt >> 4] + rel) * 16;
  asm volatile("{ .reg .pred q; setp.ne.u32 q, %2, 0; @q cp.async.cg.shared.global [%0], [%1], 16; }"
               :: "r"(dst + wt * 16), "l"(b), "r"((uint32_t)(on && wt < 97)) : "memory");
}

struct ConvC { uint32_t ca, cb, bands, qa; };
__device__ __forceinline__ ConvC conv_consts(int w, int lane) {
  const int h = w & 1, P = (w >> 1) & 1, d0 = 8 * h + (lane >> 2) - 2 * (lane & 3);
  ConvC k;
  k.ca = keep((W_KT + (16 + 256 * P + d0) * 4) | (((8 + 64 * P + lane) * 64 + (((h + ((w >> 1) & 2)) ^ (lane >> 1)) & 3) * 16) << 16));
  const int u = d0 + 2 * (lane & 1) + 2, in = (u & 7) - ((u & 7) >= 5 ? 5 : 0) - 2 * (lane & 1);
  k.cb = keep(in > 0 ? 0x1010 : in == 0 ? 0x3210 : 0x3232);
  k.qa = keep(W_QT + (2 * (u >> 3) + ((u & 7) >= 5) + 64 * P) * 16);
  k.bands = keep(__byte_perm(band8(d0 + 8), band8(d0 + 7), 0x7733) & 0x00FF00FFu);
  return k;
}
struct ConvPre { uint32_t e0, e2, f2, b0, b2, a[3][4]; };
__device__ __forceinline__ void conv_pre(ConvPre& r, uint32_t kp, uint32_t qp, int part, bool on, bool P) {
  if (part & 1) {
    r.e0 = lds32_if(kp + 4096, on && !P); r.e2 = lds32_if(kp + 4064, on && !P); r.f2 = lds32_if(kp + 4128, on && !P);
    r.b0 = lds32_if(kp + 2048, on && !P); r.b2 = lds32_if(kp + 2016, on && !P);
  }
#pragma unroll
  for (int j = 0; j < 3; j++) if (part & (j < 1 ? 1 : 2))
    asm volatile("{ .reg .pred q; setp.ne.u32 q, %5, 0; mov.b32 %0, 0; mov.b32 %1, 0; mov.b32 %2, 0; mov.b32 %3, 0; @q ld.shared.v4.b32 {%0,%1,%2,%3}, [%4]; }"
                 : "=r"(r.a[j][0]), "=r"(r.a[j][1]), "=r"(r.a[j][2]), "=r"(r.a[j][3]) : "r"(qp + 64 * j), "r"((uint32_t)on) : "memory");
}
__device__ __forceinline__ void conv_item(uint32_t tb, uint32_t tl, int bid, int bn, ConvPre& pre, const ConvC& cv, uint32_t zero, const CUtensorMap* tmx, int ch, int warp, int lane, bool hold, bool more) {
  const bool go = more && warp == 0 && lane == 0;
  const uint32_t kp = tb + (cv.ca & 0xFFFFu), qp = tb + cv.qa;
  const uint32_t dlo = (tl >> 4) + 32 + ((warp >> 1) & 2) + (1u << 16), dhi = 32u | (2u << 30);
  const bool P = warp & 2;
  float a32[16], b32[16], a64[32];
  uint32_t A[40][4];
#define STEP(J) { wgmma64<0>(a64, A[J], dlo + 256 - 4 * (J), dhi); \
    if ((J) == 32) wgmma32_init<0>(b32, A[J], dlo, dhi); else wgmma32<0>(b32, A[J], ((J) < 8 ? dlo ^ zero : dlo) + 128 - 4 * (J), dhi); \
    if ((J) == 0) wgmma32_init<0>(a32, A[J], dlo, dhi); else if ((J) < 8) wgmma32<0>(a32, A[J], (dlo ^ zero) - 4 * (J), dhi); }
#define LD(J) load_a(A[J], kp, J);
#define LQ(J) { const uint4 v = lds128(qp + 64 * ((J) - 32)); A[J][0] = v.x; A[J][1] = v.y; A[J][2] = v.z; A[J][3] = v.w; }
#define PQ(J) { A[J][0] = prmt(A[J][0], 0, cv.cb); A[J][1] = prmt(A[J][1], 0, cv.cb); A[J][2] = prmt(A[J][2], 0, cv.cb); A[J][3] = prmt(A[J][3], 0, cv.cb); }
#define FIRST(J) wg_fence(); STEP(J) wg_commit(); wg_wait<1>(); wg_fence();
  {
    uint32_t win[16], x9[4], x7[4], e[4], f[4];
    const uint32_t bz = keep(cv.bands);
#define BAND(i) keep((bz & (0x10001u << (i))) * (0x3C00u >> (i)))
    e[0] = pre.e0; e[2] = pre.e2; e[1] = keep(bz & 0x100u); e[3] = keep(bz & 0x200u);
    f[2] = pre.f2; f[0] = keep(bz & 0x4000u); f[1] = keep(bz & 0x8000u); f[3] = keep(bz & 0x300u);
#pragma unroll
    for (int j = 0; j < 12; j++) A[32 + j / 4][j & 3] = pre.a[j / 4][j & 3];
    PQ(32) PQ(33) PQ(34)
    if (!P) { A[32][0] = pre.b0; A[32][2] = pre.b2; }
    const uint32_t q[12] = {BAND(0), BAND(5), keep(bz & 0x400u), BAND(4), BAND(2), BAND(7), BAND(1), BAND(6), keep(bz & 0x800u), keep(bz & 0x1000u), BAND(3), keep(bz & 0x2000u)};
#undef BAND
    const uint32_t ta = keep(tl + 512 + (warp & 3) * 2048 + lane * 64 + (lane & 6) * 8);
    if (X_GO && hold) mbar_wait(MB_GO);
    uint32_t mbl = MB_UL + (warp & 8) * 2, ph = 0;
#pragma unroll 1
    for (int it = 0; it < SPIN_MAX; it++) {
      if (ch < 512) mbar_wait(mbl, ph);
      if (it == 1) TS(13);
      TS(3);
      wg_fence();
      wgmma64h_init(win, q[0], q[1], q[2], q[3], dlo, dhi);
      wgmma64h(win, q[4], q[5], q[6], q[7], dlo - 4, dhi);
      wgmma64h(win, q[8], q[9], q[10], q[11], dlo - 8, dhi);
      wg_commit();
      wgmma64_init<0>(a64, e, dlo, dhi);
      wgmma64<0>(a64, f, dlo - 4, dhi);
      wg_commit();
      if (ch >= 512) break;
      uint32_t r0, r1, r2, r3, ok;
      if (warp & 4) {
        mbar_wait(mbl + 8);
        if (__all_sync(0xffffffffu, it || lds32(MISC_RT + (warp & 8)) == 0)) break;
        wg_wait<0>();
        continue;
      }
      ldsm4(ta, r0, r1, r2, r3);
      ok = r0 & r1 & r2 & r3;
      ldsm4(ta ^ 32, r0, r1, r2, r3);
      asm volatile("{ .reg .pred q; setp.ne.u32 q, %1, 0; barrier.red.and.pred q, %2, 128, q; selp.u32 %0, 1, 0, q; }" : "=r"(ok) : "r"((ok & r0 & r1 & r2 & r3 & 1u) | (lane & 3)), "r"(1 + (warp >> 2)) : "memory");
      if (ok) { if ((warp & 3) == 0 && lane == 0) { sts32(MISC_RT + warp, it); mbar_arrive(MB_UL + 8 + warp * 2); } break; }
      wg_wait<0>();
      if ((warp & 3) == 0 && lane == 0) load_tile(tmx - 1, warp >> 3, ch, 56);
      mbl = MB_UL + 56 + (warp & 8) * 2; ph = it & 1;
    }
    wg_wait<1>();
#pragma unroll
    for (int i = 0; i < 4; i++) {
      const int tl = 2 * ((i & 1) + ((i & 2) ? 0 : 4));
      x9[i] = P ? win[tl + 4] : win[tl]; x7[i] = P ? win[tl + 5] : win[tl + 1];
    }
    const uint32_t l3lo = ((tb + W_L3) >> 4) + (32u << 16);
    wg_fence();
    wgmma64<0>(a64, x9, l3lo, 8);
    wgmma64<0>(a64, x7, l3lo + 96, 8);
    wg_commit();
  }
  STEP(32) STEP(33) STEP(34) wg_commit(); wg_wait<1>();
  LQ(35) LQ(36) LQ(37) LQ(38) LQ(39) LD(0) PQ(35) PQ(36) PQ(37) PQ(38) PQ(39)
  FIRST(35) STEP(36) STEP(37) STEP(38) wg_commit(); STEP(39) wg_commit();
  LD(1) LD(2) LD(3)
  if (X_GO == 1 && go) mbar_arrive(MB_GO);
  wg_wait<1>(); wg_fence(); STEP(0) wg_commit(); STEP(1) wg_commit(); STEP(2) wg_commit(); wg_wait<2>();
  LD(4) LD(5)
  wg_fence(); STEP(3) wg_commit(); wg_wait<1>();
  LD(6) LD(7)
  wg_fence(); STEP(4) STEP(5) wg_commit();
  wg_fence(); STEP(6) STEP(7) wg_commit();
#undef STEP
#undef LD
#undef LQ
#undef PQ
#undef FIRST
  TS(18);
  if (X_GO == 3 && go) mbar_arrive(MB_GO);
  const uint32_t xc = tb + W_KT + (warp & 3) * 1024 + lane * 16;
  if (more) bar_sync(7, 288);
  wg_wait<1>();
  conv_pre(pre, kp + ALT, qp + ALT, 1, more, P);
  wg_wait<0>();
  conv_pre(pre, kp + ALT, qp + ALT, 2, more, P);
  uint32_t E[16], o[8];
#define ACC(i) ((i) < 16 ? a32[i] : (i) < 32 ? b32[(i) - 16] : a64[(i) - 32])
  E[0] = pack_h(a32[0], a32[1]);
#pragma unroll
  for (int i = 1; i < 16; i++) E[i] = pack_h(ACC(4 * i) + ACC(4 * i - 2), ACC(4 * i + 1) + ACC(4 * i - 1));
#undef ACC
#pragma unroll
  for (int j = 0; j < 8; j++) o[j] = P ? (j < 2 ? 0u : E[j - 2]) : E[8 + j];
  sts128(xc, o[0], o[1], o[2], o[3]); sts128(xc + 512, o[4], o[5], o[6], o[7]);
#pragma unroll
  for (int j = 0; j < 8; j++) o[j] = P ? E[6 + j] : E[j];
  TS(25);
  if (more) {
    sts128(xc + 4096, o[0], o[1], o[2], o[3]); sts128(xc + 4608, o[4], o[5], o[6], o[7]);
    bar_arrive(12, 192);
    return;
  }
  bar_sync(1 + (warp >> 2), 128);
  const uint4 vv[2] = {lds128(xc + (P ? -2048 : 2048)), lds128(xc + (P ? -1536 : 2560))};
  const uint32_t mk = lane < 8 ? 0xFFFEFFFEu : ~0u;
#pragma unroll
  for (int q = 0; q < 2; q++) {
    const uint4 v = vv[q];
    stsm4t(tl + (cv.ca >> 16) + q * 2048, hadd2u(o[4 * q], v.x) & mk, hadd2u(o[4 * q + 1], v.y) & mk, hadd2u(o[4 * q + 2], v.z) & mk, hadd2u(o[4 * q + 3], v.w) & mk);
  }
  fence_async();
  bar_sync(bid, bn);
  if (warp == 0 && lane == 0) mbar_arrive(MB_REL);
  if ((warp & 7) == (ch < 512 ? 7 : 3) && lane == 0) {
    asm volatile("cp.async.bulk.tensor.3d.global.shared::cta.bulk_group [%0, {%3, %2, %3}], [%1];" :: "l"(tmx), "r"(tl + 512), "r"(ch), "r"(0) : "memory");
    asm volatile("cp.async.bulk.commit_group;" ::: "memory");
  }
}

template <bool FAR> __global__ void __launch_bounds__(NT, 1)
fused_kernel(const __grid_constant__ Params p, const __grid_constant__ TMaps tm) {
  extern __shared__ __align__(1024) unsigned char smem[];
  const int c = blockIdx.x;
  const bool five = (c & 1) == 0;
  const uint32_t pitch = five ? 64 : 80;
  const uint32_t ones = 0x3F803F80u;
  const int tid = threadIdx.x, lane = tid & 31;
  const uint32_t xrow = OFF_YT + ((tid & 127) >> 3) * YT_PITCH + (tid & 64) + (tid & 7) * 16;
  {
    const int w4 = tid >> 7;
    load_params<FAR>(p, w4 < 2 ? 2 * c + w4 : five ? 257 + 2 * c : 512 + (c >> 1), tid & 127, OFF_W + W_KT + (w4 < 2 ? w4 * W_BYTES : five ? 3 * W_BYTES : 3 * W_BYTES + 2048), (0xB >> w4) & 1);
  }
  if ((tid >> 7) == 2) {
    const unsigned char* xp = p.x + (uint32_t)((c * 16 - 32 + (tid >> 3)) * 1152 + (tid & 7) * 16);
    asm volatile("" : "+l"(xp));
    { const uint32_t tq = clock(); while ((int)(clock() - tq) < X_XD) {} }
#pragma unroll
    for (int k = 0; k < 9; k++) asm volatile("cp.async.cg.shared.global [%0], [%1], 16;" :: "r"(xrow + k * 128), "l"(xp + k * 128) : "memory");
  }
  const int warp = (int)uni(tid >> 5), wg = warp >> 2;
  TS(0);
  if (__builtin_expect(wg == 4, 0)) {
    asm volatile("setmaxnreg.dec.sync.aligned.u32 32;");
    const int role = warp;
    const int u0 = (c >> 1) * 9 + (five ? ((c & 2) ? 5 : 0) : ((c & 2) ? 0 : 4));
    const uint32_t t0 = clock() + c * 4;
    if (role == 16) {
      if (lane == 0) {
#pragma unroll
        for (int i = 0; i < 19; i++) if (i != 16) asm volatile("mbarrier.init.shared::cta.b64 [%0], %1;" :: "r"(OFF_MISC + i * 8), "r"((unsigned)(i - 2) < 4u ? 4 : 1) : "memory");
      }
      __syncwarp();
      if (lane < 2) asm volatile("mbarrier.arrive.expect_tx.shared::cta.b64 _, [%0], %1;" :: "r"(OFF_MISC + lane * 8), "r"(lane ? (five ? 36864 : 51200) : pitch * 1152) : "memory");
      fence_async();
      bar_arrive(5, 608);
      const CUtensorMap* tmb = &tm.m[five ? 3 : 0];
#pragma unroll 1
      for (int u = 0; u < 17; u++) {
        const uint32_t e = p.sched[five][u], kind = e & 3, s = (e >> 2) & 15, dst = e >> 14;
        if (kind == 3) continue;
        while ((int)(clock() - t0) < X_PF0 + (u < X_NE ? u * X_PFD : X_LAG + u * X_TD)) __nanosleep(20);
        if (e & 0x3FC0) mbar_wait(OFF_MISC + ((e >> 6) & 255));
        if (lane == 0) {
          if (kind == 2) asm volatile("cp.async.bulk.tensor.3d.shared::cluster.global.mbarrier::complete_tx::bytes [%0], [%1, {%3, %4, %5}], [%2];"
                                      :: "r"(dst), "l"(tmb + 2), "r"(MB_D), "r"(0), "r"(u0 * 8), "r"(s) : "memory");
          else tma_box(dst, tmb + kind, MB_GU, u0 * 8, s * 96);
        }
        if (u == 5) TS(2);
        if (u == 10) TS(3);
      }
      TS(4);
      TS_DUMP();
#define FINISH0 bar_sync(12, 192);        \
        _Pragma("unroll 1") for (int w = role & 2; w < (role & 2) + 2; w++) { \
          const uint32_t xa = OFF_W + W_KT + lane * 16, mk = lane < 8 ? 0xFFFEFFFEu : ~0u, ya = OFF_T + (8 + lane) * 64 + (((w & 1) ^ (lane >> 1)) & 3) * 16 + (w & 2) * 2048; \
          const uint4 a = lds128(xa + 4096 + w * 1024), b = lds128(xa + (w ^ 2) * 1024), d = lds128(xa + 4608 + w * 1024), e = lds128(xa + 512 + (w ^ 2) * 1024); \
          stsm4t(ya, hadd2u(a.x, b.x) & mk, hadd2u(a.y, b.y) & mk, hadd2u(a.z, b.z) & mk, hadd2u(a.w, b.w) & mk); \
          stsm4t(ya + 2048, hadd2u(d.x, e.x) & mk, hadd2u(d.y, e.y) & mk, hadd2u(d.z, e.z) & mk, hadd2u(d.w, e.w) & mk); \
        } \
        fence_async();
    } else if (role == 17) {
      if (smem_u32(smem) != SB) __trap();
      bar_sync(10, 576);
      if (lane == 0) {
        fence_async();
        while ((int)(clock() - t0) < X_NS - c * 4) {}
        asm volatile("cp.async.bulk.global.shared::cta.bulk_group [%0], [%1], 10240;" :: "l"(&p.s->X[c * DM * 2 + 512]), "r"(OFF_G) : "memory");
        asm volatile("cp.async.bulk.commit_group;" ::: "memory");
        asm volatile("cp.async.bulk.wait_group 0;" ::: "memory");
      }
      if (lane == 0) mbar_arrive(MB_GF);
      bar_arrive(11, 96);
      if (five) { FINISH0 bar_arrive(13, 192); }
    } else if (role == 18) {
      sts32(MISC_EPOCH, 0);
      sts32(MISC_T0, t0 - c * 4);
      bar_arrive(5, 608);
      uint4* q = lane < 2 ? &p.s->R[c * 2 + lane] : lane < 11 ? &p.s->HS[c * 9 + lane - 2] : lane == 11 ? &p.s->HS[1152 + (c & 7)] : (uint4*)&p.s->FLAG[c * 8];
      if (lane < (c < 8 ? 12 : 11)) str128(q, ~0u, ~0u, ~0u, ~0u);
      const uint32_t ep = __shfl_sync(0xffffffffu, ldr32(q), 31) + 1u;
      sts32(MISC_EPOCH, ep | 0x80000000u);
      TSX(21);
      if (lane == 31) str32(q, ep);
      bar_sync(11, 96);
      TSX(14);
      mbar_wait(MB_KF + (lane & 3) * 8);
      __syncwarp();
      { const uint2 e = lds64(MISC_EM); if (lane < 2) str128(&p.s->SC[c * 2 + lane], e.x, __byte_perm(e.y, ep, 0x6540), 0, 0); }
      TSX(17);
      while ((int)(clock() - t0) < X_SCT) __nanosleep(100);
      TSX(18);
      {
        uint2 v[4];
#pragma unroll 1
        for (int it = 0; it < SPIN_MAX; it++) {
          uint32_t bad = 0;
#pragma unroll
          for (int q = 0; q < 4; q++) v[q] = ldr64(&p.s->SC[lane * 2 + q * 64]);
#pragma unroll
          for (int q = 0; q < 4; q++) bad |= (v[q].y >> 8) ^ (ep & 0xFFFFFFu);
          if (!__any_sync(0xffffffffu, bad)) break;
        }
        TSX(25);
#pragma unroll
        for (int q = 0; q < 4; q++) {
          const uint32_t sa = (lane >> 4) * YT_PITCH + (lane & 15) * 2;
          sts16(sc_addr(2 * q) + sa, v[q].x); sts16(sc_addr(8 + 2 * q) + sa, v[q].x >> 16);
          if (lane & 1) asm volatile("st.shared.u8 [%0], %1;" :: "r"(sc_addr(16) + q * 16 + (lane >> 1)), "r"(v[q].y) : "memory");
        }
      }
      __syncwarp();
      if (lane == 0) mbar_arrive(MB_SC);
      TSX(27);
    } else {
      uint32_t w[9];
      const uint32_t dk = ldnc16(p.dskip + ((lane & 4) ? 512 + (c >> 1) : (lane & 2) * 128 + 2 * c + (lane & 1)));
      float s = 0.f;
#pragma unroll
      for (int i = 0; i < 9; i++) w[i] = ldnc32(p.w_r + lane + 32 * i);
      sts16(OFF_WR + 1152 + lane * 2, dk);
      bar_arrive(5, 608);
#pragma unroll
      for (int i = 0; i < 9; i++) { sts32(OFF_WR + lane * 4 + i * 128, w[i]); s += bf_lo(w[i]) + bf_hi(w[i]); }
      sts32(MISC_SW, __float_as_uint(warp_sum(s)));
      TSX(23);
      bar_sync(10, 576);
      if (lane == 0) {
        const uint32_t tp = clock();
        TSX(1);
        while ((int)(clock() - tp) < X_DELTA || (int)(clock() - t0) < X_ABS - c * 4) {}
        TSX(24);
        load_tile(&tm.m[6], 0, c);
        TSX(15);
        while ((int)(clock() - t0) < X_ABS + X_DSTEP - c * 4) {}
      }
      bar_sync(11, 96);
      if (lane == 0) {
        load_tile(&tm.m[6], 1, 128 + c);
      }
      if (five) {
        mbar_wait(MB_KF);
#pragma unroll 1
        for (int it = 0; it < SPIN_MAX; it++) {
          if (lane == 0) load_tile(&tm.m[8], 2, 512 + (c >> 1));
          mbar_wait(MB_UL + 32, it & 1);
          uint32_t m = 1;
#pragma unroll
          for (int q = 0; q < 4; q++) { uint32_t r0, r1, r2, r3; ldsm4(OFF_W + 512 + lane * 64 + (lane & 6) * 8 + q * 2048, r0, r1, r2, r3); m &= r0 & r1 & r2 & r3; }
          if (__all_sync(0xffffffffu, m || (lane & 3))) break;
        }
        bar_arrive(7, 288);
        FINISH0
        bar_arrive(13, 192);
      }
      bar_sync(0, 544);
      if (lane == 0) mbar_arrive(MB_H);
    }
    return;
  }
  const int wt = tid & 127, g = lane >> 2, t = lane & 3;
  const uint32_t wb = OFF_W + wg * W_BYTES;
  asm volatile("cp.async.commit_group;" ::: "memory");
  const ConvC cv = conv_consts(warp, lane);
  zero_pads(wb, wt);
  load_params<FAR>(p, 254 + 2 * c + wg, wt, wb + W_KT, wg == 2 || (wg == 3 && !five));
  asm volatile("cp.async.commit_group;" ::: "memory");
  asm volatile("setmaxnreg.inc.sync.aligned.u32 112;");
  {
    uint4 kw;
    uint4* kx = &p.s->KX[(c >> 1) * 128 + wt];
    bool two = wg == 3;
    uint32_t ep;
    int em = 0;
    uint32_t slot = wg + (two && !five);
    const uint32_t ra0 = wb + W_KT + (slot & 4) * 512 + wt * 2, ra6 = wb + W_KT + 1536 + (slot & 4) * 512 + (((slot & 4) ? c >> 1 : 2 * c + (wg & 1)) & 7) * 2;
    const uint32_t tr_addr = pin(tr_base(lane) + warp * 32), lca = pin(MISC_LN1 + (lane & 1) * 16);
    uint4* dst;
    { const unsigned long long a = (unsigned long long)&p.s->X[c * DM * 2 + warp * 32 + (8 * ((lane >> 1) & 1) + (lane >> 2)) * 2 + (lane & 1)];
      dst = (uint4*)(((unsigned long long)pin(a >> 32) << 32) | pin((uint32_t)a)); }
    const BuildC bc = build_consts(wt);
    uint32_t raw[7];
    if (wg != 2) {
      asm volatile("cp.async.wait_group 1;" ::: "memory");
      bar_sync(1 + wg, 128);
#pragma unroll
      for (int i = 0; i < 7; i++) raw[i] = lds16(i < 6 ? ra0 + i * 256 : ra6);
    }
    int phase = wg == 2 ? 3 : 2;
#pragma unroll 1
    for (;;) {
      if (phase != 3) {
        KgState ks;
        TS(22);
        kgen_tables_n(raw, wb, wt, ks);
        TS(20);
        bar_sync(1 + wg, 128);
        em = kgen_tables_m(wb, wt, ks);
        fence_async();
      }
      if (phase & 2) {
        if (phase == 3) {
        asm volatile("cp.async.wait_group 1;" ::: "memory");
        TS(21);
        float d[3][4], r;
        uint4 a[9];
#pragma unroll
        for (int k = 0; k < 9; k++) a[k] = lds128(xrow + k * 128);
#pragma unroll
        for (int i = 0; i < 4; i++) d[0][i] = d[1][i] = d[2][i] = 0.f;
#pragma unroll
        for (int k = 0; k < 9; k++) { mma_bf16(d[(2 * k) % 3], a[k].x, ones, a[k].y, ones, a[k].x, a[k].y); mma_bf16(d[(2 * k + 1) % 3], a[k].z, ones, a[k].w, ones, a[k].z, a[k].w); }
#pragma unroll
        for (int i = 0; i < 4; i++) d[0][i] += d[1][i] + d[2][i];
        const LnC lc = ln_consts(d[0][2] + d[0][3], __shfl_sync(0xffffffffu, d[0][0], 9 * t) + __shfl_sync(0xffffffffu, d[0][1], 9 * t + 4), r);
        if (lane < 12) sts16(MISC_LN1 + g * 32 + (warp & 3) * 8 + t * 2, lane < 4 ? lc.m2 : lane < 8 ? lc.rh2 : lc.rl2);
        }
        asm volatile("cp.async.wait_group 0;" ::: "memory");
        TS(23);
        bar_sync(5, 608);
        uint32_t x[3][4];
        ldsm4t(tr_addr, x[0][0], x[0][1], x[0][2], x[0][3]);
        uint4 m = lds128(lca);
        const uint4 rl = lds128(lca + 64), rh = lds128(lca + 32);
        ldsm4t(tr_addr + 512, x[1][0], x[1][1], x[1][2], x[1][3]);
        if (wg == 3) ldsm4t(tr_addr + 640, x[2][0], x[2][1], x[2][2], x[2][3]);
#pragma unroll
        for (int q = 0; q < 3; q++) {
          if (q < 2 || wg == 3) {
            const uint32_t r0 = ln_apply(x[q][0], m.x, rh.x, rl.x), r1 = ln_apply(x[q][1], m.y, rh.y, rl.y), r2 = ln_apply(x[q][2], m.z, rh.z, rl.z), r3 = ln_apply(x[q][3], m.w, rh.w, rl.w);
            const uint32_t w0 = (pack_h(bf_lo(r0), bf_hi(r0)) & 0xFFFEFFFEu) | 1u, w1 = pack_h(bf_lo(r1), bf_hi(r1)), w2 = pack_h(bf_lo(r2), bf_hi(r2)), w3 = pack_h(bf_lo(r3), bf_hi(r3));
            if (q == 0) str128(dst, w0, w1, w2, w3);
            else sts128(OFF_G + warp * 512 + (8 * (t >> 1) + g) * 32 + (t & 1) * 16 + (q == 2 ? 2048 : 0), w0, w1, w2, w3);
          }
          if (q == 0) {
            const uint32_t z = clock() & p.off[7];
            m.x ^= z; m.y ^= z; m.z ^= z; m.w ^= z;
          }
          if (q == 0) TS(30);
          if (q == 0 && wg >= 2) {
#pragma unroll
            for (int i = 0; i < 7; i++) raw[i] = lds16(wb + W_KT + i * 256 + (i < 6 ? wt : (2 * c + (wg & 1)) & 7) * 2);
          }
        }
        bar_arrive(10, 576);
        TS(1);
      } else bar_sync(1 + wg, 128);
      phase &= 1;
      if (phase) { phase = 0; continue; }
      TS(14);
      float acc[20];
      const uint32_t alo = (wb >> 4) | (8u << 16);
      uint4 k4 = lds128(wb + W_MISC + 16);
      uint32_t dk = lds16(OFF_WR + 1152 + slot * 2);
      wg_fence();
      wgmma40_ss_init(acc, alo, alo + 1024, 2048 >> 4);
#pragma unroll
      for (int k = 1; k < 8; k++) wgmma40_ss(acc, alo + k * 16, alo + 1024 + k * 16, 2048 >> 4);
      wg_commit();
      { const uint32_t z = clock() & p.off[7]; dk ^= z; k4.x ^= z; k4.z ^= z; }
      const float k2048 = (float)(int)((k4.x + k4.y) + (k4.z + k4.w)) * (1.f / 262144.f);
      const int ef = max(em, min((int)((dk >> 7) & 255u) - 7, 238));
      asm volatile("st.shared.u8 [%0], %1;" :: "r"(MISC_EM + slot), "r"(ef + 9) : "memory");
      const float un = __uint_as_float((uint32_t)max(114 + em - ef, 0) << 23), d0 = wt ? 0.f : bf_lo(dk) * __uint_as_float((uint32_t)(245 - ef) << 23);
      wg_wait<0>();
      kw.x = pack_h(fmaf(acc[0] - acc[3], un, d0), (acc[4] - acc[7]) * un);
      kw.y = pack_h((acc[8] - acc[11]) * un, (acc[12] - acc[15]) * un);
      kw.z = pack_h((acc[16] - acc[19]) * un, k2048 * un);
      TS(24);
      ep = 0;
      if (two) SPIN_WHILE(ep == 0, ep = lds32(MISC_EPOCH));
      if (five || !two) break;
      str128(kx, kw.x, kw.y, kw.z, ep);
      two = false;
      slot = 3;
      bar_sync(1 + wg, 128);
    }
    if (lane == 0) mbar_arrive(MB_KF + wg * 8);
    if (two) { mbar_wait(MB_KF); zero_pads(OFF_W + ALT, wt); }
    uint32_t tb = wb;
#pragma unroll 1
    for (;;) {
      kgen_build(tb, bc, wg, wt, kw.x, kw.y, kw.z);
      TS(15);
      if (!two) break;
      two = false;
      kw.w = 0;
      SPIN_WHILE(kw.w != ep, kw = ldr128(kx));
      tb = OFF_W + ALT;
    }
    fence_async();
    TS(31);
    if (tb != wb) bar_arrive(7, 288);
    bar_sync(1 + wg, 128);
  }
  uint32_t tpub;
  ConvPre pre;
  conv_pre(pre, (wb ^ p.off[7]) + (cv.ca & 0xFFFFu), (wb ^ p.off[7]) + cv.qa, 3, true, warp & 2);
#pragma unroll 1
  for (int item = 0;; item++) {
    TS(2);
    conv_item(item ? OFF_W + ALT : wb, item ? OFF_W : OFF_T + (wg >> 1) * TILE, item ? 1 : 13 + (wg >> 1), item ? 128 : five && wg == 1 ? 192 : 256, pre, cv, p.off[7],
              &tm.m[item ? 9 : 7], item ? 512 + (c >> 1) : (wg >> 1) * 128 + c, warp, lane, five && wg >= X_GW, five && !wg && !item);
    tpub = clock() - (item ? X_YD : wg >= 2 ? X_YD2 : 0);
    if (wg || !five || item) break;
    TS(27);
  }
  TS(4);

  const int ln = lane ^ p.off[7], td = warp * 32 + ln, gg = ln >> 2, tt = ln & 3;
  const int tok = c * 16 + warp;
  const int fu = warp / 3, fk = warp - fu * 3;
  uint32_t wa[12][4];
  uint4 ha[3];
  const uint4* hsrc = &p.s->HS[td + (td / 24) * 48];
  {
    uint32_t hw[9], wr[9];
    const uint32_t row = keep(OFF_YT + warp * YT_PITCH + (warp >> 3) * 64 + ln * 16);
    const uint32_t wabase = keep(((ln & 8) ? OFF_W + (fk + 1) * W_BYTES : OFF_G + fk * 192 * pitch) + ((ln >> 4) * 8 + (ln & 7)) * pitch
                                 + (five ? ((fu ^ (ln >> 1)) & 3) : min(fu, 4)) * 16);
    float sw;
    {
      const bool three = wg == 1;
      const int ch = 8 * (tt >> 1) + gg;
      const uint32_t tr_addr = tr_base(ln);
      const uint4* ysrc = &p.s->X[c * DM * 2 + ch * 2 + (tt & 1)];
      uint32_t x[3][4], s[3];
      uint4 v[3];
#define TL(q) ((q) < 2 ? 2 * warp + (q) : 28 + warp)
      if (wg >= 2) { const uint32_t ts = lds32(MISC_T0); while ((int)(clock() - ts) < X_XS) {} }
      while ((int)(clock() - tpub) < X_YD) {}
      TS(5);
      v[0] = ldr128(ysrc + TL(0) * 32); v[1] = ldr128(ysrc + TL(1) * 32); v[2] = make_uint4(three, 0, 0, 0);
      mbar_wait(MB_REL);
#pragma unroll
      for (int i = 0; i < 6; i++) if (i < 4 || three) wr[i] = (gg & 2) ? ones : lds32(OFF_WR + TL(i >> 1) * 32 + (i & 1) * 16 + tt * 4);
      const uint32_t ha = keep(OFF_YT + (ln & 7) * YT_PITCH + (ln >> 4) * (8 * YT_PITCH + 64) + (ln & 8) * 2);
      const uint32_t pa = keep(OFF_PART + warp * 4 + ((gg & 2) * 8 + (gg & 4) * 2 + 2 * tt + (gg & 1)) * 80), pb = keep(OFF_PART + 2560 + warp * 4 + gg * 80);
      float dl[4] = {0.f, 0.f, 0.f, 0.f}, dh[4] = {0.f, 0.f, 0.f, 0.f};
      sw = __uint_as_float(lds32(MISC_SW));
#pragma unroll
      for (int q = 0; q < 3; q++) {
        if (q < 2 || three) {
          ldsm4t(tr_addr + TL(q) * 32, x[q][0], x[q][1], x[q][2], x[q][3]);
        }
      }
      asm volatile("cp.async.bulk.wait_group.read 0;" ::: "memory");
      mbar_wait(MB_SC);
#pragma unroll
      for (int q = 0; q < 3; q++) {
        asm volatile("ld.shared.u8 %0, [%1];" : "=r"(s[q]) : "r"((q < 2 ? sc_addr(warp) + q * 16 : sc_addr(16) + (warp & 3) * 16) + ch) : "memory");
        s[q] = keep(s[q] * 0x800080u);
      }
#define FIN(q) stsm4t(tr_addr + TL(q) * 32, bf_fma2(h2bf(v[q].x), s[q], x[q][0]), bf_fma2(h2bf(v[q].y), s[q], x[q][1]), bf_fma2(h2bf(v[q].z), s[q], x[q][2]), bf_fma2(h2bf(v[q].w), s[q], x[q][3]));
      SPIN_WHILE((v[0].x | v[1].x) & 1u, _Pragma("unroll") for (int q = 0; q < 3; q++) if (v[q].x & 1u) v[q] = ldr128(ysrc + TL(q) * 32));
      if (v[2].x & 1u) v[2] = ldr128(ysrc + TL(2) * 32);
#define STAT(q) { uint32_t r0, r1, r2, r3; ldsm4(ha + TL(q) * 32, r0, r1, r2, r3); \
        mma_bf16(dl, r0, wr[2 * q], r1, wr[2 * q + 1], r0, r1); mma_bf16(dh, r2, wr[2 * q], r3, wr[2 * q + 1], r2, r3); }
      FIN(0) FIN(1)
      __syncwarp();
      STAT(0) STAT(1)
      if (three) {
#pragma unroll 1
        for (int it = 0; it < SPIN_MAX; it++) {
          FIN(2)
          if (!__any_sync(0xffffffffu, v[2].x & 1u)) break;
          if (v[2].x & 1u) v[2] = ldr128(ysrc + TL(2) * 32);
        }
        __syncwarp();
        STAT(2)
      }
      if (gg & 1) { dl[0] = dl[1]; dl[2] = dl[3]; dh[0] = dh[1]; dh[2] = dh[3]; }
      sts32(pa, __float_as_uint((gg & 4) ? dh[2] : dl[2]));
      if (tt == (gg >> 1)) { sts32(pb, __float_as_uint(dl[0])); sts32(pb + 640, __float_as_uint(dh[0])); }
#undef STAT
#undef FIN
#undef TL
    }
    uint32_t ra = keep(OFF_PART + (ln & 15) * 80 + (ln & 16) * 2);
    uint16_t* rp = (uint16_t*)p.s->R + c * 16 + (ln & 15);
    const uint2* rsrc = (const uint2*)p.s->R + td;
    asm volatile("" : "+l"(rp), "+l"(rsrc), "+l"(hsrc));
    uint2 rv = make_uint2(0u, 0u);
    TS(28);
    if (warp != X_PW) bar_sync(0, 544);
    else {
      float z[3], rd;
      asm volatile("bar.sync 0, 544;" : "+r"(ra) :: "memory");
#pragma unroll
      for (int k = 2; k >= 0; k--) {
        const uint4 a = lds128(ra + k * 1280), b = lds128(ra + k * 1280 + 16);
        z[k] = ((__uint_as_float(a.x) + __uint_as_float(a.y)) + (__uint_as_float(a.z) + __uint_as_float(a.w))) + ((__uint_as_float(b.x) + __uint_as_float(b.y)) + (__uint_as_float(b.z) + __uint_as_float(b.w)));
      }
#pragma unroll
      for (int k = 2; k >= 0; k--) z[k] += __shfl_xor_sync(0xffffffffu, z[k], 16);
      const LnC l = ln_consts(z[1], z[2], rd);
      const uint32_t b = pack_bf(0.f, fmaf(-bf_lo(l.m2), sw, z[0]) * rd);
      const uint32_t k16 = max(min((b ^ (((int)b >> 31) | 0x80000000u)) >> 16, 0xFFFEu), 1u);
      if (ln < 16) str16(rp, k16);
      sts64(OFF_RK + (ln & 15) * 8, __byte_perm(l.m2, l.rh2, 0x5410), __byte_perm(l.rl2, k16, 0x5410));
      sts128(MISC_CNT + ln * 16, 0, 0, 0, 0);
    }
    mbar_wait(MB_GU);
#define LD_HW { const uint4 a = lds128(row), b = lds128(row + 512); hw[8] = lds32(row + 1024 - ln * 12); \
      hw[0] = a.x; hw[1] = a.y; hw[2] = a.z; hw[3] = a.w; hw[4] = b.x; hw[5] = b.y; hw[6] = b.z; hw[7] = b.w; }
    LD_HW
    const uint32_t tr0 = clock();
    bar_sync(5, 512);
    TS(7);
    const uint2 lk = lds64(OFF_RK + warp * 8);
    LnC l2;
    l2.m2 = __byte_perm(lk.x, 0, 0x1010); l2.rh2 = __byte_perm(lk.x, 0, 0x3232); l2.rl2 = __byte_perm(lk.y, 0, 0x1010);
    const uint32_t key = (lk.y & 0xFFFF0000u) | (2047 - tok);
    uint32_t loc = ln < 16 ? (lds32(OFF_RK + 4 + ln * 8) & 0xFFFF0000u) | (2047 - c * 16 - ln) : 0u;
    int rank = __popc(__ballot_sync(0xffffffffu, loc > key));
#pragma unroll
    for (int i = 0; i < 9; i++) { wr[i] = keep(ln_apply(hw[i], l2.m2, l2.rh2, l2.rl2)); hw[i] = bf_add2(hw[i], wr[i]); }
#define OUT_ROW { uint32_t* o = p.out + tok * 288 + ln * 4; \
      *(uint4*)o = make_uint4(hw[0], hw[1], hw[2], hw[3]); *(uint4*)(o + 128) = make_uint4(hw[4], hw[5], hw[6], hw[7]); o[256 - ln * 3] = hw[8]; }
    uint4* hs = p.s->HS + ln;
    asm volatile("" : "+l"(hs));
#pragma unroll 1
    for (int base = 0; base < 8; base += 2) {
      uint32_t T[2];
#pragma unroll
      for (int j = 0; j < 2; j++) {
        const uint32_t mx = __reduce_max_sync(0xffffffffu, loc);
        if (loc == mx) loc = 0;
        T[j] = (td >> 2) < c ? (mx & 0xFFFF0000u) - 1u : mx | 0xFFFFu;
      }
      const uint32_t sh = keep(rank == base ? 0x4410u : rank == base + 1 ? 0x4432u : 0x4445u), ca = keep(MISC_CNT + base * 64 + ln * 4);
      TS(29);
      if (base == 0) {
        while ((int)(clock() - tr0) < X_RD) {}
        if ((td >> 2) != c) rv = ldr64(rsrc);
        if (rank >= X_OR) OUT_ROW
        if (warp < (five ? 12 : 15)) {
#pragma unroll
          for (int k = 0; k < X_WS; k++) ldsm4t(wabase + k * 16 * pitch, wa[k][0], wa[k][1], wa[k][2], wa[k][3]);
        }
      }
      uint32_t cnt;
#pragma unroll 1
      for (int it = 0; it < SPIN_MAX; it++) {
        const uint32_t xs = rv.x << 16, ys = rv.y << 16;
        const bool bad = max(max(rv.x, xs), max(rv.y, ys)) >= 0xFFFF0000u;
        uint32_t cn2 = 0;
        cnt = bad ? 256u : 0u;
#pragma unroll
        for (int j = 0; j < 2; j++)
          asm("{ .reg .pred a, b, c, d; setp.gt.u32 a, %2, %6; setp.gt.u32 b, %3, %6; setp.gt.u32 c, %4, %6; setp.gt.u32 d, %5, %6; "
              "@a add.u32 %1, %1, %7; @b add.u32 %1, %1, %7; @c add.u32 %0, %0, %7; @d add.u32 %0, %0, %7; }"
              : "+r"(cnt), "+r"(cn2) : "r"(rv.x), "r"(rv.y), "r"(xs), "r"(ys), "r"(T[j]), "r"(1u << (16 * j)));
        cnt = __reduce_add_sync(0xffffffffu, cnt + cn2);
        asm volatile("{ .reg .pred q; setp.eq.u32 q, %2, 0; @q red.shared.add.u32 [%0], %1; }" :: "r"(ca), "r"(cnt), "r"(cnt & 0x3F00u) : "memory");
        if (!(cnt & 0x3F00u)) break;
        if (bad) rv = ldr64(rsrc);
      }
      TS(16);
      bar_sync(0, 512);
      cnt = lds32(ca);
      if (base == 0) tpub = clock();
      const int gr = rank + __byte_perm(cnt, 0x800u, sh);
      if (gr < 8) {
        uint4* ks = hs + 1152 + gr;
        hs = (uint4*)((char*)hs + gr * 1152);
        asm volatile("{ .reg .b128 t, u; .reg .b64 a, b, c, d; mov.b64 a, {%1,%2}; mov.b64 b, {%3,%4}; mov.b64 c, {%5,%6}; mov.b64 d, {%7,%8}; mov.b128 t, {a, b}; mov.b128 u, {c, d}; "
                     "st.relaxed.gpu.global.b128 [%0], t; st.relaxed.gpu.global.b128 [%0 + 512], u; }"
                     :: "l"(hs), "r"(wr[0]), "r"(wr[1]), "r"(wr[2]), "r"(wr[3]), "r"(wr[4]), "r"(wr[5]), "r"(wr[6]), "r"(wr[7]) : "memory");
        str32((uint32_t*)(hs + 64) - ln * 3, wr[8]);
        LD_HW
        str128(hs + 576, hw[0], hw[1], hw[2], hw[3]); str128(hs + 608, hw[4], hw[5], hw[6], hw[7]); str32((uint32_t*)(hs + 640) - ln * 3, hw[8]);
        if (ln == 0) str32(ks, key);
        rank = 16;
      }
      if (__all_sync(0xffffffffu, (int)(cnt >> 16) + base + 2 >= 8)) break;
    }
    TS(8);
    if (warp < (five ? 12 : 15)) {
#pragma unroll
      for (int k = X_WS; k < 12; k++) ldsm4t(wabase + k * 16 * pitch, wa[k][0], wa[k][1], wa[k][2], wa[k][3]);
    }
    if (warp < 6) while ((int)(clock() - tpub) < X_HD) {}
    TS(19);
    if (warp < 6) { ha[0] = ldr128(hsrc); ha[1] = ldr128(hsrc + 24); ha[2] = ldr128(hsrc + 48); }
    if (rank < X_OR) OUT_ROW
  }
  uint32_t wd[10][4];
  const uint32_t xb = keep(OFF_XS + (ln & 7) * 1168 + (fk * 24 + (ln >> 3)) * 16);
  if (warp >= 7) {
    const uint32_t db = down_box(warp - 7, five) + (ln & 7) * 128;
    mbar_wait(MB_D);
#pragma unroll
    for (int j = 0; j < 4; j++) {
      const uint32_t a = db + (ln >> 4) * 1024 + (((2 * j + ((ln >> 3) & 1)) ^ (ln & 7)) << 4);
      ldsm4t(a, wd[j][0], wd[j][1], wd[j][2], wd[j][3]);
      ldsm4t(a + 2048, wd[4 + j][0], wd[4 + j][1], wd[4 + j][2], wd[4 + j][3]);
    }
#pragma unroll
    for (int j = 0; j < 2; j++) ldsm4t(db + 4096 + (((4 * j + (ln >> 3)) ^ (ln & 7)) << 4), wd[8 + j][0], wd[8 + j][1], wd[8 + j][2], wd[8 + j][3]);
  } else if (warp < 6) {
    const uint32_t xs = keep(OFF_XS + (td + (td / 24) * 49) * 16);
#pragma unroll 1
    for (int it = 0; it < SPIN_MAX; it++) {
      const bool bad = max(max(max(ha[0].x, ha[1].x), max(ha[2].x, ha[2].y)), max(ha[2].z, ha[2].w)) == ~0u;
#pragma unroll
      for (int q = 0; q < 3; q++) sts128(xs + q * 384, ha[q].x, ha[q].y, ha[q].z, ha[q].w);
      if (!__any_sync(0xffffffffu, bad)) break;
      if (bad) { ha[0] = ldr128(hsrc); ha[1] = ldr128(hsrc + 24); ha[2] = ldr128(hsrc + 48); }
    }
  }
  TS(9);

  bar_sync(0, 512);
  if (warp < (five ? 12 : 15)) {
    float d0[4] = {0.f, 0.f, 0.f, 0.f}, d1[4] = {0.f, 0.f, 0.f, 0.f};
#pragma unroll
    for (int k = 0; k < 12; k += 2) {
      uint32_t b0, b1, b2, b3;
      ldsm4(xb + k * 32, b0, b1, b2, b3);
      mma_bf16(d0, wa[k][0], wa[k][1], wa[k][2], wa[k][3], b0, b1);
      mma_bf16(d1, wa[k + 1][0], wa[k + 1][1], wa[k + 1][2], wa[k + 1][3], b2, b3);
    }
    sts128(OFF_RED + td * 16, __float_as_uint(d0[0] + d1[0]), __float_as_uint(d0[1] + d1[1]), __float_as_uint(d0[2] + d1[2]), __float_as_uint(d0[3] + d1[3]));
  }
  TS(26);
  if (warp < 5) {
    const uint32_t rb = OFF_RED + warp * 1536 + ln * 16;
    bar_sync(9, 512);
    const uint4 pa = lds128(rb), pb = lds128(rb + 512), pc = lds128(rb + 1024);
    const float ga = bfr(__uint_as_float(pa.x) + __uint_as_float(pb.x) + __uint_as_float(pc.x));
    const float gb = bfr(__uint_as_float(pa.y) + __uint_as_float(pb.y) + __uint_as_float(pc.y));
    const uint32_t uu = pack_bf(__uint_as_float(pa.z) + __uint_as_float(pb.z) + __uint_as_float(pc.z), __uint_as_float(pa.w) + __uint_as_float(pb.w) + __uint_as_float(pc.w));
    float ra, rb2;
    asm("rcp.approx.ftz.f32 %0, %1;" : "=f"(ra) : "f"(1.f + ex2(ga * -1.4426950408889634f)));
    asm("rcp.approx.ftz.f32 %0, %1;" : "=f"(rb2) : "f"(1.f + ex2(gb * -1.4426950408889634f)));
    const uint32_t act = bf_mul2(pack_bf(ga * ra, gb * rb2), uu);
    sts32(OFF_ACT + td * 4, act);
  } else bar_arrive(9, 512);
  uint4* dst = &p.s->X[c * DM * 2 + (warp - 7) * 64 + tt * 8 + gg];
  asm volatile("" : "+l"(dst));
  bar_sync(8, 512);
  tpub = clock();
  if (warp >= 7) {
    uint32_t b0, b1, b2, b3, b4;
    ldsm4t(OFF_ACT + ln * 16, b0, b1, b2, b3);
    asm volatile("ldmatrix.sync.aligned.m8n8.x1.trans.shared.b16 {%0}, [%1];" : "=r"(b4) : "r"(OFF_ACT + 512 + ln * 16) : "memory");
    float y[4][4];
#pragma unroll
    for (int j = 0; j < 4; j++) {
      y[j][0] = y[j][1] = y[j][2] = y[j][3] = 0.f;
      mma_bf16(y[j], wd[j][0], wd[j][1], wd[j][2], wd[j][3], b0, b1);
    }
#pragma unroll
    for (int j = 0; j < 4; j++) mma_bf16(y[j], wd[4 + j][0], wd[4 + j][1], wd[4 + j][2], wd[4 + j][3], b2, b3);
    if (!five) {
#pragma unroll
      for (int j = 0; j < 4; j++) mma_bf16_k8(y[j], wd[8 + (j >> 1)][2 * (j & 1)], wd[8 + (j >> 1)][2 * (j & 1) + 1], b4);
    }
    str128(dst, (pack_bf(y[0][0], y[0][1]) & ~1u) | 0x10000u, pack_bf(y[0][2], y[0][3]), pack_bf(y[1][0], y[1][1]), pack_bf(y[1][2], y[1][3]));
    str128(dst + 32, (pack_bf(y[2][0], y[2][1]) & ~1u) | 0x10000u, pack_bf(y[2][2], y[2][3]), pack_bf(y[3][0], y[3][1]), pack_bf(y[3][2], y[3][3]));
  }
  TS(10);

  if (c < 72) {
    const uint4* src = &p.s->X[(warp * 4 + tt) * (DM * 2) + c * 8 + gg];
    const int slot = (c & 3) * 2 + (ln >> 4), dw = (c >> 2) * 16 + (ln & 15);
    uint32_t hv = 0, kv = 0, res = 0, rs2 = 0;
    uint32_t* o = p.out;
    if (warp == 0) {
      hv = ~0u;
      SPIN_WHILE(max(hv, kv) == ~0u, hv = ldr32((const uint32_t*)p.s->HS + 2304 + slot * 288 + dw); kv = ldr32(&p.s->HS[1152 + slot]));
      const float r = bf_hi(kv ^ (((int)~kv >> 31) | 0x80000000u));
      float rs;
      asm("rcp.approx.ftz.f32 %0, %1;" : "=f"(rs) : "f"(1.f + ex2(r * -1.4426950408889634f)));
      rs2 = keep(pack_bf(rs, rs));
      res = lds32(OFF_XS + slot * 1168 + dw * 4);
      o += (2047 - (int)(kv & 2047u)) * 288 + dw;
      asm volatile("" : "+l"(o));
    }
    const uint32_t sel = (gg & 1) ? 0x3F800000u : 0x00003F80u;
    const uint32_t q0 = keep((gg >> 1) == 0 ? sel : 0u), q1 = keep((gg >> 1) == 1 ? sel : 0u), q2 = keep((gg >> 1) == 2 ? sel : 0u), q3 = keep((gg >> 1) == 3 ? sel : 0u);
    const uint32_t fa = keep(OFF_RED + warp * 8 + ((gg & 1) * 16 + (gg >> 1) * 4 + tt) * 144), fb = keep(OFF_RED + ln * 144);
    uint4 a0 = make_uint4(0, 0, 0, 0), a1 = a0;
    while ((int)(clock() - tpub) < X_PD) {}
    SPIN_WHILE(!(a0.x & a1.x & 0x10000u), if (!(a0.x & 0x10000u)) a0 = ldr128(src); if (!(a1.x & 0x10000u)) a1 = ldr128(src + 64 * DM * 2));
    float d[4] = {0.f, 0.f, 0.f, 0.f}, e[4] = {0.f, 0.f, 0.f, 0.f}, d2[4] = {0.f, 0.f, 0.f, 0.f}, e2[4] = {0.f, 0.f, 0.f, 0.f};
    mma_bf16(d, q0, q2, q1, q3, a0.x, a0.y); mma_bf16(e, q0, q2, q1, q3, a0.z, a0.w);
    mma_bf16(d2, q0, q2, q1, q3, a1.x, a1.y); mma_bf16(e2, q0, q2, q1, q3, a1.z, a1.w);
    sts64(fa, __float_as_uint(d[0] + e[2] + d2[0] + e2[2]), __float_as_uint(d[1] + e[3] + d2[1] + e2[3]));
    TS(11);
    if (warp == 0) {
      bar_sync(0, 512);
      float2 s[16];
#pragma unroll
      for (int i = 0; i < 16; i += 2) { const uint4 q = lds128(fb + i * 8); s[i] = make_float2(__uint_as_float(q.x), __uint_as_float(q.y)); s[i + 1] = make_float2(__uint_as_float(q.z), __uint_as_float(q.w)); }
#pragma unroll
      for (int k = 1; k < 16; k *= 2)
#pragma unroll
        for (int i = 0; i < 16; i += 2 * k) { s[i].x += s[i + k].x; s[i].y += s[i + k].y; }
      asm volatile("st.global.b32 [%0], %1;" :: "l"(o), "r"(bf_add2(hv, bf_add2(res, bf_mul2(pack_bf(s[0].x, s[0].y), rs2)))) : "memory");
    } else bar_arrive(0, 512);
  }
  TS(12);
  TS_DUMP();
}

typedef CUresult (*EncodeFn)(CUtensorMap*, CUtensorMapDataType, cuuint32_t, void*, const cuuint64_t*, const cuuint64_t*, const cuuint32_t*,
                             const cuuint32_t*, CUtensorMapInterleave, CUtensorMapSwizzle, CUtensorMapL2promotion, CUtensorMapFloatOOBfill);

}

extern "C" void kernel_launch(void* const* d_in, const int* in_sizes, int n_in, void* d_out, int out_size) {
  (void)in_sizes; (void)n_in; (void)out_size;
  static EncodeFn enc = nullptr;
  static Scratch* scratch = nullptr;
  if (!enc) {
    void* fn = nullptr;
    cudaDriverEntryPointQueryResult qr;
    cudaGetDriverEntryPoint("cuTensorMapEncodeTiled", &fn, cudaEnableDefault, &qr);
    enc = (EncodeFn)fn;
    cudaGetSymbolAddress((void**)&scratch, g_S);
    cudaFuncSetAttribute(fused_kernel<false>, cudaFuncAttributeMaxDynamicSharedMemorySize, SMEM_BYTES);
    cudaFuncSetAttribute(fused_kernel<true>, cudaFuncAttributeMaxDynamicSharedMemorySize, SMEM_BYTES);
  }
  TMaps tm;
  for (int i = 0; i < 6; i++) {
    const bool dn = i % 3 == 2;
    const cuuint32_t w = i < 3 ? 40 : 32;
    cuuint64_t gd[3] = {(cuuint64_t)(dn ? 64 : FF), (cuuint64_t)(dn ? FF : DM), 9};
    cuuint64_t gs[2] = {(cuuint64_t)(dn ? DM * 2 : FF * 2), 128};
    cuuint32_t bx[3] = {dn ? 64 : w, dn ? w : 96, i < 3 ? 2u : 3u};
    cuuint32_t es[3] = {1, 1, 1};
    enc(&tm.m[i], CU_TENSOR_MAP_DATA_TYPE_BFLOAT16, dn ? 3 : 2, d_in[11 + i % 3], gd, gs, bx, es, CU_TENSOR_MAP_INTERLEAVE_NONE,
        dn ? CU_TENSOR_MAP_SWIZZLE_128B : i < 3 ? CU_TENSOR_MAP_SWIZZLE_NONE : CU_TENSOR_MAP_SWIZZLE_64B,
        (CUtensorMapL2promotion)X_PROMO, CU_TENSOR_MAP_FLOAT_OOB_FILL_NONE);
  }
  for (int i = 6; i < 10; i++) {
    cuuint64_t gd[3] = {i < 8 ? 32u : 16u, i < 8 ? DM / 2u : DM, NCTA};
    cuuint64_t gs[2] = {i < 8 ? 64u : 32u, DM * 32};
    cuuint32_t bx[3] = {32, 1, (i & 1) ? 128u : 136u};
    cuuint32_t es[3] = {1, 1, 1};
    enc(&tm.m[i], CU_TENSOR_MAP_DATA_TYPE_FLOAT16, 3, scratch->X, gd, gs, bx, es, CU_TENSOR_MAP_INTERLEAVE_NONE, CU_TENSOR_MAP_SWIZZLE_64B,
        CU_TENSOR_MAP_L2_PROMOTION_NONE, CU_TENSOR_MAP_FLOAT_OOB_FILL_NONE);
  }
  Params p;
  p.x = (const unsigned char*)d_in[0];
  bool far = false;
  for (int i = 0; i < 7; i++) {
    p.far[i] = (const unsigned char*)d_in[1 + i];
    const long long d = (long long)((intptr_t)d_in[1 + i] - (intptr_t)d_in[0]);
    p.off[i] = (int)(d / 16);
    if ((long long)p.off[i] * 16 != d || p.off[i] > (1 << 30)) far = true;
  }
  p.dskip = (const uint16_t*)d_in[8];
  p.w_r = (const uint32_t*)d_in[10];
  for (int f = 0; f < 2; f++) {
    static const int kind[17] = {0, 0, 0, 0, 2, 2, 0, 0, 1, 1, 1, 1, 1, 1, 2, 2, 2};
    static const int idx[2][17] = {{2, 3, 4, 5, 6, 0, 0, 1, 0, 1, 2, 3, 4, 5, 2, 4, 8}, {2, 3, 4, 5, 0, -1, 0, 1, 0, 1, 2, 3, 4, 5, 3, -1, 6}};
    static const int blk[2][17] = {{-1, -1, -1, -1, 0, 1, 4, -1, -1, -1, 2, -1, 3, -1, 16, -1, -1}, {-1, -1, -1, -1, 1, -1, 4, -1, -1, -1, 2, -1, 3, -1, 16, -1, -1}};
    const int pitch = f ? 64 : 80;
    for (int u = 0; u < 17; u++) {
      const int s = idx[f][u];
      const uint32_t dst = kind[u] == 0 ? OFF_G + s * 96 * pitch : kind[u] == 2 ? down_box(s, f) : OFF_W + W_BYTES + (s >> 1) * W_BYTES + (s & 1) * 96 * pitch;
      const uint32_t mb = u >= 14 ? (u >= X_HU ? MB_H - OFF_MISC : 0) : blk[f][u] >= 0 ? MB_KF - OFF_MISC + blk[f][u] * 8 : 0;
      p.sched[f][u] = s < 0 ? 3u : kind[u] | s << 2 | mb << 6 | dst << 14;
    }
  }
  p.out = (uint32_t*)d_out;
  p.off[7] = 0;
  p.ts = nullptr;
  p.s = scratch;
  if (far) { fused_kernel<true><<<NCTA, NT, SMEM_BYTES, cudaStreamPerThread>>>(p, tm); return; }
  fused_kernel<false><<<NCTA, NT, SMEM_BYTES, cudaStreamPerThread>>>(p, tm);
}
```
